```python
import torch

def _softmax(x, axis=-1):
    return torch.softmax(x, dim=axis)
def _gelu(x):
    return torch.nn.functional.gelu(x, approximate="tanh")
def _silu(x):
    return torch.nn.functional.silu(x)
def _sigmoid(x):
    return torch.sigmoid(x)
def _layernorm(x, axis=-1, eps=1e-5):
    m = x.mean(dim=axis, keepdim=True)
    v = x.var(dim=axis, keepdim=True, unbiased=False)
    return (x - m) / torch.sqrt(v + eps)
def _scatter_add(tgt, idx, src, axis=0):
    return tgt.clone().index_add_(axis, idx, src)
def _segment_sum(src, seg, n):
    out = torch.zeros((n,) + src.shape[1:], dtype=src.dtype)
    return out.index_add_(0, seg, src)
def _pad(x, pw):
    flat = tuple(v for pair in reversed(pw) for v in pair)
    return torch.nn.functional.pad(x, flat)

kernel_name = 'standalone__window_attn_swin_v2__vision'

def setup_inputs():

    _w = (lambda a: (lambda t: t.to(torch.bfloat16) if t.is_floating_point() else t)(torch.as_tensor(a)))
    win = 7
    H = W = (512 // win) * win
    C = 192
    nh = 4
    shift = win // 2
    coords = torch.stack(torch.meshgrid(torch.arange(win), torch.arange(win), indexing="ij"), -1).reshape(-1, 2)
    rel = coords[:, None, :] - coords[None, :, :]
    rel_idx = ((rel[..., 0] + win - 1) * (2 * win - 1) + (rel[..., 1] + win - 1)).to(torch.int64)
    tab = torch.stack(torch.meshgrid(torch.arange(1 - win, win), torch.arange(1 - win, win), indexing="ij"), -1).reshape(-1, 2).to(float)
    tab = (lambda _x: torch.sign(torch.as_tensor(_x)))(tab) * (lambda _x: torch.log1p(torch.as_tensor(_x)))(torch.abs(tab))
    img = torch.zeros((H, W), dtype=torch.int64)
    cnt = 0
    for hs in (slice(0, H - win), slice(H - win, H - shift), slice(H - shift, H)):
        for ws in (slice(0, W - win), slice(W - win, W - shift), slice(W - shift, W)):
            img[hs, ws] = cnt; cnt += 1
    mw = img.reshape(H // win, win, W // win, win).permute(0, 2, 1, 3).reshape(-1, win * win)
    mask = (mw[:, :, None] != mw[:, None, :]).to(float) * (-100.0)
    return {
        "x": _w((lambda *s: torch.randn(*s, dtype=torch.bfloat16) * 0.05)(1, H, W, C)),
        "wqkv": _w((lambda *s: torch.randn(*s, dtype=torch.bfloat16) * 1.6)(C, 3 * C)),
        "wo": _w((lambda *s: torch.randn(*s, dtype=torch.bfloat16) * 0.05)(C, C)),
        "logit_scale": _w((lambda *s: torch.randn(*s, dtype=torch.bfloat16) * 1.6)(nh)),
        "cpb_w1": _w((lambda *s: torch.randn(*s, dtype=torch.bfloat16) * 1.6)(2, 4 * nh)),
        "cpb_w2": _w((lambda *s: torch.randn(*s, dtype=torch.bfloat16) * 1.6)(4 * nh, nh)),
        "rel_coords": _w(tab),
        "rel_idx": _w(rel_idx),
        "attn_mask": _w(mask),
    }

def reference(x, wqkv, wo, logit_scale, cpb_w1, cpb_w2, rel_coords, rel_idx, attn_mask):
    B, H, W, C = x.shape
    win = 7
    nh = 4
    hd = C // nh
    shift = win // 2
    ww = win * win
    nH, nW = H // win, W // win
    xs = torch.roll(x, (-shift, -shift), (1, 2))
    xw = (lambda x, *d: x.permute(*d))(xs.reshape(B, nH, win, nW, win, C), 0, 1, 3, 2, 4, 5).reshape(B * nH * nW, ww, C)
    qkv = (lambda x, *d: x.permute(*d))((xw @ wqkv).reshape(B * nH * nW, ww, 3, nh, hd), 2, 0, 3, 1, 4)
    q, k, v = qkv[0], qkv[1], qkv[2]
    qn = q * (torch.einsum("bhqd,bhqd->bhq", q, q)[..., None] + 1e-12) ** -0.5
    kn = k * (torch.einsum("bhkd,bhkd->bhk", k, k)[..., None] + 1e-12) ** -0.5
    logits = torch.einsum("bhqd,bhkd->bhqk", qn, kn)
    tau = torch.exp(torch.clip(logit_scale, -100.0, 4.6052))
    logits = logits * tau[None, :, None, None]
    hcpb = rel_coords @ cpb_w1
    hcpb = torch.where(hcpb > 0, hcpb, hcpb * 0)
    bias_tab = 16.0 * _sigmoid(hcpb @ cpb_w2)
    bias = (lambda x, *d: x.permute(*d))(bias_tab[rel_idx], 2, 0, 1)
    logits = logits.reshape(B, nH * nW, nh, ww, ww) + bias[None, None, :, :, :] + attn_mask[None, :, None, :, :]
    p = _softmax(logits.reshape(B * nH * nW, nh, ww, ww), axis=-1)
    o = (lambda x, *d: x.permute(*d))(torch.einsum("bhqk,bhkd->bhqd", p, v), 0, 2, 1, 3).reshape(B * nH * nW, ww, C) @ wo
    o = (lambda x, *d: x.permute(*d))(o.reshape(B, nH, nW, win, win, C), 0, 1, 3, 2, 4, 5).reshape(B, H, W, C)
    o = torch.roll(o, (shift, shift), (1, 2))
    return _layernorm(o, axis=-1)
```

```cpp
#include <cuda_runtime.h>
#include <cuda.h>
#include <cuda_bf16.h>
#include <stdint.h>
#include <type_traits>

namespace swin {

#define NPAIR 54
#define QFP32 0
#define PF_DIST 3
#define EXP 0
#define QSPLIT 3
#define SSPLIT 0
#define LATEMASK 0
#define CLUSTER 0
#define NOPF 0
#define NTAIL 216
#define PSTORE 1
#define PORDER 1
#define GORD 0
#define GMERGE 0
#define XSPLIT 1
#define EARLYW 1
#define NEARLY 4
#define REG_G 200
#define REG_A 144
#define REG_H 24
constexpr int IMG      = 511;
constexpr int NWS      = 73;
constexpr int NWINDOWS = NWS * NWS;
constexpr int TOK      = 49;
constexpr int NPIX     = IMG * IMG;
constexpr int NTHREADS = 512;

constexpr int W_ATOM = 6144;
constexpr int SM_WA = 0, SM_WB = 6 * W_ATOM, SM_WV = 12 * W_ATOM;
constexpr int GRP   = TOK * 16;
constexpr int XCH   = TOK * 128;
constexpr int SM_V  = 18 * W_ATOM, V_STRIDE = 10240, O_PITCH = 208;
constexpr int SM_QK = SM_V + 4 * V_STRIDE, QK_CHUNK = 4 * XCH;
constexpr int SM_MASK = SM_QK + 3 * QK_CHUNK;
constexpr int SM_TAB  = SM_V + 3 * V_STRIDE + 256;
constexpr int SM_DUMP = SM_MASK + 4816;
constexpr int SM_BAR  = SM_DUMP + 320;
constexpr int B_XFULL = 0, B_WRAW = 32, B_QKRAW = 64, B_QKFREE = 96, B_VFREE = 128, B_ODONE = 160,
              B_VRAW = 224, B_MFULL = 256, B_MCONS = 272, B_WFULL = 280, B_STORED = 288, B_PUBD = 304;
constexpr int SM_A_END = SM_BAR + 320;
static_assert(SM_QK % 1024 == 0 && TOK * O_PITCH + 64 - 16 <= V_STRIDE && (28 * O_PITCH + 64) % 128 == 0, "layout");
constexpr int SM_WO    = 0;
constexpr int SM_STAGE = 73728;
constexpr int STAGE_BYTES = 24576;
constexpr int SM_PBAR  = SM_A_END;
constexpr int SM_TOTAL = SM_PBAR + 152;
static_assert(SM_STAGE + 6 * STAGE_BYTES <= SM_BAR, "smem");
static_assert(SM_TOTAL <= 232448, "smem");
static_assert(SM_BAR % 8 == 0, "barrier alignment");

constexpr int SEG_B   = 3 * IMG;
constexpr int TILES_A = (NPIX - SEG_B + 63) / 64;
constexpr int TILES   = TILES_A + (SEG_B + 63) / 64;
constexpr uint32_t ROW_DONE = NWS * 2;

__device__ uint32_t g_cnt[NWS + 7];
__device__ uint32_t g_done;

#define TR(ev, idx)
constexpr float LOG2E = 1.4426950408889634f;

__device__ __forceinline__ uint32_t smem_u32(const void* p) {
    return (uint32_t)__cvta_generic_to_shared(p);
}
__device__ __forceinline__ uint64_t make_desc(uint32_t saddr, uint32_t lbo, uint32_t sbo, uint32_t swz = 0) {
    return (uint64_t)((saddr & 0x3FFFF) >> 4) | ((uint64_t)(lbo >> 4) << 16) | ((uint64_t)(sbo >> 4) << 32) |
           ((uint64_t)swz << 62);
}
__host__ __device__ constexpr uint64_t make_desc_c(uint32_t saddr, uint32_t lbo, uint32_t sbo, uint32_t swz) {
    return (uint64_t)(saddr >> 4) | ((uint64_t)(lbo >> 4) << 16) | ((uint64_t)(sbo >> 4) << 32) | ((uint64_t)swz << 62);
}
__device__ __forceinline__ void wgmma_fence()  { asm volatile("wgmma.fence.sync.aligned;\n" ::: "memory"); }
__device__ __forceinline__ void wgmma_commit() { asm volatile("wgmma.commit_group.sync.aligned;\n" ::: "memory"); }
template <int N> __device__ __forceinline__ void wgmma_wait() {
    asm volatile("wgmma.wait_group.sync.aligned %0;\n" :: "n"(N) : "memory");
}
__device__ __forceinline__ void fence_async_smem() { asm volatile("fence.proxy.async.shared::cta;\n" ::: "memory"); }
__device__ __forceinline__ void wg_bar(int id) { asm volatile("bar.sync %0, 128;\n" :: "r"(id) : "memory"); }

template <int N> __device__ __forceinline__ void reg_fence(float (&v)[N]) {
#pragma unroll
    for (int i = 0; i < N; i++) asm volatile("" : "+f"(v[i]) :: "memory");
}
template <int N> __device__ __forceinline__ void reg_fence(uint32_t (&v)[N]) {
#pragma unroll
    for (int i = 0; i < N; i++) asm volatile("" : "+r"(v[i]) :: "memory");
}
template <int N, int M> __device__ __forceinline__ void reg_fence(uint32_t (&v)[N][M]) {
#pragma unroll
    for (int i = 0; i < N; i++) reg_fence(v[i]);
}

__device__ __forceinline__ uint32_t pack_bf16(float lo, float hi) {
    uint32_t r;
    asm("cvt.rn.bf16x2.f32 %0, %1, %2;\n" : "=r"(r) : "f"(hi), "f"(lo));
    return r;
}
__device__ __forceinline__ float bf16lo(uint32_t v) { return __uint_as_float(v << 16); }
__device__ __forceinline__ float bf16hi(uint32_t v) { return __uint_as_float(v & 0xFFFF0000u); }
__device__ __forceinline__ uint32_t hadd2_bf16(uint32_t a, uint32_t b) {
    uint32_t r;
    asm("add.rn.bf16x2 %0, %1, %2;\n" : "=r"(r) : "r"(a), "r"(b));
    return r;
}
__device__ __forceinline__ uint32_t hmul2_bf16(uint32_t a, uint32_t b) {
    uint32_t r;
    asm("mul.rn.bf16x2 %0, %1, %2;\n" : "=r"(r) : "r"(a), "r"(b));
    return r;
}
__device__ __forceinline__ uint32_t hsub2_bf16(uint32_t a, uint32_t b) {
    uint32_t r;
    asm("sub.rn.bf16x2 %0, %1, %2;\n" : "=r"(r) : "r"(a), "r"(b));
    return r;
}
__device__ __forceinline__ uint32_t hfma2_bf16(uint32_t a, uint32_t b, uint32_t c) {
    uint32_t r;
    asm("fma.rn.bf16x2 %0, %1, %2, %3;\n" : "=r"(r) : "r"(a), "r"(b), "r"(c));
    return r;
}
__device__ __forceinline__ uint32_t hmax2_bf16(uint32_t a, uint32_t b) {
    uint32_t r;
    asm("max.bf16x2 %0, %1, %2;\n" : "=r"(r) : "r"(a), "r"(b));
    return r;
}
__device__ __forceinline__ uint32_t ex2_bf16x2(uint32_t a) {
    uint32_t r;
    asm("ex2.approx.ftz.bf16x2 %0, %1;\n" : "=r"(r) : "r"(a));
    return r;
}
__device__ __forceinline__ uint32_t ex2_bf16lo(uint32_t a) {
    uint32_t r;
    asm("{\n.reg .b16 l, h;\nmov.b32 {l, h}, %1;\nex2.approx.ftz.bf16 l, l;\ncvt.u32.u16 %0, l;\n}\n" : "=r"(r) : "r"(a));
    return r;
}
__device__ __forceinline__ uint32_t mbar_test(uint32_t bar, uint32_t parity) {
    uint32_t ok;
    asm volatile("{\n.reg .pred p;\nmbarrier.test_wait.parity.shared::cta.b64 p, [%1], %2;\nselp.u32 %0, 1, 0, p;\n}\n"
                 : "=r"(ok) : "r"(bar), "r"(parity) : "memory");
    return ok;
}
__device__ __forceinline__ uint32_t prmt(uint32_t a, uint32_t b, uint32_t sel) {
    uint32_t r;
    asm("prmt.b32 %0, %1, %2, %3;\n" : "=r"(r) : "r"(a), "r"(b), "r"(sel));
    return r;
}
__device__ __forceinline__ float round_bf16(float x) { return __bfloat162float(__float2bfloat16_rn(x)); }

__device__ __forceinline__ void mbar_init(uint32_t bar, uint32_t count) {
    asm volatile("mbarrier.init.shared::cta.b64 [%0], %1;\n" :: "r"(bar), "r"(count) : "memory");
}
__device__ __forceinline__ void mbar_wait(uint32_t bar, uint32_t parity) {
    asm volatile(
        "{\n"
        ".reg .pred p;\n"
        ".reg .u32 n;\n"
        "mov.u32 n, 0;\n"
        "WAIT_%=:\n"
        "mbarrier.try_wait.parity.shared::cta.b64 p, [%0], %1;\n"
        "@p bra DONE_%=;\n"
        "add.u32 n, n, 1;\n"
        "setp.lt.u32 p, n, 4194304;\n"
        "@p bra WAIT_%=;\n"
        "exit;\n"
        "DONE_%=:\n"
        "}\n" :: "r"(bar), "r"(parity) : "memory");
}
__device__ __forceinline__ void mbar_wait4(uint32_t b0, uint32_t p0, uint32_t b1, uint32_t p1, uint32_t b2, uint32_t p2,
                                           uint32_t b3, uint32_t p3) {
    asm volatile(
        "{\n"
        ".reg .pred p, q, r, s;\n"
        ".reg .u32 n;\n"
        "mov.u32 n, 0;\n"
        "WAIT_%=:\n"
        "mbarrier.try_wait.parity.shared::cta.b64 p, [%0], %1;\n"
        "mbarrier.try_wait.parity.shared::cta.b64 q, [%2], %3;\n"
        "mbarrier.try_wait.parity.shared::cta.b64 r, [%4], %5;\n"
        "mbarrier.try_wait.parity.shared::cta.b64 s, [%6], %7;\n"
        "and.pred p, p, q;\n"
        "and.pred r, r, s;\n"
        "and.pred p, p, r;\n"
        "@p bra DONE_%=;\n"
        "add.u32 n, n, 1;\n"
        "setp.lt.u32 p, n, 4194304;\n"
        "@p bra WAIT_%=;\n"
        "exit;\n"
        "DONE_%=:\n"
        "}\n" :: "r"(b0), "r"(p0), "r"(b1), "r"(p1), "r"(b2), "r"(p2), "r"(b3), "r"(p3) : "memory");
}
__device__ __forceinline__ void mbar_wait2(uint32_t b0, uint32_t p0, uint32_t b1, uint32_t p1) {
    asm volatile(
        "{\n"
        ".reg .pred p, q;\n"
        ".reg .u32 n;\n"
        "mov.u32 n, 0;\n"
        "WAIT_%=:\n"
        "mbarrier.try_wait.parity.shared::cta.b64 p, [%0], %1;\n"
        "mbarrier.try_wait.parity.shared::cta.b64 q, [%2], %3;\n"
        "and.pred p, p, q;\n"
        "@p bra DONE_%=;\n"
        "add.u32 n, n, 1;\n"
        "setp.lt.u32 p, n, 4194304;\n"
        "@p bra WAIT_%=;\n"
        "exit;\n"
        "DONE_%=:\n"
        "}\n" :: "r"(b0), "r"(p0), "r"(b1), "r"(p1) : "memory");
}
__device__ __forceinline__ void mbar_wait_unless(uint32_t ok, uint32_t bar, uint32_t parity) {
    asm volatile(
        "{\n"
        ".reg .pred p;\n"
        ".reg .u32 n;\n"
        "setp.ne.u32 p, %2, 0;\n"
        "vote.sync.all.pred p, p, 0xffffffff;\n"
        "@p bra DONE_%=;\n"
        "mov.u32 n, 0;\n"
        "WAIT_%=:\n"
        "mbarrier.try_wait.parity.shared::cta.b64 p, [%0], %1;\n"
        "@p bra DONE_%=;\n"
        "add.u32 n, n, 1;\n"
        "setp.lt.u32 p, n, 4194304;\n"
        "@p bra WAIT_%=;\n"
        "exit;\n"
        "DONE_%=:\n"
        "}\n" :: "r"(bar), "r"(parity), "r"(ok) : "memory");
}
__device__ __forceinline__ void mbar_wait2_unless(uint32_t ok, uint32_t b0, uint32_t p0, uint32_t b1, uint32_t p1) {
    asm volatile(
        "{\n"
        ".reg .pred p, q;\n"
        ".reg .u32 n;\n"
        "setp.ne.u32 p, %4, 0;\n"
        "vote.sync.all.pred p, p, 0xffffffff;\n"
        "@p bra DONE_%=;\n"
        "mov.u32 n, 0;\n"
        "WAIT_%=:\n"
        "mbarrier.try_wait.parity.shared::cta.b64 p, [%0], %1;\n"
        "mbarrier.try_wait.parity.shared::cta.b64 q, [%2], %3;\n"
        "and.pred p, p, q;\n"
        "@p bra DONE_%=;\n"
        "add.u32 n, n, 1;\n"
        "setp.lt.u32 p, n, 4194304;\n"
        "@p bra WAIT_%=;\n"
        "exit;\n"
        "DONE_%=:\n"
        "}\n" :: "r"(b0), "r"(p0), "r"(b1), "r"(p1), "r"(ok) : "memory");
}
__device__ __forceinline__ void mbar_wait4_unless(uint32_t ok, uint32_t b0, uint32_t p0, uint32_t b1, uint32_t p1, uint32_t b2,
                                                  uint32_t p2, uint32_t b3, uint32_t p3) {
    asm volatile(
        "{\n"
        ".reg .pred p, q, r, s;\n"
        ".reg .u32 n;\n"
        "setp.ne.u32 p, %8, 0;\n"
        "vote.sync.all.pred p, p, 0xffffffff;\n"
        "@p bra DONE_%=;\n"
        "mov.u32 n, 0;\n"
        "WAIT_%=:\n"
        "mbarrier.try_wait.parity.shared::cta.b64 p, [%0], %1;\n"
        "mbarrier.try_wait.parity.shared::cta.b64 q, [%2], %3;\n"
        "mbarrier.try_wait.parity.shared::cta.b64 r, [%4], %5;\n"
        "mbarrier.try_wait.parity.shared::cta.b64 s, [%6], %7;\n"
        "and.pred p, p, q;\n"
        "and.pred r, r, s;\n"
        "and.pred p, p, r;\n"
        "@p bra DONE_%=;\n"
        "add.u32 n, n, 1;\n"
        "setp.lt.u32 p, n, 4194304;\n"
        "@p bra WAIT_%=;\n"
        "exit;\n"
        "DONE_%=:\n"
        "}\n" :: "r"(b0), "r"(p0), "r"(b1), "r"(p1), "r"(b2), "r"(p2), "r"(b3), "r"(p3), "r"(ok) : "memory");
}
__device__ __forceinline__ void sched_fence(uint32_t zero, uint32_t a, uint32_t b, uint32_t c, uint32_t d, uint32_t e = 0,
                                            uint32_t f = 0, uint32_t g = 0, uint32_t h = 0, uint32_t i = 0, uint32_t j = 0,
                                            uint32_t k = 0) {
    asm volatile("{\n.reg .pred p;\n.reg .u32 n;\nsetp.eq.u32 p, %0, 0;\n@p bra.uni DONE_%=;\nmov.u32 n, %0;\nSPIN_%=:\n"
                 "nanosleep.u32 %1;\nnanosleep.u32 %2;\nnanosleep.u32 %3;\nnanosleep.u32 %4;\nnanosleep.u32 %5;\n"
                 "nanosleep.u32 %6;\nnanosleep.u32 %7;\nnanosleep.u32 %8;\nnanosleep.u32 %9;\nnanosleep.u32 %10;\n"
                 "nanosleep.u32 %11;\nsub.u32 n, n, 1;\nsetp.ne.u32 p, n, 0;\n@p bra.uni SPIN_%=;\nDONE_%=:\n}\n"
                 :: "r"(zero), "r"(a), "r"(b), "r"(c), "r"(d), "r"(e), "r"(f), "r"(g), "r"(h), "r"(i), "r"(j), "r"(k) : "memory");
}
__device__ __forceinline__ void mbar_arrive(uint32_t bar) {
    asm volatile("mbarrier.arrive.shared::cta.b64 _, [%0];\n" :: "r"(bar) : "memory");
}
__device__ __forceinline__ void mbar_arrive_n(uint32_t bar, uint32_t n) {
    asm volatile("mbarrier.arrive.shared::cta.b64 _, [%0], %1;\n" :: "r"(bar), "r"(n) : "memory");
}
__device__ __forceinline__ void mbar_arrive_expect_tx(uint32_t bar, uint32_t bytes) {
    asm volatile("mbarrier.arrive.expect_tx.shared::cta.b64 _, [%0], %1;\n" :: "r"(bar), "r"(bytes) : "memory");
}
__device__ __forceinline__ void stg128_if(bool p, void* addr, uint32_t x, uint32_t y, uint32_t z, uint32_t w) {
    asm volatile("{\n.reg .pred q;\nsetp.ne.b32 q, %5, 0;\n@q st.global.L1::no_allocate.v4.b32 [%0], {%1, %2, %3, %4};\n}\n"
                 :: "l"(addr), "r"(x), "r"(y), "r"(z), "r"(w), "r"((uint32_t)p) : "memory");
}
__device__ __forceinline__ void stsm_x4(uint32_t addr, uint32_t r0, uint32_t r1, uint32_t r2, uint32_t r3) {
    asm volatile("stmatrix.sync.aligned.m8n8.x4.shared.b16 [%0], {%1, %2, %3, %4};\n"
                 :: "r"(addr), "r"(r0), "r"(r1), "r"(r2), "r"(r3) : "memory");
}
__device__ __forceinline__ void stsm_x2(uint32_t addr, uint32_t r0, uint32_t r1) {
    asm volatile("stmatrix.sync.aligned.m8n8.x2.shared.b16 [%0], {%1, %2};\n" :: "r"(addr), "r"(r0), "r"(r1) : "memory");
}
__device__ __forceinline__ void sts128(uint32_t addr, uint32_t r0, uint32_t r1, uint32_t r2, uint32_t r3) {
    asm volatile("st.shared.v4.b32 [%0], {%1, %2, %3, %4};\n" :: "r"(addr), "r"(r0), "r"(r1), "r"(r2), "r"(r3) : "memory");
}
__device__ __forceinline__ void sts32(uint32_t addr, uint32_t v) {
    asm volatile("st.shared.b32 [%0], %1;\n" :: "r"(addr), "r"(v) : "memory");
}
__device__ __forceinline__ uint32_t lds32(uint32_t addr) {
    uint32_t v;
    asm volatile("ld.shared.b32 %0, [%1];\n" : "=r"(v) : "r"(addr) : "memory");
    return v;
}
__device__ __forceinline__ void ldg_nc_v4(uint32_t (&r)[4], const void* p) {
    asm volatile("ld.global.nc.L1::no_allocate.v4.u32 {%0, %1, %2, %3}, [%4];\n"
                 : "=r"(r[0]), "=r"(r[1]), "=r"(r[2]), "=r"(r[3]) : "l"(p));
}
__device__ __forceinline__ uint32_t ldg_u32(const void* p) {
    uint32_t v;
    asm volatile("ld.global.nc.L1::evict_first.u32 %0, [%1];\n" : "=r"(v) : "l"(p));
    return v;
}
__device__ __forceinline__ void ldg_u64(const void* p, uint32_t& a, uint32_t& b) {
    asm volatile("ld.global.nc.L1::evict_first.v2.u32 {%0, %1}, [%2];\n" : "=r"(a), "=r"(b) : "l"(p));
}
__device__ __forceinline__ void prefetch_l2(const void* p) {
    asm volatile("prefetch.global.L2 [%0];\n" :: "l"(p));
}
__device__ __forceinline__ void cp_async16(uint32_t dst, const void* src) {
    asm volatile("cp.async.cg.shared.global [%0], [%1], 16;\n" :: "r"(dst), "l"(src) : "memory");
}
__device__ __forceinline__ float ex2_ftz(float x) {
    float y;
    asm("ex2.approx.ftz.f32 %0, %1;\n" : "=f"(y) : "f"(x));
    return y;
}
__device__ __forceinline__ float rcp_ftz(float x) {
    float y;
    asm("rcp.approx.ftz.f32 %0, %1;\n" : "=f"(y) : "f"(x));
    return y;
}
__device__ __forceinline__ float rsqrt_ftz(float x) {
    float y;
    asm("rsqrt.approx.ftz.f32 %0, %1;\n" : "=f"(y) : "f"(x));
    return y;
}

__device__ __forceinline__ bool elect_one() {
    uint32_t p;
    asm volatile("{\n.reg .pred q;\nelect.sync _|q, 0xffffffff;\nselp.u32 %0, 1, 0, q;\n}\n" : "=r"(p));
    return p != 0;
}
__device__ __forceinline__ void ldsm_x4(uint32_t (&r)[4], uint32_t addr) {
    asm volatile("ldmatrix.sync.aligned.m8n8.x4.shared.b16 {%0, %1, %2, %3}, [%4];\n"
                 : "=r"(r[0]), "=r"(r[1]), "=r"(r[2]), "=r"(r[3]) : "r"(addr) : "memory");
}
__device__ __forceinline__ void ldsm_x2(uint32_t& r0, uint32_t& r1, uint32_t addr) {
    asm volatile("ldmatrix.sync.aligned.m8n8.x2.shared.b16 {%0, %1}, [%2];\n" : "=r"(r0), "=r"(r1) : "r"(addr) : "memory");
}
__device__ __forceinline__ void tma_2d(uint32_t dst, const CUtensorMap* map, uint32_t bar, int c0, int c1) {
    asm volatile("cp.async.bulk.tensor.2d.shared::cluster.global.mbarrier::complete_tx::bytes [%0], [%1, {%3, %4}], [%2];\n"
                 :: "r"(dst), "l"(reinterpret_cast<uint64_t>(map)), "r"(bar), "r"(c0), "r"(c1) : "memory");
}
__device__ __forceinline__ void tma_3d(uint32_t dst, const CUtensorMap* map, uint32_t bar, int c0, int c1, int c2) {
    asm volatile("cp.async.bulk.tensor.3d.shared::cluster.global.mbarrier::complete_tx::bytes [%0], [%1, {%3, %4, %5}], [%2];\n"
                 :: "r"(dst), "l"(reinterpret_cast<uint64_t>(map)), "r"(bar), "r"(c0), "r"(c1), "r"(c2) : "memory");
}
__device__ __forceinline__ void tma_store_4d(const CUtensorMap* map, uint32_t src, int c0, int c1, int c2, int c3) {
    asm volatile("cp.async.bulk.tensor.4d.global.shared::cta.tile.bulk_group [%0, {%2, %3, %4, %5}], [%1];\n"
                 :: "l"(reinterpret_cast<uint64_t>(map)), "r"(src), "r"(c0), "r"(c1), "r"(c2), "r"(c3) : "memory");
}
__device__ __forceinline__ void mbar_arrive_if(uint32_t bar, uint32_t cnt) {
    asm volatile("{\n.reg .pred q;\nsetp.ne.b32 q, %1, 0;\n@q mbarrier.arrive.shared::cta.b64 _, [%0], %1;\n}\n"
                 :: "r"(bar), "r"(cnt) : "memory");
}

template <int BOFF, int AOFF, int NA>
__device__ __forceinline__ void mma_qkv_a(float (&d)[48], const uint32_t (&a)[NA][4], uint64_t descB) {
    asm volatile(
        "{\n"
        ".reg .pred p0, p1;\n"
        ".reg .b64 ta, ta0, tb, tb0;\n"
        "setp.ne.b32 p0, 0, 0;\n"
        "setp.eq.b32 p1, 0, 0;\n"
        "add.s64 tb0, %72, %73;\n"
        "add.s64 tb, tb0, 0;\n"
        "wgmma.mma_async.sync.aligned.m64n96k16.f32.bf16.bf16 {%0, %1, %2, %3, %4, %5, %6, %7, %8, %9, %10, %11, %12, %13, %14, %15, %16, %17, %18, %19, %20, %21, %22, %23, %24, %25, %26, %27, %28, %29, %30, %31, %32, %33, %34, %35, %36, %37, %38, %39, %40, %41, %42, %43, %44, %45, %46, %47}, {%48, %49, %50, %51}, tb, p0, 1, 1, 1;\n"
        "add.s64 tb, tb0, 32;\n"
        "wgmma.mma_async.sync.aligned.m64n96k16.f32.bf16.bf16 {%0, %1, %2, %3, %4, %5, %6, %7, %8, %9, %10, %11, %12, %13, %14, %15, %16, %17, %18, %19, %20, %21, %22, %23, %24, %25, %26, %27, %28, %29, %30, %31, %32, %33, %34, %35, %36, %37, %38, %39, %40, %41, %42, %43, %44, %45, %46, %47}, {%52, %53, %54, %55}, tb, p1, 1, 1, 1;\n"
        "add.s64 tb, tb0, 64;\n"
        "wgmma.mma_async.sync.aligned.m64n96k16.f32.bf16.bf16 {%0, %1, %2, %3, %4, %5, %6, %7, %8, %9, %10, %11, %12, %13, %14, %15, %16, %17, %18, %19, %20, %21, %22, %23, %24, %25, %26, %27, %28, %29, %30, %31, %32, %33, %34, %35, %36, %37, %38, %39, %40, %41, %42, %43, %44, %45, %46, %47}, {%56, %57, %58, %59}, tb, p1, 1, 1, 1;\n"
        "add.s64 tb, tb0, 96;\n"
        "wgmma.mma_async.sync.aligned.m64n96k16.f32.bf16.bf16 {%0, %1, %2, %3, %4, %5, %6, %7, %8, %9, %10, %11, %12, %13, %14, %15, %16, %17, %18, %19, %20, %21, %22, %23, %24, %25, %26, %27, %28, %29, %30, %31, %32, %33, %34, %35, %36, %37, %38, %39, %40, %41, %42, %43, %44, %45, %46, %47}, {%60, %61, %62, %63}, tb, p1, 1, 1, 1;\n"
        "add.s64 tb, tb0, 128;\n"
        "wgmma.mma_async.sync.aligned.m64n96k16.f32.bf16.bf16 {%0, %1, %2, %3, %4, %5, %6, %7, %8, %9, %10, %11, %12, %13, %14, %15, %16, %17, %18, %19, %20, %21, %22, %23, %24, %25, %26, %27, %28, %29, %30, %31, %32, %33, %34, %35, %36, %37, %38, %39, %40, %41, %42, %43, %44, %45, %46, %47}, {%64, %65, %66, %67}, tb, p1, 1, 1, 1;\n"
        "add.s64 tb, tb0, 160;\n"
        "wgmma.mma_async.sync.aligned.m64n96k16.f32.bf16.bf16 {%0, %1, %2, %3, %4, %5, %6, %7, %8, %9, %10, %11, %12, %13, %14, %15, %16, %17, %18, %19, %20, %21, %22, %23, %24, %25, %26, %27, %28, %29, %30, %31, %32, %33, %34, %35, %36, %37, %38, %39, %40, %41, %42, %43, %44, %45, %46, %47}, {%68, %69, %70, %71}, tb, p1, 1, 1, 1;\n"
        "}\n"
        : "+f"(d[0]), "+f"(d[1]), "+f"(d[2]), "+f"(d[3]), "+f"(d[4]), "+f"(d[5]), "+f"(d[6]), "+f"(d[7]), "+f"(d[8]), "+f"(d[9]), "+f"(d[10]), "+f"(d[11]), "+f"(d[12]), "+f"(d[13]), "+f"(d[14]), "+f"(d[15]), "+f"(d[16]), "+f"(d[17]), "+f"(d[18]), "+f"(d[19]), "+f"(d[20]), "+f"(d[21]), "+f"(d[22]), "+f"(d[23]), "+f"(d[24]), "+f"(d[25]), "+f"(d[26]), "+f"(d[27]), "+f"(d[28]), "+f"(d[29]), "+f"(d[30]), "+f"(d[31]), "+f"(d[32]), "+f"(d[33]), "+f"(d[34]), "+f"(d[35]), "+f"(d[36]), "+f"(d[37]), "+f"(d[38]), "+f"(d[39]), "+f"(d[40]), "+f"(d[41]), "+f"(d[42]), "+f"(d[43]), "+f"(d[44]), "+f"(d[45]), "+f"(d[46]), "+f"(d[47])
        : "r"(a[AOFF + 0][0]), "r"(a[AOFF + 0][1]), "r"(a[AOFF + 0][2]), "r"(a[AOFF + 0][3]), "r"(a[AOFF + 1][0]), "r"(a[AOFF + 1][1]), "r"(a[AOFF + 1][2]), "r"(a[AOFF + 1][3]), "r"(a[AOFF + 2][0]), "r"(a[AOFF + 2][1]), "r"(a[AOFF + 2][2]), "r"(a[AOFF + 2][3]), "r"(a[AOFF + 3][0]), "r"(a[AOFF + 3][1]), "r"(a[AOFF + 3][2]), "r"(a[AOFF + 3][3]), "r"(a[AOFF + 4][0]), "r"(a[AOFF + 4][1]), "r"(a[AOFF + 4][2]), "r"(a[AOFF + 4][3]), "r"(a[AOFF + 5][0]), "r"(a[AOFF + 5][1]), "r"(a[AOFF + 5][2]), "r"(a[AOFF + 5][3]), "l"(descB), "n"(BOFF >> 4));
}

template <int BOFF, int AOFF, int NA>
__device__ __forceinline__ void mma_qkv_b(float (&d)[48], const uint32_t (&a)[NA][4], uint64_t descB) {
    asm volatile(
        "{\n"
        ".reg .pred p0, p1;\n"
        ".reg .b64 ta, ta0, tb, tb0;\n"
        "setp.ne.b32 p0, 0, 0;\n"
        "setp.eq.b32 p1, 0, 0;\n"
        "add.s64 tb0, %72, %73;\n"
        "add.s64 tb, tb0, 192;\n"
        "wgmma.mma_async.sync.aligned.m64n96k16.f32.bf16.bf16 {%0, %1, %2, %3, %4, %5, %6, %7, %8, %9, %10, %11, %12, %13, %14, %15, %16, %17, %18, %19, %20, %21, %22, %23, %24, %25, %26, %27, %28, %29, %30, %31, %32, %33, %34, %35, %36, %37, %38, %39, %40, %41, %42, %43, %44, %45, %46, %47}, {%48, %49, %50, %51}, tb, p1, 1, 1, 1;\n"
        "add.s64 tb, tb0, 224;\n"
        "wgmma.mma_async.sync.aligned.m64n96k16.f32.bf16.bf16 {%0, %1, %2, %3, %4, %5, %6, %7, %8, %9, %10, %11, %12, %13, %14, %15, %16, %17, %18, %19, %20, %21, %22, %23, %24, %25, %26, %27, %28, %29, %30, %31, %32, %33, %34, %35, %36, %37, %38, %39, %40, %41, %42, %43, %44, %45, %46, %47}, {%52, %53, %54, %55}, tb, p1, 1, 1, 1;\n"
        "add.s64 tb, tb0, 256;\n"
        "wgmma.mma_async.sync.aligned.m64n96k16.f32.bf16.bf16 {%0, %1, %2, %3, %4, %5, %6, %7, %8, %9, %10, %11, %12, %13, %14, %15, %16, %17, %18, %19, %20, %21, %22, %23, %24, %25, %26, %27, %28, %29, %30, %31, %32, %33, %34, %35, %36, %37, %38, %39, %40, %41, %42, %43, %44, %45, %46, %47}, {%56, %57, %58, %59}, tb, p1, 1, 1, 1;\n"
        "add.s64 tb, tb0, 288;\n"
        "wgmma.mma_async.sync.aligned.m64n96k16.f32.bf16.bf16 {%0, %1, %2, %3, %4, %5, %6, %7, %8, %9, %10, %11, %12, %13, %14, %15, %16, %17, %18, %19, %20, %21, %22, %23, %24, %25, %26, %27, %28, %29, %30, %31, %32, %33, %34, %35, %36, %37, %38, %39, %40, %41, %42, %43, %44, %45, %46, %47}, {%60, %61, %62, %63}, tb, p1, 1, 1, 1;\n"
        "add.s64 tb, tb0, 320;\n"
        "wgmma.mma_async.sync.aligned.m64n96k16.f32.bf16.bf16 {%0, %1, %2, %3, %4, %5, %6, %7, %8, %9, %10, %11, %12, %13, %14, %15, %16, %17, %18, %19, %20, %21, %22, %23, %24, %25, %26, %27, %28, %29, %30, %31, %32, %33, %34, %35, %36, %37, %38, %39, %40, %41, %42, %43, %44, %45, %46, %47}, {%64, %65, %66, %67}, tb, p1, 1, 1, 1;\n"
        "add.s64 tb, tb0, 352;\n"
        "wgmma.mma_async.sync.aligned.m64n96k16.f32.bf16.bf16 {%0, %1, %2, %3, %4, %5, %6, %7, %8, %9, %10, %11, %12, %13, %14, %15, %16, %17, %18, %19, %20, %21, %22, %23, %24, %25, %26, %27, %28, %29, %30, %31, %32, %33, %34, %35, %36, %37, %38, %39, %40, %41, %42, %43, %44, %45, %46, %47}, {%68, %69, %70, %71}, tb, p1, 1, 1, 1;\n"
        "}\n"
        : "+f"(d[0]), "+f"(d[1]), "+f"(d[2]), "+f"(d[3]), "+f"(d[4]), "+f"(d[5]), "+f"(d[6]), "+f"(d[7]), "+f"(d[8]), "+f"(d[9]), "+f"(d[10]), "+f"(d[11]), "+f"(d[12]), "+f"(d[13]), "+f"(d[14]), "+f"(d[15]), "+f"(d[16]), "+f"(d[17]), "+f"(d[18]), "+f"(d[19]), "+f"(d[20]), "+f"(d[21]), "+f"(d[22]), "+f"(d[23]), "+f"(d[24]), "+f"(d[25]), "+f"(d[26]), "+f"(d[27]), "+f"(d[28]), "+f"(d[29]), "+f"(d[30]), "+f"(d[31]), "+f"(d[32]), "+f"(d[33]), "+f"(d[34]), "+f"(d[35]), "+f"(d[36]), "+f"(d[37]), "+f"(d[38]), "+f"(d[39]), "+f"(d[40]), "+f"(d[41]), "+f"(d[42]), "+f"(d[43]), "+f"(d[44]), "+f"(d[45]), "+f"(d[46]), "+f"(d[47])
        : "r"(a[AOFF + 0][0]), "r"(a[AOFF + 0][1]), "r"(a[AOFF + 0][2]), "r"(a[AOFF + 0][3]), "r"(a[AOFF + 1][0]), "r"(a[AOFF + 1][1]), "r"(a[AOFF + 1][2]), "r"(a[AOFF + 1][3]), "r"(a[AOFF + 2][0]), "r"(a[AOFF + 2][1]), "r"(a[AOFF + 2][2]), "r"(a[AOFF + 2][3]), "r"(a[AOFF + 3][0]), "r"(a[AOFF + 3][1]), "r"(a[AOFF + 3][2]), "r"(a[AOFF + 3][3]), "r"(a[AOFF + 4][0]), "r"(a[AOFF + 4][1]), "r"(a[AOFF + 4][2]), "r"(a[AOFF + 4][3]), "r"(a[AOFF + 5][0]), "r"(a[AOFF + 5][1]), "r"(a[AOFF + 5][2]), "r"(a[AOFF + 5][3]), "l"(descB), "n"(BOFF >> 4));
}

template <int AOFF, int BOFF>
__device__ __forceinline__ void mma_qk0(float (&d)[28], uint64_t descA, uint64_t descB) {
    asm volatile(
        "{\n"
        ".reg .pred p0, p1;\n"
        ".reg .b64 ta, ta0, tb, tb0;\n"
        "setp.ne.b32 p0, 0, 0;\n"
        "setp.eq.b32 p1, 0, 0;\n"
        "add.s64 tb0, %30, %31;\n"
        "add.s64 ta0, %28, %29;\n"
        "add.s64 tb, tb0, 4;\n"
        "add.s64 ta, ta0, 0;\n"
        "wgmma.mma_async.sync.aligned.m64n56k16.f32.bf16.bf16 {%0, %1, %2, %3, %4, %5, %6, %7, %8, %9, %10, %11, %12, %13, %14, %15, %16, %17, %18, %19, %20, %21, %22, %23, %24, %25, %26, %27}, ta, tb, p1, 1, 1, 0, 0;\n"
        "add.s64 tb, tb0, 1572;\n"
        "add.s64 ta, ta0, 1568;\n"
        "wgmma.mma_async.sync.aligned.m64n56k16.f32.bf16.bf16 {%0, %1, %2, %3, %4, %5, %6, %7, %8, %9, %10, %11, %12, %13, %14, %15, %16, %17, %18, %19, %20, %21, %22, %23, %24, %25, %26, %27}, ta, tb, p1, 1, 1, 0, 0;\n"
        "add.s64 tb, tb0, 3140;\n"
        "add.s64 ta, ta0, 3136;\n"
        "wgmma.mma_async.sync.aligned.m64n56k16.f32.bf16.bf16 {%0, %1, %2, %3, %4, %5, %6, %7, %8, %9, %10, %11, %12, %13, %14, %15, %16, %17, %18, %19, %20, %21, %22, %23, %24, %25, %26, %27}, ta, tb, p1, 1, 1, 0, 0;\n"
        "}\n"
        : "+f"(d[0]), "+f"(d[1]), "+f"(d[2]), "+f"(d[3]), "+f"(d[4]), "+f"(d[5]), "+f"(d[6]), "+f"(d[7]), "+f"(d[8]), "+f"(d[9]), "+f"(d[10]), "+f"(d[11]), "+f"(d[12]), "+f"(d[13]), "+f"(d[14]), "+f"(d[15]), "+f"(d[16]), "+f"(d[17]), "+f"(d[18]), "+f"(d[19]), "+f"(d[20]), "+f"(d[21]), "+f"(d[22]), "+f"(d[23]), "+f"(d[24]), "+f"(d[25]), "+f"(d[26]), "+f"(d[27])
        : "l"(descA), "n"(AOFF >> 4), "l"(descB), "n"(BOFF >> 4));
}

template <int AOFF, int BOFF>
__device__ __forceinline__ void mma_qk1(float (&d)[28], uint64_t descA, uint64_t descB) {
    asm volatile(
        "{\n"
        ".reg .pred p0, p1;\n"
        ".reg .b64 ta, ta0, tb, tb0;\n"
        "setp.ne.b32 p0, 0, 0;\n"
        "setp.eq.b32 p1, 0, 0;\n"
        "add.s64 tb0, %30, %31;\n"
        "add.s64 ta0, %28, %29;\n"
        "add.s64 tb, tb0, 6;\n"
        "add.s64 ta, ta0, 2;\n"
        "wgmma.mma_async.sync.aligned.m64n56k16.f32.bf16.bf16 {%0, %1, %2, %3, %4, %5, %6, %7, %8, %9, %10, %11, %12, %13, %14, %15, %16, %17, %18, %19, %20, %21, %22, %23, %24, %25, %26, %27}, ta, tb, p1, 1, 1, 0, 0;\n"
        "add.s64 tb, tb0, 1574;\n"
        "add.s64 ta, ta0, 1570;\n"
        "wgmma.mma_async.sync.aligned.m64n56k16.f32.bf16.bf16 {%0, %1, %2, %3, %4, %5, %6, %7, %8, %9, %10, %11, %12, %13, %14, %15, %16, %17, %18, %19, %20, %21, %22, %23, %24, %25, %26, %27}, ta, tb, p1, 1, 1, 0, 0;\n"
        "add.s64 tb, tb0, 3142;\n"
        "add.s64 ta, ta0, 3138;\n"
        "wgmma.mma_async.sync.aligned.m64n56k16.f32.bf16.bf16 {%0, %1, %2, %3, %4, %5, %6, %7, %8, %9, %10, %11, %12, %13, %14, %15, %16, %17, %18, %19, %20, %21, %22, %23, %24, %25, %26, %27}, ta, tb, p1, 1, 1, 0, 0;\n"
        "}\n"
        : "+f"(d[0]), "+f"(d[1]), "+f"(d[2]), "+f"(d[3]), "+f"(d[4]), "+f"(d[5]), "+f"(d[6]), "+f"(d[7]), "+f"(d[8]), "+f"(d[9]), "+f"(d[10]), "+f"(d[11]), "+f"(d[12]), "+f"(d[13]), "+f"(d[14]), "+f"(d[15]), "+f"(d[16]), "+f"(d[17]), "+f"(d[18]), "+f"(d[19]), "+f"(d[20]), "+f"(d[21]), "+f"(d[22]), "+f"(d[23]), "+f"(d[24]), "+f"(d[25]), "+f"(d[26]), "+f"(d[27])
        : "l"(descA), "n"(AOFF >> 4), "l"(descB), "n"(BOFF >> 4));
}

template <int BOFF, int AOFF, int NA>
__device__ __forceinline__ void mma_pv(float (&d)[28], const uint32_t (&a)[NA][4], uint64_t descB) {
    asm volatile(
        "{\n"
        ".reg .pred p0, p1;\n"
        ".reg .b64 ta, ta0, tb, tb0;\n"
        "setp.ne.b32 p0, 0, 0;\n"
        "setp.eq.b32 p1, 0, 0;\n"
        "add.s64 tb0, %44, %45;\n"
        "add.s64 tb, tb0, 0;\n"
        "wgmma.mma_async.sync.aligned.m64n56k16.f32.bf16.bf16 {%0, %1, %2, %3, %4, %5, %6, %7, %8, %9, %10, %11, %12, %13, %14, %15, %16, %17, %18, %19, %20, %21, %22, %23, %24, %25, %26, %27}, {%28, %29, %30, %31}, tb, p0, 1, 1, 1;\n"
        "add.s64 tb, tb0, 16;\n"
        "wgmma.mma_async.sync.aligned.m64n56k16.f32.bf16.bf16 {%0, %1, %2, %3, %4, %5, %6, %7, %8, %9, %10, %11, %12, %13, %14, %15, %16, %17, %18, %19, %20, %21, %22, %23, %24, %25, %26, %27}, {%32, %33, %34, %35}, tb, p1, 1, 1, 1;\n"
        "add.s64 tb, tb0, 32;\n"
        "wgmma.mma_async.sync.aligned.m64n56k16.f32.bf16.bf16 {%0, %1, %2, %3, %4, %5, %6, %7, %8, %9, %10, %11, %12, %13, %14, %15, %16, %17, %18, %19, %20, %21, %22, %23, %24, %25, %26, %27}, {%36, %37, %38, %39}, tb, p1, 1, 1, 1;\n"
        "add.s64 tb, tb0, 48;\n"
        "wgmma.mma_async.sync.aligned.m64n56k16.f32.bf16.bf16 {%0, %1, %2, %3, %4, %5, %6, %7, %8, %9, %10, %11, %12, %13, %14, %15, %16, %17, %18, %19, %20, %21, %22, %23, %24, %25, %26, %27}, {%40, %41, %42, %43}, tb, p1, 1, 1, 1;\n"
        "}\n"
        : "=f"(d[0]), "=f"(d[1]), "=f"(d[2]), "=f"(d[3]), "=f"(d[4]), "=f"(d[5]), "=f"(d[6]), "=f"(d[7]), "=f"(d[8]), "=f"(d[9]), "=f"(d[10]), "=f"(d[11]), "=f"(d[12]), "=f"(d[13]), "=f"(d[14]), "=f"(d[15]), "=f"(d[16]), "=f"(d[17]), "=f"(d[18]), "=f"(d[19]), "=f"(d[20]), "=f"(d[21]), "=f"(d[22]), "=f"(d[23]), "=f"(d[24]), "=f"(d[25]), "=f"(d[26]), "=f"(d[27])
        : "r"(a[AOFF + 0][0]), "r"(a[AOFF + 0][1]), "r"(a[AOFF + 0][2]), "r"(a[AOFF + 0][3]), "r"(a[AOFF + 1][0]), "r"(a[AOFF + 1][1]), "r"(a[AOFF + 1][2]), "r"(a[AOFF + 1][3]), "r"(a[AOFF + 2][0]), "r"(a[AOFF + 2][1]), "r"(a[AOFF + 2][2]), "r"(a[AOFF + 2][3]), "r"(a[AOFF + 3][0]), "r"(a[AOFF + 3][1]), "r"(a[AOFF + 3][2]), "r"(a[AOFF + 3][3]), "l"(descB), "n"(BOFF >> 4));
}

template <int AOFF, int BOFF>
__device__ __forceinline__ void mma_proj(float (&d)[96], uint64_t descA, uint64_t descB) {
    asm volatile(
        "{\n"
        ".reg .pred p0, p1;\n"
        ".reg .b64 ta, ta0, tb, tb0;\n"
        "setp.ne.b32 p0, 0, 0;\n"
        "setp.eq.b32 p1, 0, 0;\n"
        "add.s64 tb0, %98, %99;\n"
        "add.s64 ta0, %96, %97;\n"
        "add.s64 tb, tb0, 0;\n"
        "add.s64 ta, ta0, 0;\n"
        "wgmma.mma_async.sync.aligned.m64n192k16.f32.bf16.bf16 {%0, %1, %2, %3, %4, %5, %6, %7, %8, %9, %10, %11, %12, %13, %14, %15, %16, %17, %18, %19, %20, %21, %22, %23, %24, %25, %26, %27, %28, %29, %30, %31, %32, %33, %34, %35, %36, %37, %38, %39, %40, %41, %42, %43, %44, %45, %46, %47, %48, %49, %50, %51, %52, %53, %54, %55, %56, %57, %58, %59, %60, %61, %62, %63, %64, %65, %66, %67, %68, %69, %70, %71, %72, %73, %74, %75, %76, %77, %78, %79, %80, %81, %82, %83, %84, %85, %86, %87, %88, %89, %90, %91, %92, %93, %94, %95}, ta, tb, p0, 1, 1, 0, 1;\n"
        "add.s64 tb, tb0, 64;\n"
        "add.s64 ta, ta0, 2;\n"
        "wgmma.mma_async.sync.aligned.m64n192k16.f32.bf16.bf16 {%0, %1, %2, %3, %4, %5, %6, %7, %8, %9, %10, %11, %12, %13, %14, %15, %16, %17, %18, %19, %20, %21, %22, %23, %24, %25, %26, %27, %28, %29, %30, %31, %32, %33, %34, %35, %36, %37, %38, %39, %40, %41, %42, %43, %44, %45, %46, %47, %48, %49, %50, %51, %52, %53, %54, %55, %56, %57, %58, %59, %60, %61, %62, %63, %64, %65, %66, %67, %68, %69, %70, %71, %72, %73, %74, %75, %76, %77, %78, %79, %80, %81, %82, %83, %84, %85, %86, %87, %88, %89, %90, %91, %92, %93, %94, %95}, ta, tb, p1, 1, 1, 0, 1;\n"
        "add.s64 tb, tb0, 128;\n"
        "add.s64 ta, ta0, 4;\n"
        "wgmma.mma_async.sync.aligned.m64n192k16.f32.bf16.bf16 {%0, %1, %2, %3, %4, %5, %6, %7, %8, %9, %10, %11, %12, %13, %14, %15, %16, %17, %18, %19, %20, %21, %22, %23, %24, %25, %26, %27, %28, %29, %30, %31, %32, %33, %34, %35, %36, %37, %38, %39, %40, %41, %42, %43, %44, %45, %46, %47, %48, %49, %50, %51, %52, %53, %54, %55, %56, %57, %58, %59, %60, %61, %62, %63, %64, %65, %66, %67, %68, %69, %70, %71, %72, %73, %74, %75, %76, %77, %78, %79, %80, %81, %82, %83, %84, %85, %86, %87, %88, %89, %90, %91, %92, %93, %94, %95}, ta, tb, p1, 1, 1, 0, 1;\n"
        "add.s64 tb, tb0, 192;\n"
        "add.s64 ta, ta0, 6;\n"
        "wgmma.mma_async.sync.aligned.m64n192k16.f32.bf16.bf16 {%0, %1, %2, %3, %4, %5, %6, %7, %8, %9, %10, %11, %12, %13, %14, %15, %16, %17, %18, %19, %20, %21, %22, %23, %24, %25, %26, %27, %28, %29, %30, %31, %32, %33, %34, %35, %36, %37, %38, %39, %40, %41, %42, %43, %44, %45, %46, %47, %48, %49, %50, %51, %52, %53, %54, %55, %56, %57, %58, %59, %60, %61, %62, %63, %64, %65, %66, %67, %68, %69, %70, %71, %72, %73, %74, %75, %76, %77, %78, %79, %80, %81, %82, %83, %84, %85, %86, %87, %88, %89, %90, %91, %92, %93, %94, %95}, ta, tb, p1, 1, 1, 0, 1;\n"
        "add.s64 tb, tb0, 256;\n"
        "add.s64 ta, ta0, 512;\n"
        "wgmma.mma_async.sync.aligned.m64n192k16.f32.bf16.bf16 {%0, %1, %2, %3, %4, %5, %6, %7, %8, %9, %10, %11, %12, %13, %14, %15, %16, %17, %18, %19, %20, %21, %22, %23, %24, %25, %26, %27, %28, %29, %30, %31, %32, %33, %34, %35, %36, %37, %38, %39, %40, %41, %42, %43, %44, %45, %46, %47, %48, %49, %50, %51, %52, %53, %54, %55, %56, %57, %58, %59, %60, %61, %62, %63, %64, %65, %66, %67, %68, %69, %70, %71, %72, %73, %74, %75, %76, %77, %78, %79, %80, %81, %82, %83, %84, %85, %86, %87, %88, %89, %90, %91, %92, %93, %94, %95}, ta, tb, p1, 1, 1, 0, 1;\n"
        "add.s64 tb, tb0, 320;\n"
        "add.s64 ta, ta0, 514;\n"
        "wgmma.mma_async.sync.aligned.m64n192k16.f32.bf16.bf16 {%0, %1, %2, %3, %4, %5, %6, %7, %8, %9, %10, %11, %12, %13, %14, %15, %16, %17, %18, %19, %20, %21, %22, %23, %24, %25, %26, %27, %28, %29, %30, %31, %32, %33, %34, %35, %36, %37, %38, %39, %40, %41, %42, %43, %44, %45, %46, %47, %48, %49, %50, %51, %52, %53, %54, %55, %56, %57, %58, %59, %60, %61, %62, %63, %64, %65, %66, %67, %68, %69, %70, %71, %72, %73, %74, %75, %76, %77, %78, %79, %80, %81, %82, %83, %84, %85, %86, %87, %88, %89, %90, %91, %92, %93, %94, %95}, ta, tb, p1, 1, 1, 0, 1;\n"
        "add.s64 tb, tb0, 384;\n"
        "add.s64 ta, ta0, 516;\n"
        "wgmma.mma_async.sync.aligned.m64n192k16.f32.bf16.bf16 {%0, %1, %2, %3, %4, %5, %6, %7, %8, %9, %10, %11, %12, %13, %14, %15, %16, %17, %18, %19, %20, %21, %22, %23, %24, %25, %26, %27, %28, %29, %30, %31, %32, %33, %34, %35, %36, %37, %38, %39, %40, %41, %42, %43, %44, %45, %46, %47, %48, %49, %50, %51, %52, %53, %54, %55, %56, %57, %58, %59, %60, %61, %62, %63, %64, %65, %66, %67, %68, %69, %70, %71, %72, %73, %74, %75, %76, %77, %78, %79, %80, %81, %82, %83, %84, %85, %86, %87, %88, %89, %90, %91, %92, %93, %94, %95}, ta, tb, p1, 1, 1, 0, 1;\n"
        "add.s64 tb, tb0, 448;\n"
        "add.s64 ta, ta0, 518;\n"
        "wgmma.mma_async.sync.aligned.m64n192k16.f32.bf16.bf16 {%0, %1, %2, %3, %4, %5, %6, %7, %8, %9, %10, %11, %12, %13, %14, %15, %16, %17, %18, %19, %20, %21, %22, %23, %24, %25, %26, %27, %28, %29, %30, %31, %32, %33, %34, %35, %36, %37, %38, %39, %40, %41, %42, %43, %44, %45, %46, %47, %48, %49, %50, %51, %52, %53, %54, %55, %56, %57, %58, %59, %60, %61, %62, %63, %64, %65, %66, %67, %68, %69, %70, %71, %72, %73, %74, %75, %76, %77, %78, %79, %80, %81, %82, %83, %84, %85, %86, %87, %88, %89, %90, %91, %92, %93, %94, %95}, ta, tb, p1, 1, 1, 0, 1;\n"
        "add.s64 tb, tb0, 512;\n"
        "add.s64 ta, ta0, 1024;\n"
        "wgmma.mma_async.sync.aligned.m64n192k16.f32.bf16.bf16 {%0, %1, %2, %3, %4, %5, %6, %7, %8, %9, %10, %11, %12, %13, %14, %15, %16, %17, %18, %19, %20, %21, %22, %23, %24, %25, %26, %27, %28, %29, %30, %31, %32, %33, %34, %35, %36, %37, %38, %39, %40, %41, %42, %43, %44, %45, %46, %47, %48, %49, %50, %51, %52, %53, %54, %55, %56, %57, %58, %59, %60, %61, %62, %63, %64, %65, %66, %67, %68, %69, %70, %71, %72, %73, %74, %75, %76, %77, %78, %79, %80, %81, %82, %83, %84, %85, %86, %87, %88, %89, %90, %91, %92, %93, %94, %95}, ta, tb, p1, 1, 1, 0, 1;\n"
        "add.s64 tb, tb0, 576;\n"
        "add.s64 ta, ta0, 1026;\n"
        "wgmma.mma_async.sync.aligned.m64n192k16.f32.bf16.bf16 {%0, %1, %2, %3, %4, %5, %6, %7, %8, %9, %10, %11, %12, %13, %14, %15, %16, %17, %18, %19, %20, %21, %22, %23, %24, %25, %26, %27, %28, %29, %30, %31, %32, %33, %34, %35, %36, %37, %38, %39, %40, %41, %42, %43, %44, %45, %46, %47, %48, %49, %50, %51, %52, %53, %54, %55, %56, %57, %58, %59, %60, %61, %62, %63, %64, %65, %66, %67, %68, %69, %70, %71, %72, %73, %74, %75, %76, %77, %78, %79, %80, %81, %82, %83, %84, %85, %86, %87, %88, %89, %90, %91, %92, %93, %94, %95}, ta, tb, p1, 1, 1, 0, 1;\n"
        "add.s64 tb, tb0, 640;\n"
        "add.s64 ta, ta0, 1028;\n"
        "wgmma.mma_async.sync.aligned.m64n192k16.f32.bf16.bf16 {%0, %1, %2, %3, %4, %5, %6, %7, %8, %9, %10, %11, %12, %13, %14, %15, %16, %17, %18, %19, %20, %21, %22, %23, %24, %25, %26, %27, %28, %29, %30, %31, %32, %33, %34, %35, %36, %37, %38, %39, %40, %41, %42, %43, %44, %45, %46, %47, %48, %49, %50, %51, %52, %53, %54, %55, %56, %57, %58, %59, %60, %61, %62, %63, %64, %65, %66, %67, %68, %69, %70, %71, %72, %73, %74, %75, %76, %77, %78, %79, %80, %81, %82, %83, %84, %85, %86, %87, %88, %89, %90, %91, %92, %93, %94, %95}, ta, tb, p1, 1, 1, 0, 1;\n"
        "add.s64 tb, tb0, 704;\n"
        "add.s64 ta, ta0, 1030;\n"
        "wgmma.mma_async.sync.aligned.m64n192k16.f32.bf16.bf16 {%0, %1, %2, %3, %4, %5, %6, %7, %8, %9, %10, %11, %12, %13, %14, %15, %16, %17, %18, %19, %20, %21, %22, %23, %24, %25, %26, %27, %28, %29, %30, %31, %32, %33, %34, %35, %36, %37, %38, %39, %40, %41, %42, %43, %44, %45, %46, %47, %48, %49, %50, %51, %52, %53, %54, %55, %56, %57, %58, %59, %60, %61, %62, %63, %64, %65, %66, %67, %68, %69, %70, %71, %72, %73, %74, %75, %76, %77, %78, %79, %80, %81, %82, %83, %84, %85, %86, %87, %88, %89, %90, %91, %92, %93, %94, %95}, ta, tb, p1, 1, 1, 0, 1;\n"
        "}\n"
        : "+f"(d[0]), "+f"(d[1]), "+f"(d[2]), "+f"(d[3]), "+f"(d[4]), "+f"(d[5]), "+f"(d[6]), "+f"(d[7]), "+f"(d[8]), "+f"(d[9]), "+f"(d[10]), "+f"(d[11]), "+f"(d[12]), "+f"(d[13]), "+f"(d[14]), "+f"(d[15]), "+f"(d[16]), "+f"(d[17]), "+f"(d[18]), "+f"(d[19]), "+f"(d[20]), "+f"(d[21]), "+f"(d[22]), "+f"(d[23]), "+f"(d[24]), "+f"(d[25]), "+f"(d[26]), "+f"(d[27]), "+f"(d[28]), "+f"(d[29]), "+f"(d[30]), "+f"(d[31]), "+f"(d[32]), "+f"(d[33]), "+f"(d[34]), "+f"(d[35]), "+f"(d[36]), "+f"(d[37]), "+f"(d[38]), "+f"(d[39]), "+f"(d[40]), "+f"(d[41]), "+f"(d[42]), "+f"(d[43]), "+f"(d[44]), "+f"(d[45]), "+f"(d[46]), "+f"(d[47]), "+f"(d[48]), "+f"(d[49]), "+f"(d[50]), "+f"(d[51]), "+f"(d[52]), "+f"(d[53]), "+f"(d[54]), "+f"(d[55]), "+f"(d[56]), "+f"(d[57]), "+f"(d[58]), "+f"(d[59]), "+f"(d[60]), "+f"(d[61]), "+f"(d[62]), "+f"(d[63]), "+f"(d[64]), "+f"(d[65]), "+f"(d[66]), "+f"(d[67]), "+f"(d[68]), "+f"(d[69]), "+f"(d[70]), "+f"(d[71]), "+f"(d[72]), "+f"(d[73]), "+f"(d[74]), "+f"(d[75]), "+f"(d[76]), "+f"(d[77]), "+f"(d[78]), "+f"(d[79]), "+f"(d[80]), "+f"(d[81]), "+f"(d[82]), "+f"(d[83]), "+f"(d[84]), "+f"(d[85]), "+f"(d[86]), "+f"(d[87]), "+f"(d[88]), "+f"(d[89]), "+f"(d[90]), "+f"(d[91]), "+f"(d[92]), "+f"(d[93]), "+f"(d[94]), "+f"(d[95])
        : "l"(descA), "n"(AOFF >> 4), "l"(descB), "n"(BOFF >> 4));
}

struct Params {
    const __nv_bfloat16* x;
    const __nv_bfloat16* wqkv;
    const __nv_bfloat16* wo;
    const __nv_bfloat16* logit_scale;
    const __nv_bfloat16* cpb_w1;
    const __nv_bfloat16* cpb_w2;
    const __nv_bfloat16* rel_coords;
    const int*           rel_idx;
    const __nv_bfloat16* mask;
    __nv_bfloat16*       out;
    unsigned long long   z1;
    int                  npair;
    uint32_t             need;
    int                  nq, nr;
    int                  t1;
};

__device__ __forceinline__ void finish(uint32_t total) {
    __threadfence();
    if (atomicAdd(&g_done, 1u) == total - 1) {
        for (int i = 0; i < NWS; i++) g_cnt[i] = 0;
        g_done = 0;
    }
}

__global__ void __launch_bounds__(NTHREADS, 1)
swin_window_attn_kernel(const Params P, const __grid_constant__ CUtensorMap xmap, const __grid_constant__ CUtensorMap xmap4,
                        const __grid_constant__ CUtensorMap xmap3,
                        const __grid_constant__ CUtensorMap omap, const __grid_constant__ CUtensorMap wmap,
                        const __grid_constant__ CUtensorMap smap, const __grid_constant__ CUtensorMap omapb,
                        const __grid_constant__ CUtensorMap xmapa, const __grid_constant__ CUtensorMap xmapb,
                        const __grid_constant__ CUtensorMap smap3, const __grid_constant__ CUtensorMap wraw) {
    extern __shared__ __align__(1024) uint8_t smem[];
    constexpr uint32_t sbase = 1024;
    if (smem_u32(smem) != sbase) return;
    const int tid = threadIdx.x;
    const int wg = __shfl_sync(0xffffffffu, tid >> 7, 0);
    const int warp = __shfl_sync(0xffffffffu, (tid >> 5) & 3, 0);
    const int lane = tid & 31;
    const int g = lane >> 2, c = lane & 3;

    TR(26, wg);
    const bool attn = (int)blockIdx.x < 2 * P.npair;
    const int pair = blockIdx.x >> 1, half = blockIdx.x & 1;
    const int nwin = P.nq + (pair < P.nr ? 1 : 0);
    const int ntiles = (nwin * TOK + 63) >> 6;
    const uint32_t bars = sbase + SM_BAR;
    const int t0 = min(warp * 16 + g, TOK - 1), t1 = min(warp * 16 + g + 8, TOK - 1);
    int ridx[26];
    uint32_t rc, w2[16];
    uint4 w1[4];
    if (attn && (wg == 1 || wg == 2)) {
        rc = reinterpret_cast<const uint32_t*>(P.rel_coords)[min(tid - 128, 168)];
#pragma unroll
        for (int i = 0; i < 4; i++) w1[i] = reinterpret_cast<const uint4*>(P.cpb_w1)[i];
#pragma unroll
        for (int u = 0; u < 16; u++) w2[u] = reinterpret_cast<const uint32_t*>(P.cpb_w2)[2 * u + half];
#pragma unroll
        for (int rh = 0; rh < 2; rh++) {
            const int* ri = P.rel_idx + (rh ? t1 : t0) * TOK;
#pragma unroll
            for (int j = 0; j < 12; j++) ridx[13 * rh + j] = ri[8 * (j >> 1) + 2 * c + (j & 1)];
            ridx[13 * rh + 12] = ri[48];
        }
    }
    {
        if (tid == 416) {
            const CUtensorMap* maps[4] = {attn ? &smap : &omap, &smap3, &xmapa, &xmapb};
#pragma unroll
            for (int i = 0; i < 4; i++) asm volatile("prefetch.tensormap [%0];\n" :: "l"(reinterpret_cast<uint64_t>(maps[i])) : "memory");
        }
        if (tid == 384) {
            for (int b = 0; b < 4; b++) {
                mbar_init(bars + B_XFULL + b * 8, 2);
                mbar_init(bars + B_QKRAW + b * 8, 4);
                mbar_init(bars + B_VRAW + b * 8, 4);
                mbar_init(bars + B_VFREE + b * 8, 2);
                mbar_init(bars + B_QKFREE + b * 8, 4);
                mbar_init(bars + B_ODONE + b * 8, 4);
            }
            mbar_init(bars + B_MFULL, 1);
            mbar_init(bars + B_MFULL + 8, 1);
            mbar_init(bars + B_MCONS, 4);
            mbar_init(bars + B_WFULL, 2);
            mbar_init(bars + B_WRAW, 1);
            for (int b = 0; b < 4; b++) mbar_init(bars + B_STORED + b * 8, 1);
            for (int b = 0; b < 6; b++) {
                mbar_init(sbase + SM_PBAR + b * 8, 1);
                mbar_init(sbase + SM_PBAR + 48 + b * 8, PSTORE ? 1 : 4);
                mbar_init(sbase + SM_PBAR + 104 + b * 8, 4);
            }
            mbar_init(sbase + SM_PBAR + 96, 13);
            asm volatile("fence.mbarrier_init.release.cluster;\n" ::: "memory");
        }
        if (wg == 3) {
            if (attn) *reinterpret_cast<uint4*>(smem + SM_V + warp * V_STRIDE + (lane < 16 ? lane * 16 : V_STRIDE - 64 + (lane & 3) * 16)) = make_uint4(0, 0, 0, 0);
            fence_async_smem();
        }
        __syncthreads();
        TR(26, 4 + wg);
            if (attn && tid == 0) {
                mbar_arrive_expect_tx(bars + B_WRAW, 2 * 192 * O_PITCH);
#pragma unroll
                for (int i = 0; i < 4; i++) {
                    const int q = (i + pair) & 3;
                    tma_3d(sbase + q * 96 * O_PITCH, &wraw, bars + B_WRAW, 0, 2 * (q >> 1) + half, (q & 1) * 96);
                }
                int wh = 0, ww = pair;
#pragma unroll
                for (int j = 0; j < NEARLY; j++) {
                    if (ww < NWS - 1) {
                        const uint32_t bar = bars + B_XFULL + (j ? j - 1 : 0) * 8;
                        if (j >= 2) mbar_arrive(bar);
                        mbar_arrive_expect_tx(bar, 3 * XCH);
#pragma unroll
                        for (int ch = 0; ch < 3; ch++)
                            tma_3d(sbase + SM_QK + j * XCH + ch * QK_CHUNK, &xmap, bar, ch * 64, 7 * ww + 3, 7 * wh + 3);
                    }
                    ww += P.npair; if (ww >= NWS) { ww -= NWS; wh++; }
                    if (j == 1) {
                        mbar_arrive_expect_tx(bars + B_MFULL, 4816);
                        asm volatile("cp.async.bulk.shared::cluster.global.mbarrier::complete_tx::bytes [%0], [%1], 4816, [%2];\n"
                                     :: "r"(sbase + SM_MASK), "l"(reinterpret_cast<const char*>(P.mask) + (((uint32_t)pair * 4802u) & ~15u)),
                                        "r"(bars + B_MFULL) : "memory");
                        mbar_arrive_expect_tx(bars + B_WFULL, 5 * W_ATOM);
#pragma unroll
                        for (int a = 1; a < 6; a++)
                            tma_2d(sbase + SM_WV + a * W_ATOM, &wmap, bars + B_WFULL, 384 + half * 96 + a * 16, 0);
                    }
                }
            }
        __syncwarp();
        TR(26, 13);
    }

    auto permute_w = [&]() {
        uint4 w[3][4];
        TR(26, 16 + wg);
        mbar_wait(bars + B_WRAW, 0);
        TR(26, 20 + wg);
#pragma unroll
        for (int it = 0; it < 3; it++) {
            const int o = ((tid >> 5) * 3 + it) * 4 + (lane >> 3);
            const uint8_t* src = smem + ((o / 6) * 8 + (lane & 7)) * O_PITCH + (o % 6) * 16;
#pragma unroll
            for (int m = 0; m < 4; m++) w[it][m] = *reinterpret_cast<const uint4*>(src + (m >> 1) * 192 * O_PITCH + (m & 1) * 96);
        }
        asm volatile("bar.sync 2, 384;\n" ::: "memory");
        if (tid == 0) {
            fence_async_smem();
            TR(26, 24);
            mbar_arrive_expect_tx(bars + B_WFULL, W_ATOM);
            tma_2d(sbase + SM_WV, &wmap, bars + B_WFULL, 384 + half * 96, 0);
        }
#pragma unroll
        for (int it = 0; it < 3; it++) {
            const int o = ((tid >> 5) * 3 + it) * 4 + (lane >> 3);
            const uint32_t d = sbase + (o % 6) * 2 * W_ATOM + ((o / 6) * 8 + (lane & 7)) * 32 + ((lane >> 2) & 1) * 16;
            sts128(d, w[it][0].x, w[it][1].x, w[it][2].x, w[it][3].x);
            sts128(d ^ 16, w[it][0].y, w[it][1].y, w[it][2].y, w[it][3].y);
            sts128(d + W_ATOM, w[it][0].z, w[it][1].z, w[it][2].z, w[it][3].z);
            sts128((d ^ 16) + W_ATOM, w[it][0].w, w[it][1].w, w[it][2].w, w[it][3].w);
        }
    };
    static_assert(2 * 192 * O_PITCH <= 13 * W_ATOM, "raw weights");
    const uint32_t nfinish = gridDim.x + 2 * P.npair;
#define PROJ_SCHEDULE                                                                                   \
    int bid = blockIdx.x;                                                                               \
    asm volatile("" : "+r"(bid));                      \
    const bool at = bid < 2 * P.npair;                                                                  \
    const int tile0 = at ? P.t1 + bid : bid - 2 * P.npair;                                              \
    const int tstep = at ? 2 * P.npair : (int)gridDim.x - 2 * P.npair;                                  \
    const int tend = at ? TILES : P.t1;
    if (wg == 3) {
        asm volatile("setmaxnreg.dec.sync.aligned.u32 %0;\n" :: "n"(REG_H));
        if (!elect_one()) return;
        if (warp == 0) {
          if (attn) {
            const int kmax = (64 * ntiles + 63) / TOK;
            int wh = 0, ww = pair;
            int ph2 = (pair + PF_DIST * P.npair) / NWS, pw2 = pair + PF_DIST * P.npair - ph2 * NWS;
#pragma unroll 1
            for (int k = -4; k + 4 <= kmax; k++) {
                const int row0 = (k + 4) * TOK;
                const uint32_t dst = sbase + SM_QK + (k & 3) * XCH, bar = bars + B_XFULL + ((row0 >> 6) & 3) * 8;
                const bool alone = (row0 & 63) >= 64 - TOK && (row0 & 63) < TOK;
                const int x0 = 7 * ww + 3, y0 = 7 * wh + 3;
                const bool done = k < NEARLY - 4 && ww < NWS - 1;
                mbar_wait(bars + B_QKFREE + (k & 3) * 8, (k >> 2) & 1);
                if (alone && !done) mbar_arrive(bar);
                if (k + 4 >= nwin) {
                    mbar_arrive(bar);
                    continue;
                }
                TR(20, k + 4);
                const bool inner = wh < NWS - 1 && ww < NWS - 1;
                if (done) {
                } else if (XSPLIT && inner && (row0 & 63) >= 64 - 21) {
                    const uint32_t bar2 = bars + B_XFULL + (((row0 >> 6) + 1) & 3) * 8;
                    mbar_arrive_expect_tx(bar, 3 * 21 * 128);
#pragma unroll
                    for (int ch = 0; ch < 3; ch++) tma_3d(dst + ch * QK_CHUNK, &xmapa, bar, ch * 64, x0, y0);
                    asm volatile("mbarrier.expect_tx.relaxed.cta.shared::cta.b64 [%0], %1;\n" :: "r"(bar2), "r"(3 * 28 * 128) : "memory");
#pragma unroll
                    for (int ch = 0; ch < 3; ch++) tma_3d(dst + ch * QK_CHUNK + 21 * 128, &xmapb, bar2, ch * 64, x0, y0 + 3);
                } else if (inner) {
                    mbar_arrive_expect_tx(bar, 3 * XCH);
#pragma unroll
                    for (int ch = 0; ch < 3; ch++) tma_3d(dst + ch * QK_CHUNK, &xmap, bar, ch * 64, x0, y0);
                } else if (ww < NWS - 1) {
                    mbar_arrive_expect_tx(bar, 3 * XCH);
#pragma unroll
                    for (int ch = 0; ch < 3; ch++) {
                        tma_3d(dst + ch * QK_CHUNK, &xmapb, bar, ch * 64, x0, y0);
                        tma_3d(dst + ch * QK_CHUNK + 28 * 128, &xmapa, bar, ch * 64, x0, 0);
                    }
                } else {
                    mbar_arrive_expect_tx(bar, 3 * XCH);
                    const int x1 = (ww == NWS - 1) ? 0 : x0 + 4;
#pragma unroll 1
                    for (int i = 0; i < 7; i++) {
                        const int y = (y0 + i >= IMG) ? y0 + i - IMG : y0 + i;
#pragma unroll
                        for (int ch = 0; ch < 3; ch++) {
                            tma_3d(dst + ch * QK_CHUNK + i * 896, &xmap4, bar, ch * 64, x0, y);
                            tma_3d(dst + ch * QK_CHUNK + i * 896 + 512, &xmap3, bar, ch * 64, x1, y);
                        }
                    }
                }
                if (NOPF) {
                } else if (half == 0) {
                    if (ph2 < NWS) {
#pragma unroll
                        for (int ch = 0; ch < 3; ch++)
                            asm volatile("cp.async.bulk.prefetch.tensor.3d.L2.global.tile [%0, {%1, %2, %3}];\n"
                                         :: "l"(reinterpret_cast<uint64_t>(&xmap)), "r"(ch * 64), "r"(7 * pw2 + 3), "r"(7 * ph2 + 3)
                                         : "memory");
                    }
                } else if (ph2 < NWS) {
                    asm volatile("cp.async.bulk.prefetch.L2.global [%0], %1;\n"
                                 :: "l"(reinterpret_cast<const char*>(P.mask) + (((uint32_t)(ph2 * NWS + pw2) * 4802u) & ~15u)),
                                    "r"(4800) : "memory");
                }
                ww += P.npair; if (ww >= NWS) { ww -= NWS; wh++; }
                pw2 += P.npair; if (pw2 >= NWS) { pw2 -= NWS; ph2++; }
            }
            mbar_wait(sbase + SM_PBAR + 96, 0);
            fence_async_smem();
          }
            PROJ_SCHEDULE
            int st = 0, ready = -1;
            uint32_t ph = 1;
#pragma unroll 1
            for (int t = tile0; t < tend; t += tstep) {
                const int p0 = (t < TILES_A) ? SEG_B + 64 * t : 64 * (t - TILES_A);
                const int w1 = (t < TILES_A) ? min((64 * t + 63) / (7 * IMG), NWS - 1) : NWS - 1;
                if (ready < w1) {
                    ready = max(ready, w1 - 2);
#pragma unroll 1
                    while (ready < w1) {
                        ready++;
#pragma unroll 1
                        for (uint32_t n = 0; n < (1u << 22); n++) {
                            uint32_t a;
                            asm volatile("ld.acquire.gpu.global.u32 %0, [%1];\n" : "=r"(a) : "l"(g_cnt + ready) : "memory");
                            if (a >= P.need) break;
                            __nanosleep(64);
                        }
                    }
                    asm volatile("fence.proxy.async.global;\n" ::: "memory");
                }
                mbar_wait(sbase + SM_PBAR + 48 + st * 8, ph);
                mbar_arrive_expect_tx(sbase + SM_PBAR + st * 8, STAGE_BYTES);
#pragma unroll
                for (int ch = 0; ch < 3; ch++)
                    tma_2d(sbase + SM_STAGE + st * STAGE_BYTES + ch * 8192, &omap, sbase + SM_PBAR + st * 8, ch * 64, p0);
                if (++st == 6) { st = 0; ph ^= 1; }
            }
            finish(nfinish);
        } else if (!attn) {
        } else if (warp == 1) {
          {
            const uint16_t mlast = reinterpret_cast<const uint16_t*>(P.mask)[NWINDOWS * TOK * TOK - 1];
            auto load_mask = [&](int k) {
                const int win = pair + k * P.npair;
                uint32_t bytes = 4816;
                if (win == NWINDOWS - 1) {
                    bytes = 4800;
                    asm volatile("st.shared.u16 [%0], %1;\n" :: "r"(sbase + SM_MASK + 4800), "h"(mlast) : "memory");
                }
                TR(25, k);
                mbar_arrive_expect_tx(bars + B_MFULL + (k & 1) * 8, bytes);
                asm volatile("cp.async.bulk.shared::cluster.global.mbarrier::complete_tx::bytes [%0], [%1], %2, [%3];\n"
                             :: "r"(sbase + SM_MASK),
                                "l"(reinterpret_cast<const char*>(P.mask) + (((uint32_t)win * 4802u) & ~15u)),
                                "r"(bytes), "r"(bars + B_MFULL + (k & 1) * 8) : "memory");
            };
#pragma unroll 1
            for (int k = 1; k < nwin; k++) {
                mbar_wait(bars + B_MCONS, (k + 1) & 1);
                fence_async_smem();
                load_mask(k);
            }
          }
        } else if (warp == 2) {
            int wh = 0, ww = pair;
#pragma unroll 1
            for (int k = 0; k < nwin; k++) {
                mbar_wait(bars + B_STORED + (k & 1) * 8, (k >> 1) & 1);
                mbar_arrive(bars + B_PUBD + (k & 1) * 8);
                asm volatile("red.release.gpu.global.add.u32 [%0], 1;\n" :: "l"(g_cnt + wh) : "memory");
                TR(24, k);
                ww += P.npair; if (ww >= NWS) { ww -= NWS; wh++; }
            }
            finish(nfinish);
        } else {
            for (int t = 0; t < 3; t++) mbar_arrive_n(bars + B_VFREE + t * 8, 2);
            int wh = 0, ww = pair;
#pragma unroll 1
            for (int k = 0; k < nwin; k++) {
                const uint32_t src = sbase + SM_V + (k & 3) * V_STRIDE;
                const int x0 = 7 * ww + 3, y0 = 7 * wh + 3;
                mbar_wait(bars + B_ODONE + (k & 3) * 8, (k >> 2) & 1);
                fence_async_smem();
                TR(22, k);
                tma_store_4d(&smap, src, 0, half, x0, y0);
                tma_store_4d(&smap3, src + 28 * O_PITCH + 64, 0, half, x0, wh == NWS - 1 ? 0 : y0 + 4);
                if (ww == NWS - 1) {
#pragma unroll 1
                    for (int i = 0; i < 7; i++) {
                        char* const d = reinterpret_cast<char*>(P.out) + (uint32_t)((y0 + i >= IMG ? y0 + i - IMG : y0 + i) * IMG) * 384u + half * 192;
#pragma unroll
                        for (int j = 0; j < 3; j++)
                            asm volatile("cp.async.bulk.global.shared::cta.bulk_group [%0], [%1], 192;\n"
                                         :: "l"(d + j * 384), "r"(src + (7 * i + 4 + j) * O_PITCH + (i >= 4 ? 64 : 0)) : "memory");
                    }
                }
                asm volatile("cp.async.bulk.commit_group;\n" ::: "memory");
                asm volatile("cp.async.bulk.wait_group.read 0;\n" ::: "memory");
                {
                    const int row0 = (k + 4) * TOK;
                    mbar_arrive_n(bars + B_VFREE + ((row0 >> 6) & 3) * 8, ((row0 & 63) >= 64 - TOK && (row0 & 63) < TOK) ? 2 : 1);
                }
                TR(23, k);
                asm volatile("cp.async.bulk.wait_group 0;\n" ::: "memory");
                asm volatile("fence.proxy.async.global;\n" ::: "memory");
                mbar_wait(bars + B_PUBD + (k & 1) * 8, ((k >> 1) + 1) & 1);
                mbar_arrive(bars + B_STORED + (k & 1) * 8);
                ww += P.npair; if (ww >= NWS) { ww -= NWS; wh++; }
            }
            mbar_arrive(sbase + SM_PBAR + 96);
        }
        if (PSTORE && warp == 1) {
            PROJ_SCHEDULE
            int st = 0, prev = -1;
            uint32_t ph = 0;
#pragma unroll 1
            for (int t = tile0; t < tend; t += tstep) {
                const int p0 = (t < TILES_A) ? SEG_B + 64 * t : 64 * (t - TILES_A);
                mbar_wait(sbase + SM_PBAR + 104 + st * 8, ph);
                fence_async_smem();
#pragma unroll
                for (int ch = 0; ch < 3; ch++)
                    asm volatile("cp.async.bulk.tensor.2d.global.shared::cta.tile.bulk_group [%0, {%2, %3}], [%1];\n"
                                 :: "l"(reinterpret_cast<uint64_t>(t < TILES_A ? &omap : &omapb)),
                                    "r"(sbase + SM_STAGE + st * STAGE_BYTES + ch * 8192), "r"(ch * 64), "r"(p0) : "memory");
                asm volatile("cp.async.bulk.commit_group;\n" ::: "memory");
                if (prev >= 0) {
                    asm volatile("cp.async.bulk.wait_group.read 1;\n" ::: "memory");
                    mbar_arrive(sbase + SM_PBAR + 48 + prev * 8);
                }
                prev = st;
                if (++st == 6) { st = 0; ph ^= 1; }
            }
            asm volatile("cp.async.bulk.wait_group 0;\n" ::: "memory");
            TR(30, 0);
        }
        return;
    }
    if (!attn) {
        asm volatile("setmaxnreg.inc.sync.aligned.u32 160;\n");
    } else if (wg == 0) {
        asm volatile("setmaxnreg.inc.sync.aligned.u32 %0;\n" :: "n"(REG_G));
        float qs = 1.f;
        if (c < 2) qs = round_bf16(expf(round_bf16(fminf(fmaxf(__bfloat162float(P.logit_scale[2 * half + c]), -100.f), 4.6052f))));
        uint32_t xa[12][4];
        float accA[48], accB[48];
#pragma unroll
        for (int i = 0; i < 48; i++) { accA[i] = 0.f; accB[i] = 0.f; }
        uint32_t rho = warp * 16 + (lane & 15), rq = warp * 16 + g;
        uint32_t hi = lane >> 4, lane0 = lane == 0, c2 = 2 * c;
        asm volatile("" : "+r"(hi), "+r"(lane0), "+r"(c2));
        auto row_addr = [&](uint32_t (&ax)[4], uint32_t r) {
            ax[0] = sbase + SM_QK + r * 128 + (((r & 7) ^ hi) << 4);
#pragma unroll
            for (int i = 1; i < 4; i++) ax[i] = ax[0] ^ (32 * i);
        };
#define XADDR(ax, s) ((ax)[((s) & 3) ^ (((s) >> 1) & 2)] + ((s) >> 2) * QK_CHUNK)
        uint64_t descW = make_desc(sbase, W_ATOM, 256, 3);
        const uint32_t zero = (uint32_t)P.z1;
        const uint32_t vbase = sbase + SM_V + (lane >> 4) * GRP;
        uint32_t ones = 0x3F803F80u | zero, ones2 = ones | (zero >> 1);
        asm volatile("" : "+r"(ones), "+r"(ones2));
        permute_w();
        TR(26, 10);
        {
            uint32_t ax[4];
            row_addr(ax, rho);
            mbar_wait(bars + B_XFULL, 0);
#pragma unroll
            for (int s = 0; s < 12; s++) ldsm_x4(xa[s], XADDR(ax, s));
        }
        TR(26, 8);
        asm volatile("bar.sync 7, 384;\n" ::: "memory");
        fence_async_smem();
        TR(26, 9);
        wgmma_fence();
        mma_qkv_a<SM_WA, 0>(accA, xa, descW);
        mma_qkv_b<SM_WA, 6>(accA, xa, descW);
        wgmma_commit();
        mma_qkv_a<SM_WB, 0>(accB, xa, descW);
        wgmma_commit();
        TR(26, 11);
        mbar_wait(bars + B_WFULL, 0);
        TR(26, 12);
        for (int t = 0; t < ntiles; t++) {
            descW += P.z1;
            float ss[4];
            uint32_t pk[2][24];
            wgmma_wait<1>();
            reg_fence(accA);
            TR(0, t);
#pragma unroll
            for (int i = 0; i < 4; i++) ss[i] = accA[i] * accA[i];
#pragma unroll
            for (int i = 4; i < 48; i++) ss[i & 3] = fmaf(accA[i], accA[i], ss[i & 3]);
            mma_qkv_b<SM_WB, 6>(accB, xa, descW);
            wgmma_commit();
            sched_fence(zero, __float_as_uint(ss[0]), __float_as_uint(ss[1]), __float_as_uint(ss[2]), __float_as_uint(ss[3]));
#pragma unroll
            for (int j = 0; j < 12; j++) {
                pk[0][j] = pack_bf16(accA[4 * j], accA[4 * j + 1]);
                pk[1][j] = pack_bf16(accA[4 * j + 2], accA[4 * j + 3]);
                asm volatile("" : "+r"(pk[0][j]), "+r"(pk[1][j]));
            }
            wgmma_fence();
            mma_qkv_a<SM_WV, 0>(accA, xa, descW);
            wgmma_commit();
            uint32_t av = vbase + rho * 16 + ((rho * 1338) >> 16) * (V_STRIDE - GRP);
            uint32_t aq[2];
            aq[0] = sbase + SM_QK + rq * 128 + (((rq & 7) ^ c2) << 4);
            aq[1] = aq[0] + 1024;
            if (rq >= 4 * TOK - 8) aq[1] = (aq[1] - QK_CHUNK) ^ 64;
            rho += 64;
            if (rho >= 4 * TOK) rho -= 4 * TOK;
            rq += 64;
            if (rq >= 4 * TOK) rq -= 4 * TOK;
            uint32_t an[4];
            row_addr(an, rho);
            const uint32_t bt = bars + (t & 3) * 8, pt = (t >> 2) & 1, bn = bars + ((t + 1) & 3) * 8, pn = ((t + 1) >> 2) & 1;
            const uint32_t xok = mbar_test(bn + B_XFULL, pn);
            wgmma_wait<1>();
            reg_fence(accB);
#pragma unroll
            for (int i = 0; i < 48; i++) ss[i & 3] = fmaf(accB[i], accB[i], ss[i & 3]);
            ss[0] += ss[1]; ss[2] += ss[3];
            mma_qkv_b<SM_WV, 6>(accA, xa, descW);
            wgmma_commit();
            sched_fence(zero, __float_as_uint(ss[0]), __float_as_uint(ss[2]), av, aq[0], aq[1], an[0], an[1], an[2], an[3], rho, rq);
            const float f0 = rsqrt_ftz(ss[0] + 1e-12f) * qs, f1 = rsqrt_ftz(ss[2] + 1e-12f) * qs;
            const uint32_t f2[2] = {pack_bf16(f0, f0), pack_bf16(f1, f1)};
#pragma unroll
            for (int j = 0; j < 12; j++) {
                pk[0][12 + j] = pack_bf16(accB[4 * j], accB[4 * j + 1]);
                pk[1][12 + j] = pack_bf16(accB[4 * j + 2], accB[4 * j + 3]);
            }
            auto qk_store = [&](int u0, int u1) {
#pragma unroll
                for (int u = u0; u < u1; u++)
#pragma unroll
                    for (int r = 0; r < 2; r++)
                        sts128((aq[r] ^ ((u & 1) * 16 + (u & 2) * 32)) + (u >> 1) * QK_CHUNK,
                               hmul2_bf16(pk[r][4 * u], f2[r]), hmul2_bf16(pk[r][4 * u + 1], f2[r]),
                               hmul2_bf16(pk[r][4 * u + 2], f2[r]), hmul2_bf16(pk[r][4 * u + 3], f2[r]));
            };
            qk_store(0, QSPLIT);
            TR(1, t);
            mbar_wait_unless(xok, bn + B_XFULL, pn);
            TR(2, t);
            wgmma_wait<0>();
            reg_fence(accA);
#pragma unroll
            for (int s = 0; s < 12; s++) ldsm_x4(xa[s], XADDR(an, s));
            const uint32_t vok = mbar_test(bt + B_VFREE, pt);
            qk_store(QSPLIT, 6);
            __syncwarp();
            mbar_arrive_if(bt + B_QKRAW, lane0);
            TR(3, t);
            uint32_t vp[24];
#pragma unroll
            for (int j = 0; j < 24; j++) vp[j] = pack_bf16(accA[2 * j], accA[2 * j + 1]);
            reg_fence(vp);
            wgmma_fence();
            mma_qkv_a<SM_WA, 0>(accA, xa, descW);
            mma_qkv_b<SM_WA, 6>(accA, xa, descW);
            wgmma_commit();
            mbar_wait_unless(vok, bt + B_VFREE, pt);
            if (t == 2) asm volatile("bar.sync 3, 384;\n" ::: "memory");
#pragma unroll
            for (int p = 0; p < 6; p++)
                stsm_x4(av + (p < 3 ? 2 * p : 2 * p + 1) * GRP, vp[4 * p], vp[4 * p + 1], vp[4 * p + 2], vp[4 * p + 3]);
            stsm_x2(av + 6 * GRP, ones, ones2);
            __syncwarp();
            mbar_arrive_if(bt + B_VRAW, lane0);
            TR(4, t);
            wgmma_fence();
            mma_qkv_a<SM_WB, 0>(accB, xa, descW);
            wgmma_commit();
        }
        wgmma_wait<0>();
        reg_fence(accA);
        reg_fence(accB);
        wg_bar(2);
        asm volatile("setmaxnreg.dec.sync.aligned.u32 160;\n");
    } else {
        if (REG_A > 128) asm volatile("setmaxnreg.inc.sync.aligned.u32 %0;\n" :: "n"(REG_A));
        {
            const float c0 = bf16lo(rc), c1 = bf16hi(rc);
            float a0 = 0.f, a1 = 0.f;
#pragma unroll
            for (int u = 0; u < 16; u++) {
                const uint32_t p = reinterpret_cast<const uint32_t*>(w1)[u >> 1], q = reinterpret_cast<const uint32_t*>(w1)[8 + (u >> 1)];
                float h = round_bf16(c0 * ((u & 1) ? bf16hi(p) : bf16lo(p)) + c1 * ((u & 1) ? bf16hi(q) : bf16lo(q)));
                h = fmaxf(h, 0.f);
                a0 += h * bf16lo(w2[u]);
                a1 += h * bf16hi(w2[u]);
            }
            const float s0 = round_bf16(__fdividef(1.f, 1.f + expf(-round_bf16(a0))));
            const float s1 = round_bf16(__fdividef(1.f, 1.f + expf(-round_bf16(a1))));
            if (tid - 128 < 169) sts32(sbase + SM_TAB + (tid - 128) * 4, pack_bf16(16.f * s0, 16.f * s1));
        }
        permute_w();
        asm volatile("bar.arrive 7, 384;\n" ::: "memory");
        asm volatile("bar.sync 1, 256;\n" ::: "memory");
        uint32_t bias[28];
        {
            const uint32_t* tab = reinterpret_cast<const uint32_t*>(smem + SM_TAB);
#pragma unroll
            for (int rh = 0; rh < 2; rh++) {
#pragma unroll
                for (int j = 0; j < 6; j++) {
                    const uint32_t lo = tab[min(max(ridx[13 * rh + 2 * j], 0), 168)];
                    const uint32_t hi = tab[min(max(ridx[13 * rh + 2 * j + 1], 0), 168)];
                    bias[2 * j + rh]      = prmt(lo, hi, 0x5410);
                    bias[14 + 2 * j + rh] = prmt(lo, hi, 0x7632);
                }
                const uint32_t l = (c == 0) ? tab[min(max(ridx[13 * rh + 12], 0), 168)] : 0xFF80FF80u;
                bias[12 + rh] = (l & 0xFFFFu) | 0xFF800000u;
                bias[26 + rh] = (l >> 16) | 0xFF800000u;
            }
        }
        reg_fence(bias);
        asm volatile("bar.arrive 3, 384;\n" ::: "memory");
        const bool ov = warp * 16 + (lane & 15) < TOK;
        const int orow = warp * 16 + (lane & 15);
        const uint32_t orel = sbase + (ov ? SM_V + orow * O_PITCH + (orow >= 28 ? 64 : 0) : SM_DUMP + (lane & 7) * 16) + (lane >> 4) * 16;
        const uint32_t omul = ov ? V_STRIDE : 0;
        uint32_t mdelta = 2 * (pair + (wg - 1) * P.npair);
        const uint64_t descK0 = make_desc(sbase + SM_QK, 16, 1024, 1);
        const uint64_t descV0 = make_desc(sbase + SM_V, 128, GRP, 0);
        const uint32_t mrel = (sbase + SM_MASK + t0 * 98 + c * 4 + (mdelta & 2)) & ~3u;
        const uint32_t msel = ((t0 * 98 + mdelta) & 2) ? 0x5432u : 0x3210u;
        const uint32_t mrow = (warp < 3) ? 784 : 0;
        const uint32_t pmask = (c == 0) ? 0xFFFFu : 0u;

        uint32_t mk[14];
        auto align_mask = [&](const uint32_t (&mw)[26]) {
#pragma unroll
            for (int i = 0; i < 14; i++) mk[i] = prmt(mw[i], i < 12 ? mw[14 + i] : 0u, msel);
        };
        auto load_mask = [&](uint32_t (&mw)[26]) {
            const uint32_t ma = mrel + (mdelta & 12);
#pragma unroll
            for (int i = 0; i < 14; i++) {
                mw[i] = lds32(ma + (i & 1) * mrow + (i >> 1) * 16);
                if (i < 12) mw[14 + i] = lds32(ma + (i & 1) * mrow + (i >> 1) * 16 + 4);
            }
            __syncwarp();
            if (lane == 0) mbar_arrive(bars + B_MCONS);
            mdelta += 4 * P.npair;
        };
        {
            uint32_t mw[26];
            mbar_wait(bars + B_MFULL + (wg - 1) * 8, 0);
            load_mask(mw);
            align_mask(mw);
        }
        const uint32_t barw = bars + (wg - 1) * 8;
        const uint64_t descKw = descK0 + (uint64_t)((wg - 1) * (XCH >> 4)), descVw = descV0 + (uint64_t)((wg - 1) * (V_STRIDE >> 4));
        uint32_t oa = orel + (wg - 1) * omul;
        const uint32_t oflip = oa ^ (oa + 2 * omul);
        uint32_t qok = 0;
        const uint32_t zero = (uint32_t)P.z1;
        auto window = [&](auto IT_, int k) {
            constexpr int IT = decltype(IT_)::value;
            const uint32_t bar = barw + 16 * IT;
            const int tl = (k * TOK + TOK - 1) >> 6, tn = ((k + 2) * TOK + TOK - 1) >> 6;
            const uint32_t bt = bars + (tl & 3) * 8, pt = (tl >> 2) & 1;
            TR(8, k);
            float sc0[28], sc1[28];
            auto init = [&](float (&S)[28], int h) {
#pragma unroll
                for (int i = 0; i < 14; i++) {
                    const uint32_t b = hadd2_bf16(bias[14 * h + i], mk[i]);
                    S[2 * i] = bf16lo(b);
                    S[2 * i + 1] = (i < 12) ? bf16hi(b) : 0.f;
                }
                reg_fence(S);
            };
            init(sc0, 0);
            init(sc1, 1);
            TR(10, k);
            mbar_wait_unless(qok, bt + B_QKRAW, pt);
            fence_async_smem();
            TR(11, k);
            wgmma_fence();
            mma_qk0<2 * IT * XCH, 2 * IT * XCH>(sc0, descKw, descKw);
            mma_qk1<2 * IT * XCH, 2 * IT * XCH>(sc1, descKw, descKw);
            wgmma_commit();
            const uint32_t mok = mbar_test(barw + B_MFULL, IT ^ 1) | (k + 2 >= nwin);
            const uint32_t vok = mbar_test(bt + B_VRAW, pt);
            float m[4];
            auto rowmax = [&](const float (&S)[28], int h) {
#pragma unroll
                for (int o = 0; o < 4; o += 2) {
                    float a = fmaxf(S[o], S[o + 1]), b = fmaxf(S[4 + o], S[5 + o]);
#pragma unroll
                    for (int j = 2; j < 6; j += 2) {
                        a = fmaxf(a, fmaxf(S[4 * j + o], S[4 * j + o + 1]));
                        b = fmaxf(b, fmaxf(S[4 * j + 4 + o], S[4 * j + 5 + o]));
                    }
                    m[2 * h + (o >> 1)] = fmaxf(fmaxf(a, b), S[24 + o]);
                }
            };
            wgmma_wait<0>();
            reg_fence(sc0);
            reg_fence(sc1);
            if (lane == 0) mbar_arrive(bar + B_QKFREE);
            TR(12, k);
            rowmax(sc0, 0);
            rowmax(sc1, 1);
#pragma unroll
            for (int i = 0; i < 4; i++) m[i] = fmaxf(m[i], __shfl_xor_sync(0xffffffffu, m[i], 1));
#pragma unroll
            for (int i = 0; i < 4; i++) m[i] = fmaxf(m[i], __shfl_xor_sync(0xffffffffu, m[i], 2)) * -LOG2E;
            auto probs = [&](const float (&S)[28], float m0, float m1, uint32_t (&pa)[4][4]) {
#pragma unroll
                for (int j = 0; j < 6; j++) {
                    pa[j >> 1][(j & 1) * 2]     = pack_bf16(ex2_ftz(fmaf(S[4 * j], LOG2E, m0)), ex2_ftz(fmaf(S[4 * j + 1], LOG2E, m0)));
                    pa[j >> 1][(j & 1) * 2 + 1] = pack_bf16(ex2_ftz(fmaf(S[4 * j + 2], LOG2E, m1)), ex2_ftz(fmaf(S[4 * j + 3], LOG2E, m1)));
                }
                pa[3][0] = pack_bf16(ex2_ftz(fmaf(S[24], LOG2E, m0)), 0.f) & pmask;
                pa[3][1] = pack_bf16(ex2_ftz(fmaf(S[26], LOG2E, m1)), 0.f) & pmask;
                pa[3][2] = 0u; pa[3][3] = 0u;
                reg_fence(pa);
            };
            uint32_t pa0[4][4], pa1[4][4];
            float o0[28], o1[28];
            TR(13, k);
            mbar_wait2_unless(vok & mok, bt + B_VRAW, pt, k + 2 < nwin ? barw + B_MFULL : bt + B_VRAW, k + 2 < nwin ? IT ^ 1 : pt);
            fence_async_smem();
            TR(14, k);
            uint32_t mw[26];
            load_mask(mw);
            probs(sc0, m[0], m[1], pa0);
            align_mask(mw);
            wgmma_fence();
            mma_pv<2 * IT * V_STRIDE, 0>(o0, pa0, descVw);
            wgmma_commit();
            probs(sc1, m[2], m[3], pa1);
            wgmma_fence();
            mma_pv<2 * IT * V_STRIDE + 6 * GRP, 0>(o1, pa1, descVw);
            wgmma_commit();
            uint32_t w[24];
            wgmma_wait<1>();
            reg_fence(o0);
            {
                const float il0 = rcp_ftz(o0[24]), il1 = rcp_ftz(o0[26]);
                const uint32_t l0 = pack_bf16(il0, il0), l1 = pack_bf16(il1, il1);
#pragma unroll
                for (int j = 0; j < 12; j++) w[j] = hmul2_bf16(pack_bf16(o0[2 * j], o0[2 * j + 1]), (j & 1) ? l1 : l0);
            }
            wgmma_wait<0>();
            reg_fence(o1);
            TR(15, k);
            asm volatile("{\n.reg .pred p;\nsetp.eq.u32 p, %0, 1;\n@p bar.sync 4, 128;\n@!p bar.sync 5, 128;\n}\n"
                         :: "r"(wg) : "memory");
            qok = mbar_test(bars + (tn & 3) * 8 + B_QKRAW, (tn >> 2) & 1);
            {
                const float il2 = rcp_ftz(o1[0]), il3 = rcp_ftz(o1[2]);
                const uint32_t l2 = pack_bf16(il2, il2), l3 = pack_bf16(il3, il3);
#pragma unroll
                for (int j = 0; j < 12; j++) w[12 + j] = hmul2_bf16(pack_bf16(o1[2 * j + 4], o1[2 * j + 5]), (j & 1) ? l3 : l2);
#pragma unroll
                for (int p = 0; p < 6; p++) stsm_x4(oa + p * 32, w[4 * p], w[4 * p + 1], w[4 * p + 2], w[4 * p + 3]);
            }
            __syncwarp();
            if (lane == 0) mbar_arrive(bar + B_ODONE);
            TR(16, k);
            oa ^= oflip;
            asm volatile("" : "+r"(oa));
        };
        for (int k = wg - 1;; k += 4) {
            window(std::integral_constant<int, 0>(), k);
            if (k + 2 >= nwin) break;
            window(std::integral_constant<int, 1>(), k + 2);
            if (k + 4 >= nwin) break;
        }
        (void)zero;
        asm volatile("setmaxnreg.inc.sync.aligned.u32 160;\n");
    }

    TR(27, wg);
    if (attn) {
        __syncwarp();
        if (lane == 0) mbar_arrive(sbase + SM_PBAR + 96);
    }
    if (!attn || wg == 0) {
#pragma unroll 3
        for (int row = tid >> 2; row < 192; row += attn ? 32 : 96) {
            uint4 w[6];
#pragma unroll
            for (int a = 0; a < 6; a++) w[a] = *reinterpret_cast<const uint4*>(P.wo + row * 192 + 32 * a + 8 * c);
            float s = 0.f;
#pragma unroll
            for (int a = 0; a < 6; a++)
                s += ((bf16lo(w[a].x) + bf16hi(w[a].x)) + (bf16lo(w[a].y) + bf16hi(w[a].y))) +
                     ((bf16lo(w[a].z) + bf16hi(w[a].z)) + (bf16lo(w[a].w) + bf16hi(w[a].w)));
            s += __shfl_xor_sync(0xffffffffu, s, 1);
            s += __shfl_xor_sync(0xffffffffu, s, 2);
            s *= (1.f / 192.f);
            const uint32_t d = sbase + SM_WO + row * 64 + ((c ^ ((row >> 1) & 3)) << 4);
#pragma unroll
            for (int a = 0; a < 6; a++)
                sts128(d + a * 12288, pack_bf16(bf16lo(w[a].x) - s, bf16hi(w[a].x) - s), pack_bf16(bf16lo(w[a].y) - s, bf16hi(w[a].y) - s),
                       pack_bf16(bf16lo(w[a].z) - s, bf16hi(w[a].z) - s), pack_bf16(bf16lo(w[a].w) - s, bf16hi(w[a].w) - s));
        }
        fence_async_smem();
    }
    asm volatile("bar.sync 6, 384;\n" ::: "memory");
    TR(27, 4 + wg);
    {
        PROJ_SCHEDULE
        uint64_t descW = make_desc(sbase + SM_WO, 12288, 512, 2);
        const uint64_t descA = make_desc(sbase + SM_STAGE + wg * STAGE_BYTES, 16, 1024, 1);
        const uint32_t bar = sbase + SM_PBAR + wg * 8;
        const uint32_t yrel = sbase + SM_STAGE + wg * STAGE_BYTES + (warp * 16 + (lane & 15)) * 128 + (((lane & 7) ^ (lane >> 4)) << 4);
        float acc[96];
#pragma unroll
        for (int i = 0; i < 96; i++) acc[i] = 0.f;
        uint32_t it = 0;
        for (int tile = tile0 + wg * tstep; tile < tend; tile += 3 * tstep, it++) {
            descW += P.z1;
            mbar_wait(bar + (it & 1) * 24, (it >> 1) & 1);
            TR(28, it * 3 + wg);
            if (it > 0 || wg > 0) asm volatile("bar.sync %0, 256;\n" :: "r"(8 + wg) : "memory");
            wgmma_fence();
            mma_proj<0, 0>(acc, descA + (uint64_t)((it & 1) * (3 * STAGE_BYTES >> 4)), descW);
            wgmma_commit();
            if (tile + tstep < tend) asm volatile("bar.arrive %0, 256;\n" :: "r"(wg == 2 ? 8 : 9 + wg) : "memory");
            wgmma_wait<0>();
            reg_fence(acc);
            float a[4];
#pragma unroll
            for (int i = 0; i < 4; i++) a[i] = acc[i] * acc[i];
#pragma unroll
            for (int j = 1; j < 24; j++)
#pragma unroll
                for (int i = 0; i < 4; i++) a[i] = fmaf(acc[4 * j + i], acc[4 * j + i], a[i]);
            float s0 = a[0] + a[1], s1 = a[2] + a[3];
            s0 += __shfl_xor_sync(0xffffffffu, s0, 1);
            s1 += __shfl_xor_sync(0xffffffffu, s1, 1);
            s0 += __shfl_xor_sync(0xffffffffu, s0, 2);
            s1 += __shfl_xor_sync(0xffffffffu, s1, 2);
            const float rs0 = rsqrt_ftz(fmaf(s0, 1.f / 192.f, 1e-5f));
            const float rs1 = rsqrt_ftz(fmaf(s1, 1.f / 192.f, 1e-5f));
            const uint32_t ya = yrel + (it & 1) * 3 * STAGE_BYTES;
#pragma unroll
            for (int p = 0; p < 12; p++)
                stsm_x4((ya ^ (32 * (p & 3))) + (p >> 2) * 8192,
                        pack_bf16(acc[8 * p] * rs0, acc[8 * p + 1] * rs0), pack_bf16(acc[8 * p + 2] * rs1, acc[8 * p + 3] * rs1),
                        pack_bf16(acc[8 * p + 4] * rs0, acc[8 * p + 5] * rs0), pack_bf16(acc[8 * p + 6] * rs1, acc[8 * p + 7] * rs1));
            __syncwarp();
            if (lane == 0) mbar_arrive(bar + 104 + (it & 1) * 24);
            TR(29, it * 3 + wg);
        }
    }
}

}

typedef CUresult (*PFN_encodeTiled)(CUtensorMap*, CUtensorMapDataType, cuuint32_t, void*, const cuuint64_t*,
                                    const cuuint64_t*, const cuuint32_t*, const cuuint32_t*, CUtensorMapInterleave,
                                    CUtensorMapSwizzle, CUtensorMapL2promotion, CUtensorMapFloatOOBfill);

extern "C" void kernel_launch(void* const* d_in, const int* in_sizes, int n_in, void* d_out, int out_size) {
    swin::Params P;
    P.x           = (const __nv_bfloat16*)d_in[0];
    P.wqkv        = (const __nv_bfloat16*)d_in[1];
    P.wo          = (const __nv_bfloat16*)d_in[2];
    P.logit_scale = (const __nv_bfloat16*)d_in[3];
    P.cpb_w1      = (const __nv_bfloat16*)d_in[4];
    P.cpb_w2      = (const __nv_bfloat16*)d_in[5];
    P.rel_coords  = (const __nv_bfloat16*)d_in[6];
    P.rel_idx     = (const int*)d_in[7];
    P.mask        = (const __nv_bfloat16*)d_in[8];
    P.out         = (__nv_bfloat16*)d_out;
    P.z1 = 0;
    static PFN_encodeTiled encode = nullptr;
    if (!encode) {
        cudaFuncSetAttribute(swin::swin_window_attn_kernel, cudaFuncAttributeMaxDynamicSharedMemorySize, swin::SM_TOTAL);
        cudaDriverEntryPointQueryResult qr;
        cudaGetDriverEntryPoint("cuTensorMapEncodeTiled", (void**)&encode, cudaEnableDefault, &qr);
    }
    CUtensorMap xmap, xmap4, xmap3, omap, wmap, smap, omapb, xmapa, xmapb, smap3, wraw;
    const cuuint32_t estr[4] = {1, 1, 1, 1};
    auto make = [&](CUtensorMap* m, const void* base, int rank, const cuuint64_t* gdim, const cuuint64_t* gstr,
                    const cuuint32_t* box, CUtensorMapSwizzle swz = CU_TENSOR_MAP_SWIZZLE_128B) {
        CUresult r = encode(m, CU_TENSOR_MAP_DATA_TYPE_BFLOAT16, rank, const_cast<void*>(base), gdim, gstr, box, estr,
               CU_TENSOR_MAP_INTERLEAVE_NONE, swz, CU_TENSOR_MAP_L2_PROMOTION_L2_128B,
               CU_TENSOR_MAP_FLOAT_OOB_FILL_NONE);
        (void)r;
    };
    {
        const cuuint64_t gdim[3] = {192, swin::IMG, swin::IMG}, gstr[2] = {384, swin::IMG * 384};
        const cuuint32_t box[3] = {64, 7, 7}, box4[3] = {64, 4, 1}, box3[3] = {64, 3, 1};
        make(&xmap, P.x, 3, gdim, gstr, box);
        make(&xmap4, P.x, 3, gdim, gstr, box4);
        make(&xmap3, P.x, 3, gdim, gstr, box3);
        const cuuint32_t boxa[3] = {64, 7, 3}, boxb[3] = {64, 7, 4};
        make(&xmapa, P.x, 3, gdim, gstr, boxa);
        make(&xmapb, P.x, 3, gdim, gstr, boxb);
    }
    {
        const cuuint64_t gdim[2] = {192, (cuuint64_t)swin::NPIX}, gstr[1] = {384};
        const cuuint32_t box64[2] = {64, 64};
        make(&omap, d_out, 2, gdim, gstr, box64);
        const cuuint64_t gdimb[2] = {192, (cuuint64_t)swin::SEG_B};
        make(&omapb, d_out, 2, gdimb, gstr, box64);
    }
    {
        const cuuint64_t gdim[2] = {576, 192}, gstr[1] = {1152};
        const cuuint32_t box[2] = {16, 192};
        make(&wmap, P.wqkv, 2, gdim, gstr, box, CU_TENSOR_MAP_SWIZZLE_32B);
        const cuuint64_t gdim3[3] = {96, 6, 192}, gstr3[2] = {192, 1152};
        const cuuint32_t box3[3] = {104, 1, 96};
        make(&wraw, P.wqkv, 3, gdim3, gstr3, box3, CU_TENSOR_MAP_SWIZZLE_NONE);
    }
    {
        const cuuint64_t gdim[4] = {96, 2, swin::IMG, swin::IMG}, gstr[3] = {192, 384, swin::IMG * 384};
        const cuuint32_t box4[4] = {104, 1, 7, 4}, box3[4] = {104, 1, 7, 3};
        make(&smap, d_out, 4, gdim, gstr, box4, CU_TENSOR_MAP_SWIZZLE_NONE);
        make(&smap3, d_out, 4, gdim, gstr, box3, CU_TENSOR_MAP_SWIZZLE_NONE);
    }
    P.npair = NPAIR; P.need = swin::ROW_DONE; P.nq = swin::NWINDOWS / NPAIR; P.nr = swin::NWINDOWS % NPAIR;
    P.t1 = swin::TILES - NTAIL;
    swin::swin_window_attn_kernel<<<132, swin::NTHREADS, swin::SM_TOTAL>>>(P, xmap, xmap4, xmap3, omap, wmap, smap, omapb, xmapa, xmapb, smap3, wraw);
}
```

```cpp
#include <cuda_runtime.h>
#include <cuda.h>
#include <cuda_bf16.h>
#include <stdint.h>
#include <type_traits>

namespace swin {
#define HINT ""

#define NPAIR 53
#define QFP32 0
#define PF_DIST 3
#define EXP 0
#define QSPLIT 3
#define SSPLIT 0
#define LATEMASK 0
#define CLUSTER 0
#define NOPF 0
#define NTAIL 216
#define PSTORE 1
#define PORDER 1
#define GORD 0
#define GMERGE 0
#define XSPLIT 1
#define EARLYW 1
#define NEARLY 4
#define MLD 0
#define PIN 3
#define SEQ 1
#define TAU_FAST 40.f
#define REG_G 232
#define REG_A 128
#define REG_H 24
constexpr int IMG      = 511;
constexpr int NWS      = 73;
constexpr int NWINDOWS = NWS * NWS;
constexpr int TOK      = 49;
constexpr int NPIX     = IMG * IMG;
constexpr int NTHREADS = 512;

constexpr int W_ATOM = 6144;
constexpr int SM_WA = 0, SM_WB = 6 * W_ATOM, SM_WV = 12 * W_ATOM;
constexpr int GRP   = TOK * 16;
constexpr int XCH   = TOK * 128;
constexpr int SM_V  = 18 * W_ATOM, V_STRIDE = 10240, O_PITCH = 208;
constexpr int SM_QK = SM_V + 4 * V_STRIDE, QK_CHUNK = 4 * XCH;
constexpr int SM_MASK = SM_QK + 3 * QK_CHUNK;
constexpr int SM_TAB  = SM_V + 3 * V_STRIDE + 256;
constexpr int SM_DUMP = SM_MASK + 4816;
constexpr int SM_BAR  = SM_DUMP + 320;
constexpr int B_XFULL = 0, B_WRAW = 32, B_QKRAW = 64, B_QKFREE = 96, B_VFREE = 128, B_ODONE = 160,
              B_VRAW = 224, B_MFULL = 256, B_MCONS = 272, B_WFULL = 280, B_STORED = 288, B_PUBD = 304;
constexpr int SM_A_END = SM_BAR + 320;
static_assert(SM_QK % 1024 == 0 && TOK * O_PITCH + 64 - 16 <= V_STRIDE && (28 * O_PITCH + 64) % 128 == 0, "layout");
constexpr int SM_WO    = 0;
constexpr int SM_STAGE = 73728;
constexpr int STAGE_BYTES = 24576;
constexpr int SM_PBAR  = SM_A_END;
constexpr int SM_TOTAL = SM_PBAR + 152;
static_assert(SM_STAGE + 6 * STAGE_BYTES <= SM_BAR, "smem");
static_assert(SM_TOTAL <= 232448, "smem");
static_assert(SM_BAR % 8 == 0, "barrier alignment");

constexpr int SEG_B   = 3 * IMG;
constexpr int TILES_A = (NPIX - SEG_B + 63) / 64;
constexpr int TILES   = TILES_A + (SEG_B + 63) / 64;
constexpr uint32_t ROW_DONE = NWS * 2;

__device__ uint32_t g_cnt[NWS + 7];
__device__ uint32_t g_done;

#define TR(ev, idx)
constexpr float LOG2E = 1.4426950408889634f;

__device__ __forceinline__ uint32_t smem_u32(const void* p) {
    return (uint32_t)__cvta_generic_to_shared(p);
}
__device__ __forceinline__ uint64_t make_desc(uint32_t saddr, uint32_t lbo, uint32_t sbo, uint32_t swz = 0) {
    return (uint64_t)((saddr & 0x3FFFF) >> 4) | ((uint64_t)(lbo >> 4) << 16) | ((uint64_t)(sbo >> 4) << 32) |
           ((uint64_t)swz << 62);
}
__host__ __device__ constexpr uint64_t make_desc_c(uint32_t saddr, uint32_t lbo, uint32_t sbo, uint32_t swz) {
    return (uint64_t)(saddr >> 4) | ((uint64_t)(lbo >> 4) << 16) | ((uint64_t)(sbo >> 4) << 32) | ((uint64_t)swz << 62);
}
__device__ __forceinline__ void wgmma_fence()  { asm volatile("wgmma.fence.sync.aligned;\n" ::: "memory"); }
__device__ __forceinline__ void wgmma_commit() { asm volatile("wgmma.commit_group.sync.aligned;\n" ::: "memory"); }
template <int N> __device__ __forceinline__ void wgmma_wait() {
    asm volatile("wgmma.wait_group.sync.aligned %0;\n" :: "n"(N) : "memory");
}
__device__ __forceinline__ void fence_async_smem() { asm volatile("fence.proxy.async.shared::cta;\n" ::: "memory"); }
__device__ __forceinline__ void wg_bar(int id) { asm volatile("bar.sync %0, 128;\n" :: "r"(id) : "memory"); }

template <int N> __device__ __forceinline__ void reg_fence(float (&v)[N]) {
#pragma unroll
    for (int i = 0; i < N; i++) asm volatile("" : "+f"(v[i]) :: "memory");
}
template <int N> __device__ __forceinline__ void reg_fence(uint32_t (&v)[N]) {
#pragma unroll
    for (int i = 0; i < N; i++) asm volatile("" : "+r"(v[i]) :: "memory");
}
template <int N, int M> __device__ __forceinline__ void reg_fence(uint32_t (&v)[N][M]) {
#pragma unroll
    for (int i = 0; i < N; i++) reg_fence(v[i]);
}

__device__ __forceinline__ uint32_t pack_bf16(float lo, float hi) {
    uint32_t r;
    asm("cvt.rn.bf16x2.f32 %0, %1, %2;\n" : "=r"(r) : "f"(hi), "f"(lo));
    return r;
}
__device__ __forceinline__ float bf16lo(uint32_t v) { return __uint_as_float(v << 16); }
__device__ __forceinline__ float bf16hi(uint32_t v) { return __uint_as_float(v & 0xFFFF0000u); }
__device__ __forceinline__ uint32_t hadd2_bf16(uint32_t a, uint32_t b) {
    uint32_t r;
    asm("add.rn.bf16x2 %0, %1, %2;\n" : "=r"(r) : "r"(a), "r"(b));
    return r;
}
__device__ __forceinline__ uint32_t hmul2_bf16(uint32_t a, uint32_t b) {
    uint32_t r;
    asm("mul.rn.bf16x2 %0, %1, %2;\n" : "=r"(r) : "r"(a), "r"(b));
    return r;
}
__device__ __forceinline__ uint32_t hsub2_bf16(uint32_t a, uint32_t b) {
    uint32_t r;
    asm("sub.rn.bf16x2 %0, %1, %2;\n" : "=r"(r) : "r"(a), "r"(b));
    return r;
}
__device__ __forceinline__ uint32_t hfma2_bf16(uint32_t a, uint32_t b, uint32_t c) {
    uint32_t r;
    asm("fma.rn.bf16x2 %0, %1, %2, %3;\n" : "=r"(r) : "r"(a), "r"(b), "r"(c));
    return r;
}
__device__ __forceinline__ uint32_t hmax2_bf16(uint32_t a, uint32_t b) {
    uint32_t r;
    asm("max.bf16x2 %0, %1, %2;\n" : "=r"(r) : "r"(a), "r"(b));
    return r;
}
__device__ __forceinline__ uint32_t hmin2_bf16(uint32_t a, uint32_t b) {
    uint32_t r;
    asm("min.bf16x2 %0, %1, %2;\n" : "=r"(r) : "r"(a), "r"(b));
    return r;
}
__device__ __forceinline__ uint32_t ex2_bf16x2(uint32_t a) {
    uint32_t r;
    asm("ex2.approx.ftz.bf16x2 %0, %1;\n" : "=r"(r) : "r"(a));
    return r;
}
__device__ __forceinline__ uint32_t ex2_bf16lo(uint32_t a) {
    uint32_t r;
    asm("{\n.reg .b16 l, h;\nmov.b32 {l, h}, %1;\nex2.approx.ftz.bf16 l, l;\ncvt.u32.u16 %0, l;\n}\n" : "=r"(r) : "r"(a));
    return r;
}
__device__ __forceinline__ uint32_t mbar_test(uint32_t bar, uint32_t parity) {
    uint32_t ok;
    asm volatile("{\n.reg .pred p;\nmbarrier.test_wait.parity.shared::cta.b64 p, [%1], %2;\nselp.u32 %0, 1, 0, p;\n}\n"
                 : "=r"(ok) : "r"(bar), "r"(parity) : "memory");
    return ok;
}
__device__ __forceinline__ uint32_t prmt(uint32_t a, uint32_t b, uint32_t sel) {
    uint32_t r;
    asm("prmt.b32 %0, %1, %2, %3;\n" : "=r"(r) : "r"(a), "r"(b), "r"(sel));
    return r;
}
__device__ __forceinline__ float round_bf16(float x) { return __bfloat162float(__float2bfloat16_rn(x)); }

__device__ __forceinline__ void mbar_init(uint32_t bar, uint32_t count) {
    asm volatile("mbarrier.init.shared::cta.b64 [%0], %1;\n" :: "r"(bar), "r"(count) : "memory");
}
__device__ __forceinline__ void mbar_wait(uint32_t bar, uint32_t parity) {
    asm volatile(
        "{\n"
        ".reg .pred p;\n"
        ".reg .u32 n;\n"
        "mov.u32 n, 0;\n"
        "WAIT_%=:\n"
        "mbarrier.try_wait.parity.shared::cta.b64 p, [%0], %1" HINT ";\n"
        "@p bra DONE_%=;\n"
        "add.u32 n, n, 1;\n"
        "setp.lt.u32 p, n, 4194304;\n"
        "@p bra WAIT_%=;\n"
        "exit;\n"
        "DONE_%=:\n"
        "}\n" :: "r"(bar), "r"(parity) : "memory");
}
__device__ __forceinline__ void mbar_wait4(uint32_t b0, uint32_t p0, uint32_t b1, uint32_t p1, uint32_t b2, uint32_t p2,
                                           uint32_t b3, uint32_t p3) {
    asm volatile(
        "{\n"
        ".reg .pred p, q, r, s;\n"
        ".reg .u32 n;\n"
        "mov.u32 n, 0;\n"
        "WAIT_%=:\n"
        "mbarrier.try_wait.parity.shared::cta.b64 p, [%0], %1" HINT ";\n"
        "mbarrier.try_wait.parity.shared::cta.b64 q, [%2], %3" HINT ";\n"
        "mbarrier.try_wait.parity.shared::cta.b64 r, [%4], %5" HINT ";\n"
        "mbarrier.try_wait.parity.shared::cta.b64 s, [%6], %7" HINT ";\n"
        "and.pred p, p, q;\n"
        "and.pred r, r, s;\n"
        "and.pred p, p, r;\n"
        "@p bra DONE_%=;\n"
        "add.u32 n, n, 1;\n"
        "setp.lt.u32 p, n, 4194304;\n"
        "@p bra WAIT_%=;\n"
        "exit;\n"
        "DONE_%=:\n"
        "}\n" :: "r"(b0), "r"(p0), "r"(b1), "r"(p1), "r"(b2), "r"(p2), "r"(b3), "r"(p3) : "memory");
}
__device__ __forceinline__ void mbar_wait2(uint32_t b0, uint32_t p0, uint32_t b1, uint32_t p1) {
    asm volatile(
        "{\n"
        ".reg .pred p, q;\n"
        ".reg .u32 n;\n"
        "mov.u32 n, 0;\n"
        "WAIT_%=:\n"
        "mbarrier.try_wait.parity.shared::cta.b64 p, [%0], %1" HINT ";\n"
        "mbarrier.try_wait.parity.shared::cta.b64 q, [%2], %3" HINT ";\n"
        "and.pred p, p, q;\n"
        "@p bra DONE_%=;\n"
        "add.u32 n, n, 1;\n"
        "setp.lt.u32 p, n, 4194304;\n"
        "@p bra WAIT_%=;\n"
        "exit;\n"
        "DONE_%=:\n"
        "}\n" :: "r"(b0), "r"(p0), "r"(b1), "r"(p1) : "memory");
}
__device__ __forceinline__ void mbar_wait_unless(uint32_t ok, uint32_t bar, uint32_t parity) {
    asm volatile(
        "{\n"
        ".reg .pred p;\n"
        ".reg .u32 n;\n"
        "setp.ne.u32 p, %2, 0;\n"
        "vote.sync.all.pred p, p, 0xffffffff;\n"
        "@p bra DONE_%=;\n"
        "mov.u32 n, 0;\n"
        "WAIT_%=:\n"
        "mbarrier.try_wait.parity.shared::cta.b64 p, [%0], %1" HINT ";\n"
        "@p bra DONE_%=;\n"
        "add.u32 n, n, 1;\n"
        "setp.lt.u32 p, n, 4194304;\n"
        "@p bra WAIT_%=;\n"
        "exit;\n"
        "DONE_%=:\n"
        "}\n" :: "r"(bar), "r"(parity), "r"(ok) : "memory");
}
__device__ __forceinline__ void mbar_wait2_unless(uint32_t ok, uint32_t b0, uint32_t p0, uint32_t b1, uint32_t p1) {
    asm volatile(
        "{\n"
        ".reg .pred p, q;\n"
        ".reg .u32 n;\n"
        "setp.ne.u32 p, %4, 0;\n"
        "vote.sync.all.pred p, p, 0xffffffff;\n"
        "@p bra DONE_%=;\n"
        "mov.u32 n, 0;\n"
        "WAIT_%=:\n"
        "mbarrier.try_wait.parity.shared::cta.b64 p, [%0], %1" HINT ";\n"
        "mbarrier.try_wait.parity.shared::cta.b64 q, [%2], %3" HINT ";\n"
        "and.pred p, p, q;\n"
        "@p bra DONE_%=;\n"
        "add.u32 n, n, 1;\n"
        "setp.lt.u32 p, n, 4194304;\n"
        "@p bra WAIT_%=;\n"
        "exit;\n"
        "DONE_%=:\n"
        "}\n" :: "r"(b0), "r"(p0), "r"(b1), "r"(p1), "r"(ok) : "memory");
}
__device__ __forceinline__ void mbar_wait4_unless(uint32_t ok, uint32_t b0, uint32_t p0, uint32_t b1, uint32_t p1, uint32_t b2,
                                                  uint32_t p2, uint32_t b3, uint32_t p3) {
    asm volatile(
        "{\n"
        ".reg .pred p, q, r, s;\n"
        ".reg .u32 n;\n"
        "setp.ne.u32 p, %8, 0;\n"
        "vote.sync.all.pred p, p, 0xffffffff;\n"
        "@p bra DONE_%=;\n"
        "mov.u32 n, 0;\n"
        "WAIT_%=:\n"
        "mbarrier.try_wait.parity.shared::cta.b64 p, [%0], %1" HINT ";\n"
        "mbarrier.try_wait.parity.shared::cta.b64 q, [%2], %3" HINT ";\n"
        "mbarrier.try_wait.parity.shared::cta.b64 r, [%4], %5" HINT ";\n"
        "mbarrier.try_wait.parity.shared::cta.b64 s, [%6], %7" HINT ";\n"
        "and.pred p, p, q;\n"
        "and.pred r, r, s;\n"
        "and.pred p, p, r;\n"
        "@p bra DONE_%=;\n"
        "add.u32 n, n, 1;\n"
        "setp.lt.u32 p, n, 4194304;\n"
        "@p bra WAIT_%=;\n"
        "exit;\n"
        "DONE_%=:\n"
        "}\n" :: "r"(b0), "r"(p0), "r"(b1), "r"(p1), "r"(b2), "r"(p2), "r"(b3), "r"(p3), "r"(ok) : "memory");
}
__device__ __forceinline__ void sched_fence(uint32_t zero, uint32_t a, uint32_t b, uint32_t c, uint32_t d, uint32_t e = 0,
                                            uint32_t f = 0, uint32_t g = 0, uint32_t h = 0, uint32_t i = 0, uint32_t j = 0,
                                            uint32_t k = 0) {
    asm volatile("{\n.reg .pred p;\n.reg .u32 n;\nsetp.eq.u32 p, %0, 0;\n@p bra.uni DONE_%=;\nmov.u32 n, %0;\nSPIN_%=:\n"
                 "nanosleep.u32 %1;\nnanosleep.u32 %2;\nnanosleep.u32 %3;\nnanosleep.u32 %4;\nnanosleep.u32 %5;\n"
                 "nanosleep.u32 %6;\nnanosleep.u32 %7;\nnanosleep.u32 %8;\nnanosleep.u32 %9;\nnanosleep.u32 %10;\n"
                 "nanosleep.u32 %11;\nsub.u32 n, n, 1;\nsetp.ne.u32 p, n, 0;\n@p bra.uni SPIN_%=;\nDONE_%=:\n}\n"
                 :: "r"(zero), "r"(a), "r"(b), "r"(c), "r"(d), "r"(e), "r"(f), "r"(g), "r"(h), "r"(i), "r"(j), "r"(k) : "memory");
}
__device__ __forceinline__ void sched_fence_rw(uint32_t zero, uint32_t (&v)[13]) {
    asm volatile("{\n.reg .pred p;\n.reg .u32 n;\nsetp.eq.u32 p, %13, 0;\n@p bra.uni DONE_%=;\nmov.u32 n, %13;\nSPIN_%=:\n"
                 "add.u32 %0, %0, %1;\nadd.u32 %1, %1, %2;\nadd.u32 %2, %2, %3;\nadd.u32 %3, %3, %4;\nadd.u32 %4, %4, %5;\n"
                 "add.u32 %5, %5, %6;\nadd.u32 %6, %6, %7;\nadd.u32 %7, %7, %8;\nadd.u32 %8, %8, %9;\nadd.u32 %9, %9, %10;\n"
                 "add.u32 %10, %10, %11;\nadd.u32 %11, %11, %12;\nadd.u32 %12, %12, %0;\n"
                 "sub.u32 n, n, 1;\nsetp.ne.u32 p, n, 0;\n@p bra.uni SPIN_%=;\nDONE_%=:\n}\n"
                 : "+r"(v[0]), "+r"(v[1]), "+r"(v[2]), "+r"(v[3]), "+r"(v[4]), "+r"(v[5]), "+r"(v[6]), "+r"(v[7]), "+r"(v[8]),
                   "+r"(v[9]), "+r"(v[10]), "+r"(v[11]), "+r"(v[12]) : "r"(zero) : "memory");
}
__device__ __forceinline__ void mbar_arrive(uint32_t bar) {
    asm volatile("mbarrier.arrive.shared::cta.b64 _, [%0];\n" :: "r"(bar) : "memory");
}
__device__ __forceinline__ void mbar_arrive_n(uint32_t bar, uint32_t n) {
    asm volatile("mbarrier.arrive.shared::cta.b64 _, [%0], %1;\n" :: "r"(bar), "r"(n) : "memory");
}
__device__ __forceinline__ void mbar_arrive_expect_tx(uint32_t bar, uint32_t bytes) {
    asm volatile("mbarrier.arrive.expect_tx.shared::cta.b64 _, [%0], %1;\n" :: "r"(bar), "r"(bytes) : "memory");
}
__device__ __forceinline__ void stg128_if(bool p, void* addr, uint32_t x, uint32_t y, uint32_t z, uint32_t w) {
    asm volatile("{\n.reg .pred q;\nsetp.ne.b32 q, %5, 0;\n@q st.global.L1::no_allocate.v4.b32 [%0], {%1, %2, %3, %4};\n}\n"
                 :: "l"(addr), "r"(x), "r"(y), "r"(z), "r"(w), "r"((uint32_t)p) : "memory");
}
__device__ __forceinline__ void stsm_x4(uint32_t addr, uint32_t r0, uint32_t r1, uint32_t r2, uint32_t r3) {
    asm volatile("stmatrix.sync.aligned.m8n8.x4.shared.b16 [%0], {%1, %2, %3, %4};\n"
                 :: "r"(addr), "r"(r0), "r"(r1), "r"(r2), "r"(r3) : "memory");
}
__device__ __forceinline__ void stsm_x2(uint32_t addr, uint32_t r0, uint32_t r1) {
    asm volatile("stmatrix.sync.aligned.m8n8.x2.shared.b16 [%0], {%1, %2};\n" :: "r"(addr), "r"(r0), "r"(r1) : "memory");
}
__device__ __forceinline__ void sts128(uint32_t addr, uint32_t r0, uint32_t r1, uint32_t r2, uint32_t r3) {
    asm volatile("st.shared.v4.b32 [%0], {%1, %2, %3, %4};\n" :: "r"(addr), "r"(r0), "r"(r1), "r"(r2), "r"(r3) : "memory");
}
__device__ __forceinline__ void sts32(uint32_t addr, uint32_t v) {
    asm volatile("st.shared.b32 [%0], %1;\n" :: "r"(addr), "r"(v) : "memory");
}
__device__ __forceinline__ uint32_t lds32(uint32_t addr) {
    uint32_t v;
    asm volatile("ld.shared.b32 %0, [%1];\n" : "=r"(v) : "r"(addr) : "memory");
    return v;
}
__device__ __forceinline__ void ldg_nc_v4(uint32_t (&r)[4], const void* p) {
    asm volatile("ld.global.nc.L1::no_allocate.v4.u32 {%0, %1, %2, %3}, [%4];\n"
                 : "=r"(r[0]), "=r"(r[1]), "=r"(r[2]), "=r"(r[3]) : "l"(p));
}
__device__ __forceinline__ uint32_t ldg_u32(const void* p) {
    uint32_t v;
    asm volatile("ld.global.nc.L1::evict_first.u32 %0, [%1];\n" : "=r"(v) : "l"(p));
    return v;
}
__device__ __forceinline__ void ldg_u64(const void* p, uint32_t& a, uint32_t& b) {
    asm volatile("ld.global.nc.L1::evict_first.v2.u32 {%0, %1}, [%2];\n" : "=r"(a), "=r"(b) : "l"(p));
}
__device__ __forceinline__ void prefetch_l2(const void* p) {
    asm volatile("prefetch.global.L2 [%0];\n" :: "l"(p));
}
__device__ __forceinline__ void cp_async16(uint32_t dst, const void* src) {
    asm volatile("cp.async.cg.shared.global [%0], [%1], 16;\n" :: "r"(dst), "l"(src) : "memory");
}
__device__ __forceinline__ float ex2_ftz(float x) {
    float y;
    asm("ex2.approx.ftz.f32 %0, %1;\n" : "=f"(y) : "f"(x));
    return y;
}
__device__ __forceinline__ float lg2_ftz(float x) {
    float y;
    asm("lg2.approx.ftz.f32 %0, %1;\n" : "=f"(y) : "f"(x));
    return y;
}
__device__ __forceinline__ float rcp_ftz(float x) {
    float y;
    asm("rcp.approx.ftz.f32 %0, %1;\n" : "=f"(y) : "f"(x));
    return y;
}
__device__ __forceinline__ float rsqrt_ftz(float x) {
    float y;
    asm("rsqrt.approx.ftz.f32 %0, %1;\n" : "=f"(y) : "f"(x));
    return y;
}

__device__ __forceinline__ bool elect_one() {
    uint32_t p;
    asm volatile("{\n.reg .pred q;\nelect.sync _|q, 0xffffffff;\nselp.u32 %0, 1, 0, q;\n}\n" : "=r"(p));
    return p != 0;
}
__device__ __forceinline__ void ldsm_x4(uint32_t (&r)[4], uint32_t addr) {
    asm volatile("ldmatrix.sync.aligned.m8n8.x4.shared.b16 {%0, %1, %2, %3}, [%4];\n"
                 : "=r"(r[0]), "=r"(r[1]), "=r"(r[2]), "=r"(r[3]) : "r"(addr) : "memory");
}
__device__ __forceinline__ void ldsm_x2(uint32_t& r0, uint32_t& r1, uint32_t addr) {
    asm volatile("ldmatrix.sync.aligned.m8n8.x2.shared.b16 {%0, %1}, [%2];\n" : "=r"(r0), "=r"(r1) : "r"(addr) : "memory");
}
__device__ __forceinline__ void tma_2d(uint32_t dst, const CUtensorMap* map, uint32_t bar, int c0, int c1) {
    asm volatile("cp.async.bulk.tensor.2d.shared::cluster.global.mbarrier::complete_tx::bytes [%0], [%1, {%3, %4}], [%2];\n"
                 :: "r"(dst), "l"(reinterpret_cast<uint64_t>(map)), "r"(bar), "r"(c0), "r"(c1) : "memory");
}
__device__ __forceinline__ void tma_3d(uint32_t dst, const CUtensorMap* map, uint32_t bar, int c0, int c1, int c2) {
    asm volatile("cp.async.bulk.tensor.3d.shared::cluster.global.mbarrier::complete_tx::bytes [%0], [%1, {%3, %4, %5}], [%2];\n"
                 :: "r"(dst), "l"(reinterpret_cast<uint64_t>(map)), "r"(bar), "r"(c0), "r"(c1), "r"(c2) : "memory");
}
__device__ __forceinline__ void tma_store_4d(const CUtensorMap* map, uint32_t src, int c0, int c1, int c2, int c3) {
    asm volatile("cp.async.bulk.tensor.4d.global.shared::cta.tile.bulk_group [%0, {%2, %3, %4, %5}], [%1];\n"
                 :: "l"(reinterpret_cast<uint64_t>(map)), "r"(src), "r"(c0), "r"(c1), "r"(c2), "r"(c3) : "memory");
}
__device__ __forceinline__ void mbar_arrive_if(uint32_t bar, uint32_t cnt) {
    asm volatile("{\n.reg .pred q;\nsetp.ne.b32 q, %1, 0;\n@q mbarrier.arrive.shared::cta.b64 _, [%0], %1;\n}\n"
                 :: "r"(bar), "r"(cnt) : "memory");
}

template <int BOFF, int AOFF, int NA>
__device__ __forceinline__ void mma_qkv_a(float (&d)[48], const uint32_t (&a)[NA][4], uint64_t descB) {
    asm volatile(
        "{\n"
        ".reg .pred p0, p1;\n"
        ".reg .b64 ta, ta0, tb, tb0;\n"
        "setp.ne.b32 p0, 0, 0;\n"
        "setp.eq.b32 p1, 0, 0;\n"
        "add.s64 tb0, %72, %73;\n"
        "add.s64 tb, tb0, 0;\n"
        "wgmma.mma_async.sync.aligned.m64n96k16.f32.bf16.bf16 {%0, %1, %2, %3, %4, %5, %6, %7, %8, %9, %10, %11, %12, %13, %14, %15, %16, %17, %18, %19, %20, %21, %22, %23, %24, %25, %26, %27, %28, %29, %30, %31, %32, %33, %34, %35, %36, %37, %38, %39, %40, %41, %42, %43, %44, %45, %46, %47}, {%48, %49, %50, %51}, tb, p0, 1, 1, 1;\n"
        "add.s64 tb, tb0, 32;\n"
        "wgmma.mma_async.sync.aligned.m64n96k16.f32.bf16.bf16 {%0, %1, %2, %3, %4, %5, %6, %7, %8, %9, %10, %11, %12, %13, %14, %15, %16, %17, %18, %19, %20, %21, %22, %23, %24, %25, %26, %27, %28, %29, %30, %31, %32, %33, %34, %35, %36, %37, %38, %39, %40, %41, %42, %43, %44, %45, %46, %47}, {%52, %53, %54, %55}, tb, p1, 1, 1, 1;\n"
        "add.s64 tb, tb0, 64;\n"
        "wgmma.mma_async.sync.aligned.m64n96k16.f32.bf16.bf16 {%0, %1, %2, %3, %4, %5, %6, %7, %8, %9, %10, %11, %12, %13, %14, %15, %16, %17, %18, %19, %20, %21, %22, %23, %24, %25, %26, %27, %28, %29, %30, %31, %32, %33, %34, %35, %36, %37, %38, %39, %40, %41, %42, %43, %44, %45, %46, %47}, {%56, %57, %58, %59}, tb, p1, 1, 1, 1;\n"
        "add.s64 tb, tb0, 96;\n"
        "wgmma.mma_async.sync.aligned.m64n96k16.f32.bf16.bf16 {%0, %1, %2, %3, %4, %5, %6, %7, %8, %9, %10, %11, %12, %13, %14, %15, %16, %17, %18, %19, %20, %21, %22, %23, %24, %25, %26, %27, %28, %29, %30, %31, %32, %33, %34, %35, %36, %37, %38, %39, %40, %41, %42, %43, %44, %45, %46, %47}, {%60, %61, %62, %63}, tb, p1, 1, 1, 1;\n"
        "add.s64 tb, tb0, 128;\n"
        "wgmma.mma_async.sync.aligned.m64n96k16.f32.bf16.bf16 {%0, %1, %2, %3, %4, %5, %6, %7, %8, %9, %10, %11, %12, %13, %14, %15, %16, %17, %18, %19, %20, %21, %22, %23, %24, %25, %26, %27, %28, %29, %30, %31, %32, %33, %34, %35, %36, %37, %38, %39, %40, %41, %42, %43, %44, %45, %46, %47}, {%64, %65, %66, %67}, tb, p1, 1, 1, 1;\n"
        "add.s64 tb, tb0, 160;\n"
        "wgmma.mma_async.sync.aligned.m64n96k16.f32.bf16.bf16 {%0, %1, %2, %3, %4, %5, %6, %7, %8, %9, %10, %11, %12, %13, %14, %15, %16, %17, %18, %19, %20, %21, %22, %23, %24, %25, %26, %27, %28, %29, %30, %31, %32, %33, %34, %35, %36, %37, %38, %39, %40, %41, %42, %43, %44, %45, %46, %47}, {%68, %69, %70, %71}, tb, p1, 1, 1, 1;\n"
        "}\n"
        : "=f"(d[0]), "=f"(d[1]), "=f"(d[2]), "=f"(d[3]), "=f"(d[4]), "=f"(d[5]), "=f"(d[6]), "=f"(d[7]), "=f"(d[8]), "=f"(d[9]), "=f"(d[10]), "=f"(d[11]), "=f"(d[12]), "=f"(d[13]), "=f"(d[14]), "=f"(d[15]), "=f"(d[16]), "=f"(d[17]), "=f"(d[18]), "=f"(d[19]), "=f"(d[20]), "=f"(d[21]), "=f"(d[22]), "=f"(d[23]), "=f"(d[24]), "=f"(d[25]), "=f"(d[26]), "=f"(d[27]), "=f"(d[28]), "=f"(d[29]), "=f"(d[30]), "=f"(d[31]), "=f"(d[32]), "=f"(d[33]), "=f"(d[34]), "=f"(d[35]), "=f"(d[36]), "=f"(d[37]), "=f"(d[38]), "=f"(d[39]), "=f"(d[40]), "=f"(d[41]), "=f"(d[42]), "=f"(d[43]), "=f"(d[44]), "=f"(d[45]), "=f"(d[46]), "=f"(d[47])
        : "r"(a[AOFF + 0][0]), "r"(a[AOFF + 0][1]), "r"(a[AOFF + 0][2]), "r"(a[AOFF + 0][3]), "r"(a[AOFF + 1][0]), "r"(a[AOFF + 1][1]), "r"(a[AOFF + 1][2]), "r"(a[AOFF + 1][3]), "r"(a[AOFF + 2][0]), "r"(a[AOFF + 2][1]), "r"(a[AOFF + 2][2]), "r"(a[AOFF + 2][3]), "r"(a[AOFF + 3][0]), "r"(a[AOFF + 3][1]), "r"(a[AOFF + 3][2]), "r"(a[AOFF + 3][3]), "r"(a[AOFF + 4][0]), "r"(a[AOFF + 4][1]), "r"(a[AOFF + 4][2]), "r"(a[AOFF + 4][3]), "r"(a[AOFF + 5][0]), "r"(a[AOFF + 5][1]), "r"(a[AOFF + 5][2]), "r"(a[AOFF + 5][3]), "l"(descB), "n"(BOFF >> 4));
}

template <int BOFF, int AOFF, int NA>
__device__ __forceinline__ void mma_qkv_b(float (&d)[48], const uint32_t (&a)[NA][4], uint64_t descB) {
    asm volatile(
        "{\n"
        ".reg .pred p0, p1;\n"
        ".reg .b64 ta, ta0, tb, tb0;\n"
        "setp.ne.b32 p0, 0, 0;\n"
        "setp.eq.b32 p1, 0, 0;\n"
        "add.s64 tb0, %72, %73;\n"
        "add.s64 tb, tb0, 192;\n"
        "wgmma.mma_async.sync.aligned.m64n96k16.f32.bf16.bf16 {%0, %1, %2, %3, %4, %5, %6, %7, %8, %9, %10, %11, %12, %13, %14, %15, %16, %17, %18, %19, %20, %21, %22, %23, %24, %25, %26, %27, %28, %29, %30, %31, %32, %33, %34, %35, %36, %37, %38, %39, %40, %41, %42, %43, %44, %45, %46, %47}, {%48, %49, %50, %51}, tb, p1, 1, 1, 1;\n"
        "add.s64 tb, tb0, 224;\n"
        "wgmma.mma_async.sync.aligned.m64n96k16.f32.bf16.bf16 {%0, %1, %2, %3, %4, %5, %6, %7, %8, %9, %10, %11, %12, %13, %14, %15, %16, %17, %18, %19, %20, %21, %22, %23, %24, %25, %26, %27, %28, %29, %30, %31, %32, %33, %34, %35, %36, %37, %38, %39, %40, %41, %42, %43, %44, %45, %46, %47}, {%52, %53, %54, %55}, tb, p1, 1, 1, 1;\n"
        "add.s64 tb, tb0, 256;\n"
        "wgmma.mma_async.sync.aligned.m64n96k16.f32.bf16.bf16 {%0, %1, %2, %3, %4, %5, %6, %7, %8, %9, %10, %11, %12, %13, %14, %15, %16, %17, %18, %19, %20, %21, %22, %23, %24, %25, %26, %27, %28, %29, %30, %31, %32, %33, %34, %35, %36, %37, %38, %39, %40, %41, %42, %43, %44, %45, %46, %47}, {%56, %57, %58, %59}, tb, p1, 1, 1, 1;\n"
        "add.s64 tb, tb0, 288;\n"
        "wgmma.mma_async.sync.aligned.m64n96k16.f32.bf16.bf16 {%0, %1, %2, %3, %4, %5, %6, %7, %8, %9, %10, %11, %12, %13, %14, %15, %16, %17, %18, %19, %20, %21, %22, %23, %24, %25, %26, %27, %28, %29, %30, %31, %32, %33, %34, %35, %36, %37, %38, %39, %40, %41, %42, %43, %44, %45, %46, %47}, {%60, %61, %62, %63}, tb, p1, 1, 1, 1;\n"
        "add.s64 tb, tb0, 320;\n"
        "wgmma.mma_async.sync.aligned.m64n96k16.f32.bf16.bf16 {%0, %1, %2, %3, %4, %5, %6, %7, %8, %9, %10, %11, %12, %13, %14, %15, %16, %17, %18, %19, %20, %21, %22, %23, %24, %25, %26, %27, %28, %29, %30, %31, %32, %33, %34, %35, %36, %37, %38, %39, %40, %41, %42, %43, %44, %45, %46, %47}, {%64, %65, %66, %67}, tb, p1, 1, 1, 1;\n"
        "add.s64 tb, tb0, 352;\n"
        "wgmma.mma_async.sync.aligned.m64n96k16.f32.bf16.bf16 {%0, %1, %2, %3, %4, %5, %6, %7, %8, %9, %10, %11, %12, %13, %14, %15, %16, %17, %18, %19, %20, %21, %22, %23, %24, %25, %26, %27, %28, %29, %30, %31, %32, %33, %34, %35, %36, %37, %38, %39, %40, %41, %42, %43, %44, %45, %46, %47}, {%68, %69, %70, %71}, tb, p1, 1, 1, 1;\n"
        "}\n"
        : "+f"(d[0]), "+f"(d[1]), "+f"(d[2]), "+f"(d[3]), "+f"(d[4]), "+f"(d[5]), "+f"(d[6]), "+f"(d[7]), "+f"(d[8]), "+f"(d[9]), "+f"(d[10]), "+f"(d[11]), "+f"(d[12]), "+f"(d[13]), "+f"(d[14]), "+f"(d[15]), "+f"(d[16]), "+f"(d[17]), "+f"(d[18]), "+f"(d[19]), "+f"(d[20]), "+f"(d[21]), "+f"(d[22]), "+f"(d[23]), "+f"(d[24]), "+f"(d[25]), "+f"(d[26]), "+f"(d[27]), "+f"(d[28]), "+f"(d[29]), "+f"(d[30]), "+f"(d[31]), "+f"(d[32]), "+f"(d[33]), "+f"(d[34]), "+f"(d[35]), "+f"(d[36]), "+f"(d[37]), "+f"(d[38]), "+f"(d[39]), "+f"(d[40]), "+f"(d[41]), "+f"(d[42]), "+f"(d[43]), "+f"(d[44]), "+f"(d[45]), "+f"(d[46]), "+f"(d[47])
        : "r"(a[AOFF + 0][0]), "r"(a[AOFF + 0][1]), "r"(a[AOFF + 0][2]), "r"(a[AOFF + 0][3]), "r"(a[AOFF + 1][0]), "r"(a[AOFF + 1][1]), "r"(a[AOFF + 1][2]), "r"(a[AOFF + 1][3]), "r"(a[AOFF + 2][0]), "r"(a[AOFF + 2][1]), "r"(a[AOFF + 2][2]), "r"(a[AOFF + 2][3]), "r"(a[AOFF + 3][0]), "r"(a[AOFF + 3][1]), "r"(a[AOFF + 3][2]), "r"(a[AOFF + 3][3]), "r"(a[AOFF + 4][0]), "r"(a[AOFF + 4][1]), "r"(a[AOFF + 4][2]), "r"(a[AOFF + 4][3]), "r"(a[AOFF + 5][0]), "r"(a[AOFF + 5][1]), "r"(a[AOFF + 5][2]), "r"(a[AOFF + 5][3]), "l"(descB), "n"(BOFF >> 4));
}

template <int AOFF, int BOFF>
__device__ __forceinline__ void mma_qk0(float (&d)[28], uint64_t descA, uint64_t descB) {
    asm volatile(
        "{\n"
        ".reg .pred p0, p1;\n"
        ".reg .b64 ta, ta0, tb, tb0;\n"
        "setp.ne.b32 p0, 0, 0;\n"
        "setp.eq.b32 p1, 0, 0;\n"
        "add.s64 tb0, %30, %31;\n"
        "add.s64 ta0, %28, %29;\n"
        "add.s64 tb, tb0, 4;\n"
        "add.s64 ta, ta0, 0;\n"
        "wgmma.mma_async.sync.aligned.m64n56k16.f32.bf16.bf16 {%0, %1, %2, %3, %4, %5, %6, %7, %8, %9, %10, %11, %12, %13, %14, %15, %16, %17, %18, %19, %20, %21, %22, %23, %24, %25, %26, %27}, ta, tb, p0, 1, 1, 0, 0;\n"
        "add.s64 tb, tb0, 1572;\n"
        "add.s64 ta, ta0, 1568;\n"
        "wgmma.mma_async.sync.aligned.m64n56k16.f32.bf16.bf16 {%0, %1, %2, %3, %4, %5, %6, %7, %8, %9, %10, %11, %12, %13, %14, %15, %16, %17, %18, %19, %20, %21, %22, %23, %24, %25, %26, %27}, ta, tb, p1, 1, 1, 0, 0;\n"
        "add.s64 tb, tb0, 3140;\n"
        "add.s64 ta, ta0, 3136;\n"
        "wgmma.mma_async.sync.aligned.m64n56k16.f32.bf16.bf16 {%0, %1, %2, %3, %4, %5, %6, %7, %8, %9, %10, %11, %12, %13, %14, %15, %16, %17, %18, %19, %20, %21, %22, %23, %24, %25, %26, %27}, ta, tb, p1, 1, 1, 0, 0;\n"
        "}\n"
        : "=f"(d[0]), "=f"(d[1]), "=f"(d[2]), "=f"(d[3]), "=f"(d[4]), "=f"(d[5]), "=f"(d[6]), "=f"(d[7]), "=f"(d[8]), "=f"(d[9]), "=f"(d[10]), "=f"(d[11]), "=f"(d[12]), "=f"(d[13]), "=f"(d[14]), "=f"(d[15]), "=f"(d[16]), "=f"(d[17]), "=f"(d[18]), "=f"(d[19]), "=f"(d[20]), "=f"(d[21]), "=f"(d[22]), "=f"(d[23]), "=f"(d[24]), "=f"(d[25]), "=f"(d[26]), "=f"(d[27])
        : "l"(descA), "n"(AOFF >> 4), "l"(descB), "n"(BOFF >> 4));
}

template <int AOFF, int BOFF>
__device__ __forceinline__ void mma_qk1(float (&d)[28], uint64_t descA, uint64_t descB) {
    asm volatile(
        "{\n"
        ".reg .pred p0, p1;\n"
        ".reg .b64 ta, ta0, tb, tb0;\n"
        "setp.ne.b32 p0, 0, 0;\n"
        "setp.eq.b32 p1, 0, 0;\n"
        "add.s64 tb0, %30, %31;\n"
        "add.s64 ta0, %28, %29;\n"
        "add.s64 tb, tb0, 6;\n"
        "add.s64 ta, ta0, 2;\n"
        "wgmma.mma_async.sync.aligned.m64n56k16.f32.bf16.bf16 {%0, %1, %2, %3, %4, %5, %6, %7, %8, %9, %10, %11, %12, %13, %14, %15, %16, %17, %18, %19, %20, %21, %22, %23, %24, %25, %26, %27}, ta, tb, p0, 1, 1, 0, 0;\n"
        "add.s64 tb, tb0, 1574;\n"
        "add.s64 ta, ta0, 1570;\n"
        "wgmma.mma_async.sync.aligned.m64n56k16.f32.bf16.bf16 {%0, %1, %2, %3, %4, %5, %6, %7, %8, %9, %10, %11, %12, %13, %14, %15, %16, %17, %18, %19, %20, %21, %22, %23, %24, %25, %26, %27}, ta, tb, p1, 1, 1, 0, 0;\n"
        "add.s64 tb, tb0, 3142;\n"
        "add.s64 ta, ta0, 3138;\n"
        "wgmma.mma_async.sync.aligned.m64n56k16.f32.bf16.bf16 {%0, %1, %2, %3, %4, %5, %6, %7, %8, %9, %10, %11, %12, %13, %14, %15, %16, %17, %18, %19, %20, %21, %22, %23, %24, %25, %26, %27}, ta, tb, p1, 1, 1, 0, 0;\n"
        "}\n"
        : "=f"(d[0]), "=f"(d[1]), "=f"(d[2]), "=f"(d[3]), "=f"(d[4]), "=f"(d[5]), "=f"(d[6]), "=f"(d[7]), "=f"(d[8]), "=f"(d[9]), "=f"(d[10]), "=f"(d[11]), "=f"(d[12]), "=f"(d[13]), "=f"(d[14]), "=f"(d[15]), "=f"(d[16]), "=f"(d[17]), "=f"(d[18]), "=f"(d[19]), "=f"(d[20]), "=f"(d[21]), "=f"(d[22]), "=f"(d[23]), "=f"(d[24]), "=f"(d[25]), "=f"(d[26]), "=f"(d[27])
        : "l"(descA), "n"(AOFF >> 4), "l"(descB), "n"(BOFF >> 4));
}

template <int BOFF, int AOFF, int NA>
__device__ __forceinline__ void mma_pv(float (&d)[28], const uint32_t (&a)[NA][4], uint64_t descB) {
    asm volatile(
        "{\n"
        ".reg .pred p0, p1;\n"
        ".reg .b64 ta, ta0, tb, tb0;\n"
        "setp.ne.b32 p0, 0, 0;\n"
        "setp.eq.b32 p1, 0, 0;\n"
        "add.s64 tb0, %44, %45;\n"
        "add.s64 tb, tb0, 0;\n"
        "wgmma.mma_async.sync.aligned.m64n56k16.f32.bf16.bf16 {%0, %1, %2, %3, %4, %5, %6, %7, %8, %9, %10, %11, %12, %13, %14, %15, %16, %17, %18, %19, %20, %21, %22, %23, %24, %25, %26, %27}, {%28, %29, %30, %31}, tb, p0, 1, 1, 1;\n"
        "add.s64 tb, tb0, 16;\n"
        "wgmma.mma_async.sync.aligned.m64n56k16.f32.bf16.bf16 {%0, %1, %2, %3, %4, %5, %6, %7, %8, %9, %10, %11, %12, %13, %14, %15, %16, %17, %18, %19, %20, %21, %22, %23, %24, %25, %26, %27}, {%32, %33, %34, %35}, tb, p1, 1, 1, 1;\n"
        "add.s64 tb, tb0, 32;\n"
        "wgmma.mma_async.sync.aligned.m64n56k16.f32.bf16.bf16 {%0, %1, %2, %3, %4, %5, %6, %7, %8, %9, %10, %11, %12, %13, %14, %15, %16, %17, %18, %19, %20, %21, %22, %23, %24, %25, %26, %27}, {%36, %37, %38, %39}, tb, p1, 1, 1, 1;\n"
        "add.s64 tb, tb0, 48;\n"
        "wgmma.mma_async.sync.aligned.m64n56k16.f32.bf16.bf16 {%0, %1, %2, %3, %4, %5, %6, %7, %8, %9, %10, %11, %12, %13, %14, %15, %16, %17, %18, %19, %20, %21, %22, %23, %24, %25, %26, %27}, {%40, %41, %42, %43}, tb, p1, 1, 1, 1;\n"
        "}\n"
        : "=f"(d[0]), "=f"(d[1]), "=f"(d[2]), "=f"(d[3]), "=f"(d[4]), "=f"(d[5]), "=f"(d[6]), "=f"(d[7]), "=f"(d[8]), "=f"(d[9]), "=f"(d[10]), "=f"(d[11]), "=f"(d[12]), "=f"(d[13]), "=f"(d[14]), "=f"(d[15]), "=f"(d[16]), "=f"(d[17]), "=f"(d[18]), "=f"(d[19]), "=f"(d[20]), "=f"(d[21]), "=f"(d[22]), "=f"(d[23]), "=f"(d[24]), "=f"(d[25]), "=f"(d[26]), "=f"(d[27])
        : "r"(a[AOFF + 0][0]), "r"(a[AOFF + 0][1]), "r"(a[AOFF + 0][2]), "r"(a[AOFF + 0][3]), "r"(a[AOFF + 1][0]), "r"(a[AOFF + 1][1]), "r"(a[AOFF + 1][2]), "r"(a[AOFF + 1][3]), "r"(a[AOFF + 2][0]), "r"(a[AOFF + 2][1]), "r"(a[AOFF + 2][2]), "r"(a[AOFF + 2][3]), "r"(a[AOFF + 3][0]), "r"(a[AOFF + 3][1]), "r"(a[AOFF + 3][2]), "r"(a[AOFF + 3][3]), "l"(descB), "n"(BOFF >> 4));
}

template <int AOFF, int BOFF>
__device__ __forceinline__ void mma_proj(float (&d)[96], uint64_t descA, uint64_t descB) {
    asm volatile(
        "{\n"
        ".reg .pred p0, p1;\n"
        ".reg .b64 ta, ta0, tb, tb0;\n"
        "setp.ne.b32 p0, 0, 0;\n"
        "setp.eq.b32 p1, 0, 0;\n"
        "add.s64 tb0, %98, %99;\n"
        "add.s64 ta0, %96, %97;\n"
        "add.s64 tb, tb0, 0;\n"
        "add.s64 ta, ta0, 0;\n"
        "wgmma.mma_async.sync.aligned.m64n192k16.f32.bf16.bf16 {%0, %1, %2, %3, %4, %5, %6, %7, %8, %9, %10, %11, %12, %13, %14, %15, %16, %17, %18, %19, %20, %21, %22, %23, %24, %25, %26, %27, %28, %29, %30, %31, %32, %33, %34, %35, %36, %37, %38, %39, %40, %41, %42, %43, %44, %45, %46, %47, %48, %49, %50, %51, %52, %53, %54, %55, %56, %57, %58, %59, %60, %61, %62, %63, %64, %65, %66, %67, %68, %69, %70, %71, %72, %73, %74, %75, %76, %77, %78, %79, %80, %81, %82, %83, %84, %85, %86, %87, %88, %89, %90, %91, %92, %93, %94, %95}, ta, tb, p0, 1, 1, 0, 1;\n"
        "add.s64 tb, tb0, 64;\n"
        "add.s64 ta, ta0, 2;\n"
        "wgmma.mma_async.sync.aligned.m64n192k16.f32.bf16.bf16 {%0, %1, %2, %3, %4, %5, %6, %7, %8, %9, %10, %11, %12, %13, %14, %15, %16, %17, %18, %19, %20, %21, %22, %23, %24, %25, %26, %27, %28, %29, %30, %31, %32, %33, %34, %35, %36, %37, %38, %39, %40, %41, %42, %43, %44, %45, %46, %47, %48, %49, %50, %51, %52, %53, %54, %55, %56, %57, %58, %59, %60, %61, %62, %63, %64, %65, %66, %67, %68, %69, %70, %71, %72, %73, %74, %75, %76, %77, %78, %79, %80, %81, %82, %83, %84, %85, %86, %87, %88, %89, %90, %91, %92, %93, %94, %95}, ta, tb, p1, 1, 1, 0, 1;\n"
        "add.s64 tb, tb0, 128;\n"
        "add.s64 ta, ta0, 4;\n"
        "wgmma.mma_async.sync.aligned.m64n192k16.f32.bf16.bf16 {%0, %1, %2, %3, %4, %5, %6, %7, %8, %9, %10, %11, %12, %13, %14, %15, %16, %17, %18, %19, %20, %21, %22, %23, %24, %25, %26, %27, %28, %29, %30, %31, %32, %33, %34, %35, %36, %37, %38, %39, %40, %41, %42, %43, %44, %45, %46, %47, %48, %49, %50, %51, %52, %53, %54, %55, %56, %57, %58, %59, %60, %61, %62, %63, %64, %65, %66, %67, %68, %69, %70, %71, %72, %73, %74, %75, %76, %77, %78, %79, %80, %81, %82, %83, %84, %85, %86, %87, %88, %89, %90, %91, %92, %93, %94, %95}, ta, tb, p1, 1, 1, 0, 1;\n"
        "add.s64 tb, tb0, 192;\n"
        "add.s64 ta, ta0, 6;\n"
        "wgmma.mma_async.sync.aligned.m64n192k16.f32.bf16.bf16 {%0, %1, %2, %3, %4, %5, %6, %7, %8, %9, %10, %11, %12, %13, %14, %15, %16, %17, %18, %19, %20, %21, %22, %23, %24, %25, %26, %27, %28, %29, %30, %31, %32, %33, %34, %35, %36, %37, %38, %39, %40, %41, %42, %43, %44, %45, %46, %47, %48, %49, %50, %51, %52, %53, %54, %55, %56, %57, %58, %59, %60, %61, %62, %63, %64, %65, %66, %67, %68, %69, %70, %71, %72, %73, %74, %75, %76, %77, %78, %79, %80, %81, %82, %83, %84, %85, %86, %87, %88, %89, %90, %91, %92, %93, %94, %95}, ta, tb, p1, 1, 1, 0, 1;\n"
        "add.s64 tb, tb0, 256;\n"
        "add.s64 ta, ta0, 512;\n"
        "wgmma.mma_async.sync.aligned.m64n192k16.f32.bf16.bf16 {%0, %1, %2, %3, %4, %5, %6, %7, %8, %9, %10, %11, %12, %13, %14, %15, %16, %17, %18, %19, %20, %21, %22, %23, %24, %25, %26, %27, %28, %29, %30, %31, %32, %33, %34, %35, %36, %37, %38, %39, %40, %41, %42, %43, %44, %45, %46, %47, %48, %49, %50, %51, %52, %53, %54, %55, %56, %57, %58, %59, %60, %61, %62, %63, %64, %65, %66, %67, %68, %69, %70, %71, %72, %73, %74, %75, %76, %77, %78, %79, %80, %81, %82, %83, %84, %85, %86, %87, %88, %89, %90, %91, %92, %93, %94, %95}, ta, tb, p1, 1, 1, 0, 1;\n"
        "add.s64 tb, tb0, 320;\n"
        "add.s64 ta, ta0, 514;\n"
        "wgmma.mma_async.sync.aligned.m64n192k16.f32.bf16.bf16 {%0, %1, %2, %3, %4, %5, %6, %7, %8, %9, %10, %11, %12, %13, %14, %15, %16, %17, %18, %19, %20, %21, %22, %23, %24, %25, %26, %27, %28, %29, %30, %31, %32, %33, %34, %35, %36, %37, %38, %39, %40, %41, %42, %43, %44, %45, %46, %47, %48, %49, %50, %51, %52, %53, %54, %55, %56, %57, %58, %59, %60, %61, %62, %63, %64, %65, %66, %67, %68, %69, %70, %71, %72, %73, %74, %75, %76, %77, %78, %79, %80, %81, %82, %83, %84, %85, %86, %87, %88, %89, %90, %91, %92, %93, %94, %95}, ta, tb, p1, 1, 1, 0, 1;\n"
        "add.s64 tb, tb0, 384;\n"
        "add.s64 ta, ta0, 516;\n"
        "wgmma.mma_async.sync.aligned.m64n192k16.f32.bf16.bf16 {%0, %1, %2, %3, %4, %5, %6, %7, %8, %9, %10, %11, %12, %13, %14, %15, %16, %17, %18, %19, %20, %21, %22, %23, %24, %25, %26, %27, %28, %29, %30, %31, %32, %33, %34, %35, %36, %37, %38, %39, %40, %41, %42, %43, %44, %45, %46, %47, %48, %49, %50, %51, %52, %53, %54, %55, %56, %57, %58, %59, %60, %61, %62, %63, %64, %65, %66, %67, %68, %69, %70, %71, %72, %73, %74, %75, %76, %77, %78, %79, %80, %81, %82, %83, %84, %85, %86, %87, %88, %89, %90, %91, %92, %93, %94, %95}, ta, tb, p1, 1, 1, 0, 1;\n"
        "add.s64 tb, tb0, 448;\n"
        "add.s64 ta, ta0, 518;\n"
        "wgmma.mma_async.sync.aligned.m64n192k16.f32.bf16.bf16 {%0, %1, %2, %3, %4, %5, %6, %7, %8, %9, %10, %11, %12, %13, %14, %15, %16, %17, %18, %19, %20, %21, %22, %23, %24, %25, %26, %27, %28, %29, %30, %31, %32, %33, %34, %35, %36, %37, %38, %39, %40, %41, %42, %43, %44, %45, %46, %47, %48, %49, %50, %51, %52, %53, %54, %55, %56, %57, %58, %59, %60, %61, %62, %63, %64, %65, %66, %67, %68, %69, %70, %71, %72, %73, %74, %75, %76, %77, %78, %79, %80, %81, %82, %83, %84, %85, %86, %87, %88, %89, %90, %91, %92, %93, %94, %95}, ta, tb, p1, 1, 1, 0, 1;\n"
        "add.s64 tb, tb0, 512;\n"
        "add.s64 ta, ta0, 1024;\n"
        "wgmma.mma_async.sync.aligned.m64n192k16.f32.bf16.bf16 {%0, %1, %2, %3, %4, %5, %6, %7, %8, %9, %10, %11, %12, %13, %14, %15, %16, %17, %18, %19, %20, %21, %22, %23, %24, %25, %26, %27, %28, %29, %30, %31, %32, %33, %34, %35, %36, %37, %38, %39, %40, %41, %42, %43, %44, %45, %46, %47, %48, %49, %50, %51, %52, %53, %54, %55, %56, %57, %58, %59, %60, %61, %62, %63, %64, %65, %66, %67, %68, %69, %70, %71, %72, %73, %74, %75, %76, %77, %78, %79, %80, %81, %82, %83, %84, %85, %86, %87, %88, %89, %90, %91, %92, %93, %94, %95}, ta, tb, p1, 1, 1, 0, 1;\n"
        "add.s64 tb, tb0, 576;\n"
        "add.s64 ta, ta0, 1026;\n"
        "wgmma.mma_async.sync.aligned.m64n192k16.f32.bf16.bf16 {%0, %1, %2, %3, %4, %5, %6, %7, %8, %9, %10, %11, %12, %13, %14, %15, %16, %17, %18, %19, %20, %21, %22, %23, %24, %25, %26, %27, %28, %29, %30, %31, %32, %33, %34, %35, %36, %37, %38, %39, %40, %41, %42, %43, %44, %45, %46, %47, %48, %49, %50, %51, %52, %53, %54, %55, %56, %57, %58, %59, %60, %61, %62, %63, %64, %65, %66, %67, %68, %69, %70, %71, %72, %73, %74, %75, %76, %77, %78, %79, %80, %81, %82, %83, %84, %85, %86, %87, %88, %89, %90, %91, %92, %93, %94, %95}, ta, tb, p1, 1, 1, 0, 1;\n"
        "add.s64 tb, tb0, 640;\n"
        "add.s64 ta, ta0, 1028;\n"
        "wgmma.mma_async.sync.aligned.m64n192k16.f32.bf16.bf16 {%0, %1, %2, %3, %4, %5, %6, %7, %8, %9, %10, %11, %12, %13, %14, %15, %16, %17, %18, %19, %20, %21, %22, %23, %24, %25, %26, %27, %28, %29, %30, %31, %32, %33, %34, %35, %36, %37, %38, %39, %40, %41, %42, %43, %44, %45, %46, %47, %48, %49, %50, %51, %52, %53, %54, %55, %56, %57, %58, %59, %60, %61, %62, %63, %64, %65, %66, %67, %68, %69, %70, %71, %72, %73, %74, %75, %76, %77, %78, %79, %80, %81, %82, %83, %84, %85, %86, %87, %88, %89, %90, %91, %92, %93, %94, %95}, ta, tb, p1, 1, 1, 0, 1;\n"
        "add.s64 tb, tb0, 704;\n"
        "add.s64 ta, ta0, 1030;\n"
        "wgmma.mma_async.sync.aligned.m64n192k16.f32.bf16.bf16 {%0, %1, %2, %3, %4, %5, %6, %7, %8, %9, %10, %11, %12, %13, %14, %15, %16, %17, %18, %19, %20, %21, %22, %23, %24, %25, %26, %27, %28, %29, %30, %31, %32, %33, %34, %35, %36, %37, %38, %39, %40, %41, %42, %43, %44, %45, %46, %47, %48, %49, %50, %51, %52, %53, %54, %55, %56, %57, %58, %59, %60, %61, %62, %63, %64, %65, %66, %67, %68, %69, %70, %71, %72, %73, %74, %75, %76, %77, %78, %79, %80, %81, %82, %83, %84, %85, %86, %87, %88, %89, %90, %91, %92, %93, %94, %95}, ta, tb, p1, 1, 1, 0, 1;\n"
        "}\n"
        : "+f"(d[0]), "+f"(d[1]), "+f"(d[2]), "+f"(d[3]), "+f"(d[4]), "+f"(d[5]), "+f"(d[6]), "+f"(d[7]), "+f"(d[8]), "+f"(d[9]), "+f"(d[10]), "+f"(d[11]), "+f"(d[12]), "+f"(d[13]), "+f"(d[14]), "+f"(d[15]), "+f"(d[16]), "+f"(d[17]), "+f"(d[18]), "+f"(d[19]), "+f"(d[20]), "+f"(d[21]), "+f"(d[22]), "+f"(d[23]), "+f"(d[24]), "+f"(d[25]), "+f"(d[26]), "+f"(d[27]), "+f"(d[28]), "+f"(d[29]), "+f"(d[30]), "+f"(d[31]), "+f"(d[32]), "+f"(d[33]), "+f"(d[34]), "+f"(d[35]), "+f"(d[36]), "+f"(d[37]), "+f"(d[38]), "+f"(d[39]), "+f"(d[40]), "+f"(d[41]), "+f"(d[42]), "+f"(d[43]), "+f"(d[44]), "+f"(d[45]), "+f"(d[46]), "+f"(d[47]), "+f"(d[48]), "+f"(d[49]), "+f"(d[50]), "+f"(d[51]), "+f"(d[52]), "+f"(d[53]), "+f"(d[54]), "+f"(d[55]), "+f"(d[56]), "+f"(d[57]), "+f"(d[58]), "+f"(d[59]), "+f"(d[60]), "+f"(d[61]), "+f"(d[62]), "+f"(d[63]), "+f"(d[64]), "+f"(d[65]), "+f"(d[66]), "+f"(d[67]), "+f"(d[68]), "+f"(d[69]), "+f"(d[70]), "+f"(d[71]), "+f"(d[72]), "+f"(d[73]), "+f"(d[74]), "+f"(d[75]), "+f"(d[76]), "+f"(d[77]), "+f"(d[78]), "+f"(d[79]), "+f"(d[80]), "+f"(d[81]), "+f"(d[82]), "+f"(d[83]), "+f"(d[84]), "+f"(d[85]), "+f"(d[86]), "+f"(d[87]), "+f"(d[88]), "+f"(d[89]), "+f"(d[90]), "+f"(d[91]), "+f"(d[92]), "+f"(d[93]), "+f"(d[94]), "+f"(d[95])
        : "l"(descA), "n"(AOFF >> 4), "l"(descB), "n"(BOFF >> 4));
}

struct Params {
    const __nv_bfloat16* x;
    const __nv_bfloat16* wqkv;
    const __nv_bfloat16* wo;
    const __nv_bfloat16* logit_scale;
    const __nv_bfloat16* cpb_w1;
    const __nv_bfloat16* cpb_w2;
    const __nv_bfloat16* rel_coords;
    const int*           rel_idx;
    const __nv_bfloat16* mask;
    __nv_bfloat16*       out;
    unsigned long long   z1;
    int                  npair;
    uint32_t             need;
    int                  nq, nr;
    int                  t1;
};

__device__ __forceinline__ void finish(uint32_t total) {
    __threadfence();
    if (atomicAdd(&g_done, 1u) == total - 1) {
        for (int i = 0; i < NWS; i++) g_cnt[i] = 0;
        g_done = 0;
    }
}

__global__ void __launch_bounds__(NTHREADS, 1)
swin_window_attn_kernel(const Params P, const __grid_constant__ CUtensorMap xmap, const __grid_constant__ CUtensorMap xmap4,
                        const __grid_constant__ CUtensorMap xmap3,
                        const __grid_constant__ CUtensorMap omap, const __grid_constant__ CUtensorMap wmap,
                        const __grid_constant__ CUtensorMap smap, const __grid_constant__ CUtensorMap omapb,
                        const __grid_constant__ CUtensorMap xmapa, const __grid_constant__ CUtensorMap xmapb,
                        const __grid_constant__ CUtensorMap smap3, const __grid_constant__ CUtensorMap wraw) {
    extern __shared__ __align__(1024) uint8_t smem[];
    constexpr uint32_t sbase = 1024;
    if (smem_u32(smem) != sbase) return;
    const int tid = threadIdx.x;
    const int wg = __shfl_sync(0xffffffffu, tid >> 7, 0);
    const int warp = __shfl_sync(0xffffffffu, (tid >> 5) & 3, 0);
    const int lane = tid & 31;
    const int g = lane >> 2, c = lane & 3;

    TR(26, wg);
    const bool attn = (int)blockIdx.x < 2 * P.npair;
    const int pair = blockIdx.x >> 1, half = blockIdx.x & 1;
    const int nwin = P.nq + (pair < P.nr ? 1 : 0);
    const int ntiles = (nwin * TOK + 63) >> 6;
    const uint32_t bars = sbase + SM_BAR;
    const int t0 = min(warp * 16 + g, TOK - 1), t1 = min(warp * 16 + g + 8, TOK - 1);
    int ridx[26];
    uint32_t rc, w2[16];
    uint4 w1[4];
    if (attn && (wg == 1 || wg == 2)) {
        rc = reinterpret_cast<const uint32_t*>(P.rel_coords)[min(tid - 128, 168)];
#pragma unroll
        for (int i = 0; i < 4; i++) w1[i] = reinterpret_cast<const uint4*>(P.cpb_w1)[i];
#pragma unroll
        for (int u = 0; u < 16; u++) w2[u] = reinterpret_cast<const uint32_t*>(P.cpb_w2)[2 * u + half];
#pragma unroll
        for (int rh = 0; rh < 2; rh++) {
            const int* ri = P.rel_idx + (rh ? t1 : t0) * TOK;
#pragma unroll
            for (int j = 0; j < 12; j++) ridx[13 * rh + j] = ri[8 * (j >> 1) + 2 * c + (j & 1)];
            ridx[13 * rh + 12] = ri[48];
        }
    }
    {
        if (tid == 416) {
            const CUtensorMap* maps[4] = {attn ? &smap : &omap, &smap3, &xmapa, &xmapb};
#pragma unroll
            for (int i = 0; i < 4; i++) asm volatile("prefetch.tensormap [%0];\n" :: "l"(reinterpret_cast<uint64_t>(maps[i])) : "memory");
        }
        if (tid == 384) {
            for (int b = 0; b < 4; b++) {
                mbar_init(bars + B_XFULL + b * 8, 2);
                mbar_init(bars + B_QKRAW + b * 8, 4);
                mbar_init(bars + B_VRAW + b * 8, 4);
                mbar_init(bars + B_VFREE + b * 8, 2);
                mbar_init(bars + B_QKFREE + b * 8, 4);
                mbar_init(bars + B_ODONE + b * 8, 4);
            }
            mbar_init(bars + B_WFULL, 2);
            mbar_init(bars + B_WRAW, 1);
            mbar_init(bars + B_MFULL, 1);
            mbar_init(bars + B_MFULL + 8, 1);
            mbar_init(bars + B_MCONS, 4);
            for (int b = 0; b < 4; b++) mbar_init(bars + B_STORED + b * 8, 1);
            for (int b = 0; b < 6; b++) {
                mbar_init(sbase + SM_PBAR + b * 8, 1);
                mbar_init(sbase + SM_PBAR + 48 + b * 8, PSTORE ? 1 : 4);
                mbar_init(sbase + SM_PBAR + 104 + b * 8, 4);
            }
            mbar_init(sbase + SM_PBAR + 96, 13);
            asm volatile("fence.mbarrier_init.release.cluster;\n" ::: "memory");
        }
        if (wg == 3) {
            if (attn) *reinterpret_cast<uint4*>(smem + SM_V + warp * V_STRIDE + (lane < 16 ? lane * 16 : V_STRIDE - 64 + (lane & 3) * 16)) = make_uint4(0, 0, 0, 0);
            fence_async_smem();
        }
        __syncthreads();
        TR(26, 4 + wg);
            if (attn && tid == 0) {
                mbar_arrive_expect_tx(bars + B_WRAW, 2 * 192 * O_PITCH);
#pragma unroll
                for (int i = 0; i < 4; i++) {
                    const int q = (i + pair) & 3;
                    tma_3d(sbase + q * 96 * O_PITCH, &wraw, bars + B_WRAW, 0, 2 * (q >> 1) + half, (q & 1) * 96);
                }
                int wh = 0, ww = pair;
#pragma unroll
                for (int j = 0; j < NEARLY; j++) {
                    if (ww < NWS - 1) {
                        const uint32_t bar = bars + B_XFULL + (j ? j - 1 : 0) * 8;
                        if (j >= 2) mbar_arrive(bar);
                        mbar_arrive_expect_tx(bar, 3 * XCH);
#pragma unroll
                        for (int ch = 0; ch < 3; ch++)
                            tma_3d(sbase + SM_QK + j * XCH + ch * QK_CHUNK, &xmap, bar, ch * 64, 7 * ww + 3, 7 * wh + 3);
                    }
                    ww += P.npair; if (ww >= NWS) { ww -= NWS; wh++; }
                    if (j == 1) {
                        mbar_arrive_expect_tx(bars + B_MFULL, 4816);
                        asm volatile("cp.async.bulk.shared::cluster.global.mbarrier::complete_tx::bytes [%0], [%1], 4816, [%2];\n"
                                     :: "r"(sbase + SM_MASK), "l"(reinterpret_cast<const char*>(P.mask) + (((uint32_t)pair * 4802u) & ~15u)),
                                        "r"(bars + B_MFULL) : "memory");
                        mbar_arrive_expect_tx(bars + B_WFULL, 5 * W_ATOM);
#pragma unroll
                        for (int a = 1; a < 6; a++)
                            tma_2d(sbase + SM_WV + a * W_ATOM, &wmap, bars + B_WFULL, 384 + half * 96 + a * 16, 0);
                    }
                }
            }
        __syncwarp();
        TR(26, 13);
    }

    auto permute_w = [&]() {
        uint4 w[3][4];
        TR(26, 16 + wg);
        mbar_wait(bars + B_WRAW, 0);
        TR(26, 20 + wg);
#pragma unroll
        for (int it = 0; it < 3; it++) {
            const int o = ((tid >> 5) * 3 + it) * 4 + (lane >> 3);
            const uint8_t* src = smem + ((o / 6) * 8 + (lane & 7)) * O_PITCH + (o % 6) * 16;
#pragma unroll
            for (int m = 0; m < 4; m++) w[it][m] = *reinterpret_cast<const uint4*>(src + (m >> 1) * 192 * O_PITCH + (m & 1) * 96);
        }
        asm volatile("bar.sync 2, 384;\n" ::: "memory");
        if (tid == 0) {
            fence_async_smem();
            TR(26, 24);
            mbar_arrive_expect_tx(bars + B_WFULL, W_ATOM);
            tma_2d(sbase + SM_WV, &wmap, bars + B_WFULL, 384 + half * 96, 0);
        }
#pragma unroll
        for (int it = 0; it < 3; it++) {
            const int o = ((tid >> 5) * 3 + it) * 4 + (lane >> 3);
            const uint32_t d = sbase + (o % 6) * 2 * W_ATOM + ((o / 6) * 8 + (lane & 7)) * 32 + ((lane >> 2) & 1) * 16;
            sts128(d, w[it][0].x, w[it][1].x, w[it][2].x, w[it][3].x);
            sts128(d ^ 16, w[it][0].y, w[it][1].y, w[it][2].y, w[it][3].y);
            sts128(d + W_ATOM, w[it][0].z, w[it][1].z, w[it][2].z, w[it][3].z);
            sts128((d ^ 16) + W_ATOM, w[it][0].w, w[it][1].w, w[it][2].w, w[it][3].w);
        }
    };
    static_assert(2 * 192 * O_PITCH <= 13 * W_ATOM, "raw weights");
    const uint32_t nfinish = gridDim.x + 2 * P.npair;
#define PROJ_SCHEDULE                                                                                   \
    int bid = blockIdx.x;                                                                               \
    asm volatile("" : "+r"(bid));                      \
    const bool at = bid < 2 * P.npair;                                                                  \
    const int tile0 = at ? P.t1 + bid : bid - 2 * P.npair;                                              \
    const int tstep = at ? 2 * P.npair : (int)gridDim.x - 2 * P.npair;                                  \
    const int tend = at ? TILES : P.t1;
    if (wg == 3) {
        asm volatile("setmaxnreg.dec.sync.aligned.u32 %0;\n" :: "n"(REG_H));
        if (!elect_one()) return;
        if (warp == 0) {
          if (attn) {
            const int kmax = (64 * ntiles + 63) / TOK;
            int wh = 0, ww = pair;
            int ph2 = (pair + PF_DIST * P.npair) / NWS, pw2 = pair + PF_DIST * P.npair - ph2 * NWS;
#pragma unroll 1
            for (int k = -4; k + 4 <= kmax; k++) {
                const int row0 = (k + 4) * TOK;
                const uint32_t dst = sbase + SM_QK + (k & 3) * XCH, bar = bars + B_XFULL + ((row0 >> 6) & 3) * 8;
                const bool alone = (row0 & 63) >= 64 - TOK && (row0 & 63) < TOK;
                const int x0 = 7 * ww + 3, y0 = 7 * wh + 3;
                const bool done = k < NEARLY - 4 && ww < NWS - 1;
                mbar_wait(bars + B_QKFREE + (k & 3) * 8, (k >> 2) & 1);
                if (alone && !done) mbar_arrive(bar);
                if (k + 4 >= nwin) {
                    mbar_arrive(bar);
                    continue;
                }
                TR(20, k + 4);
                const bool inner = wh < NWS - 1 && ww < NWS - 1;
                if (done) {
                } else if (XSPLIT && inner && (row0 & 63) >= 64 - 21) {
                    const uint32_t bar2 = bars + B_XFULL + (((row0 >> 6) + 1) & 3) * 8;
                    mbar_arrive_expect_tx(bar, 3 * 21 * 128);
#pragma unroll
                    for (int ch = 0; ch < 3; ch++) tma_3d(dst + ch * QK_CHUNK, &xmapa, bar, ch * 64, x0, y0);
                    asm volatile("mbarrier.expect_tx.relaxed.cta.shared::cta.b64 [%0], %1;\n" :: "r"(bar2), "r"(3 * 28 * 128) : "memory");
#pragma unroll
                    for (int ch = 0; ch < 3; ch++) tma_3d(dst + ch * QK_CHUNK + 21 * 128, &xmapb, bar2, ch * 64, x0, y0 + 3);
                } else if (inner) {
                    mbar_arrive_expect_tx(bar, 3 * XCH);
#pragma unroll
                    for (int ch = 0; ch < 3; ch++) tma_3d(dst + ch * QK_CHUNK, &xmap, bar, ch * 64, x0, y0);
                } else if (ww < NWS - 1) {
                    mbar_arrive_expect_tx(bar, 3 * XCH);
#pragma unroll
                    for (int ch = 0; ch < 3; ch++) {
                        tma_3d(dst + ch * QK_CHUNK, &xmapb, bar, ch * 64, x0, y0);
                        tma_3d(dst + ch * QK_CHUNK + 28 * 128, &xmapa, bar, ch * 64, x0, 0);
                    }
                } else {
                    mbar_arrive_expect_tx(bar, 3 * XCH);
                    const int x1 = (ww == NWS - 1) ? 0 : x0 + 4;
#pragma unroll 1
                    for (int i = 0; i < 7; i++) {
                        const int y = (y0 + i >= IMG) ? y0 + i - IMG : y0 + i;
#pragma unroll
                        for (int ch = 0; ch < 3; ch++) {
                            tma_3d(dst + ch * QK_CHUNK + i * 896, &xmap4, bar, ch * 64, x0, y);
                            tma_3d(dst + ch * QK_CHUNK + i * 896 + 512, &xmap3, bar, ch * 64, x1, y);
                        }
                    }
                }
                if (NOPF) {
                } else if (half == 0) {
                    if (ph2 < NWS) {
#pragma unroll
                        for (int ch = 0; ch < 3; ch++)
                            asm volatile("cp.async.bulk.prefetch.tensor.3d.L2.global.tile [%0, {%1, %2, %3}];\n"
                                         :: "l"(reinterpret_cast<uint64_t>(&xmap)), "r"(ch * 64), "r"(7 * pw2 + 3), "r"(7 * ph2 + 3)
                                         : "memory");
                    }
                } else if (ph2 < NWS) {
                    asm volatile("cp.async.bulk.prefetch.L2.global [%0], %1;\n"
                                 :: "l"(reinterpret_cast<const char*>(P.mask) + (((uint32_t)(ph2 * NWS + pw2) * 4802u) & ~15u)),
                                    "r"(4800) : "memory");
                }
                ww += P.npair; if (ww >= NWS) { ww -= NWS; wh++; }
                pw2 += P.npair; if (pw2 >= NWS) { pw2 -= NWS; ph2++; }
            }
            mbar_wait(sbase + SM_PBAR + 96, 0);
            fence_async_smem();
          }
            PROJ_SCHEDULE
            int st = 0, ready = -1;
            uint32_t ph = 1;
#pragma unroll 1
            for (int t = tile0; t < tend; t += tstep) {
                const int p0 = (t < TILES_A) ? SEG_B + 64 * t : 64 * (t - TILES_A);
                const int w1 = (t < TILES_A) ? min((64 * t + 63) / (7 * IMG), NWS - 1) : NWS - 1;
                if (ready < w1) {
                    ready = max(ready, w1 - 2);
#pragma unroll 1
                    while (ready < w1) {
                        ready++;
#pragma unroll 1
                        for (uint32_t n = 0; n < (1u << 22); n++) {
                            uint32_t a;
                            asm volatile("ld.acquire.gpu.global.u32 %0, [%1];\n" : "=r"(a) : "l"(g_cnt + ready) : "memory");
                            if (a >= P.need) break;
                            __nanosleep(64);
                        }
                    }
                    asm volatile("fence.proxy.async.global;\n" ::: "memory");
                }
                mbar_wait(sbase + SM_PBAR + 48 + st * 8, ph);
                mbar_arrive_expect_tx(sbase + SM_PBAR + st * 8, STAGE_BYTES);
#pragma unroll
                for (int ch = 0; ch < 3; ch++)
                    tma_2d(sbase + SM_STAGE + st * STAGE_BYTES + ch * 8192, &omap, sbase + SM_PBAR + st * 8, ch * 64, p0);
                if (++st == 6) { st = 0; ph ^= 1; }
            }
            finish(nfinish);
        } else if (!attn) {
        } else if (warp == 1) {
          {
            const uint16_t mlast = reinterpret_cast<const uint16_t*>(P.mask)[NWINDOWS * TOK * TOK - 1];
            auto load_mask = [&](int k) {
                const int win = pair + k * P.npair;
                uint32_t bytes = 4816;
                if (win == NWINDOWS - 1) {
                    bytes = 4800;
                    asm volatile("st.shared.u16 [%0], %1;\n" :: "r"(sbase + SM_MASK + 4800), "h"(mlast) : "memory");
                }
                TR(25, k);
                mbar_arrive_expect_tx(bars + B_MFULL + (k & 1) * 8, bytes);
                asm volatile("cp.async.bulk.shared::cluster.global.mbarrier::complete_tx::bytes [%0], [%1], %2, [%3];\n"
                             :: "r"(sbase + SM_MASK),
                                "l"(reinterpret_cast<const char*>(P.mask) + (((uint32_t)win * 4802u) & ~15u)),
                                "r"(bytes), "r"(bars + B_MFULL + (k & 1) * 8) : "memory");
            };
#pragma unroll 1
            for (int k = 1; k < nwin; k++) {
                mbar_wait(bars + B_MCONS, (k + 1) & 1);
                fence_async_smem();
                load_mask(k);
            }
          }
        } else if (warp == 2) {
            int wh = 0, ww = pair;
#pragma unroll 1
            for (int k = 0; k < nwin; k++) {
                mbar_wait(bars + B_STORED + (k & 1) * 8, (k >> 1) & 1);
                mbar_arrive(bars + B_PUBD + (k & 1) * 8);
                asm volatile("red.release.gpu.global.add.u32 [%0], 1;\n" :: "l"(g_cnt + wh) : "memory");
                TR(24, k);
                ww += P.npair; if (ww >= NWS) { ww -= NWS; wh++; }
            }
            finish(nfinish);
        } else {
            for (int t = 0; t < 3; t++) mbar_arrive_n(bars + B_VFREE + t * 8, 2);
            int wh = 0, ww = pair;
#pragma unroll 1
            for (int k = 0; k < nwin; k++) {
                const uint32_t src = sbase + SM_V + (k & 3) * V_STRIDE;
                const int x0 = 7 * ww + 3, y0 = 7 * wh + 3;
                mbar_wait(bars + B_ODONE + (k & 3) * 8, (k >> 2) & 1);
                fence_async_smem();
                TR(22, k);
                tma_store_4d(&smap, src, 0, half, x0, y0);
                tma_store_4d(&smap3, src + 28 * O_PITCH + 64, 0, half, x0, wh == NWS - 1 ? 0 : y0 + 4);
                if (ww == NWS - 1) {
#pragma unroll 1
                    for (int i = 0; i < 7; i++) {
                        char* const d = reinterpret_cast<char*>(P.out) + (uint32_t)((y0 + i >= IMG ? y0 + i - IMG : y0 + i) * IMG) * 384u + half * 192;
#pragma unroll
                        for (int j = 0; j < 3; j++)
                            asm volatile("cp.async.bulk.global.shared::cta.bulk_group [%0], [%1], 192;\n"
                                         :: "l"(d + j * 384), "r"(src + (7 * i + 4 + j) * O_PITCH + (i >= 4 ? 64 : 0)) : "memory");
                    }
                }
                asm volatile("cp.async.bulk.commit_group;\n" ::: "memory");
                asm volatile("cp.async.bulk.wait_group.read 0;\n" ::: "memory");
                {
                    const int row0 = (k + 4) * TOK;
                    mbar_arrive_n(bars + B_VFREE + ((row0 >> 6) & 3) * 8, ((row0 & 63) >= 64 - TOK && (row0 & 63) < TOK) ? 2 : 1);
                }
                TR(23, k);
                asm volatile("cp.async.bulk.wait_group 0;\n" ::: "memory");
                asm volatile("fence.proxy.async.global;\n" ::: "memory");
                mbar_wait(bars + B_PUBD + (k & 1) * 8, ((k >> 1) + 1) & 1);
                mbar_arrive(bars + B_STORED + (k & 1) * 8);
                ww += P.npair; if (ww >= NWS) { ww -= NWS; wh++; }
            }
            mbar_arrive(sbase + SM_PBAR + 96);
        }
        if (PSTORE && warp == 1) {
            PROJ_SCHEDULE
            int st = 0, prev = -1;
            uint32_t ph = 0;
#pragma unroll 1
            for (int t = tile0; t < tend; t += tstep) {
                const int p0 = (t < TILES_A) ? SEG_B + 64 * t : 64 * (t - TILES_A);
                mbar_wait(sbase + SM_PBAR + 104 + st * 8, ph);
                fence_async_smem();
#pragma unroll
                for (int ch = 0; ch < 3; ch++)
                    asm volatile("cp.async.bulk.tensor.2d.global.shared::cta.tile.bulk_group [%0, {%2, %3}], [%1];\n"
                                 :: "l"(reinterpret_cast<uint64_t>(t < TILES_A ? &omap : &omapb)),
                                    "r"(sbase + SM_STAGE + st * STAGE_BYTES + ch * 8192), "r"(ch * 64), "r"(p0) : "memory");
                asm volatile("cp.async.bulk.commit_group;\n" ::: "memory");
                if (prev >= 0) {
                    asm volatile("cp.async.bulk.wait_group.read 1;\n" ::: "memory");
                    mbar_arrive(sbase + SM_PBAR + 48 + prev * 8);
                }
                prev = st;
                if (++st == 6) { st = 0; ph ^= 1; }
            }
            asm volatile("cp.async.bulk.wait_group 0;\n" ::: "memory");
            TR(30, 0);
        }
        return;
    }
    if (!attn) {
        asm volatile("setmaxnreg.inc.sync.aligned.u32 160;\n");
    } else if (wg == 0) {
        asm volatile("setmaxnreg.inc.sync.aligned.u32 %0;\n" :: "n"(REG_G));
        float qs = 1.f;
        if (c < 2) qs = round_bf16(expf(round_bf16(fminf(fmaxf(__bfloat162float(P.logit_scale[2 * half + c]), -100.f), 4.6052f)))) * LOG2E;
        uint32_t xa[12][4];
        float accA[48], accB[48], accV[48];
        uint32_t rho = warp * 16 + (lane & 15), rq = warp * 16 + g;
        uint32_t hi = lane >> 4, lane0 = lane == 0, c2 = 2 * c;
        asm volatile("" : "+r"(hi), "+r"(lane0), "+r"(c2));
        auto row_addr = [&](uint32_t (&ax)[4], uint32_t r) {
            ax[0] = sbase + SM_QK + r * 128 + (((r & 7) ^ hi) << 4);
#pragma unroll
            for (int i = 1; i < 4; i++) ax[i] = ax[0] ^ (32 * i);
        };
#define XADDR(ax, s) ((ax)[((s) & 3) ^ (((s) >> 1) & 2)] + ((s) >> 2) * QK_CHUNK)
        uint64_t descW = make_desc(sbase, W_ATOM, 256, 3);
        const uint32_t zero = (uint32_t)P.z1;
        const uint32_t vbase = sbase + SM_V + (lane >> 4) * GRP;
        uint32_t ones = 0x3F803F80u | zero, ones2 = ones | (zero >> 1);
        asm volatile("" : "+r"(ones), "+r"(ones2));
        permute_w();
        TR(26, 10);
        {
            uint32_t ax[4];
            row_addr(ax, rho);
            mbar_wait(bars + B_XFULL, 0);
#pragma unroll
            for (int s = 0; s < 12; s++) ldsm_x4(xa[s], XADDR(ax, s));
        }
        TR(26, 8);
        asm volatile("bar.sync 7, 384;\n" ::: "memory");
        fence_async_smem();
        TR(26, 9);
        wgmma_fence();
        mma_qkv_a<SM_WA, 0>(accA, xa, descW);
        mma_qkv_b<SM_WA, 6>(accA, xa, descW);
        wgmma_commit();
        mma_qkv_a<SM_WB, 0>(accB, xa, descW);
        wgmma_commit();
        TR(26, 11);
        mbar_wait(bars + B_WFULL, 0);
        TR(26, 12);
        for (int t = 0; t < ntiles; t++) {
            descW += P.z1;
            float ss[4];
            uint32_t pk[2][24];
            wgmma_wait<1>();
            reg_fence(accA);
            TR(0, t);
#pragma unroll
            for (int i = 0; i < 4; i++) ss[i] = accA[i] * accA[i];
#pragma unroll
            for (int i = 4; i < 48; i++) ss[i & 3] = fmaf(accA[i], accA[i], ss[i & 3]);
            mma_qkv_b<SM_WB, 6>(accB, xa, descW);
            wgmma_commit();
            sched_fence(zero, __float_as_uint(ss[0]), __float_as_uint(ss[1]), __float_as_uint(ss[2]), __float_as_uint(ss[3]));
#pragma unroll
            for (int j = 0; j < 12; j++) {
                pk[0][j] = pack_bf16(accA[4 * j], accA[4 * j + 1]);
                pk[1][j] = pack_bf16(accA[4 * j + 2], accA[4 * j + 3]);
                asm volatile("" : "+r"(pk[0][j]), "+r"(pk[1][j]));
            }
            wgmma_fence();
            mma_qkv_a<SM_WV, 0>(accV, xa, descW);
            wgmma_commit();
            uint32_t av = vbase + rho * 16 + ((rho * 1338) >> 16) * (V_STRIDE - GRP);
            uint32_t aq[2];
            aq[0] = sbase + SM_QK + rq * 128 + (((rq & 7) ^ c2) << 4);
            aq[1] = aq[0] + 1024;
            if (rq >= 4 * TOK - 8) aq[1] = (aq[1] - QK_CHUNK) ^ 64;
            rho += 64;
            if (rho >= 4 * TOK) rho -= 4 * TOK;
            rq += 64;
            if (rq >= 4 * TOK) rq -= 4 * TOK;
            uint32_t an[4];
            row_addr(an, rho);
            const uint32_t bt = bars + (t & 3) * 8, pt = (t >> 2) & 1, bn = bars + ((t + 1) & 3) * 8, pn = ((t + 1) >> 2) & 1;
            const uint32_t xok = mbar_test(bn + B_XFULL, pn);
            wgmma_wait<1>();
            reg_fence(accB);
#pragma unroll
            for (int i = 0; i < 48; i++) ss[i & 3] = fmaf(accB[i], accB[i], ss[i & 3]);
            ss[0] += ss[1]; ss[2] += ss[3];
            mma_qkv_b<SM_WV, 6>(accV, xa, descW);
            wgmma_commit();
            sched_fence(zero, __float_as_uint(ss[0]), __float_as_uint(ss[2]), av, aq[0], aq[1], an[0], an[1], an[2], an[3], rho, rq);
            const float f0 = rsqrt_ftz(ss[0] + 1e-12f) * qs, f1 = rsqrt_ftz(ss[2] + 1e-12f) * qs;
            const uint32_t f2[2] = {pack_bf16(f0, f0), pack_bf16(f1, f1)};
#pragma unroll
            for (int j = 0; j < 12; j++) {
                pk[0][12 + j] = pack_bf16(accB[4 * j], accB[4 * j + 1]);
                pk[1][12 + j] = pack_bf16(accB[4 * j + 2], accB[4 * j + 3]);
            }
            auto qk_store = [&](int u0, int u1) {
#pragma unroll
                for (int u = u0; u < u1; u++)
#pragma unroll
                    for (int r = 0; r < 2; r++)
                        sts128((aq[r] ^ ((u & 1) * 16 + (u & 2) * 32)) + (u >> 1) * QK_CHUNK,
                               hmul2_bf16(pk[r][4 * u], f2[r]), hmul2_bf16(pk[r][4 * u + 1], f2[r]),
                               hmul2_bf16(pk[r][4 * u + 2], f2[r]), hmul2_bf16(pk[r][4 * u + 3], f2[r]));
            };
            qk_store(0, QSPLIT);
            TR(1, t);
            mbar_wait_unless(xok, bn + B_XFULL, pn);
            TR(2, t);
            wgmma_wait<1>();
#pragma unroll
            for (int s = 0; s < 6; s++) ldsm_x4(xa[s], XADDR(an, s));
            qk_store(QSPLIT, 6);
            __syncwarp();
            mbar_arrive_if(bt + B_QKRAW, lane0);
            TR(3, t);
            wgmma_fence();
            mma_qkv_a<SM_WA, 0>(accA, xa, descW);
            wgmma_commit();
            wgmma_wait<1>();
            reg_fence(accV);
#pragma unroll
            for (int s = 6; s < 12; s++) ldsm_x4(xa[s], XADDR(an, s));
            const uint32_t vok = mbar_test(bt + B_VFREE, pt);
            uint32_t vp[24];
#pragma unroll
            for (int j = 0; j < 24; j++) vp[j] = pack_bf16(accV[2 * j], accV[2 * j + 1]);
            reg_fence(vp);
            wgmma_fence();
            mma_qkv_b<SM_WA, 6>(accA, xa, descW);
            wgmma_commit();
            mbar_wait_unless(vok, bt + B_VFREE, pt);
            if (t == 2) asm volatile("bar.sync 3, 384;\n" ::: "memory");
#pragma unroll
            for (int p = 0; p < 6; p++)
                stsm_x4(av + (p < 3 ? 2 * p : 2 * p + 1) * GRP, vp[4 * p], vp[4 * p + 1], vp[4 * p + 2], vp[4 * p + 3]);
            stsm_x2(av + 6 * GRP, ones, ones2);
            __syncwarp();
            mbar_arrive_if(bt + B_VRAW, lane0);
            TR(4, t);
            wgmma_fence();
            mma_qkv_a<SM_WB, 0>(accB, xa, descW);
            wgmma_commit();
        }
        wgmma_wait<0>();
        reg_fence(accA);
        reg_fence(accB);
        wg_bar(2);
        asm volatile("setmaxnreg.dec.sync.aligned.u32 160;\n");
    } else {
        if (REG_A > 128) asm volatile("setmaxnreg.inc.sync.aligned.u32 %0;\n" :: "n"(REG_A));
        {
            const float c0 = bf16lo(rc), c1 = bf16hi(rc);
            float a0 = 0.f, a1 = 0.f;
#pragma unroll
            for (int u = 0; u < 16; u++) {
                const uint32_t p = reinterpret_cast<const uint32_t*>(w1)[u >> 1], q = reinterpret_cast<const uint32_t*>(w1)[8 + (u >> 1)];
                float h = round_bf16(c0 * ((u & 1) ? bf16hi(p) : bf16lo(p)) + c1 * ((u & 1) ? bf16hi(q) : bf16lo(q)));
                h = fmaxf(h, 0.f);
                a0 += h * bf16lo(w2[u]);
                a1 += h * bf16hi(w2[u]);
            }
            const float s0 = round_bf16(__fdividef(1.f, 1.f + expf(-round_bf16(a0))));
            const float s1 = round_bf16(__fdividef(1.f, 1.f + expf(-round_bf16(a1))));
            if (tid - 128 < 169) sts32(sbase + SM_TAB + (tid - 128) * 4, pack_bf16(exp2f(fmaf(s0, 16.f * LOG2E, -12.f)), exp2f(fmaf(s1, 16.f * LOG2E, -12.f))));
        }
        permute_w();
        asm volatile("bar.arrive 7, 384;\n" ::: "memory");
        asm volatile("bar.sync 1, 256;\n" ::: "memory");
        uint32_t eb[26];
        {
            const uint32_t* tab = reinterpret_cast<const uint32_t*>(smem + SM_TAB);
#pragma unroll
            for (int i = 0; i < 13; i++) {
                const uint32_t lo = tab[min(max(ridx[i < 12 ? 13 * (i & 1) + (i & ~1) : 12], 0), 168)];
                const uint32_t hi = tab[min(max(ridx[i < 12 ? 13 * (i & 1) + (i | 1) : 25], 0), 168)];
                eb[i]      = prmt(lo, hi, 0x5410);
                eb[13 + i] = prmt(lo, hi, 0x7632);
            }
            if (c != 0) eb[12] = eb[25] = 0;
        }
        uint32_t slow = 0;
#pragma unroll
        for (int h = 0; h < 2; h++)
            if (!(expf(__bfloat162float(P.logit_scale[2 * half + h])) <= TAU_FAST)) slow = 1;
        reg_fence(eb);
        asm volatile("bar.arrive 3, 384;\n" ::: "memory");
        const bool ov = warp * 16 + (lane & 15) < TOK;
        const int orow = warp * 16 + (lane & 15);
        const uint32_t orel = sbase + (ov ? SM_V + orow * O_PITCH + (orow >= 28 ? 64 : 0) : SM_DUMP + (lane & 7) * 16) + (lane >> 4) * 16;
        const uint32_t omul = ov ? V_STRIDE : 0;
        const uint64_t descK0 = make_desc(sbase + SM_QK, 16, 1024, 1);
        const uint64_t descV0 = make_desc(sbase + SM_V, 128, GRP, 0);
        uint32_t ma = sbase + SM_MASK + (tid & 127) * 16;
        if (PIN & 2) ma = __shfl_sync(0xffffffffu, ma, lane);
        slow = __shfl_sync(0xffffffffu, slow, 0);
        auto mask_load = [&]() {
            uint32_t v[12];
            asm volatile("ld.shared.v4.b32 {%0, %1, %2, %3}, [%4];\n" : "=r"(v[0]), "=r"(v[1]), "=r"(v[2]), "=r"(v[3]) : "r"(ma) : "memory");
            asm volatile("ld.shared.v4.b32 {%0, %1, %2, %3}, [%4+2048];\n" : "=r"(v[4]), "=r"(v[5]), "=r"(v[6]), "=r"(v[7]) : "r"(ma) : "memory");
            asm volatile("ld.shared.v4.b32 {%0, %1, %2, %3}, [%4+2768];\n" : "=r"(v[8]), "=r"(v[9]), "=r"(v[10]), "=r"(v[11]) : "r"(ma) : "memory");
            __syncwarp();
            if (lane == 0) mbar_arrive(bars + B_MCONS);
            return (uint32_t)__any_sync(0xffffffffu, (((v[0] | v[1] | v[2]) | (v[3] | v[4] | v[5])) | ((v[6] | v[7] | v[8]) | (v[9] | v[10] | v[11]))) & 0x7FFF7FFFu);
        };
        auto mask_any = [&](uint32_t a) {
            uint32_t r;
            asm volatile("{\n.reg .pred p, q;\nsetp.eq.u32 p, %1, 1;\nsetp.ne.u32 q, %2, 0;\n"
                         "@p bar.red.or.pred q, 4, 128, q;\n@!p bar.red.or.pred q, 5, 128, q;\nselp.u32 %0, 1, 0, q;\n}\n"
                         : "=r"(r) : "r"(wg), "r"(a) : "memory");
            return r;
        };
        mbar_wait(bars + B_MFULL + (wg - 1) * 8, 0);
        uint32_t masked = mask_any(mask_load());
        const uint32_t barw = bars + (wg - 1) * 8;
        const uint64_t descKw = descK0 + (uint64_t)((wg - 1) * (XCH >> 4)), descVw = descV0 + (uint64_t)((wg - 1) * (V_STRIDE >> 4));
        uint32_t oa = orel + (wg - 1) * omul;
        uint32_t qok = 0;
        const uint32_t zero = (uint32_t)P.z1;
        auto window = [&](auto IT_, int k) {
            constexpr int IT = decltype(IT_)::value;
            const uint32_t bar = barw + 16 * IT;
            const int tl = (k * TOK + TOK - 1) >> 6, tn = ((k + 2) * TOK + TOK - 1) >> 6;
            const uint32_t bt = bars + (tl & 3) * 8, pt = (tl >> 2) & 1;
            TR(8, k);
            float sc0[28], sc1[28];
            TR(10, k);
            mbar_wait_unless(qok, bt + B_QKRAW, pt);
            fence_async_smem();
            TR(11, k);
            wgmma_fence();
            mma_qk0<2 * IT * XCH, 2 * IT * XCH>(sc0, descKw, descKw);
            mma_qk1<2 * IT * XCH, 2 * IT * XCH>(sc1, descKw, descKw);
            wgmma_commit();
            const uint32_t vok = mbar_test(bt + B_VRAW, pt);
            uint32_t mnext;
            if (MLD == 0) {
                if (k + 2 < nwin) mbar_wait(barw + B_MFULL, IT ^ 1);
                mnext = mask_load();
            }
            const uint32_t mok = MLD == 1 ? mbar_test(barw + B_MFULL, IT ^ 1) | (k + 2 >= nwin) : 0;
            wgmma_wait<0>();
            reg_fence(sc0);
            reg_fence(sc1);
            if (lane == 0) mbar_arrive(bar + B_QKFREE);
            if (MLD == 1) {
                mbar_wait_unless(mok, barw + B_MFULL, IT ^ 1);
                mnext = mask_load();
            }
            TR(12, k);
            if (masked | slow) {
                if (masked) {
                    uint32_t u = threadIdx.x, bid = blockIdx.x;
                    asm volatile("" : "+r"(u), "+r"(bid));
                    const uint32_t r0 = ((u >> 1) & 48) + ((u >> 2) & 7);
                    const unsigned short* const mp = reinterpret_cast<const unsigned short*>(P.mask) + ((bid >> 1) + k * P.npair) * (TOK * TOK);
                    const unsigned short* const mr[2] = {mp + min(r0, TOK - 1u) * TOK, mp + min(r0 + 8, TOK - 1u) * TOK};
                    uint32_t mk[26];
#pragma unroll
                    for (int i = 0; i < 24; i++) mk[i] = __ldg(mr[(i >> 1) & 1] + 2 * (u & 3) + 8 * (i >> 2) + (i & 1));
                    mk[24] = __ldg(mr[0] + TOK - 1);
                    mk[25] = __ldg(mr[1] + TOK - 1);
#pragma unroll
                    for (int i = 0; i < 26; i++) {
                        float v = bf16lo(mk[i]) * LOG2E;
                        asm("min.NaN.f32 %0, %0, 0f7F000000;\n\tmax.NaN.f32 %0, %0, 0fFF000000;\n" : "+f"(v));
                        sc0[i < 25 ? i : 26] += v;
                        sc1[i < 25 ? i : 26] += v;
                    }
                }
                auto shift = [&](float (&S)[28], int h) {
                    float m[2];
#pragma unroll
                    for (int i = 12; i >= 0; i--) {
                        uint32_t e = eb[13 * h + i];
                        asm volatile("" : "+r"(e));
                        const float a = S[2 * i] + lg2_ftz(bf16lo(e)), b = S[i < 12 ? 2 * i + 1 : 26] + lg2_ftz(bf16hi(e));
                        if (i == 12) { m[0] = a; m[1] = b; }
                        else m[i & 1] = fmaxf(m[i & 1], fmaxf(a, b));
                    }
#pragma unroll
                    for (int r = 0; r < 2; r++) {
                        m[r] = fmaxf(m[r], __shfl_xor_sync(0xffffffffu, m[r], 1));
                        m[r] = fmaxf(m[r], __shfl_xor_sync(0xffffffffu, m[r], 2));
                    }
#pragma unroll
                    for (int i = 0; i < 27; i++) S[i] -= m[(i >> 1) & 1];
                };
                shift(sc0, 0);
                shift(sc1, 1);
            }
            auto exps = [&](const float (&S)[28], uint32_t (&e)[13]) {
#pragma unroll
                for (int i = 0; i < 12; i++) e[i] = pack_bf16(ex2_ftz(S[2 * i]), ex2_ftz(S[2 * i + 1]));
                e[12] = hmin2_bf16(pack_bf16(ex2_ftz(S[24]), ex2_ftz(S[26])), 0x7F7F7F7Fu);
            };
            auto probs = [&](const uint32_t (&e)[13], int h, uint32_t (&pa)[4][4]) {
#pragma unroll
                for (int i = 0; i < 12; i++) pa[i >> 2][i & 3] = hmul2_bf16(e[i], eb[13 * h + i]);
                const uint32_t l = hmul2_bf16(e[12], eb[13 * h + 12]);
                pa[3][0] = l & 0xFFFFu;
                pa[3][1] = l >> 16;
                pa[3][2] = 0u; pa[3][3] = 0u;
                reg_fence(pa);
            };
            uint32_t pa0[4][4], pa1[4][4], e[13];
            float o0[28], o1[28];
            TR(13, k);
            exps(sc0, e);
            probs(e, 0, pa0);
            mbar_wait_unless(vok, bt + B_VRAW, pt);
            fence_async_smem();
            TR(14, k);
            wgmma_fence();
            mma_pv<2 * IT * V_STRIDE, 0>(o0, pa0, descVw);
            wgmma_commit();
            exps(sc1, e);
            reg_fence(e);
            wgmma_wait<0>();
            reg_fence(o0);
            sched_fence_rw(zero, e);
            probs(e, 1, pa1);
            wgmma_fence();
            mma_pv<2 * IT * V_STRIDE + 6 * GRP, 0>(o1, pa1, descVw);
            wgmma_commit();
            uint32_t w[24];
            {
                const float il0 = rcp_ftz(o0[24]), il1 = rcp_ftz(o0[26]);
                const uint32_t l0 = pack_bf16(il0, il0), l1 = pack_bf16(il1, il1);
#pragma unroll
                for (int j = 0; j < 12; j++) w[j] = hmul2_bf16(pack_bf16(o0[2 * j], o0[2 * j + 1]), (j & 1) ? l1 : l0);
            }
            wgmma_wait<0>();
            reg_fence(o1);
            TR(15, k);
            masked = mask_any(mnext);
            qok = mbar_test(bars + (tn & 3) * 8 + B_QKRAW, (tn >> 2) & 1);
            {
                const float il2 = rcp_ftz(o1[0]), il3 = rcp_ftz(o1[2]);
                const uint32_t l2 = pack_bf16(il2, il2), l3 = pack_bf16(il3, il3);
#pragma unroll
                for (int j = 0; j < 12; j++) w[12 + j] = hmul2_bf16(pack_bf16(o1[2 * j + 4], o1[2 * j + 5]), (j & 1) ? l3 : l2);
#pragma unroll
                for (int p = 0; p < 6; p++) stsm_x4(oa + p * 32, w[4 * p], w[4 * p + 1], w[4 * p + 2], w[4 * p + 3]);
            }
            __syncwarp();
            if (lane == 0) mbar_arrive(bar + B_ODONE);
            TR(16, k);
            if (ov) oa += (uint32_t)(IT ? -2 * V_STRIDE : 2 * V_STRIDE);
            asm volatile("" : "+r"(oa));
        };
        for (int k = wg - 1;; k += 4) {
            window(std::integral_constant<int, 0>(), k);
            if (k + 2 >= nwin) break;
            window(std::integral_constant<int, 1>(), k + 2);
            if (k + 4 >= nwin) break;
        }
        (void)zero;
        asm volatile("setmaxnreg.inc.sync.aligned.u32 160;\n");
    }

    TR(27, wg);
    if (attn) {
        __syncwarp();
        if (lane == 0) mbar_arrive(sbase + SM_PBAR + 96);
    }
    if (!attn || wg == 0) {
#pragma unroll 3
        for (int row = tid >> 2; row < 192; row += attn ? 32 : 96) {
            uint4 w[6];
#pragma unroll
            for (int a = 0; a < 6; a++) w[a] = *reinterpret_cast<const uint4*>(P.wo + row * 192 + 32 * a + 8 * c);
            float s = 0.f;
#pragma unroll
            for (int a = 0; a < 6; a++)
                s += ((bf16lo(w[a].x) + bf16hi(w[a].x)) + (bf16lo(w[a].y) + bf16hi(w[a].y))) +
                     ((bf16lo(w[a].z) + bf16hi(w[a].z)) + (bf16lo(w[a].w) + bf16hi(w[a].w)));
            s += __shfl_xor_sync(0xffffffffu, s, 1);
            s += __shfl_xor_sync(0xffffffffu, s, 2);
            s *= (1.f / 192.f);
            const uint32_t d = sbase + SM_WO + row * 64 + ((c ^ ((row >> 1) & 3)) << 4);
#pragma unroll
            for (int a = 0; a < 6; a++)
                sts128(d + a * 12288, pack_bf16(bf16lo(w[a].x) - s, bf16hi(w[a].x) - s), pack_bf16(bf16lo(w[a].y) - s, bf16hi(w[a].y) - s),
                       pack_bf16(bf16lo(w[a].z) - s, bf16hi(w[a].z) - s), pack_bf16(bf16lo(w[a].w) - s, bf16hi(w[a].w) - s));
        }
        fence_async_smem();
    }
    asm volatile("bar.sync 6, 384;\n" ::: "memory");
    TR(27, 4 + wg);
    {
        PROJ_SCHEDULE
        uint64_t descW = make_desc(sbase + SM_WO, 12288, 512, 2);
        const uint64_t descA = make_desc(sbase + SM_STAGE + wg * STAGE_BYTES, 16, 1024, 1);
        const uint32_t bar = sbase + SM_PBAR + wg * 8;
        const uint32_t yrel = sbase + SM_STAGE + wg * STAGE_BYTES + (warp * 16 + (lane & 15)) * 128 + (((lane & 7) ^ (lane >> 4)) << 4);
        float acc[96];
#pragma unroll
        for (int i = 0; i < 96; i++) acc[i] = 0.f;
        uint32_t it = 0;
        for (int tile = tile0 + wg * tstep; tile < tend; tile += 3 * tstep, it++) {
            descW += P.z1;
            mbar_wait(bar + (it & 1) * 24, (it >> 1) & 1);
            TR(28, it * 3 + wg);
            if (it > 0 || wg > 0) asm volatile("bar.sync %0, 256;\n" :: "r"(8 + wg) : "memory");
            wgmma_fence();
            mma_proj<0, 0>(acc, descA + (uint64_t)((it & 1) * (3 * STAGE_BYTES >> 4)), descW);
            wgmma_commit();
            if (tile + tstep < tend) asm volatile("bar.arrive %0, 256;\n" :: "r"(wg == 2 ? 8 : 9 + wg) : "memory");
            wgmma_wait<0>();
            reg_fence(acc);
            float a[4];
#pragma unroll
            for (int i = 0; i < 4; i++) a[i] = acc[i] * acc[i];
#pragma unroll
            for (int j = 1; j < 24; j++)
#pragma unroll
                for (int i = 0; i < 4; i++) a[i] = fmaf(acc[4 * j + i], acc[4 * j + i], a[i]);
            float s0 = a[0] + a[1], s1 = a[2] + a[3];
            s0 += __shfl_xor_sync(0xffffffffu, s0, 1);
            s1 += __shfl_xor_sync(0xffffffffu, s1, 1);
            s0 += __shfl_xor_sync(0xffffffffu, s0, 2);
            s1 += __shfl_xor_sync(0xffffffffu, s1, 2);
            const float rs0 = rsqrt_ftz(fmaf(s0, 1.f / 192.f, 1e-5f));
            const float rs1 = rsqrt_ftz(fmaf(s1, 1.f / 192.f, 1e-5f));
            const uint32_t ya = yrel + (it & 1) * 3 * STAGE_BYTES;
#pragma unroll
            for (int p = 0; p < 12; p++)
                stsm_x4((ya ^ (32 * (p & 3))) + (p >> 2) * 8192,
                        pack_bf16(acc[8 * p] * rs0, acc[8 * p + 1] * rs0), pack_bf16(acc[8 * p + 2] * rs1, acc[8 * p + 3] * rs1),
                        pack_bf16(acc[8 * p + 4] * rs0, acc[8 * p + 5] * rs0), pack_bf16(acc[8 * p + 6] * rs1, acc[8 * p + 7] * rs1));
            __syncwarp();
            if (lane == 0) mbar_arrive(bar + 104 + (it & 1) * 24);
            TR(29, it * 3 + wg);
        }
    }
}

}

typedef CUresult (*PFN_encodeTiled)(CUtensorMap*, CUtensorMapDataType, cuuint32_t, void*, const cuuint64_t*,
                                    const cuuint64_t*, const cuuint32_t*, const cuuint32_t*, CUtensorMapInterleave,
                                    CUtensorMapSwizzle, CUtensorMapL2promotion, CUtensorMapFloatOOBfill);

extern "C" void kernel_launch(void* const* d_in, const int* in_sizes, int n_in, void* d_out, int out_size) {
    swin::Params P;
    P.x           = (const __nv_bfloat16*)d_in[0];
    P.wqkv        = (const __nv_bfloat16*)d_in[1];
    P.wo          = (const __nv_bfloat16*)d_in[2];
    P.logit_scale = (const __nv_bfloat16*)d_in[3];
    P.cpb_w1      = (const __nv_bfloat16*)d_in[4];
    P.cpb_w2      = (const __nv_bfloat16*)d_in[5];
    P.rel_coords  = (const __nv_bfloat16*)d_in[6];
    P.rel_idx     = (const int*)d_in[7];
    P.mask        = (const __nv_bfloat16*)d_in[8];
    P.out         = (__nv_bfloat16*)d_out;
    P.z1 = 0;
    static PFN_encodeTiled encode = nullptr;
    if (!encode) {
        cudaFuncSetAttribute(swin::swin_window_attn_kernel, cudaFuncAttributeMaxDynamicSharedMemorySize, swin::SM_TOTAL);
        cudaDriverEntryPointQueryResult qr;
        cudaGetDriverEntryPoint("cuTensorMapEncodeTiled", (void**)&encode, cudaEnableDefault, &qr);
    }
    CUtensorMap xmap, xmap4, xmap3, omap, wmap, smap, omapb, xmapa, xmapb, smap3, wraw;
    const cuuint32_t estr[4] = {1, 1, 1, 1};
    auto make = [&](CUtensorMap* m, const void* base, int rank, const cuuint64_t* gdim, const cuuint64_t* gstr,
                    const cuuint32_t* box, CUtensorMapSwizzle swz = CU_TENSOR_MAP_SWIZZLE_128B) {
        CUresult r = encode(m, CU_TENSOR_MAP_DATA_TYPE_BFLOAT16, rank, const_cast<void*>(base), gdim, gstr, box, estr,
               CU_TENSOR_MAP_INTERLEAVE_NONE, swz, CU_TENSOR_MAP_L2_PROMOTION_L2_128B,
               CU_TENSOR_MAP_FLOAT_OOB_FILL_NONE);
        (void)r;
    };
    {
        const cuuint64_t gdim[3] = {192, swin::IMG, swin::IMG}, gstr[2] = {384, swin::IMG * 384};
        const cuuint32_t box[3] = {64, 7, 7}, box4[3] = {64, 4, 1}, box3[3] = {64, 3, 1};
        make(&xmap, P.x, 3, gdim, gstr, box);
        make(&xmap4, P.x, 3, gdim, gstr, box4);
        make(&xmap3, P.x, 3, gdim, gstr, box3);
        const cuuint32_t boxa[3] = {64, 7, 3}, boxb[3] = {64, 7, 4};
        make(&xmapa, P.x, 3, gdim, gstr, boxa);
        make(&xmapb, P.x, 3, gdim, gstr, boxb);
    }
    {
        const cuuint64_t gdim[2] = {192, (cuuint64_t)swin::NPIX}, gstr[1] = {384};
        const cuuint32_t box64[2] = {64, 64};
        make(&omap, d_out, 2, gdim, gstr, box64);
        const cuuint64_t gdimb[2] = {192, (cuuint64_t)swin::SEG_B};
        make(&omapb, d_out, 2, gdimb, gstr, box64);
    }
    {
        const cuuint64_t gdim[2] = {576, 192}, gstr[1] = {1152};
        const cuuint32_t box[2] = {16, 192};
        make(&wmap, P.wqkv, 2, gdim, gstr, box, CU_TENSOR_MAP_SWIZZLE_32B);
        const cuuint64_t gdim3[3] = {96, 6, 192}, gstr3[2] = {192, 1152};
        const cuuint32_t box3[3] = {104, 1, 96};
        make(&wraw, P.wqkv, 3, gdim3, gstr3, box3, CU_TENSOR_MAP_SWIZZLE_NONE);
    }
    {
        const cuuint64_t gdim[4] = {96, 2, swin::IMG, swin::IMG}, gstr[3] = {192, 384, swin::IMG * 384};
        const cuuint32_t box4[4] = {104, 1, 7, 4}, box3[4] = {104, 1, 7, 3};
        make(&smap, d_out, 4, gdim, gstr, box4, CU_TENSOR_MAP_SWIZZLE_NONE);
        make(&smap3, d_out, 4, gdim, gstr, box3, CU_TENSOR_MAP_SWIZZLE_NONE);
    }
    P.npair = NPAIR; P.need = swin::ROW_DONE; P.nq = swin::NWINDOWS / NPAIR; P.nr = swin::NWINDOWS % NPAIR;
    P.t1 = swin::TILES - NTAIL;
    swin::swin_window_attn_kernel<<<132, swin::NTHREADS, swin::SM_TOTAL>>>(P, xmap, xmap4, xmap3, omap, wmap, smap, omapb, xmapa, xmapb, smap3, wraw);
}
```

```cpp
#include <cuda_runtime.h>
#include <cuda.h>
#include <cuda_bf16.h>
#include <stdint.h>
#include <type_traits>

namespace swin {
#define HINT ""

#define NPAIR 54
#define QFP32 0
#define PF_DIST 3
#define EXP 0
#define QSPLIT 3
#define SSPLIT 0
#define LATEMASK 0
#define CLUSTER 0
#define NOPF 0
#define NTAIL 432
#define PSTORE 1
#define PORDER 1
#define GORD 0
#define GMERGE 0
#define XSPLIT 1
#define EARLYW 1
#define NEARLY 4
#define MLD 0
#define PIN 3
#define SEQ 1
#define PREL 0
#define PEXP 0
#define PFD 0
#define PFW 0
#define TAU_FAST 40.f
#define REG_G 224
#define REG_A 128
#define REG_H 32
constexpr int IMG      = 511;
constexpr int NWS      = 73;
constexpr int NWINDOWS = NWS * NWS;
constexpr int TOK      = 49;
constexpr int NPIX     = IMG * IMG;
constexpr int NTHREADS = 512;

constexpr int W_ATOM = 6144;
constexpr int SM_WA = 0, SM_WB = 6 * W_ATOM, SM_WV = 12 * W_ATOM;
constexpr int GRP   = TOK * 16;
constexpr int XCH   = TOK * 128;
constexpr int SM_V  = 18 * W_ATOM, V_STRIDE = 10240, O_PITCH = 208;
constexpr int SM_QK = SM_V + 4 * V_STRIDE, QK_CHUNK = 4 * XCH;
constexpr int SM_MASK = SM_QK + 3 * QK_CHUNK;
constexpr int SM_TAB  = SM_V + 3 * V_STRIDE + 256;
constexpr int SM_DUMP = SM_MASK + 4816;
constexpr int SM_BAR  = SM_DUMP + 320;
constexpr int B_XFULL = 0, B_WRAW = 32, B_QKRAW = 64, B_QKFREE = 96, B_VFREE = 128, B_ODONE = 160,
              B_MFLAG = 192, B_VRAW = 224, B_MFULL = 256, B_MCONS = 272, B_WFULL = 280, B_STORED = 288, B_PUBD = 304;
constexpr int SM_A_END = SM_BAR + 320;
static_assert(SM_QK % 1024 == 0 && TOK * O_PITCH + 64 - 16 <= V_STRIDE && (28 * O_PITCH + 64) % 128 == 0, "layout");
constexpr int SM_WO    = 0;
constexpr int SM_STAGE = 73728;
constexpr int STAGE_BYTES = 24576;
constexpr int SM_PBAR  = SM_A_END;
constexpr int SM_TOTAL = SM_PBAR + 152;
static_assert(SM_STAGE + 6 * STAGE_BYTES <= SM_BAR, "smem");
static_assert(SM_TOTAL <= 232448, "smem");
static_assert(SM_BAR % 8 == 0, "barrier alignment");

constexpr int SEG_B   = (IMG - 4) * IMG;
constexpr int TILES_A = (NPIX - SEG_B + 63) / 64;
constexpr int TILES   = TILES_A + (SEG_B + 63) / 64;
constexpr uint32_t ROW_DONE = NWS * 2;

__device__ uint32_t g_cnt[NWS + 7];
__device__ __align__(128) uint8_t g_wo[73728];
__device__ uint32_t g_done;

#define TR(ev, idx)
#define TC(slot)
#define TS(i)
#define TRH(ev, idx)
constexpr float LOG2E = 1.4426950408889634f;

__device__ __forceinline__ uint32_t smem_u32(const void* p) {
    return (uint32_t)__cvta_generic_to_shared(p);
}
__device__ __forceinline__ uint64_t make_desc(uint32_t saddr, uint32_t lbo, uint32_t sbo, uint32_t swz = 0) {
    return (uint64_t)((saddr & 0x3FFFF) >> 4) | ((uint64_t)(lbo >> 4) << 16) | ((uint64_t)(sbo >> 4) << 32) |
           ((uint64_t)swz << 62);
}
__host__ __device__ constexpr uint64_t make_desc_c(uint32_t saddr, uint32_t lbo, uint32_t sbo, uint32_t swz) {
    return (uint64_t)(saddr >> 4) | ((uint64_t)(lbo >> 4) << 16) | ((uint64_t)(sbo >> 4) << 32) | ((uint64_t)swz << 62);
}
__device__ __forceinline__ void wgmma_fence()  { asm volatile("wgmma.fence.sync.aligned;\n" ::: "memory"); }
__device__ __forceinline__ void wgmma_commit() { asm volatile("wgmma.commit_group.sync.aligned;\n" ::: "memory"); }
template <int N> __device__ __forceinline__ void wgmma_wait() {
    asm volatile("wgmma.wait_group.sync.aligned %0;\n" :: "n"(N) : "memory");
}
__device__ __forceinline__ void fence_async_smem() { asm volatile("fence.proxy.async.shared::cta;\n" ::: "memory"); }
__device__ __forceinline__ void wg_bar(int id) { asm volatile("bar.sync %0, 128;\n" :: "r"(id) : "memory"); }

template <int N> __device__ __forceinline__ void reg_fence(float (&v)[N]) {
#pragma unroll
    for (int i = 0; i < N; i++) asm volatile("" : "+f"(v[i]) :: "memory");
}
template <int N> __device__ __forceinline__ void reg_fence(uint32_t (&v)[N]) {
#pragma unroll
    for (int i = 0; i < N; i++) asm volatile("" : "+r"(v[i]) :: "memory");
}
template <int N, int M> __device__ __forceinline__ void reg_fence(uint32_t (&v)[N][M]) {
#pragma unroll
    for (int i = 0; i < N; i++) reg_fence(v[i]);
}

__device__ __forceinline__ uint32_t pack_bf16(float lo, float hi) {
    uint32_t r;
    asm("cvt.rn.bf16x2.f32 %0, %1, %2;\n" : "=r"(r) : "f"(hi), "f"(lo));
    return r;
}
__device__ __forceinline__ float bf16lo(uint32_t v) { return __uint_as_float(v << 16); }
__device__ __forceinline__ float bf16hi(uint32_t v) { return __uint_as_float(v & 0xFFFF0000u); }
__device__ __forceinline__ uint32_t hadd2_bf16(uint32_t a, uint32_t b) {
    uint32_t r;
    asm("add.rn.bf16x2 %0, %1, %2;\n" : "=r"(r) : "r"(a), "r"(b));
    return r;
}
__device__ __forceinline__ uint32_t hmul2_bf16(uint32_t a, uint32_t b) {
    uint32_t r;
    asm("mul.rn.bf16x2 %0, %1, %2;\n" : "=r"(r) : "r"(a), "r"(b));
    return r;
}
__device__ __forceinline__ uint32_t hsub2_bf16(uint32_t a, uint32_t b) {
    uint32_t r;
    asm("sub.rn.bf16x2 %0, %1, %2;\n" : "=r"(r) : "r"(a), "r"(b));
    return r;
}
__device__ __forceinline__ uint32_t hfma2_bf16(uint32_t a, uint32_t b, uint32_t c) {
    uint32_t r;
    asm("fma.rn.bf16x2 %0, %1, %2, %3;\n" : "=r"(r) : "r"(a), "r"(b), "r"(c));
    return r;
}
__device__ __forceinline__ uint32_t hmax2_bf16(uint32_t a, uint32_t b) {
    uint32_t r;
    asm("max.bf16x2 %0, %1, %2;\n" : "=r"(r) : "r"(a), "r"(b));
    return r;
}
__device__ __forceinline__ uint32_t hmin2_bf16(uint32_t a, uint32_t b) {
    uint32_t r;
    asm("min.bf16x2 %0, %1, %2;\n" : "=r"(r) : "r"(a), "r"(b));
    return r;
}
__device__ __forceinline__ uint32_t ex2_bf16x2(uint32_t a) {
    uint32_t r;
    asm("ex2.approx.ftz.bf16x2 %0, %1;\n" : "=r"(r) : "r"(a));
    return r;
}
__device__ __forceinline__ uint32_t ex2_bf16lo(uint32_t a) {
    uint32_t r;
    asm("{\n.reg .b16 l, h;\nmov.b32 {l, h}, %1;\nex2.approx.ftz.bf16 l, l;\ncvt.u32.u16 %0, l;\n}\n" : "=r"(r) : "r"(a));
    return r;
}
__device__ __forceinline__ uint32_t mbar_test(uint32_t bar, uint32_t parity) {
    uint32_t ok;
    asm volatile("{\n.reg .pred p;\nmbarrier.test_wait.parity.shared::cta.b64 p, [%1], %2;\nselp.u32 %0, 1, 0, p;\n}\n"
                 : "=r"(ok) : "r"(bar), "r"(parity) : "memory");
    return ok;
}
__device__ __forceinline__ uint32_t prmt(uint32_t a, uint32_t b, uint32_t sel) {
    uint32_t r;
    asm("prmt.b32 %0, %1, %2, %3;\n" : "=r"(r) : "r"(a), "r"(b), "r"(sel));
    return r;
}
__device__ __forceinline__ float round_bf16(float x) { return __bfloat162float(__float2bfloat16_rn(x)); }

__device__ __forceinline__ void mbar_init(uint32_t bar, uint32_t count) {
    asm volatile("mbarrier.init.shared::cta.b64 [%0], %1;\n" :: "r"(bar), "r"(count) : "memory");
}
__device__ __forceinline__ void mbar_wait(uint32_t bar, uint32_t parity) {
    asm volatile(
        "{\n"
        ".reg .pred p;\n"
        ".reg .u32 n;\n"
        "mov.u32 n, 0;\n"
        "WAIT_%=:\n"
        "mbarrier.try_wait.parity.shared::cta.b64 p, [%0], %1" HINT ";\n"
        "@p bra DONE_%=;\n"
        "add.u32 n, n, 1;\n"
        "setp.lt.u32 p, n, 4194304;\n"
        "@p bra WAIT_%=;\n"
        "exit;\n"
        "DONE_%=:\n"
        "}\n" :: "r"(bar), "r"(parity) : "memory");
}
__device__ __forceinline__ void mbar_wait4(uint32_t b0, uint32_t p0, uint32_t b1, uint32_t p1, uint32_t b2, uint32_t p2,
                                           uint32_t b3, uint32_t p3) {
    asm volatile(
        "{\n"
        ".reg .pred p, q, r, s;\n"
        ".reg .u32 n;\n"
        "mov.u32 n, 0;\n"
        "WAIT_%=:\n"
        "mbarrier.try_wait.parity.shared::cta.b64 p, [%0], %1" HINT ";\n"
        "mbarrier.try_wait.parity.shared::cta.b64 q, [%2], %3" HINT ";\n"
        "mbarrier.try_wait.parity.shared::cta.b64 r, [%4], %5" HINT ";\n"
        "mbarrier.try_wait.parity.shared::cta.b64 s, [%6], %7" HINT ";\n"
        "and.pred p, p, q;\n"
        "and.pred r, r, s;\n"
        "and.pred p, p, r;\n"
        "@p bra DONE_%=;\n"
        "add.u32 n, n, 1;\n"
        "setp.lt.u32 p, n, 4194304;\n"
        "@p bra WAIT_%=;\n"
        "exit;\n"
        "DONE_%=:\n"
        "}\n" :: "r"(b0), "r"(p0), "r"(b1), "r"(p1), "r"(b2), "r"(p2), "r"(b3), "r"(p3) : "memory");
}
__device__ __forceinline__ void mbar_wait2(uint32_t b0, uint32_t p0, uint32_t b1, uint32_t p1) {
    asm volatile(
        "{\n"
        ".reg .pred p, q;\n"
        ".reg .u32 n;\n"
        "mov.u32 n, 0;\n"
        "WAIT_%=:\n"
        "mbarrier.try_wait.parity.shared::cta.b64 p, [%0], %1" HINT ";\n"
        "mbarrier.try_wait.parity.shared::cta.b64 q, [%2], %3" HINT ";\n"
        "and.pred p, p, q;\n"
        "@p bra DONE_%=;\n"
        "add.u32 n, n, 1;\n"
        "setp.lt.u32 p, n, 4194304;\n"
        "@p bra WAIT_%=;\n"
        "exit;\n"
        "DONE_%=:\n"
        "}\n" :: "r"(b0), "r"(p0), "r"(b1), "r"(p1) : "memory");
}
__device__ __forceinline__ void mbar_wait_unless(uint32_t ok, uint32_t bar, uint32_t parity) {
    asm volatile(
        "{\n"
        ".reg .pred p;\n"
        ".reg .u32 n;\n"
        "setp.ne.u32 p, %2, 0;\n"
        "vote.sync.all.pred p, p, 0xffffffff;\n"
        "@p bra DONE_%=;\n"
        "mov.u32 n, 0;\n"
        "WAIT_%=:\n"
        "mbarrier.try_wait.parity.shared::cta.b64 p, [%0], %1" HINT ";\n"
        "@p bra DONE_%=;\n"
        "add.u32 n, n, 1;\n"
        "setp.lt.u32 p, n, 4194304;\n"
        "@p bra WAIT_%=;\n"
        "exit;\n"
        "DONE_%=:\n"
        "}\n" :: "r"(bar), "r"(parity), "r"(ok) : "memory");
}
__device__ __forceinline__ void mbar_wait2_unless(uint32_t ok, uint32_t b0, uint32_t p0, uint32_t b1, uint32_t p1) {
    asm volatile(
        "{\n"
        ".reg .pred p, q;\n"
        ".reg .u32 n;\n"
        "setp.ne.u32 p, %4, 0;\n"
        "vote.sync.all.pred p, p, 0xffffffff;\n"
        "@p bra DONE_%=;\n"
        "mov.u32 n, 0;\n"
        "WAIT_%=:\n"
        "mbarrier.try_wait.parity.shared::cta.b64 p, [%0], %1" HINT ";\n"
        "mbarrier.try_wait.parity.shared::cta.b64 q, [%2], %3" HINT ";\n"
        "and.pred p, p, q;\n"
        "@p bra DONE_%=;\n"
        "add.u32 n, n, 1;\n"
        "setp.lt.u32 p, n, 4194304;\n"
        "@p bra WAIT_%=;\n"
        "exit;\n"
        "DONE_%=:\n"
        "}\n" :: "r"(b0), "r"(p0), "r"(b1), "r"(p1), "r"(ok) : "memory");
}
__device__ __forceinline__ void mbar_wait4_unless(uint32_t ok, uint32_t b0, uint32_t p0, uint32_t b1, uint32_t p1, uint32_t b2,
                                                  uint32_t p2, uint32_t b3, uint32_t p3) {
    asm volatile(
        "{\n"
        ".reg .pred p, q, r, s;\n"
        ".reg .u32 n;\n"
        "setp.ne.u32 p, %8, 0;\n"
        "vote.sync.all.pred p, p, 0xffffffff;\n"
        "@p bra DONE_%=;\n"
        "mov.u32 n, 0;\n"
        "WAIT_%=:\n"
        "mbarrier.try_wait.parity.shared::cta.b64 p, [%0], %1" HINT ";\n"
        "mbarrier.try_wait.parity.shared::cta.b64 q, [%2], %3" HINT ";\n"
        "mbarrier.try_wait.parity.shared::cta.b64 r, [%4], %5" HINT ";\n"
        "mbarrier.try_wait.parity.shared::cta.b64 s, [%6], %7" HINT ";\n"
        "and.pred p, p, q;\n"
        "and.pred r, r, s;\n"
        "and.pred p, p, r;\n"
        "@p bra DONE_%=;\n"
        "add.u32 n, n, 1;\n"
        "setp.lt.u32 p, n, 4194304;\n"
        "@p bra WAIT_%=;\n"
        "exit;\n"
        "DONE_%=:\n"
        "}\n" :: "r"(b0), "r"(p0), "r"(b1), "r"(p1), "r"(b2), "r"(p2), "r"(b3), "r"(p3), "r"(ok) : "memory");
}
__device__ __forceinline__ void sched_fence(uint32_t zero, uint32_t a, uint32_t b, uint32_t c, uint32_t d, uint32_t e = 0,
                                            uint32_t f = 0, uint32_t g = 0, uint32_t h = 0, uint32_t i = 0, uint32_t j = 0,
                                            uint32_t k = 0) {
    asm volatile("{\n.reg .pred p;\n.reg .u32 n;\nsetp.eq.u32 p, %0, 0;\n@p bra.uni DONE_%=;\nmov.u32 n, %0;\nSPIN_%=:\n"
                 "nanosleep.u32 %1;\nnanosleep.u32 %2;\nnanosleep.u32 %3;\nnanosleep.u32 %4;\nnanosleep.u32 %5;\n"
                 "nanosleep.u32 %6;\nnanosleep.u32 %7;\nnanosleep.u32 %8;\nnanosleep.u32 %9;\nnanosleep.u32 %10;\n"
                 "nanosleep.u32 %11;\nsub.u32 n, n, 1;\nsetp.ne.u32 p, n, 0;\n@p bra.uni SPIN_%=;\nDONE_%=:\n}\n"
                 :: "r"(zero), "r"(a), "r"(b), "r"(c), "r"(d), "r"(e), "r"(f), "r"(g), "r"(h), "r"(i), "r"(j), "r"(k) : "memory");
}
__device__ __forceinline__ void sched_fence_rw(uint32_t zero, uint32_t (&v)[13]) {
    asm volatile("{\n.reg .pred p;\n.reg .u32 n;\nsetp.eq.u32 p, %13, 0;\n@p bra.uni DONE_%=;\nmov.u32 n, %13;\nSPIN_%=:\n"
                 "add.u32 %0, %0, %1;\nadd.u32 %1, %1, %2;\nadd.u32 %2, %2, %3;\nadd.u32 %3, %3, %4;\nadd.u32 %4, %4, %5;\n"
                 "add.u32 %5, %5, %6;\nadd.u32 %6, %6, %7;\nadd.u32 %7, %7, %8;\nadd.u32 %8, %8, %9;\nadd.u32 %9, %9, %10;\n"
                 "add.u32 %10, %10, %11;\nadd.u32 %11, %11, %12;\nadd.u32 %12, %12, %0;\n"
                 "sub.u32 n, n, 1;\nsetp.ne.u32 p, n, 0;\n@p bra.uni SPIN_%=;\nDONE_%=:\n}\n"
                 : "+r"(v[0]), "+r"(v[1]), "+r"(v[2]), "+r"(v[3]), "+r"(v[4]), "+r"(v[5]), "+r"(v[6]), "+r"(v[7]), "+r"(v[8]),
                   "+r"(v[9]), "+r"(v[10]), "+r"(v[11]), "+r"(v[12]) : "r"(zero) : "memory");
}
__device__ __forceinline__ void mbar_arrive(uint32_t bar) {
    asm volatile("mbarrier.arrive.shared::cta.b64 _, [%0];\n" :: "r"(bar) : "memory");
}
__device__ __forceinline__ void mbar_arrive_n(uint32_t bar, uint32_t n) {
    asm volatile("mbarrier.arrive.shared::cta.b64 _, [%0], %1;\n" :: "r"(bar), "r"(n) : "memory");
}
__device__ __forceinline__ void mbar_arrive_expect_tx(uint32_t bar, uint32_t bytes) {
    asm volatile("mbarrier.arrive.expect_tx.shared::cta.b64 _, [%0], %1;\n" :: "r"(bar), "r"(bytes) : "memory");
}
__device__ __forceinline__ void stg128_if(bool p, void* addr, uint32_t x, uint32_t y, uint32_t z, uint32_t w) {
    asm volatile("{\n.reg .pred q;\nsetp.ne.b32 q, %5, 0;\n@q st.global.L1::no_allocate.v4.b32 [%0], {%1, %2, %3, %4};\n}\n"
                 :: "l"(addr), "r"(x), "r"(y), "r"(z), "r"(w), "r"((uint32_t)p) : "memory");
}
__device__ __forceinline__ void stsm_x4(uint32_t addr, uint32_t r0, uint32_t r1, uint32_t r2, uint32_t r3) {
    asm volatile("stmatrix.sync.aligned.m8n8.x4.shared.b16 [%0], {%1, %2, %3, %4};\n"
                 :: "r"(addr), "r"(r0), "r"(r1), "r"(r2), "r"(r3) : "memory");
}
__device__ __forceinline__ void stsm_x2(uint32_t addr, uint32_t r0, uint32_t r1) {
    asm volatile("stmatrix.sync.aligned.m8n8.x2.shared.b16 [%0], {%1, %2};\n" :: "r"(addr), "r"(r0), "r"(r1) : "memory");
}
__device__ __forceinline__ void sts128(uint32_t addr, uint32_t r0, uint32_t r1, uint32_t r2, uint32_t r3) {
    asm volatile("st.shared.v4.b32 [%0], {%1, %2, %3, %4};\n" :: "r"(addr), "r"(r0), "r"(r1), "r"(r2), "r"(r3) : "memory");
}
__device__ __forceinline__ void sts32(uint32_t addr, uint32_t v) {
    asm volatile("st.shared.b32 [%0], %1;\n" :: "r"(addr), "r"(v) : "memory");
}
__device__ __forceinline__ uint32_t lds32(uint32_t addr) {
    uint32_t v;
    asm volatile("ld.shared.b32 %0, [%1];\n" : "=r"(v) : "r"(addr) : "memory");
    return v;
}
__device__ __forceinline__ void ldg_nc_v4(uint32_t (&r)[4], const void* p) {
    asm volatile("ld.global.nc.L1::no_allocate.v4.u32 {%0, %1, %2, %3}, [%4];\n"
                 : "=r"(r[0]), "=r"(r[1]), "=r"(r[2]), "=r"(r[3]) : "l"(p));
}
__device__ __forceinline__ uint32_t ldg_u32(const void* p) {
    uint32_t v;
    asm volatile("ld.global.nc.L1::evict_first.u32 %0, [%1];\n" : "=r"(v) : "l"(p));
    return v;
}
__device__ __forceinline__ void ldg_u64(const void* p, uint32_t& a, uint32_t& b) {
    asm volatile("ld.global.nc.L1::evict_first.v2.u32 {%0, %1}, [%2];\n" : "=r"(a), "=r"(b) : "l"(p));
}
__device__ __forceinline__ void prefetch_l2(const void* p) {
    asm volatile("prefetch.global.L2 [%0];\n" :: "l"(p));
}
__device__ __forceinline__ void cp_async16(uint32_t dst, const void* src) {
    asm volatile("cp.async.cg.shared.global [%0], [%1], 16;\n" :: "r"(dst), "l"(src) : "memory");
}
__device__ __forceinline__ float ex2_ftz(float x) {
    float y;
    asm("ex2.approx.ftz.f32 %0, %1;\n" : "=f"(y) : "f"(x));
    return y;
}
__device__ __forceinline__ float lg2_ftz(float x) {
    float y;
    asm("lg2.approx.ftz.f32 %0, %1;\n" : "=f"(y) : "f"(x));
    return y;
}
__device__ __forceinline__ float rcp_ftz(float x) {
    float y;
    asm("rcp.approx.ftz.f32 %0, %1;\n" : "=f"(y) : "f"(x));
    return y;
}
__device__ __forceinline__ float rsqrt_ftz(float x) {
    float y;
    asm("rsqrt.approx.ftz.f32 %0, %1;\n" : "=f"(y) : "f"(x));
    return y;
}

__device__ __forceinline__ bool elect_one() {
    uint32_t p;
    asm volatile("{\n.reg .pred q;\nelect.sync _|q, 0xffffffff;\nselp.u32 %0, 1, 0, q;\n}\n" : "=r"(p));
    return p != 0;
}
__device__ __forceinline__ void ldsm_x4(uint32_t (&r)[4], uint32_t addr) {
    asm volatile("ldmatrix.sync.aligned.m8n8.x4.shared.b16 {%0, %1, %2, %3}, [%4];\n"
                 : "=r"(r[0]), "=r"(r[1]), "=r"(r[2]), "=r"(r[3]) : "r"(addr) : "memory");
}
__device__ __forceinline__ void ldsm_x2(uint32_t& r0, uint32_t& r1, uint32_t addr) {
    asm volatile("ldmatrix.sync.aligned.m8n8.x2.shared.b16 {%0, %1}, [%2];\n" : "=r"(r0), "=r"(r1) : "r"(addr) : "memory");
}
__device__ __forceinline__ void tma_2d(uint32_t dst, const CUtensorMap* map, uint32_t bar, int c0, int c1) {
    asm volatile("cp.async.bulk.tensor.2d.shared::cluster.global.mbarrier::complete_tx::bytes [%0], [%1, {%3, %4}], [%2];\n"
                 :: "r"(dst), "l"(reinterpret_cast<uint64_t>(map)), "r"(bar), "r"(c0), "r"(c1) : "memory");
}
__device__ __forceinline__ void tma_3d(uint32_t dst, const CUtensorMap* map, uint32_t bar, int c0, int c1, int c2) {
    asm volatile("cp.async.bulk.tensor.3d.shared::cluster.global.mbarrier::complete_tx::bytes [%0], [%1, {%3, %4, %5}], [%2];\n"
                 :: "r"(dst), "l"(reinterpret_cast<uint64_t>(map)), "r"(bar), "r"(c0), "r"(c1), "r"(c2) : "memory");
}
__device__ __forceinline__ void tma_store_4d(const CUtensorMap* map, uint32_t src, int c0, int c1, int c2, int c3) {
    asm volatile("cp.async.bulk.tensor.4d.global.shared::cta.tile.bulk_group [%0, {%2, %3, %4, %5}], [%1];\n"
                 :: "l"(reinterpret_cast<uint64_t>(map)), "r"(src), "r"(c0), "r"(c1), "r"(c2), "r"(c3) : "memory");
}
__device__ __forceinline__ void mbar_arrive_if(uint32_t bar, uint32_t cnt) {
    asm volatile("{\n.reg .pred q;\nsetp.ne.b32 q, %1, 0;\n@q mbarrier.arrive.shared::cta.b64 _, [%0], %1;\n}\n"
                 :: "r"(bar), "r"(cnt) : "memory");
}

template <int BOFF, int AOFF, int NA>
__device__ __forceinline__ void mma_qkv_a(float (&d)[48], const uint32_t (&a)[NA][4], uint64_t descB) {
    asm volatile(
        "{\n"
        ".reg .pred p0, p1;\n"
        ".reg .b64 ta, ta0, tb, tb0;\n"
        "setp.ne.b32 p0, 0, 0;\n"
        "setp.eq.b32 p1, 0, 0;\n"
        "add.s64 tb0, %72, %73;\n"
        "add.s64 tb, tb0, 0;\n"
        "wgmma.mma_async.sync.aligned.m64n96k16.f32.bf16.bf16 {%0, %1, %2, %3, %4, %5, %6, %7, %8, %9, %10, %11, %12, %13, %14, %15, %16, %17, %18, %19, %20, %21, %22, %23, %24, %25, %26, %27, %28, %29, %30, %31, %32, %33, %34, %35, %36, %37, %38, %39, %40, %41, %42, %43, %44, %45, %46, %47}, {%48, %49, %50, %51}, tb, p0, 1, 1, 1;\n"
        "add.s64 tb, tb0, 32;\n"
        "wgmma.mma_async.sync.aligned.m64n96k16.f32.bf16.bf16 {%0, %1, %2, %3, %4, %5, %6, %7, %8, %9, %10, %11, %12, %13, %14, %15, %16, %17, %18, %19, %20, %21, %22, %23, %24, %25, %26, %27, %28, %29, %30, %31, %32, %33, %34, %35, %36, %37, %38, %39, %40, %41, %42, %43, %44, %45, %46, %47}, {%52, %53, %54, %55}, tb, p1, 1, 1, 1;\n"
        "add.s64 tb, tb0, 64;\n"
        "wgmma.mma_async.sync.aligned.m64n96k16.f32.bf16.bf16 {%0, %1, %2, %3, %4, %5, %6, %7, %8, %9, %10, %11, %12, %13, %14, %15, %16, %17, %18, %19, %20, %21, %22, %23, %24, %25, %26, %27, %28, %29, %30, %31, %32, %33, %34, %35, %36, %37, %38, %39, %40, %41, %42, %43, %44, %45, %46, %47}, {%56, %57, %58, %59}, tb, p1, 1, 1, 1;\n"
        "add.s64 tb, tb0, 96;\n"
        "wgmma.mma_async.sync.aligned.m64n96k16.f32.bf16.bf16 {%0, %1, %2, %3, %4, %5, %6, %7, %8, %9, %10, %11, %12, %13, %14, %15, %16, %17, %18, %19, %20, %21, %22, %23, %24, %25, %26, %27, %28, %29, %30, %31, %32, %33, %34, %35, %36, %37, %38, %39, %40, %41, %42, %43, %44, %45, %46, %47}, {%60, %61, %62, %63}, tb, p1, 1, 1, 1;\n"
        "add.s64 tb, tb0, 128;\n"
        "wgmma.mma_async.sync.aligned.m64n96k16.f32.bf16.bf16 {%0, %1, %2, %3, %4, %5, %6, %7, %8, %9, %10, %11, %12, %13, %14, %15, %16, %17, %18, %19, %20, %21, %22, %23, %24, %25, %26, %27, %28, %29, %30, %31, %32, %33, %34, %35, %36, %37, %38, %39, %40, %41, %42, %43, %44, %45, %46, %47}, {%64, %65, %66, %67}, tb, p1, 1, 1, 1;\n"
        "add.s64 tb, tb0, 160;\n"
        "wgmma.mma_async.sync.aligned.m64n96k16.f32.bf16.bf16 {%0, %1, %2, %3, %4, %5, %6, %7, %8, %9, %10, %11, %12, %13, %14, %15, %16, %17, %18, %19, %20, %21, %22, %23, %24, %25, %26, %27, %28, %29, %30, %31, %32, %33, %34, %35, %36, %37, %38, %39, %40, %41, %42, %43, %44, %45, %46, %47}, {%68, %69, %70, %71}, tb, p1, 1, 1, 1;\n"
        "}\n"
        : "=f"(d[0]), "=f"(d[1]), "=f"(d[2]), "=f"(d[3]), "=f"(d[4]), "=f"(d[5]), "=f"(d[6]), "=f"(d[7]), "=f"(d[8]), "=f"(d[9]), "=f"(d[10]), "=f"(d[11]), "=f"(d[12]), "=f"(d[13]), "=f"(d[14]), "=f"(d[15]), "=f"(d[16]), "=f"(d[17]), "=f"(d[18]), "=f"(d[19]), "=f"(d[20]), "=f"(d[21]), "=f"(d[22]), "=f"(d[23]), "=f"(d[24]), "=f"(d[25]), "=f"(d[26]), "=f"(d[27]), "=f"(d[28]), "=f"(d[29]), "=f"(d[30]), "=f"(d[31]), "=f"(d[32]), "=f"(d[33]), "=f"(d[34]), "=f"(d[35]), "=f"(d[36]), "=f"(d[37]), "=f"(d[38]), "=f"(d[39]), "=f"(d[40]), "=f"(d[41]), "=f"(d[42]), "=f"(d[43]), "=f"(d[44]), "=f"(d[45]), "=f"(d[46]), "=f"(d[47])
        : "r"(a[AOFF + 0][0]), "r"(a[AOFF + 0][1]), "r"(a[AOFF + 0][2]), "r"(a[AOFF + 0][3]), "r"(a[AOFF + 1][0]), "r"(a[AOFF + 1][1]), "r"(a[AOFF + 1][2]), "r"(a[AOFF + 1][3]), "r"(a[AOFF + 2][0]), "r"(a[AOFF + 2][1]), "r"(a[AOFF + 2][2]), "r"(a[AOFF + 2][3]), "r"(a[AOFF + 3][0]), "r"(a[AOFF + 3][1]), "r"(a[AOFF + 3][2]), "r"(a[AOFF + 3][3]), "r"(a[AOFF + 4][0]), "r"(a[AOFF + 4][1]), "r"(a[AOFF + 4][2]), "r"(a[AOFF + 4][3]), "r"(a[AOFF + 5][0]), "r"(a[AOFF + 5][1]), "r"(a[AOFF + 5][2]), "r"(a[AOFF + 5][3]), "l"(descB), "n"(BOFF >> 4));
}

template <int BOFF, int AOFF, int NA>
__device__ __forceinline__ void mma_qkv_b(float (&d)[48], const uint32_t (&a)[NA][4], uint64_t descB) {
    asm volatile(
        "{\n"
        ".reg .pred p0, p1;\n"
        ".reg .b64 ta, ta0, tb, tb0;\n"
        "setp.ne.b32 p0, 0, 0;\n"
        "setp.eq.b32 p1, 0, 0;\n"
        "add.s64 tb0, %72, %73;\n"
        "add.s64 tb, tb0, 192;\n"
        "wgmma.mma_async.sync.aligned.m64n96k16.f32.bf16.bf16 {%0, %1, %2, %3, %4, %5, %6, %7, %8, %9, %10, %11, %12, %13, %14, %15, %16, %17, %18, %19, %20, %21, %22, %23, %24, %25, %26, %27, %28, %29, %30, %31, %32, %33, %34, %35, %36, %37, %38, %39, %40, %41, %42, %43, %44, %45, %46, %47}, {%48, %49, %50, %51}, tb, p1, 1, 1, 1;\n"
        "add.s64 tb, tb0, 224;\n"
        "wgmma.mma_async.sync.aligned.m64n96k16.f32.bf16.bf16 {%0, %1, %2, %3, %4, %5, %6, %7, %8, %9, %10, %11, %12, %13, %14, %15, %16, %17, %18, %19, %20, %21, %22, %23, %24, %25, %26, %27, %28, %29, %30, %31, %32, %33, %34, %35, %36, %37, %38, %39, %40, %41, %42, %43, %44, %45, %46, %47}, {%52, %53, %54, %55}, tb, p1, 1, 1, 1;\n"
        "add.s64 tb, tb0, 256;\n"
        "wgmma.mma_async.sync.aligned.m64n96k16.f32.bf16.bf16 {%0, %1, %2, %3, %4, %5, %6, %7, %8, %9, %10, %11, %12, %13, %14, %15, %16, %17, %18, %19, %20, %21, %22, %23, %24, %25, %26, %27, %28, %29, %30, %31, %32, %33, %34, %35, %36, %37, %38, %39, %40, %41, %42, %43, %44, %45, %46, %47}, {%56, %57, %58, %59}, tb, p1, 1, 1, 1;\n"
        "add.s64 tb, tb0, 288;\n"
        "wgmma.mma_async.sync.aligned.m64n96k16.f32.bf16.bf16 {%0, %1, %2, %3, %4, %5, %6, %7, %8, %9, %10, %11, %12, %13, %14, %15, %16, %17, %18, %19, %20, %21, %22, %23, %24, %25, %26, %27, %28, %29, %30, %31, %32, %33, %34, %35, %36, %37, %38, %39, %40, %41, %42, %43, %44, %45, %46, %47}, {%60, %61, %62, %63}, tb, p1, 1, 1, 1;\n"
        "add.s64 tb, tb0, 320;\n"
        "wgmma.mma_async.sync.aligned.m64n96k16.f32.bf16.bf16 {%0, %1, %2, %3, %4, %5, %6, %7, %8, %9, %10, %11, %12, %13, %14, %15, %16, %17, %18, %19, %20, %21, %22, %23, %24, %25, %26, %27, %28, %29, %30, %31, %32, %33, %34, %35, %36, %37, %38, %39, %40, %41, %42, %43, %44, %45, %46, %47}, {%64, %65, %66, %67}, tb, p1, 1, 1, 1;\n"
        "add.s64 tb, tb0, 352;\n"
        "wgmma.mma_async.sync.aligned.m64n96k16.f32.bf16.bf16 {%0, %1, %2, %3, %4, %5, %6, %7, %8, %9, %10, %11, %12, %13, %14, %15, %16, %17, %18, %19, %20, %21, %22, %23, %24, %25, %26, %27, %28, %29, %30, %31, %32, %33, %34, %35, %36, %37, %38, %39, %40, %41, %42, %43, %44, %45, %46, %47}, {%68, %69, %70, %71}, tb, p1, 1, 1, 1;\n"
        "}\n"
        : "+f"(d[0]), "+f"(d[1]), "+f"(d[2]), "+f"(d[3]), "+f"(d[4]), "+f"(d[5]), "+f"(d[6]), "+f"(d[7]), "+f"(d[8]), "+f"(d[9]), "+f"(d[10]), "+f"(d[11]), "+f"(d[12]), "+f"(d[13]), "+f"(d[14]), "+f"(d[15]), "+f"(d[16]), "+f"(d[17]), "+f"(d[18]), "+f"(d[19]), "+f"(d[20]), "+f"(d[21]), "+f"(d[22]), "+f"(d[23]), "+f"(d[24]), "+f"(d[25]), "+f"(d[26]), "+f"(d[27]), "+f"(d[28]), "+f"(d[29]), "+f"(d[30]), "+f"(d[31]), "+f"(d[32]), "+f"(d[33]), "+f"(d[34]), "+f"(d[35]), "+f"(d[36]), "+f"(d[37]), "+f"(d[38]), "+f"(d[39]), "+f"(d[40]), "+f"(d[41]), "+f"(d[42]), "+f"(d[43]), "+f"(d[44]), "+f"(d[45]), "+f"(d[46]), "+f"(d[47])
        : "r"(a[AOFF + 0][0]), "r"(a[AOFF + 0][1]), "r"(a[AOFF + 0][2]), "r"(a[AOFF + 0][3]), "r"(a[AOFF + 1][0]), "r"(a[AOFF + 1][1]), "r"(a[AOFF + 1][2]), "r"(a[AOFF + 1][3]), "r"(a[AOFF + 2][0]), "r"(a[AOFF + 2][1]), "r"(a[AOFF + 2][2]), "r"(a[AOFF + 2][3]), "r"(a[AOFF + 3][0]), "r"(a[AOFF + 3][1]), "r"(a[AOFF + 3][2]), "r"(a[AOFF + 3][3]), "r"(a[AOFF + 4][0]), "r"(a[AOFF + 4][1]), "r"(a[AOFF + 4][2]), "r"(a[AOFF + 4][3]), "r"(a[AOFF + 5][0]), "r"(a[AOFF + 5][1]), "r"(a[AOFF + 5][2]), "r"(a[AOFF + 5][3]), "l"(descB), "n"(BOFF >> 4));
}

template <int AOFF, int BOFF>
__device__ __forceinline__ void mma_qk0(float (&d)[28], uint64_t descA, uint64_t descB) {
    asm volatile(
        "{\n"
        ".reg .pred p0, p1;\n"
        ".reg .b64 ta, ta0, tb, tb0;\n"
        "setp.ne.b32 p0, 0, 0;\n"
        "setp.eq.b32 p1, 0, 0;\n"
        "add.s64 tb0, %30, %31;\n"
        "add.s64 ta0, %28, %29;\n"
        "add.s64 tb, tb0, 4;\n"
        "add.s64 ta, ta0, 0;\n"
        "wgmma.mma_async.sync.aligned.m64n56k16.f32.bf16.bf16 {%0, %1, %2, %3, %4, %5, %6, %7, %8, %9, %10, %11, %12, %13, %14, %15, %16, %17, %18, %19, %20, %21, %22, %23, %24, %25, %26, %27}, ta, tb, p0, 1, 1, 0, 0;\n"
        "add.s64 tb, tb0, 1572;\n"
        "add.s64 ta, ta0, 1568;\n"
        "wgmma.mma_async.sync.aligned.m64n56k16.f32.bf16.bf16 {%0, %1, %2, %3, %4, %5, %6, %7, %8, %9, %10, %11, %12, %13, %14, %15, %16, %17, %18, %19, %20, %21, %22, %23, %24, %25, %26, %27}, ta, tb, p1, 1, 1, 0, 0;\n"
        "add.s64 tb, tb0, 3140;\n"
        "add.s64 ta, ta0, 3136;\n"
        "wgmma.mma_async.sync.aligned.m64n56k16.f32.bf16.bf16 {%0, %1, %2, %3, %4, %5, %6, %7, %8, %9, %10, %11, %12, %13, %14, %15, %16, %17, %18, %19, %20, %21, %22, %23, %24, %25, %26, %27}, ta, tb, p1, 1, 1, 0, 0;\n"
        "}\n"
        : "=f"(d[0]), "=f"(d[1]), "=f"(d[2]), "=f"(d[3]), "=f"(d[4]), "=f"(d[5]), "=f"(d[6]), "=f"(d[7]), "=f"(d[8]), "=f"(d[9]), "=f"(d[10]), "=f"(d[11]), "=f"(d[12]), "=f"(d[13]), "=f"(d[14]), "=f"(d[15]), "=f"(d[16]), "=f"(d[17]), "=f"(d[18]), "=f"(d[19]), "=f"(d[20]), "=f"(d[21]), "=f"(d[22]), "=f"(d[23]), "=f"(d[24]), "=f"(d[25]), "=f"(d[26]), "=f"(d[27])
        : "l"(descA), "n"(AOFF >> 4), "l"(descB), "n"(BOFF >> 4));
}

template <int AOFF, int BOFF>
__device__ __forceinline__ void mma_qk1(float (&d)[28], uint64_t descA, uint64_t descB) {
    asm volatile(
        "{\n"
        ".reg .pred p0, p1;\n"
        ".reg .b64 ta, ta0, tb, tb0;\n"
        "setp.ne.b32 p0, 0, 0;\n"
        "setp.eq.b32 p1, 0, 0;\n"
        "add.s64 tb0, %30, %31;\n"
        "add.s64 ta0, %28, %29;\n"
        "add.s64 tb, tb0, 6;\n"
        "add.s64 ta, ta0, 2;\n"
        "wgmma.mma_async.sync.aligned.m64n56k16.f32.bf16.bf16 {%0, %1, %2, %3, %4, %5, %6, %7, %8, %9, %10, %11, %12, %13, %14, %15, %16, %17, %18, %19, %20, %21, %22, %23, %24, %25, %26, %27}, ta, tb, p0, 1, 1, 0, 0;\n"
        "add.s64 tb, tb0, 1574;\n"
        "add.s64 ta, ta0, 1570;\n"
        "wgmma.mma_async.sync.aligned.m64n56k16.f32.bf16.bf16 {%0, %1, %2, %3, %4, %5, %6, %7, %8, %9, %10, %11, %12, %13, %14, %15, %16, %17, %18, %19, %20, %21, %22, %23, %24, %25, %26, %27}, ta, tb, p1, 1, 1, 0, 0;\n"
        "add.s64 tb, tb0, 3142;\n"
        "add.s64 ta, ta0, 3138;\n"
        "wgmma.mma_async.sync.aligned.m64n56k16.f32.bf16.bf16 {%0, %1, %2, %3, %4, %5, %6, %7, %8, %9, %10, %11, %12, %13, %14, %15, %16, %17, %18, %19, %20, %21, %22, %23, %24, %25, %26, %27}, ta, tb, p1, 1, 1, 0, 0;\n"
        "}\n"
        : "=f"(d[0]), "=f"(d[1]), "=f"(d[2]), "=f"(d[3]), "=f"(d[4]), "=f"(d[5]), "=f"(d[6]), "=f"(d[7]), "=f"(d[8]), "=f"(d[9]), "=f"(d[10]), "=f"(d[11]), "=f"(d[12]), "=f"(d[13]), "=f"(d[14]), "=f"(d[15]), "=f"(d[16]), "=f"(d[17]), "=f"(d[18]), "=f"(d[19]), "=f"(d[20]), "=f"(d[21]), "=f"(d[22]), "=f"(d[23]), "=f"(d[24]), "=f"(d[25]), "=f"(d[26]), "=f"(d[27])
        : "l"(descA), "n"(AOFF >> 4), "l"(descB), "n"(BOFF >> 4));
}

template <int BOFF, int AOFF, int NA>
__device__ __forceinline__ void mma_pv(float (&d)[28], const uint32_t (&a)[NA][4], uint64_t descB) {
    asm volatile(
        "{\n"
        ".reg .pred p0, p1;\n"
        ".reg .b64 ta, ta0, tb, tb0;\n"
        "setp.ne.b32 p0, 0, 0;\n"
        "setp.eq.b32 p1, 0, 0;\n"
        "add.s64 tb0, %44, %45;\n"
        "add.s64 tb, tb0, 0;\n"
        "wgmma.mma_async.sync.aligned.m64n56k16.f32.bf16.bf16 {%0, %1, %2, %3, %4, %5, %6, %7, %8, %9, %10, %11, %12, %13, %14, %15, %16, %17, %18, %19, %20, %21, %22, %23, %24, %25, %26, %27}, {%28, %29, %30, %31}, tb, p0, 1, 1, 1;\n"
        "add.s64 tb, tb0, 16;\n"
        "wgmma.mma_async.sync.aligned.m64n56k16.f32.bf16.bf16 {%0, %1, %2, %3, %4, %5, %6, %7, %8, %9, %10, %11, %12, %13, %14, %15, %16, %17, %18, %19, %20, %21, %22, %23, %24, %25, %26, %27}, {%32, %33, %34, %35}, tb, p1, 1, 1, 1;\n"
        "add.s64 tb, tb0, 32;\n"
        "wgmma.mma_async.sync.aligned.m64n56k16.f32.bf16.bf16 {%0, %1, %2, %3, %4, %5, %6, %7, %8, %9, %10, %11, %12, %13, %14, %15, %16, %17, %18, %19, %20, %21, %22, %23, %24, %25, %26, %27}, {%36, %37, %38, %39}, tb, p1, 1, 1, 1;\n"
        "add.s64 tb, tb0, 48;\n"
        "wgmma.mma_async.sync.aligned.m64n56k16.f32.bf16.bf16 {%0, %1, %2, %3, %4, %5, %6, %7, %8, %9, %10, %11, %12, %13, %14, %15, %16, %17, %18, %19, %20, %21, %22, %23, %24, %25, %26, %27}, {%40, %41, %42, %43}, tb, p1, 1, 1, 1;\n"
        "}\n"
        : "=f"(d[0]), "=f"(d[1]), "=f"(d[2]), "=f"(d[3]), "=f"(d[4]), "=f"(d[5]), "=f"(d[6]), "=f"(d[7]), "=f"(d[8]), "=f"(d[9]), "=f"(d[10]), "=f"(d[11]), "=f"(d[12]), "=f"(d[13]), "=f"(d[14]), "=f"(d[15]), "=f"(d[16]), "=f"(d[17]), "=f"(d[18]), "=f"(d[19]), "=f"(d[20]), "=f"(d[21]), "=f"(d[22]), "=f"(d[23]), "=f"(d[24]), "=f"(d[25]), "=f"(d[26]), "=f"(d[27])
        : "r"(a[AOFF + 0][0]), "r"(a[AOFF + 0][1]), "r"(a[AOFF + 0][2]), "r"(a[AOFF + 0][3]), "r"(a[AOFF + 1][0]), "r"(a[AOFF + 1][1]), "r"(a[AOFF + 1][2]), "r"(a[AOFF + 1][3]), "r"(a[AOFF + 2][0]), "r"(a[AOFF + 2][1]), "r"(a[AOFF + 2][2]), "r"(a[AOFF + 2][3]), "r"(a[AOFF + 3][0]), "r"(a[AOFF + 3][1]), "r"(a[AOFF + 3][2]), "r"(a[AOFF + 3][3]), "l"(descB), "n"(BOFF >> 4));
}

template <int AOFF, int BOFF>
__device__ __forceinline__ void mma_proj(float (&d)[96], uint64_t descA, uint64_t descB) {
    asm volatile(
        "{\n"
        ".reg .pred p0, p1;\n"
        ".reg .b64 ta, ta0, tb, tb0;\n"
        "setp.ne.b32 p0, 0, 0;\n"
        "setp.eq.b32 p1, 0, 0;\n"
        "add.s64 tb0, %98, %99;\n"
        "add.s64 ta0, %96, %97;\n"
        "add.s64 tb, tb0, 0;\n"
        "add.s64 ta, ta0, 0;\n"
        "wgmma.mma_async.sync.aligned.m64n192k16.f32.bf16.bf16 {%0, %1, %2, %3, %4, %5, %6, %7, %8, %9, %10, %11, %12, %13, %14, %15, %16, %17, %18, %19, %20, %21, %22, %23, %24, %25, %26, %27, %28, %29, %30, %31, %32, %33, %34, %35, %36, %37, %38, %39, %40, %41, %42, %43, %44, %45, %46, %47, %48, %49, %50, %51, %52, %53, %54, %55, %56, %57, %58, %59, %60, %61, %62, %63, %64, %65, %66, %67, %68, %69, %70, %71, %72, %73, %74, %75, %76, %77, %78, %79, %80, %81, %82, %83, %84, %85, %86, %87, %88, %89, %90, %91, %92, %93, %94, %95}, ta, tb, p0, 1, 1, 0, 1;\n"
        "add.s64 tb, tb0, 64;\n"
        "add.s64 ta, ta0, 2;\n"
        "wgmma.mma_async.sync.aligned.m64n192k16.f32.bf16.bf16 {%0, %1, %2, %3, %4, %5, %6, %7, %8, %9, %10, %11, %12, %13, %14, %15, %16, %17, %18, %19, %20, %21, %22, %23, %24, %25, %26, %27, %28, %29, %30, %31, %32, %33, %34, %35, %36, %37, %38, %39, %40, %41, %42, %43, %44, %45, %46, %47, %48, %49, %50, %51, %52, %53, %54, %55, %56, %57, %58, %59, %60, %61, %62, %63, %64, %65, %66, %67, %68, %69, %70, %71, %72, %73, %74, %75, %76, %77, %78, %79, %80, %81, %82, %83, %84, %85, %86, %87, %88, %89, %90, %91, %92, %93, %94, %95}, ta, tb, p1, 1, 1, 0, 1;\n"
        "add.s64 tb, tb0, 128;\n"
        "add.s64 ta, ta0, 4;\n"
        "wgmma.mma_async.sync.aligned.m64n192k16.f32.bf16.bf16 {%0, %1, %2, %3, %4, %5, %6, %7, %8, %9, %10, %11, %12, %13, %14, %15, %16, %17, %18, %19, %20, %21, %22, %23, %24, %25, %26, %27, %28, %29, %30, %31, %32, %33, %34, %35, %36, %37, %38, %39, %40, %41, %42, %43, %44, %45, %46, %47, %48, %49, %50, %51, %52, %53, %54, %55, %56, %57, %58, %59, %60, %61, %62, %63, %64, %65, %66, %67, %68, %69, %70, %71, %72, %73, %74, %75, %76, %77, %78, %79, %80, %81, %82, %83, %84, %85, %86, %87, %88, %89, %90, %91, %92, %93, %94, %95}, ta, tb, p1, 1, 1, 0, 1;\n"
        "add.s64 tb, tb0, 192;\n"
        "add.s64 ta, ta0, 6;\n"
        "wgmma.mma_async.sync.aligned.m64n192k16.f32.bf16.bf16 {%0, %1, %2, %3, %4, %5, %6, %7, %8, %9, %10, %11, %12, %13, %14, %15, %16, %17, %18, %19, %20, %21, %22, %23, %24, %25, %26, %27, %28, %29, %30, %31, %32, %33, %34, %35, %36, %37, %38, %39, %40, %41, %42, %43, %44, %45, %46, %47, %48, %49, %50, %51, %52, %53, %54, %55, %56, %57, %58, %59, %60, %61, %62, %63, %64, %65, %66, %67, %68, %69, %70, %71, %72, %73, %74, %75, %76, %77, %78, %79, %80, %81, %82, %83, %84, %85, %86, %87, %88, %89, %90, %91, %92, %93, %94, %95}, ta, tb, p1, 1, 1, 0, 1;\n"
        "add.s64 tb, tb0, 256;\n"
        "add.s64 ta, ta0, 512;\n"
        "wgmma.mma_async.sync.aligned.m64n192k16.f32.bf16.bf16 {%0, %1, %2, %3, %4, %5, %6, %7, %8, %9, %10, %11, %12, %13, %14, %15, %16, %17, %18, %19, %20, %21, %22, %23, %24, %25, %26, %27, %28, %29, %30, %31, %32, %33, %34, %35, %36, %37, %38, %39, %40, %41, %42, %43, %44, %45, %46, %47, %48, %49, %50, %51, %52, %53, %54, %55, %56, %57, %58, %59, %60, %61, %62, %63, %64, %65, %66, %67, %68, %69, %70, %71, %72, %73, %74, %75, %76, %77, %78, %79, %80, %81, %82, %83, %84, %85, %86, %87, %88, %89, %90, %91, %92, %93, %94, %95}, ta, tb, p1, 1, 1, 0, 1;\n"
        "add.s64 tb, tb0, 320;\n"
        "add.s64 ta, ta0, 514;\n"
        "wgmma.mma_async.sync.aligned.m64n192k16.f32.bf16.bf16 {%0, %1, %2, %3, %4, %5, %6, %7, %8, %9, %10, %11, %12, %13, %14, %15, %16, %17, %18, %19, %20, %21, %22, %23, %24, %25, %26, %27, %28, %29, %30, %31, %32, %33, %34, %35, %36, %37, %38, %39, %40, %41, %42, %43, %44, %45, %46, %47, %48, %49, %50, %51, %52, %53, %54, %55, %56, %57, %58, %59, %60, %61, %62, %63, %64, %65, %66, %67, %68, %69, %70, %71, %72, %73, %74, %75, %76, %77, %78, %79, %80, %81, %82, %83, %84, %85, %86, %87, %88, %89, %90, %91, %92, %93, %94, %95}, ta, tb, p1, 1, 1, 0, 1;\n"
        "add.s64 tb, tb0, 384;\n"
        "add.s64 ta, ta0, 516;\n"
        "wgmma.mma_async.sync.aligned.m64n192k16.f32.bf16.bf16 {%0, %1, %2, %3, %4, %5, %6, %7, %8, %9, %10, %11, %12, %13, %14, %15, %16, %17, %18, %19, %20, %21, %22, %23, %24, %25, %26, %27, %28, %29, %30, %31, %32, %33, %34, %35, %36, %37, %38, %39, %40, %41, %42, %43, %44, %45, %46, %47, %48, %49, %50, %51, %52, %53, %54, %55, %56, %57, %58, %59, %60, %61, %62, %63, %64, %65, %66, %67, %68, %69, %70, %71, %72, %73, %74, %75, %76, %77, %78, %79, %80, %81, %82, %83, %84, %85, %86, %87, %88, %89, %90, %91, %92, %93, %94, %95}, ta, tb, p1, 1, 1, 0, 1;\n"
        "add.s64 tb, tb0, 448;\n"
        "add.s64 ta, ta0, 518;\n"
        "wgmma.mma_async.sync.aligned.m64n192k16.f32.bf16.bf16 {%0, %1, %2, %3, %4, %5, %6, %7, %8, %9, %10, %11, %12, %13, %14, %15, %16, %17, %18, %19, %20, %21, %22, %23, %24, %25, %26, %27, %28, %29, %30, %31, %32, %33, %34, %35, %36, %37, %38, %39, %40, %41, %42, %43, %44, %45, %46, %47, %48, %49, %50, %51, %52, %53, %54, %55, %56, %57, %58, %59, %60, %61, %62, %63, %64, %65, %66, %67, %68, %69, %70, %71, %72, %73, %74, %75, %76, %77, %78, %79, %80, %81, %82, %83, %84, %85, %86, %87, %88, %89, %90, %91, %92, %93, %94, %95}, ta, tb, p1, 1, 1, 0, 1;\n"
        "add.s64 tb, tb0, 512;\n"
        "add.s64 ta, ta0, 1024;\n"
        "wgmma.mma_async.sync.aligned.m64n192k16.f32.bf16.bf16 {%0, %1, %2, %3, %4, %5, %6, %7, %8, %9, %10, %11, %12, %13, %14, %15, %16, %17, %18, %19, %20, %21, %22, %23, %24, %25, %26, %27, %28, %29, %30, %31, %32, %33, %34, %35, %36, %37, %38, %39, %40, %41, %42, %43, %44, %45, %46, %47, %48, %49, %50, %51, %52, %53, %54, %55, %56, %57, %58, %59, %60, %61, %62, %63, %64, %65, %66, %67, %68, %69, %70, %71, %72, %73, %74, %75, %76, %77, %78, %79, %80, %81, %82, %83, %84, %85, %86, %87, %88, %89, %90, %91, %92, %93, %94, %95}, ta, tb, p1, 1, 1, 0, 1;\n"
        "add.s64 tb, tb0, 576;\n"
        "add.s64 ta, ta0, 1026;\n"
        "wgmma.mma_async.sync.aligned.m64n192k16.f32.bf16.bf16 {%0, %1, %2, %3, %4, %5, %6, %7, %8, %9, %10, %11, %12, %13, %14, %15, %16, %17, %18, %19, %20, %21, %22, %23, %24, %25, %26, %27, %28, %29, %30, %31, %32, %33, %34, %35, %36, %37, %38, %39, %40, %41, %42, %43, %44, %45, %46, %47, %48, %49, %50, %51, %52, %53, %54, %55, %56, %57, %58, %59, %60, %61, %62, %63, %64, %65, %66, %67, %68, %69, %70, %71, %72, %73, %74, %75, %76, %77, %78, %79, %80, %81, %82, %83, %84, %85, %86, %87, %88, %89, %90, %91, %92, %93, %94, %95}, ta, tb, p1, 1, 1, 0, 1;\n"
        "add.s64 tb, tb0, 640;\n"
        "add.s64 ta, ta0, 1028;\n"
        "wgmma.mma_async.sync.aligned.m64n192k16.f32.bf16.bf16 {%0, %1, %2, %3, %4, %5, %6, %7, %8, %9, %10, %11, %12, %13, %14, %15, %16, %17, %18, %19, %20, %21, %22, %23, %24, %25, %26, %27, %28, %29, %30, %31, %32, %33, %34, %35, %36, %37, %38, %39, %40, %41, %42, %43, %44, %45, %46, %47, %48, %49, %50, %51, %52, %53, %54, %55, %56, %57, %58, %59, %60, %61, %62, %63, %64, %65, %66, %67, %68, %69, %70, %71, %72, %73, %74, %75, %76, %77, %78, %79, %80, %81, %82, %83, %84, %85, %86, %87, %88, %89, %90, %91, %92, %93, %94, %95}, ta, tb, p1, 1, 1, 0, 1;\n"
        "add.s64 tb, tb0, 704;\n"
        "add.s64 ta, ta0, 1030;\n"
        "wgmma.mma_async.sync.aligned.m64n192k16.f32.bf16.bf16 {%0, %1, %2, %3, %4, %5, %6, %7, %8, %9, %10, %11, %12, %13, %14, %15, %16, %17, %18, %19, %20, %21, %22, %23, %24, %25, %26, %27, %28, %29, %30, %31, %32, %33, %34, %35, %36, %37, %38, %39, %40, %41, %42, %43, %44, %45, %46, %47, %48, %49, %50, %51, %52, %53, %54, %55, %56, %57, %58, %59, %60, %61, %62, %63, %64, %65, %66, %67, %68, %69, %70, %71, %72, %73, %74, %75, %76, %77, %78, %79, %80, %81, %82, %83, %84, %85, %86, %87, %88, %89, %90, %91, %92, %93, %94, %95}, ta, tb, p1, 1, 1, 0, 1;\n"
        "}\n"
        : "+f"(d[0]), "+f"(d[1]), "+f"(d[2]), "+f"(d[3]), "+f"(d[4]), "+f"(d[5]), "+f"(d[6]), "+f"(d[7]), "+f"(d[8]), "+f"(d[9]), "+f"(d[10]), "+f"(d[11]), "+f"(d[12]), "+f"(d[13]), "+f"(d[14]), "+f"(d[15]), "+f"(d[16]), "+f"(d[17]), "+f"(d[18]), "+f"(d[19]), "+f"(d[20]), "+f"(d[21]), "+f"(d[22]), "+f"(d[23]), "+f"(d[24]), "+f"(d[25]), "+f"(d[26]), "+f"(d[27]), "+f"(d[28]), "+f"(d[29]), "+f"(d[30]), "+f"(d[31]), "+f"(d[32]), "+f"(d[33]), "+f"(d[34]), "+f"(d[35]), "+f"(d[36]), "+f"(d[37]), "+f"(d[38]), "+f"(d[39]), "+f"(d[40]), "+f"(d[41]), "+f"(d[42]), "+f"(d[43]), "+f"(d[44]), "+f"(d[45]), "+f"(d[46]), "+f"(d[47]), "+f"(d[48]), "+f"(d[49]), "+f"(d[50]), "+f"(d[51]), "+f"(d[52]), "+f"(d[53]), "+f"(d[54]), "+f"(d[55]), "+f"(d[56]), "+f"(d[57]), "+f"(d[58]), "+f"(d[59]), "+f"(d[60]), "+f"(d[61]), "+f"(d[62]), "+f"(d[63]), "+f"(d[64]), "+f"(d[65]), "+f"(d[66]), "+f"(d[67]), "+f"(d[68]), "+f"(d[69]), "+f"(d[70]), "+f"(d[71]), "+f"(d[72]), "+f"(d[73]), "+f"(d[74]), "+f"(d[75]), "+f"(d[76]), "+f"(d[77]), "+f"(d[78]), "+f"(d[79]), "+f"(d[80]), "+f"(d[81]), "+f"(d[82]), "+f"(d[83]), "+f"(d[84]), "+f"(d[85]), "+f"(d[86]), "+f"(d[87]), "+f"(d[88]), "+f"(d[89]), "+f"(d[90]), "+f"(d[91]), "+f"(d[92]), "+f"(d[93]), "+f"(d[94]), "+f"(d[95])
        : "l"(descA), "n"(AOFF >> 4), "l"(descB), "n"(BOFF >> 4));
}

struct Params {
    const __nv_bfloat16* x;
    const __nv_bfloat16* wqkv;
    const __nv_bfloat16* wo;
    const __nv_bfloat16* logit_scale;
    const __nv_bfloat16* cpb_w1;
    const __nv_bfloat16* cpb_w2;
    const __nv_bfloat16* rel_coords;
    const int*           rel_idx;
    const __nv_bfloat16* mask;
    __nv_bfloat16*       out;
    unsigned long long   z1;
    int                  npair;
    uint32_t             need;
    int                  nq, nr;
    int                  t1;
};

__device__ __forceinline__ int unrot(int r) { return r ? r - 1 : NWS - 1; }
__device__ __forceinline__ void finish(uint32_t total) {
    __threadfence();
    if (atomicAdd(&g_done, 1u) == total - 1) {
        for (int i = 0; i <= NWS; i++) g_cnt[i] = 0;
        g_done = 0;
    }
}

__global__ void __launch_bounds__(NTHREADS, 1)
swin_window_attn_kernel(const Params P, const __grid_constant__ CUtensorMap xmap, const __grid_constant__ CUtensorMap xmap4,
                        const __grid_constant__ CUtensorMap xmap3,
                        const __grid_constant__ CUtensorMap omap, const __grid_constant__ CUtensorMap wmap,
                        const __grid_constant__ CUtensorMap smap, const __grid_constant__ CUtensorMap omapb,
                        const __grid_constant__ CUtensorMap xmapa, const __grid_constant__ CUtensorMap xmapb,
                        const __grid_constant__ CUtensorMap smap3, const __grid_constant__ CUtensorMap wraw) {
    extern __shared__ __align__(1024) uint8_t smem[];
    constexpr uint32_t sbase = 1024;
    if (smem_u32(smem) != sbase) return;
    const int tid = threadIdx.x;
    const int wg = __shfl_sync(0xffffffffu, tid >> 7, 0);
    const int warp = __shfl_sync(0xffffffffu, (tid >> 5) & 3, 0);
    const int lane = tid & 31;
    const int g = lane >> 2, c = lane & 3;

    TR(26, wg);
    if (tid == 0) TC(0);
    const bool attn = (int)blockIdx.x < 2 * P.npair;
    const int pair = blockIdx.x >> 1, half = blockIdx.x & 1;
    const int nwin = P.nq + (pair < P.nr ? 1 : 0);
    const int ntiles = (nwin * TOK + 63) >> 6;
    const uint32_t bars = sbase + SM_BAR;
    const int t0 = min(warp * 16 + g, TOK - 1), t1 = min(warp * 16 + g + 8, TOK - 1);
    int ridx[26];
    uint32_t rc, w2[16];
    uint4 w1[4];
    if (attn && (wg == 1 || wg == 2)) {
        rc = reinterpret_cast<const uint32_t*>(P.rel_coords)[min(tid - 128, 168)];
#pragma unroll
        for (int i = 0; i < 4; i++) w1[i] = reinterpret_cast<const uint4*>(P.cpb_w1)[i];
#pragma unroll
        for (int u = 0; u < 16; u++) w2[u] = reinterpret_cast<const uint32_t*>(P.cpb_w2)[2 * u + half];
#pragma unroll
        for (int rh = 0; rh < 2; rh++) {
            const int* ri = P.rel_idx + (rh ? t1 : t0) * TOK;
#pragma unroll
            for (int j = 0; j < 12; j++) ridx[13 * rh + j] = ri[8 * (j >> 1) + 2 * c + (j & 1)];
            ridx[13 * rh + 12] = ri[48];
        }
    }
    {
        if (PFD && tid == 448) {
            const CUtensorMap* maps[3] = {&wraw, &xmapb, &xmapa};
#pragma unroll
            for (int i = 0; i < 3; i++) asm volatile("prefetch.tensormap [%0];\n" :: "l"(reinterpret_cast<uint64_t>(maps[i])) : "memory");
        }
        if (PFW && wg == 0 && tid < 16) {
            const int line = blockIdx.x * 16 + tid;
            if (line < 192 * 9) prefetch_l2(reinterpret_cast<const char*>(P.wqkv) + line * 128);
        }
        if (tid == 416) {
            const CUtensorMap* maps[4] = {attn ? &wmap : &omap, &xmap, &smap, &smap3};
#pragma unroll
            for (int i = 0; i < 4; i++) asm volatile("prefetch.tensormap [%0];\n" :: "l"(reinterpret_cast<uint64_t>(maps[i])) : "memory");
        }
        if (tid == 384) {
            for (int b = 0; b < 4; b++) {
                mbar_init(bars + B_XFULL + b * 8, 2);
                mbar_init(bars + B_QKRAW + b * 8, 4);
                mbar_init(bars + B_VRAW + b * 8, 4);
                mbar_init(bars + B_VFREE + b * 8, 2);
                mbar_init(bars + B_QKFREE + b * 8, 4);
                mbar_init(bars + B_ODONE + b * 8, 4);
            }
            mbar_init(bars + B_WFULL, 2);
            mbar_init(bars + B_WRAW, 1);
            mbar_init(bars + B_MFULL, 1);
            mbar_init(bars + B_MFULL + 8, 1);
            for (int b = 0; b < 8; b++) sts32(bars + B_MFLAG + b * 4, 0);
            mbar_init(bars + B_MCONS, 4);
            for (int b = 0; b < 4; b++) mbar_init(bars + B_STORED + b * 8, 1);
            for (int b = 0; b < 6; b++) {
                mbar_init(sbase + SM_PBAR + b * 8, 1);
                mbar_init(sbase + SM_PBAR + 48 + b * 8, PSTORE ? 1 : 4);
                mbar_init(sbase + SM_PBAR + 104 + b * 8, 4);
            }
            mbar_init(sbase + SM_PBAR + 96, 13);
            asm volatile("fence.mbarrier_init.release.cluster;\n" ::: "memory");
        }
        if (wg == 3) {
            if (attn) *reinterpret_cast<uint4*>(smem + SM_V + warp * V_STRIDE + (lane < 16 ? lane * 16 : V_STRIDE - 64 + (lane & 3) * 16)) = make_uint4(0, 0, 0, 0);
            fence_async_smem();
        }
        __syncthreads();
        TR(26, 4 + wg);
            if (attn && tid == 0) {
                const int q1 = pair + P.npair - (pair + P.npair >= NWS ? NWS : 0);
                if (q1 != 0) asm volatile("mbarrier.expect_tx.relaxed.cta.shared::cta.b64 [%0], %1;\n" :: "r"(bars + B_XFULL + 8), "r"(3 * 21 * 128) : "memory");
                mbar_arrive_expect_tx(bars + B_WRAW, 2 * 192 * O_PITCH);
#pragma unroll
                for (int i = 0; i < 4; i++) {
                    const int q = (i + pair) & 3;
                    tma_3d(sbase + q * 96 * O_PITCH, &wraw, bars + B_WRAW, 0, 2 * (q >> 1) + half, (q & 1) * 96);
                }
                TR(26, 25);
#pragma unroll
                for (int j = 0; j < 2; j++) {
                    const int q = j ? q1 : pair;
                    const bool r0 = j == 0 || q1 > pair;
                    if (q != 0) {
                        mbar_arrive_expect_tx(bars + B_XFULL, j ? 3 * 28 * 128 : 3 * XCH);
#pragma unroll
                        for (int ch = 0; ch < 3; ch++)
                            tma_3d(sbase + SM_QK + j * XCH + ch * QK_CHUNK, &xmapb, bars + B_XFULL, ch * 64, 7 * q - 4, r0 ? IMG - 4 : 3);
#pragma unroll
                        for (int ch = 0; ch < 3; ch++)
                            tma_3d(sbase + SM_QK + j * XCH + ch * QK_CHUNK + 28 * 128, &xmapa, bars + B_XFULL + j * 8, ch * 64, 7 * q - 4, r0 ? 0 : 7);
                    }
                    TR(26, 26 + j);
                }
            }
        __syncwarp();
        TR(26, 13);
    }

    auto permute_w = [&]() {
        uint4 w[3][4];
        TR(26, 16 + wg);
        mbar_wait(bars + B_WRAW, 0);
        TR(26, 20 + wg);
#pragma unroll
        for (int it = 0; it < 3; it++) {
            const int o = ((tid >> 5) * 3 + it) * 4 + (lane >> 3);
            const uint8_t* src = smem + ((o / 6) * 8 + (lane & 7)) * O_PITCH + (o % 6) * 16;
#pragma unroll
            for (int m = 0; m < 4; m++) w[it][m] = *reinterpret_cast<const uint4*>(src + (m >> 1) * 192 * O_PITCH + (m & 1) * 96);
        }
        asm volatile("bar.sync 2, 384;\n" ::: "memory");
        if (tid == 0) {
            fence_async_smem();
            TR(26, 24);
            mbar_arrive_expect_tx(bars + B_WFULL, W_ATOM);
            tma_2d(sbase + SM_WV, &wmap, bars + B_WFULL, 384 + half * 96, 0);
        }
#pragma unroll
        for (int it = 0; it < 3; it++) {
            const int o = ((tid >> 5) * 3 + it) * 4 + (lane >> 3);
            const uint32_t d = sbase + (o % 6) * 2 * W_ATOM + ((o / 6) * 8 + (lane & 7)) * 32 + ((lane >> 2) & 1) * 16;
            sts128(d, w[it][0].x, w[it][1].x, w[it][2].x, w[it][3].x);
            sts128(d ^ 16, w[it][0].y, w[it][1].y, w[it][2].y, w[it][3].y);
            sts128(d + W_ATOM, w[it][0].z, w[it][1].z, w[it][2].z, w[it][3].z);
            sts128((d ^ 16) + W_ATOM, w[it][0].w, w[it][1].w, w[it][2].w, w[it][3].w);
        }
    };
    static_assert(2 * 192 * O_PITCH <= 13 * W_ATOM, "raw weights");
    const uint32_t nfinish = gridDim.x + 4 * P.npair;
#define PROJ_SCHEDULE                                                                                   \
    int bid = blockIdx.x;                                                                               \
    asm volatile("" : "+r"(bid));                      \
    const bool at = bid < 2 * P.npair;                                                                  \
    const int tile0 = at ? P.t1 + 2 * P.npair - 1 - bid : bid - 2 * P.npair;                                              \
    const int tstep = at ? 2 * P.npair : (int)gridDim.x - 2 * P.npair;                                  \
    const int tend = at ? TILES : P.t1;
    if (wg == 3) {
        asm volatile("setmaxnreg.dec.sync.aligned.u32 %0;\n" :: "n"(REG_H));
        if (attn && warp == 1) {
            int wr = 0, wq = pair;
            uint32_t mph = 0, ph0 = 0, off = 0;
            constexpr int H0 = 2416;
            auto next = [&]() {
                off = ((uint32_t)(unrot(wr) * NWS + unrot(wq)) * 4802u) & ~15u;
                wq += P.npair; if (wq >= NWS) { wq -= NWS; wr++; }
            };
            auto load = [&](int h) {
                if (elect_one()) {
                    uint32_t bytes = h ? 4816 - H0 : H0;
                    if (h && off == (NWINDOWS - 1) * 4802u) {
                        bytes -= 16;
                        asm volatile("st.shared.u16 [%0], %1;\n" :: "r"(sbase + SM_MASK + 4800),
                                     "h"(reinterpret_cast<const uint16_t*>(P.mask)[NWINDOWS * TOK * TOK - 1]) : "memory");
                    }
                    mbar_arrive_expect_tx(bars + B_MFULL + h * 8, bytes);
                    asm volatile("cp.async.bulk.shared::cluster.global.mbarrier::complete_tx::bytes [%0], [%1], %2, [%3];\n"
                                 :: "r"(sbase + SM_MASK + h * H0), "l"(reinterpret_cast<const char*>(P.mask) + off + h * H0),
                                    "r"(bytes), "r"(bars + B_MFULL + h * 8) : "memory");
                }
            };
            const uint32_t ma = sbase + SM_MASK + lane * 16;
            auto scan = [&](int h) {
                uint32_t any = 0;
#pragma unroll
                for (int i = 0; i < 5; i++) {
                    uint32_t v[4];
                    asm volatile("ld.shared.v4.b32 {%0, %1, %2, %3}, [%4];\n" : "=r"(v[0]), "=r"(v[1]), "=r"(v[2]), "=r"(v[3])
                                 : "r"(ma + (i < 4 ? h * H0 + i * 512 : (h ? 4816 : H0) - 512)) : "memory");
                    any |= (v[0] | v[1]) | (v[2] | v[3]);
                }
                return (uint32_t)__any_sync(0xffffffffu, any & 0x7FFF7FFFu);
            };
            next();
            mbar_wait(bars + B_WRAW, 0);
            load(0);
            load(1);
#pragma unroll 1
            for (int k = 0; k < nwin; k++) {
                const bool more = k + 1 < nwin;
                next();
                mbar_wait(bars + B_QKFREE + (k & 3) * 8, ((k >> 2) + 1) & 1);
                mbar_wait(bars + B_MFULL, ph0);
                ph0 ^= 1;
                TR(17, k);
                const uint32_t a0 = scan(0);
                if (!a0 && more) load(0);
                mbar_wait(bars + B_MFULL + 8, k & 1);
                const uint32_t masked = a0 | scan(1);
                if (masked) {
                    if (!a0 && more) {
                        mbar_wait(bars + B_MFULL, ph0);
                        ph0 ^= 1;
#pragma unroll
                        for (int i = 0; i < 5; i++) sts128(ma + (i < 4 ? i * 512 : H0 - 512), 0, 0, 0, 0);
                    }
                    __syncwarp();
                    __threadfence_block();
                }
                asm volatile("st.volatile.shared.b32 [%0], %1;\n" :: "r"(bars + B_MFLAG + (k & 7) * 4), "r"(2 * k + 2 + masked) : "memory");
                TR(18, k);
                if (masked) {
                    mbar_wait(bars + B_MCONS, mph);
                    mph ^= 1;
                    fence_async_smem();
                    __syncwarp();
                    if (more) load(0);
                }
                if (more) load(1);
                TR(25, k + 1);
            }
            if (blockIdx.x < 18 && elect_one())
                asm volatile("cp.async.bulk.prefetch.L2.global [%0], 4096;\n" :: "l"(g_wo + blockIdx.x * 4096) : "memory");
        }
        if (!elect_one()) return;
        if (warp == 0) {
          if (attn) {
            const int kmax = (64 * ntiles + 63) / TOK;
            int wr = 0, wq = pair;
            int pr2 = (pair + PF_DIST * P.npair) / NWS, pq2 = pair + PF_DIST * P.npair - pr2 * NWS;
#pragma unroll 1
            for (int k = -4; k + 4 <= kmax; k++) {
                const int row0 = (k + 4) * TOK;
                const uint32_t dst = sbase + SM_QK + (k & 3) * XCH, bar = bars + B_XFULL + ((row0 >> 6) & 3) * 8;
                const bool alone = (row0 & 63) >= 64 - TOK && (row0 & 63) < TOK;
                const int wh = unrot(wr), ww = unrot(wq), ph2 = unrot(pr2), pw2 = unrot(pq2);
                const int x0 = 7 * ww + 3, y0 = 7 * wh + 3;
                const bool done = k < -2 && ww < NWS - 1;
                if (k == -2) {
                    mbar_wait(bars + B_WRAW, 0);
                    mbar_arrive_expect_tx(bars + B_WFULL, 5 * W_ATOM);
#pragma unroll
                    for (int a = 1; a < 6; a++)
                        tma_2d(sbase + SM_WV + a * W_ATOM, &wmap, bars + B_WFULL, 384 + half * 96 + a * 16, 0);
                }
                mbar_wait(bars + B_QKFREE + (k & 3) * 8, (k >> 2) & 1);
                if (alone && !done) mbar_arrive(bar);
                if (k + 4 >= nwin) {
                    mbar_arrive(bar);
                    continue;
                }
                TR(20, k + 4);
                const bool inner = wh < NWS - 1 && ww < NWS - 1;
                if (done) {
                } else if (XSPLIT && inner && (row0 & 63) >= 64 - 21) {
                    const uint32_t bar2 = bars + B_XFULL + (((row0 >> 6) + 1) & 3) * 8;
                    mbar_arrive_expect_tx(bar, 3 * 21 * 128);
#pragma unroll
                    for (int ch = 0; ch < 3; ch++) tma_3d(dst + ch * QK_CHUNK, &xmapa, bar, ch * 64, x0, y0);
                    asm volatile("mbarrier.expect_tx.relaxed.cta.shared::cta.b64 [%0], %1;\n" :: "r"(bar2), "r"(3 * 28 * 128) : "memory");
#pragma unroll
                    for (int ch = 0; ch < 3; ch++) tma_3d(dst + ch * QK_CHUNK + 21 * 128, &xmapb, bar2, ch * 64, x0, y0 + 3);
                } else if (inner) {
                    mbar_arrive_expect_tx(bar, 3 * XCH);
#pragma unroll
                    for (int ch = 0; ch < 3; ch++) tma_3d(dst + ch * QK_CHUNK, &xmap, bar, ch * 64, x0, y0);
                } else if (ww < NWS - 1) {
                    mbar_arrive_expect_tx(bar, 3 * XCH);
#pragma unroll
                    for (int ch = 0; ch < 3; ch++) {
                        tma_3d(dst + ch * QK_CHUNK, &xmapb, bar, ch * 64, x0, y0);
                        tma_3d(dst + ch * QK_CHUNK + 28 * 128, &xmapa, bar, ch * 64, x0, 0);
                    }
                } else {
                    mbar_arrive_expect_tx(bar, 3 * XCH);
                    const int x1 = (ww == NWS - 1) ? 0 : x0 + 4;
#pragma unroll 1
                    for (int i = 0; i < 7; i++) {
                        const int y = (y0 + i >= IMG) ? y0 + i - IMG : y0 + i;
#pragma unroll
                        for (int ch = 0; ch < 3; ch++) {
                            tma_3d(dst + ch * QK_CHUNK + i * 896, &xmap4, bar, ch * 64, x0, y);
                            tma_3d(dst + ch * QK_CHUNK + i * 896 + 512, &xmap3, bar, ch * 64, x1, y);
                        }
                    }
                }
                if (NOPF) {
                } else if (half == 0) {
                    if (pr2 < NWS) {
#pragma unroll
                        for (int ch = 0; ch < 3; ch++)
                            asm volatile("cp.async.bulk.prefetch.tensor.3d.L2.global.tile [%0, {%1, %2, %3}];\n"
                                         :: "l"(reinterpret_cast<uint64_t>(&xmap)), "r"(ch * 64), "r"(7 * pw2 + 3), "r"(7 * ph2 + 3)
                                         : "memory");
                    }
                } else if (pr2 < NWS) {
                    asm volatile("cp.async.bulk.prefetch.L2.global [%0], %1;\n"
                                 :: "l"(reinterpret_cast<const char*>(P.mask) + (((uint32_t)(ph2 * NWS + pw2) * 4802u) & ~15u)),
                                    "r"(4800) : "memory");
                }
                wq += P.npair; if (wq >= NWS) { wq -= NWS; wr++; }
                pq2 += P.npair; if (pq2 >= NWS) { pq2 -= NWS; pr2++; }
            }
            mbar_wait(bars + B_VRAW + ((ntiles - 1) & 3) * 8, ((ntiles - 1) >> 2) & 1);
          }
            PROJ_SCHEDULE
            int st = 0, ready = -1;
            uint32_t ph = 1;
#pragma unroll 1
            for (int t = tile0; t < tend; t += tstep) {
                const int p0 = (t < TILES_A) ? SEG_B + 64 * t : 64 * (t - TILES_A);
                const int w1 = (t < TILES_A) ? 0 : min((p0 + 63 + 4 * IMG) / (7 * IMG), NWS - 1);
                if (at && t == tile0 + tstep) {
                    mbar_wait(sbase + SM_PBAR + 96, 0);
                    fence_async_smem();
                }
                if (ready < w1) {
                    ready = max(ready, w1 - 2);
#pragma unroll 1
                    while (ready < w1) {
                        ready++;
#pragma unroll 1
                        for (uint32_t n = 0; n < (1u << 22); n++) {
                            uint32_t a;
                            asm volatile("ld.acquire.gpu.global.u32 %0, [%1];\n" : "=r"(a) : "l"(g_cnt + ready) : "memory");
                            if (a >= P.need) break;
                            __nanosleep(64);
                        }
                    }
                    asm volatile("fence.proxy.async.global;\n" ::: "memory");
                }
                TRH(9, (t - tile0) / tstep);
                mbar_wait(sbase + SM_PBAR + 48 + st * 8, ph);
                TRH(5, (t - tile0) / tstep);
                if (PEXP & 2) mbar_arrive(sbase + SM_PBAR + st * 8); else {
                mbar_arrive_expect_tx(sbase + SM_PBAR + st * 8, STAGE_BYTES);
#pragma unroll
                for (int ch = 0; ch < 3; ch++)
                    tma_2d(sbase + SM_STAGE + st * STAGE_BYTES + ch * 8192, &omap, sbase + SM_PBAR + st * 8, ch * 64, (PEXP & 4) ? p0 & 8191 : p0);
                }
                if (++st == 6) { st = 0; ph ^= 1; }
            }
            finish(nfinish);
        } else if (!attn) {
        } else if (warp == 1) {
          {
            if (P.t1 < TILES) {
#pragma unroll 1
                for (uint32_t n = 0; n < (1u << 22); n++) {
                    uint32_t a;
                    asm volatile("ld.acquire.gpu.global.u32 %0, [%1];\n" : "=r"(a) : "l"(g_cnt + NWS) : "memory");
                    if (a) break;
                    __nanosleep(64);
                }
                asm volatile("fence.proxy.async.global;\n" ::: "memory");
                mbar_wait(bars + B_QKRAW + ((ntiles - 1) & 3) * 8, ((ntiles - 1) >> 2) & 1);
                mbar_arrive_expect_tx(bars + B_WRAW, 73728);
#pragma unroll
                for (int i = 0; i < 4; i++) {
                    const uint32_t o = ((i + pair) & 3) * 18432;
                    asm volatile("cp.async.bulk.shared::cluster.global.mbarrier::complete_tx::bytes [%0], [%1], 18432, [%2];\n"
                                 :: "r"(sbase + SM_WO + o), "l"(g_wo + o), "r"(bars + B_WRAW) : "memory");
                }
            }
            finish(nfinish);
          }
        } else if (warp == 2) {
            int wh = 0, ww = pair;
#pragma unroll 1
            for (int k = 0; k < nwin; k++) {
                mbar_wait(bars + B_STORED + (k & 1) * 8, (k >> 1) & 1);
                mbar_arrive(bars + B_PUBD + (k & 1) * 8);
                asm volatile("red.release.gpu.global.add.u32 [%0], 1;\n" :: "l"(g_cnt + wh) : "memory");
                TR(24, k);
                TS(k & 127);
                if (k == nwin - 1) TC(7);
                ww += P.npair; if (ww >= NWS) { ww -= NWS; wh++; }
            }
            finish(nfinish);
        } else {
            for (int t = 0; t < 3; t++) mbar_arrive_n(bars + B_VFREE + t * 8, 2);
            int wr = 0, wq = pair;
#pragma unroll 1
            for (int k = 0; k < nwin; k++) {
                const uint32_t src = sbase + SM_V + (k & 3) * V_STRIDE;
                const int wh = unrot(wr), ww = unrot(wq);
                const int x0 = 7 * ww + 3, y0 = 7 * wh + 3;
                mbar_wait(bars + B_ODONE + (k & 3) * 8, (k >> 2) & 1);
                fence_async_smem();
                TR(22, k);
                tma_store_4d(&smap, src, 0, half, x0, y0);
                tma_store_4d(&smap3, src + 28 * O_PITCH + 64, 0, half, x0, wh == NWS - 1 ? 0 : y0 + 4);
                if (ww == NWS - 1) {
#pragma unroll 1
                    for (int i = 0; i < 7; i++) {
                        char* const d = reinterpret_cast<char*>(P.out) + (uint32_t)((y0 + i >= IMG ? y0 + i - IMG : y0 + i) * IMG) * 384u + half * 192;
#pragma unroll
                        for (int j = 0; j < 3; j++)
                            asm volatile("cp.async.bulk.global.shared::cta.bulk_group [%0], [%1], 192;\n"
                                         :: "l"(d + j * 384), "r"(src + (7 * i + 4 + j) * O_PITCH + (i >= 4 ? 64 : 0)) : "memory");
                    }
                }
                asm volatile("cp.async.bulk.commit_group;\n" ::: "memory");
                asm volatile("cp.async.bulk.wait_group.read 0;\n" ::: "memory");
                {
                    const int row0 = (k + 4) * TOK;
                    mbar_arrive_n(bars + B_VFREE + ((row0 >> 6) & 3) * 8, ((row0 & 63) >= 64 - TOK && (row0 & 63) < TOK) ? 2 : 1);
                }
                TR(23, k);
                if (k == nwin - 1) mbar_arrive(sbase + SM_PBAR + 96);
                asm volatile("cp.async.bulk.wait_group 0;\n" ::: "memory");
                asm volatile("fence.proxy.async.global;\n" ::: "memory");
                mbar_wait(bars + B_PUBD + (k & 1) * 8, ((k >> 1) + 1) & 1);
                mbar_arrive(bars + B_STORED + (k & 1) * 8);
                wq += P.npair; if (wq >= NWS) { wq -= NWS; wr++; }
            }
        }
        if (PSTORE && warp == 1) {
            PROJ_SCHEDULE
            int st = 0, prev = -1;
            uint32_t ph = 0;
#pragma unroll 1
            for (int t = tile0; t < tend; t += tstep) {
                const int p0 = (t < TILES_A) ? SEG_B + 64 * t : 64 * (t - TILES_A);
                mbar_wait(sbase + SM_PBAR + 104 + st * 8, ph);
                fence_async_smem();
#pragma unroll
                for (int ch = 0; ch < ((PEXP & 1) ? 0 : 3); ch++)
                    asm volatile("cp.async.bulk.tensor.2d.global.shared::cta.tile.bulk_group [%0, {%2, %3}], [%1];\n"
                                 :: "l"(reinterpret_cast<uint64_t>(t < TILES_A ? &omap : &omapb)),
                                    "r"(sbase + SM_STAGE + st * STAGE_BYTES + ch * 8192), "r"(ch * 64), "r"((PEXP & 8) ? (p0 & 8191) + 16384 : p0) : "memory");
                asm volatile("cp.async.bulk.commit_group;\n" ::: "memory");
                TRH(6, (t - tile0) / tstep);
                if (prev >= 0) {
                    asm volatile("cp.async.bulk.wait_group.read 1;\n" ::: "memory");
                    mbar_arrive(sbase + SM_PBAR + 48 + prev * 8);
                    TRH(21, (t - tile0) / tstep - 1);
                }
                prev = st;
                if (++st == 6) { st = 0; ph ^= 1; }
            }
            asm volatile("cp.async.bulk.wait_group 0;\n" ::: "memory");
            TR(30, 0);
            TC(1);
        }
        return;
    }
    if (!attn) {
        asm volatile("setmaxnreg.inc.sync.aligned.u32 160;\n");
    } else if (wg == 0) {
        asm volatile("setmaxnreg.inc.sync.aligned.u32 %0;\n" :: "n"(REG_G));
        float qs = 1.f;
        if (c < 2) qs = round_bf16(expf(round_bf16(fminf(fmaxf(__bfloat162float(P.logit_scale[2 * half + c]), -100.f), 4.6052f)))) * LOG2E;
        uint32_t xa[12][4];
        float accA[48], accB[48], accV[48];
        uint32_t rho = warp * 16 + (lane & 15), rq = warp * 16 + g;
        uint32_t hi = lane >> 4, lane0 = lane == 0, c2 = 2 * c;
        asm volatile("" : "+r"(hi), "+r"(lane0), "+r"(c2));
        auto row_addr = [&](uint32_t (&ax)[4], uint32_t r) {
            ax[0] = sbase + SM_QK + r * 128 + (((r & 7) ^ hi) << 4);
#pragma unroll
            for (int i = 1; i < 4; i++) ax[i] = ax[0] ^ (32 * i);
        };
#define XADDR(ax, s) ((ax)[((s) & 3) ^ (((s) >> 1) & 2)] + ((s) >> 2) * QK_CHUNK)
        uint64_t descW = make_desc(sbase, W_ATOM, 256, 3);
        const uint32_t zero = (uint32_t)P.z1;
        const uint32_t vbase = sbase + SM_V + (lane >> 4) * GRP;
        uint32_t ones = 0x3F803F80u | zero, ones2 = ones | (zero >> 1);
        asm volatile("" : "+r"(ones), "+r"(ones2));
        permute_w();
        TR(26, 10);
        {
            uint32_t ax[4];
            row_addr(ax, rho);
            mbar_wait(bars + B_XFULL, 0);
#pragma unroll
            for (int s = 0; s < 12; s++) ldsm_x4(xa[s], XADDR(ax, s));
        }
        TR(26, 8);
        asm volatile("bar.sync 7, 384;\n" ::: "memory");
        fence_async_smem();
        TR(26, 9);
        wgmma_fence();
        mma_qkv_a<SM_WA, 0>(accA, xa, descW);
        mma_qkv_b<SM_WA, 6>(accA, xa, descW);
        wgmma_commit();
        mma_qkv_a<SM_WB, 0>(accB, xa, descW);
        wgmma_commit();
        TR(26, 11);
        mbar_wait(bars + B_WFULL, 0);
        TR(26, 12);
        if (tid == 0) TC(3);
        for (int t = 0; t < ntiles; t++) {
            descW += P.z1;
            float ss[4];
            uint32_t pk[2][24];
            wgmma_wait<1>();
            reg_fence(accA);
            TR(0, t);
#pragma unroll
            for (int i = 0; i < 4; i++) ss[i] = accA[i] * accA[i];
#pragma unroll
            for (int i = 4; i < 48; i++) ss[i & 3] = fmaf(accA[i], accA[i], ss[i & 3]);
            mma_qkv_b<SM_WB, 6>(accB, xa, descW);
            wgmma_commit();
            sched_fence(zero, __float_as_uint(ss[0]), __float_as_uint(ss[1]), __float_as_uint(ss[2]), __float_as_uint(ss[3]));
#pragma unroll
            for (int j = 0; j < 12; j++) {
                pk[0][j] = pack_bf16(accA[4 * j], accA[4 * j + 1]);
                pk[1][j] = pack_bf16(accA[4 * j + 2], accA[4 * j + 3]);
                asm volatile("" : "+r"(pk[0][j]), "+r"(pk[1][j]));
            }
            wgmma_fence();
            mma_qkv_a<SM_WV, 0>(accV, xa, descW);
            wgmma_commit();
            uint32_t av = vbase + rho * 16 + ((rho * 1338) >> 16) * (V_STRIDE - GRP);
            uint32_t aq[2];
            aq[0] = sbase + SM_QK + rq * 128 + (((rq & 7) ^ c2) << 4);
            aq[1] = aq[0] + 1024;
            if (rq >= 4 * TOK - 8) aq[1] = (aq[1] - QK_CHUNK) ^ 64;
            rho += 64;
            if (rho >= 4 * TOK) rho -= 4 * TOK;
            rq += 64;
            if (rq >= 4 * TOK) rq -= 4 * TOK;
            uint32_t an[4];
            row_addr(an, rho);
            const uint32_t bt = bars + (t & 3) * 8, pt = (t >> 2) & 1, bn = bars + ((t + 1) & 3) * 8, pn = ((t + 1) >> 2) & 1;
            const uint32_t xok = mbar_test(bn + B_XFULL, pn);
            wgmma_wait<1>();
            reg_fence(accB);
#pragma unroll
            for (int i = 0; i < 48; i++) ss[i & 3] = fmaf(accB[i], accB[i], ss[i & 3]);
            ss[0] += ss[1]; ss[2] += ss[3];
            mma_qkv_b<SM_WV, 6>(accV, xa, descW);
            wgmma_commit();
            sched_fence(zero, __float_as_uint(ss[0]), __float_as_uint(ss[2]), av, aq[0], aq[1], an[0], an[1], an[2], an[3], rho, rq);
            const float f0 = rsqrt_ftz(ss[0] + 1e-12f) * qs, f1 = rsqrt_ftz(ss[2] + 1e-12f) * qs;
            const uint32_t f2[2] = {pack_bf16(f0, f0), pack_bf16(f1, f1)};
#pragma unroll
            for (int j = 0; j < 12; j++) {
                pk[0][12 + j] = pack_bf16(accB[4 * j], accB[4 * j + 1]);
                pk[1][12 + j] = pack_bf16(accB[4 * j + 2], accB[4 * j + 3]);
            }
            auto qk_store = [&](int u0, int u1) {
#pragma unroll
                for (int u = u0; u < u1; u++)
#pragma unroll
                    for (int r = 0; r < 2; r++)
                        sts128((aq[r] ^ ((u & 1) * 16 + (u & 2) * 32)) + (u >> 1) * QK_CHUNK,
                               hmul2_bf16(pk[r][4 * u], f2[r]), hmul2_bf16(pk[r][4 * u + 1], f2[r]),
                               hmul2_bf16(pk[r][4 * u + 2], f2[r]), hmul2_bf16(pk[r][4 * u + 3], f2[r]));
            };
            qk_store(0, QSPLIT);
            TR(1, t);
            mbar_wait_unless(xok, bn + B_XFULL, pn);
            TR(2, t);
            wgmma_wait<1>();
#pragma unroll
            for (int s = 0; s < 6; s++) ldsm_x4(xa[s], XADDR(an, s));
            qk_store(QSPLIT, 6);
            __syncwarp();
            mbar_arrive_if(bt + B_QKRAW, lane0);
            TR(3, t);
            wgmma_fence();
            mma_qkv_a<SM_WA, 0>(accA, xa, descW);
            wgmma_commit();
            wgmma_wait<1>();
            reg_fence(accV);
#pragma unroll
            for (int s = 6; s < 12; s++) ldsm_x4(xa[s], XADDR(an, s));
            const uint32_t vok = mbar_test(bt + B_VFREE, pt);
            uint32_t vp[24];
#pragma unroll
            for (int j = 0; j < 24; j++) vp[j] = pack_bf16(accV[2 * j], accV[2 * j + 1]);
            reg_fence(vp);
            wgmma_fence();
            mma_qkv_b<SM_WA, 6>(accA, xa, descW);
            wgmma_commit();
            mbar_wait_unless(vok, bt + B_VFREE, pt);
            if (t == 2) asm volatile("bar.sync 3, 384;\n" ::: "memory");
#pragma unroll
            for (int p = 0; p < 6; p++)
                stsm_x4(av + (p < 3 ? 2 * p : 2 * p + 1) * GRP, vp[4 * p], vp[4 * p + 1], vp[4 * p + 2], vp[4 * p + 3]);
            stsm_x2(av + 6 * GRP, ones, ones2);
            __syncwarp();
            mbar_arrive_if(bt + B_VRAW, lane0);
            TR(4, t);
            wgmma_fence();
            mma_qkv_a<SM_WB, 0>(accB, xa, descW);
            wgmma_commit();
        }
        wgmma_wait<0>();
        reg_fence(accA);
        reg_fence(accB);
        asm volatile("setmaxnreg.dec.sync.aligned.u32 160;\n");
    } else {
        if (REG_A > 128) asm volatile("setmaxnreg.inc.sync.aligned.u32 %0;\n" :: "n"(REG_A));
        {
            const float c0 = bf16lo(rc), c1 = bf16hi(rc);
            float a0 = 0.f, a1 = 0.f;
#pragma unroll
            for (int u = 0; u < 16; u++) {
                const uint32_t p = reinterpret_cast<const uint32_t*>(w1)[u >> 1], q = reinterpret_cast<const uint32_t*>(w1)[8 + (u >> 1)];
                float h = round_bf16(c0 * ((u & 1) ? bf16hi(p) : bf16lo(p)) + c1 * ((u & 1) ? bf16hi(q) : bf16lo(q)));
                h = fmaxf(h, 0.f);
                a0 += h * bf16lo(w2[u]);
                a1 += h * bf16hi(w2[u]);
            }
            const float s0 = round_bf16(__fdividef(1.f, 1.f + expf(-round_bf16(a0))));
            const float s1 = round_bf16(__fdividef(1.f, 1.f + expf(-round_bf16(a1))));
            if (tid - 128 < 169) sts32(sbase + SM_TAB + (tid - 128) * 4, pack_bf16(exp2f(fmaf(s0, 16.f * LOG2E, -12.f)), exp2f(fmaf(s1, 16.f * LOG2E, -12.f))));
        }
        permute_w();
        asm volatile("bar.arrive 7, 384;\n" ::: "memory");
        asm volatile("bar.sync 1, 256;\n" ::: "memory");
        uint32_t eb[26];
        {
            const uint32_t* tab = reinterpret_cast<const uint32_t*>(smem + SM_TAB);
#pragma unroll
            for (int i = 0; i < 13; i++) {
                const uint32_t lo = tab[min(max(ridx[i < 12 ? 13 * (i & 1) + (i & ~1) : 12], 0), 168)];
                const uint32_t hi = tab[min(max(ridx[i < 12 ? 13 * (i & 1) + (i | 1) : 25], 0), 168)];
                eb[i]      = prmt(lo, hi, 0x5410);
                eb[13 + i] = prmt(lo, hi, 0x7632);
            }
            if (c != 0) eb[12] = eb[25] = 0;
        }
        uint32_t slow = 0;
#pragma unroll
        for (int h = 0; h < 2; h++)
            if (!(expf(__bfloat162float(P.logit_scale[2 * half + h])) <= TAU_FAST)) slow = 1;
        reg_fence(eb);
        asm volatile("bar.arrive 3, 384;\n" ::: "memory");
        const bool ov = warp * 16 + (lane & 15) < TOK;
        const int orow = warp * 16 + (lane & 15);
        const uint32_t orel = sbase + (ov ? SM_V + orow * O_PITCH + (orow >= 28 ? 64 : 0) : SM_DUMP + (lane & 7) * 16) + (lane >> 4) * 16;
        const uint32_t omul = ov ? V_STRIDE : 0;
        const uint64_t descK0 = make_desc(sbase + SM_QK, 16, 1024, 1);
        const uint64_t descV0 = make_desc(sbase + SM_V, 128, GRP, 0);
        slow = __shfl_sync(0xffffffffu, slow, 0);
        const uint32_t barw = bars + (wg - 1) * 8;
        const uint64_t descKw = descK0 + (uint64_t)((wg - 1) * (XCH >> 4)), descVw = descV0 + (uint64_t)((wg - 1) * (V_STRIDE >> 4));
        uint32_t oa = orel + (wg - 1) * omul;
        uint32_t qok = 0;
        const uint32_t zero = (uint32_t)P.z1;
        uint32_t mk[13];
#pragma unroll
        for (int i = 0; i < 13; i++) mk[i] = 0;
        auto window = [&](auto IT_, int k) {
            constexpr int IT = decltype(IT_)::value;
            const uint32_t bar = barw + 16 * IT;
            const int tl = (k * TOK + TOK - 1) >> 6, tn = ((k + 2) * TOK + TOK - 1) >> 6;
            const uint32_t bt = bars + (tl & 3) * 8, pt = (tl >> 2) & 1;
            TR(8, k);
            float sc0[28], sc1[28];
            TR(10, k);
            mbar_wait_unless(qok, bt + B_QKRAW, pt);
            fence_async_smem();
            TR(11, k);
            wgmma_fence();
            mma_qk0<2 * IT * XCH, 2 * IT * XCH>(sc0, descKw, descKw);
            mma_qk1<2 * IT * XCH, 2 * IT * XCH>(sc1, descKw, descKw);
            wgmma_commit();
            const uint32_t vok = mbar_test(bt + B_VRAW, pt);
            uint32_t masked;
            asm volatile(
                "{\n.reg .pred p;\n.reg .u32 n;\nmov.u32 n, 0;\n"
                "WAIT_%=:\n"
                "ld.volatile.shared.b32 %0, [%1];\n"
                "sub.u32 %0, %0, %2;\n"
                "setp.lt.u32 p, %0, 2;\n"
                "@p bra DONE_%=;\n"
                "add.u32 n, n, 1;\n"
                "setp.lt.u32 p, n, 16777216;\n"
                "@p bra WAIT_%=;\n"
                "exit;\n"
                "DONE_%=:\n}\n" : "=r"(masked) : "r"(bars + B_MFLAG + (k & 7) * 4), "r"(2 * k + 2) : "memory");
            if (masked) {
                __threadfence_block();
                uint32_t u = threadIdx.x, bid = blockIdx.x;
                asm volatile("" : "+r"(u), "+r"(bid));
                const uint32_t r0 = ((u >> 1) & 48) + ((u >> 2) & 7);
                const int wi = (bid >> 1) + k * P.npair, wr = wi / NWS;
                const uint32_t mp = sbase + SM_MASK + (((unrot(wr) * NWS + unrot(wi - wr * NWS)) * 2) & 15);
                const uint32_t mr[2] = {mp + min(r0, TOK - 1u) * (2 * TOK), mp + min(r0 + 8, TOK - 1u) * (2 * TOK)};
#pragma unroll
                for (int i = 0; i < 13; i++) {
                    const uint32_t a0 = i < 12 ? mr[i & 1] + 4 * (u & 3) + 16 * (i >> 1) : mr[0] + 2 * TOK - 2;
                    const uint32_t a1 = i < 12 ? a0 + 2 : mr[1] + 2 * TOK - 2;
                    uint32_t lo, hi;
                    asm volatile("ld.shared.u16 %0, [%1];\n" : "=r"(lo) : "r"(a0) : "memory");
                    asm volatile("ld.shared.u16 %0, [%1];\n" : "=r"(hi) : "r"(a1) : "memory");
                    mk[i] = prmt(lo, hi, 0x5410);
                }
                __syncwarp();
                if (lane == 0) mbar_arrive(bars + B_MCONS);
            }
            wgmma_wait<0>();
            reg_fence(sc0);
            reg_fence(sc1);
            if (lane == 0) mbar_arrive(bar + B_QKFREE);
            TR(12, k);
            if (masked) {
                uint32_t m0 = mk[0], m1 = mk[1];
#pragma unroll
                for (int i = 2; i < 12; i += 2) { m0 = hmax2_bf16(m0, mk[i]); m1 = hmax2_bf16(m1, mk[i + 1]); }
                m0 = hmax2_bf16(hmax2_bf16(prmt(m0, m1, 0x5410), prmt(m0, m1, 0x7632)), mk[12]);
                m0 = hmax2_bf16(m0, __shfl_xor_sync(0xffffffffu, m0, 1));
                m0 = hmax2_bf16(m0, __shfl_xor_sync(0xffffffffu, m0, 2));
                const float m[2] = {bf16lo(m0), bf16hi(m0)};
#pragma unroll
                for (int i = 0; i < 13; i++) {
                    const float lo = bf16lo(mk[i]) - m[i & 1], hi = bf16hi(mk[i]) - m[i < 12 ? i & 1 : 1];
                    const int j = i < 12 ? 2 * i + 1 : 26;
                    sc0[2 * i] = fmaf(lo, LOG2E, sc0[2 * i]); sc0[j] = fmaf(hi, LOG2E, sc0[j]);
                    sc1[2 * i] = fmaf(lo, LOG2E, sc1[2 * i]); sc1[j] = fmaf(hi, LOG2E, sc1[j]);
                }
            }
            if (slow) {
                auto shift = [&](float (&S)[28], int h) {
                    float m[2];
#pragma unroll
                    for (int i = 12; i >= 0; i--) {
                        uint32_t e = eb[13 * h + i];
                        asm volatile("" : "+r"(e));
                        const float a = S[2 * i] + lg2_ftz(bf16lo(e)), b = S[i < 12 ? 2 * i + 1 : 26] + lg2_ftz(bf16hi(e));
                        if (i == 12) { m[0] = a; m[1] = b; }
                        else m[i & 1] = fmaxf(m[i & 1], fmaxf(a, b));
                    }
#pragma unroll
                    for (int r = 0; r < 2; r++) {
                        m[r] = fmaxf(m[r], __shfl_xor_sync(0xffffffffu, m[r], 1));
                        m[r] = fmaxf(m[r], __shfl_xor_sync(0xffffffffu, m[r], 2));
                    }
#pragma unroll
                    for (int i = 0; i < 27; i++) S[i] -= m[(i >> 1) & 1];
                };
                shift(sc0, 0);
                shift(sc1, 1);
            }
            auto exps = [&](const float (&S)[28], uint32_t (&e)[13]) {
#pragma unroll
                for (int i = 0; i < 12; i++) e[i] = pack_bf16(ex2_ftz(S[2 * i]), ex2_ftz(S[2 * i + 1]));
                e[12] = hmin2_bf16(pack_bf16(ex2_ftz(S[24]), ex2_ftz(S[26])), 0x7F7F7F7Fu);
            };
            auto probs = [&](const uint32_t (&e)[13], int h, uint32_t (&pa)[4][4]) {
#pragma unroll
                for (int i = 0; i < 12; i++) pa[i >> 2][i & 3] = hmul2_bf16(e[i], eb[13 * h + i]);
                const uint32_t l = hmul2_bf16(e[12], eb[13 * h + 12]);
                pa[3][0] = l & 0xFFFFu;
                pa[3][1] = l >> 16;
                pa[3][2] = 0u; pa[3][3] = 0u;
                reg_fence(pa);
            };
            uint32_t pa0[4][4], pa1[4][4], e[13];
            float o0[28], o1[28];
            TR(13, k);
            exps(sc0, e);
            probs(e, 0, pa0);
            mbar_wait_unless(vok, bt + B_VRAW, pt);
            fence_async_smem();
            TR(14, k);
            wgmma_fence();
            mma_pv<2 * IT * V_STRIDE, 0>(o0, pa0, descVw);
            wgmma_commit();
            exps(sc1, e);
            reg_fence(e);
            wgmma_wait<0>();
            reg_fence(o0);
            sched_fence_rw(zero, e);
            probs(e, 1, pa1);
            wgmma_fence();
            mma_pv<2 * IT * V_STRIDE + 6 * GRP, 0>(o1, pa1, descVw);
            wgmma_commit();
            uint32_t w[24];
            {
                const float il0 = rcp_ftz(o0[24]), il1 = rcp_ftz(o0[26]);
                const uint32_t l0 = pack_bf16(il0, il0), l1 = pack_bf16(il1, il1);
#pragma unroll
                for (int j = 0; j < 12; j++) w[j] = hmul2_bf16(pack_bf16(o0[2 * j], o0[2 * j + 1]), (j & 1) ? l1 : l0);
            }
            wgmma_wait<0>();
            reg_fence(o1);
            TR(15, k);
            wg_bar(3 + wg);
#pragma unroll
            for (int i = 0; i < 13; i++) mk[i] = pa1[i >> 2][i & 3];
            qok = mbar_test(bars + (tn & 3) * 8 + B_QKRAW, (tn >> 2) & 1);
            {
                const float il2 = rcp_ftz(o1[0]), il3 = rcp_ftz(o1[2]);
                const uint32_t l2 = pack_bf16(il2, il2), l3 = pack_bf16(il3, il3);
#pragma unroll
                for (int j = 0; j < 12; j++) w[12 + j] = hmul2_bf16(pack_bf16(o1[2 * j + 4], o1[2 * j + 5]), (j & 1) ? l3 : l2);
#pragma unroll
                for (int p = 0; p < 6; p++) stsm_x4(oa + p * 32, w[4 * p], w[4 * p + 1], w[4 * p + 2], w[4 * p + 3]);
            }
            __syncwarp();
            if (lane == 0) mbar_arrive(bar + B_ODONE);
            TR(16, k);
            if (ov) oa += (uint32_t)(IT ? -2 * V_STRIDE : 2 * V_STRIDE);
            asm volatile("" : "+r"(oa));
        };
        for (int k = wg - 1;; k += 4) {
            window(std::integral_constant<int, 0>(), k);
            if (k + 2 >= nwin) break;
            window(std::integral_constant<int, 1>(), k + 2);
            if (k + 4 >= nwin) break;
        }
        (void)zero;
        asm volatile("setmaxnreg.inc.sync.aligned.u32 160;\n");
    }

    TR(27, wg);
    if ((tid & 127) == 0) TC(4 + wg);
    if (attn) {
        __syncwarp();
        if (lane == 0) mbar_arrive(sbase + SM_PBAR + 96);
    }
    if (!attn) {
#pragma unroll
        for (int row = tid >> 2; row < 192; row += 96) {
            uint4 w[6];
#pragma unroll
            for (int a = 0; a < 6; a++) w[a] = *reinterpret_cast<const uint4*>(P.wo + row * 192 + 32 * a + 8 * c);
            float s = 0.f;
#pragma unroll
            for (int a = 0; a < 6; a++)
                s += ((bf16lo(w[a].x) + bf16hi(w[a].x)) + (bf16lo(w[a].y) + bf16hi(w[a].y))) +
                     ((bf16lo(w[a].z) + bf16hi(w[a].z)) + (bf16lo(w[a].w) + bf16hi(w[a].w)));
            s += __shfl_xor_sync(0xffffffffu, s, 1);
            s += __shfl_xor_sync(0xffffffffu, s, 2);
            s *= (1.f / 192.f);
            const uint32_t d = sbase + SM_WO + row * 64 + ((c ^ ((row >> 1) & 3)) << 4);
#pragma unroll
            for (int a = 0; a < 6; a++)
                sts128(d + a * 12288, pack_bf16(bf16lo(w[a].x) - s, bf16hi(w[a].x) - s), pack_bf16(bf16lo(w[a].y) - s, bf16hi(w[a].y) - s),
                       pack_bf16(bf16lo(w[a].z) - s, bf16hi(w[a].z) - s), pack_bf16(bf16lo(w[a].w) - s, bf16hi(w[a].w) - s));
        }
        fence_async_smem();
        asm volatile("bar.sync 6, 384;\n" ::: "memory");
        if (tid == 0 && (int)blockIdx.x == 2 * P.npair) {
            asm volatile("cp.async.bulk.global.shared::cta.bulk_group [%0], [%1], 73728;\n" :: "l"(g_wo), "r"(sbase + SM_WO) : "memory");
            asm volatile("cp.async.bulk.commit_group;\n" ::: "memory");
            asm volatile("cp.async.bulk.wait_group 0;\n" ::: "memory");
            asm volatile("fence.proxy.async.global;\n" ::: "memory");
            asm volatile("red.release.gpu.global.add.u32 [%0], 1;\n" :: "l"(g_cnt + NWS) : "memory");
        }
        __syncwarp();
    } else if (P.t1 < TILES) {
        mbar_wait(sbase + SM_BAR + B_WRAW, 1);
    }
    TR(27, 4 + wg);
    if (tid == 0) TC(2);
    {
        PROJ_SCHEDULE
        uint64_t descW = make_desc(sbase + SM_WO, 12288, 512, 2);
        const uint64_t descA = make_desc(sbase + SM_STAGE + wg * STAGE_BYTES, 16, 1024, 1);
        const uint32_t bar = sbase + SM_PBAR + wg * 8;
        const uint32_t yrel = sbase + SM_STAGE + wg * STAGE_BYTES + (warp * 16 + (lane & 15)) * 128 + (((lane & 7) ^ (lane >> 4)) << 4);
        float acc[96];
#pragma unroll
        for (int i = 0; i < 96; i++) acc[i] = 0.f;
        uint32_t it = 0;
        for (int tile = tile0 + wg * tstep; tile < tend; tile += 3 * tstep, it++) {
            descW += P.z1;
            mbar_wait(bar + (it & 1) * 24, (it >> 1) & 1);
            TR(28, it * 3 + wg);
            if (it > 0 || wg > 0) asm volatile("bar.sync %0, 256;\n" :: "r"(8 + wg) : "memory");
            wgmma_fence();
            mma_proj<0, 0>(acc, descA + (uint64_t)((it & 1) * (3 * STAGE_BYTES >> 4)), descW);
            wgmma_commit();
            if (tile + tstep < tend) asm volatile("bar.arrive %0, 256;\n" :: "r"(wg == 2 ? 8 : 9 + wg) : "memory");
            wgmma_wait<0>();
            reg_fence(acc);
            float a[4];
#pragma unroll
            for (int i = 0; i < 4; i++) a[i] = acc[i] * acc[i];
#pragma unroll
            for (int j = 1; j < 24; j++)
#pragma unroll
                for (int i = 0; i < 4; i++) a[i] = fmaf(acc[4 * j + i], acc[4 * j + i], a[i]);
            float s0 = a[0] + a[1], s1 = a[2] + a[3];
            s0 += __shfl_xor_sync(0xffffffffu, s0, 1);
            s1 += __shfl_xor_sync(0xffffffffu, s1, 1);
            s0 += __shfl_xor_sync(0xffffffffu, s0, 2);
            s1 += __shfl_xor_sync(0xffffffffu, s1, 2);
            const float rs0 = rsqrt_ftz(fmaf(s0, 1.f / 192.f, 1e-5f));
            const float rs1 = rsqrt_ftz(fmaf(s1, 1.f / 192.f, 1e-5f));
            const uint32_t ya = yrel + (it & 1) * 3 * STAGE_BYTES;
#pragma unroll
            for (int p = 0; p < 12; p++)
                stsm_x4((ya ^ (32 * (p & 3))) + (p >> 2) * 8192,
                        pack_bf16(acc[8 * p] * rs0, acc[8 * p + 1] * rs0), pack_bf16(acc[8 * p + 2] * rs1, acc[8 * p + 3] * rs1),
                        pack_bf16(acc[8 * p + 4] * rs0, acc[8 * p + 5] * rs0), pack_bf16(acc[8 * p + 6] * rs1, acc[8 * p + 7] * rs1));
            __syncwarp();
            if (lane == 0) mbar_arrive(bar + 104 + (it & 1) * 24);
            TR(29, it * 3 + wg);
        }
    }
}

}

typedef CUresult (*PFN_encodeTiled)(CUtensorMap*, CUtensorMapDataType, cuuint32_t, void*, const cuuint64_t*,
                                    const cuuint64_t*, const cuuint32_t*, const cuuint32_t*, CUtensorMapInterleave,
                                    CUtensorMapSwizzle, CUtensorMapL2promotion, CUtensorMapFloatOOBfill);

extern "C" void kernel_launch(void* const* d_in, const int* in_sizes, int n_in, void* d_out, int out_size) {
    swin::Params P;
    P.x           = (const __nv_bfloat16*)d_in[0];
    P.wqkv        = (const __nv_bfloat16*)d_in[1];
    P.wo          = (const __nv_bfloat16*)d_in[2];
    P.logit_scale = (const __nv_bfloat16*)d_in[3];
    P.cpb_w1      = (const __nv_bfloat16*)d_in[4];
    P.cpb_w2      = (const __nv_bfloat16*)d_in[5];
    P.rel_coords  = (const __nv_bfloat16*)d_in[6];
    P.rel_idx     = (const int*)d_in[7];
    P.mask        = (const __nv_bfloat16*)d_in[8];
    P.out         = (__nv_bfloat16*)d_out;
    P.z1 = 0;
    static PFN_encodeTiled encode = nullptr;
    if (!encode) {
        cudaFuncSetAttribute(swin::swin_window_attn_kernel, cudaFuncAttributeMaxDynamicSharedMemorySize, swin::SM_TOTAL);
        cudaDriverEntryPointQueryResult qr;
        cudaGetDriverEntryPoint("cuTensorMapEncodeTiled", (void**)&encode, cudaEnableDefault, &qr);
    }
    CUtensorMap xmap, xmap4, xmap3, omap, wmap, smap, omapb, xmapa, xmapb, smap3, wraw;
    const cuuint32_t estr[4] = {1, 1, 1, 1};
    auto make = [&](CUtensorMap* m, const void* base, int rank, const cuuint64_t* gdim, const cuuint64_t* gstr,
                    const cuuint32_t* box, CUtensorMapSwizzle swz = CU_TENSOR_MAP_SWIZZLE_128B) {
        CUresult r = encode(m, CU_TENSOR_MAP_DATA_TYPE_BFLOAT16, rank, const_cast<void*>(base), gdim, gstr, box, estr,
               CU_TENSOR_MAP_INTERLEAVE_NONE, swz, CU_TENSOR_MAP_L2_PROMOTION_L2_128B,
               CU_TENSOR_MAP_FLOAT_OOB_FILL_NONE);
        (void)r;
    };
    {
        const cuuint64_t gdim[3] = {192, swin::IMG, swin::IMG}, gstr[2] = {384, swin::IMG * 384};
        const cuuint32_t box[3] = {64, 7, 7}, box4[3] = {64, 4, 1}, box3[3] = {64, 3, 1};
        make(&xmap, P.x, 3, gdim, gstr, box);
        make(&xmap4, P.x, 3, gdim, gstr, box4);
        make(&xmap3, P.x, 3, gdim, gstr, box3);
        const cuuint32_t boxa[3] = {64, 7, 3}, boxb[3] = {64, 7, 4};
        make(&xmapa, P.x, 3, gdim, gstr, boxa);
        make(&xmapb, P.x, 3, gdim, gstr, boxb);
    }
    {
        const cuuint64_t gdim[2] = {192, (cuuint64_t)swin::NPIX}, gstr[1] = {384};
        const cuuint32_t box64[2] = {64, 64};
        make(&omap, d_out, 2, gdim, gstr, box64);
        const cuuint64_t gdimb[2] = {192, (cuuint64_t)swin::SEG_B};
        make(&omapb, d_out, 2, gdimb, gstr, box64);
    }
    {
        const cuuint64_t gdim[2] = {576, 192}, gstr[1] = {1152};
        const cuuint32_t box[2] = {16, 192};
        make(&wmap, P.wqkv, 2, gdim, gstr, box, CU_TENSOR_MAP_SWIZZLE_32B);
        const cuuint64_t gdim3[3] = {96, 6, 192}, gstr3[2] = {192, 1152};
        const cuuint32_t box3[3] = {104, 1, 96};
        make(&wraw, P.wqkv, 3, gdim3, gstr3, box3, CU_TENSOR_MAP_SWIZZLE_NONE);
    }
    {
        const cuuint64_t gdim[4] = {96, 2, swin::IMG, swin::IMG}, gstr[3] = {192, 384, swin::IMG * 384};
        const cuuint32_t box4[4] = {104, 1, 7, 4}, box3[4] = {104, 1, 7, 3};
        make(&smap, d_out, 4, gdim, gstr, box4, CU_TENSOR_MAP_SWIZZLE_NONE);
        make(&smap3, d_out, 4, gdim, gstr, box3, CU_TENSOR_MAP_SWIZZLE_NONE);
    }
    P.npair = NPAIR; P.need = swin::ROW_DONE; P.nq = swin::NWINDOWS / NPAIR; P.nr = swin::NWINDOWS % NPAIR;
    P.t1 = swin::TILES - NTAIL;
    swin::swin_window_attn_kernel<<<132, swin::NTHREADS, swin::SM_TOTAL>>>(P, xmap, xmap4, xmap3, omap, wmap, smap, omapb, xmapa, xmapb, smap3, wraw);
}
```

```cpp
#include <cuda_runtime.h>
#include <cuda.h>
#include <cuda_bf16.h>
#include <stdint.h>
#include <type_traits>

namespace swin {
#define HINT ""

#define NPAIR 53
#define PF_DIST 3
#define QSPLIT 3
#define CLUSTER 0
#define NOPF 0
#define NTAIL 318
#define PSTORE 1
#define PORDER 1
#define GORD 0
#define GF1 1
#define MERGEW 1
#define MWAIT 1
#define PSLEEP 200
#define CH 5
#define NB 1
#define SCM 0
#define MPF 2
#define MLEAD 4
#define PFM 0
#define PFK 4
#define XP 0
#define KLO 6
#define VPOS 1
#define XSPLIT 1
#define SEQ 1
#define PREL 0
#define PEXP 0
#define PFD 0
#define PFW 0
#define TAU_FAST 40.f
#define REG_G 224
#define REG_A 128
#define REG_H 32
constexpr int IMG      = 511;
constexpr int NWS      = 73;
constexpr int NWINDOWS = NWS * NWS;
constexpr int TOK      = 49;
constexpr int NPIX     = IMG * IMG;
constexpr int NTHREADS = 512;

constexpr int W_ATOM = 6144;
constexpr int SM_WA = 0, SM_WB = 6 * W_ATOM, SM_WV = 12 * W_ATOM;
constexpr int GRP   = TOK * 16;
constexpr int XCH   = TOK * 128;
constexpr int SM_V  = 18 * W_ATOM, V_STRIDE = 10240, O_PITCH = 192, W_PITCH = 208;
constexpr int SM_QK = SM_V + 4 * V_STRIDE, QK_CHUNK = 4 * XCH;
constexpr int SM_MASK = SM_QK + 3 * QK_CHUNK;
constexpr int SM_TAB  = SM_V + 3 * V_STRIDE + 256;
constexpr int SM_BAR  = SM_MASK + 4816;
constexpr int B_XFULL = 0, B_WRAW = 32, B_QKRAW = 64, B_QKFREE = 96, B_VFREE = 128, B_ODONE = 160,
              B_PROG = 192, B_VRAW = 224, B_MFULL = 256, B_MCONS = 272, B_WFULL = 280, B_STORED = 288, B_PUBD = 304;
constexpr int SM_FLAG = SM_BAR + 320;
constexpr int SM_A_END = SM_FLAG + 128;
static_assert(SM_QK % 1024 == 0 && 13 * GRP <= V_STRIDE && V_STRIDE % 128 == 0, "layout");
constexpr int SM_WO    = 0;
constexpr int SM_STAGE = 73728;
constexpr int STAGE_BYTES = 24576;
constexpr int SM_PBAR  = SM_A_END;
constexpr int SM_TOTAL = SM_PBAR + 152;
static_assert(SM_STAGE + 6 * STAGE_BYTES <= SM_BAR, "smem");
static_assert(SM_TOTAL <= 232448, "smem");
static_assert(SM_BAR % 8 == 0 && NWINDOWS / NPAIR < 127, "barrier alignment, flags");

constexpr int SEG_B   = (IMG - 4) * IMG;
constexpr int TILES_A = (NPIX - SEG_B + 63) / 64;
constexpr int TILES   = TILES_A + (SEG_B + 63) / 64;
constexpr uint32_t ROW_DONE = NWS * 2;

__device__ uint32_t g_cnt[NWS + 7];
__device__ __align__(128) uint8_t g_wo[73728];
__device__ uint32_t g_flag[66 * 128];
__device__ uint32_t g_done;

#define TR(ev, idx)
#define TC(slot)
#define TS(i)
#define TRH(ev, idx)
constexpr float LOG2E = 1.4426950408889634f;

__device__ __forceinline__ uint32_t smem_u32(const void* p) {
    return (uint32_t)__cvta_generic_to_shared(p);
}
__device__ __forceinline__ uint64_t make_desc(uint32_t saddr, uint32_t lbo, uint32_t sbo, uint32_t swz = 0) {
    return (uint64_t)((saddr & 0x3FFFF) >> 4) | ((uint64_t)(lbo >> 4) << 16) | ((uint64_t)(sbo >> 4) << 32) |
           ((uint64_t)swz << 62);
}
__host__ __device__ constexpr uint64_t make_desc_c(uint32_t saddr, uint32_t lbo, uint32_t sbo, uint32_t swz) {
    return (uint64_t)(saddr >> 4) | ((uint64_t)(lbo >> 4) << 16) | ((uint64_t)(sbo >> 4) << 32) | ((uint64_t)swz << 62);
}
__device__ __forceinline__ void wgmma_fence()  { asm volatile("wgmma.fence.sync.aligned;\n" ::: "memory"); }
__device__ __forceinline__ void wgmma_commit() { asm volatile("wgmma.commit_group.sync.aligned;\n" ::: "memory"); }
template <int N> __device__ __forceinline__ void wgmma_wait() {
    asm volatile("wgmma.wait_group.sync.aligned %0;\n" :: "n"(N) : "memory");
}
__device__ __forceinline__ void fence_async_smem() { asm volatile("fence.proxy.async.shared::cta;\n" ::: "memory"); }
template <int N> __device__ __forceinline__ void nb_sync(int id) { asm volatile("bar.sync %0, %1;\n" :: "r"(id), "n"(N) : "memory"); }
template <int N> __device__ __forceinline__ void nb_arrive(int id) { asm volatile("bar.arrive %0, %1;\n" :: "r"(id), "n"(N) : "memory"); }
constexpr int NB_ODONE = 0, NB_QKFREE = 6, NB_QKRAW = 12;
__device__ __forceinline__ void wg_bar(int id) { asm volatile("bar.sync %0, 128;\n" :: "r"(id) : "memory"); }

template <int N> __device__ __forceinline__ void reg_fence(float (&v)[N]) {
#pragma unroll
    for (int i = 0; i < N; i++) asm volatile("" : "+f"(v[i]) :: "memory");
}
template <int N> __device__ __forceinline__ void reg_fence(uint32_t (&v)[N]) {
#pragma unroll
    for (int i = 0; i < N; i++) asm volatile("" : "+r"(v[i]) :: "memory");
}
template <int N, int M> __device__ __forceinline__ void reg_fence(uint32_t (&v)[N][M]) {
#pragma unroll
    for (int i = 0; i < N; i++) reg_fence(v[i]);
}

__device__ __forceinline__ uint32_t pack_bf16(float lo, float hi) {
    uint32_t r;
    asm("cvt.rn.bf16x2.f32 %0, %1, %2;\n" : "=r"(r) : "f"(hi), "f"(lo));
    return r;
}
__device__ __forceinline__ float bf16lo(uint32_t v) { return __uint_as_float(v << 16); }
__device__ __forceinline__ float bf16hi(uint32_t v) { return __uint_as_float(v & 0xFFFF0000u); }
__device__ __forceinline__ uint32_t hadd2_bf16(uint32_t a, uint32_t b) {
    uint32_t r;
    asm("add.rn.bf16x2 %0, %1, %2;\n" : "=r"(r) : "r"(a), "r"(b));
    return r;
}
__device__ __forceinline__ uint32_t hmul2_bf16(uint32_t a, uint32_t b) {
    uint32_t r;
    asm("mul.rn.bf16x2 %0, %1, %2;\n" : "=r"(r) : "r"(a), "r"(b));
    return r;
}
__device__ __forceinline__ uint32_t hsub2_bf16(uint32_t a, uint32_t b) {
    uint32_t r;
    asm("sub.rn.bf16x2 %0, %1, %2;\n" : "=r"(r) : "r"(a), "r"(b));
    return r;
}
__device__ __forceinline__ uint32_t hfma2_bf16(uint32_t a, uint32_t b, uint32_t c) {
    uint32_t r;
    asm("fma.rn.bf16x2 %0, %1, %2, %3;\n" : "=r"(r) : "r"(a), "r"(b), "r"(c));
    return r;
}
__device__ __forceinline__ uint32_t hmax2_bf16(uint32_t a, uint32_t b) {
    uint32_t r;
    asm("max.bf16x2 %0, %1, %2;\n" : "=r"(r) : "r"(a), "r"(b));
    return r;
}
__device__ __forceinline__ uint32_t hmin2_bf16(uint32_t a, uint32_t b) {
    uint32_t r;
    asm("min.bf16x2 %0, %1, %2;\n" : "=r"(r) : "r"(a), "r"(b));
    return r;
}
__device__ __forceinline__ uint32_t ex2_bf16x2(uint32_t a) {
    uint32_t r;
    asm("ex2.approx.ftz.bf16x2 %0, %1;\n" : "=r"(r) : "r"(a));
    return r;
}
__device__ __forceinline__ uint32_t ex2_bf16lo(uint32_t a) {
    uint32_t r;
    asm("{\n.reg .b16 l, h;\nmov.b32 {l, h}, %1;\nex2.approx.ftz.bf16 l, l;\ncvt.u32.u16 %0, l;\n}\n" : "=r"(r) : "r"(a));
    return r;
}
__device__ __forceinline__ uint32_t mbar_test(uint32_t bar, uint32_t parity) {
    uint32_t ok;
    asm volatile("{\n.reg .pred p;\nmbarrier.test_wait.parity.shared::cta.b64 p, [%1], %2;\nselp.u32 %0, 1, 0, p;\n}\n"
                 : "=r"(ok) : "r"(bar), "r"(parity) : "memory");
    return ok;
}
__device__ __forceinline__ uint32_t prmt(uint32_t a, uint32_t b, uint32_t sel) {
    uint32_t r;
    asm("prmt.b32 %0, %1, %2, %3;\n" : "=r"(r) : "r"(a), "r"(b), "r"(sel));
    return r;
}
__device__ __forceinline__ float round_bf16(float x) { return __bfloat162float(__float2bfloat16_rn(x)); }

__device__ __forceinline__ void mbar_init(uint32_t bar, uint32_t count) {
    asm volatile("mbarrier.init.shared::cta.b64 [%0], %1;\n" :: "r"(bar), "r"(count) : "memory");
}
__device__ __forceinline__ void mbar_wait(uint32_t bar, uint32_t parity) {
    asm volatile(
        "{\n"
        ".reg .pred p;\n"
        ".reg .u32 n;\n"
        "mov.u32 n, 0;\n"
        "WAIT_%=:\n"
        "mbarrier.try_wait.parity.shared::cta.b64 p, [%0], %1" HINT ";\n"
        "@p bra DONE_%=;\n"
        "add.u32 n, n, 1;\n"
        "setp.lt.u32 p, n, 4194304;\n"
        "@p bra WAIT_%=;\n"
        "trap;\n"
        "DONE_%=:\n"
        "}\n" :: "r"(bar), "r"(parity) : "memory");
}
__device__ __forceinline__ void mbar_wait4(uint32_t b0, uint32_t p0, uint32_t b1, uint32_t p1, uint32_t b2, uint32_t p2,
                                           uint32_t b3, uint32_t p3) {
    asm volatile(
        "{\n"
        ".reg .pred p, q, r, s;\n"
        ".reg .u32 n;\n"
        "mov.u32 n, 0;\n"
        "WAIT_%=:\n"
        "mbarrier.try_wait.parity.shared::cta.b64 p, [%0], %1" HINT ";\n"
        "mbarrier.try_wait.parity.shared::cta.b64 q, [%2], %3" HINT ";\n"
        "mbarrier.try_wait.parity.shared::cta.b64 r, [%4], %5" HINT ";\n"
        "mbarrier.try_wait.parity.shared::cta.b64 s, [%6], %7" HINT ";\n"
        "and.pred p, p, q;\n"
        "and.pred r, r, s;\n"
        "and.pred p, p, r;\n"
        "@p bra DONE_%=;\n"
        "add.u32 n, n, 1;\n"
        "setp.lt.u32 p, n, 4194304;\n"
        "@p bra WAIT_%=;\n"
        "trap;\n"
        "DONE_%=:\n"
        "}\n" :: "r"(b0), "r"(p0), "r"(b1), "r"(p1), "r"(b2), "r"(p2), "r"(b3), "r"(p3) : "memory");
}
__device__ __forceinline__ void mbar_wait2(uint32_t b0, uint32_t p0, uint32_t b1, uint32_t p1) {
    asm volatile(
        "{\n"
        ".reg .pred p, q;\n"
        ".reg .u32 n;\n"
        "mov.u32 n, 0;\n"
        "WAIT_%=:\n"
        "mbarrier.try_wait.parity.shared::cta.b64 p, [%0], %1" HINT ";\n"
        "mbarrier.try_wait.parity.shared::cta.b64 q, [%2], %3" HINT ";\n"
        "and.pred p, p, q;\n"
        "@p bra DONE_%=;\n"
        "add.u32 n, n, 1;\n"
        "setp.lt.u32 p, n, 4194304;\n"
        "@p bra WAIT_%=;\n"
        "trap;\n"
        "DONE_%=:\n"
        "}\n" :: "r"(b0), "r"(p0), "r"(b1), "r"(p1) : "memory");
}
__device__ __forceinline__ void mbar_wait_unless(uint32_t ok, uint32_t bar, uint32_t parity) {
    asm volatile(
        "{\n"
        ".reg .pred p;\n"
        ".reg .u32 n;\n"
        "setp.ne.u32 p, %2, 0;\n"
        "vote.sync.all.pred p, p, 0xffffffff;\n"
        "@p bra DONE_%=;\n"
        "mov.u32 n, 0;\n"
        "WAIT_%=:\n"
        "mbarrier.try_wait.parity.shared::cta.b64 p, [%0], %1" HINT ";\n"
        "@p bra DONE_%=;\n"
        "add.u32 n, n, 1;\n"
        "setp.lt.u32 p, n, 4194304;\n"
        "@p bra WAIT_%=;\n"
        "trap;\n"
        "DONE_%=:\n"
        "}\n" :: "r"(bar), "r"(parity), "r"(ok) : "memory");
}
__device__ __forceinline__ void mbar_wait2_unless(uint32_t ok, uint32_t b0, uint32_t p0, uint32_t b1, uint32_t p1) {
    asm volatile(
        "{\n"
        ".reg .pred p, q;\n"
        ".reg .u32 n;\n"
        "setp.ne.u32 p, %4, 0;\n"
        "vote.sync.all.pred p, p, 0xffffffff;\n"
        "@p bra DONE_%=;\n"
        "mov.u32 n, 0;\n"
        "WAIT_%=:\n"
        "mbarrier.try_wait.parity.shared::cta.b64 p, [%0], %1" HINT ";\n"
        "mbarrier.try_wait.parity.shared::cta.b64 q, [%2], %3" HINT ";\n"
        "and.pred p, p, q;\n"
        "@p bra DONE_%=;\n"
        "add.u32 n, n, 1;\n"
        "setp.lt.u32 p, n, 4194304;\n"
        "@p bra WAIT_%=;\n"
        "trap;\n"
        "DONE_%=:\n"
        "}\n" :: "r"(b0), "r"(p0), "r"(b1), "r"(p1), "r"(ok) : "memory");
}
__device__ __forceinline__ void mbar_wait4_unless(uint32_t ok, uint32_t b0, uint32_t p0, uint32_t b1, uint32_t p1, uint32_t b2,
                                                  uint32_t p2, uint32_t b3, uint32_t p3) {
    asm volatile(
        "{\n"
        ".reg .pred p, q, r, s;\n"
        ".reg .u32 n;\n"
        "setp.ne.u32 p, %8, 0;\n"
        "vote.sync.all.pred p, p, 0xffffffff;\n"
        "@p bra DONE_%=;\n"
        "mov.u32 n, 0;\n"
        "WAIT_%=:\n"
        "mbarrier.try_wait.parity.shared::cta.b64 p, [%0], %1" HINT ";\n"
        "mbarrier.try_wait.parity.shared::cta.b64 q, [%2], %3" HINT ";\n"
        "mbarrier.try_wait.parity.shared::cta.b64 r, [%4], %5" HINT ";\n"
        "mbarrier.try_wait.parity.shared::cta.b64 s, [%6], %7" HINT ";\n"
        "and.pred p, p, q;\n"
        "and.pred r, r, s;\n"
        "and.pred p, p, r;\n"
        "@p bra DONE_%=;\n"
        "add.u32 n, n, 1;\n"
        "setp.lt.u32 p, n, 4194304;\n"
        "@p bra WAIT_%=;\n"
        "trap;\n"
        "DONE_%=:\n"
        "}\n" :: "r"(b0), "r"(p0), "r"(b1), "r"(p1), "r"(b2), "r"(p2), "r"(b3), "r"(p3), "r"(ok) : "memory");
}
__device__ __forceinline__ void sched_fence(uint32_t zero, uint32_t a, uint32_t b, uint32_t c, uint32_t d, uint32_t e = 0,
                                            uint32_t f = 0, uint32_t g = 0, uint32_t h = 0, uint32_t i = 0, uint32_t j = 0,
                                            uint32_t k = 0) {
    asm volatile("{\n.reg .pred p;\n.reg .u32 n;\nsetp.eq.u32 p, %0, 0;\n@p bra.uni DONE_%=;\nmov.u32 n, %0;\nSPIN_%=:\n"
                 "nanosleep.u32 %1;\nnanosleep.u32 %2;\nnanosleep.u32 %3;\nnanosleep.u32 %4;\nnanosleep.u32 %5;\n"
                 "nanosleep.u32 %6;\nnanosleep.u32 %7;\nnanosleep.u32 %8;\nnanosleep.u32 %9;\nnanosleep.u32 %10;\n"
                 "nanosleep.u32 %11;\nsub.u32 n, n, 1;\nsetp.ne.u32 p, n, 0;\n@p bra.uni SPIN_%=;\nDONE_%=:\n}\n"
                 :: "r"(zero), "r"(a), "r"(b), "r"(c), "r"(d), "r"(e), "r"(f), "r"(g), "r"(h), "r"(i), "r"(j), "r"(k) : "memory");
}
template <int N> __device__ __forceinline__ void use_regs(const uint32_t* v) {
    if constexpr (N >= 4) {
        asm volatile("nanosleep.u32 %0;\nnanosleep.u32 %1;\nnanosleep.u32 %2;\nnanosleep.u32 %3;\n" :: "r"(v[0]), "r"(v[1]), "r"(v[2]), "r"(v[3]) : "memory");
        use_regs<N - 4>(v + 4);
    } else if constexpr (N > 0) {
        asm volatile("nanosleep.u32 %0;\n" :: "r"(v[0]) : "memory");
        use_regs<N - 1>(v + 1);
    }
}
template <int N> __device__ __forceinline__ void sched_fence_n(uint32_t zero, const uint32_t (&v)[N]) {
    if (__builtin_expect(zero != 0, 0)) {
#pragma unroll 1
        for (uint32_t n = zero; n; n--) use_regs<N>(v);
    }
}
__device__ __forceinline__ void sched_fence_rw(uint32_t zero, uint32_t (&v)[13]) {
    asm volatile("{\n.reg .pred p;\n.reg .u32 n;\nsetp.eq.u32 p, %13, 0;\n@p bra.uni DONE_%=;\nmov.u32 n, %13;\nSPIN_%=:\n"
                 "add.u32 %0, %0, %1;\nadd.u32 %1, %1, %2;\nadd.u32 %2, %2, %3;\nadd.u32 %3, %3, %4;\nadd.u32 %4, %4, %5;\n"
                 "add.u32 %5, %5, %6;\nadd.u32 %6, %6, %7;\nadd.u32 %7, %7, %8;\nadd.u32 %8, %8, %9;\nadd.u32 %9, %9, %10;\n"
                 "add.u32 %10, %10, %11;\nadd.u32 %11, %11, %12;\nadd.u32 %12, %12, %0;\n"
                 "sub.u32 n, n, 1;\nsetp.ne.u32 p, n, 0;\n@p bra.uni SPIN_%=;\nDONE_%=:\n}\n"
                 : "+r"(v[0]), "+r"(v[1]), "+r"(v[2]), "+r"(v[3]), "+r"(v[4]), "+r"(v[5]), "+r"(v[6]), "+r"(v[7]), "+r"(v[8]),
                   "+r"(v[9]), "+r"(v[10]), "+r"(v[11]), "+r"(v[12]) : "r"(zero) : "memory");
}
__device__ __forceinline__ void mbar_arrive(uint32_t bar) {
    asm volatile("mbarrier.arrive.shared::cta.b64 _, [%0];\n" :: "r"(bar) : "memory");
}
__device__ __forceinline__ void mbar_arrive_n(uint32_t bar, uint32_t n) {
    asm volatile("mbarrier.arrive.shared::cta.b64 _, [%0], %1;\n" :: "r"(bar), "r"(n) : "memory");
}
__device__ __forceinline__ void mbar_arrive_expect_tx(uint32_t bar, uint32_t bytes) {
    asm volatile("mbarrier.arrive.expect_tx.shared::cta.b64 _, [%0], %1;\n" :: "r"(bar), "r"(bytes) : "memory");
}
__device__ __forceinline__ void stg128_if(bool p, void* addr, uint32_t x, uint32_t y, uint32_t z, uint32_t w) {
    asm volatile("{\n.reg .pred q;\nsetp.ne.b32 q, %5, 0;\n@q st.global.L1::no_allocate.v4.b32 [%0], {%1, %2, %3, %4};\n}\n"
                 :: "l"(addr), "r"(x), "r"(y), "r"(z), "r"(w), "r"((uint32_t)p) : "memory");
}
__device__ __forceinline__ void stsm_x4(uint32_t addr, uint32_t r0, uint32_t r1, uint32_t r2, uint32_t r3) {
    asm volatile("stmatrix.sync.aligned.m8n8.x4.shared.b16 [%0], {%1, %2, %3, %4};\n"
                 :: "r"(addr), "r"(r0), "r"(r1), "r"(r2), "r"(r3) : "memory");
}
__device__ __forceinline__ void stsm_x2(uint32_t addr, uint32_t r0, uint32_t r1) {
    asm volatile("stmatrix.sync.aligned.m8n8.x2.shared.b16 [%0], {%1, %2};\n" :: "r"(addr), "r"(r0), "r"(r1) : "memory");
}
__device__ __forceinline__ void sts128(uint32_t addr, uint32_t r0, uint32_t r1, uint32_t r2, uint32_t r3) {
    asm volatile("st.shared.v4.b32 [%0], {%1, %2, %3, %4};\n" :: "r"(addr), "r"(r0), "r"(r1), "r"(r2), "r"(r3) : "memory");
}
__device__ __forceinline__ void sts128_if(uint32_t p, uint32_t addr, uint32_t r0, uint32_t r1, uint32_t r2, uint32_t r3) {
    asm volatile("{\n.reg .pred q;\nsetp.ne.b32 q, %5, 0;\n@q st.shared.v4.b32 [%0], {%1, %2, %3, %4};\n}\n"
                 :: "r"(addr), "r"(r0), "r"(r1), "r"(r2), "r"(r3), "r"(p) : "memory");
}
__device__ __forceinline__ void sts32(uint32_t addr, uint32_t v) {
    asm volatile("st.shared.b32 [%0], %1;\n" :: "r"(addr), "r"(v) : "memory");
}
__device__ __forceinline__ uint32_t lds32(uint32_t addr) {
    uint32_t v;
    asm volatile("ld.shared.b32 %0, [%1];\n" : "=r"(v) : "r"(addr) : "memory");
    return v;
}
__device__ __forceinline__ void ldg_nc_v4(uint32_t (&r)[4], const void* p) {
    asm volatile("ld.global.nc.L1::no_allocate.v4.u32 {%0, %1, %2, %3}, [%4];\n"
                 : "=r"(r[0]), "=r"(r[1]), "=r"(r[2]), "=r"(r[3]) : "l"(p));
}
__device__ __forceinline__ uint32_t ldg_u32(const void* p) {
    uint32_t v;
    asm volatile("ld.global.nc.L1::evict_first.u32 %0, [%1];\n" : "=r"(v) : "l"(p));
    return v;
}
__device__ __forceinline__ void ldg_u64(const void* p, uint32_t& a, uint32_t& b) {
    asm volatile("ld.global.nc.L1::evict_first.v2.u32 {%0, %1}, [%2];\n" : "=r"(a), "=r"(b) : "l"(p));
}
__device__ __forceinline__ void prefetch_l2(const void* p) {
    asm volatile("prefetch.global.L2 [%0];\n" :: "l"(p));
}
__device__ __forceinline__ void cp_async16(uint32_t dst, const void* src) {
    asm volatile("cp.async.cg.shared.global [%0], [%1], 16;\n" :: "r"(dst), "l"(src) : "memory");
}
__device__ __forceinline__ float ex2_ftz(float x) {
    float y;
    asm("ex2.approx.ftz.f32 %0, %1;\n" : "=f"(y) : "f"(x));
    return y;
}
__device__ __forceinline__ float lg2_ftz(float x) {
    float y;
    asm("lg2.approx.ftz.f32 %0, %1;\n" : "=f"(y) : "f"(x));
    return y;
}
__device__ __forceinline__ float rcp_ftz(float x) {
    float y;
    asm("rcp.approx.ftz.f32 %0, %1;\n" : "=f"(y) : "f"(x));
    return y;
}
__device__ __forceinline__ float rsqrt_ftz(float x) {
    float y;
    asm("rsqrt.approx.ftz.f32 %0, %1;\n" : "=f"(y) : "f"(x));
    return y;
}

__device__ __forceinline__ bool elect_one() {
    uint32_t p;
    asm volatile("{\n.reg .pred q;\nelect.sync _|q, 0xffffffff;\nselp.u32 %0, 1, 0, q;\n}\n" : "=r"(p));
    return p != 0;
}
__device__ __forceinline__ void ldsm_x4(uint32_t (&r)[4], uint32_t addr) {
    asm volatile("ldmatrix.sync.aligned.m8n8.x4.shared.b16 {%0, %1, %2, %3}, [%4];\n"
                 : "=r"(r[0]), "=r"(r[1]), "=r"(r[2]), "=r"(r[3]) : "r"(addr) : "memory");
}
__device__ __forceinline__ void ldsm_x2(uint32_t& r0, uint32_t& r1, uint32_t addr) {
    asm volatile("ldmatrix.sync.aligned.m8n8.x2.shared.b16 {%0, %1}, [%2];\n" : "=r"(r0), "=r"(r1) : "r"(addr) : "memory");
}
__device__ __forceinline__ void tma_2d(uint32_t dst, const CUtensorMap* map, uint32_t bar, int c0, int c1) {
    asm volatile("cp.async.bulk.tensor.2d.shared::cluster.global.mbarrier::complete_tx::bytes [%0], [%1, {%3, %4}], [%2];\n"
                 :: "r"(dst), "l"(reinterpret_cast<uint64_t>(map)), "r"(bar), "r"(c0), "r"(c1) : "memory");
}
__device__ __forceinline__ void tma_3d(uint32_t dst, const CUtensorMap* map, uint32_t bar, int c0, int c1, int c2) {
    asm volatile("cp.async.bulk.tensor.3d.shared::cluster.global.mbarrier::complete_tx::bytes [%0], [%1, {%3, %4, %5}], [%2];\n"
                 :: "r"(dst), "l"(reinterpret_cast<uint64_t>(map)), "r"(bar), "r"(c0), "r"(c1), "r"(c2) : "memory");
}
constexpr uint64_t EVICT_FIRST = 0x12F0000000000000ull;
__device__ __forceinline__ void tma_3d_x(uint32_t dst, const CUtensorMap* map, uint32_t bar, int c0, int c1, int c2) {
    if (CH & 50)
        asm volatile("cp.async.bulk.tensor.3d.shared::cluster.global.mbarrier::complete_tx::bytes.L2::cache_hint [%0], [%1, {%3, %4, %5}], [%2], %6;\n"
                     :: "r"(dst), "l"(reinterpret_cast<uint64_t>(map)), "r"(bar), "r"(c0), "r"(c1), "r"(c2),
                        "l"((CH & 2) || (blockIdx.x & 1) == ((CH >> 5) & 1) ? EVICT_FIRST : 0x1000000000000000ull) : "memory");
    else tma_3d(dst, map, bar, c0, c1, c2);
}
__device__ __forceinline__ void tma_store_4d(const CUtensorMap* map, uint32_t src, int c0, int c1, int c2, int c3) {
    asm volatile("cp.async.bulk.tensor.4d.global.shared::cta.tile.bulk_group [%0, {%2, %3, %4, %5}], [%1];\n"
                 :: "l"(reinterpret_cast<uint64_t>(map)), "r"(src), "r"(c0), "r"(c1), "r"(c2), "r"(c3) : "memory");
}
__device__ __forceinline__ void mbar_arrive_if(uint32_t bar, uint32_t cnt) {
    asm volatile("{\n.reg .pred q;\nsetp.ne.b32 q, %1, 0;\n@q mbarrier.arrive.shared::cta.b64 _, [%0], %1;\n}\n"
                 :: "r"(bar), "r"(cnt) : "memory");
}

template <int BOFF, int AOFF, int NA>
__device__ __forceinline__ void mma_qkv_a(float (&d)[48], const uint32_t (&a)[NA][4], uint64_t descB) {
    asm volatile(
        "{\n"
        ".reg .pred p0, p1;\n"
        ".reg .b64 ta, ta0, tb, tb0;\n"
        "setp.ne.b32 p0, 0, 0;\n"
        "setp.eq.b32 p1, 0, 0;\n"
        "add.s64 tb0, %72, %73;\n"
        "add.s64 tb, tb0, 0;\n"
        "wgmma.mma_async.sync.aligned.m64n96k16.f32.bf16.bf16 {%0, %1, %2, %3, %4, %5, %6, %7, %8, %9, %10, %11, %12, %13, %14, %15, %16, %17, %18, %19, %20, %21, %22, %23, %24, %25, %26, %27, %28, %29, %30, %31, %32, %33, %34, %35, %36, %37, %38, %39, %40, %41, %42, %43, %44, %45, %46, %47}, {%48, %49, %50, %51}, tb, p0, 1, 1, 1;\n"
        "add.s64 tb, tb0, 32;\n"
        "wgmma.mma_async.sync.aligned.m64n96k16.f32.bf16.bf16 {%0, %1, %2, %3, %4, %5, %6, %7, %8, %9, %10, %11, %12, %13, %14, %15, %16, %17, %18, %19, %20, %21, %22, %23, %24, %25, %26, %27, %28, %29, %30, %31, %32, %33, %34, %35, %36, %37, %38, %39, %40, %41, %42, %43, %44, %45, %46, %47}, {%52, %53, %54, %55}, tb, p1, 1, 1, 1;\n"
        "add.s64 tb, tb0, 64;\n"
        "wgmma.mma_async.sync.aligned.m64n96k16.f32.bf16.bf16 {%0, %1, %2, %3, %4, %5, %6, %7, %8, %9, %10, %11, %12, %13, %14, %15, %16, %17, %18, %19, %20, %21, %22, %23, %24, %25, %26, %27, %28, %29, %30, %31, %32, %33, %34, %35, %36, %37, %38, %39, %40, %41, %42, %43, %44, %45, %46, %47}, {%56, %57, %58, %59}, tb, p1, 1, 1, 1;\n"
        "add.s64 tb, tb0, 96;\n"
        "wgmma.mma_async.sync.aligned.m64n96k16.f32.bf16.bf16 {%0, %1, %2, %3, %4, %5, %6, %7, %8, %9, %10, %11, %12, %13, %14, %15, %16, %17, %18, %19, %20, %21, %22, %23, %24, %25, %26, %27, %28, %29, %30, %31, %32, %33, %34, %35, %36, %37, %38, %39, %40, %41, %42, %43, %44, %45, %46, %47}, {%60, %61, %62, %63}, tb, p1, 1, 1, 1;\n"
        "add.s64 tb, tb0, 128;\n"
        "wgmma.mma_async.sync.aligned.m64n96k16.f32.bf16.bf16 {%0, %1, %2, %3, %4, %5, %6, %7, %8, %9, %10, %11, %12, %13, %14, %15, %16, %17, %18, %19, %20, %21, %22, %23, %24, %25, %26, %27, %28, %29, %30, %31, %32, %33, %34, %35, %36, %37, %38, %39, %40, %41, %42, %43, %44, %45, %46, %47}, {%64, %65, %66, %67}, tb, p1, 1, 1, 1;\n"
        "add.s64 tb, tb0, 160;\n"
        "wgmma.mma_async.sync.aligned.m64n96k16.f32.bf16.bf16 {%0, %1, %2, %3, %4, %5, %6, %7, %8, %9, %10, %11, %12, %13, %14, %15, %16, %17, %18, %19, %20, %21, %22, %23, %24, %25, %26, %27, %28, %29, %30, %31, %32, %33, %34, %35, %36, %37, %38, %39, %40, %41, %42, %43, %44, %45, %46, %47}, {%68, %69, %70, %71}, tb, p1, 1, 1, 1;\n"
        "}\n"
        : "=f"(d[0]), "=f"(d[1]), "=f"(d[2]), "=f"(d[3]), "=f"(d[4]), "=f"(d[5]), "=f"(d[6]), "=f"(d[7]), "=f"(d[8]), "=f"(d[9]), "=f"(d[10]), "=f"(d[11]), "=f"(d[12]), "=f"(d[13]), "=f"(d[14]), "=f"(d[15]), "=f"(d[16]), "=f"(d[17]), "=f"(d[18]), "=f"(d[19]), "=f"(d[20]), "=f"(d[21]), "=f"(d[22]), "=f"(d[23]), "=f"(d[24]), "=f"(d[25]), "=f"(d[26]), "=f"(d[27]), "=f"(d[28]), "=f"(d[29]), "=f"(d[30]), "=f"(d[31]), "=f"(d[32]), "=f"(d[33]), "=f"(d[34]), "=f"(d[35]), "=f"(d[36]), "=f"(d[37]), "=f"(d[38]), "=f"(d[39]), "=f"(d[40]), "=f"(d[41]), "=f"(d[42]), "=f"(d[43]), "=f"(d[44]), "=f"(d[45]), "=f"(d[46]), "=f"(d[47])
        : "r"(a[AOFF + 0][0]), "r"(a[AOFF + 0][1]), "r"(a[AOFF + 0][2]), "r"(a[AOFF + 0][3]), "r"(a[AOFF + 1][0]), "r"(a[AOFF + 1][1]), "r"(a[AOFF + 1][2]), "r"(a[AOFF + 1][3]), "r"(a[AOFF + 2][0]), "r"(a[AOFF + 2][1]), "r"(a[AOFF + 2][2]), "r"(a[AOFF + 2][3]), "r"(a[AOFF + 3][0]), "r"(a[AOFF + 3][1]), "r"(a[AOFF + 3][2]), "r"(a[AOFF + 3][3]), "r"(a[AOFF + 4][0]), "r"(a[AOFF + 4][1]), "r"(a[AOFF + 4][2]), "r"(a[AOFF + 4][3]), "r"(a[AOFF + 5][0]), "r"(a[AOFF + 5][1]), "r"(a[AOFF + 5][2]), "r"(a[AOFF + 5][3]), "l"(descB), "n"(BOFF >> 4));
}

template <int BOFF, int AOFF, int NA>
__device__ __forceinline__ void mma_qkv_b(float (&d)[48], const uint32_t (&a)[NA][4], uint64_t descB) {
    asm volatile(
        "{\n"
        ".reg .pred p0, p1;\n"
        ".reg .b64 ta, ta0, tb, tb0;\n"
        "setp.ne.b32 p0, 0, 0;\n"
        "setp.eq.b32 p1, 0, 0;\n"
        "add.s64 tb0, %72, %73;\n"
        "add.s64 tb, tb0, 192;\n"
        "wgmma.mma_async.sync.aligned.m64n96k16.f32.bf16.bf16 {%0, %1, %2, %3, %4, %5, %6, %7, %8, %9, %10, %11, %12, %13, %14, %15, %16, %17, %18, %19, %20, %21, %22, %23, %24, %25, %26, %27, %28, %29, %30, %31, %32, %33, %34, %35, %36, %37, %38, %39, %40, %41, %42, %43, %44, %45, %46, %47}, {%48, %49, %50, %51}, tb, p1, 1, 1, 1;\n"
        "add.s64 tb, tb0, 224;\n"
        "wgmma.mma_async.sync.aligned.m64n96k16.f32.bf16.bf16 {%0, %1, %2, %3, %4, %5, %6, %7, %8, %9, %10, %11, %12, %13, %14, %15, %16, %17, %18, %19, %20, %21, %22, %23, %24, %25, %26, %27, %28, %29, %30, %31, %32, %33, %34, %35, %36, %37, %38, %39, %40, %41, %42, %43, %44, %45, %46, %47}, {%52, %53, %54, %55}, tb, p1, 1, 1, 1;\n"
        "add.s64 tb, tb0, 256;\n"
        "wgmma.mma_async.sync.aligned.m64n96k16.f32.bf16.bf16 {%0, %1, %2, %3, %4, %5, %6, %7, %8, %9, %10, %11, %12, %13, %14, %15, %16, %17, %18, %19, %20, %21, %22, %23, %24, %25, %26, %27, %28, %29, %30, %31, %32, %33, %34, %35, %36, %37, %38, %39, %40, %41, %42, %43, %44, %45, %46, %47}, {%56, %57, %58, %59}, tb, p1, 1, 1, 1;\n"
        "add.s64 tb, tb0, 288;\n"
        "wgmma.mma_async.sync.aligned.m64n96k16.f32.bf16.bf16 {%0, %1, %2, %3, %4, %5, %6, %7, %8, %9, %10, %11, %12, %13, %14, %15, %16, %17, %18, %19, %20, %21, %22, %23, %24, %25, %26, %27, %28, %29, %30, %31, %32, %33, %34, %35, %36, %37, %38, %39, %40, %41, %42, %43, %44, %45, %46, %47}, {%60, %61, %62, %63}, tb, p1, 1, 1, 1;\n"
        "add.s64 tb, tb0, 320;\n"
        "wgmma.mma_async.sync.aligned.m64n96k16.f32.bf16.bf16 {%0, %1, %2, %3, %4, %5, %6, %7, %8, %9, %10, %11, %12, %13, %14, %15, %16, %17, %18, %19, %20, %21, %22, %23, %24, %25, %26, %27, %28, %29, %30, %31, %32, %33, %34, %35, %36, %37, %38, %39, %40, %41, %42, %43, %44, %45, %46, %47}, {%64, %65, %66, %67}, tb, p1, 1, 1, 1;\n"
        "add.s64 tb, tb0, 352;\n"
        "wgmma.mma_async.sync.aligned.m64n96k16.f32.bf16.bf16 {%0, %1, %2, %3, %4, %5, %6, %7, %8, %9, %10, %11, %12, %13, %14, %15, %16, %17, %18, %19, %20, %21, %22, %23, %24, %25, %26, %27, %28, %29, %30, %31, %32, %33, %34, %35, %36, %37, %38, %39, %40, %41, %42, %43, %44, %45, %46, %47}, {%68, %69, %70, %71}, tb, p1, 1, 1, 1;\n"
        "}\n"
        : "+f"(d[0]), "+f"(d[1]), "+f"(d[2]), "+f"(d[3]), "+f"(d[4]), "+f"(d[5]), "+f"(d[6]), "+f"(d[7]), "+f"(d[8]), "+f"(d[9]), "+f"(d[10]), "+f"(d[11]), "+f"(d[12]), "+f"(d[13]), "+f"(d[14]), "+f"(d[15]), "+f"(d[16]), "+f"(d[17]), "+f"(d[18]), "+f"(d[19]), "+f"(d[20]), "+f"(d[21]), "+f"(d[22]), "+f"(d[23]), "+f"(d[24]), "+f"(d[25]), "+f"(d[26]), "+f"(d[27]), "+f"(d[28]), "+f"(d[29]), "+f"(d[30]), "+f"(d[31]), "+f"(d[32]), "+f"(d[33]), "+f"(d[34]), "+f"(d[35]), "+f"(d[36]), "+f"(d[37]), "+f"(d[38]), "+f"(d[39]), "+f"(d[40]), "+f"(d[41]), "+f"(d[42]), "+f"(d[43]), "+f"(d[44]), "+f"(d[45]), "+f"(d[46]), "+f"(d[47])
        : "r"(a[AOFF + 0][0]), "r"(a[AOFF + 0][1]), "r"(a[AOFF + 0][2]), "r"(a[AOFF + 0][3]), "r"(a[AOFF + 1][0]), "r"(a[AOFF + 1][1]), "r"(a[AOFF + 1][2]), "r"(a[AOFF + 1][3]), "r"(a[AOFF + 2][0]), "r"(a[AOFF + 2][1]), "r"(a[AOFF + 2][2]), "r"(a[AOFF + 2][3]), "r"(a[AOFF + 3][0]), "r"(a[AOFF + 3][1]), "r"(a[AOFF + 3][2]), "r"(a[AOFF + 3][3]), "r"(a[AOFF + 4][0]), "r"(a[AOFF + 4][1]), "r"(a[AOFF + 4][2]), "r"(a[AOFF + 4][3]), "r"(a[AOFF + 5][0]), "r"(a[AOFF + 5][1]), "r"(a[AOFF + 5][2]), "r"(a[AOFF + 5][3]), "l"(descB), "n"(BOFF >> 4));
}

template <int AOFF, int BOFF>
__device__ __forceinline__ void mma_qk0(float (&d)[28], uint64_t descA, uint64_t descB) {
    asm volatile(
        "{\n"
        ".reg .pred p0, p1;\n"
        ".reg .b64 ta, ta0, tb, tb0;\n"
        "setp.ne.b32 p0, 0, 0;\n"
        "setp.eq.b32 p1, 0, 0;\n"
        "add.s64 tb0, %30, %31;\n"
        "add.s64 ta0, %28, %29;\n"
        "add.s64 tb, tb0, 4;\n"
        "add.s64 ta, ta0, 0;\n"
        "wgmma.mma_async.sync.aligned.m64n56k16.f32.bf16.bf16 {%0, %1, %2, %3, %4, %5, %6, %7, %8, %9, %10, %11, %12, %13, %14, %15, %16, %17, %18, %19, %20, %21, %22, %23, %24, %25, %26, %27}, ta, tb, p0, 1, 1, 0, 0;\n"
        "add.s64 tb, tb0, 1572;\n"
        "add.s64 ta, ta0, 1568;\n"
        "wgmma.mma_async.sync.aligned.m64n56k16.f32.bf16.bf16 {%0, %1, %2, %3, %4, %5, %6, %7, %8, %9, %10, %11, %12, %13, %14, %15, %16, %17, %18, %19, %20, %21, %22, %23, %24, %25, %26, %27}, ta, tb, p1, 1, 1, 0, 0;\n"
        "add.s64 tb, tb0, 3140;\n"
        "add.s64 ta, ta0, 3136;\n"
        "wgmma.mma_async.sync.aligned.m64n56k16.f32.bf16.bf16 {%0, %1, %2, %3, %4, %5, %6, %7, %8, %9, %10, %11, %12, %13, %14, %15, %16, %17, %18, %19, %20, %21, %22, %23, %24, %25, %26, %27}, ta, tb, p1, 1, 1, 0, 0;\n"
        "}\n"
        : "=f"(d[0]), "=f"(d[1]), "=f"(d[2]), "=f"(d[3]), "=f"(d[4]), "=f"(d[5]), "=f"(d[6]), "=f"(d[7]), "=f"(d[8]), "=f"(d[9]), "=f"(d[10]), "=f"(d[11]), "=f"(d[12]), "=f"(d[13]), "=f"(d[14]), "=f"(d[15]), "=f"(d[16]), "=f"(d[17]), "=f"(d[18]), "=f"(d[19]), "=f"(d[20]), "=f"(d[21]), "=f"(d[22]), "=f"(d[23]), "=f"(d[24]), "=f"(d[25]), "=f"(d[26]), "=f"(d[27])
        : "l"(descA), "n"(AOFF >> 4), "l"(descB), "n"(BOFF >> 4));
}

template <int AOFF, int BOFF>
__device__ __forceinline__ void mma_qk1(float (&d)[28], uint64_t descA, uint64_t descB) {
    asm volatile(
        "{\n"
        ".reg .pred p0, p1;\n"
        ".reg .b64 ta, ta0, tb, tb0;\n"
        "setp.ne.b32 p0, 0, 0;\n"
        "setp.eq.b32 p1, 0, 0;\n"
        "add.s64 tb0, %30, %31;\n"
        "add.s64 ta0, %28, %29;\n"
        "add.s64 tb, tb0, 6;\n"
        "add.s64 ta, ta0, 2;\n"
        "wgmma.mma_async.sync.aligned.m64n56k16.f32.bf16.bf16 {%0, %1, %2, %3, %4, %5, %6, %7, %8, %9, %10, %11, %12, %13, %14, %15, %16, %17, %18, %19, %20, %21, %22, %23, %24, %25, %26, %27}, ta, tb, p0, 1, 1, 0, 0;\n"
        "add.s64 tb, tb0, 1574;\n"
        "add.s64 ta, ta0, 1570;\n"
        "wgmma.mma_async.sync.aligned.m64n56k16.f32.bf16.bf16 {%0, %1, %2, %3, %4, %5, %6, %7, %8, %9, %10, %11, %12, %13, %14, %15, %16, %17, %18, %19, %20, %21, %22, %23, %24, %25, %26, %27}, ta, tb, p1, 1, 1, 0, 0;\n"
        "add.s64 tb, tb0, 3142;\n"
        "add.s64 ta, ta0, 3138;\n"
        "wgmma.mma_async.sync.aligned.m64n56k16.f32.bf16.bf16 {%0, %1, %2, %3, %4, %5, %6, %7, %8, %9, %10, %11, %12, %13, %14, %15, %16, %17, %18, %19, %20, %21, %22, %23, %24, %25, %26, %27}, ta, tb, p1, 1, 1, 0, 0;\n"
        "}\n"
        : "=f"(d[0]), "=f"(d[1]), "=f"(d[2]), "=f"(d[3]), "=f"(d[4]), "=f"(d[5]), "=f"(d[6]), "=f"(d[7]), "=f"(d[8]), "=f"(d[9]), "=f"(d[10]), "=f"(d[11]), "=f"(d[12]), "=f"(d[13]), "=f"(d[14]), "=f"(d[15]), "=f"(d[16]), "=f"(d[17]), "=f"(d[18]), "=f"(d[19]), "=f"(d[20]), "=f"(d[21]), "=f"(d[22]), "=f"(d[23]), "=f"(d[24]), "=f"(d[25]), "=f"(d[26]), "=f"(d[27])
        : "l"(descA), "n"(AOFF >> 4), "l"(descB), "n"(BOFF >> 4));
}

template <int BOFF, int AOFF, int NA>
__device__ __forceinline__ void mma_pv(float (&d)[28], const uint32_t (&a)[NA][4], uint64_t descB) {
    asm volatile(
        "{\n"
        ".reg .pred p0, p1;\n"
        ".reg .b64 ta, ta0, tb, tb0;\n"
        "setp.ne.b32 p0, 0, 0;\n"
        "setp.eq.b32 p1, 0, 0;\n"
        "add.s64 tb0, %44, %45;\n"
        "add.s64 tb, tb0, 0;\n"
        "wgmma.mma_async.sync.aligned.m64n56k16.f32.bf16.bf16 {%0, %1, %2, %3, %4, %5, %6, %7, %8, %9, %10, %11, %12, %13, %14, %15, %16, %17, %18, %19, %20, %21, %22, %23, %24, %25, %26, %27}, {%28, %29, %30, %31}, tb, p0, 1, 1, 1;\n"
        "add.s64 tb, tb0, 16;\n"
        "wgmma.mma_async.sync.aligned.m64n56k16.f32.bf16.bf16 {%0, %1, %2, %3, %4, %5, %6, %7, %8, %9, %10, %11, %12, %13, %14, %15, %16, %17, %18, %19, %20, %21, %22, %23, %24, %25, %26, %27}, {%32, %33, %34, %35}, tb, p1, 1, 1, 1;\n"
        "add.s64 tb, tb0, 32;\n"
        "wgmma.mma_async.sync.aligned.m64n56k16.f32.bf16.bf16 {%0, %1, %2, %3, %4, %5, %6, %7, %8, %9, %10, %11, %12, %13, %14, %15, %16, %17, %18, %19, %20, %21, %22, %23, %24, %25, %26, %27}, {%36, %37, %38, %39}, tb, p1, 1, 1, 1;\n"
        "add.s64 tb, tb0, 48;\n"
        "wgmma.mma_async.sync.aligned.m64n56k16.f32.bf16.bf16 {%0, %1, %2, %3, %4, %5, %6, %7, %8, %9, %10, %11, %12, %13, %14, %15, %16, %17, %18, %19, %20, %21, %22, %23, %24, %25, %26, %27}, {%40, %41, %42, %43}, tb, p1, 1, 1, 1;\n"
        "}\n"
        : "=f"(d[0]), "=f"(d[1]), "=f"(d[2]), "=f"(d[3]), "=f"(d[4]), "=f"(d[5]), "=f"(d[6]), "=f"(d[7]), "=f"(d[8]), "=f"(d[9]), "=f"(d[10]), "=f"(d[11]), "=f"(d[12]), "=f"(d[13]), "=f"(d[14]), "=f"(d[15]), "=f"(d[16]), "=f"(d[17]), "=f"(d[18]), "=f"(d[19]), "=f"(d[20]), "=f"(d[21]), "=f"(d[22]), "=f"(d[23]), "=f"(d[24]), "=f"(d[25]), "=f"(d[26]), "=f"(d[27])
        : "r"(a[AOFF + 0][0]), "r"(a[AOFF + 0][1]), "r"(a[AOFF + 0][2]), "r"(a[AOFF + 0][3]), "r"(a[AOFF + 1][0]), "r"(a[AOFF + 1][1]), "r"(a[AOFF + 1][2]), "r"(a[AOFF + 1][3]), "r"(a[AOFF + 2][0]), "r"(a[AOFF + 2][1]), "r"(a[AOFF + 2][2]), "r"(a[AOFF + 2][3]), "r"(a[AOFF + 3][0]), "r"(a[AOFF + 3][1]), "r"(a[AOFF + 3][2]), "r"(a[AOFF + 3][3]), "l"(descB), "n"(BOFF >> 4));
}

template <int AOFF, int BOFF>
__device__ __forceinline__ void mma_proj(float (&d)[96], uint64_t descA, uint64_t descB) {
    asm volatile(
        "{\n"
        ".reg .pred p0, p1;\n"
        ".reg .b64 ta, ta0, tb, tb0;\n"
        "setp.ne.b32 p0, 0, 0;\n"
        "setp.eq.b32 p1, 0, 0;\n"
        "add.s64 tb0, %98, %99;\n"
        "add.s64 ta0, %96, %97;\n"
        "add.s64 tb, tb0, 0;\n"
        "add.s64 ta, ta0, 0;\n"
        "wgmma.mma_async.sync.aligned.m64n192k16.f32.bf16.bf16 {%0, %1, %2, %3, %4, %5, %6, %7, %8, %9, %10, %11, %12, %13, %14, %15, %16, %17, %18, %19, %20, %21, %22, %23, %24, %25, %26, %27, %28, %29, %30, %31, %32, %33, %34, %35, %36, %37, %38, %39, %40, %41, %42, %43, %44, %45, %46, %47, %48, %49, %50, %51, %52, %53, %54, %55, %56, %57, %58, %59, %60, %61, %62, %63, %64, %65, %66, %67, %68, %69, %70, %71, %72, %73, %74, %75, %76, %77, %78, %79, %80, %81, %82, %83, %84, %85, %86, %87, %88, %89, %90, %91, %92, %93, %94, %95}, ta, tb, p0, 1, 1, 0, 1;\n"
        "add.s64 tb, tb0, 64;\n"
        "add.s64 ta, ta0, 2;\n"
        "wgmma.mma_async.sync.aligned.m64n192k16.f32.bf16.bf16 {%0, %1, %2, %3, %4, %5, %6, %7, %8, %9, %10, %11, %12, %13, %14, %15, %16, %17, %18, %19, %20, %21, %22, %23, %24, %25, %26, %27, %28, %29, %30, %31, %32, %33, %34, %35, %36, %37, %38, %39, %40, %41, %42, %43, %44, %45, %46, %47, %48, %49, %50, %51, %52, %53, %54, %55, %56, %57, %58, %59, %60, %61, %62, %63, %64, %65, %66, %67, %68, %69, %70, %71, %72, %73, %74, %75, %76, %77, %78, %79, %80, %81, %82, %83, %84, %85, %86, %87, %88, %89, %90, %91, %92, %93, %94, %95}, ta, tb, p1, 1, 1, 0, 1;\n"
        "add.s64 tb, tb0, 128;\n"
        "add.s64 ta, ta0, 4;\n"
        "wgmma.mma_async.sync.aligned.m64n192k16.f32.bf16.bf16 {%0, %1, %2, %3, %4, %5, %6, %7, %8, %9, %10, %11, %12, %13, %14, %15, %16, %17, %18, %19, %20, %21, %22, %23, %24, %25, %26, %27, %28, %29, %30, %31, %32, %33, %34, %35, %36, %37, %38, %39, %40, %41, %42, %43, %44, %45, %46, %47, %48, %49, %50, %51, %52, %53, %54, %55, %56, %57, %58, %59, %60, %61, %62, %63, %64, %65, %66, %67, %68, %69, %70, %71, %72, %73, %74, %75, %76, %77, %78, %79, %80, %81, %82, %83, %84, %85, %86, %87, %88, %89, %90, %91, %92, %93, %94, %95}, ta, tb, p1, 1, 1, 0, 1;\n"
        "add.s64 tb, tb0, 192;\n"
        "add.s64 ta, ta0, 6;\n"
        "wgmma.mma_async.sync.aligned.m64n192k16.f32.bf16.bf16 {%0, %1, %2, %3, %4, %5, %6, %7, %8, %9, %10, %11, %12, %13, %14, %15, %16, %17, %18, %19, %20, %21, %22, %23, %24, %25, %26, %27, %28, %29, %30, %31, %32, %33, %34, %35, %36, %37, %38, %39, %40, %41, %42, %43, %44, %45, %46, %47, %48, %49, %50, %51, %52, %53, %54, %55, %56, %57, %58, %59, %60, %61, %62, %63, %64, %65, %66, %67, %68, %69, %70, %71, %72, %73, %74, %75, %76, %77, %78, %79, %80, %81, %82, %83, %84, %85, %86, %87, %88, %89, %90, %91, %92, %93, %94, %95}, ta, tb, p1, 1, 1, 0, 1;\n"
        "add.s64 tb, tb0, 256;\n"
        "add.s64 ta, ta0, 512;\n"
        "wgmma.mma_async.sync.aligned.m64n192k16.f32.bf16.bf16 {%0, %1, %2, %3, %4, %5, %6, %7, %8, %9, %10, %11, %12, %13, %14, %15, %16, %17, %18, %19, %20, %21, %22, %23, %24, %25, %26, %27, %28, %29, %30, %31, %32, %33, %34, %35, %36, %37, %38, %39, %40, %41, %42, %43, %44, %45, %46, %47, %48, %49, %50, %51, %52, %53, %54, %55, %56, %57, %58, %59, %60, %61, %62, %63, %64, %65, %66, %67, %68, %69, %70, %71, %72, %73, %74, %75, %76, %77, %78, %79, %80, %81, %82, %83, %84, %85, %86, %87, %88, %89, %90, %91, %92, %93, %94, %95}, ta, tb, p1, 1, 1, 0, 1;\n"
        "add.s64 tb, tb0, 320;\n"
        "add.s64 ta, ta0, 514;\n"
        "wgmma.mma_async.sync.aligned.m64n192k16.f32.bf16.bf16 {%0, %1, %2, %3, %4, %5, %6, %7, %8, %9, %10, %11, %12, %13, %14, %15, %16, %17, %18, %19, %20, %21, %22, %23, %24, %25, %26, %27, %28, %29, %30, %31, %32, %33, %34, %35, %36, %37, %38, %39, %40, %41, %42, %43, %44, %45, %46, %47, %48, %49, %50, %51, %52, %53, %54, %55, %56, %57, %58, %59, %60, %61, %62, %63, %64, %65, %66, %67, %68, %69, %70, %71, %72, %73, %74, %75, %76, %77, %78, %79, %80, %81, %82, %83, %84, %85, %86, %87, %88, %89, %90, %91, %92, %93, %94, %95}, ta, tb, p1, 1, 1, 0, 1;\n"
        "add.s64 tb, tb0, 384;\n"
        "add.s64 ta, ta0, 516;\n"
        "wgmma.mma_async.sync.aligned.m64n192k16.f32.bf16.bf16 {%0, %1, %2, %3, %4, %5, %6, %7, %8, %9, %10, %11, %12, %13, %14, %15, %16, %17, %18, %19, %20, %21, %22, %23, %24, %25, %26, %27, %28, %29, %30, %31, %32, %33, %34, %35, %36, %37, %38, %39, %40, %41, %42, %43, %44, %45, %46, %47, %48, %49, %50, %51, %52, %53, %54, %55, %56, %57, %58, %59, %60, %61, %62, %63, %64, %65, %66, %67, %68, %69, %70, %71, %72, %73, %74, %75, %76, %77, %78, %79, %80, %81, %82, %83, %84, %85, %86, %87, %88, %89, %90, %91, %92, %93, %94, %95}, ta, tb, p1, 1, 1, 0, 1;\n"
        "add.s64 tb, tb0, 448;\n"
        "add.s64 ta, ta0, 518;\n"
        "wgmma.mma_async.sync.aligned.m64n192k16.f32.bf16.bf16 {%0, %1, %2, %3, %4, %5, %6, %7, %8, %9, %10, %11, %12, %13, %14, %15, %16, %17, %18, %19, %20, %21, %22, %23, %24, %25, %26, %27, %28, %29, %30, %31, %32, %33, %34, %35, %36, %37, %38, %39, %40, %41, %42, %43, %44, %45, %46, %47, %48, %49, %50, %51, %52, %53, %54, %55, %56, %57, %58, %59, %60, %61, %62, %63, %64, %65, %66, %67, %68, %69, %70, %71, %72, %73, %74, %75, %76, %77, %78, %79, %80, %81, %82, %83, %84, %85, %86, %87, %88, %89, %90, %91, %92, %93, %94, %95}, ta, tb, p1, 1, 1, 0, 1;\n"
        "add.s64 tb, tb0, 512;\n"
        "add.s64 ta, ta0, 1024;\n"
        "wgmma.mma_async.sync.aligned.m64n192k16.f32.bf16.bf16 {%0, %1, %2, %3, %4, %5, %6, %7, %8, %9, %10, %11, %12, %13, %14, %15, %16, %17, %18, %19, %20, %21, %22, %23, %24, %25, %26, %27, %28, %29, %30, %31, %32, %33, %34, %35, %36, %37, %38, %39, %40, %41, %42, %43, %44, %45, %46, %47, %48, %49, %50, %51, %52, %53, %54, %55, %56, %57, %58, %59, %60, %61, %62, %63, %64, %65, %66, %67, %68, %69, %70, %71, %72, %73, %74, %75, %76, %77, %78, %79, %80, %81, %82, %83, %84, %85, %86, %87, %88, %89, %90, %91, %92, %93, %94, %95}, ta, tb, p1, 1, 1, 0, 1;\n"
        "add.s64 tb, tb0, 576;\n"
        "add.s64 ta, ta0, 1026;\n"
        "wgmma.mma_async.sync.aligned.m64n192k16.f32.bf16.bf16 {%0, %1, %2, %3, %4, %5, %6, %7, %8, %9, %10, %11, %12, %13, %14, %15, %16, %17, %18, %19, %20, %21, %22, %23, %24, %25, %26, %27, %28, %29, %30, %31, %32, %33, %34, %35, %36, %37, %38, %39, %40, %41, %42, %43, %44, %45, %46, %47, %48, %49, %50, %51, %52, %53, %54, %55, %56, %57, %58, %59, %60, %61, %62, %63, %64, %65, %66, %67, %68, %69, %70, %71, %72, %73, %74, %75, %76, %77, %78, %79, %80, %81, %82, %83, %84, %85, %86, %87, %88, %89, %90, %91, %92, %93, %94, %95}, ta, tb, p1, 1, 1, 0, 1;\n"
        "add.s64 tb, tb0, 640;\n"
        "add.s64 ta, ta0, 1028;\n"
        "wgmma.mma_async.sync.aligned.m64n192k16.f32.bf16.bf16 {%0, %1, %2, %3, %4, %5, %6, %7, %8, %9, %10, %11, %12, %13, %14, %15, %16, %17, %18, %19, %20, %21, %22, %23, %24, %25, %26, %27, %28, %29, %30, %31, %32, %33, %34, %35, %36, %37, %38, %39, %40, %41, %42, %43, %44, %45, %46, %47, %48, %49, %50, %51, %52, %53, %54, %55, %56, %57, %58, %59, %60, %61, %62, %63, %64, %65, %66, %67, %68, %69, %70, %71, %72, %73, %74, %75, %76, %77, %78, %79, %80, %81, %82, %83, %84, %85, %86, %87, %88, %89, %90, %91, %92, %93, %94, %95}, ta, tb, p1, 1, 1, 0, 1;\n"
        "add.s64 tb, tb0, 704;\n"
        "add.s64 ta, ta0, 1030;\n"
        "wgmma.mma_async.sync.aligned.m64n192k16.f32.bf16.bf16 {%0, %1, %2, %3, %4, %5, %6, %7, %8, %9, %10, %11, %12, %13, %14, %15, %16, %17, %18, %19, %20, %21, %22, %23, %24, %25, %26, %27, %28, %29, %30, %31, %32, %33, %34, %35, %36, %37, %38, %39, %40, %41, %42, %43, %44, %45, %46, %47, %48, %49, %50, %51, %52, %53, %54, %55, %56, %57, %58, %59, %60, %61, %62, %63, %64, %65, %66, %67, %68, %69, %70, %71, %72, %73, %74, %75, %76, %77, %78, %79, %80, %81, %82, %83, %84, %85, %86, %87, %88, %89, %90, %91, %92, %93, %94, %95}, ta, tb, p1, 1, 1, 0, 1;\n"
        "}\n"
        : "+f"(d[0]), "+f"(d[1]), "+f"(d[2]), "+f"(d[3]), "+f"(d[4]), "+f"(d[5]), "+f"(d[6]), "+f"(d[7]), "+f"(d[8]), "+f"(d[9]), "+f"(d[10]), "+f"(d[11]), "+f"(d[12]), "+f"(d[13]), "+f"(d[14]), "+f"(d[15]), "+f"(d[16]), "+f"(d[17]), "+f"(d[18]), "+f"(d[19]), "+f"(d[20]), "+f"(d[21]), "+f"(d[22]), "+f"(d[23]), "+f"(d[24]), "+f"(d[25]), "+f"(d[26]), "+f"(d[27]), "+f"(d[28]), "+f"(d[29]), "+f"(d[30]), "+f"(d[31]), "+f"(d[32]), "+f"(d[33]), "+f"(d[34]), "+f"(d[35]), "+f"(d[36]), "+f"(d[37]), "+f"(d[38]), "+f"(d[39]), "+f"(d[40]), "+f"(d[41]), "+f"(d[42]), "+f"(d[43]), "+f"(d[44]), "+f"(d[45]), "+f"(d[46]), "+f"(d[47]), "+f"(d[48]), "+f"(d[49]), "+f"(d[50]), "+f"(d[51]), "+f"(d[52]), "+f"(d[53]), "+f"(d[54]), "+f"(d[55]), "+f"(d[56]), "+f"(d[57]), "+f"(d[58]), "+f"(d[59]), "+f"(d[60]), "+f"(d[61]), "+f"(d[62]), "+f"(d[63]), "+f"(d[64]), "+f"(d[65]), "+f"(d[66]), "+f"(d[67]), "+f"(d[68]), "+f"(d[69]), "+f"(d[70]), "+f"(d[71]), "+f"(d[72]), "+f"(d[73]), "+f"(d[74]), "+f"(d[75]), "+f"(d[76]), "+f"(d[77]), "+f"(d[78]), "+f"(d[79]), "+f"(d[80]), "+f"(d[81]), "+f"(d[82]), "+f"(d[83]), "+f"(d[84]), "+f"(d[85]), "+f"(d[86]), "+f"(d[87]), "+f"(d[88]), "+f"(d[89]), "+f"(d[90]), "+f"(d[91]), "+f"(d[92]), "+f"(d[93]), "+f"(d[94]), "+f"(d[95])
        : "l"(descA), "n"(AOFF >> 4), "l"(descB), "n"(BOFF >> 4));
}

struct Params {
    const __nv_bfloat16* x;
    const __nv_bfloat16* wqkv;
    const __nv_bfloat16* wo;
    const __nv_bfloat16* logit_scale;
    const __nv_bfloat16* cpb_w1;
    const __nv_bfloat16* cpb_w2;
    const __nv_bfloat16* rel_coords;
    const int*           rel_idx;
    const __nv_bfloat16* mask;
    __nv_bfloat16*       out;
    unsigned long long   z1;
    int                  npair;
    uint32_t             need;
    int                  nq, nr;
    int                  nr2, nt0, nt1;
    int                  t1;
};

struct Maps {
    CUtensorMap x77, x47, x37, x44, x43, x34, x33;
    CUtensorMap s47, s37, s43, s33;
    CUtensorMap o, ob, w, wraw;
};

__device__ __forceinline__ uint32_t row_token(uint32_t r) {
    return r < 28 ? r + 3 * (r >> 2) : r - 24 + 4 * (((r - 28) * 11) >> 5);
}
__device__ __forceinline__ int unrot(int r) { return r ? r - 1 : NWS - 1; }
__device__ __forceinline__ void finish(uint32_t total) {
    __threadfence();
    if (atomicAdd(&g_done, 1u) == total - 1) {
        for (int i = 0; i <= NWS; i++) g_cnt[i] = 0;
        g_done = 0;
    }
}

__global__ void __launch_bounds__(NTHREADS, 1)
swin_window_attn_kernel(const Params P, const __grid_constant__ Maps M) {
    const CUtensorMap &xmap = M.x77, &omap = M.o, &omapb = M.ob, &wmap = M.w, &wraw = M.wraw;
    extern __shared__ __align__(1024) uint8_t smem[];
    constexpr uint32_t sbase = 1024;
    if (smem_u32(smem) != sbase) return;
    const int tid = threadIdx.x;
    const int wg = __shfl_sync(0xffffffffu, tid >> 7, 0);
    const int warp = __shfl_sync(0xffffffffu, (tid >> 5) & 3, 0);
    const int lane = tid & 31;
    const int g = lane >> 2, c = lane & 3;

    TR(26, wg);
    if (tid == 0) TC(0);
    const bool attn = (int)blockIdx.x < 2 * P.npair;
    const int pair = blockIdx.x >> 1, half = blockIdx.x & 1;
    const int nwin = P.nq + (pair < P.nr ? 1 : 0);
    const int ntiles = (nwin * TOK + 63) >> 6;
    const uint32_t bars = sbase + SM_BAR;
    auto load_x = [&](uint32_t dst, uint32_t bar, uint32_t bar2, int wh, int ww) {
        const int x0 = 7 * ww + 3, y0 = 7 * wh + 3, x1 = ww == NWS - 1 ? 0 : x0 + 4;
        if (wh < NWS - 1) {
#pragma unroll
            for (int ch = 0; ch < 3; ch++) tma_3d_x(dst + ch * QK_CHUNK, &M.x47, bar, ch * 64, x0, y0);
#pragma unroll
            for (int ch = 0; ch < 3; ch++) tma_3d_x(dst + ch * QK_CHUNK + 28 * 128, &M.x37, bar2, ch * 64, x1, y0);
        } else {
#pragma unroll
            for (int ch = 0; ch < 3; ch++) {
                tma_3d_x(dst + ch * QK_CHUNK, &M.x44, bar, ch * 64, x0, y0);
                tma_3d_x(dst + ch * QK_CHUNK + 16 * 128, &M.x43, bar, ch * 64, x0, 0);
            }
#pragma unroll
            for (int ch = 0; ch < 3; ch++) {
                tma_3d_x(dst + ch * QK_CHUNK + 28 * 128, &M.x34, bar2, ch * 64, x1, y0);
                tma_3d_x(dst + ch * QK_CHUNK + 40 * 128, &M.x33, bar2, ch * 64, x1, 0);
            }
        }
    };
    const int t0 = min(warp * 16 + g, TOK - 1), t1 = min(warp * 16 + g + 8, TOK - 1);
    int ridx[26];
    uint32_t rc, w2[16];
    uint4 w1[4];
    if (attn && (wg == 1 || wg == 2)) {
        rc = reinterpret_cast<const uint32_t*>(P.rel_coords)[min(tid - 128, 168)];
#pragma unroll
        for (int i = 0; i < 4; i++) w1[i] = reinterpret_cast<const uint4*>(P.cpb_w1)[i];
#pragma unroll
        for (int u = 0; u < 16; u++) w2[u] = reinterpret_cast<const uint32_t*>(P.cpb_w2)[2 * u + half];
#pragma unroll
        for (int rh = 0; rh < 2; rh++) {
            const int* ri = P.rel_idx + row_token(rh ? t1 : t0) * TOK;
#pragma unroll
            for (int j = 0; j < 12; j++) ridx[13 * rh + j] = ri[row_token(8 * (j >> 1) + 2 * c + (j & 1))];
            ridx[13 * rh + 12] = ri[48];
        }
    }
    {
        if (wg == 3 && warp == 1 && lane < 15)
            asm volatile("prefetch.tensormap [%0];\n" :: "l"(reinterpret_cast<uint64_t>(&M.x77 + lane)) : "memory");
        if (tid == 384) {
            for (int b = 0; b < 4; b++) {
                mbar_init(bars + B_XFULL + b * 8, 2);
                mbar_init(bars + B_QKRAW + b * 8, 4);
                mbar_init(bars + B_VRAW + b * 8, 4);
                mbar_init(bars + B_VFREE + b * 8, 2);
                mbar_init(bars + B_QKFREE + b * 8, (NB & 1) ? 1 : 4);
                mbar_init(bars + B_ODONE + b * 8, 4);
            }
            mbar_init(bars + B_WFULL, 2);
            mbar_init(bars + B_WRAW, 1);
            mbar_init(bars + B_MFULL, 1);
            mbar_init(bars + B_MCONS, 4);
            sts32(bars + B_PROG, 0);
            for (int b = 0; b < 4; b++) mbar_init(bars + B_STORED + b * 8, 1);
            for (int b = 0; b < 6; b++) {
                mbar_init(sbase + SM_PBAR + b * 8, 1);
                mbar_init(sbase + SM_PBAR + 48 + b * 8, PSTORE ? 1 : 4);
                mbar_init(sbase + SM_PBAR + 104 + b * 8, 4);
            }
            mbar_init(sbase + SM_PBAR + 96, 13);
            asm volatile("fence.mbarrier_init.release.cluster;\n" ::: "memory");
        }
        if (wg == 3) {
            if (attn) *reinterpret_cast<uint4*>(smem + SM_V + warp * V_STRIDE + (lane < 16 ? lane * 16 : V_STRIDE - 64 + (lane & 3) * 16)) = make_uint4(0, 0, 0, 0);
            if (warp == 2) sts32(sbase + SM_FLAG + lane * 4, 0);
            fence_async_smem();
        }
        __syncthreads();
        TR(26, 4 + wg);
        if (attn && tid == 0) {
            asm volatile("mbarrier.expect_tx.relaxed.cta.shared::cta.b64 [%0], %1;\n" :: "r"(bars + B_XFULL + 8), "r"(3 * 21 * 128) : "memory");
            mbar_arrive_expect_tx(bars + B_WRAW, 2 * 192 * W_PITCH);
#pragma unroll
            for (int i = 0; i < 4; i++) {
                const int q = (i + pair) & 3;
                tma_3d(sbase + q * 96 * W_PITCH, &wraw, bars + B_WRAW, 0, 2 * (q >> 1) + half, (q & 1) * 96);
            }
            TR(26, 25);
#pragma unroll 1
            for (int j = 0; j < 2; j++) {
                const int q = pair + j * P.npair, r = q >= NWS;
                mbar_arrive_expect_tx(bars + B_XFULL, j ? 3 * 28 * 128 : 3 * XCH);
                load_x(sbase + SM_QK + j * XCH, bars + B_XFULL, bars + B_XFULL + j * 8, unrot(r), unrot(q - r * NWS));
                TR(26, 26 + j);
            }
        }
        __syncwarp();
        TR(26, 13);
    }

    auto permute_w = [&]() {
        uint4 w[3][4];
        TR(26, 16 + wg);
        mbar_wait(bars + B_WRAW, 0);
        TR(26, 20 + wg);
#pragma unroll
        for (int it = 0; it < 3; it++) {
            const int o = ((tid >> 5) * 3 + it) * 4 + (lane >> 3);
            const uint8_t* src = smem + ((o / 6) * 8 + (lane & 7)) * W_PITCH + (o % 6) * 16;
#pragma unroll
            for (int m = 0; m < 4; m++) w[it][m] = *reinterpret_cast<const uint4*>(src + (m >> 1) * 192 * W_PITCH + (m & 1) * 96);
        }
        asm volatile("bar.sync 2, 384;\n" ::: "memory");
        if (tid == 0) {
            fence_async_smem();
            TR(26, 24);
            mbar_arrive_expect_tx(bars + B_WFULL, W_ATOM);
            tma_2d(sbase + SM_WV, &wmap, bars + B_WFULL, 384 + half * 96, 0);
        }
#pragma unroll
        for (int it = 0; it < 3; it++) {
            const int o = ((tid >> 5) * 3 + it) * 4 + (lane >> 3);
            const uint32_t d = sbase + (o % 6) * 2 * W_ATOM + ((o / 6) * 8 + (lane & 7)) * 32 + ((lane >> 2) & 1) * 16;
            sts128(d, w[it][0].x, w[it][1].x, w[it][2].x, w[it][3].x);
            sts128(d ^ 16, w[it][0].y, w[it][1].y, w[it][2].y, w[it][3].y);
            sts128(d + W_ATOM, w[it][0].z, w[it][1].z, w[it][2].z, w[it][3].z);
            sts128((d ^ 16) + W_ATOM, w[it][0].w, w[it][1].w, w[it][2].w, w[it][3].w);
        }
    };
    static_assert(2 * 192 * W_PITCH <= 13 * W_ATOM, "raw weights");
    const uint32_t nfinish = gridDim.x + 4 * P.npair;
#define PROJ_SCHEDULE                                                                                   \
    int bid = blockIdx.x;                                                                               \
    asm volatile("" : "+r"(bid));                      \
    const bool at = bid < 2 * P.npair;                                                                  \
    const int tile0 = at ? P.t1 + 2 * P.npair - 1 - bid : bid - 2 * P.npair;                                              \
    const int tstep = at ? 2 * P.npair : (int)gridDim.x - 2 * P.npair;                                  \
    const int tend = at ? TILES : P.t1;
    if (wg == 3) {
        asm volatile("setmaxnreg.dec.sync.aligned.u32 %0;\n" :: "n"(REG_H));
        if (attn && warp == 1 && !(XP & 1)) {
            uint32_t fph = 0, cph = 0, mis;
            auto load = [&](int k) {
                const int wi = pair + k * P.npair, wr = wi / NWS;
                const uint32_t off = (uint32_t)(unrot(wr) * NWS + unrot(wi - wr * NWS)) * 4802u;
                mis = off & 15;
                if (elect_one()) {
                    uint32_t bytes = 4816;
                    if (wi == 0) {
                        bytes = 4800;
                        asm volatile("st.shared.u16 [%0], %1;\n" :: "r"(sbase + SM_MASK + 4800),
                                     "h"(reinterpret_cast<const uint16_t*>(P.mask)[NWINDOWS * TOK * TOK - 1]) : "memory");
                    }
                    mbar_arrive_expect_tx(bars + B_MFULL, bytes);
                    asm volatile("cp.async.bulk.shared::cluster.global.mbarrier::complete_tx::bytes.L2::cache_hint [%0], [%1], %2, [%3], %4;\n"
                                 :: "r"(sbase + SM_MASK), "l"(reinterpret_cast<const char*>(P.mask) + (off - mis)),
                                    "r"(bytes), "r"(bars + B_MFULL), "l"(EVICT_FIRST) : "memory");
                }
            };
            auto landed = [&]() {
                mbar_wait(bars + B_MFULL, fph);
                fph ^= 1;
            };
            auto flag = [&](int k, uint32_t f) {
                asm volatile("st.volatile.shared.u8 [%0], %1;\n" :: "r"(sbase + SM_FLAG + k), "r"(f) : "memory");
                TR(18, k);
            };
            if (MWAIT) mbar_wait(bars + B_WRAW, 0);
            load(2 + half);
            uint32_t todo = 3;
            int sp = 0;
#pragma unroll 1
            for (int k = 2 + half; sp < nwin; k += 2) {
                if (k < nwin) {
#pragma unroll 1
                    for (uint32_t n = 0; n < (1u << 22); n++) {
                        int done;
                        asm volatile("ld.volatile.shared.b32 %0, [%1];\n" : "=r"(done) : "r"(bars + B_PROG) : "memory");
                        if (done >= (k + 2 < nwin ? k - MLEAD : k - 3)) break;
                        __nanosleep(PSLEEP);
                    }
                    landed();
                    TR(17, k);
                    uint32_t any;
                    asm volatile("ld.shared.u16 %0, [%1];\n" : "=r"(any)
                                 : "r"(sbase + SM_MASK + mis + ((lane & 8) ? 4800 - 14 : 0) + (lane & 7) * 2) : "memory");
#pragma unroll
                    for (int i = 0; i < 10; i++) {
                        uint32_t v[4];
                        asm volatile("ld.shared.v4.b32 {%0, %1, %2, %3}, [%4];\n" : "=r"(v[0]), "=r"(v[1]), "=r"(v[2]), "=r"(v[3])
                                     : "r"(sbase + SM_MASK + lane * 16 + (i < 9 ? 16 + i * 512 : 4800 - 512)) : "memory");
                        any |= (v[0] | v[1]) | (v[2] | v[3]);
                    }
                    const uint32_t masked = __any_sync(0xffffffffu, any & 0x7FFF7FFFu);
                    asm volatile("st.relaxed.gpu.global.u32 [%0], %1;\n" :: "l"(g_flag + pair * 128 + k), "r"(1 + masked) : "memory");
                    if (masked) todo |= 1u << (k - sp);
                    else flag(k, 1);
                }
                if (k > 2 && k <= nwin) {
                    uint32_t f;
#pragma unroll 1
                    for (uint32_t n = 0; n < (1u << 22); n++) {
                        asm volatile("ld.relaxed.gpu.global.u32 %0, [%1];\n" : "=r"(f) : "l"(g_flag + pair * 128 + k - 1) : "memory");
                        if (__all_sync(0xffffffffu, f)) break;
                        __nanosleep(PSLEEP);
                    }
                    g_flag[pair * 128 + k - 1] = 0;
                    if (f != 1) todo |= 1u << (k - 1 - sp);
                    else flag(k - 1, 1);
                }
#pragma unroll 1
                for (; sp < k; sp++, todo >>= 1)
                    if (todo & 1) {
                        load(sp);
                        landed();
                        __threadfence_block();
                        flag(sp, 2);
                        mbar_wait(bars + B_MCONS, cph);
                        cph ^= 1;
                        fence_async_smem();
                    }
                if (k + 2 < nwin) load(k + 2);
            }
        }
        if (!elect_one()) return;
        if (warp == 0) {
          if (attn) {
            const int kmax = (64 * ntiles + 63) / TOK;
            int wr = 0, wq = pair;
            int pr2 = (pair + PF_DIST * P.npair) / NWS, pq2 = pair + PF_DIST * P.npair - pr2 * NWS;
#pragma unroll 1
            for (int k = -4; k + 4 <= kmax; k++) {
                const int row0 = (k + 4) * TOK;
                const uint32_t dst = sbase + SM_QK + (k & 3) * XCH, bar = bars + B_XFULL + ((row0 >> 6) & 3) * 8;
                const bool alone = (row0 & 63) >= 64 - TOK && (row0 & 63) < TOK;
                const int wh = unrot(wr), ww = unrot(wq), ph2 = unrot(pr2), pw2 = unrot(pq2);
                const bool done = k < -2;
                if (k == -2) {
                    mbar_wait(bars + B_WRAW, 0);
                    mbar_arrive_expect_tx(bars + B_WFULL, 5 * W_ATOM);
#pragma unroll
                    for (int a = 1; a < 6; a++)
                        tma_2d(sbase + SM_WV + a * W_ATOM, &wmap, bars + B_WFULL, 384 + half * 96 + a * 16, 0);
                }
                if (NB & 1) {
                    if (k >= 0) nb_sync<160>(NB_QKFREE + (k & 1));
                } else mbar_wait(bars + B_QKFREE + (k & 3) * 8, (k >> 2) & 1);
                if (alone && !done) mbar_arrive(bar);
                if (k + 4 >= nwin) {
                    mbar_arrive(bar);
                    continue;
                }
                TR(20, k + 4);
                if (!done) {
                    uint32_t bar2 = bar;
                    if ((row0 & 63) >= 64 - 28) {
                        bar2 = bars + B_XFULL + (((row0 >> 6) + 1) & 3) * 8;
                        asm volatile("mbarrier.expect_tx.relaxed.cta.shared::cta.b64 [%0], %1;\n" :: "r"(bar2), "r"(3 * 21 * 128) : "memory");
                    }
                    mbar_arrive_expect_tx(bar, bar2 != bar ? 3 * 28 * 128 : 3 * XCH);
                    load_x(dst, bar, bar2, wh, ww);
                }
                asm volatile("st.volatile.shared.b32 [%0], %1;\n" :: "r"(bars + B_PROG), "r"(max(k + 1, 0)) : "memory");
                if (NOPF) {
                } else if (PFM == 2) {
                    if (pr2 < NWS && half == 0) {
                        const char* xp = reinterpret_cast<const char*>(P.x) + (size_t)((7 * ph2 + 3) * IMG + 7 * pw2 + 3) * 384;
#pragma unroll 1
                        for (int r = 0; r < (ph2 == NWS - 1 ? 3 : 7); r++)
                            asm volatile("cp.async.bulk.prefetch.L2.global [%0], 2688;\n" :: "l"(xp + r * (IMG * 384)) : "memory");
                    }
                } else if (PFM == 1 ? ((k ^ half) & 1) : PFM == 4 ? half == 1 : PFM == 5 ? 1 : half == 0) {
                    if (pr2 < NWS) {
#pragma unroll
                        for (int ch = 0; ch < 3; ch++)
                            if (CH & 8)
                            asm volatile("cp.async.bulk.prefetch.tensor.3d.L2.global.tile.L2::cache_hint [%0, {%1, %2, %3}], %4;\n"
                                         :: "l"(reinterpret_cast<uint64_t>(&xmap)), "r"(ch * 64), "r"(7 * pw2 + 3), "r"(7 * ph2 + 3), "l"(EVICT_FIRST)
                                         : "memory");
                            else
                            asm volatile("cp.async.bulk.prefetch.tensor.3d.L2.global.tile [%0, {%1, %2, %3}];\n"
                                         :: "l"(reinterpret_cast<uint64_t>(&xmap)), "r"(ch * 64), "r"(7 * pw2 + 3), "r"(7 * ph2 + 3)
                                         : "memory");
                    }
                }
                wq += P.npair; if (wq >= NWS) { wq -= NWS; wr++; }
                pq2 += P.npair; if (pq2 >= NWS) { pq2 -= NWS; pr2++; }
            }
            mbar_wait(bars + B_VRAW + ((ntiles - 1) & 3) * 8, ((ntiles - 1) >> 2) & 1);
          }
            PROJ_SCHEDULE
            int st = 0, ready = -1;
            uint32_t ph = 1;
#pragma unroll 1
            for (int t = tile0; t < tend; t += tstep) {
                const int p0 = (t < TILES_A) ? SEG_B + 64 * t : 64 * (t - TILES_A);
                const int w1 = (t < TILES_A) ? 0 : min((p0 + 63 + 4 * IMG) / (7 * IMG), NWS - 1);
                if (at && t == tile0 + tstep) {
                    mbar_wait(sbase + SM_PBAR + 96, 0);
                    fence_async_smem();
                }
                if (ready < w1) {
                    ready = max(ready, w1 - 2);
#pragma unroll 1
                    while (ready < w1) {
                        ready++;
#pragma unroll 1
                        for (uint32_t n = 0; n < (1u << 22); n++) {
                            uint32_t a;
                            asm volatile("ld.acquire.gpu.global.u32 %0, [%1];\n" : "=r"(a) : "l"(g_cnt + ready) : "memory");
                            if (a >= P.need) break;
                            __nanosleep(64);
                        }
                    }
                    asm volatile("fence.proxy.async.global;\n" ::: "memory");
                }
                TRH(9, (t - tile0) / tstep);
                mbar_wait(sbase + SM_PBAR + 48 + st * 8, ph);
                TRH(5, (t - tile0) / tstep);
                if (PEXP & 2) mbar_arrive(sbase + SM_PBAR + st * 8); else {
                mbar_arrive_expect_tx(sbase + SM_PBAR + st * 8, STAGE_BYTES);
#pragma unroll
                for (int ch = 0; ch < 3; ch++)
                    tma_2d(sbase + SM_STAGE + st * STAGE_BYTES + ch * 8192, &omap, sbase + SM_PBAR + st * 8, ch * 64, (PEXP & 4) ? p0 & 8191 : p0);
                }
                if (++st == 6) { st = 0; ph ^= 1; }
            }
            finish(nfinish);
        } else if (!attn) {
        } else if (warp == 1) {
          {
            if (P.t1 < TILES) {
#pragma unroll 1
                for (uint32_t n = 0; n < (1u << 22); n++) {
                    uint32_t a;
                    asm volatile("ld.acquire.gpu.global.u32 %0, [%1];\n" : "=r"(a) : "l"(g_cnt + NWS) : "memory");
                    if (a) break;
                    __nanosleep(64);
                }
                asm volatile("fence.proxy.async.global;\n" ::: "memory");
                if (blockIdx.x % 6 == 0)
                    asm volatile("cp.async.bulk.prefetch.L2.global [%0], 4096;\n" :: "l"(g_wo + blockIdx.x / 6 % 18 * 4096) : "memory");
                if (NB & 4) mbar_wait(bars + B_QKRAW, 0);
                else mbar_wait(bars + B_QKRAW + ((ntiles - 1) & 3) * 8, ((ntiles - 1) >> 2) & 1);
                mbar_arrive_expect_tx(bars + B_WRAW, 73728);
#pragma unroll
                for (int i = 0; i < 4; i++) {
                    const uint32_t o = ((i + pair) & 3) * 18432;
                    asm volatile("cp.async.bulk.shared::cluster.global.mbarrier::complete_tx::bytes [%0], [%1], 18432, [%2];\n"
                                 :: "r"(sbase + SM_WO + o), "l"(g_wo + o), "r"(bars + B_WRAW) : "memory");
                }
            }
            finish(nfinish);
          }
        } else if (warp == 2) {
            int wh = 0, ww = pair;
#pragma unroll 1
            for (int k = 0; k < nwin; k++) {
                mbar_wait(bars + B_STORED + (k & 1) * 8, (k >> 1) & 1);
                mbar_arrive(bars + B_PUBD + (k & 1) * 8);
                asm volatile("red.release.gpu.global.add.u32 [%0], 1;\n" :: "l"(g_cnt + wh) : "memory");
                TR(24, k);
                TS(k & 127);
                if (k == nwin - 1) TC(7);
                ww += P.npair; if (ww >= NWS) { ww -= NWS; wh++; }
            }
            finish(nfinish);
        } else {
            for (int t = 0; t < 2; t++) mbar_arrive_n(bars + B_VFREE + t * 8, 2);
            int wr = 0, wq = pair;
#pragma unroll 1
            for (int k = 0; k < nwin; k++) {
                const uint32_t src = sbase + SM_V + (k & 3) * V_STRIDE;
                const int wh = unrot(wr), ww = unrot(wq);
                const int x0 = 7 * ww + 3, y0 = 7 * wh + 3;
                if (NB & 2) nb_sync<160>(NB_ODONE + (k & 3));
                else mbar_wait(bars + B_ODONE + (k & 3) * 8, (k >> 2) & 1);
                fence_async_smem();
                TR(22, k);
                const int x1 = ww == NWS - 1 ? 0 : x0 + 4;
                if (!(XP & 2)) tma_store_4d(&M.s47, src, 0, half, x0, y0);
                if (!(XP & 2)) tma_store_4d(&M.s37, src + 28 * O_PITCH, 0, half, x1, y0);
                if (wh == NWS - 1) {
                    tma_store_4d(&M.s43, src + 16 * O_PITCH, 0, half, x0, 0);
                    tma_store_4d(&M.s33, src + 40 * O_PITCH, 0, half, x1, 0);
                }
                asm volatile("cp.async.bulk.commit_group;\n" ::: "memory");
                asm volatile("cp.async.bulk.wait_group.read 0;\n" ::: "memory");
                {
                    const int row0 = (k + 4) * TOK;
                    mbar_arrive_n(bars + B_VFREE + ((row0 >> 6) & 3) * 8, ((row0 & 63) >= 64 - TOK && (row0 & 63) < TOK) ? 2 : 1);
                }
                TR(23, k);
                if (k == nwin - 1) mbar_arrive(sbase + SM_PBAR + 96);
                asm volatile("cp.async.bulk.wait_group 0;\n" ::: "memory");
                asm volatile("fence.proxy.async.global;\n" ::: "memory");
                mbar_wait(bars + B_PUBD + (k & 1) * 8, ((k >> 1) + 1) & 1);
                mbar_arrive(bars + B_STORED + (k & 1) * 8);
                wq += P.npair; if (wq >= NWS) { wq -= NWS; wr++; }
            }
        }
        if (PSTORE && warp == 1) {
            PROJ_SCHEDULE
            int st = 0, prev = -1;
            uint32_t ph = 0;
#pragma unroll 1
            for (int t = tile0; t < tend; t += tstep) {
                const int p0 = (t < TILES_A) ? SEG_B + 64 * t : 64 * (t - TILES_A);
                mbar_wait(sbase + SM_PBAR + 104 + st * 8, ph);
                fence_async_smem();
#pragma unroll
                for (int ch = 0; ch < ((PEXP & 1) ? 0 : 3); ch++)
                    if (CH & 1)
                    asm volatile("cp.async.bulk.tensor.2d.global.shared::cta.tile.bulk_group.L2::cache_hint [%0, {%2, %3}], [%1], %4;\n"
                                 :: "l"(reinterpret_cast<uint64_t>(t < TILES_A ? &omap : &omapb)),
                                    "r"(sbase + SM_STAGE + st * STAGE_BYTES + ch * 8192), "r"(ch * 64), "r"(p0), "l"(EVICT_FIRST) : "memory");
                    else
                    asm volatile("cp.async.bulk.tensor.2d.global.shared::cta.tile.bulk_group [%0, {%2, %3}], [%1];\n"
                                 :: "l"(reinterpret_cast<uint64_t>(t < TILES_A ? &omap : &omapb)),
                                    "r"(sbase + SM_STAGE + st * STAGE_BYTES + ch * 8192), "r"(ch * 64), "r"((PEXP & 8) ? (p0 & 8191) + 16384 : p0) : "memory");
                asm volatile("cp.async.bulk.commit_group;\n" ::: "memory");
                TRH(6, (t - tile0) / tstep);
                if (prev >= 0) {
                    asm volatile("cp.async.bulk.wait_group.read 1;\n" ::: "memory");
                    mbar_arrive(sbase + SM_PBAR + 48 + prev * 8);
                    TRH(21, (t - tile0) / tstep - 1);
                }
                prev = st;
                if (++st == 6) { st = 0; ph ^= 1; }
            }
            asm volatile("cp.async.bulk.wait_group 0;\n" ::: "memory");
            TR(30, 0);
            TC(1);
        }
        return;
    }
    if (!attn) {
        asm volatile("setmaxnreg.inc.sync.aligned.u32 160;\n");
    } else if (wg == 0) {
        asm volatile("setmaxnreg.inc.sync.aligned.u32 %0;\n" :: "n"(REG_G));
        float qs = 1.f;
        if (c < 2) qs = round_bf16(expf(round_bf16(fminf(fmaxf(__bfloat162float(P.logit_scale[2 * half + c]), -100.f), 4.6052f)))) * LOG2E;
        uint32_t xa[12][4];
        float accA[48], accB[48], accV[48];
        uint32_t rho = warp * 16 + (lane & 15), rq = warp * 16 + g;
        uint32_t hi = lane >> 4, lane0 = lane == 0, c2 = 2 * c;
        asm volatile("" : "+r"(hi), "+r"(lane0), "+r"(c2));
        auto row_addr = [&](uint32_t (&ax)[4], uint32_t r) {
            ax[0] = sbase + SM_QK + r * 128 + (((r & 7) ^ hi) << 4);
#pragma unroll
            for (int i = 1; i < 4; i++) ax[i] = ax[0] ^ (32 * i);
        };
#define XADDR(ax, s) ((ax)[((s) & 3) ^ (((s) >> 1) & 2)] + ((s) >> 2) * QK_CHUNK)
        uint64_t descW = make_desc(sbase, W_ATOM, 256, 3);
        const uint32_t zero = (uint32_t)P.z1;
        const uint32_t vbase = sbase + SM_V + (lane >> 4) * GRP;
        const uint32_t ones = 0x3F803F80u, ones2 = ones;
        permute_w();
        TR(26, 10);
        {
            uint32_t ax[4];
            row_addr(ax, rho);
            mbar_wait(bars + B_XFULL, 0);
#pragma unroll
            for (int s = 0; s < 12; s++) ldsm_x4(xa[s], XADDR(ax, s));
        }
        TR(26, 8);
        asm volatile("bar.sync 7, 384;\n" ::: "memory");
        fence_async_smem();
        TR(26, 9);
        wgmma_fence();
        mma_qkv_a<SM_WA, 0>(accA, xa, descW);
        mma_qkv_b<SM_WA, KLO>(accA, xa, descW);
        wgmma_commit();
        mma_qkv_a<SM_WB, 0>(accB, xa, descW);
        wgmma_commit();
        TR(26, 11);
        mbar_wait(bars + B_WFULL, 0);
        TR(26, 12);
        if (tid == 0) TC(3);
        const int nt = (int)blockIdx.x < P.nr2 ? P.nt1 : P.nt0;
        for (int t = 0; t < nt; t++) {
            descW += P.z1;
            float ss[4];
            uint32_t pk[2][24];
            wgmma_wait<1>();
            reg_fence(accA);
            TR(0, t);
#pragma unroll
            for (int i = 0; i < 4; i++) ss[i] = accA[i] * accA[i];
#pragma unroll
            for (int i = 4; i < 48; i++) ss[i & 3] = fmaf(accA[i], accA[i], ss[i & 3]);
            mma_qkv_b<SM_WB, KLO>(accB, xa, descW);
            wgmma_commit();
            sched_fence(zero, __float_as_uint(ss[0]), __float_as_uint(ss[1]), __float_as_uint(ss[2]), __float_as_uint(ss[3]));
#pragma unroll
            for (int j = 0; j < 12; j++) {
                pk[0][j] = pack_bf16(accA[4 * j], accA[4 * j + 1]);
                pk[1][j] = pack_bf16(accA[4 * j + 2], accA[4 * j + 3]);
                asm volatile("" : "+r"(pk[0][j]), "+r"(pk[1][j]));
            }
            wgmma_fence();
            mma_qkv_a<SM_WV, 0>(accV, xa, descW);
            wgmma_commit();
            uint32_t av = vbase + rho * 16 + ((rho * 1338) >> 16) * (V_STRIDE - GRP);
            uint32_t aq[2];
            aq[0] = sbase + SM_QK + rq * 128 + (((rq & 7) ^ c2) << 4);
            aq[1] = aq[0] + 1024;
            if (rq >= 4 * TOK - 8) aq[1] = (aq[1] - QK_CHUNK) ^ 64;
            rho += 64;
            if (rho >= 4 * TOK) rho -= 4 * TOK;
            rq += 64;
            if (rq >= 4 * TOK) rq -= 4 * TOK;
            uint32_t an[4];
            row_addr(an, rho);
            const uint32_t bt = bars + (t & 3) * 8, pt = (t >> 2) & 1, bn = bars + ((t + 1) & 3) * 8, pn = ((t + 1) >> 2) & 1;
            const uint32_t xok = mbar_test(bn + B_XFULL, pn) & mbar_test(bt + B_VFREE, pt);
            wgmma_wait<1>();
            reg_fence(accB);
#pragma unroll
            for (int i = 0; i < 48; i++) ss[i & 3] = fmaf(accB[i], accB[i], ss[i & 3]);
            ss[0] += ss[1]; ss[2] += ss[3];
            mma_qkv_b<SM_WV, KLO>(accV, xa, descW);
            wgmma_commit();
            sched_fence(zero, __float_as_uint(ss[0]), __float_as_uint(ss[2]), av, aq[0], aq[1], an[0], an[1], an[2], an[3], rho, rq);
            const float f0 = rsqrt_ftz(ss[0] + 1e-12f) * qs, f1 = rsqrt_ftz(ss[2] + 1e-12f) * qs;
            const uint32_t f2[2] = {pack_bf16(f0, f0), pack_bf16(f1, f1)};
#pragma unroll
            for (int j = 0; j < 12; j++) {
                pk[0][12 + j] = pack_bf16(accB[4 * j], accB[4 * j + 1]);
                pk[1][12 + j] = pack_bf16(accB[4 * j + 2], accB[4 * j + 3]);
            }
            auto qk_store = [&](int u0, int u1) {
#pragma unroll
                for (int u = u0; u < u1; u++)
#pragma unroll
                    for (int r = 0; r < 2; r++)
                        sts128((aq[r] ^ ((u & 1) * 16 + (u & 2) * 32)) + (u >> 1) * QK_CHUNK,
                               hmul2_bf16(pk[r][4 * u], f2[r]), hmul2_bf16(pk[r][4 * u + 1], f2[r]),
                               hmul2_bf16(pk[r][4 * u + 2], f2[r]), hmul2_bf16(pk[r][4 * u + 3], f2[r]));
            };
            qk_store(0, QSPLIT);
            TR(1, t);
            mbar_wait2_unless(xok, bn + B_XFULL, pn, bt + B_VFREE, pt);
            TR(2, t);
            wgmma_wait<1>();
#pragma unroll
            for (int s = 0; s < KLO; s++) ldsm_x4(xa[s], XADDR(an, s));
            qk_store(QSPLIT, 6);
            if (NB & 4) {
                const int kc = (t * 21400) >> 14, two = ((t + 1) * 21400) >> 14;
                nb_arrive<256>(NB_QKRAW + (kc & 3));
                asm volatile("{\n.reg .pred p;\nsetp.eq.u32 p, %1, 2;\n@p bar.arrive %0, 256;\n}\n" :: "r"(NB_QKRAW + ((kc + 1) & 3)), "r"(two - kc) : "memory");
                mbar_arrive_if(bars + B_QKRAW, t == nt - 1 ? lane0 : 0);
            } else {
                __syncwarp();
                mbar_arrive_if(bt + B_QKRAW, lane0);
            }
            TR(3, t);
            wgmma_fence();
            mma_qkv_a<SM_WA, 0>(accA, xa, descW);
            wgmma_commit();
            wgmma_wait<1>();
            reg_fence(accV);
#pragma unroll
            for (int s = KLO; s < 12; s++) ldsm_x4(xa[s], XADDR(an, s));
            uint32_t vp[24];
#pragma unroll
            for (int j = 0; j < 24; j++) vp[j] = pack_bf16(accV[2 * j], accV[2 * j + 1]);
            reg_fence(vp);
            wgmma_fence();
            mma_qkv_b<SM_WA, KLO>(accA, xa, descW);
            wgmma_commit();
#pragma unroll
            for (int p = 0; p < 6; p++)
                stsm_x4(av + (p < 3 ? 2 * p : 2 * p + 1) * GRP, vp[4 * p], vp[4 * p + 1], vp[4 * p + 2], vp[4 * p + 3]);
            stsm_x2(av + 6 * GRP, ones, ones2);
            __syncwarp();
            mbar_arrive_if(bt + B_VRAW, lane0);
            TR(4, t);
            if (!MERGEW) wgmma_fence();
            mma_qkv_a<SM_WB, 0>(accB, xa, descW);
            wgmma_commit();
        }
        wgmma_wait<0>();
        reg_fence(accA);
        reg_fence(accB);
        asm volatile("setmaxnreg.dec.sync.aligned.u32 160;\n");
    } else {
        if (REG_A > 128) asm volatile("setmaxnreg.inc.sync.aligned.u32 %0;\n" :: "n"(REG_A));
        {
            const float c0 = bf16lo(rc), c1 = bf16hi(rc);
            float a0 = 0.f, a1 = 0.f;
#pragma unroll
            for (int u = 0; u < 16; u++) {
                const uint32_t p = reinterpret_cast<const uint32_t*>(w1)[u >> 1], q = reinterpret_cast<const uint32_t*>(w1)[8 + (u >> 1)];
                float h = round_bf16(c0 * ((u & 1) ? bf16hi(p) : bf16lo(p)) + c1 * ((u & 1) ? bf16hi(q) : bf16lo(q)));
                h = fmaxf(h, 0.f);
                a0 += h * bf16lo(w2[u]);
                a1 += h * bf16hi(w2[u]);
            }
            const float s0 = round_bf16(__fdividef(1.f, 1.f + expf(-round_bf16(a0))));
            const float s1 = round_bf16(__fdividef(1.f, 1.f + expf(-round_bf16(a1))));
            if (tid - 128 < 169) sts32(sbase + SM_TAB + (tid - 128) * 4, pack_bf16(exp2f(fmaf(s0, 16.f * LOG2E, -12.f)), exp2f(fmaf(s1, 16.f * LOG2E, -12.f))));
        }
        permute_w();
        asm volatile("bar.arrive 7, 384;\n" ::: "memory");
        asm volatile("bar.sync 1, 256;\n" ::: "memory");
        uint32_t eb[26];
        {
            const uint32_t* tab = reinterpret_cast<const uint32_t*>(smem + SM_TAB);
#pragma unroll
            for (int i = 0; i < 13; i++) {
                const uint32_t lo = tab[min(max(ridx[i < 12 ? 13 * (i & 1) + (i & ~1) : 12], 0), 168)];
                const uint32_t hi = tab[min(max(ridx[i < 12 ? 13 * (i & 1) + (i | 1) : 25], 0), 168)];
                eb[i]      = prmt(lo, hi, 0x5410);
                eb[13 + i] = prmt(lo, hi, 0x7632);
            }
            if (c != 0) eb[12] = eb[25] = 0;
        }
        uint32_t slow = 0;
#pragma unroll
        for (int h = 0; h < 2; h++)
            if (!(expf(__bfloat162float(P.logit_scale[2 * half + h])) <= TAU_FAST)) slow = 1;
        reg_fence(eb);
        wg_bar(3 + wg);
        if ((tid & 127) == 0) mbar_arrive(bars + B_VFREE + 16);
        const uint32_t ov0 = warp * 16 + g < TOK, ov1 = warp < 3;
        const uint64_t descK0 = make_desc(sbase + SM_QK, 16, 1024, 1);
        const uint64_t descV0 = make_desc(sbase + SM_V, 128, GRP, 0);
        slow = __shfl_sync(0xffffffffu, slow, 0);
        const uint32_t barw = bars + (wg - 1) * 8;
        const uint64_t descKw = descK0 + (uint64_t)((wg - 1) * (XCH >> 4)), descVw = descV0 + (uint64_t)((wg - 1) * (V_STRIDE >> 4));
        const uint32_t oa = sbase + SM_V + (wg - 1) * V_STRIDE + (warp * 16 + g) * O_PITCH + c * 48;
        uint32_t qok = 0;
        const uint32_t zero = (uint32_t)P.z1;
        auto window = [&](auto IT_, int k) {
            constexpr int IT = decltype(IT_)::value;
            const uint32_t bar = barw + 16 * IT;
            const int tl = (k * TOK + TOK - 1) >> 6, tn = ((k + 2) * TOK + TOK - 1) >> 6;
            const uint32_t bt = bars + (tl & 3) * 8, pt = (tl >> 2) & 1;
            TR(8, k);
            float sc0[28], sc1[28];
            TR(10, k);
            if (NB & 4) nb_sync<256>(NB_QKRAW + 2 * IT - 1 + wg);
            else mbar_wait_unless(qok, bt + B_QKRAW, pt);
            fence_async_smem();
            TR(11, k);
            wgmma_fence();
            mma_qk0<2 * IT * XCH, 2 * IT * XCH>(sc0, descKw, descKw);
            mma_qk1<2 * IT * XCH, 2 * IT * XCH>(sc1, descKw, descKw);
            wgmma_commit();
            const uint32_t vok = mbar_test(bt + B_VRAW, pt);
            uint32_t mflag = 1;
            if (!(XP & 1)) asm volatile("ld.volatile.shared.u8 %0, [%1];\n" : "=r"(mflag) : "r"(sbase + SM_FLAG + k) : "memory");
            wgmma_wait<0>();
            reg_fence(sc0);
            reg_fence(sc1);
            if (NB & 1) nb_arrive<160>(NB_QKFREE - 1 + wg);
            else if (lane == 0) mbar_arrive(bar + B_QKFREE);
            TR(12, k);
            if (mflag != 1) {
              asm volatile(
                "{\n.reg .pred p;\n.reg .u32 n;\nmov.u32 n, 0;\n"
                "WAIT_%=:\n"
                "ld.volatile.shared.u8 %0, [%1];\n"
                "setp.ne.u32 p, %0, 0;\n"
                "@p bra DONE_%=;\n"
                "add.u32 n, n, 1;\n"
                "setp.lt.u32 p, n, 16777216;\n"
                "@p bra WAIT_%=;\n"
                "trap;\n"
                "DONE_%=:\n}\n" : "=r"(mflag) : "r"(sbase + SM_FLAG + k) : "memory");
              if (mflag == 2) {
                uint32_t mk[13];
                __threadfence_block();
                uint32_t u = threadIdx.x, bid = blockIdx.x;
                asm volatile("" : "+r"(u), "+r"(bid));
                const uint32_t r0 = ((u >> 1) & 48) + ((u >> 2) & 7);
                const int wi = (bid >> 1) + k * P.npair, wr = wi / NWS;
                const uint32_t mp = sbase + SM_MASK + (((unrot(wr) * NWS + unrot(wi - wr * NWS)) * 2) & 15);
                const uint32_t mr[2] = {mp + row_token(min(r0, TOK - 1u)) * (2 * TOK), mp + row_token(min(r0 + 8, TOK - 1u)) * (2 * TOK)};
                const uint32_t c0 = 2 * row_token(2 * (u & 3));
#pragma unroll
                for (int i = 0; i < 13; i++) {
                    const uint32_t a0 = i < 6 ? mr[i & 1] + c0 + 28 * (i >> 1) : i < 12 ? mr[i & 1] + 2 * row_token(2 * (u & 3) + 8 * (i >> 1)) : mr[0] + 2 * TOK - 2;
                    const uint32_t a1 = i < 6 ? a0 + 2 : i < 12 ? mr[i & 1] + 2 * row_token(2 * (u & 3) + 8 * (i >> 1) + 1) : mr[1] + 2 * TOK - 2;
                    uint32_t lo, hi;
                    asm volatile("ld.shared.u16 %0, [%1];\n" : "=r"(lo) : "r"(a0) : "memory");
                    asm volatile("ld.shared.u16 %0, [%1];\n" : "=r"(hi) : "r"(a1) : "memory");
                    mk[i] = prmt(lo, hi, 0x5410);
                }
                reg_fence(mk);
                __syncwarp();
                if (lane == 0) mbar_arrive(bars + B_MCONS);
                uint32_t m0 = mk[0], m1 = mk[1];
#pragma unroll
                for (int i = 2; i < 12; i += 2) { m0 = hmax2_bf16(m0, mk[i]); m1 = hmax2_bf16(m1, mk[i + 1]); }
                m0 = hmax2_bf16(hmax2_bf16(prmt(m0, m1, 0x5410), prmt(m0, m1, 0x7632)), mk[12]);
                m0 = hmax2_bf16(m0, __shfl_xor_sync(0xffffffffu, m0, 1));
                m0 = hmax2_bf16(m0, __shfl_xor_sync(0xffffffffu, m0, 2));
                const float m[2] = {bf16lo(m0), bf16hi(m0)};
#pragma unroll
                for (int i = 0; i < 13; i++) {
                    const float lo = bf16lo(mk[i]) - m[i & 1], hi = bf16hi(mk[i]) - m[i < 12 ? i & 1 : 1];
                    const int j = i < 12 ? 2 * i + 1 : 26;
                    sc0[2 * i] = fmaf(lo, LOG2E, sc0[2 * i]); sc0[j] = fmaf(hi, LOG2E, sc0[j]);
                    sc1[2 * i] = fmaf(lo, LOG2E, sc1[2 * i]); sc1[j] = fmaf(hi, LOG2E, sc1[j]);
                }
              }
            }
            if (slow) {
                auto shift = [&](float (&S)[28], int h) {
                    float m[2];
#pragma unroll
                    for (int i = 12; i >= 0; i--) {
                        uint32_t e = eb[13 * h + i];
                        asm volatile("" : "+r"(e));
                        const float a = S[2 * i] + lg2_ftz(bf16lo(e)), b = S[i < 12 ? 2 * i + 1 : 26] + lg2_ftz(bf16hi(e));
                        if (i == 12) { m[0] = a; m[1] = b; }
                        else m[i & 1] = fmaxf(m[i & 1], fmaxf(a, b));
                    }
#pragma unroll
                    for (int r = 0; r < 2; r++) {
                        m[r] = fmaxf(m[r], __shfl_xor_sync(0xffffffffu, m[r], 1));
                        m[r] = fmaxf(m[r], __shfl_xor_sync(0xffffffffu, m[r], 2));
                    }
#pragma unroll
                    for (int i = 0; i < 27; i++) S[i] -= m[(i >> 1) & 1];
                };
                shift(sc0, 0);
                shift(sc1, 1);
            }
            auto exps = [&](const float (&S)[28], uint32_t (&e)[13]) {
#pragma unroll
                for (int i = 0; i < 12; i++) e[i] = pack_bf16(ex2_ftz(S[2 * i]), ex2_ftz(S[2 * i + 1]));
                e[12] = hmin2_bf16(pack_bf16(ex2_ftz(S[24]), ex2_ftz(S[26])), 0x7F7F7F7Fu);
            };
            auto probs = [&](const uint32_t (&e)[13], int h, uint32_t (&pa)[4][4]) {
#pragma unroll
                for (int i = 0; i < 12; i++) pa[i >> 2][i & 3] = hmul2_bf16(e[i], eb[13 * h + i]);
                const uint32_t l = hmul2_bf16(e[12], eb[13 * h + 12]);
                pa[3][0] = l & 0xFFFFu;
                pa[3][1] = l >> 16;
                pa[3][2] = 0u; pa[3][3] = 0u;
                reg_fence(pa);
            };
            uint32_t pa0[4][4], pa1[4][4], e[13];
            float o0[28], o1[28];
            TR(13, k);
            exps(sc0, e);
            probs(e, 0, pa0);
            mbar_wait_unless(vok, bt + B_VRAW, pt);
            fence_async_smem();
            TR(14, k);
            wgmma_fence();
            mma_pv<2 * IT * V_STRIDE, 0>(o0, pa0, descVw);
            wgmma_commit();
            exps(sc1, e);
            reg_fence(e);
            wgmma_wait<0>();
            reg_fence(o0);
            sched_fence_rw(zero, e);
            probs(e, 1, pa1);
            wgmma_fence();
            mma_pv<2 * IT * V_STRIDE + 6 * GRP, 0>(o1, pa1, descVw);
            wgmma_commit();
            uint32_t w[24];
            {
                const float il0 = rcp_ftz(o0[24]), il1 = rcp_ftz(o0[26]);
                const uint32_t l0 = pack_bf16(il0, il0), l1 = pack_bf16(il1, il1);
#pragma unroll
                for (int j = 0; j < 12; j++) w[j] = hmul2_bf16(pack_bf16(o0[2 * j], o0[2 * j + 1]), (j & 1) ? l1 : l0);
            }
            wgmma_wait<0>();
            reg_fence(o1);
            TR(15, k);
            wg_bar(3 + wg);
            if (!(NB & 4)) qok = mbar_test(bars + (tn & 3) * 8 + B_QKRAW, (tn >> 2) & 1);
            {
                const float il2 = rcp_ftz(o1[0]), il3 = rcp_ftz(o1[2]);
                const uint32_t l2 = pack_bf16(il2, il2), l3 = pack_bf16(il3, il3);
#pragma unroll
                for (int j = 0; j < 12; j++) w[12 + j] = hmul2_bf16(pack_bf16(o1[2 * j + 4], o1[2 * j + 5]), (j & 1) ? l3 : l2);
#pragma unroll
                for (int p = 0; p < 6; p++) {
                    const int j = 8 * (p >> 1) + (p & 1);
                    sts128_if((p & 1) ? ov1 : ov0, oa + 2 * IT * V_STRIDE + (p & 1) * 8 * O_PITCH + (p >> 1) * 16, w[j], w[j + 2], w[j + 4], w[j + 6]);
                }
            }
            if (NB & 2) nb_arrive<160>(NB_ODONE + 2 * IT - 1 + wg);
            else {
                __syncwarp();
                if (lane == 0) mbar_arrive(bar + B_ODONE);
            }
            TR(16, k);
        };
        for (int k = wg - 1;; k += 4) {
            window(std::integral_constant<int, 0>(), k);
            if (k + 2 >= nwin) break;
            window(std::integral_constant<int, 1>(), k + 2);
            if (k + 4 >= nwin) break;
        }
        (void)zero;
        asm volatile("setmaxnreg.inc.sync.aligned.u32 160;\n");
    }

    TR(27, wg);
    if ((tid & 127) == 0) TC(4 + wg);
    if (attn) {
        __syncwarp();
        if (lane == 0) mbar_arrive(sbase + SM_PBAR + 96);
    }
    if (!attn) {
#pragma unroll
        for (int row = tid >> 2; row < 192; row += 96) {
            uint4 w[6];
            const int pr = row % 96, srow = row - pr + (pr % 24) / 12 * 48 + (pr % 12) / 2 * 8 + pr / 24 * 2 + (pr & 1);
#pragma unroll
            for (int a = 0; a < 6; a++) w[a] = *reinterpret_cast<const uint4*>(P.wo + srow * 192 + 32 * a + 8 * c);
            float s = 0.f;
#pragma unroll
            for (int a = 0; a < 6; a++)
                s += ((bf16lo(w[a].x) + bf16hi(w[a].x)) + (bf16lo(w[a].y) + bf16hi(w[a].y))) +
                     ((bf16lo(w[a].z) + bf16hi(w[a].z)) + (bf16lo(w[a].w) + bf16hi(w[a].w)));
            s += __shfl_xor_sync(0xffffffffu, s, 1);
            s += __shfl_xor_sync(0xffffffffu, s, 2);
            s *= (1.f / 192.f);
            const uint32_t d = sbase + SM_WO + row * 64 + ((c ^ ((row >> 1) & 3)) << 4);
#pragma unroll
            for (int a = 0; a < 6; a++)
                sts128(d + a * 12288, pack_bf16(bf16lo(w[a].x) - s, bf16hi(w[a].x) - s), pack_bf16(bf16lo(w[a].y) - s, bf16hi(w[a].y) - s),
                       pack_bf16(bf16lo(w[a].z) - s, bf16hi(w[a].z) - s), pack_bf16(bf16lo(w[a].w) - s, bf16hi(w[a].w) - s));
        }
        fence_async_smem();
        asm volatile("bar.sync 6, 384;\n" ::: "memory");
        if (tid == 0 && (int)blockIdx.x == 2 * P.npair) {
            asm volatile("cp.async.bulk.global.shared::cta.bulk_group [%0], [%1], 73728;\n" :: "l"(g_wo), "r"(sbase + SM_WO) : "memory");
            asm volatile("cp.async.bulk.commit_group;\n" ::: "memory");
            asm volatile("cp.async.bulk.wait_group 0;\n" ::: "memory");
            asm volatile("fence.proxy.async.global;\n" ::: "memory");
            asm volatile("red.release.gpu.global.add.u32 [%0], 1;\n" :: "l"(g_cnt + NWS) : "memory");
        }
        __syncwarp();
    } else if (P.t1 < TILES) {
        mbar_wait(sbase + SM_BAR + B_WRAW, 1);
    }
    TR(27, 4 + wg);
    if (tid == 0) TC(2);
    {
        PROJ_SCHEDULE
        uint64_t descW = make_desc(sbase + SM_WO, 12288, 512, 2);
        const uint64_t descA = make_desc(sbase + SM_STAGE + wg * STAGE_BYTES, 16, 1024, 1);
        const uint32_t bar = sbase + SM_PBAR + wg * 8;
        const uint32_t yrel = sbase + SM_STAGE + wg * STAGE_BYTES + (warp * 16 + (lane & 15)) * 128 + (((lane & 7) ^ (lane >> 4)) << 4);
        float acc[96];
#pragma unroll
        for (int i = 0; i < 96; i++) acc[i] = 0.f;
        uint32_t it = 0;
        for (int tile = tile0 + wg * tstep; tile < tend; tile += 3 * tstep, it++) {
            descW += P.z1;
            mbar_wait(bar + (it & 1) * 24, (it >> 1) & 1);
            TR(28, it * 3 + wg);
            if (it > 0 || wg > 0) asm volatile("bar.sync %0, 256;\n" :: "r"(8 + wg) : "memory");
            wgmma_fence();
            mma_proj<0, 0>(acc, descA + (uint64_t)((it & 1) * (3 * STAGE_BYTES >> 4)), descW);
            wgmma_commit();
            if (tile + tstep < tend) asm volatile("bar.arrive %0, 256;\n" :: "r"(wg == 2 ? 8 : 9 + wg) : "memory");
            wgmma_wait<0>();
            reg_fence(acc);
            float a[4];
#pragma unroll
            for (int i = 0; i < 4; i++) a[i] = acc[i] * acc[i];
#pragma unroll
            for (int j = 1; j < 24; j++)
#pragma unroll
                for (int i = 0; i < 4; i++) a[i] = fmaf(acc[4 * j + i], acc[4 * j + i], a[i]);
            float s0 = a[0] + a[1], s1 = a[2] + a[3];
            s0 += __shfl_xor_sync(0xffffffffu, s0, 1);
            s1 += __shfl_xor_sync(0xffffffffu, s1, 1);
            s0 += __shfl_xor_sync(0xffffffffu, s0, 2);
            s1 += __shfl_xor_sync(0xffffffffu, s1, 2);
            const float rs0 = rsqrt_ftz(fmaf(s0, 1.f / 192.f, 1e-5f));
            const float rs1 = rsqrt_ftz(fmaf(s1, 1.f / 192.f, 1e-5f));
            const uint32_t ya = yrel + (it & 1) * 3 * STAGE_BYTES;
#pragma unroll
            for (int p = 0; p < 12; p++)
                stsm_x4((ya ^ (32 * (p & 3))) + (p >> 2) * 8192,
                        pack_bf16(acc[8 * p] * rs0, acc[8 * p + 1] * rs0), pack_bf16(acc[8 * p + 2] * rs1, acc[8 * p + 3] * rs1),
                        pack_bf16(acc[8 * p + 4] * rs0, acc[8 * p + 5] * rs0), pack_bf16(acc[8 * p + 6] * rs1, acc[8 * p + 7] * rs1));
            __syncwarp();
            if (lane == 0) mbar_arrive(bar + 104 + (it & 1) * 24);
            TR(29, it * 3 + wg);
        }
    }
}

}

typedef CUresult (*PFN_encodeTiled)(CUtensorMap*, CUtensorMapDataType, cuuint32_t, void*, const cuuint64_t*,
                                    const cuuint64_t*, const cuuint32_t*, const cuuint32_t*, CUtensorMapInterleave,
                                    CUtensorMapSwizzle, CUtensorMapL2promotion, CUtensorMapFloatOOBfill);

extern "C" void kernel_launch(void* const* d_in, const int* in_sizes, int n_in, void* d_out, int out_size) {
    swin::Params P;
    P.x           = (const __nv_bfloat16*)d_in[0];
    P.wqkv        = (const __nv_bfloat16*)d_in[1];
    P.wo          = (const __nv_bfloat16*)d_in[2];
    P.logit_scale = (const __nv_bfloat16*)d_in[3];
    P.cpb_w1      = (const __nv_bfloat16*)d_in[4];
    P.cpb_w2      = (const __nv_bfloat16*)d_in[5];
    P.rel_coords  = (const __nv_bfloat16*)d_in[6];
    P.rel_idx     = (const int*)d_in[7];
    P.mask        = (const __nv_bfloat16*)d_in[8];
    P.out         = (__nv_bfloat16*)d_out;
    P.z1 = 0;
    static PFN_encodeTiled encode = nullptr;
    if (!encode) {
        cudaFuncSetAttribute(swin::swin_window_attn_kernel, cudaFuncAttributeMaxDynamicSharedMemorySize, swin::SM_TOTAL);
        cudaDriverEntryPointQueryResult qr;
        cudaGetDriverEntryPoint("cuTensorMapEncodeTiled", (void**)&encode, cudaEnableDefault, &qr);
    }
    swin::Maps M;
    const cuuint32_t estr[4] = {1, 1, 1, 1};
    auto make = [&](CUtensorMap* m, const void* base, int rank, const cuuint64_t* gdim, const cuuint64_t* gstr,
                    const cuuint32_t* box, CUtensorMapSwizzle swz = CU_TENSOR_MAP_SWIZZLE_128B) {
        CUresult r = encode(m, CU_TENSOR_MAP_DATA_TYPE_BFLOAT16, rank, const_cast<void*>(base), gdim, gstr, box, estr,
               CU_TENSOR_MAP_INTERLEAVE_NONE, swz, CU_TENSOR_MAP_L2_PROMOTION_L2_128B,
               CU_TENSOR_MAP_FLOAT_OOB_FILL_NONE);
        (void)r;
    };
    {
        const cuuint64_t gdim[3] = {192, swin::IMG, swin::IMG}, gstr[2] = {384, swin::IMG * 384};
        const cuuint32_t box[7][3] = {{64, 7, 7}, {64, 4, 7}, {64, 3, 7}, {64, 4, 4}, {64, 4, 3}, {64, 3, 4}, {64, 3, 3}};
        for (int i = 0; i < 7; i++) make(&M.x77 + i, P.x, 3, gdim, gstr, box[i]);
    }
    {
        const cuuint64_t gdim[2] = {192, (cuuint64_t)swin::NPIX}, gstr[1] = {384};
        const cuuint32_t box64[2] = {64, 64};
        make(&M.o, d_out, 2, gdim, gstr, box64);
        const cuuint64_t gdimb[2] = {192, (cuuint64_t)swin::SEG_B};
        make(&M.ob, d_out, 2, gdimb, gstr, box64);
    }
    {
        const cuuint64_t gdim[2] = {576, 192}, gstr[1] = {1152};
        const cuuint32_t box[2] = {16, 192};
        make(&M.w, P.wqkv, 2, gdim, gstr, box, CU_TENSOR_MAP_SWIZZLE_32B);
        const cuuint64_t gdim3[3] = {96, 6, 192}, gstr3[2] = {192, 1152};
        const cuuint32_t box3[3] = {104, 1, 96};
        make(&M.wraw, P.wqkv, 3, gdim3, gstr3, box3, CU_TENSOR_MAP_SWIZZLE_NONE);
    }
    {
        const cuuint64_t gdim[4] = {96, 2, swin::IMG, swin::IMG}, gstr[3] = {192, 384, swin::IMG * 384};
        const cuuint32_t box[4][4] = {{96, 1, 4, 7}, {96, 1, 3, 7}, {96, 1, 4, 3}, {96, 1, 3, 3}};
        for (int i = 0; i < 4; i++) make(&M.s47 + i, d_out, 4, gdim, gstr, box[i], CU_TENSOR_MAP_SWIZZLE_NONE);
    }
    P.npair = NPAIR; P.need = swin::ROW_DONE; P.nq = swin::NWINDOWS / NPAIR; P.nr = swin::NWINDOWS % NPAIR;
    P.nr2 = 2 * P.nr; P.nt0 = (P.nq * swin::TOK + 63) / 64; P.nt1 = ((P.nq + 1) * swin::TOK + 63) / 64;
    P.t1 = swin::TILES - NTAIL;
    swin::swin_window_attn_kernel<<<132, swin::NTHREADS, swin::SM_TOTAL>>>(P, M);
}
```

```cpp
#include <cuda_runtime.h>
#include <cuda.h>
#include <cuda_bf16.h>
#include <stdint.h>
#include <type_traits>

namespace swin {
#define HINT ""

#define NPAIR 53
#define PF_DIST 3
#define QSPLIT 4
#define CLUSTER 0
#define NOPF 0
#define NTAIL 318
#define PSTORE 1
#define PORDER 1
#define GORD 0
#define GF1 1
#define MERGEW 1
#define MWAIT 0
#define PSLEEP 200
#define CH 5
#define NB 1
#define SCM 0
#define MPF 2
#define MLEAD 4
#define PFM 0
#define PFK 4
#define XP 0
#define KLO 6
#define VPOS 1
#define XSPLIT 1
#define SEQ 1
#define PREL 0
#define PEXP 0
#define PFD 0
#define PFW 0
#define WVK -4
#define WSEQ 1
#define PF1 1
#define WFIRST 1
#define MPRE 1
#define SLOWH 2
#define LS_FAST 4.f
#define REG_G 224
#define REG_A 128
#define REG_H 32
constexpr int IMG      = 511;
constexpr int NWS      = 73;
constexpr int NWINDOWS = NWS * NWS;
constexpr int TOK      = 49;
constexpr int NPIX     = IMG * IMG;
constexpr int NTHREADS = 512;

constexpr int W_ATOM = 6144;
constexpr int SM_WA = 0, SM_WB = 6 * 2048, SM_WV = 12 * W_ATOM, D_WV = SM_WV + ((W_ATOM - 2048) << 16);
constexpr int GRP   = TOK * 16;
constexpr int XCH   = TOK * 128;
constexpr int SM_V  = 18 * W_ATOM, V_STRIDE = 10240, O_PITCH = 192;
constexpr int SM_QK = SM_V + 4 * V_STRIDE, QK_CHUNK = 4 * XCH;
constexpr int SM_MASK = SM_QK + 3 * QK_CHUNK;
constexpr int SM_TAB  = SM_V + 3 * V_STRIDE + 256;
constexpr int SM_BAR  = SM_MASK + 4816;
constexpr int B_XFULL = 0, B_WRAW = 32, B_QKRAW = 64, B_QKFREE = 96, B_VFREE = 128, B_ODONE = 160,
              B_PROG = 192, B_VRAW = 224, B_MFULL = 256, B_MCONS = 272, B_WFULL = 280, B_STORED = 288, B_PUBD = 304;
constexpr int SM_FLAG = SM_BAR + 320;
constexpr int SM_A_END = SM_FLAG + 128;
static_assert(SM_QK % 1024 == 0 && 13 * GRP <= V_STRIDE && V_STRIDE % 128 == 0, "layout");
constexpr int SM_WO    = 0;
constexpr int SM_STAGE = 73728;
constexpr int STAGE_BYTES = 24576;
constexpr int SM_PBAR  = SM_A_END;
constexpr int SM_TOTAL = SM_PBAR + 152;
#define TP(idx)
static_assert(SM_STAGE + 6 * STAGE_BYTES <= SM_BAR, "smem");
static_assert(SM_TOTAL <= 232448, "smem");
static_assert(SM_BAR % 8 == 0 && NWINDOWS / NPAIR < 127, "barrier alignment, flags");

constexpr int SEG_B   = (IMG - 4) * IMG;
constexpr int TILES_A = (NPIX - SEG_B + 63) / 64;
constexpr int TILES   = TILES_A + (SEG_B + 63) / 64;
constexpr uint32_t ROW_DONE = NWS * 2;

__device__ uint32_t g_cnt[NWS + 7];
__device__ __align__(128) uint8_t g_wo[73728];
__device__ uint32_t g_flag[66 * 128];
__device__ uint32_t g_done;

#define TR(ev, idx)
#define TC(slot)
#define TS(i)
#define TRH(ev, idx)
constexpr float LOG2E = 1.4426950408889634f;

__device__ __forceinline__ uint32_t smem_u32(const void* p) {
    return (uint32_t)__cvta_generic_to_shared(p);
}
__device__ __forceinline__ uint64_t make_desc(uint32_t saddr, uint32_t lbo, uint32_t sbo, uint32_t swz = 0) {
    return (uint64_t)((saddr & 0x3FFFF) >> 4) | ((uint64_t)(lbo >> 4) << 16) | ((uint64_t)(sbo >> 4) << 32) |
           ((uint64_t)swz << 62);
}
__host__ __device__ constexpr uint64_t make_desc_c(uint32_t saddr, uint32_t lbo, uint32_t sbo, uint32_t swz) {
    return (uint64_t)(saddr >> 4) | ((uint64_t)(lbo >> 4) << 16) | ((uint64_t)(sbo >> 4) << 32) | ((uint64_t)swz << 62);
}
__device__ __forceinline__ void wgmma_fence()  { asm volatile("wgmma.fence.sync.aligned;\n" ::: "memory"); }
__device__ __forceinline__ void wgmma_commit() { asm volatile("wgmma.commit_group.sync.aligned;\n" ::: "memory"); }
template <int N> __device__ __forceinline__ void wgmma_wait() {
    asm volatile("wgmma.wait_group.sync.aligned %0;\n" :: "n"(N) : "memory");
}
__device__ __forceinline__ void fence_async_smem() { asm volatile("fence.proxy.async.shared::cta;\n" ::: "memory"); }
template <int N> __device__ __forceinline__ void nb_sync(int id) { asm volatile("bar.sync %0, %1;\n" :: "r"(id), "n"(N) : "memory"); }
template <int N> __device__ __forceinline__ void nb_arrive(int id) { asm volatile("bar.arrive %0, %1;\n" :: "r"(id), "n"(N) : "memory"); }
constexpr int NB_ODONE = 0, NB_QKFREE = 6, NB_QKRAW = 12;
__device__ __forceinline__ void wg_bar(int id) { asm volatile("bar.sync %0, 128;\n" :: "r"(id) : "memory"); }

template <int N> __device__ __forceinline__ void reg_fence(float (&v)[N]) {
#pragma unroll
    for (int i = 0; i < N; i++) asm volatile("" : "+f"(v[i]) :: "memory");
}
template <int N> __device__ __forceinline__ void reg_fence(uint32_t (&v)[N]) {
#pragma unroll
    for (int i = 0; i < N; i++) asm volatile("" : "+r"(v[i]) :: "memory");
}
template <int N, int M> __device__ __forceinline__ void reg_fence(uint32_t (&v)[N][M]) {
#pragma unroll
    for (int i = 0; i < N; i++) reg_fence(v[i]);
}

__device__ __forceinline__ uint32_t pack_bf16(float lo, float hi) {
    uint32_t r;
    asm("cvt.rn.bf16x2.f32 %0, %1, %2;\n" : "=r"(r) : "f"(hi), "f"(lo));
    return r;
}
__device__ __forceinline__ float bf16lo(uint32_t v) { return __uint_as_float(v << 16); }
__device__ __forceinline__ float bf16hi(uint32_t v) { return __uint_as_float(v & 0xFFFF0000u); }
__device__ __forceinline__ uint32_t hadd2_bf16(uint32_t a, uint32_t b) {
    uint32_t r;
    asm("add.rn.bf16x2 %0, %1, %2;\n" : "=r"(r) : "r"(a), "r"(b));
    return r;
}
__device__ __forceinline__ uint32_t hmul2_bf16(uint32_t a, uint32_t b) {
    uint32_t r;
    asm("mul.rn.bf16x2 %0, %1, %2;\n" : "=r"(r) : "r"(a), "r"(b));
    return r;
}
__device__ __forceinline__ uint32_t hsub2_bf16(uint32_t a, uint32_t b) {
    uint32_t r;
    asm("sub.rn.bf16x2 %0, %1, %2;\n" : "=r"(r) : "r"(a), "r"(b));
    return r;
}
__device__ __forceinline__ uint32_t hfma2_bf16(uint32_t a, uint32_t b, uint32_t c) {
    uint32_t r;
    asm("fma.rn.bf16x2 %0, %1, %2, %3;\n" : "=r"(r) : "r"(a), "r"(b), "r"(c));
    return r;
}
__device__ __forceinline__ uint32_t hmax2_bf16(uint32_t a, uint32_t b) {
    uint32_t r;
    asm("max.bf16x2 %0, %1, %2;\n" : "=r"(r) : "r"(a), "r"(b));
    return r;
}
__device__ __forceinline__ uint32_t hmin2_bf16(uint32_t a, uint32_t b) {
    uint32_t r;
    asm("min.bf16x2 %0, %1, %2;\n" : "=r"(r) : "r"(a), "r"(b));
    return r;
}
__device__ __forceinline__ uint32_t ex2_bf16x2(uint32_t a) {
    uint32_t r;
    asm("ex2.approx.ftz.bf16x2 %0, %1;\n" : "=r"(r) : "r"(a));
    return r;
}
__device__ __forceinline__ uint32_t ex2_bf16lo(uint32_t a) {
    uint32_t r;
    asm("{\n.reg .b16 l, h;\nmov.b32 {l, h}, %1;\nex2.approx.ftz.bf16 l, l;\ncvt.u32.u16 %0, l;\n}\n" : "=r"(r) : "r"(a));
    return r;
}
__device__ __forceinline__ uint32_t mbar_test(uint32_t bar, uint32_t parity) {
    uint32_t ok;
    asm volatile("{\n.reg .pred p;\nmbarrier.test_wait.parity.shared::cta.b64 p, [%1], %2;\nselp.u32 %0, 1, 0, p;\n}\n"
                 : "=r"(ok) : "r"(bar), "r"(parity) : "memory");
    return ok;
}
__device__ __forceinline__ uint32_t prmt(uint32_t a, uint32_t b, uint32_t sel) {
    uint32_t r;
    asm("prmt.b32 %0, %1, %2, %3;\n" : "=r"(r) : "r"(a), "r"(b), "r"(sel));
    return r;
}
__device__ __forceinline__ float round_bf16(float x) { return __bfloat162float(__float2bfloat16_rn(x)); }

__device__ __forceinline__ void mbar_init(uint32_t bar, uint32_t count) {
    asm volatile("mbarrier.init.shared::cta.b64 [%0], %1;\n" :: "r"(bar), "r"(count) : "memory");
}
__device__ __forceinline__ void mbar_wait(uint32_t bar, uint32_t parity) {
    asm volatile(
        "{\n"
        ".reg .pred p;\n"
        ".reg .u32 n;\n"
        "mov.u32 n, 0;\n"
        "WAIT_%=:\n"
        "mbarrier.try_wait.parity.shared::cta.b64 p, [%0], %1" HINT ";\n"
        "@p bra DONE_%=;\n"
        "add.u32 n, n, 1;\n"
        "setp.lt.u32 p, n, 4194304;\n"
        "@p bra WAIT_%=;\n"
        "trap;\n"
        "DONE_%=:\n"
        "}\n" :: "r"(bar), "r"(parity) : "memory");
}
__device__ __forceinline__ void mbar_wait4(uint32_t b0, uint32_t p0, uint32_t b1, uint32_t p1, uint32_t b2, uint32_t p2,
                                           uint32_t b3, uint32_t p3) {
    asm volatile(
        "{\n"
        ".reg .pred p, q, r, s;\n"
        ".reg .u32 n;\n"
        "mov.u32 n, 0;\n"
        "WAIT_%=:\n"
        "mbarrier.try_wait.parity.shared::cta.b64 p, [%0], %1" HINT ";\n"
        "mbarrier.try_wait.parity.shared::cta.b64 q, [%2], %3" HINT ";\n"
        "mbarrier.try_wait.parity.shared::cta.b64 r, [%4], %5" HINT ";\n"
        "mbarrier.try_wait.parity.shared::cta.b64 s, [%6], %7" HINT ";\n"
        "and.pred p, p, q;\n"
        "and.pred r, r, s;\n"
        "and.pred p, p, r;\n"
        "@p bra DONE_%=;\n"
        "add.u32 n, n, 1;\n"
        "setp.lt.u32 p, n, 4194304;\n"
        "@p bra WAIT_%=;\n"
        "trap;\n"
        "DONE_%=:\n"
        "}\n" :: "r"(b0), "r"(p0), "r"(b1), "r"(p1), "r"(b2), "r"(p2), "r"(b3), "r"(p3) : "memory");
}
__device__ __forceinline__ void mbar_wait2(uint32_t b0, uint32_t p0, uint32_t b1, uint32_t p1) {
    asm volatile(
        "{\n"
        ".reg .pred p, q;\n"
        ".reg .u32 n;\n"
        "mov.u32 n, 0;\n"
        "WAIT_%=:\n"
        "mbarrier.try_wait.parity.shared::cta.b64 p, [%0], %1" HINT ";\n"
        "mbarrier.try_wait.parity.shared::cta.b64 q, [%2], %3" HINT ";\n"
        "and.pred p, p, q;\n"
        "@p bra DONE_%=;\n"
        "add.u32 n, n, 1;\n"
        "setp.lt.u32 p, n, 4194304;\n"
        "@p bra WAIT_%=;\n"
        "trap;\n"
        "DONE_%=:\n"
        "}\n" :: "r"(b0), "r"(p0), "r"(b1), "r"(p1) : "memory");
}
__device__ __forceinline__ void mbar_wait_unless(uint32_t ok, uint32_t bar, uint32_t parity) {
    asm volatile(
        "{\n"
        ".reg .pred p;\n"
        ".reg .u32 n;\n"
        "setp.ne.u32 p, %2, 0;\n"
        "vote.sync.all.pred p, p, 0xffffffff;\n"
        "@p bra DONE_%=;\n"
        "mov.u32 n, 0;\n"
        "WAIT_%=:\n"
        "mbarrier.try_wait.parity.shared::cta.b64 p, [%0], %1" HINT ";\n"
        "@p bra DONE_%=;\n"
        "add.u32 n, n, 1;\n"
        "setp.lt.u32 p, n, 4194304;\n"
        "@p bra WAIT_%=;\n"
        "trap;\n"
        "DONE_%=:\n"
        "}\n" :: "r"(bar), "r"(parity), "r"(ok) : "memory");
}
__device__ __forceinline__ void mbar_wait2_unless(uint32_t ok, uint32_t b0, uint32_t p0, uint32_t b1, uint32_t p1) {
    asm volatile(
        "{\n"
        ".reg .pred p, q;\n"
        ".reg .u32 n;\n"
        "setp.ne.u32 p, %4, 0;\n"
        "vote.sync.all.pred p, p, 0xffffffff;\n"
        "@p bra DONE_%=;\n"
        "mov.u32 n, 0;\n"
        "WAIT_%=:\n"
        "mbarrier.try_wait.parity.shared::cta.b64 p, [%0], %1" HINT ";\n"
        "mbarrier.try_wait.parity.shared::cta.b64 q, [%2], %3" HINT ";\n"
        "and.pred p, p, q;\n"
        "@p bra DONE_%=;\n"
        "add.u32 n, n, 1;\n"
        "setp.lt.u32 p, n, 4194304;\n"
        "@p bra WAIT_%=;\n"
        "trap;\n"
        "DONE_%=:\n"
        "}\n" :: "r"(b0), "r"(p0), "r"(b1), "r"(p1), "r"(ok) : "memory");
}
__device__ __forceinline__ void mbar_wait4_unless(uint32_t ok, uint32_t b0, uint32_t p0, uint32_t b1, uint32_t p1, uint32_t b2,
                                                  uint32_t p2, uint32_t b3, uint32_t p3) {
    asm volatile(
        "{\n"
        ".reg .pred p, q, r, s;\n"
        ".reg .u32 n;\n"
        "setp.ne.u32 p, %8, 0;\n"
        "vote.sync.all.pred p, p, 0xffffffff;\n"
        "@p bra DONE_%=;\n"
        "mov.u32 n, 0;\n"
        "WAIT_%=:\n"
        "mbarrier.try_wait.parity.shared::cta.b64 p, [%0], %1" HINT ";\n"
        "mbarrier.try_wait.parity.shared::cta.b64 q, [%2], %3" HINT ";\n"
        "mbarrier.try_wait.parity.shared::cta.b64 r, [%4], %5" HINT ";\n"
        "mbarrier.try_wait.parity.shared::cta.b64 s, [%6], %7" HINT ";\n"
        "and.pred p, p, q;\n"
        "and.pred r, r, s;\n"
        "and.pred p, p, r;\n"
        "@p bra DONE_%=;\n"
        "add.u32 n, n, 1;\n"
        "setp.lt.u32 p, n, 4194304;\n"
        "@p bra WAIT_%=;\n"
        "trap;\n"
        "DONE_%=:\n"
        "}\n" :: "r"(b0), "r"(p0), "r"(b1), "r"(p1), "r"(b2), "r"(p2), "r"(b3), "r"(p3), "r"(ok) : "memory");
}
__device__ __forceinline__ void sched_fence(uint32_t zero, uint32_t a, uint32_t b, uint32_t c, uint32_t d, uint32_t e = 0,
                                            uint32_t f = 0, uint32_t g = 0, uint32_t h = 0, uint32_t i = 0, uint32_t j = 0,
                                            uint32_t k = 0) {
    asm volatile("{\n.reg .pred p;\n.reg .u32 n;\nsetp.eq.u32 p, %0, 0;\n@p bra.uni DONE_%=;\nmov.u32 n, %0;\nSPIN_%=:\n"
                 "nanosleep.u32 %1;\nnanosleep.u32 %2;\nnanosleep.u32 %3;\nnanosleep.u32 %4;\nnanosleep.u32 %5;\n"
                 "nanosleep.u32 %6;\nnanosleep.u32 %7;\nnanosleep.u32 %8;\nnanosleep.u32 %9;\nnanosleep.u32 %10;\n"
                 "nanosleep.u32 %11;\nsub.u32 n, n, 1;\nsetp.ne.u32 p, n, 0;\n@p bra.uni SPIN_%=;\nDONE_%=:\n}\n"
                 :: "r"(zero), "r"(a), "r"(b), "r"(c), "r"(d), "r"(e), "r"(f), "r"(g), "r"(h), "r"(i), "r"(j), "r"(k) : "memory");
}
template <int N> __device__ __forceinline__ void use_regs(const uint32_t* v) {
    if constexpr (N >= 4) {
        asm volatile("nanosleep.u32 %0;\nnanosleep.u32 %1;\nnanosleep.u32 %2;\nnanosleep.u32 %3;\n" :: "r"(v[0]), "r"(v[1]), "r"(v[2]), "r"(v[3]) : "memory");
        use_regs<N - 4>(v + 4);
    } else if constexpr (N > 0) {
        asm volatile("nanosleep.u32 %0;\n" :: "r"(v[0]) : "memory");
        use_regs<N - 1>(v + 1);
    }
}
template <int N> __device__ __forceinline__ void sched_fence_n(uint32_t zero, const uint32_t (&v)[N]) {
    if (__builtin_expect(zero != 0, 0)) {
#pragma unroll 1
        for (uint32_t n = zero; n; n--) use_regs<N>(v);
    }
}
__device__ __forceinline__ void sched_fence_rw(uint32_t zero, uint32_t (&v)[13]) {
    asm volatile("{\n.reg .pred p;\n.reg .u32 n;\nsetp.eq.u32 p, %13, 0;\n@p bra.uni DONE_%=;\nmov.u32 n, %13;\nSPIN_%=:\n"
                 "add.u32 %0, %0, %1;\nadd.u32 %1, %1, %2;\nadd.u32 %2, %2, %3;\nadd.u32 %3, %3, %4;\nadd.u32 %4, %4, %5;\n"
                 "add.u32 %5, %5, %6;\nadd.u32 %6, %6, %7;\nadd.u32 %7, %7, %8;\nadd.u32 %8, %8, %9;\nadd.u32 %9, %9, %10;\n"
                 "add.u32 %10, %10, %11;\nadd.u32 %11, %11, %12;\nadd.u32 %12, %12, %0;\n"
                 "sub.u32 n, n, 1;\nsetp.ne.u32 p, n, 0;\n@p bra.uni SPIN_%=;\nDONE_%=:\n}\n"
                 : "+r"(v[0]), "+r"(v[1]), "+r"(v[2]), "+r"(v[3]), "+r"(v[4]), "+r"(v[5]), "+r"(v[6]), "+r"(v[7]), "+r"(v[8]),
                   "+r"(v[9]), "+r"(v[10]), "+r"(v[11]), "+r"(v[12]) : "r"(zero) : "memory");
}
__device__ __forceinline__ void mbar_arrive(uint32_t bar) {
    asm volatile("mbarrier.arrive.shared::cta.b64 _, [%0];\n" :: "r"(bar) : "memory");
}
__device__ __forceinline__ void mbar_arrive_n(uint32_t bar, uint32_t n) {
    asm volatile("mbarrier.arrive.shared::cta.b64 _, [%0], %1;\n" :: "r"(bar), "r"(n) : "memory");
}
__device__ __forceinline__ void mbar_arrive_expect_tx(uint32_t bar, uint32_t bytes) {
    asm volatile("mbarrier.arrive.expect_tx.shared::cta.b64 _, [%0], %1;\n" :: "r"(bar), "r"(bytes) : "memory");
}
__device__ __forceinline__ void stg128_if(bool p, void* addr, uint32_t x, uint32_t y, uint32_t z, uint32_t w) {
    asm volatile("{\n.reg .pred q;\nsetp.ne.b32 q, %5, 0;\n@q st.global.L1::no_allocate.v4.b32 [%0], {%1, %2, %3, %4};\n}\n"
                 :: "l"(addr), "r"(x), "r"(y), "r"(z), "r"(w), "r"((uint32_t)p) : "memory");
}
__device__ __forceinline__ void stsm_x4(uint32_t addr, uint32_t r0, uint32_t r1, uint32_t r2, uint32_t r3) {
    asm volatile("stmatrix.sync.aligned.m8n8.x4.shared.b16 [%0], {%1, %2, %3, %4};\n"
                 :: "r"(addr), "r"(r0), "r"(r1), "r"(r2), "r"(r3) : "memory");
}
__device__ __forceinline__ void stsm_x2(uint32_t addr, uint32_t r0, uint32_t r1) {
    asm volatile("stmatrix.sync.aligned.m8n8.x2.shared.b16 [%0], {%1, %2};\n" :: "r"(addr), "r"(r0), "r"(r1) : "memory");
}
__device__ __forceinline__ void sts128(uint32_t addr, uint32_t r0, uint32_t r1, uint32_t r2, uint32_t r3) {
    asm volatile("st.shared.v4.b32 [%0], {%1, %2, %3, %4};\n" :: "r"(addr), "r"(r0), "r"(r1), "r"(r2), "r"(r3) : "memory");
}
__device__ __forceinline__ void sts128_if(uint32_t p, uint32_t addr, uint32_t r0, uint32_t r1, uint32_t r2, uint32_t r3) {
    asm volatile("{\n.reg .pred q;\nsetp.ne.b32 q, %5, 0;\n@q st.shared.v4.b32 [%0], {%1, %2, %3, %4};\n}\n"
                 :: "r"(addr), "r"(r0), "r"(r1), "r"(r2), "r"(r3), "r"(p) : "memory");
}
__device__ __forceinline__ void sts32(uint32_t addr, uint32_t v) {
    asm volatile("st.shared.b32 [%0], %1;\n" :: "r"(addr), "r"(v) : "memory");
}
__device__ __forceinline__ uint32_t lds32(uint32_t addr) {
    uint32_t v;
    asm volatile("ld.shared.b32 %0, [%1];\n" : "=r"(v) : "r"(addr) : "memory");
    return v;
}
__device__ __forceinline__ void ldg_nc_v4(uint32_t (&r)[4], const void* p) {
    asm volatile("ld.global.nc.L1::no_allocate.v4.u32 {%0, %1, %2, %3}, [%4];\n"
                 : "=r"(r[0]), "=r"(r[1]), "=r"(r[2]), "=r"(r[3]) : "l"(p));
}
__device__ __forceinline__ uint32_t ldg_u32(const void* p) {
    uint32_t v;
    asm volatile("ld.global.nc.L1::evict_first.u32 %0, [%1];\n" : "=r"(v) : "l"(p));
    return v;
}
__device__ __forceinline__ void ldg_u64(const void* p, uint32_t& a, uint32_t& b) {
    asm volatile("ld.global.nc.L1::evict_first.v2.u32 {%0, %1}, [%2];\n" : "=r"(a), "=r"(b) : "l"(p));
}
__device__ __forceinline__ void prefetch_l2(const void* p) {
    asm volatile("prefetch.global.L2 [%0];\n" :: "l"(p));
}
__device__ __forceinline__ void cp_async16(uint32_t dst, const void* src) {
    asm volatile("cp.async.cg.shared.global [%0], [%1], 16;\n" :: "r"(dst), "l"(src) : "memory");
}
__device__ __forceinline__ float ex2_ftz(float x) {
    float y;
    asm("ex2.approx.ftz.f32 %0, %1;\n" : "=f"(y) : "f"(x));
    return y;
}
__device__ __forceinline__ float lg2_ftz(float x) {
    float y;
    asm("lg2.approx.ftz.f32 %0, %1;\n" : "=f"(y) : "f"(x));
    return y;
}
__device__ __forceinline__ float rcp_ftz(float x) {
    float y;
    asm("rcp.approx.ftz.f32 %0, %1;\n" : "=f"(y) : "f"(x));
    return y;
}
__device__ __forceinline__ float rsqrt_ftz(float x) {
    float y;
    asm("rsqrt.approx.ftz.f32 %0, %1;\n" : "=f"(y) : "f"(x));
    return y;
}

__device__ __forceinline__ bool elect_one() {
    uint32_t p;
    asm volatile("{\n.reg .pred q;\nelect.sync _|q, 0xffffffff;\nselp.u32 %0, 1, 0, q;\n}\n" : "=r"(p));
    return p != 0;
}
__device__ __forceinline__ void ldsm_x4(uint32_t (&r)[4], uint32_t addr) {
    asm volatile("ldmatrix.sync.aligned.m8n8.x4.shared.b16 {%0, %1, %2, %3}, [%4];\n"
                 : "=r"(r[0]), "=r"(r[1]), "=r"(r[2]), "=r"(r[3]) : "r"(addr) : "memory");
}
__device__ __forceinline__ void ldsm_x2(uint32_t& r0, uint32_t& r1, uint32_t addr) {
    asm volatile("ldmatrix.sync.aligned.m8n8.x2.shared.b16 {%0, %1}, [%2];\n" : "=r"(r0), "=r"(r1) : "r"(addr) : "memory");
}
__device__ __forceinline__ void tma_2d(uint32_t dst, const CUtensorMap* map, uint32_t bar, int c0, int c1) {
    asm volatile("cp.async.bulk.tensor.2d.shared::cluster.global.mbarrier::complete_tx::bytes [%0], [%1, {%3, %4}], [%2];\n"
                 :: "r"(dst), "l"(reinterpret_cast<uint64_t>(map)), "r"(bar), "r"(c0), "r"(c1) : "memory");
}
__device__ __forceinline__ void tma_3d(uint32_t dst, const CUtensorMap* map, uint32_t bar, int c0, int c1, int c2) {
    asm volatile("cp.async.bulk.tensor.3d.shared::cluster.global.mbarrier::complete_tx::bytes [%0], [%1, {%3, %4, %5}], [%2];\n"
                 :: "r"(dst), "l"(reinterpret_cast<uint64_t>(map)), "r"(bar), "r"(c0), "r"(c1), "r"(c2) : "memory");
}
constexpr uint64_t EVICT_FIRST = 0x12F0000000000000ull;
__device__ __forceinline__ void tma_3d_x(uint32_t dst, const CUtensorMap* map, uint32_t bar, int c0, int c1, int c2) {
    if (CH & 50)
        asm volatile("cp.async.bulk.tensor.3d.shared::cluster.global.mbarrier::complete_tx::bytes.L2::cache_hint [%0], [%1, {%3, %4, %5}], [%2], %6;\n"
                     :: "r"(dst), "l"(reinterpret_cast<uint64_t>(map)), "r"(bar), "r"(c0), "r"(c1), "r"(c2),
                        "l"((CH & 2) || (blockIdx.x & 1) == ((CH >> 5) & 1) ? EVICT_FIRST : 0x1000000000000000ull) : "memory");
    else tma_3d(dst, map, bar, c0, c1, c2);
}
__device__ __forceinline__ void tma_store_4d(const CUtensorMap* map, uint32_t src, int c0, int c1, int c2, int c3) {
    asm volatile("cp.async.bulk.tensor.4d.global.shared::cta.tile.bulk_group [%0, {%2, %3, %4, %5}], [%1];\n"
                 :: "l"(reinterpret_cast<uint64_t>(map)), "r"(src), "r"(c0), "r"(c1), "r"(c2), "r"(c3) : "memory");
}
__device__ __forceinline__ void mbar_arrive_if(uint32_t bar, uint32_t cnt) {
    asm volatile("{\n.reg .pred q;\nsetp.ne.b32 q, %1, 0;\n@q mbarrier.arrive.shared::cta.b64 _, [%0], %1;\n}\n"
                 :: "r"(bar), "r"(cnt) : "memory");
}

template <int BOFF, int AOFF, int NA>
__device__ __forceinline__ void mma_qkv_a(float (&d)[48], const uint32_t (&a)[NA][4], uint64_t descB) {
    asm volatile(
        "{\n"
        ".reg .pred p0, p1;\n"
        ".reg .b64 ta, ta0, tb, tb0;\n"
        "setp.ne.b32 p0, 0, 0;\n"
        "setp.eq.b32 p1, 0, 0;\n"
        "add.s64 tb0, %72, %73;\n"
        "add.s64 tb, tb0, 0;\n"
        "wgmma.mma_async.sync.aligned.m64n96k16.f32.bf16.bf16 {%0, %1, %2, %3, %4, %5, %6, %7, %8, %9, %10, %11, %12, %13, %14, %15, %16, %17, %18, %19, %20, %21, %22, %23, %24, %25, %26, %27, %28, %29, %30, %31, %32, %33, %34, %35, %36, %37, %38, %39, %40, %41, %42, %43, %44, %45, %46, %47}, {%48, %49, %50, %51}, tb, p0, 1, 1, 1;\n"
        "add.s64 tb, tb0, 32;\n"
        "wgmma.mma_async.sync.aligned.m64n96k16.f32.bf16.bf16 {%0, %1, %2, %3, %4, %5, %6, %7, %8, %9, %10, %11, %12, %13, %14, %15, %16, %17, %18, %19, %20, %21, %22, %23, %24, %25, %26, %27, %28, %29, %30, %31, %32, %33, %34, %35, %36, %37, %38, %39, %40, %41, %42, %43, %44, %45, %46, %47}, {%52, %53, %54, %55}, tb, p1, 1, 1, 1;\n"
        "add.s64 tb, tb0, 64;\n"
        "wgmma.mma_async.sync.aligned.m64n96k16.f32.bf16.bf16 {%0, %1, %2, %3, %4, %5, %6, %7, %8, %9, %10, %11, %12, %13, %14, %15, %16, %17, %18, %19, %20, %21, %22, %23, %24, %25, %26, %27, %28, %29, %30, %31, %32, %33, %34, %35, %36, %37, %38, %39, %40, %41, %42, %43, %44, %45, %46, %47}, {%56, %57, %58, %59}, tb, p1, 1, 1, 1;\n"
        "add.s64 tb, tb0, 96;\n"
        "wgmma.mma_async.sync.aligned.m64n96k16.f32.bf16.bf16 {%0, %1, %2, %3, %4, %5, %6, %7, %8, %9, %10, %11, %12, %13, %14, %15, %16, %17, %18, %19, %20, %21, %22, %23, %24, %25, %26, %27, %28, %29, %30, %31, %32, %33, %34, %35, %36, %37, %38, %39, %40, %41, %42, %43, %44, %45, %46, %47}, {%60, %61, %62, %63}, tb, p1, 1, 1, 1;\n"
        "add.s64 tb, tb0, 1536;\n"
        "wgmma.mma_async.sync.aligned.m64n96k16.f32.bf16.bf16 {%0, %1, %2, %3, %4, %5, %6, %7, %8, %9, %10, %11, %12, %13, %14, %15, %16, %17, %18, %19, %20, %21, %22, %23, %24, %25, %26, %27, %28, %29, %30, %31, %32, %33, %34, %35, %36, %37, %38, %39, %40, %41, %42, %43, %44, %45, %46, %47}, {%64, %65, %66, %67}, tb, p1, 1, 1, 1;\n"
        "add.s64 tb, tb0, 1568;\n"
        "wgmma.mma_async.sync.aligned.m64n96k16.f32.bf16.bf16 {%0, %1, %2, %3, %4, %5, %6, %7, %8, %9, %10, %11, %12, %13, %14, %15, %16, %17, %18, %19, %20, %21, %22, %23, %24, %25, %26, %27, %28, %29, %30, %31, %32, %33, %34, %35, %36, %37, %38, %39, %40, %41, %42, %43, %44, %45, %46, %47}, {%68, %69, %70, %71}, tb, p1, 1, 1, 1;\n"
        "}\n"
        : "=f"(d[0]), "=f"(d[1]), "=f"(d[2]), "=f"(d[3]), "=f"(d[4]), "=f"(d[5]), "=f"(d[6]), "=f"(d[7]), "=f"(d[8]), "=f"(d[9]), "=f"(d[10]), "=f"(d[11]), "=f"(d[12]), "=f"(d[13]), "=f"(d[14]), "=f"(d[15]), "=f"(d[16]), "=f"(d[17]), "=f"(d[18]), "=f"(d[19]), "=f"(d[20]), "=f"(d[21]), "=f"(d[22]), "=f"(d[23]), "=f"(d[24]), "=f"(d[25]), "=f"(d[26]), "=f"(d[27]), "=f"(d[28]), "=f"(d[29]), "=f"(d[30]), "=f"(d[31]), "=f"(d[32]), "=f"(d[33]), "=f"(d[34]), "=f"(d[35]), "=f"(d[36]), "=f"(d[37]), "=f"(d[38]), "=f"(d[39]), "=f"(d[40]), "=f"(d[41]), "=f"(d[42]), "=f"(d[43]), "=f"(d[44]), "=f"(d[45]), "=f"(d[46]), "=f"(d[47])
        : "r"(a[AOFF + 0][0]), "r"(a[AOFF + 0][1]), "r"(a[AOFF + 0][2]), "r"(a[AOFF + 0][3]), "r"(a[AOFF + 1][0]), "r"(a[AOFF + 1][1]), "r"(a[AOFF + 1][2]), "r"(a[AOFF + 1][3]), "r"(a[AOFF + 2][0]), "r"(a[AOFF + 2][1]), "r"(a[AOFF + 2][2]), "r"(a[AOFF + 2][3]), "r"(a[AOFF + 3][0]), "r"(a[AOFF + 3][1]), "r"(a[AOFF + 3][2]), "r"(a[AOFF + 3][3]), "r"(a[AOFF + 4][0]), "r"(a[AOFF + 4][1]), "r"(a[AOFF + 4][2]), "r"(a[AOFF + 4][3]), "r"(a[AOFF + 5][0]), "r"(a[AOFF + 5][1]), "r"(a[AOFF + 5][2]), "r"(a[AOFF + 5][3]), "l"(descB), "n"(BOFF >> 4));
}

template <int BOFF, int AOFF, int NA>
__device__ __forceinline__ void mma_qkv_b(float (&d)[48], const uint32_t (&a)[NA][4], uint64_t descB) {
    asm volatile(
        "{\n"
        ".reg .pred p0, p1;\n"
        ".reg .b64 ta, ta0, tb, tb0;\n"
        "setp.ne.b32 p0, 0, 0;\n"
        "setp.eq.b32 p1, 0, 0;\n"
        "add.s64 tb0, %72, %73;\n"
        "add.s64 tb, tb0, 1600;\n"
        "wgmma.mma_async.sync.aligned.m64n96k16.f32.bf16.bf16 {%0, %1, %2, %3, %4, %5, %6, %7, %8, %9, %10, %11, %12, %13, %14, %15, %16, %17, %18, %19, %20, %21, %22, %23, %24, %25, %26, %27, %28, %29, %30, %31, %32, %33, %34, %35, %36, %37, %38, %39, %40, %41, %42, %43, %44, %45, %46, %47}, {%48, %49, %50, %51}, tb, p1, 1, 1, 1;\n"
        "add.s64 tb, tb0, 1632;\n"
        "wgmma.mma_async.sync.aligned.m64n96k16.f32.bf16.bf16 {%0, %1, %2, %3, %4, %5, %6, %7, %8, %9, %10, %11, %12, %13, %14, %15, %16, %17, %18, %19, %20, %21, %22, %23, %24, %25, %26, %27, %28, %29, %30, %31, %32, %33, %34, %35, %36, %37, %38, %39, %40, %41, %42, %43, %44, %45, %46, %47}, {%52, %53, %54, %55}, tb, p1, 1, 1, 1;\n"
        "add.s64 tb, tb0, 3072;\n"
        "wgmma.mma_async.sync.aligned.m64n96k16.f32.bf16.bf16 {%0, %1, %2, %3, %4, %5, %6, %7, %8, %9, %10, %11, %12, %13, %14, %15, %16, %17, %18, %19, %20, %21, %22, %23, %24, %25, %26, %27, %28, %29, %30, %31, %32, %33, %34, %35, %36, %37, %38, %39, %40, %41, %42, %43, %44, %45, %46, %47}, {%56, %57, %58, %59}, tb, p1, 1, 1, 1;\n"
        "add.s64 tb, tb0, 3104;\n"
        "wgmma.mma_async.sync.aligned.m64n96k16.f32.bf16.bf16 {%0, %1, %2, %3, %4, %5, %6, %7, %8, %9, %10, %11, %12, %13, %14, %15, %16, %17, %18, %19, %20, %21, %22, %23, %24, %25, %26, %27, %28, %29, %30, %31, %32, %33, %34, %35, %36, %37, %38, %39, %40, %41, %42, %43, %44, %45, %46, %47}, {%60, %61, %62, %63}, tb, p1, 1, 1, 1;\n"
        "add.s64 tb, tb0, 3136;\n"
        "wgmma.mma_async.sync.aligned.m64n96k16.f32.bf16.bf16 {%0, %1, %2, %3, %4, %5, %6, %7, %8, %9, %10, %11, %12, %13, %14, %15, %16, %17, %18, %19, %20, %21, %22, %23, %24, %25, %26, %27, %28, %29, %30, %31, %32, %33, %34, %35, %36, %37, %38, %39, %40, %41, %42, %43, %44, %45, %46, %47}, {%64, %65, %66, %67}, tb, p1, 1, 1, 1;\n"
        "add.s64 tb, tb0, 3168;\n"
        "wgmma.mma_async.sync.aligned.m64n96k16.f32.bf16.bf16 {%0, %1, %2, %3, %4, %5, %6, %7, %8, %9, %10, %11, %12, %13, %14, %15, %16, %17, %18, %19, %20, %21, %22, %23, %24, %25, %26, %27, %28, %29, %30, %31, %32, %33, %34, %35, %36, %37, %38, %39, %40, %41, %42, %43, %44, %45, %46, %47}, {%68, %69, %70, %71}, tb, p1, 1, 1, 1;\n"
        "}\n"
        : "+f"(d[0]), "+f"(d[1]), "+f"(d[2]), "+f"(d[3]), "+f"(d[4]), "+f"(d[5]), "+f"(d[6]), "+f"(d[7]), "+f"(d[8]), "+f"(d[9]), "+f"(d[10]), "+f"(d[11]), "+f"(d[12]), "+f"(d[13]), "+f"(d[14]), "+f"(d[15]), "+f"(d[16]), "+f"(d[17]), "+f"(d[18]), "+f"(d[19]), "+f"(d[20]), "+f"(d[21]), "+f"(d[22]), "+f"(d[23]), "+f"(d[24]), "+f"(d[25]), "+f"(d[26]), "+f"(d[27]), "+f"(d[28]), "+f"(d[29]), "+f"(d[30]), "+f"(d[31]), "+f"(d[32]), "+f"(d[33]), "+f"(d[34]), "+f"(d[35]), "+f"(d[36]), "+f"(d[37]), "+f"(d[38]), "+f"(d[39]), "+f"(d[40]), "+f"(d[41]), "+f"(d[42]), "+f"(d[43]), "+f"(d[44]), "+f"(d[45]), "+f"(d[46]), "+f"(d[47])
        : "r"(a[AOFF + 0][0]), "r"(a[AOFF + 0][1]), "r"(a[AOFF + 0][2]), "r"(a[AOFF + 0][3]), "r"(a[AOFF + 1][0]), "r"(a[AOFF + 1][1]), "r"(a[AOFF + 1][2]), "r"(a[AOFF + 1][3]), "r"(a[AOFF + 2][0]), "r"(a[AOFF + 2][1]), "r"(a[AOFF + 2][2]), "r"(a[AOFF + 2][3]), "r"(a[AOFF + 3][0]), "r"(a[AOFF + 3][1]), "r"(a[AOFF + 3][2]), "r"(a[AOFF + 3][3]), "r"(a[AOFF + 4][0]), "r"(a[AOFF + 4][1]), "r"(a[AOFF + 4][2]), "r"(a[AOFF + 4][3]), "r"(a[AOFF + 5][0]), "r"(a[AOFF + 5][1]), "r"(a[AOFF + 5][2]), "r"(a[AOFF + 5][3]), "l"(descB), "n"(BOFF >> 4));
}

template <int BOFF, int AOFF, int NA>
__device__ __forceinline__ void mma_v_a(float (&d)[48], const uint32_t (&a)[NA][4], uint64_t descB) {
    asm volatile(
        "{\n"
        ".reg .pred p0, p1;\n"
        ".reg .b64 ta, ta0, tb, tb0;\n"
        "setp.ne.b32 p0, 0, 0;\n"
        "setp.eq.b32 p1, 0, 0;\n"
        "add.s64 tb0, %72, %73;\n"
        "add.s64 tb, tb0, 0;\n"
        "wgmma.mma_async.sync.aligned.m64n96k16.f32.bf16.bf16 {%0, %1, %2, %3, %4, %5, %6, %7, %8, %9, %10, %11, %12, %13, %14, %15, %16, %17, %18, %19, %20, %21, %22, %23, %24, %25, %26, %27, %28, %29, %30, %31, %32, %33, %34, %35, %36, %37, %38, %39, %40, %41, %42, %43, %44, %45, %46, %47}, {%48, %49, %50, %51}, tb, p0, 1, 1, 1;\n"
        "add.s64 tb, tb0, 32;\n"
        "wgmma.mma_async.sync.aligned.m64n96k16.f32.bf16.bf16 {%0, %1, %2, %3, %4, %5, %6, %7, %8, %9, %10, %11, %12, %13, %14, %15, %16, %17, %18, %19, %20, %21, %22, %23, %24, %25, %26, %27, %28, %29, %30, %31, %32, %33, %34, %35, %36, %37, %38, %39, %40, %41, %42, %43, %44, %45, %46, %47}, {%52, %53, %54, %55}, tb, p1, 1, 1, 1;\n"
        "add.s64 tb, tb0, 64;\n"
        "wgmma.mma_async.sync.aligned.m64n96k16.f32.bf16.bf16 {%0, %1, %2, %3, %4, %5, %6, %7, %8, %9, %10, %11, %12, %13, %14, %15, %16, %17, %18, %19, %20, %21, %22, %23, %24, %25, %26, %27, %28, %29, %30, %31, %32, %33, %34, %35, %36, %37, %38, %39, %40, %41, %42, %43, %44, %45, %46, %47}, {%56, %57, %58, %59}, tb, p1, 1, 1, 1;\n"
        "add.s64 tb, tb0, 96;\n"
        "wgmma.mma_async.sync.aligned.m64n96k16.f32.bf16.bf16 {%0, %1, %2, %3, %4, %5, %6, %7, %8, %9, %10, %11, %12, %13, %14, %15, %16, %17, %18, %19, %20, %21, %22, %23, %24, %25, %26, %27, %28, %29, %30, %31, %32, %33, %34, %35, %36, %37, %38, %39, %40, %41, %42, %43, %44, %45, %46, %47}, {%60, %61, %62, %63}, tb, p1, 1, 1, 1;\n"
        "add.s64 tb, tb0, 128;\n"
        "wgmma.mma_async.sync.aligned.m64n96k16.f32.bf16.bf16 {%0, %1, %2, %3, %4, %5, %6, %7, %8, %9, %10, %11, %12, %13, %14, %15, %16, %17, %18, %19, %20, %21, %22, %23, %24, %25, %26, %27, %28, %29, %30, %31, %32, %33, %34, %35, %36, %37, %38, %39, %40, %41, %42, %43, %44, %45, %46, %47}, {%64, %65, %66, %67}, tb, p1, 1, 1, 1;\n"
        "add.s64 tb, tb0, 160;\n"
        "wgmma.mma_async.sync.aligned.m64n96k16.f32.bf16.bf16 {%0, %1, %2, %3, %4, %5, %6, %7, %8, %9, %10, %11, %12, %13, %14, %15, %16, %17, %18, %19, %20, %21, %22, %23, %24, %25, %26, %27, %28, %29, %30, %31, %32, %33, %34, %35, %36, %37, %38, %39, %40, %41, %42, %43, %44, %45, %46, %47}, {%68, %69, %70, %71}, tb, p1, 1, 1, 1;\n"
        "}\n"
        : "=f"(d[0]), "=f"(d[1]), "=f"(d[2]), "=f"(d[3]), "=f"(d[4]), "=f"(d[5]), "=f"(d[6]), "=f"(d[7]), "=f"(d[8]), "=f"(d[9]), "=f"(d[10]), "=f"(d[11]), "=f"(d[12]), "=f"(d[13]), "=f"(d[14]), "=f"(d[15]), "=f"(d[16]), "=f"(d[17]), "=f"(d[18]), "=f"(d[19]), "=f"(d[20]), "=f"(d[21]), "=f"(d[22]), "=f"(d[23]), "=f"(d[24]), "=f"(d[25]), "=f"(d[26]), "=f"(d[27]), "=f"(d[28]), "=f"(d[29]), "=f"(d[30]), "=f"(d[31]), "=f"(d[32]), "=f"(d[33]), "=f"(d[34]), "=f"(d[35]), "=f"(d[36]), "=f"(d[37]), "=f"(d[38]), "=f"(d[39]), "=f"(d[40]), "=f"(d[41]), "=f"(d[42]), "=f"(d[43]), "=f"(d[44]), "=f"(d[45]), "=f"(d[46]), "=f"(d[47])
        : "r"(a[AOFF + 0][0]), "r"(a[AOFF + 0][1]), "r"(a[AOFF + 0][2]), "r"(a[AOFF + 0][3]), "r"(a[AOFF + 1][0]), "r"(a[AOFF + 1][1]), "r"(a[AOFF + 1][2]), "r"(a[AOFF + 1][3]), "r"(a[AOFF + 2][0]), "r"(a[AOFF + 2][1]), "r"(a[AOFF + 2][2]), "r"(a[AOFF + 2][3]), "r"(a[AOFF + 3][0]), "r"(a[AOFF + 3][1]), "r"(a[AOFF + 3][2]), "r"(a[AOFF + 3][3]), "r"(a[AOFF + 4][0]), "r"(a[AOFF + 4][1]), "r"(a[AOFF + 4][2]), "r"(a[AOFF + 4][3]), "r"(a[AOFF + 5][0]), "r"(a[AOFF + 5][1]), "r"(a[AOFF + 5][2]), "r"(a[AOFF + 5][3]), "l"(descB), "n"(BOFF >> 4));
}

template <int BOFF, int AOFF, int NA>
__device__ __forceinline__ void mma_v_b(float (&d)[48], const uint32_t (&a)[NA][4], uint64_t descB) {
    asm volatile(
        "{\n"
        ".reg .pred p0, p1;\n"
        ".reg .b64 ta, ta0, tb, tb0;\n"
        "setp.ne.b32 p0, 0, 0;\n"
        "setp.eq.b32 p1, 0, 0;\n"
        "add.s64 tb0, %72, %73;\n"
        "add.s64 tb, tb0, 192;\n"
        "wgmma.mma_async.sync.aligned.m64n96k16.f32.bf16.bf16 {%0, %1, %2, %3, %4, %5, %6, %7, %8, %9, %10, %11, %12, %13, %14, %15, %16, %17, %18, %19, %20, %21, %22, %23, %24, %25, %26, %27, %28, %29, %30, %31, %32, %33, %34, %35, %36, %37, %38, %39, %40, %41, %42, %43, %44, %45, %46, %47}, {%48, %49, %50, %51}, tb, p1, 1, 1, 1;\n"
        "add.s64 tb, tb0, 224;\n"
        "wgmma.mma_async.sync.aligned.m64n96k16.f32.bf16.bf16 {%0, %1, %2, %3, %4, %5, %6, %7, %8, %9, %10, %11, %12, %13, %14, %15, %16, %17, %18, %19, %20, %21, %22, %23, %24, %25, %26, %27, %28, %29, %30, %31, %32, %33, %34, %35, %36, %37, %38, %39, %40, %41, %42, %43, %44, %45, %46, %47}, {%52, %53, %54, %55}, tb, p1, 1, 1, 1;\n"
        "add.s64 tb, tb0, 256;\n"
        "wgmma.mma_async.sync.aligned.m64n96k16.f32.bf16.bf16 {%0, %1, %2, %3, %4, %5, %6, %7, %8, %9, %10, %11, %12, %13, %14, %15, %16, %17, %18, %19, %20, %21, %22, %23, %24, %25, %26, %27, %28, %29, %30, %31, %32, %33, %34, %35, %36, %37, %38, %39, %40, %41, %42, %43, %44, %45, %46, %47}, {%56, %57, %58, %59}, tb, p1, 1, 1, 1;\n"
        "add.s64 tb, tb0, 288;\n"
        "wgmma.mma_async.sync.aligned.m64n96k16.f32.bf16.bf16 {%0, %1, %2, %3, %4, %5, %6, %7, %8, %9, %10, %11, %12, %13, %14, %15, %16, %17, %18, %19, %20, %21, %22, %23, %24, %25, %26, %27, %28, %29, %30, %31, %32, %33, %34, %35, %36, %37, %38, %39, %40, %41, %42, %43, %44, %45, %46, %47}, {%60, %61, %62, %63}, tb, p1, 1, 1, 1;\n"
        "add.s64 tb, tb0, 320;\n"
        "wgmma.mma_async.sync.aligned.m64n96k16.f32.bf16.bf16 {%0, %1, %2, %3, %4, %5, %6, %7, %8, %9, %10, %11, %12, %13, %14, %15, %16, %17, %18, %19, %20, %21, %22, %23, %24, %25, %26, %27, %28, %29, %30, %31, %32, %33, %34, %35, %36, %37, %38, %39, %40, %41, %42, %43, %44, %45, %46, %47}, {%64, %65, %66, %67}, tb, p1, 1, 1, 1;\n"
        "add.s64 tb, tb0, 352;\n"
        "wgmma.mma_async.sync.aligned.m64n96k16.f32.bf16.bf16 {%0, %1, %2, %3, %4, %5, %6, %7, %8, %9, %10, %11, %12, %13, %14, %15, %16, %17, %18, %19, %20, %21, %22, %23, %24, %25, %26, %27, %28, %29, %30, %31, %32, %33, %34, %35, %36, %37, %38, %39, %40, %41, %42, %43, %44, %45, %46, %47}, {%68, %69, %70, %71}, tb, p1, 1, 1, 1;\n"
        "}\n"
        : "+f"(d[0]), "+f"(d[1]), "+f"(d[2]), "+f"(d[3]), "+f"(d[4]), "+f"(d[5]), "+f"(d[6]), "+f"(d[7]), "+f"(d[8]), "+f"(d[9]), "+f"(d[10]), "+f"(d[11]), "+f"(d[12]), "+f"(d[13]), "+f"(d[14]), "+f"(d[15]), "+f"(d[16]), "+f"(d[17]), "+f"(d[18]), "+f"(d[19]), "+f"(d[20]), "+f"(d[21]), "+f"(d[22]), "+f"(d[23]), "+f"(d[24]), "+f"(d[25]), "+f"(d[26]), "+f"(d[27]), "+f"(d[28]), "+f"(d[29]), "+f"(d[30]), "+f"(d[31]), "+f"(d[32]), "+f"(d[33]), "+f"(d[34]), "+f"(d[35]), "+f"(d[36]), "+f"(d[37]), "+f"(d[38]), "+f"(d[39]), "+f"(d[40]), "+f"(d[41]), "+f"(d[42]), "+f"(d[43]), "+f"(d[44]), "+f"(d[45]), "+f"(d[46]), "+f"(d[47])
        : "r"(a[AOFF + 0][0]), "r"(a[AOFF + 0][1]), "r"(a[AOFF + 0][2]), "r"(a[AOFF + 0][3]), "r"(a[AOFF + 1][0]), "r"(a[AOFF + 1][1]), "r"(a[AOFF + 1][2]), "r"(a[AOFF + 1][3]), "r"(a[AOFF + 2][0]), "r"(a[AOFF + 2][1]), "r"(a[AOFF + 2][2]), "r"(a[AOFF + 2][3]), "r"(a[AOFF + 3][0]), "r"(a[AOFF + 3][1]), "r"(a[AOFF + 3][2]), "r"(a[AOFF + 3][3]), "r"(a[AOFF + 4][0]), "r"(a[AOFF + 4][1]), "r"(a[AOFF + 4][2]), "r"(a[AOFF + 4][3]), "r"(a[AOFF + 5][0]), "r"(a[AOFF + 5][1]), "r"(a[AOFF + 5][2]), "r"(a[AOFF + 5][3]), "l"(descB), "n"(BOFF >> 4));
}

template <int AOFF, int BOFF>
__device__ __forceinline__ void mma_qk0(float (&d)[28], uint64_t descA, uint64_t descB) {
    asm volatile(
        "{\n"
        ".reg .pred p0, p1;\n"
        ".reg .b64 ta, ta0, tb, tb0;\n"
        "setp.ne.b32 p0, 0, 0;\n"
        "setp.eq.b32 p1, 0, 0;\n"
        "add.s64 tb0, %30, %31;\n"
        "add.s64 ta0, %28, %29;\n"
        "add.s64 tb, tb0, 4;\n"
        "add.s64 ta, ta0, 0;\n"
        "wgmma.mma_async.sync.aligned.m64n56k16.f32.bf16.bf16 {%0, %1, %2, %3, %4, %5, %6, %7, %8, %9, %10, %11, %12, %13, %14, %15, %16, %17, %18, %19, %20, %21, %22, %23, %24, %25, %26, %27}, ta, tb, p0, 1, 1, 0, 0;\n"
        "add.s64 tb, tb0, 1572;\n"
        "add.s64 ta, ta0, 1568;\n"
        "wgmma.mma_async.sync.aligned.m64n56k16.f32.bf16.bf16 {%0, %1, %2, %3, %4, %5, %6, %7, %8, %9, %10, %11, %12, %13, %14, %15, %16, %17, %18, %19, %20, %21, %22, %23, %24, %25, %26, %27}, ta, tb, p1, 1, 1, 0, 0;\n"
        "add.s64 tb, tb0, 3140;\n"
        "add.s64 ta, ta0, 3136;\n"
        "wgmma.mma_async.sync.aligned.m64n56k16.f32.bf16.bf16 {%0, %1, %2, %3, %4, %5, %6, %7, %8, %9, %10, %11, %12, %13, %14, %15, %16, %17, %18, %19, %20, %21, %22, %23, %24, %25, %26, %27}, ta, tb, p1, 1, 1, 0, 0;\n"
        "}\n"
        : "=f"(d[0]), "=f"(d[1]), "=f"(d[2]), "=f"(d[3]), "=f"(d[4]), "=f"(d[5]), "=f"(d[6]), "=f"(d[7]), "=f"(d[8]), "=f"(d[9]), "=f"(d[10]), "=f"(d[11]), "=f"(d[12]), "=f"(d[13]), "=f"(d[14]), "=f"(d[15]), "=f"(d[16]), "=f"(d[17]), "=f"(d[18]), "=f"(d[19]), "=f"(d[20]), "=f"(d[21]), "=f"(d[22]), "=f"(d[23]), "=f"(d[24]), "=f"(d[25]), "=f"(d[26]), "=f"(d[27])
        : "l"(descA), "n"(AOFF >> 4), "l"(descB), "n"(BOFF >> 4));
}

template <int AOFF, int BOFF>
__device__ __forceinline__ void mma_qk1(float (&d)[28], uint64_t descA, uint64_t descB) {
    asm volatile(
        "{\n"
        ".reg .pred p0, p1;\n"
        ".reg .b64 ta, ta0, tb, tb0;\n"
        "setp.ne.b32 p0, 0, 0;\n"
        "setp.eq.b32 p1, 0, 0;\n"
        "add.s64 tb0, %30, %31;\n"
        "add.s64 ta0, %28, %29;\n"
        "add.s64 tb, tb0, 6;\n"
        "add.s64 ta, ta0, 2;\n"
        "wgmma.mma_async.sync.aligned.m64n56k16.f32.bf16.bf16 {%0, %1, %2, %3, %4, %5, %6, %7, %8, %9, %10, %11, %12, %13, %14, %15, %16, %17, %18, %19, %20, %21, %22, %23, %24, %25, %26, %27}, ta, tb, p0, 1, 1, 0, 0;\n"
        "add.s64 tb, tb0, 1574;\n"
        "add.s64 ta, ta0, 1570;\n"
        "wgmma.mma_async.sync.aligned.m64n56k16.f32.bf16.bf16 {%0, %1, %2, %3, %4, %5, %6, %7, %8, %9, %10, %11, %12, %13, %14, %15, %16, %17, %18, %19, %20, %21, %22, %23, %24, %25, %26, %27}, ta, tb, p1, 1, 1, 0, 0;\n"
        "add.s64 tb, tb0, 3142;\n"
        "add.s64 ta, ta0, 3138;\n"
        "wgmma.mma_async.sync.aligned.m64n56k16.f32.bf16.bf16 {%0, %1, %2, %3, %4, %5, %6, %7, %8, %9, %10, %11, %12, %13, %14, %15, %16, %17, %18, %19, %20, %21, %22, %23, %24, %25, %26, %27}, ta, tb, p1, 1, 1, 0, 0;\n"
        "}\n"
        : "=f"(d[0]), "=f"(d[1]), "=f"(d[2]), "=f"(d[3]), "=f"(d[4]), "=f"(d[5]), "=f"(d[6]), "=f"(d[7]), "=f"(d[8]), "=f"(d[9]), "=f"(d[10]), "=f"(d[11]), "=f"(d[12]), "=f"(d[13]), "=f"(d[14]), "=f"(d[15]), "=f"(d[16]), "=f"(d[17]), "=f"(d[18]), "=f"(d[19]), "=f"(d[20]), "=f"(d[21]), "=f"(d[22]), "=f"(d[23]), "=f"(d[24]), "=f"(d[25]), "=f"(d[26]), "=f"(d[27])
        : "l"(descA), "n"(AOFF >> 4), "l"(descB), "n"(BOFF >> 4));
}

template <int BOFF, int AOFF, int NA>
__device__ __forceinline__ void mma_pv(float (&d)[28], const uint32_t (&a)[NA][4], uint64_t descB) {
    asm volatile(
        "{\n"
        ".reg .pred p0, p1;\n"
        ".reg .b64 ta, ta0, tb, tb0;\n"
        "setp.ne.b32 p0, 0, 0;\n"
        "setp.eq.b32 p1, 0, 0;\n"
        "add.s64 tb0, %44, %45;\n"
        "add.s64 tb, tb0, 0;\n"
        "wgmma.mma_async.sync.aligned.m64n56k16.f32.bf16.bf16 {%0, %1, %2, %3, %4, %5, %6, %7, %8, %9, %10, %11, %12, %13, %14, %15, %16, %17, %18, %19, %20, %21, %22, %23, %24, %25, %26, %27}, {%28, %29, %30, %31}, tb, p0, 1, 1, 1;\n"
        "add.s64 tb, tb0, 16;\n"
        "wgmma.mma_async.sync.aligned.m64n56k16.f32.bf16.bf16 {%0, %1, %2, %3, %4, %5, %6, %7, %8, %9, %10, %11, %12, %13, %14, %15, %16, %17, %18, %19, %20, %21, %22, %23, %24, %25, %26, %27}, {%32, %33, %34, %35}, tb, p1, 1, 1, 1;\n"
        "add.s64 tb, tb0, 32;\n"
        "wgmma.mma_async.sync.aligned.m64n56k16.f32.bf16.bf16 {%0, %1, %2, %3, %4, %5, %6, %7, %8, %9, %10, %11, %12, %13, %14, %15, %16, %17, %18, %19, %20, %21, %22, %23, %24, %25, %26, %27}, {%36, %37, %38, %39}, tb, p1, 1, 1, 1;\n"
        "add.s64 tb, tb0, 48;\n"
        "wgmma.mma_async.sync.aligned.m64n56k16.f32.bf16.bf16 {%0, %1, %2, %3, %4, %5, %6, %7, %8, %9, %10, %11, %12, %13, %14, %15, %16, %17, %18, %19, %20, %21, %22, %23, %24, %25, %26, %27}, {%40, %41, %42, %43}, tb, p1, 1, 1, 1;\n"
        "}\n"
        : "=f"(d[0]), "=f"(d[1]), "=f"(d[2]), "=f"(d[3]), "=f"(d[4]), "=f"(d[5]), "=f"(d[6]), "=f"(d[7]), "=f"(d[8]), "=f"(d[9]), "=f"(d[10]), "=f"(d[11]), "=f"(d[12]), "=f"(d[13]), "=f"(d[14]), "=f"(d[15]), "=f"(d[16]), "=f"(d[17]), "=f"(d[18]), "=f"(d[19]), "=f"(d[20]), "=f"(d[21]), "=f"(d[22]), "=f"(d[23]), "=f"(d[24]), "=f"(d[25]), "=f"(d[26]), "=f"(d[27])
        : "r"(a[AOFF + 0][0]), "r"(a[AOFF + 0][1]), "r"(a[AOFF + 0][2]), "r"(a[AOFF + 0][3]), "r"(a[AOFF + 1][0]), "r"(a[AOFF + 1][1]), "r"(a[AOFF + 1][2]), "r"(a[AOFF + 1][3]), "r"(a[AOFF + 2][0]), "r"(a[AOFF + 2][1]), "r"(a[AOFF + 2][2]), "r"(a[AOFF + 2][3]), "r"(a[AOFF + 3][0]), "r"(a[AOFF + 3][1]), "r"(a[AOFF + 3][2]), "r"(a[AOFF + 3][3]), "l"(descB), "n"(BOFF >> 4));
}

template <int AOFF, int BOFF>
__device__ __forceinline__ void mma_proj(float (&d)[96], uint64_t descA, uint64_t descB) {
    asm volatile(
        "{\n"
        ".reg .pred p0, p1;\n"
        ".reg .b64 ta, ta0, tb, tb0;\n"
        "setp.ne.b32 p0, 0, 0;\n"
        "setp.eq.b32 p1, 0, 0;\n"
        "add.s64 tb0, %98, %99;\n"
        "add.s64 ta0, %96, %97;\n"
        "add.s64 tb, tb0, 0;\n"
        "add.s64 ta, ta0, 0;\n"
        "wgmma.mma_async.sync.aligned.m64n192k16.f32.bf16.bf16 {%0, %1, %2, %3, %4, %5, %6, %7, %8, %9, %10, %11, %12, %13, %14, %15, %16, %17, %18, %19, %20, %21, %22, %23, %24, %25, %26, %27, %28, %29, %30, %31, %32, %33, %34, %35, %36, %37, %38, %39, %40, %41, %42, %43, %44, %45, %46, %47, %48, %49, %50, %51, %52, %53, %54, %55, %56, %57, %58, %59, %60, %61, %62, %63, %64, %65, %66, %67, %68, %69, %70, %71, %72, %73, %74, %75, %76, %77, %78, %79, %80, %81, %82, %83, %84, %85, %86, %87, %88, %89, %90, %91, %92, %93, %94, %95}, ta, tb, p0, 1, 1, 0, 1;\n"
        "add.s64 tb, tb0, 64;\n"
        "add.s64 ta, ta0, 2;\n"
        "wgmma.mma_async.sync.aligned.m64n192k16.f32.bf16.bf16 {%0, %1, %2, %3, %4, %5, %6, %7, %8, %9, %10, %11, %12, %13, %14, %15, %16, %17, %18, %19, %20, %21, %22, %23, %24, %25, %26, %27, %28, %29, %30, %31, %32, %33, %34, %35, %36, %37, %38, %39, %40, %41, %42, %43, %44, %45, %46, %47, %48, %49, %50, %51, %52, %53, %54, %55, %56, %57, %58, %59, %60, %61, %62, %63, %64, %65, %66, %67, %68, %69, %70, %71, %72, %73, %74, %75, %76, %77, %78, %79, %80, %81, %82, %83, %84, %85, %86, %87, %88, %89, %90, %91, %92, %93, %94, %95}, ta, tb, p1, 1, 1, 0, 1;\n"
        "add.s64 tb, tb0, 128;\n"
        "add.s64 ta, ta0, 4;\n"
        "wgmma.mma_async.sync.aligned.m64n192k16.f32.bf16.bf16 {%0, %1, %2, %3, %4, %5, %6, %7, %8, %9, %10, %11, %12, %13, %14, %15, %16, %17, %18, %19, %20, %21, %22, %23, %24, %25, %26, %27, %28, %29, %30, %31, %32, %33, %34, %35, %36, %37, %38, %39, %40, %41, %42, %43, %44, %45, %46, %47, %48, %49, %50, %51, %52, %53, %54, %55, %56, %57, %58, %59, %60, %61, %62, %63, %64, %65, %66, %67, %68, %69, %70, %71, %72, %73, %74, %75, %76, %77, %78, %79, %80, %81, %82, %83, %84, %85, %86, %87, %88, %89, %90, %91, %92, %93, %94, %95}, ta, tb, p1, 1, 1, 0, 1;\n"
        "add.s64 tb, tb0, 192;\n"
        "add.s64 ta, ta0, 6;\n"
        "wgmma.mma_async.sync.aligned.m64n192k16.f32.bf16.bf16 {%0, %1, %2, %3, %4, %5, %6, %7, %8, %9, %10, %11, %12, %13, %14, %15, %16, %17, %18, %19, %20, %21, %22, %23, %24, %25, %26, %27, %28, %29, %30, %31, %32, %33, %34, %35, %36, %37, %38, %39, %40, %41, %42, %43, %44, %45, %46, %47, %48, %49, %50, %51, %52, %53, %54, %55, %56, %57, %58, %59, %60, %61, %62, %63, %64, %65, %66, %67, %68, %69, %70, %71, %72, %73, %74, %75, %76, %77, %78, %79, %80, %81, %82, %83, %84, %85, %86, %87, %88, %89, %90, %91, %92, %93, %94, %95}, ta, tb, p1, 1, 1, 0, 1;\n"
        "add.s64 tb, tb0, 256;\n"
        "add.s64 ta, ta0, 512;\n"
        "wgmma.mma_async.sync.aligned.m64n192k16.f32.bf16.bf16 {%0, %1, %2, %3, %4, %5, %6, %7, %8, %9, %10, %11, %12, %13, %14, %15, %16, %17, %18, %19, %20, %21, %22, %23, %24, %25, %26, %27, %28, %29, %30, %31, %32, %33, %34, %35, %36, %37, %38, %39, %40, %41, %42, %43, %44, %45, %46, %47, %48, %49, %50, %51, %52, %53, %54, %55, %56, %57, %58, %59, %60, %61, %62, %63, %64, %65, %66, %67, %68, %69, %70, %71, %72, %73, %74, %75, %76, %77, %78, %79, %80, %81, %82, %83, %84, %85, %86, %87, %88, %89, %90, %91, %92, %93, %94, %95}, ta, tb, p1, 1, 1, 0, 1;\n"
        "add.s64 tb, tb0, 320;\n"
        "add.s64 ta, ta0, 514;\n"
        "wgmma.mma_async.sync.aligned.m64n192k16.f32.bf16.bf16 {%0, %1, %2, %3, %4, %5, %6, %7, %8, %9, %10, %11, %12, %13, %14, %15, %16, %17, %18, %19, %20, %21, %22, %23, %24, %25, %26, %27, %28, %29, %30, %31, %32, %33, %34, %35, %36, %37, %38, %39, %40, %41, %42, %43, %44, %45, %46, %47, %48, %49, %50, %51, %52, %53, %54, %55, %56, %57, %58, %59, %60, %61, %62, %63, %64, %65, %66, %67, %68, %69, %70, %71, %72, %73, %74, %75, %76, %77, %78, %79, %80, %81, %82, %83, %84, %85, %86, %87, %88, %89, %90, %91, %92, %93, %94, %95}, ta, tb, p1, 1, 1, 0, 1;\n"
        "add.s64 tb, tb0, 384;\n"
        "add.s64 ta, ta0, 516;\n"
        "wgmma.mma_async.sync.aligned.m64n192k16.f32.bf16.bf16 {%0, %1, %2, %3, %4, %5, %6, %7, %8, %9, %10, %11, %12, %13, %14, %15, %16, %17, %18, %19, %20, %21, %22, %23, %24, %25, %26, %27, %28, %29, %30, %31, %32, %33, %34, %35, %36, %37, %38, %39, %40, %41, %42, %43, %44, %45, %46, %47, %48, %49, %50, %51, %52, %53, %54, %55, %56, %57, %58, %59, %60, %61, %62, %63, %64, %65, %66, %67, %68, %69, %70, %71, %72, %73, %74, %75, %76, %77, %78, %79, %80, %81, %82, %83, %84, %85, %86, %87, %88, %89, %90, %91, %92, %93, %94, %95}, ta, tb, p1, 1, 1, 0, 1;\n"
        "add.s64 tb, tb0, 448;\n"
        "add.s64 ta, ta0, 518;\n"
        "wgmma.mma_async.sync.aligned.m64n192k16.f32.bf16.bf16 {%0, %1, %2, %3, %4, %5, %6, %7, %8, %9, %10, %11, %12, %13, %14, %15, %16, %17, %18, %19, %20, %21, %22, %23, %24, %25, %26, %27, %28, %29, %30, %31, %32, %33, %34, %35, %36, %37, %38, %39, %40, %41, %42, %43, %44, %45, %46, %47, %48, %49, %50, %51, %52, %53, %54, %55, %56, %57, %58, %59, %60, %61, %62, %63, %64, %65, %66, %67, %68, %69, %70, %71, %72, %73, %74, %75, %76, %77, %78, %79, %80, %81, %82, %83, %84, %85, %86, %87, %88, %89, %90, %91, %92, %93, %94, %95}, ta, tb, p1, 1, 1, 0, 1;\n"
        "add.s64 tb, tb0, 512;\n"
        "add.s64 ta, ta0, 1024;\n"
        "wgmma.mma_async.sync.aligned.m64n192k16.f32.bf16.bf16 {%0, %1, %2, %3, %4, %5, %6, %7, %8, %9, %10, %11, %12, %13, %14, %15, %16, %17, %18, %19, %20, %21, %22, %23, %24, %25, %26, %27, %28, %29, %30, %31, %32, %33, %34, %35, %36, %37, %38, %39, %40, %41, %42, %43, %44, %45, %46, %47, %48, %49, %50, %51, %52, %53, %54, %55, %56, %57, %58, %59, %60, %61, %62, %63, %64, %65, %66, %67, %68, %69, %70, %71, %72, %73, %74, %75, %76, %77, %78, %79, %80, %81, %82, %83, %84, %85, %86, %87, %88, %89, %90, %91, %92, %93, %94, %95}, ta, tb, p1, 1, 1, 0, 1;\n"
        "add.s64 tb, tb0, 576;\n"
        "add.s64 ta, ta0, 1026;\n"
        "wgmma.mma_async.sync.aligned.m64n192k16.f32.bf16.bf16 {%0, %1, %2, %3, %4, %5, %6, %7, %8, %9, %10, %11, %12, %13, %14, %15, %16, %17, %18, %19, %20, %21, %22, %23, %24, %25, %26, %27, %28, %29, %30, %31, %32, %33, %34, %35, %36, %37, %38, %39, %40, %41, %42, %43, %44, %45, %46, %47, %48, %49, %50, %51, %52, %53, %54, %55, %56, %57, %58, %59, %60, %61, %62, %63, %64, %65, %66, %67, %68, %69, %70, %71, %72, %73, %74, %75, %76, %77, %78, %79, %80, %81, %82, %83, %84, %85, %86, %87, %88, %89, %90, %91, %92, %93, %94, %95}, ta, tb, p1, 1, 1, 0, 1;\n"
        "add.s64 tb, tb0, 640;\n"
        "add.s64 ta, ta0, 1028;\n"
        "wgmma.mma_async.sync.aligned.m64n192k16.f32.bf16.bf16 {%0, %1, %2, %3, %4, %5, %6, %7, %8, %9, %10, %11, %12, %13, %14, %15, %16, %17, %18, %19, %20, %21, %22, %23, %24, %25, %26, %27, %28, %29, %30, %31, %32, %33, %34, %35, %36, %37, %38, %39, %40, %41, %42, %43, %44, %45, %46, %47, %48, %49, %50, %51, %52, %53, %54, %55, %56, %57, %58, %59, %60, %61, %62, %63, %64, %65, %66, %67, %68, %69, %70, %71, %72, %73, %74, %75, %76, %77, %78, %79, %80, %81, %82, %83, %84, %85, %86, %87, %88, %89, %90, %91, %92, %93, %94, %95}, ta, tb, p1, 1, 1, 0, 1;\n"
        "add.s64 tb, tb0, 704;\n"
        "add.s64 ta, ta0, 1030;\n"
        "wgmma.mma_async.sync.aligned.m64n192k16.f32.bf16.bf16 {%0, %1, %2, %3, %4, %5, %6, %7, %8, %9, %10, %11, %12, %13, %14, %15, %16, %17, %18, %19, %20, %21, %22, %23, %24, %25, %26, %27, %28, %29, %30, %31, %32, %33, %34, %35, %36, %37, %38, %39, %40, %41, %42, %43, %44, %45, %46, %47, %48, %49, %50, %51, %52, %53, %54, %55, %56, %57, %58, %59, %60, %61, %62, %63, %64, %65, %66, %67, %68, %69, %70, %71, %72, %73, %74, %75, %76, %77, %78, %79, %80, %81, %82, %83, %84, %85, %86, %87, %88, %89, %90, %91, %92, %93, %94, %95}, ta, tb, p1, 1, 1, 0, 1;\n"
        "}\n"
        : "+f"(d[0]), "+f"(d[1]), "+f"(d[2]), "+f"(d[3]), "+f"(d[4]), "+f"(d[5]), "+f"(d[6]), "+f"(d[7]), "+f"(d[8]), "+f"(d[9]), "+f"(d[10]), "+f"(d[11]), "+f"(d[12]), "+f"(d[13]), "+f"(d[14]), "+f"(d[15]), "+f"(d[16]), "+f"(d[17]), "+f"(d[18]), "+f"(d[19]), "+f"(d[20]), "+f"(d[21]), "+f"(d[22]), "+f"(d[23]), "+f"(d[24]), "+f"(d[25]), "+f"(d[26]), "+f"(d[27]), "+f"(d[28]), "+f"(d[29]), "+f"(d[30]), "+f"(d[31]), "+f"(d[32]), "+f"(d[33]), "+f"(d[34]), "+f"(d[35]), "+f"(d[36]), "+f"(d[37]), "+f"(d[38]), "+f"(d[39]), "+f"(d[40]), "+f"(d[41]), "+f"(d[42]), "+f"(d[43]), "+f"(d[44]), "+f"(d[45]), "+f"(d[46]), "+f"(d[47]), "+f"(d[48]), "+f"(d[49]), "+f"(d[50]), "+f"(d[51]), "+f"(d[52]), "+f"(d[53]), "+f"(d[54]), "+f"(d[55]), "+f"(d[56]), "+f"(d[57]), "+f"(d[58]), "+f"(d[59]), "+f"(d[60]), "+f"(d[61]), "+f"(d[62]), "+f"(d[63]), "+f"(d[64]), "+f"(d[65]), "+f"(d[66]), "+f"(d[67]), "+f"(d[68]), "+f"(d[69]), "+f"(d[70]), "+f"(d[71]), "+f"(d[72]), "+f"(d[73]), "+f"(d[74]), "+f"(d[75]), "+f"(d[76]), "+f"(d[77]), "+f"(d[78]), "+f"(d[79]), "+f"(d[80]), "+f"(d[81]), "+f"(d[82]), "+f"(d[83]), "+f"(d[84]), "+f"(d[85]), "+f"(d[86]), "+f"(d[87]), "+f"(d[88]), "+f"(d[89]), "+f"(d[90]), "+f"(d[91]), "+f"(d[92]), "+f"(d[93]), "+f"(d[94]), "+f"(d[95])
        : "l"(descA), "n"(AOFF >> 4), "l"(descB), "n"(BOFF >> 4));
}

struct Params {
    const __nv_bfloat16* x;
    const __nv_bfloat16* wqkv;
    const __nv_bfloat16* wo;
    const __nv_bfloat16* logit_scale;
    const __nv_bfloat16* cpb_w1;
    const __nv_bfloat16* cpb_w2;
    const __nv_bfloat16* rel_coords;
    const int*           rel_idx;
    const __nv_bfloat16* mask;
    __nv_bfloat16*       out;
    unsigned long long   z1;
    int                  npair;
    uint32_t             need;
    int                  nq, nr;
    int                  nr2, nt0, nt1;
    int                  t1;
};

struct Maps {
    CUtensorMap x77, x47, x37, x44, x43, x34, x33;
    CUtensorMap w64, w32, w;
    CUtensorMap s47, s37, s43, s33;
    CUtensorMap o, ob;
};

__device__ __forceinline__ uint32_t row_token(uint32_t r) {
    return r < 28 ? r + 3 * (r >> 2) : r - 24 + 4 * (((r - 28) * 11) >> 5);
}
__device__ __forceinline__ int unrot(int r) { return r ? r - 1 : NWS - 1; }
__device__ __forceinline__ void finish(uint32_t total) {
    __threadfence();
    if (atomicAdd(&g_done, 1u) == total - 1) {
        for (int i = 0; i <= NWS; i++) g_cnt[i] = 0;
        g_done = 0;
    }
}

__global__ void __launch_bounds__(NTHREADS, 1)
swin_window_attn_kernel(const Params P, const __grid_constant__ Maps M) {
    const CUtensorMap &xmap = M.x77, &omap = M.o, &omapb = M.ob, &wmap = M.w;
    extern __shared__ __align__(1024) uint8_t smem[];
    constexpr uint32_t sbase = 1024;
    if (smem_u32(smem) != sbase) return;
    const int tid = threadIdx.x;
    const int wg = __shfl_sync(0xffffffffu, tid >> 7, 0);
    const int warp = __shfl_sync(0xffffffffu, (tid >> 5) & 3, 0);
    const int lane = tid & 31;
    const int g = lane >> 2, c = lane & 3;

    TR(26, wg);
    TP(wg);
    if (tid == 0) TC(0);
    const bool attn = (int)blockIdx.x < 2 * P.npair;
    const int pair = blockIdx.x >> 1, half = blockIdx.x & 1;
    const int nwin = P.nq + (pair < P.nr ? 1 : 0);
    const int ntiles = (nwin * TOK + 63) >> 6;
    const uint32_t bars = sbase + SM_BAR;
    auto load_x = [&](uint32_t dst, uint32_t bar, uint32_t bar2, int wh, int ww) {
        const int x0 = 7 * ww + 3, y0 = 7 * wh + 3, x1 = ww == NWS - 1 ? 0 : x0 + 4;
        if (wh < NWS - 1) {
#pragma unroll
            for (int ch = 0; ch < 3; ch++) tma_3d_x(dst + ch * QK_CHUNK, &M.x47, bar, ch * 64, x0, y0);
#pragma unroll
            for (int ch = 0; ch < 3; ch++) tma_3d_x(dst + ch * QK_CHUNK + 28 * 128, &M.x37, bar2, ch * 64, x1, y0);
        } else {
#pragma unroll
            for (int ch = 0; ch < 3; ch++) {
                tma_3d_x(dst + ch * QK_CHUNK, &M.x44, bar, ch * 64, x0, y0);
                tma_3d_x(dst + ch * QK_CHUNK + 16 * 128, &M.x43, bar, ch * 64, x0, 0);
            }
#pragma unroll
            for (int ch = 0; ch < 3; ch++) {
                tma_3d_x(dst + ch * QK_CHUNK + 28 * 128, &M.x34, bar2, ch * 64, x1, y0);
                tma_3d_x(dst + ch * QK_CHUNK + 40 * 128, &M.x33, bar2, ch * 64, x1, 0);
            }
        }
    };
    uint32_t ls = 0;
    if (wg == 0) {
        TP(28);
        if (attn && warp < (WSEQ ? 1 : 3) && elect_one()) {
#pragma unroll
            for (int i = 0; i < (WSEQ ? 3 : 1); i++) mbar_init(bars + B_WRAW + 16 - 8 * (warp + i), 1);
            fence_async_smem();
            TP(29);
#pragma unroll 1
            for (int i = warp; i < warp + (WSEQ ? 3 : 1); i++) {
                const uint32_t bar = bars + B_WRAW + 16 - 8 * i, dst = sbase + i * 24576;
                mbar_arrive_expect_tx(bar, 24576);
                tma_3d(dst, &M.w64, bar, half * 128, 64 * i, 0);
                tma_3d(dst + 16384, &M.w32, bar, 64 + half * 32, 64 * i, 0);
            }
            TP(30);
        }
        __syncwarp();
        if (WFIRST && warp == 0) asm volatile("bar.arrive 3, 96;\n" ::: "memory");
        if (attn) asm volatile("ld.global.nc.u16 %0, [%1];\n" : "=r"(ls) : "l"(P.logit_scale + 2 * half + (c & 1)));
    } else if (wg == 3) {
        if (warp == 3) {
            if (elect_one()) {
#pragma unroll
                for (int i = 0; i < 6; i++)
                    asm volatile("prefetch.tensormap [%0];\n" :: "l"(reinterpret_cast<uint64_t>(&M.x44 + (i < 4 ? i : i - 6))) : "memory");
            }
            if (attn)
#pragma unroll
                for (int i = 0; i < 4; i++) sts128(sbase + SM_V + i * V_STRIDE + (lane < 16 ? lane * 16 : V_STRIDE - 64 + (lane & 3) * 16), 0, 0, 0, 0);
            sts32(sbase + SM_FLAG + lane * 4, 0);
            fence_async_smem();
            asm volatile("bar.arrive 0, 256;\nbar.arrive 11, 384;\n" ::: "memory");
        } else if (warp != 1) {
            if (tid == 384) {
                for (int b = 0; b < 4; b++) mbar_init(bars + B_XFULL + b * 8, 2);
                asm volatile("mbarrier.expect_tx.relaxed.cta.shared::cta.b64 [%0], %1;\n" :: "r"(bars + B_XFULL + 8), "r"(3 * 21 * 128) : "memory");
                fence_async_smem();
            }
            __syncwarp();
            asm volatile("bar.arrive 0, 256;\nbar.arrive 11, 384;\n" ::: "memory");
            nb_sync<WFIRST ? 96 : 64>(3);
            if (attn && elect_one()) {
                const int j = warp >> 1, q = pair + j * P.npair, r = q >= NWS;
                mbar_arrive_expect_tx(bars + B_XFULL, j ? 3 * 28 * 128 : 3 * XCH);
                load_x(sbase + SM_QK + j * XCH, bars + B_XFULL, bars + B_XFULL + j * 8, unrot(r), unrot(q - r * NWS));
                TP(26 + j);
            }
            __syncwarp();
        } else {
            if (lane == 0) {
                for (int b = 0; b < 4; b++) {
                    mbar_init(bars + B_QKRAW + b * 8, 4);
                    mbar_init(bars + B_VRAW + b * 8, 4);
                    mbar_init(bars + B_VFREE + b * 8, 2);
                    mbar_init(bars + B_QKFREE + b * 8, (NB & 1) ? 1 : 4);
                    mbar_init(bars + B_ODONE + b * 8, 4);
                }
                mbar_init(bars + B_WFULL, 1);
                mbar_init(bars + B_MFULL, 1);
                mbar_init(bars + B_MCONS, 4);
                sts32(bars + B_PROG, 0);
                for (int b = 0; b < 4; b++) mbar_init(bars + B_STORED + b * 8, 1);
                for (int b = 0; b < 6; b++) {
                    mbar_init(sbase + SM_PBAR + b * 8, 1);
                    mbar_init(sbase + SM_PBAR + 48 + b * 8, PSTORE ? 1 : 4);
                    mbar_init(sbase + SM_PBAR + 104 + b * 8, 4);
                }
                mbar_init(sbase + SM_PBAR + 96, 13);
                fence_async_smem();
            }
            __syncwarp();
            TP(19);
            asm volatile("bar.arrive 0, 256;\nbar.arrive 11, 384;\n" ::: "memory");
        }
        asm volatile("bar.sync 2, 128;\n" ::: "memory");
        if (warp == 3 && lane < 8)
            asm volatile("prefetch.tensormap [%0];\n" :: "l"(reinterpret_cast<uint64_t>(&M.x77 + (lane ? lane + 8 : 0))) : "memory");
        TP(13);
    }
    uint32_t ridx[26];
    uint32_t rc, w2[16];
    uint4 w1[4];
    if (attn && (wg == 1 || wg == 2)) {
        rc = reinterpret_cast<const uint32_t*>(P.rel_coords)[min(tid - 128, 168)];
#pragma unroll
        for (int i = 0; i < 4; i++) w1[i] = reinterpret_cast<const uint4*>(P.cpb_w1)[i];
#pragma unroll
        for (int u = 0; u < 16; u++) w2[u] = reinterpret_cast<const uint32_t*>(P.cpb_w2)[2 * u + half];
        ls = reinterpret_cast<const uint32_t*>(P.logit_scale)[half];
        asm volatile("" ::: "memory");
        uint32_t col[7];
#pragma unroll
        for (int j = 0; j < 7; j++) {
            const uint32_t n = j ? 8 * ((j + 5) >> 1) + ((j + 1) & 1) : 0;
            col[j] = prmt(0, row_token(n) | row_token(n + 2) << 8 | row_token(n + 4) << 16 | row_token(n + 6) << 24, 4 + c);
        }
#pragma unroll
        for (int rh = 0; rh < 2; rh++) {
            const uint32_t* ri = reinterpret_cast<const uint32_t*>(P.rel_idx) + row_token(min(warp * 16 + g + 8 * rh, TOK - 1)) * TOK;
            asm volatile("" : "+l"(ri));
#pragma unroll
            for (int j = 0; j < 12; j++) ridx[13 * rh + j] = j < 6 ? (ri + col[0])[14 * (j >> 1) + (j & 1)] : ri[col[j - 5]];
            ridx[13 * rh + 12] = ri[48];
        }
    }
    if (wg == 1) TP(31);
    if (wg == 0) asm volatile("bar.sync 0, 256;\n" ::: "memory");
    else if (wg < 3) asm volatile("bar.sync 11, 384;\n" ::: "memory");
    TP(4 + wg);

    const uint32_t nfinish = gridDim.x + 4 * P.npair;
#define PROJ_SCHEDULE                                                                                   \
    int bid = blockIdx.x;                                                                               \
    asm volatile("" : "+r"(bid));                      \
    const bool at = bid < 2 * P.npair;                                                                  \
    const int tile0 = at ? P.t1 + 2 * P.npair - 1 - bid : bid - 2 * P.npair;                                              \
    const int tstep = at ? 2 * P.npair : (int)gridDim.x - 2 * P.npair;                                  \
    const int tend = at ? TILES : P.t1;
    if (wg == 3) {
        asm volatile("setmaxnreg.dec.sync.aligned.u32 %0;\n" :: "n"(REG_H));
        if (attn && warp == 1 && !(XP & 1)) {
            uint32_t fph = 0, cph = 0, mis;
            auto load = [&](int k) {
                const int wi = pair + k * P.npair, wr = wi / NWS;
                const uint32_t off = (uint32_t)(unrot(wr) * NWS + unrot(wi - wr * NWS)) * 4802u;
                mis = off & 15;
                if (elect_one()) {
                    uint32_t bytes = 4816;
                    if (wi == 0) {
                        bytes = 4800;
                        asm volatile("st.shared.u16 [%0], %1;\n" :: "r"(sbase + SM_MASK + 4800),
                                     "h"(reinterpret_cast<const uint16_t*>(P.mask)[NWINDOWS * TOK * TOK - 1]) : "memory");
                    }
                    mbar_arrive_expect_tx(bars + B_MFULL, bytes);
                    asm volatile("cp.async.bulk.shared::cluster.global.mbarrier::complete_tx::bytes.L2::cache_hint [%0], [%1], %2, [%3], %4;\n"
                                 :: "r"(sbase + SM_MASK), "l"(reinterpret_cast<const char*>(P.mask) + (off - mis)),
                                    "r"(bytes), "r"(bars + B_MFULL), "l"(EVICT_FIRST) : "memory");
                }
            };
            auto landed = [&]() {
                mbar_wait(bars + B_MFULL, fph);
                fph ^= 1;
            };
            auto flag = [&](int k, uint32_t f) {
                asm volatile("st.volatile.shared.u8 [%0], %1;\n" :: "r"(sbase + SM_FLAG + k), "r"(f) : "memory");
                TR(18, k);
                if (k < 2) TP(14 + k);
            };
            if (MWAIT) mbar_wait(bars + B_XFULL, 0);
            load(2 + half);
            if (MPRE && elect_one()) {
                const int wi = pair + half * P.npair, wr = wi / NWS;
                const uint32_t off = (uint32_t)(unrot(wr) * NWS + unrot(wi - wr * NWS)) * 4802u;
                asm volatile("cp.async.bulk.prefetch.L2.global [%0], 4800;\n" :: "l"(reinterpret_cast<const char*>(P.mask) + (off & ~15u)) : "memory");
            }
            uint32_t todo = 3;
            int sp = 0;
#pragma unroll 1
            for (int k = 2 + half; sp < nwin; k += 2) {
                if (k < nwin) {
#pragma unroll 1
                    for (uint32_t n = 0; n < (1u << 22); n++) {
                        int done;
                        asm volatile("ld.volatile.shared.b32 %0, [%1];\n" : "=r"(done) : "r"(bars + B_PROG) : "memory");
                        if (done >= (k + 2 < nwin ? k - MLEAD : k - 3)) break;
                        __nanosleep(PSLEEP);
                    }
                    landed();
                    TR(17, k);
                    uint32_t any;
                    asm volatile("ld.shared.u16 %0, [%1];\n" : "=r"(any)
                                 : "r"(sbase + SM_MASK + mis + ((lane & 8) ? 4800 - 14 : 0) + (lane & 7) * 2) : "memory");
#pragma unroll
                    for (int i = 0; i < 10; i++) {
                        uint32_t v[4];
                        asm volatile("ld.shared.v4.b32 {%0, %1, %2, %3}, [%4];\n" : "=r"(v[0]), "=r"(v[1]), "=r"(v[2]), "=r"(v[3])
                                     : "r"(sbase + SM_MASK + lane * 16 + (i < 9 ? 16 + i * 512 : 4800 - 512)) : "memory");
                        any |= (v[0] | v[1]) | (v[2] | v[3]);
                    }
                    const uint32_t masked = __any_sync(0xffffffffu, any & 0x7FFF7FFFu);
                    asm volatile("st.relaxed.gpu.global.u32 [%0], %1;\n" :: "l"(g_flag + pair * 128 + k), "r"(1 + masked) : "memory");
                    if (masked) todo |= 1u << (k - sp);
                    else flag(k, 1);
                }
                if (k > 2 && k <= nwin) {
                    uint32_t f;
#pragma unroll 1
                    for (uint32_t n = 0; n < (1u << 22); n++) {
                        asm volatile("ld.relaxed.gpu.global.u32 %0, [%1];\n" : "=r"(f) : "l"(g_flag + pair * 128 + k - 1) : "memory");
                        if (__all_sync(0xffffffffu, f)) break;
                        __nanosleep(PSLEEP);
                    }
                    g_flag[pair * 128 + k - 1] = 0;
                    if (f != 1) todo |= 1u << (k - 1 - sp);
                    else flag(k - 1, 1);
                }
#pragma unroll 1
                for (; sp < k; sp++, todo >>= 1)
                    if (todo & 1) {
                        load(sp);
                        landed();
                        __threadfence_block();
                        flag(sp, 2);
                        mbar_wait(bars + B_MCONS, cph);
                        cph ^= 1;
                        fence_async_smem();
                    }
                if (k + 2 < nwin) load(k + 2);
            }
        }
        if (!elect_one()) return;
        if (warp == 0) {
          if (attn) {
            const int kmax = (64 * ntiles + 63) / TOK;
            int wr = 0, wq = pair;
            int pr2 = (pair + PF_DIST * P.npair) / NWS, pq2 = pair + PF_DIST * P.npair - pr2 * NWS;
#pragma unroll 1
            for (int k = -4; k + 4 <= kmax; k++) {
                const int row0 = (k + 4) * TOK;
                const uint32_t dst = sbase + SM_QK + (k & 3) * XCH, bar = bars + B_XFULL + ((row0 >> 6) & 3) * 8;
                const bool alone = (row0 & 63) >= 64 - TOK && (row0 & 63) < TOK;
                const int wh = unrot(wr), ww = unrot(wq), ph2 = unrot(pr2), pw2 = unrot(pq2);
                const bool done = k < -2;
                if (k == WVK) {
                    TP(24);
                    mbar_arrive_expect_tx(bars + B_WFULL, 6 * W_ATOM);
                    tma_3d(sbase + SM_WV, &wmap, bars + B_WFULL, 0, 0, 24 + half * 6);
                }
                if (NB & 1) {
                    if (k >= 0) nb_sync<160>(NB_QKFREE + (k & 1));
                } else mbar_wait(bars + B_QKFREE + (k & 3) * 8, (k >> 2) & 1);
                if (alone && !done) mbar_arrive(bar);
                if (k + 4 >= nwin) {
                    mbar_arrive(bar);
                    continue;
                }
                TR(20, k + 4);
                if (k < 0) TP(44 + k);
                if (!done) {
                    uint32_t bar2 = bar;
                    if ((row0 & 63) >= 64 - 28) {
                        bar2 = bars + B_XFULL + (((row0 >> 6) + 1) & 3) * 8;
                        asm volatile("mbarrier.expect_tx.relaxed.cta.shared::cta.b64 [%0], %1;\n" :: "r"(bar2), "r"(3 * 21 * 128) : "memory");
                    }
                    mbar_arrive_expect_tx(bar, bar2 != bar ? 3 * 28 * 128 : 3 * XCH);
                    load_x(dst, bar, bar2, wh, ww);
                }
                asm volatile("st.volatile.shared.b32 [%0], %1;\n" :: "r"(bars + B_PROG), "r"(max(k + 1, 0)) : "memory");
                if (NOPF) {
                } else if (PFM == 2) {
                    if (pr2 < NWS && half == 0) {
                        const char* xp = reinterpret_cast<const char*>(P.x) + (size_t)((7 * ph2 + 3) * IMG + 7 * pw2 + 3) * 384;
#pragma unroll 1
                        for (int r = 0; r < (ph2 == NWS - 1 ? 3 : 7); r++)
                            asm volatile("cp.async.bulk.prefetch.L2.global [%0], 2688;\n" :: "l"(xp + r * (IMG * 384)) : "memory");
                    }
                } else if (PFM == 1 ? ((k ^ half) & 1) : PFM == 4 ? half == 1 : PFM == 5 ? 1 : half == 0) {
                    if (pr2 < NWS) {
#pragma unroll
                        for (int ch = 0; ch < (PF1 ? 1 : 3); ch++)
                            if (CH & 8)
                            asm volatile("cp.async.bulk.prefetch.tensor.3d.L2.global.tile.L2::cache_hint [%0, {%1, %2, %3}], %4;\n"
                                         :: "l"(reinterpret_cast<uint64_t>(&xmap)), "r"(ch * 64), "r"(7 * pw2 + 3), "r"(7 * ph2 + 3), "l"(EVICT_FIRST)
                                         : "memory");
                            else
                            asm volatile("cp.async.bulk.prefetch.tensor.3d.L2.global.tile [%0, {%1, %2, %3}];\n"
                                         :: "l"(reinterpret_cast<uint64_t>(&xmap)), "r"(ch * 64), "r"(7 * pw2 + 3), "r"(7 * ph2 + 3)
                                         : "memory");
                    }
                }
                wq += P.npair; if (wq >= NWS) { wq -= NWS; wr++; }
                pq2 += P.npair; if (pq2 >= NWS) { pq2 -= NWS; pr2++; }
            }
            mbar_wait(bars + B_VRAW + ((ntiles - 1) & 3) * 8, ((ntiles - 1) >> 2) & 1);
          }
            PROJ_SCHEDULE
            int st = 0, ready = -1;
            uint32_t ph = 1;
#pragma unroll 1
            for (int t = tile0; t < tend; t += tstep) {
                const int p0 = (t < TILES_A) ? SEG_B + 64 * t : 64 * (t - TILES_A);
                const int w1 = (t < TILES_A) ? 0 : min((p0 + 63 + 4 * IMG) / (7 * IMG), NWS - 1);
                if (at && t == tile0 + tstep) {
                    mbar_wait(sbase + SM_PBAR + 96, 0);
                    fence_async_smem();
                }
                if (ready < w1) {
                    ready = max(ready, w1 - 2);
#pragma unroll 1
                    while (ready < w1) {
                        ready++;
#pragma unroll 1
                        for (uint32_t n = 0; n < (1u << 22); n++) {
                            uint32_t a;
                            asm volatile("ld.acquire.gpu.global.u32 %0, [%1];\n" : "=r"(a) : "l"(g_cnt + ready) : "memory");
                            if (a >= P.need) break;
                            __nanosleep(64);
                        }
                    }
                    asm volatile("fence.proxy.async.global;\n" ::: "memory");
                }
                TRH(9, (t - tile0) / tstep);
                mbar_wait(sbase + SM_PBAR + 48 + st * 8, ph);
                TRH(5, (t - tile0) / tstep);
                if (PEXP & 2) mbar_arrive(sbase + SM_PBAR + st * 8); else {
                mbar_arrive_expect_tx(sbase + SM_PBAR + st * 8, STAGE_BYTES);
#pragma unroll
                for (int ch = 0; ch < 3; ch++)
                    tma_2d(sbase + SM_STAGE + st * STAGE_BYTES + ch * 8192, &omap, sbase + SM_PBAR + st * 8, ch * 64, (PEXP & 4) ? p0 & 8191 : p0);
                }
                if (++st == 6) { st = 0; ph ^= 1; }
            }
            finish(nfinish);
        } else if (!attn) {
        } else if (warp == 1) {
          {
            if (P.t1 < TILES) {
#pragma unroll 1
                for (uint32_t n = 0; n < (1u << 22); n++) {
                    uint32_t a;
                    asm volatile("ld.acquire.gpu.global.u32 %0, [%1];\n" : "=r"(a) : "l"(g_cnt + NWS) : "memory");
                    if (a) break;
                    __nanosleep(64);
                }
                asm volatile("fence.proxy.async.global;\n" ::: "memory");
                if (blockIdx.x % 6 == 0)
                    asm volatile("cp.async.bulk.prefetch.L2.global [%0], 4096;\n" :: "l"(g_wo + blockIdx.x / 6 % 18 * 4096) : "memory");
                if (NB & 4) mbar_wait(bars + B_QKRAW, 0);
                else mbar_wait(bars + B_QKRAW + ((ntiles - 1) & 3) * 8, ((ntiles - 1) >> 2) & 1);
                mbar_arrive_expect_tx(bars + B_WRAW, 73728);
#pragma unroll
                for (int i = 0; i < 4; i++) {
                    const uint32_t o = ((i + pair) & 3) * 18432;
                    asm volatile("cp.async.bulk.shared::cluster.global.mbarrier::complete_tx::bytes [%0], [%1], 18432, [%2];\n"
                                 :: "r"(sbase + SM_WO + o), "l"(g_wo + o), "r"(bars + B_WRAW) : "memory");
                }
            }
            finish(nfinish);
          }
        } else if (warp == 2) {
            int wh = 0, ww = pair;
#pragma unroll 1
            for (int k = 0; k < nwin; k++) {
                mbar_wait(bars + B_STORED + (k & 1) * 8, (k >> 1) & 1);
                mbar_arrive(bars + B_PUBD + (k & 1) * 8);
                asm volatile("red.release.gpu.global.add.u32 [%0], 1;\n" :: "l"(g_cnt + wh) : "memory");
                TR(24, k);
                TS(k & 127);
                if (k == nwin - 1) TC(7);
                ww += P.npair; if (ww >= NWS) { ww -= NWS; wh++; }
            }
            finish(nfinish);
        } else {
            for (int t = 0; t < 2; t++) mbar_arrive_n(bars + B_VFREE + t * 8, 2);
            int wr = 0, wq = pair;
#pragma unroll 1
            for (int k = 0; k < nwin; k++) {
                const uint32_t src = sbase + SM_V + (k & 3) * V_STRIDE;
                const int wh = unrot(wr), ww = unrot(wq);
                const int x0 = 7 * ww + 3, y0 = 7 * wh + 3;
                if (NB & 2) nb_sync<160>(NB_ODONE + (k & 3));
                else mbar_wait(bars + B_ODONE + (k & 3) * 8, (k >> 2) & 1);
                fence_async_smem();
                TR(22, k);
                const int x1 = ww == NWS - 1 ? 0 : x0 + 4;
                if (!(XP & 2)) tma_store_4d(&M.s47, src, 0, half, x0, y0);
                if (!(XP & 2)) tma_store_4d(&M.s37, src + 28 * O_PITCH, 0, half, x1, y0);
                if (wh == NWS - 1) {
                    tma_store_4d(&M.s43, src + 16 * O_PITCH, 0, half, x0, 0);
                    tma_store_4d(&M.s33, src + 40 * O_PITCH, 0, half, x1, 0);
                }
                asm volatile("cp.async.bulk.commit_group;\n" ::: "memory");
                asm volatile("cp.async.bulk.wait_group.read 0;\n" ::: "memory");
                {
                    const int row0 = (k + 4) * TOK;
                    mbar_arrive_n(bars + B_VFREE + ((row0 >> 6) & 3) * 8, ((row0 & 63) >= 64 - TOK && (row0 & 63) < TOK) ? 2 : 1);
                }
                TR(23, k);
                if (k == nwin - 1) mbar_arrive(sbase + SM_PBAR + 96);
                asm volatile("cp.async.bulk.wait_group 0;\n" ::: "memory");
                asm volatile("fence.proxy.async.global;\n" ::: "memory");
                mbar_wait(bars + B_PUBD + (k & 1) * 8, ((k >> 1) + 1) & 1);
                mbar_arrive(bars + B_STORED + (k & 1) * 8);
                wq += P.npair; if (wq >= NWS) { wq -= NWS; wr++; }
            }
        }
        if (PSTORE && warp == 1) {
            PROJ_SCHEDULE
            int st = 0, prev = -1;
            uint32_t ph = 0;
#pragma unroll 1
            for (int t = tile0; t < tend; t += tstep) {
                const int p0 = (t < TILES_A) ? SEG_B + 64 * t : 64 * (t - TILES_A);
                mbar_wait(sbase + SM_PBAR + 104 + st * 8, ph);
                fence_async_smem();
#pragma unroll
                for (int ch = 0; ch < ((PEXP & 1) ? 0 : 3); ch++)
                    if (CH & 1)
                    asm volatile("cp.async.bulk.tensor.2d.global.shared::cta.tile.bulk_group.L2::cache_hint [%0, {%2, %3}], [%1], %4;\n"
                                 :: "l"(reinterpret_cast<uint64_t>(t < TILES_A ? &omap : &omapb)),
                                    "r"(sbase + SM_STAGE + st * STAGE_BYTES + ch * 8192), "r"(ch * 64), "r"(p0), "l"(EVICT_FIRST) : "memory");
                    else
                    asm volatile("cp.async.bulk.tensor.2d.global.shared::cta.tile.bulk_group [%0, {%2, %3}], [%1];\n"
                                 :: "l"(reinterpret_cast<uint64_t>(t < TILES_A ? &omap : &omapb)),
                                    "r"(sbase + SM_STAGE + st * STAGE_BYTES + ch * 8192), "r"(ch * 64), "r"((PEXP & 8) ? (p0 & 8191) + 16384 : p0) : "memory");
                asm volatile("cp.async.bulk.commit_group;\n" ::: "memory");
                TRH(6, (t - tile0) / tstep);
                if (prev >= 0) {
                    asm volatile("cp.async.bulk.wait_group.read 1;\n" ::: "memory");
                    mbar_arrive(sbase + SM_PBAR + 48 + prev * 8);
                    TRH(21, (t - tile0) / tstep - 1);
                }
                prev = st;
                if (++st == 6) { st = 0; ph ^= 1; }
            }
            asm volatile("cp.async.bulk.wait_group 0;\n" ::: "memory");
            TR(30, 0);
            TC(1);
        }
        return;
    }
    if (!attn) {
        asm volatile("setmaxnreg.inc.sync.aligned.u32 160;\n");
    } else if (wg == 0) {
        {
            uint32_t src[3][4], dst[3];
#pragma unroll
            for (int it = 0; it < 3; it++) {
                const int o = warp * 12 + it * 4 + (lane >> 3), r = (o / 6) * 8 + (lane & 7), u = o % 6;
#pragma unroll
                for (int h = 0; h < 2; h++) {
                    const int v = u + 6 * h + 4 * half;
                    const bool wide = v >> 3 == half;
                    src[it][h] = wide ? r * 128 + (((v ^ r) & 7) << 4) : 16384 + r * 64 + (((v ^ (r >> 1)) & 3) << 4);
                    src[it][2 + h] = src[it][h] + (wide ? 8192 : 4096);
                }
                dst[it] = sbase + u * 4096 + r * 32 + ((lane >> 2) & 1) * 16;
            }
            TP(16);
#pragma unroll 1
            for (int i = 0; i < 3; i++) {
                uint4 w[3][4];
                mbar_wait(bars + B_WRAW + 16 - 8 * i, 0);
                TP(20 + i);
#pragma unroll
                for (int it = 0; it < 3; it++)
#pragma unroll
                    for (int m = 0; m < 4; m++) w[it][m] = *reinterpret_cast<const uint4*>(smem + src[it][m] + i * 24576);
                wg_bar(7);
#pragma unroll
                for (int it = 0; it < 3; it++) {
                    const uint32_t d = dst[it] + i * 24576;
                    sts128(d, w[it][0].x, w[it][1].x, w[it][2].x, w[it][3].x);
                    sts128(d ^ 16, w[it][0].y, w[it][1].y, w[it][2].y, w[it][3].y);
                    sts128(d + 2048, w[it][0].z, w[it][1].z, w[it][2].z, w[it][3].z);
                    sts128((d ^ 16) + 2048, w[it][0].w, w[it][1].w, w[it][2].w, w[it][3].w);
                }
            }
        }
        asm volatile("setmaxnreg.inc.sync.aligned.u32 %0;\n" :: "n"(REG_G));
        float qs = 1.f;
        if (c < 2) qs = round_bf16(expf(round_bf16(fminf(fmaxf(bf16lo(ls), -100.f), 4.6052f)))) * LOG2E;
        uint32_t xa[12][4];
        float accA[48], accB[48], accV[48];
        uint32_t rho = warp * 16 + (lane & 15), rq = warp * 16 + g;
        uint32_t hi = lane >> 4, lane0 = lane == 0, c2 = 2 * c;
        asm volatile("" : "+r"(hi), "+r"(lane0), "+r"(c2));
        auto row_addr = [&](uint32_t (&ax)[4], uint32_t r) {
            ax[0] = sbase + SM_QK + r * 128 + (((r & 7) ^ hi) << 4);
#pragma unroll
            for (int i = 1; i < 4; i++) ax[i] = ax[0] ^ (32 * i);
        };
#define XADDR(ax, s) ((ax)[((s) & 3) ^ (((s) >> 1) & 2)] + ((s) >> 2) * QK_CHUNK)
        uint64_t descW = make_desc(sbase, 2048, 256, 3);
        const uint32_t zero = (uint32_t)P.z1;
        const uint32_t vbase = sbase + SM_V + (lane >> 4) * GRP;
        const uint32_t ones = 0x3F803F80u, ones2 = ones;
        TP(10);
        {
            uint32_t ax[4];
            row_addr(ax, rho);
            mbar_wait(bars + B_XFULL, 0);
#pragma unroll
            for (int s = 0; s < 12; s++) ldsm_x4(xa[s], XADDR(ax, s));
        }
        TP(8);
        wg_bar(7);
        fence_async_smem();
        TP(9);
        wgmma_fence();
        mma_qkv_a<SM_WA, 0>(accA, xa, descW);
        mma_qkv_b<SM_WA, KLO>(accA, xa, descW);
        wgmma_commit();
        mma_qkv_a<SM_WB, 0>(accB, xa, descW);
        wgmma_commit();
        TP(11);
        mbar_wait(bars + B_WFULL, 0);
        TP(12);
        if (tid == 0) TC(3);
        const int nt = (int)blockIdx.x < P.nr2 ? P.nt1 : P.nt0;
        for (int t = 0; t < nt; t++) {
            descW += P.z1;
            float ss[4];
            uint32_t pk[2][24];
            wgmma_wait<1>();
            reg_fence(accA);
            TR(0, t);
            if (t < 12 && (t < 4 || (t & 1))) TP(t < 4 ? 32 + t : 34 + (t >> 1));
#pragma unroll
            for (int i = 0; i < 4; i++) ss[i] = accA[i] * accA[i];
#pragma unroll
            for (int i = 4; i < 48; i++) ss[i & 3] = fmaf(accA[i], accA[i], ss[i & 3]);
            mma_qkv_b<SM_WB, KLO>(accB, xa, descW);
            wgmma_commit();
            sched_fence(zero, __float_as_uint(ss[0]), __float_as_uint(ss[1]), __float_as_uint(ss[2]), __float_as_uint(ss[3]));
#pragma unroll
            for (int j = 0; j < 12; j++) {
                pk[0][j] = pack_bf16(accA[4 * j], accA[4 * j + 1]);
                pk[1][j] = pack_bf16(accA[4 * j + 2], accA[4 * j + 3]);
                asm volatile("" : "+r"(pk[0][j]), "+r"(pk[1][j]));
            }
            wgmma_fence();
            mma_v_a<D_WV, 0>(accV, xa, descW);
            wgmma_commit();
            uint32_t av = vbase + rho * 16 + ((rho * 1338) >> 16) * (V_STRIDE - GRP);
            uint32_t aq[2];
            aq[0] = sbase + SM_QK + rq * 128 + (((rq & 7) ^ c2) << 4);
            aq[1] = aq[0] + 1024;
            if (rq >= 4 * TOK - 8) aq[1] = (aq[1] - QK_CHUNK) ^ 64;
            rho += 64;
            if (rho >= 4 * TOK) rho -= 4 * TOK;
            rq += 64;
            if (rq >= 4 * TOK) rq -= 4 * TOK;
            uint32_t an[4];
            row_addr(an, rho);
            const uint32_t bt = bars + (t & 3) * 8, pt = (t >> 2) & 1, bn = bars + ((t + 1) & 3) * 8, pn = ((t + 1) >> 2) & 1;
            const uint32_t xok = mbar_test(bn + B_XFULL, pn) & mbar_test(bt + B_VFREE, pt);
            wgmma_wait<1>();
            reg_fence(accB);
#pragma unroll
            for (int i = 0; i < 48; i++) ss[i & 3] = fmaf(accB[i], accB[i], ss[i & 3]);
            ss[0] += ss[1]; ss[2] += ss[3];
            mma_v_b<D_WV, KLO>(accV, xa, descW);
            wgmma_commit();
            sched_fence(zero, __float_as_uint(ss[0]), __float_as_uint(ss[2]), av, aq[0], aq[1], an[0], an[1], an[2], an[3], rho, rq);
            const float f0 = rsqrt_ftz(ss[0] + 1e-12f) * qs, f1 = rsqrt_ftz(ss[2] + 1e-12f) * qs;
            const uint32_t f2[2] = {pack_bf16(f0, f0), pack_bf16(f1, f1)};
#pragma unroll
            for (int j = 0; j < 12; j++) {
                pk[0][12 + j] = pack_bf16(accB[4 * j], accB[4 * j + 1]);
                pk[1][12 + j] = pack_bf16(accB[4 * j + 2], accB[4 * j + 3]);
            }
            auto qk_store = [&](int u0, int u1) {
#pragma unroll
                for (int u = u0; u < u1; u++)
#pragma unroll
                    for (int r = 0; r < 2; r++)
                        sts128((aq[r] ^ ((u & 1) * 16 + (u & 2) * 32)) + (u >> 1) * QK_CHUNK,
                               hmul2_bf16(pk[r][4 * u], f2[r]), hmul2_bf16(pk[r][4 * u + 1], f2[r]),
                               hmul2_bf16(pk[r][4 * u + 2], f2[r]), hmul2_bf16(pk[r][4 * u + 3], f2[r]));
            };
            qk_store(0, QSPLIT);
            TR(1, t);
            mbar_wait2_unless(xok, bn + B_XFULL, pn, bt + B_VFREE, pt);
            TR(2, t);
            wgmma_wait<1>();
#pragma unroll
            for (int s = 0; s < KLO; s++) ldsm_x4(xa[s], XADDR(an, s));
            qk_store(QSPLIT, 6);
            if (NB & 4) {
                const int kc = (t * 21400) >> 14, two = ((t + 1) * 21400) >> 14;
                nb_arrive<256>(NB_QKRAW + (kc & 3));
                asm volatile("{\n.reg .pred p;\nsetp.eq.u32 p, %1, 2;\n@p bar.arrive %0, 256;\n}\n" :: "r"(NB_QKRAW + ((kc + 1) & 3)), "r"(two - kc) : "memory");
                mbar_arrive_if(bars + B_QKRAW, t == nt - 1 ? lane0 : 0);
            } else {
                __syncwarp();
                mbar_arrive_if(bt + B_QKRAW, lane0);
            }
            TR(3, t);
            wgmma_fence();
            mma_qkv_a<SM_WA, 0>(accA, xa, descW);
            wgmma_commit();
            wgmma_wait<1>();
            reg_fence(accV);
#pragma unroll
            for (int s = KLO; s < 12; s++) ldsm_x4(xa[s], XADDR(an, s));
            uint32_t vp[24];
#pragma unroll
            for (int j = 0; j < 24; j++) vp[j] = pack_bf16(accV[2 * j], accV[2 * j + 1]);
            reg_fence(vp);
            wgmma_fence();
            mma_qkv_b<SM_WA, KLO>(accA, xa, descW);
            wgmma_commit();
#pragma unroll
            for (int p = 0; p < 6; p++)
                stsm_x4(av + (p < 3 ? 2 * p : 2 * p + 1) * GRP, vp[4 * p], vp[4 * p + 1], vp[4 * p + 2], vp[4 * p + 3]);
            stsm_x2(av + 6 * GRP, ones, ones2);
            __syncwarp();
            mbar_arrive_if(bt + B_VRAW, lane0);
            TR(4, t);
            if (!MERGEW) wgmma_fence();
            mma_qkv_a<SM_WB, 0>(accB, xa, descW);
            wgmma_commit();
        }
        wgmma_wait<0>();
        reg_fence(accA);
        reg_fence(accB);
        asm volatile("setmaxnreg.dec.sync.aligned.u32 160;\n");
    } else {
        if (REG_A > 128) asm volatile("setmaxnreg.inc.sync.aligned.u32 %0;\n" :: "n"(REG_A));
        {
            const float c0 = bf16lo(rc), c1 = bf16hi(rc);
            float a0 = 0.f, a1 = 0.f;
#pragma unroll
            for (int u = 0; u < 16; u += 2) {
                const uint32_t p = reinterpret_cast<const uint32_t*>(w1)[u >> 1], q = reinterpret_cast<const uint32_t*>(w1)[8 + (u >> 1)];
                uint32_t h;
                asm("cvt.rn.relu.bf16x2.f32 %0, %1, %2;\n" : "=r"(h) : "f"(c0 * bf16hi(p) + c1 * bf16hi(q)), "f"(c0 * bf16lo(p) + c1 * bf16lo(q)));
                a0 += bf16lo(h) * bf16lo(w2[u]);
                a1 += bf16lo(h) * bf16hi(w2[u]);
                a0 += bf16hi(h) * bf16lo(w2[u + 1]);
                a1 += bf16hi(h) * bf16hi(w2[u + 1]);
            }
            const float s0 = round_bf16(__fdividef(1.f, 1.f + expf(-round_bf16(a0))));
            const float s1 = round_bf16(__fdividef(1.f, 1.f + expf(-round_bf16(a1))));
            if (tid - 128 < 169) sts32(sbase + SM_TAB + (tid - 128) * 4, pack_bf16(exp2f(fmaf(s0, 16.f * LOG2E, -12.f)), exp2f(fmaf(s1, 16.f * LOG2E, -12.f))));
        }
        asm volatile("bar.sync 1, 256;\n" ::: "memory");
        uint32_t eb[26];
        {
            const uint32_t* tab = reinterpret_cast<const uint32_t*>(smem + SM_TAB);
#pragma unroll
            for (int i = 0; i < 13; i++) {
                const uint32_t lo = tab[min(ridx[i < 12 ? 13 * (i & 1) + (i & ~1) : 12], 168u)];
                const uint32_t hi = tab[min(ridx[i < 12 ? 13 * (i & 1) + (i | 1) : 25], 168u)];
                eb[i]      = prmt(lo, hi, 0x5410);
                eb[13 + i] = prmt(lo, hi, 0x7632);
            }
            if (c != 0) eb[12] = eb[25] = 0;
        }
        uint32_t slow = (bf16lo(ls) <= LS_FAST ? 0 : 1) | (bf16hi(ls) <= LS_FAST ? 0 : 2);
        reg_fence(eb);
        if (SLOWH == 2) sts32(bars + B_PROG + 4, slow);
        wg_bar(3 + wg);
        if ((tid & 127) == 0) mbar_arrive(bars + B_VFREE + 16);
        const uint32_t ov0 = warp * 16 + g < TOK, ov1 = warp < 3;
        const uint64_t descK0 = make_desc(sbase + SM_QK, 16, 1024, 1);
        const uint64_t descV0 = make_desc(sbase + SM_V, 128, GRP, 0);
        slow = __shfl_sync(0xffffffffu, slow, 0);
        const uint32_t barw = bars + (wg - 1) * 8;
        const uint64_t descKw = descK0 + (uint64_t)((wg - 1) * (XCH >> 4)), descVw = descV0 + (uint64_t)((wg - 1) * (V_STRIDE >> 4));
        const uint32_t oa = sbase + SM_V + (wg - 1) * V_STRIDE + (warp * 16 + g) * O_PITCH + c * 48;
        uint32_t qok = 0;
        const uint32_t zero = (uint32_t)P.z1;
        auto window = [&](auto IT_, int k) {
            constexpr int IT = decltype(IT_)::value;
            const uint32_t bar = barw + 16 * IT;
            const int tl = (k * TOK + TOK - 1) >> 6, tn = ((k + 2) * TOK + TOK - 1) >> 6;
            const uint32_t bt = bars + (tl & 3) * 8, pt = (tl >> 2) & 1;
            TR(8, k);
            if (k < 2) TP(44 + k);
            float sc0[28], sc1[28];
            TR(10, k);
            if (NB & 4) nb_sync<256>(NB_QKRAW + 2 * IT - 1 + wg);
            else mbar_wait_unless(qok, bt + B_QKRAW, pt);
            fence_async_smem();
            TR(11, k);
            if (k == 0) TP(17);
            wgmma_fence();
            mma_qk0<2 * IT * XCH, 2 * IT * XCH>(sc0, descKw, descKw);
            mma_qk1<2 * IT * XCH, 2 * IT * XCH>(sc1, descKw, descKw);
            wgmma_commit();
            const uint32_t vok = mbar_test(bt + B_VRAW, pt);
            uint32_t mflag = 1;
            if (!(XP & 1)) asm volatile("ld.volatile.shared.u8 %0, [%1];\n" : "=r"(mflag) : "r"(sbase + SM_FLAG + k) : "memory");
            wgmma_wait<0>();
            reg_fence(sc0);
            reg_fence(sc1);
            if (NB & 1) nb_arrive<160>(NB_QKFREE - 1 + wg);
            else if (lane == 0) mbar_arrive(bar + B_QKFREE);
            TR(12, k);
            if (k == 0) TP(18);
            if (mflag != 1) {
              asm volatile(
                "{\n.reg .pred p;\n.reg .u32 n;\nmov.u32 n, 0;\n"
                "WAIT_%=:\n"
                "ld.volatile.shared.u8 %0, [%1];\n"
                "setp.ne.u32 p, %0, 0;\n"
                "@p bra DONE_%=;\n"
                "add.u32 n, n, 1;\n"
                "setp.lt.u32 p, n, 16777216;\n"
                "@p bra WAIT_%=;\n"
                "trap;\n"
                "DONE_%=:\n}\n" : "=r"(mflag) : "r"(sbase + SM_FLAG + k) : "memory");
              if (mflag == 2) {
                uint32_t mk[13];
                __threadfence_block();
                uint32_t u = threadIdx.x, bid = blockIdx.x;
                asm volatile("" : "+r"(u), "+r"(bid));
                const uint32_t r0 = ((u >> 1) & 48) + ((u >> 2) & 7);
                const int wi = (bid >> 1) + k * P.npair, wr = wi / NWS;
                const uint32_t mp = sbase + SM_MASK + (((unrot(wr) * NWS + unrot(wi - wr * NWS)) * 2) & 15);
                const uint32_t mr[2] = {mp + row_token(min(r0, TOK - 1u)) * (2 * TOK), mp + row_token(min(r0 + 8, TOK - 1u)) * (2 * TOK)};
                const uint32_t c0 = 2 * row_token(2 * (u & 3));
#pragma unroll
                for (int i = 0; i < 13; i++) {
                    const uint32_t a0 = i < 6 ? mr[i & 1] + c0 + 28 * (i >> 1) : i < 12 ? mr[i & 1] + 2 * row_token(2 * (u & 3) + 8 * (i >> 1)) : mr[0] + 2 * TOK - 2;
                    const uint32_t a1 = i < 6 ? a0 + 2 : i < 12 ? mr[i & 1] + 2 * row_token(2 * (u & 3) + 8 * (i >> 1) + 1) : mr[1] + 2 * TOK - 2;
                    uint32_t lo, hi;
                    asm volatile("ld.shared.u16 %0, [%1];\n" : "=r"(lo) : "r"(a0) : "memory");
                    asm volatile("ld.shared.u16 %0, [%1];\n" : "=r"(hi) : "r"(a1) : "memory");
                    mk[i] = prmt(lo, hi, 0x5410);
                }
                reg_fence(mk);
                __syncwarp();
                if (lane == 0) mbar_arrive(bars + B_MCONS);
                uint32_t m0 = mk[0], m1 = mk[1];
#pragma unroll
                for (int i = 2; i < 12; i += 2) { m0 = hmax2_bf16(m0, mk[i]); m1 = hmax2_bf16(m1, mk[i + 1]); }
                m0 = hmax2_bf16(hmax2_bf16(prmt(m0, m1, 0x5410), prmt(m0, m1, 0x7632)), mk[12]);
                m0 = hmax2_bf16(m0, __shfl_xor_sync(0xffffffffu, m0, 1));
                m0 = hmax2_bf16(m0, __shfl_xor_sync(0xffffffffu, m0, 2));
                const float m[2] = {bf16lo(m0), bf16hi(m0)};
#pragma unroll
                for (int i = 0; i < 13; i++) {
                    const float lo = bf16lo(mk[i]) - m[i & 1], hi = bf16hi(mk[i]) - m[i < 12 ? i & 1 : 1];
                    const int j = i < 12 ? 2 * i + 1 : 26;
                    sc0[2 * i] = fmaf(lo, LOG2E, sc0[2 * i]); sc0[j] = fmaf(hi, LOG2E, sc0[j]);
                    sc1[2 * i] = fmaf(lo, LOG2E, sc1[2 * i]); sc1[j] = fmaf(hi, LOG2E, sc1[j]);
                }
              }
            }
            if (slow) {
                auto shift = [&](float (&S)[28], int h) {
                    float m[2];
#pragma unroll
                    for (int i = 12; i >= 0; i--) {
                        uint32_t e = eb[13 * h + i];
                        asm volatile("" : "+r"(e));
                        const float a = S[2 * i] + lg2_ftz(bf16lo(e)), b = S[i < 12 ? 2 * i + 1 : 26] + lg2_ftz(bf16hi(e));
                        if (i == 12) { m[0] = a; m[1] = b; }
                        else m[i & 1] = fmaxf(m[i & 1], fmaxf(a, b));
                    }
#pragma unroll
                    for (int r = 0; r < 2; r++) {
                        m[r] = fmaxf(m[r], __shfl_xor_sync(0xffffffffu, m[r], 1));
                        m[r] = fmaxf(m[r], __shfl_xor_sync(0xffffffffu, m[r], 2));
                    }
#pragma unroll
                    for (int i = 0; i < 27; i++) S[i] -= m[(i >> 1) & 1];
                };
                uint32_t sl = slow;
                if (SLOWH == 2) asm volatile("ld.volatile.shared.u32 %0, [%1];\n" : "=r"(sl) : "r"(bars + B_PROG + 4) : "memory");
                if (!SLOWH || (sl & 1)) shift(sc0, 0);
                if (!SLOWH || (sl & 2)) shift(sc1, 1);
            }
            auto exps = [&](const float (&S)[28], uint32_t (&e)[13]) {
#pragma unroll
                for (int i = 0; i < 12; i++) e[i] = pack_bf16(ex2_ftz(S[2 * i]), ex2_ftz(S[2 * i + 1]));
                e[12] = hmin2_bf16(pack_bf16(ex2_ftz(S[24]), ex2_ftz(S[26])), 0x7F7F7F7Fu);
            };
            auto probs = [&](const uint32_t (&e)[13], int h, uint32_t (&pa)[4][4]) {
#pragma unroll
                for (int i = 0; i < 12; i++) pa[i >> 2][i & 3] = hmul2_bf16(e[i], eb[13 * h + i]);
                const uint32_t l = hmul2_bf16(e[12], eb[13 * h + 12]);
                pa[3][0] = l & 0xFFFFu;
                pa[3][1] = l >> 16;
                pa[3][2] = 0u; pa[3][3] = 0u;
                reg_fence(pa);
            };
            uint32_t pa0[4][4], pa1[4][4], e[13];
            float o0[28], o1[28];
            TR(13, k);
            if (k == 0) TP(23);
            exps(sc0, e);
            probs(e, 0, pa0);
            mbar_wait_unless(vok, bt + B_VRAW, pt);
            fence_async_smem();
            TR(14, k);
            wgmma_fence();
            mma_pv<2 * IT * V_STRIDE, 0>(o0, pa0, descVw);
            wgmma_commit();
            exps(sc1, e);
            reg_fence(e);
            wgmma_wait<0>();
            reg_fence(o0);
            sched_fence_rw(zero, e);
            probs(e, 1, pa1);
            wgmma_fence();
            mma_pv<2 * IT * V_STRIDE + 6 * GRP, 0>(o1, pa1, descVw);
            wgmma_commit();
            uint32_t w[24];
            {
                const float il0 = rcp_ftz(o0[24]), il1 = rcp_ftz(o0[26]);
                const uint32_t l0 = pack_bf16(il0, il0), l1 = pack_bf16(il1, il1);
#pragma unroll
                for (int j = 0; j < 12; j++) w[j] = hmul2_bf16(pack_bf16(o0[2 * j], o0[2 * j + 1]), (j & 1) ? l1 : l0);
            }
            wgmma_wait<0>();
            reg_fence(o1);
            TR(15, k);
            if (k == 0) TP(25);
            wg_bar(3 + wg);
            if (!(NB & 4)) qok = mbar_test(bars + (tn & 3) * 8 + B_QKRAW, (tn >> 2) & 1);
            {
                const float il2 = rcp_ftz(o1[0]), il3 = rcp_ftz(o1[2]);
                const uint32_t l2 = pack_bf16(il2, il2), l3 = pack_bf16(il3, il3);
#pragma unroll
                for (int j = 0; j < 12; j++) w[12 + j] = hmul2_bf16(pack_bf16(o1[2 * j + 4], o1[2 * j + 5]), (j & 1) ? l3 : l2);
#pragma unroll
                for (int p = 0; p < 6; p++) {
                    const int j = 8 * (p >> 1) + (p & 1);
                    sts128_if((p & 1) ? ov1 : ov0, oa + 2 * IT * V_STRIDE + (p & 1) * 8 * O_PITCH + (p >> 1) * 16, w[j], w[j + 2], w[j + 4], w[j + 6]);
                }
            }
            if (NB & 2) nb_arrive<160>(NB_ODONE + 2 * IT - 1 + wg);
            else {
                __syncwarp();
                if (lane == 0) mbar_arrive(bar + B_ODONE);
            }
            TR(16, k);
            if (k < 2) TP(46 + k);
        };
        for (int k = wg - 1;; k += 4) {
            window(std::integral_constant<int, 0>(), k);
            if (k + 2 >= nwin) break;
            window(std::integral_constant<int, 1>(), k + 2);
            if (k + 4 >= nwin) break;
        }
        (void)zero;
        asm volatile("setmaxnreg.inc.sync.aligned.u32 160;\n");
    }

    TR(27, wg);
    if ((tid & 127) == 0) TC(4 + wg);
    if (attn) {
        __syncwarp();
        if (lane == 0) mbar_arrive(sbase + SM_PBAR + 96);
    }
    if (!attn) {
#pragma unroll
        for (int row = tid >> 2; row < 192; row += 96) {
            uint4 w[6];
            const int pr = row % 96, srow = row - pr + (pr % 24) / 12 * 48 + (pr % 12) / 2 * 8 + pr / 24 * 2 + (pr & 1);
#pragma unroll
            for (int a = 0; a < 6; a++) w[a] = *reinterpret_cast<const uint4*>(P.wo + srow * 192 + 32 * a + 8 * c);
            float s = 0.f;
#pragma unroll
            for (int a = 0; a < 6; a++)
                s += ((bf16lo(w[a].x) + bf16hi(w[a].x)) + (bf16lo(w[a].y) + bf16hi(w[a].y))) +
                     ((bf16lo(w[a].z) + bf16hi(w[a].z)) + (bf16lo(w[a].w) + bf16hi(w[a].w)));
            s += __shfl_xor_sync(0xffffffffu, s, 1);
            s += __shfl_xor_sync(0xffffffffu, s, 2);
            s *= (1.f / 192.f);
            const uint32_t d = sbase + SM_WO + row * 64 + ((c ^ ((row >> 1) & 3)) << 4);
#pragma unroll
            for (int a = 0; a < 6; a++)
                sts128(d + a * 12288, pack_bf16(bf16lo(w[a].x) - s, bf16hi(w[a].x) - s), pack_bf16(bf16lo(w[a].y) - s, bf16hi(w[a].y) - s),
                       pack_bf16(bf16lo(w[a].z) - s, bf16hi(w[a].z) - s), pack_bf16(bf16lo(w[a].w) - s, bf16hi(w[a].w) - s));
        }
        fence_async_smem();
        asm volatile("bar.sync 6, 384;\n" ::: "memory");
        if (tid == 0 && (int)blockIdx.x == 2 * P.npair) {
            asm volatile("cp.async.bulk.global.shared::cta.bulk_group [%0], [%1], 73728;\n" :: "l"(g_wo), "r"(sbase + SM_WO) : "memory");
            asm volatile("cp.async.bulk.commit_group;\n" ::: "memory");
            asm volatile("cp.async.bulk.wait_group 0;\n" ::: "memory");
            asm volatile("fence.proxy.async.global;\n" ::: "memory");
            asm volatile("red.release.gpu.global.add.u32 [%0], 1;\n" :: "l"(g_cnt + NWS) : "memory");
        }
        __syncwarp();
    } else if (P.t1 < TILES) {
        mbar_wait(sbase + SM_BAR + B_WRAW, 1);
    }
    TR(27, 4 + wg);
    if (tid == 0) TC(2);
    {
        PROJ_SCHEDULE
        uint64_t descW = make_desc(sbase + SM_WO, 12288, 512, 2);
        const uint64_t descA = make_desc(sbase + SM_STAGE + wg * STAGE_BYTES, 16, 1024, 1);
        const uint32_t bar = sbase + SM_PBAR + wg * 8;
        const uint32_t yrel = sbase + SM_STAGE + wg * STAGE_BYTES + (warp * 16 + (lane & 15)) * 128 + (((lane & 7) ^ (lane >> 4)) << 4);
        float acc[96];
#pragma unroll
        for (int i = 0; i < 96; i++) acc[i] = 0.f;
        uint32_t it = 0;
        for (int tile = tile0 + wg * tstep; tile < tend; tile += 3 * tstep, it++) {
            descW += P.z1;
            mbar_wait(bar + (it & 1) * 24, (it >> 1) & 1);
            TR(28, it * 3 + wg);
            if (it > 0 || wg > 0) asm volatile("bar.sync %0, 256;\n" :: "r"(8 + wg) : "memory");
            wgmma_fence();
            mma_proj<0, 0>(acc, descA + (uint64_t)((it & 1) * (3 * STAGE_BYTES >> 4)), descW);
            wgmma_commit();
            if (tile + tstep < tend) asm volatile("bar.arrive %0, 256;\n" :: "r"(wg == 2 ? 8 : 9 + wg) : "memory");
            wgmma_wait<0>();
            reg_fence(acc);
            float a[4];
#pragma unroll
            for (int i = 0; i < 4; i++) a[i] = acc[i] * acc[i];
#pragma unroll
            for (int j = 1; j < 24; j++)
#pragma unroll
                for (int i = 0; i < 4; i++) a[i] = fmaf(acc[4 * j + i], acc[4 * j + i], a[i]);
            float s0 = a[0] + a[1], s1 = a[2] + a[3];
            s0 += __shfl_xor_sync(0xffffffffu, s0, 1);
            s1 += __shfl_xor_sync(0xffffffffu, s1, 1);
            s0 += __shfl_xor_sync(0xffffffffu, s0, 2);
            s1 += __shfl_xor_sync(0xffffffffu, s1, 2);
            const float rs0 = rsqrt_ftz(fmaf(s0, 1.f / 192.f, 1e-5f));
            const float rs1 = rsqrt_ftz(fmaf(s1, 1.f / 192.f, 1e-5f));
            const uint32_t ya = yrel + (it & 1) * 3 * STAGE_BYTES;
#pragma unroll
            for (int p = 0; p < 12; p++)
                stsm_x4((ya ^ (32 * (p & 3))) + (p >> 2) * 8192,
                        pack_bf16(acc[8 * p] * rs0, acc[8 * p + 1] * rs0), pack_bf16(acc[8 * p + 2] * rs1, acc[8 * p + 3] * rs1),
                        pack_bf16(acc[8 * p + 4] * rs0, acc[8 * p + 5] * rs0), pack_bf16(acc[8 * p + 6] * rs1, acc[8 * p + 7] * rs1));
            __syncwarp();
            if (lane == 0) mbar_arrive(bar + 104 + (it & 1) * 24);
            TR(29, it * 3 + wg);
        }
    }
}

}

typedef CUresult (*PFN_encodeTiled)(CUtensorMap*, CUtensorMapDataType, cuuint32_t, void*, const cuuint64_t*,
                                    const cuuint64_t*, const cuuint32_t*, const cuuint32_t*, CUtensorMapInterleave,
                                    CUtensorMapSwizzle, CUtensorMapL2promotion, CUtensorMapFloatOOBfill);

extern "C" void kernel_launch(void* const* d_in, const int* in_sizes, int n_in, void* d_out, int out_size) {
    swin::Params P;
    P.x           = (const __nv_bfloat16*)d_in[0];
    P.wqkv        = (const __nv_bfloat16*)d_in[1];
    P.wo          = (const __nv_bfloat16*)d_in[2];
    P.logit_scale = (const __nv_bfloat16*)d_in[3];
    P.cpb_w1      = (const __nv_bfloat16*)d_in[4];
    P.cpb_w2      = (const __nv_bfloat16*)d_in[5];
    P.rel_coords  = (const __nv_bfloat16*)d_in[6];
    P.rel_idx     = (const int*)d_in[7];
    P.mask        = (const __nv_bfloat16*)d_in[8];
    P.out         = (__nv_bfloat16*)d_out;
    P.z1 = 0;
    static PFN_encodeTiled encode = nullptr;
    if (!encode) {
        cudaFuncSetAttribute(swin::swin_window_attn_kernel, cudaFuncAttributeMaxDynamicSharedMemorySize, swin::SM_TOTAL);
        cudaDriverEntryPointQueryResult qr;
        cudaGetDriverEntryPoint("cuTensorMapEncodeTiled", (void**)&encode, cudaEnableDefault, &qr);
    }
    swin::Maps M;
    const cuuint32_t estr[4] = {1, 1, 1, 1};
    auto make = [&](CUtensorMap* m, const void* base, int rank, const cuuint64_t* gdim, const cuuint64_t* gstr,
                    const cuuint32_t* box, CUtensorMapSwizzle swz = CU_TENSOR_MAP_SWIZZLE_128B) {
        CUresult r = encode(m, CU_TENSOR_MAP_DATA_TYPE_BFLOAT16, rank, const_cast<void*>(base), gdim, gstr, box, estr,
               CU_TENSOR_MAP_INTERLEAVE_NONE, swz, CU_TENSOR_MAP_L2_PROMOTION_L2_128B,
               CU_TENSOR_MAP_FLOAT_OOB_FILL_NONE);
        (void)r;
    };
    {
        const cuuint64_t gdim[3] = {192, swin::IMG, swin::IMG}, gstr[2] = {384, swin::IMG * 384};
        const cuuint32_t box[7][3] = {{64, 7, 7}, {64, 4, 7}, {64, 3, 7}, {64, 4, 4}, {64, 4, 3}, {64, 3, 4}, {64, 3, 3}};
        for (int i = 0; i < 7; i++) make(&M.x77 + i, P.x, 3, gdim, gstr, box[i]);
        const cuuint32_t boxp[3] = {192, 7, 7};
        if (PF1) make(&M.x77, P.x, 3, gdim, gstr, boxp, CU_TENSOR_MAP_SWIZZLE_NONE);
    }
    {
        const cuuint64_t gdim[2] = {192, (cuuint64_t)swin::NPIX}, gstr[1] = {384};
        const cuuint32_t box64[2] = {64, 64};
        make(&M.o, d_out, 2, gdim, gstr, box64);
        const cuuint64_t gdimb[2] = {192, (cuuint64_t)swin::SEG_B};
        make(&M.ob, d_out, 2, gdimb, gstr, box64);
    }
    {
        const cuuint64_t gdim[3] = {16, 192, 36}, gstr[2] = {1152, 32};
        const cuuint32_t box[3] = {16, 192, 6};
        make(&M.w, P.wqkv, 3, gdim, gstr, box, CU_TENSOR_MAP_SWIZZLE_32B);
        const cuuint64_t gdim3[3] = {192, 192, 3}, gstr3[2] = {1152, 384};
        const cuuint32_t box64[3] = {64, 64, 2}, box32[3] = {32, 64, 2};
        make(&M.w64, P.wqkv, 3, gdim3, gstr3, box64);
        make(&M.w32, P.wqkv, 3, gdim3, gstr3, box32, CU_TENSOR_MAP_SWIZZLE_64B);
    }
    {
        const cuuint64_t gdim[4] = {96, 2, swin::IMG, swin::IMG}, gstr[3] = {192, 384, swin::IMG * 384};
        const cuuint32_t box[4][4] = {{96, 1, 4, 7}, {96, 1, 3, 7}, {96, 1, 4, 3}, {96, 1, 3, 3}};
        for (int i = 0; i < 4; i++) make(&M.s47 + i, d_out, 4, gdim, gstr, box[i], CU_TENSOR_MAP_SWIZZLE_NONE);
    }
    P.npair = NPAIR; P.need = swin::ROW_DONE; P.nq = swin::NWINDOWS / NPAIR; P.nr = swin::NWINDOWS % NPAIR;
    P.nr2 = 2 * P.nr; P.nt0 = (P.nq * swin::TOK + 63) / 64; P.nt1 = ((P.nq + 1) * swin::TOK + 63) / 64;
    P.t1 = swin::TILES - NTAIL;
    swin::swin_window_attn_kernel<<<132, swin::NTHREADS, swin::SM_TOTAL>>>(P, M);
}
```

```cpp
#include <cuda_runtime.h>
#include <cuda.h>
#include <cuda_bf16.h>
#include <stdint.h>
#include <type_traits>

namespace swin {
#define HINT ""

#define NPAIR 53
#define PF_DIST 3
#define QSPLIT 4
#define CLUSTER 0
#define NOPF 0
#define NTAIL 318
#define PSTORE 1
#define PORDER 1
#define GORD 0
#define GF1 1
#define MERGEW 1
#define MWAIT 0
#define PSLEEP 200
#define CH 5
#define NB 1
#define SCM 0
#define MPF 2
#define MLEAD 4
#define PFM 0
#define PFK 4
#define XP 0
#define KLO 6
#define VPOS 1
#define XSPLIT 1
#define SEQ 1
#define PREL 0
#define PEXP 0
#define PFD 0
#define PFW 0
#define WVK -4
#define WSEQ 1
#define PF1 1
#define WFIRST 1
#define MPRE 1
#define SLOWH 2
#define LS_FAST 4.f
#define ENDR 1
#define EBZ 1
#define HSQ 0
#define AFENCE 0
#define FM 0
#define QPOST 0
#define EARLYQ 0
#define KL 4
#define VB1 4
#define VA0 1
#define K1 3
#define Q1 2
#define RWF 3
#define PUBM 2
#define PBE 70
#define PUBW 1
#define WFEN 1
#define PB_LO 0x5555555555555555ull
#define PB_HI 0x3ffu
#define REG_G 224
#define REG_A 128
#define REG_H 32
constexpr int IMG      = 511;
constexpr int NWS      = 73;
constexpr int NWINDOWS = NWS * NWS;
constexpr int TOK      = 49;
constexpr int NPIX     = IMG * IMG;
constexpr int NTHREADS = 512;

constexpr int W_ATOM = 6144;
constexpr int SM_WA = 0, SM_WB = 6 * 2048, SM_WV = 12 * W_ATOM, D_WV = SM_WV + ((W_ATOM - 2048) << 16);
constexpr int GRP   = TOK * 16;
constexpr int XCH   = TOK * 128;
constexpr int SM_V  = 18 * W_ATOM, V_STRIDE = 10240, O_PITCH = 192;
constexpr int SM_QK = SM_V + 4 * V_STRIDE, QK_CHUNK = 4 * XCH;
constexpr int SM_MASK = SM_QK + 3 * QK_CHUNK;
constexpr int SM_TAB  = SM_V + 3 * V_STRIDE + 256;
constexpr int SM_BAR  = SM_MASK + 4816;
constexpr int B_XFULL = 0, B_WRAW = 32, B_QKRAW = 64, B_QKFREE = 96, B_VFREE = 128, B_ODONE = 160,
              B_PROG = 192, B_VRAW = 224, B_MFULL = 256, B_MCONS = 272, B_WFULL = 280, B_STORED = 288, B_PUBD = 304;
constexpr int SM_FLAG = SM_BAR + 320;
constexpr int SM_A_END = SM_FLAG + 128;
static_assert(SM_QK % 1024 == 0 && 13 * GRP <= V_STRIDE && V_STRIDE % 128 == 0, "layout");
constexpr int SM_WO    = 0;
constexpr int SM_STAGE = 73728;
constexpr int STAGE_BYTES = 24576;
constexpr int SM_PBAR  = SM_A_END;
#define TA(role, idx)
#define TAEND(role)
constexpr int SM_TOTAL = SM_PBAR + 152;
#define TP(idx)
static_assert(SM_STAGE + 6 * STAGE_BYTES <= SM_BAR, "smem");
static_assert(SM_TOTAL <= 232448, "smem");
static_assert(SM_BAR % 8 == 0 && NWINDOWS / NPAIR < 127, "barrier alignment, flags");

constexpr int SEG_B   = (IMG - 4) * IMG;
constexpr int TILES_A = (NPIX - SEG_B + 63) / 64;
constexpr int TILES   = TILES_A + (SEG_B + 63) / 64;
constexpr uint32_t ROW_DONE = NWS * 2;

__device__ uint32_t g_cnt[NWS + 7];
__device__ __align__(128) uint8_t g_wo[73728];
__device__ uint32_t g_flag[66 * 128];
__device__ uint32_t g_done;

#define TR(ev, idx)
#define TC(slot)
#define TS(i)
#define TRH(ev, idx)
constexpr float LOG2E = 1.4426950408889634f;

__device__ __forceinline__ uint32_t smem_u32(const void* p) {
    return (uint32_t)__cvta_generic_to_shared(p);
}
__device__ __forceinline__ uint64_t make_desc(uint32_t saddr, uint32_t lbo, uint32_t sbo, uint32_t swz = 0) {
    return (uint64_t)((saddr & 0x3FFFF) >> 4) | ((uint64_t)(lbo >> 4) << 16) | ((uint64_t)(sbo >> 4) << 32) |
           ((uint64_t)swz << 62);
}
__host__ __device__ constexpr uint64_t make_desc_c(uint32_t saddr, uint32_t lbo, uint32_t sbo, uint32_t swz) {
    return (uint64_t)(saddr >> 4) | ((uint64_t)(lbo >> 4) << 16) | ((uint64_t)(sbo >> 4) << 32) | ((uint64_t)swz << 62);
}
__device__ __forceinline__ void wgmma_fence()  { asm volatile("wgmma.fence.sync.aligned;\n" ::: "memory"); }
__device__ __forceinline__ void wgmma_commit() { asm volatile("wgmma.commit_group.sync.aligned;\n" ::: "memory"); }
template <int N> __device__ __forceinline__ void wgmma_wait() {
    asm volatile("wgmma.wait_group.sync.aligned %0;\n" :: "n"(N) : "memory");
}
__device__ __forceinline__ void fence_async_smem() { asm volatile("fence.proxy.async.shared::cta;\n" ::: "memory"); }
template <int N> __device__ __forceinline__ void nb_sync(int id) { asm volatile("bar.sync %0, %1;\n" :: "r"(id), "n"(N) : "memory"); }
template <int N> __device__ __forceinline__ void nb_arrive(int id) { asm volatile("bar.arrive %0, %1;\n" :: "r"(id), "n"(N) : "memory"); }
constexpr int NB_ODONE = 0, NB_QKFREE = 6, NB_QKRAW = 12;
__device__ __forceinline__ void wg_bar(int id) { asm volatile("bar.sync %0, 128;\n" :: "r"(id) : "memory"); }

template <int N> __device__ __forceinline__ void reg_fence(float (&v)[N]) {
#pragma unroll
    for (int i = 0; i < N; i++) asm volatile("" : "+f"(v[i]) :: "memory");
}
template <int N> __device__ __forceinline__ void reg_fence(uint32_t (&v)[N]) {
#pragma unroll
    for (int i = 0; i < N; i++) asm volatile("" : "+r"(v[i]) :: "memory");
}
template <int N, int M> __device__ __forceinline__ void reg_fence(uint32_t (&v)[N][M]) {
#pragma unroll
    for (int i = 0; i < N; i++) reg_fence(v[i]);
}

__device__ __forceinline__ uint32_t pack_bf16(float lo, float hi) {
    uint32_t r;
    asm("cvt.rn.bf16x2.f32 %0, %1, %2;\n" : "=r"(r) : "f"(hi), "f"(lo));
    return r;
}
__device__ __forceinline__ float bf16lo(uint32_t v) { return __uint_as_float(v << 16); }
__device__ __forceinline__ float bf16hi(uint32_t v) { return __uint_as_float(v & 0xFFFF0000u); }
__device__ __forceinline__ uint32_t hadd2_bf16(uint32_t a, uint32_t b) {
    uint32_t r;
    asm("add.rn.bf16x2 %0, %1, %2;\n" : "=r"(r) : "r"(a), "r"(b));
    return r;
}
__device__ __forceinline__ uint32_t hmul2_bf16(uint32_t a, uint32_t b) {
    uint32_t r;
    asm("mul.rn.bf16x2 %0, %1, %2;\n" : "=r"(r) : "r"(a), "r"(b));
    return r;
}
__device__ __forceinline__ uint32_t hsub2_bf16(uint32_t a, uint32_t b) {
    uint32_t r;
    asm("sub.rn.bf16x2 %0, %1, %2;\n" : "=r"(r) : "r"(a), "r"(b));
    return r;
}
__device__ __forceinline__ uint32_t hfma2_bf16(uint32_t a, uint32_t b, uint32_t c) {
    uint32_t r;
    asm("fma.rn.bf16x2 %0, %1, %2, %3;\n" : "=r"(r) : "r"(a), "r"(b), "r"(c));
    return r;
}
__device__ __forceinline__ uint32_t hmax2_bf16(uint32_t a, uint32_t b) {
    uint32_t r;
    asm("max.bf16x2 %0, %1, %2;\n" : "=r"(r) : "r"(a), "r"(b));
    return r;
}
__device__ __forceinline__ uint32_t hmin2_bf16(uint32_t a, uint32_t b) {
    uint32_t r;
    asm("min.bf16x2 %0, %1, %2;\n" : "=r"(r) : "r"(a), "r"(b));
    return r;
}
__device__ __forceinline__ uint32_t ex2_bf16x2(uint32_t a) {
    uint32_t r;
    asm("ex2.approx.ftz.bf16x2 %0, %1;\n" : "=r"(r) : "r"(a));
    return r;
}
__device__ __forceinline__ uint32_t ex2_bf16lo(uint32_t a) {
    uint32_t r;
    asm("{\n.reg .b16 l, h;\nmov.b32 {l, h}, %1;\nex2.approx.ftz.bf16 l, l;\ncvt.u32.u16 %0, l;\n}\n" : "=r"(r) : "r"(a));
    return r;
}
__device__ __forceinline__ uint32_t mbar_test(uint32_t bar, uint32_t parity) {
    uint32_t ok;
    asm volatile("{\n.reg .pred p;\nmbarrier.test_wait.parity.shared::cta.b64 p, [%1], %2;\nselp.u32 %0, 1, 0, p;\n}\n"
                 : "=r"(ok) : "r"(bar), "r"(parity) : "memory");
    return ok;
}
__device__ __forceinline__ uint32_t prmt(uint32_t a, uint32_t b, uint32_t sel) {
    uint32_t r;
    asm("prmt.b32 %0, %1, %2, %3;\n" : "=r"(r) : "r"(a), "r"(b), "r"(sel));
    return r;
}
__device__ __forceinline__ float round_bf16(float x) { return __bfloat162float(__float2bfloat16_rn(x)); }

__device__ __forceinline__ void mbar_init(uint32_t bar, uint32_t count) {
    asm volatile("mbarrier.init.shared::cta.b64 [%0], %1;\n" :: "r"(bar), "r"(count) : "memory");
}
__device__ __forceinline__ void mbar_wait(uint32_t bar, uint32_t parity) {
    asm volatile(
        "{\n"
        ".reg .pred p;\n"
        ".reg .u32 n;\n"
        "mov.u32 n, 0;\n"
        "WAIT_%=:\n"
        "mbarrier.try_wait.parity.shared::cta.b64 p, [%0], %1" HINT ";\n"
        "@p bra DONE_%=;\n"
        "add.u32 n, n, 1;\n"
        "setp.lt.u32 p, n, 4194304;\n"
        "@p bra WAIT_%=;\n"
        "trap;\n"
        "DONE_%=:\n"
        "}\n" :: "r"(bar), "r"(parity) : "memory");
}
__device__ __forceinline__ void mbar_wait4(uint32_t b0, uint32_t p0, uint32_t b1, uint32_t p1, uint32_t b2, uint32_t p2,
                                           uint32_t b3, uint32_t p3) {
    asm volatile(
        "{\n"
        ".reg .pred p, q, r, s;\n"
        ".reg .u32 n;\n"
        "mov.u32 n, 0;\n"
        "WAIT_%=:\n"
        "mbarrier.try_wait.parity.shared::cta.b64 p, [%0], %1" HINT ";\n"
        "mbarrier.try_wait.parity.shared::cta.b64 q, [%2], %3" HINT ";\n"
        "mbarrier.try_wait.parity.shared::cta.b64 r, [%4], %5" HINT ";\n"
        "mbarrier.try_wait.parity.shared::cta.b64 s, [%6], %7" HINT ";\n"
        "and.pred p, p, q;\n"
        "and.pred r, r, s;\n"
        "and.pred p, p, r;\n"
        "@p bra DONE_%=;\n"
        "add.u32 n, n, 1;\n"
        "setp.lt.u32 p, n, 4194304;\n"
        "@p bra WAIT_%=;\n"
        "trap;\n"
        "DONE_%=:\n"
        "}\n" :: "r"(b0), "r"(p0), "r"(b1), "r"(p1), "r"(b2), "r"(p2), "r"(b3), "r"(p3) : "memory");
}
__device__ __forceinline__ void mbar_wait2(uint32_t b0, uint32_t p0, uint32_t b1, uint32_t p1) {
    asm volatile(
        "{\n"
        ".reg .pred p, q;\n"
        ".reg .u32 n;\n"
        "mov.u32 n, 0;\n"
        "WAIT_%=:\n"
        "mbarrier.try_wait.parity.shared::cta.b64 p, [%0], %1" HINT ";\n"
        "mbarrier.try_wait.parity.shared::cta.b64 q, [%2], %3" HINT ";\n"
        "and.pred p, p, q;\n"
        "@p bra DONE_%=;\n"
        "add.u32 n, n, 1;\n"
        "setp.lt.u32 p, n, 4194304;\n"
        "@p bra WAIT_%=;\n"
        "trap;\n"
        "DONE_%=:\n"
        "}\n" :: "r"(b0), "r"(p0), "r"(b1), "r"(p1) : "memory");
}
__device__ __forceinline__ void mbar_wait_unless(uint32_t ok, uint32_t bar, uint32_t parity) {
    asm volatile(
        "{\n"
        ".reg .pred p;\n"
        ".reg .u32 n;\n"
        "setp.ne.u32 p, %2, 0;\n"
        "vote.sync.all.pred p, p, 0xffffffff;\n"
        "@p bra DONE_%=;\n"
        "mov.u32 n, 0;\n"
        "WAIT_%=:\n"
        "mbarrier.try_wait.parity.shared::cta.b64 p, [%0], %1" HINT ";\n"
        "@p bra DONE_%=;\n"
        "add.u32 n, n, 1;\n"
        "setp.lt.u32 p, n, 4194304;\n"
        "@p bra WAIT_%=;\n"
        "trap;\n"
        "DONE_%=:\n"
        "}\n" :: "r"(bar), "r"(parity), "r"(ok) : "memory");
}
__device__ __forceinline__ void mbar_wait2_unless(uint32_t ok, uint32_t b0, uint32_t p0, uint32_t b1, uint32_t p1) {
    asm volatile(
        "{\n"
        ".reg .pred p, q;\n"
        ".reg .u32 n;\n"
        "setp.ne.u32 p, %4, 0;\n"
        "vote.sync.all.pred p, p, 0xffffffff;\n"
        "@p bra DONE_%=;\n"
        "mov.u32 n, 0;\n"
        "WAIT_%=:\n"
        "mbarrier.try_wait.parity.shared::cta.b64 p, [%0], %1" HINT ";\n"
        "mbarrier.try_wait.parity.shared::cta.b64 q, [%2], %3" HINT ";\n"
        "and.pred p, p, q;\n"
        "@p bra DONE_%=;\n"
        "add.u32 n, n, 1;\n"
        "setp.lt.u32 p, n, 4194304;\n"
        "@p bra WAIT_%=;\n"
        "trap;\n"
        "DONE_%=:\n"
        "}\n" :: "r"(b0), "r"(p0), "r"(b1), "r"(p1), "r"(ok) : "memory");
}
__device__ __forceinline__ void mbar_wait4_unless(uint32_t ok, uint32_t b0, uint32_t p0, uint32_t b1, uint32_t p1, uint32_t b2,
                                                  uint32_t p2, uint32_t b3, uint32_t p3) {
    asm volatile(
        "{\n"
        ".reg .pred p, q, r, s;\n"
        ".reg .u32 n;\n"
        "setp.ne.u32 p, %8, 0;\n"
        "vote.sync.all.pred p, p, 0xffffffff;\n"
        "@p bra DONE_%=;\n"
        "mov.u32 n, 0;\n"
        "WAIT_%=:\n"
        "mbarrier.try_wait.parity.shared::cta.b64 p, [%0], %1" HINT ";\n"
        "mbarrier.try_wait.parity.shared::cta.b64 q, [%2], %3" HINT ";\n"
        "mbarrier.try_wait.parity.shared::cta.b64 r, [%4], %5" HINT ";\n"
        "mbarrier.try_wait.parity.shared::cta.b64 s, [%6], %7" HINT ";\n"
        "and.pred p, p, q;\n"
        "and.pred r, r, s;\n"
        "and.pred p, p, r;\n"
        "@p bra DONE_%=;\n"
        "add.u32 n, n, 1;\n"
        "setp.lt.u32 p, n, 4194304;\n"
        "@p bra WAIT_%=;\n"
        "trap;\n"
        "DONE_%=:\n"
        "}\n" :: "r"(b0), "r"(p0), "r"(b1), "r"(p1), "r"(b2), "r"(p2), "r"(b3), "r"(p3), "r"(ok) : "memory");
}
__device__ __forceinline__ void sched_fence(uint32_t zero, uint32_t a, uint32_t b, uint32_t c, uint32_t d, uint32_t e = 0,
                                            uint32_t f = 0, uint32_t g = 0, uint32_t h = 0, uint32_t i = 0, uint32_t j = 0,
                                            uint32_t k = 0) {
    asm volatile("{\n.reg .pred p;\n.reg .u32 n;\nsetp.eq.u32 p, %0, 0;\n@p bra.uni DONE_%=;\nmov.u32 n, %0;\nSPIN_%=:\n"
                 "nanosleep.u32 %1;\nnanosleep.u32 %2;\nnanosleep.u32 %3;\nnanosleep.u32 %4;\nnanosleep.u32 %5;\n"
                 "nanosleep.u32 %6;\nnanosleep.u32 %7;\nnanosleep.u32 %8;\nnanosleep.u32 %9;\nnanosleep.u32 %10;\n"
                 "nanosleep.u32 %11;\nsub.u32 n, n, 1;\nsetp.ne.u32 p, n, 0;\n@p bra.uni SPIN_%=;\nDONE_%=:\n}\n"
                 :: "r"(zero), "r"(a), "r"(b), "r"(c), "r"(d), "r"(e), "r"(f), "r"(g), "r"(h), "r"(i), "r"(j), "r"(k) : "memory");
}
__device__ __forceinline__ void sched_fence2(uint32_t zero, float& x, float& y, uint32_t a, uint32_t b, uint32_t c, uint32_t d = 0,
                                             uint32_t e = 0, uint32_t f = 0) {
    asm volatile("{\n.reg .pred p;\n.reg .u32 n;\nsetp.eq.u32 p, %2, 0;\n@p bra.uni DONE_%=;\nmov.u32 n, %2;\nSPIN_%=:\n"
                 "add.f32 %0, %0, %1;\nadd.f32 %1, %1, %0;\nnanosleep.u32 %3;\nnanosleep.u32 %4;\nnanosleep.u32 %5;\n"
                 "nanosleep.u32 %6;\nnanosleep.u32 %7;\nnanosleep.u32 %8;\n"
                 "sub.u32 n, n, 1;\nsetp.ne.u32 p, n, 0;\n@p bra.uni SPIN_%=;\nDONE_%=:\n}\n"
                 : "+f"(x), "+f"(y) : "r"(zero), "r"(a), "r"(b), "r"(c), "r"(d), "r"(e), "r"(f) : "memory");
}
template <int N> __device__ __forceinline__ void use_regs(const uint32_t* v) {
    if constexpr (N >= 4) {
        asm volatile("nanosleep.u32 %0;\nnanosleep.u32 %1;\nnanosleep.u32 %2;\nnanosleep.u32 %3;\n" :: "r"(v[0]), "r"(v[1]), "r"(v[2]), "r"(v[3]) : "memory");
        use_regs<N - 4>(v + 4);
    } else if constexpr (N > 0) {
        asm volatile("nanosleep.u32 %0;\n" :: "r"(v[0]) : "memory");
        use_regs<N - 1>(v + 1);
    }
}
template <int N> __device__ __forceinline__ void sched_fence_n(uint32_t zero, const uint32_t (&v)[N]) {
    if (__builtin_expect(zero != 0, 0)) {
#pragma unroll 1
        for (uint32_t n = zero; n; n--) use_regs<N>(v);
    }
}
__device__ __forceinline__ void sched_fence_rw(uint32_t zero, uint32_t (&v)[13]) {
    asm volatile("{\n.reg .pred p;\n.reg .u32 n;\nsetp.eq.u32 p, %13, 0;\n@p bra.uni DONE_%=;\nmov.u32 n, %13;\nSPIN_%=:\n"
                 "add.u32 %0, %0, %1;\nadd.u32 %1, %1, %2;\nadd.u32 %2, %2, %3;\nadd.u32 %3, %3, %4;\nadd.u32 %4, %4, %5;\n"
                 "add.u32 %5, %5, %6;\nadd.u32 %6, %6, %7;\nadd.u32 %7, %7, %8;\nadd.u32 %8, %8, %9;\nadd.u32 %9, %9, %10;\n"
                 "add.u32 %10, %10, %11;\nadd.u32 %11, %11, %12;\nadd.u32 %12, %12, %0;\n"
                 "sub.u32 n, n, 1;\nsetp.ne.u32 p, n, 0;\n@p bra.uni SPIN_%=;\nDONE_%=:\n}\n"
                 : "+r"(v[0]), "+r"(v[1]), "+r"(v[2]), "+r"(v[3]), "+r"(v[4]), "+r"(v[5]), "+r"(v[6]), "+r"(v[7]), "+r"(v[8]),
                   "+r"(v[9]), "+r"(v[10]), "+r"(v[11]), "+r"(v[12]) : "r"(zero) : "memory");
}
__device__ __forceinline__ void mbar_arrive(uint32_t bar) {
    asm volatile("mbarrier.arrive.shared::cta.b64 _, [%0];\n" :: "r"(bar) : "memory");
}
__device__ __forceinline__ void mbar_arrive_n(uint32_t bar, uint32_t n) {
    asm volatile("mbarrier.arrive.shared::cta.b64 _, [%0], %1;\n" :: "r"(bar), "r"(n) : "memory");
}
__device__ __forceinline__ void mbar_arrive_expect_tx(uint32_t bar, uint32_t bytes) {
    asm volatile("mbarrier.arrive.expect_tx.shared::cta.b64 _, [%0], %1;\n" :: "r"(bar), "r"(bytes) : "memory");
}
__device__ __forceinline__ void stg128_if(bool p, void* addr, uint32_t x, uint32_t y, uint32_t z, uint32_t w) {
    asm volatile("{\n.reg .pred q;\nsetp.ne.b32 q, %5, 0;\n@q st.global.L1::no_allocate.v4.b32 [%0], {%1, %2, %3, %4};\n}\n"
                 :: "l"(addr), "r"(x), "r"(y), "r"(z), "r"(w), "r"((uint32_t)p) : "memory");
}
__device__ __forceinline__ void stsm_x4(uint32_t addr, uint32_t r0, uint32_t r1, uint32_t r2, uint32_t r3) {
    asm volatile("stmatrix.sync.aligned.m8n8.x4.shared.b16 [%0], {%1, %2, %3, %4};\n"
                 :: "r"(addr), "r"(r0), "r"(r1), "r"(r2), "r"(r3) : "memory");
}
__device__ __forceinline__ void stsm_x2(uint32_t addr, uint32_t r0, uint32_t r1) {
    asm volatile("stmatrix.sync.aligned.m8n8.x2.shared.b16 [%0], {%1, %2};\n" :: "r"(addr), "r"(r0), "r"(r1) : "memory");
}
__device__ __forceinline__ void sts128(uint32_t addr, uint32_t r0, uint32_t r1, uint32_t r2, uint32_t r3) {
    asm volatile("st.shared.v4.b32 [%0], {%1, %2, %3, %4};\n" :: "r"(addr), "r"(r0), "r"(r1), "r"(r2), "r"(r3) : "memory");
}
__device__ __forceinline__ void sts128_if(uint32_t p, uint32_t addr, uint32_t r0, uint32_t r1, uint32_t r2, uint32_t r3) {
    asm volatile("{\n.reg .pred q;\nsetp.ne.b32 q, %5, 0;\n@q st.shared.v4.b32 [%0], {%1, %2, %3, %4};\n}\n"
                 :: "r"(addr), "r"(r0), "r"(r1), "r"(r2), "r"(r3), "r"(p) : "memory");
}
__device__ __forceinline__ void sts32(uint32_t addr, uint32_t v) {
    asm volatile("st.shared.b32 [%0], %1;\n" :: "r"(addr), "r"(v) : "memory");
}
__device__ __forceinline__ uint32_t lds32(uint32_t addr) {
    uint32_t v;
    asm volatile("ld.shared.b32 %0, [%1];\n" : "=r"(v) : "r"(addr) : "memory");
    return v;
}
__device__ __forceinline__ void ldg_nc_v4(uint32_t (&r)[4], const void* p) {
    asm volatile("ld.global.nc.L1::no_allocate.v4.u32 {%0, %1, %2, %3}, [%4];\n"
                 : "=r"(r[0]), "=r"(r[1]), "=r"(r[2]), "=r"(r[3]) : "l"(p));
}
__device__ __forceinline__ uint32_t ldg_u32(const void* p) {
    uint32_t v;
    asm volatile("ld.global.nc.L1::evict_first.u32 %0, [%1];\n" : "=r"(v) : "l"(p));
    return v;
}
__device__ __forceinline__ void ldg_u64(const void* p, uint32_t& a, uint32_t& b) {
    asm volatile("ld.global.nc.L1::evict_first.v2.u32 {%0, %1}, [%2];\n" : "=r"(a), "=r"(b) : "l"(p));
}
__device__ __forceinline__ void prefetch_l2(const void* p) {
    asm volatile("prefetch.global.L2 [%0];\n" :: "l"(p));
}
__device__ __forceinline__ void cp_async16(uint32_t dst, const void* src) {
    asm volatile("cp.async.cg.shared.global [%0], [%1], 16;\n" :: "r"(dst), "l"(src) : "memory");
}
__device__ __forceinline__ float ex2_ftz(float x) {
    float y;
    asm("ex2.approx.ftz.f32 %0, %1;\n" : "=f"(y) : "f"(x));
    return y;
}
__device__ __forceinline__ float lg2_ftz(float x) {
    float y;
    asm("lg2.approx.ftz.f32 %0, %1;\n" : "=f"(y) : "f"(x));
    return y;
}
__device__ __forceinline__ float rcp_ftz(float x) {
    float y;
    asm("rcp.approx.ftz.f32 %0, %1;\n" : "=f"(y) : "f"(x));
    return y;
}
__device__ __forceinline__ float rsqrt_ftz(float x) {
    float y;
    asm("rsqrt.approx.ftz.f32 %0, %1;\n" : "=f"(y) : "f"(x));
    return y;
}

__device__ __forceinline__ bool elect_one() {
    uint32_t p;
    asm volatile("{\n.reg .pred q;\nelect.sync _|q, 0xffffffff;\nselp.u32 %0, 1, 0, q;\n}\n" : "=r"(p));
    return p != 0;
}
__device__ __forceinline__ void ldsm_x4(uint32_t (&r)[4], uint32_t addr) {
    asm volatile("ldmatrix.sync.aligned.m8n8.x4.shared.b16 {%0, %1, %2, %3}, [%4];\n"
                 : "=r"(r[0]), "=r"(r[1]), "=r"(r[2]), "=r"(r[3]) : "r"(addr) : "memory");
}
__device__ __forceinline__ void ldsm_x2(uint32_t& r0, uint32_t& r1, uint32_t addr) {
    asm volatile("ldmatrix.sync.aligned.m8n8.x2.shared.b16 {%0, %1}, [%2];\n" : "=r"(r0), "=r"(r1) : "r"(addr) : "memory");
}
__device__ __forceinline__ void tma_2d(uint32_t dst, const CUtensorMap* map, uint32_t bar, int c0, int c1) {
    asm volatile("cp.async.bulk.tensor.2d.shared::cluster.global.mbarrier::complete_tx::bytes [%0], [%1, {%3, %4}], [%2];\n"
                 :: "r"(dst), "l"(reinterpret_cast<uint64_t>(map)), "r"(bar), "r"(c0), "r"(c1) : "memory");
}
__device__ __forceinline__ void tma_3d(uint32_t dst, const CUtensorMap* map, uint32_t bar, int c0, int c1, int c2) {
    asm volatile("cp.async.bulk.tensor.3d.shared::cluster.global.mbarrier::complete_tx::bytes [%0], [%1, {%3, %4, %5}], [%2];\n"
                 :: "r"(dst), "l"(reinterpret_cast<uint64_t>(map)), "r"(bar), "r"(c0), "r"(c1), "r"(c2) : "memory");
}
constexpr uint64_t EVICT_FIRST = 0x12F0000000000000ull;
__device__ __forceinline__ void tma_3d_x(uint32_t dst, const CUtensorMap* map, uint32_t bar, int c0, int c1, int c2) {
    if (CH & 50)
        asm volatile("cp.async.bulk.tensor.3d.shared::cluster.global.mbarrier::complete_tx::bytes.L2::cache_hint [%0], [%1, {%3, %4, %5}], [%2], %6;\n"
                     :: "r"(dst), "l"(reinterpret_cast<uint64_t>(map)), "r"(bar), "r"(c0), "r"(c1), "r"(c2),
                        "l"((CH & 2) || (blockIdx.x & 1) == ((CH >> 5) & 1) ? EVICT_FIRST : 0x1000000000000000ull) : "memory");
    else tma_3d(dst, map, bar, c0, c1, c2);
}
__device__ __forceinline__ void tma_store_4d(const CUtensorMap* map, uint32_t src, int c0, int c1, int c2, int c3) {
    asm volatile("cp.async.bulk.tensor.4d.global.shared::cta.tile.bulk_group [%0, {%2, %3, %4, %5}], [%1];\n"
                 :: "l"(reinterpret_cast<uint64_t>(map)), "r"(src), "r"(c0), "r"(c1), "r"(c2), "r"(c3) : "memory");
}
__device__ __forceinline__ void mbar_arrive_if(uint32_t bar, uint32_t cnt) {
    asm volatile("{\n.reg .pred q;\nsetp.ne.b32 q, %1, 0;\n@q mbarrier.arrive.shared::cta.b64 _, [%0], %1;\n}\n"
                 :: "r"(bar), "r"(cnt) : "memory");
}

template <int BOFF, int AOFF, int NA>
__device__ __forceinline__ void mma_qkv_a(float (&d)[48], const uint32_t (&a)[NA][4], uint64_t descB) {
    asm volatile(
        "{\n"
        ".reg .pred p0, p1;\n"
        ".reg .b64 ta, ta0, tb, tb0;\n"
        "setp.ne.b32 p0, 0, 0;\n"
        "setp.eq.b32 p1, 0, 0;\n"
        "add.s64 tb0, %72, %73;\n"
        "add.s64 tb, tb0, 0;\n"
        "wgmma.mma_async.sync.aligned.m64n96k16.f32.bf16.bf16 {%0, %1, %2, %3, %4, %5, %6, %7, %8, %9, %10, %11, %12, %13, %14, %15, %16, %17, %18, %19, %20, %21, %22, %23, %24, %25, %26, %27, %28, %29, %30, %31, %32, %33, %34, %35, %36, %37, %38, %39, %40, %41, %42, %43, %44, %45, %46, %47}, {%48, %49, %50, %51}, tb, p0, 1, 1, 1;\n"
        "add.s64 tb, tb0, 32;\n"
        "wgmma.mma_async.sync.aligned.m64n96k16.f32.bf16.bf16 {%0, %1, %2, %3, %4, %5, %6, %7, %8, %9, %10, %11, %12, %13, %14, %15, %16, %17, %18, %19, %20, %21, %22, %23, %24, %25, %26, %27, %28, %29, %30, %31, %32, %33, %34, %35, %36, %37, %38, %39, %40, %41, %42, %43, %44, %45, %46, %47}, {%52, %53, %54, %55}, tb, p1, 1, 1, 1;\n"
        "add.s64 tb, tb0, 64;\n"
        "wgmma.mma_async.sync.aligned.m64n96k16.f32.bf16.bf16 {%0, %1, %2, %3, %4, %5, %6, %7, %8, %9, %10, %11, %12, %13, %14, %15, %16, %17, %18, %19, %20, %21, %22, %23, %24, %25, %26, %27, %28, %29, %30, %31, %32, %33, %34, %35, %36, %37, %38, %39, %40, %41, %42, %43, %44, %45, %46, %47}, {%56, %57, %58, %59}, tb, p1, 1, 1, 1;\n"
        "add.s64 tb, tb0, 96;\n"
        "wgmma.mma_async.sync.aligned.m64n96k16.f32.bf16.bf16 {%0, %1, %2, %3, %4, %5, %6, %7, %8, %9, %10, %11, %12, %13, %14, %15, %16, %17, %18, %19, %20, %21, %22, %23, %24, %25, %26, %27, %28, %29, %30, %31, %32, %33, %34, %35, %36, %37, %38, %39, %40, %41, %42, %43, %44, %45, %46, %47}, {%60, %61, %62, %63}, tb, p1, 1, 1, 1;\n"
        "add.s64 tb, tb0, 1536;\n"
        "wgmma.mma_async.sync.aligned.m64n96k16.f32.bf16.bf16 {%0, %1, %2, %3, %4, %5, %6, %7, %8, %9, %10, %11, %12, %13, %14, %15, %16, %17, %18, %19, %20, %21, %22, %23, %24, %25, %26, %27, %28, %29, %30, %31, %32, %33, %34, %35, %36, %37, %38, %39, %40, %41, %42, %43, %44, %45, %46, %47}, {%64, %65, %66, %67}, tb, p1, 1, 1, 1;\n"
        "add.s64 tb, tb0, 1568;\n"
        "wgmma.mma_async.sync.aligned.m64n96k16.f32.bf16.bf16 {%0, %1, %2, %3, %4, %5, %6, %7, %8, %9, %10, %11, %12, %13, %14, %15, %16, %17, %18, %19, %20, %21, %22, %23, %24, %25, %26, %27, %28, %29, %30, %31, %32, %33, %34, %35, %36, %37, %38, %39, %40, %41, %42, %43, %44, %45, %46, %47}, {%68, %69, %70, %71}, tb, p1, 1, 1, 1;\n"
        "}\n"
        : "=f"(d[0]), "=f"(d[1]), "=f"(d[2]), "=f"(d[3]), "=f"(d[4]), "=f"(d[5]), "=f"(d[6]), "=f"(d[7]), "=f"(d[8]), "=f"(d[9]), "=f"(d[10]), "=f"(d[11]), "=f"(d[12]), "=f"(d[13]), "=f"(d[14]), "=f"(d[15]), "=f"(d[16]), "=f"(d[17]), "=f"(d[18]), "=f"(d[19]), "=f"(d[20]), "=f"(d[21]), "=f"(d[22]), "=f"(d[23]), "=f"(d[24]), "=f"(d[25]), "=f"(d[26]), "=f"(d[27]), "=f"(d[28]), "=f"(d[29]), "=f"(d[30]), "=f"(d[31]), "=f"(d[32]), "=f"(d[33]), "=f"(d[34]), "=f"(d[35]), "=f"(d[36]), "=f"(d[37]), "=f"(d[38]), "=f"(d[39]), "=f"(d[40]), "=f"(d[41]), "=f"(d[42]), "=f"(d[43]), "=f"(d[44]), "=f"(d[45]), "=f"(d[46]), "=f"(d[47])
        : "r"(a[AOFF + 0][0]), "r"(a[AOFF + 0][1]), "r"(a[AOFF + 0][2]), "r"(a[AOFF + 0][3]), "r"(a[AOFF + 1][0]), "r"(a[AOFF + 1][1]), "r"(a[AOFF + 1][2]), "r"(a[AOFF + 1][3]), "r"(a[AOFF + 2][0]), "r"(a[AOFF + 2][1]), "r"(a[AOFF + 2][2]), "r"(a[AOFF + 2][3]), "r"(a[AOFF + 3][0]), "r"(a[AOFF + 3][1]), "r"(a[AOFF + 3][2]), "r"(a[AOFF + 3][3]), "r"(a[AOFF + 4][0]), "r"(a[AOFF + 4][1]), "r"(a[AOFF + 4][2]), "r"(a[AOFF + 4][3]), "r"(a[AOFF + 5][0]), "r"(a[AOFF + 5][1]), "r"(a[AOFF + 5][2]), "r"(a[AOFF + 5][3]), "l"(descB), "n"(BOFF >> 4));
}

template <int BOFF, int AOFF, int NA>
__device__ __forceinline__ void mma_qkv_b(float (&d)[48], const uint32_t (&a)[NA][4], uint64_t descB) {
    asm volatile(
        "{\n"
        ".reg .pred p0, p1;\n"
        ".reg .b64 ta, ta0, tb, tb0;\n"
        "setp.ne.b32 p0, 0, 0;\n"
        "setp.eq.b32 p1, 0, 0;\n"
        "add.s64 tb0, %72, %73;\n"
        "add.s64 tb, tb0, 1600;\n"
        "wgmma.mma_async.sync.aligned.m64n96k16.f32.bf16.bf16 {%0, %1, %2, %3, %4, %5, %6, %7, %8, %9, %10, %11, %12, %13, %14, %15, %16, %17, %18, %19, %20, %21, %22, %23, %24, %25, %26, %27, %28, %29, %30, %31, %32, %33, %34, %35, %36, %37, %38, %39, %40, %41, %42, %43, %44, %45, %46, %47}, {%48, %49, %50, %51}, tb, p1, 1, 1, 1;\n"
        "add.s64 tb, tb0, 1632;\n"
        "wgmma.mma_async.sync.aligned.m64n96k16.f32.bf16.bf16 {%0, %1, %2, %3, %4, %5, %6, %7, %8, %9, %10, %11, %12, %13, %14, %15, %16, %17, %18, %19, %20, %21, %22, %23, %24, %25, %26, %27, %28, %29, %30, %31, %32, %33, %34, %35, %36, %37, %38, %39, %40, %41, %42, %43, %44, %45, %46, %47}, {%52, %53, %54, %55}, tb, p1, 1, 1, 1;\n"
        "add.s64 tb, tb0, 3072;\n"
        "wgmma.mma_async.sync.aligned.m64n96k16.f32.bf16.bf16 {%0, %1, %2, %3, %4, %5, %6, %7, %8, %9, %10, %11, %12, %13, %14, %15, %16, %17, %18, %19, %20, %21, %22, %23, %24, %25, %26, %27, %28, %29, %30, %31, %32, %33, %34, %35, %36, %37, %38, %39, %40, %41, %42, %43, %44, %45, %46, %47}, {%56, %57, %58, %59}, tb, p1, 1, 1, 1;\n"
        "add.s64 tb, tb0, 3104;\n"
        "wgmma.mma_async.sync.aligned.m64n96k16.f32.bf16.bf16 {%0, %1, %2, %3, %4, %5, %6, %7, %8, %9, %10, %11, %12, %13, %14, %15, %16, %17, %18, %19, %20, %21, %22, %23, %24, %25, %26, %27, %28, %29, %30, %31, %32, %33, %34, %35, %36, %37, %38, %39, %40, %41, %42, %43, %44, %45, %46, %47}, {%60, %61, %62, %63}, tb, p1, 1, 1, 1;\n"
        "add.s64 tb, tb0, 3136;\n"
        "wgmma.mma_async.sync.aligned.m64n96k16.f32.bf16.bf16 {%0, %1, %2, %3, %4, %5, %6, %7, %8, %9, %10, %11, %12, %13, %14, %15, %16, %17, %18, %19, %20, %21, %22, %23, %24, %25, %26, %27, %28, %29, %30, %31, %32, %33, %34, %35, %36, %37, %38, %39, %40, %41, %42, %43, %44, %45, %46, %47}, {%64, %65, %66, %67}, tb, p1, 1, 1, 1;\n"
        "add.s64 tb, tb0, 3168;\n"
        "wgmma.mma_async.sync.aligned.m64n96k16.f32.bf16.bf16 {%0, %1, %2, %3, %4, %5, %6, %7, %8, %9, %10, %11, %12, %13, %14, %15, %16, %17, %18, %19, %20, %21, %22, %23, %24, %25, %26, %27, %28, %29, %30, %31, %32, %33, %34, %35, %36, %37, %38, %39, %40, %41, %42, %43, %44, %45, %46, %47}, {%68, %69, %70, %71}, tb, p1, 1, 1, 1;\n"
        "}\n"
        : "+f"(d[0]), "+f"(d[1]), "+f"(d[2]), "+f"(d[3]), "+f"(d[4]), "+f"(d[5]), "+f"(d[6]), "+f"(d[7]), "+f"(d[8]), "+f"(d[9]), "+f"(d[10]), "+f"(d[11]), "+f"(d[12]), "+f"(d[13]), "+f"(d[14]), "+f"(d[15]), "+f"(d[16]), "+f"(d[17]), "+f"(d[18]), "+f"(d[19]), "+f"(d[20]), "+f"(d[21]), "+f"(d[22]), "+f"(d[23]), "+f"(d[24]), "+f"(d[25]), "+f"(d[26]), "+f"(d[27]), "+f"(d[28]), "+f"(d[29]), "+f"(d[30]), "+f"(d[31]), "+f"(d[32]), "+f"(d[33]), "+f"(d[34]), "+f"(d[35]), "+f"(d[36]), "+f"(d[37]), "+f"(d[38]), "+f"(d[39]), "+f"(d[40]), "+f"(d[41]), "+f"(d[42]), "+f"(d[43]), "+f"(d[44]), "+f"(d[45]), "+f"(d[46]), "+f"(d[47])
        : "r"(a[AOFF + 0][0]), "r"(a[AOFF + 0][1]), "r"(a[AOFF + 0][2]), "r"(a[AOFF + 0][3]), "r"(a[AOFF + 1][0]), "r"(a[AOFF + 1][1]), "r"(a[AOFF + 1][2]), "r"(a[AOFF + 1][3]), "r"(a[AOFF + 2][0]), "r"(a[AOFF + 2][1]), "r"(a[AOFF + 2][2]), "r"(a[AOFF + 2][3]), "r"(a[AOFF + 3][0]), "r"(a[AOFF + 3][1]), "r"(a[AOFF + 3][2]), "r"(a[AOFF + 3][3]), "r"(a[AOFF + 4][0]), "r"(a[AOFF + 4][1]), "r"(a[AOFF + 4][2]), "r"(a[AOFF + 4][3]), "r"(a[AOFF + 5][0]), "r"(a[AOFF + 5][1]), "r"(a[AOFF + 5][2]), "r"(a[AOFF + 5][3]), "l"(descB), "n"(BOFF >> 4));
}

template <int BOFF, int AOFF, int NA>
__device__ __forceinline__ void mma_v_a(float (&d)[48], const uint32_t (&a)[NA][4], uint64_t descB) {
    asm volatile(
        "{\n"
        ".reg .pred p0, p1;\n"
        ".reg .b64 ta, ta0, tb, tb0;\n"
        "setp.ne.b32 p0, 0, 0;\n"
        "setp.eq.b32 p1, 0, 0;\n"
        "add.s64 tb0, %72, %73;\n"
        "add.s64 tb, tb0, 0;\n"
        "wgmma.mma_async.sync.aligned.m64n96k16.f32.bf16.bf16 {%0, %1, %2, %3, %4, %5, %6, %7, %8, %9, %10, %11, %12, %13, %14, %15, %16, %17, %18, %19, %20, %21, %22, %23, %24, %25, %26, %27, %28, %29, %30, %31, %32, %33, %34, %35, %36, %37, %38, %39, %40, %41, %42, %43, %44, %45, %46, %47}, {%48, %49, %50, %51}, tb, p0, 1, 1, 1;\n"
        "add.s64 tb, tb0, 32;\n"
        "wgmma.mma_async.sync.aligned.m64n96k16.f32.bf16.bf16 {%0, %1, %2, %3, %4, %5, %6, %7, %8, %9, %10, %11, %12, %13, %14, %15, %16, %17, %18, %19, %20, %21, %22, %23, %24, %25, %26, %27, %28, %29, %30, %31, %32, %33, %34, %35, %36, %37, %38, %39, %40, %41, %42, %43, %44, %45, %46, %47}, {%52, %53, %54, %55}, tb, p1, 1, 1, 1;\n"
        "add.s64 tb, tb0, 64;\n"
        "wgmma.mma_async.sync.aligned.m64n96k16.f32.bf16.bf16 {%0, %1, %2, %3, %4, %5, %6, %7, %8, %9, %10, %11, %12, %13, %14, %15, %16, %17, %18, %19, %20, %21, %22, %23, %24, %25, %26, %27, %28, %29, %30, %31, %32, %33, %34, %35, %36, %37, %38, %39, %40, %41, %42, %43, %44, %45, %46, %47}, {%56, %57, %58, %59}, tb, p1, 1, 1, 1;\n"
        "add.s64 tb, tb0, 96;\n"
        "wgmma.mma_async.sync.aligned.m64n96k16.f32.bf16.bf16 {%0, %1, %2, %3, %4, %5, %6, %7, %8, %9, %10, %11, %12, %13, %14, %15, %16, %17, %18, %19, %20, %21, %22, %23, %24, %25, %26, %27, %28, %29, %30, %31, %32, %33, %34, %35, %36, %37, %38, %39, %40, %41, %42, %43, %44, %45, %46, %47}, {%60, %61, %62, %63}, tb, p1, 1, 1, 1;\n"
        "add.s64 tb, tb0, 128;\n"
        "wgmma.mma_async.sync.aligned.m64n96k16.f32.bf16.bf16 {%0, %1, %2, %3, %4, %5, %6, %7, %8, %9, %10, %11, %12, %13, %14, %15, %16, %17, %18, %19, %20, %21, %22, %23, %24, %25, %26, %27, %28, %29, %30, %31, %32, %33, %34, %35, %36, %37, %38, %39, %40, %41, %42, %43, %44, %45, %46, %47}, {%64, %65, %66, %67}, tb, p1, 1, 1, 1;\n"
        "add.s64 tb, tb0, 160;\n"
        "wgmma.mma_async.sync.aligned.m64n96k16.f32.bf16.bf16 {%0, %1, %2, %3, %4, %5, %6, %7, %8, %9, %10, %11, %12, %13, %14, %15, %16, %17, %18, %19, %20, %21, %22, %23, %24, %25, %26, %27, %28, %29, %30, %31, %32, %33, %34, %35, %36, %37, %38, %39, %40, %41, %42, %43, %44, %45, %46, %47}, {%68, %69, %70, %71}, tb, p1, 1, 1, 1;\n"
        "}\n"
        : "=f"(d[0]), "=f"(d[1]), "=f"(d[2]), "=f"(d[3]), "=f"(d[4]), "=f"(d[5]), "=f"(d[6]), "=f"(d[7]), "=f"(d[8]), "=f"(d[9]), "=f"(d[10]), "=f"(d[11]), "=f"(d[12]), "=f"(d[13]), "=f"(d[14]), "=f"(d[15]), "=f"(d[16]), "=f"(d[17]), "=f"(d[18]), "=f"(d[19]), "=f"(d[20]), "=f"(d[21]), "=f"(d[22]), "=f"(d[23]), "=f"(d[24]), "=f"(d[25]), "=f"(d[26]), "=f"(d[27]), "=f"(d[28]), "=f"(d[29]), "=f"(d[30]), "=f"(d[31]), "=f"(d[32]), "=f"(d[33]), "=f"(d[34]), "=f"(d[35]), "=f"(d[36]), "=f"(d[37]), "=f"(d[38]), "=f"(d[39]), "=f"(d[40]), "=f"(d[41]), "=f"(d[42]), "=f"(d[43]), "=f"(d[44]), "=f"(d[45]), "=f"(d[46]), "=f"(d[47])
        : "r"(a[AOFF + 0][0]), "r"(a[AOFF + 0][1]), "r"(a[AOFF + 0][2]), "r"(a[AOFF + 0][3]), "r"(a[AOFF + 1][0]), "r"(a[AOFF + 1][1]), "r"(a[AOFF + 1][2]), "r"(a[AOFF + 1][3]), "r"(a[AOFF + 2][0]), "r"(a[AOFF + 2][1]), "r"(a[AOFF + 2][2]), "r"(a[AOFF + 2][3]), "r"(a[AOFF + 3][0]), "r"(a[AOFF + 3][1]), "r"(a[AOFF + 3][2]), "r"(a[AOFF + 3][3]), "r"(a[AOFF + 4][0]), "r"(a[AOFF + 4][1]), "r"(a[AOFF + 4][2]), "r"(a[AOFF + 4][3]), "r"(a[AOFF + 5][0]), "r"(a[AOFF + 5][1]), "r"(a[AOFF + 5][2]), "r"(a[AOFF + 5][3]), "l"(descB), "n"(BOFF >> 4));
}

template <int BOFF, int AOFF, int NA>
__device__ __forceinline__ void mma_v_b(float (&d)[48], const uint32_t (&a)[NA][4], uint64_t descB) {
    asm volatile(
        "{\n"
        ".reg .pred p0, p1;\n"
        ".reg .b64 ta, ta0, tb, tb0;\n"
        "setp.ne.b32 p0, 0, 0;\n"
        "setp.eq.b32 p1, 0, 0;\n"
        "add.s64 tb0, %72, %73;\n"
        "add.s64 tb, tb0, 192;\n"
        "wgmma.mma_async.sync.aligned.m64n96k16.f32.bf16.bf16 {%0, %1, %2, %3, %4, %5, %6, %7, %8, %9, %10, %11, %12, %13, %14, %15, %16, %17, %18, %19, %20, %21, %22, %23, %24, %25, %26, %27, %28, %29, %30, %31, %32, %33, %34, %35, %36, %37, %38, %39, %40, %41, %42, %43, %44, %45, %46, %47}, {%48, %49, %50, %51}, tb, p1, 1, 1, 1;\n"
        "add.s64 tb, tb0, 224;\n"
        "wgmma.mma_async.sync.aligned.m64n96k16.f32.bf16.bf16 {%0, %1, %2, %3, %4, %5, %6, %7, %8, %9, %10, %11, %12, %13, %14, %15, %16, %17, %18, %19, %20, %21, %22, %23, %24, %25, %26, %27, %28, %29, %30, %31, %32, %33, %34, %35, %36, %37, %38, %39, %40, %41, %42, %43, %44, %45, %46, %47}, {%52, %53, %54, %55}, tb, p1, 1, 1, 1;\n"
        "add.s64 tb, tb0, 256;\n"
        "wgmma.mma_async.sync.aligned.m64n96k16.f32.bf16.bf16 {%0, %1, %2, %3, %4, %5, %6, %7, %8, %9, %10, %11, %12, %13, %14, %15, %16, %17, %18, %19, %20, %21, %22, %23, %24, %25, %26, %27, %28, %29, %30, %31, %32, %33, %34, %35, %36, %37, %38, %39, %40, %41, %42, %43, %44, %45, %46, %47}, {%56, %57, %58, %59}, tb, p1, 1, 1, 1;\n"
        "add.s64 tb, tb0, 288;\n"
        "wgmma.mma_async.sync.aligned.m64n96k16.f32.bf16.bf16 {%0, %1, %2, %3, %4, %5, %6, %7, %8, %9, %10, %11, %12, %13, %14, %15, %16, %17, %18, %19, %20, %21, %22, %23, %24, %25, %26, %27, %28, %29, %30, %31, %32, %33, %34, %35, %36, %37, %38, %39, %40, %41, %42, %43, %44, %45, %46, %47}, {%60, %61, %62, %63}, tb, p1, 1, 1, 1;\n"
        "add.s64 tb, tb0, 320;\n"
        "wgmma.mma_async.sync.aligned.m64n96k16.f32.bf16.bf16 {%0, %1, %2, %3, %4, %5, %6, %7, %8, %9, %10, %11, %12, %13, %14, %15, %16, %17, %18, %19, %20, %21, %22, %23, %24, %25, %26, %27, %28, %29, %30, %31, %32, %33, %34, %35, %36, %37, %38, %39, %40, %41, %42, %43, %44, %45, %46, %47}, {%64, %65, %66, %67}, tb, p1, 1, 1, 1;\n"
        "add.s64 tb, tb0, 352;\n"
        "wgmma.mma_async.sync.aligned.m64n96k16.f32.bf16.bf16 {%0, %1, %2, %3, %4, %5, %6, %7, %8, %9, %10, %11, %12, %13, %14, %15, %16, %17, %18, %19, %20, %21, %22, %23, %24, %25, %26, %27, %28, %29, %30, %31, %32, %33, %34, %35, %36, %37, %38, %39, %40, %41, %42, %43, %44, %45, %46, %47}, {%68, %69, %70, %71}, tb, p1, 1, 1, 1;\n"
        "}\n"
        : "+f"(d[0]), "+f"(d[1]), "+f"(d[2]), "+f"(d[3]), "+f"(d[4]), "+f"(d[5]), "+f"(d[6]), "+f"(d[7]), "+f"(d[8]), "+f"(d[9]), "+f"(d[10]), "+f"(d[11]), "+f"(d[12]), "+f"(d[13]), "+f"(d[14]), "+f"(d[15]), "+f"(d[16]), "+f"(d[17]), "+f"(d[18]), "+f"(d[19]), "+f"(d[20]), "+f"(d[21]), "+f"(d[22]), "+f"(d[23]), "+f"(d[24]), "+f"(d[25]), "+f"(d[26]), "+f"(d[27]), "+f"(d[28]), "+f"(d[29]), "+f"(d[30]), "+f"(d[31]), "+f"(d[32]), "+f"(d[33]), "+f"(d[34]), "+f"(d[35]), "+f"(d[36]), "+f"(d[37]), "+f"(d[38]), "+f"(d[39]), "+f"(d[40]), "+f"(d[41]), "+f"(d[42]), "+f"(d[43]), "+f"(d[44]), "+f"(d[45]), "+f"(d[46]), "+f"(d[47])
        : "r"(a[AOFF + 0][0]), "r"(a[AOFF + 0][1]), "r"(a[AOFF + 0][2]), "r"(a[AOFF + 0][3]), "r"(a[AOFF + 1][0]), "r"(a[AOFF + 1][1]), "r"(a[AOFF + 1][2]), "r"(a[AOFF + 1][3]), "r"(a[AOFF + 2][0]), "r"(a[AOFF + 2][1]), "r"(a[AOFF + 2][2]), "r"(a[AOFF + 2][3]), "r"(a[AOFF + 3][0]), "r"(a[AOFF + 3][1]), "r"(a[AOFF + 3][2]), "r"(a[AOFF + 3][3]), "r"(a[AOFF + 4][0]), "r"(a[AOFF + 4][1]), "r"(a[AOFF + 4][2]), "r"(a[AOFF + 4][3]), "r"(a[AOFF + 5][0]), "r"(a[AOFF + 5][1]), "r"(a[AOFF + 5][2]), "r"(a[AOFF + 5][3]), "l"(descB), "n"(BOFF >> 4));
}
template <int V, int S0, int S1> struct Rng;
template <> struct Rng<0, 0, 3> {
template <int BOFF, int AOFF, int NA>
static __device__ __forceinline__ void run(float (&d)[48], const uint32_t (&a)[NA][4], uint64_t descB) {
    asm volatile(
        "{\n"
        ".reg .pred p0, p1;\n"
        ".reg .b64 ta, ta0, tb, tb0;\n"
        "setp.ne.b32 p0, 0, 0;\n"
        "setp.eq.b32 p1, 0, 0;\n"
        "add.s64 tb0, %60, %61;\n"
        "add.s64 tb, tb0, 0;\n"
        "wgmma.mma_async.sync.aligned.m64n96k16.f32.bf16.bf16 {%0, %1, %2, %3, %4, %5, %6, %7, %8, %9, %10, %11, %12, %13, %14, %15, %16, %17, %18, %19, %20, %21, %22, %23, %24, %25, %26, %27, %28, %29, %30, %31, %32, %33, %34, %35, %36, %37, %38, %39, %40, %41, %42, %43, %44, %45, %46, %47}, {%48, %49, %50, %51}, tb, p0, 1, 1, 1;\n"
        "add.s64 tb, tb0, 32;\n"
        "wgmma.mma_async.sync.aligned.m64n96k16.f32.bf16.bf16 {%0, %1, %2, %3, %4, %5, %6, %7, %8, %9, %10, %11, %12, %13, %14, %15, %16, %17, %18, %19, %20, %21, %22, %23, %24, %25, %26, %27, %28, %29, %30, %31, %32, %33, %34, %35, %36, %37, %38, %39, %40, %41, %42, %43, %44, %45, %46, %47}, {%52, %53, %54, %55}, tb, p1, 1, 1, 1;\n"
        "add.s64 tb, tb0, 64;\n"
        "wgmma.mma_async.sync.aligned.m64n96k16.f32.bf16.bf16 {%0, %1, %2, %3, %4, %5, %6, %7, %8, %9, %10, %11, %12, %13, %14, %15, %16, %17, %18, %19, %20, %21, %22, %23, %24, %25, %26, %27, %28, %29, %30, %31, %32, %33, %34, %35, %36, %37, %38, %39, %40, %41, %42, %43, %44, %45, %46, %47}, {%56, %57, %58, %59}, tb, p1, 1, 1, 1;\n"
        "}\n"
        : "=f"(d[0]), "=f"(d[1]), "=f"(d[2]), "=f"(d[3]), "=f"(d[4]), "=f"(d[5]), "=f"(d[6]), "=f"(d[7]), "=f"(d[8]), "=f"(d[9]), "=f"(d[10]), "=f"(d[11]), "=f"(d[12]), "=f"(d[13]), "=f"(d[14]), "=f"(d[15]), "=f"(d[16]), "=f"(d[17]), "=f"(d[18]), "=f"(d[19]), "=f"(d[20]), "=f"(d[21]), "=f"(d[22]), "=f"(d[23]), "=f"(d[24]), "=f"(d[25]), "=f"(d[26]), "=f"(d[27]), "=f"(d[28]), "=f"(d[29]), "=f"(d[30]), "=f"(d[31]), "=f"(d[32]), "=f"(d[33]), "=f"(d[34]), "=f"(d[35]), "=f"(d[36]), "=f"(d[37]), "=f"(d[38]), "=f"(d[39]), "=f"(d[40]), "=f"(d[41]), "=f"(d[42]), "=f"(d[43]), "=f"(d[44]), "=f"(d[45]), "=f"(d[46]), "=f"(d[47])
        : "r"(a[AOFF + 0][0]), "r"(a[AOFF + 0][1]), "r"(a[AOFF + 0][2]), "r"(a[AOFF + 0][3]), "r"(a[AOFF + 1][0]), "r"(a[AOFF + 1][1]), "r"(a[AOFF + 1][2]), "r"(a[AOFF + 1][3]), "r"(a[AOFF + 2][0]), "r"(a[AOFF + 2][1]), "r"(a[AOFF + 2][2]), "r"(a[AOFF + 2][3]), "l"(descB), "n"(BOFF >> 4));
}
};
template <> struct Rng<1, 0, 3> {
template <int BOFF, int AOFF, int NA>
static __device__ __forceinline__ void run(float (&d)[48], const uint32_t (&a)[NA][4], uint64_t descB) {
    asm volatile(
        "{\n"
        ".reg .pred p0, p1;\n"
        ".reg .b64 ta, ta0, tb, tb0;\n"
        "setp.ne.b32 p0, 0, 0;\n"
        "setp.eq.b32 p1, 0, 0;\n"
        "add.s64 tb0, %60, %61;\n"
        "add.s64 tb, tb0, 0;\n"
        "wgmma.mma_async.sync.aligned.m64n96k16.f32.bf16.bf16 {%0, %1, %2, %3, %4, %5, %6, %7, %8, %9, %10, %11, %12, %13, %14, %15, %16, %17, %18, %19, %20, %21, %22, %23, %24, %25, %26, %27, %28, %29, %30, %31, %32, %33, %34, %35, %36, %37, %38, %39, %40, %41, %42, %43, %44, %45, %46, %47}, {%48, %49, %50, %51}, tb, p0, 1, 1, 1;\n"
        "add.s64 tb, tb0, 32;\n"
        "wgmma.mma_async.sync.aligned.m64n96k16.f32.bf16.bf16 {%0, %1, %2, %3, %4, %5, %6, %7, %8, %9, %10, %11, %12, %13, %14, %15, %16, %17, %18, %19, %20, %21, %22, %23, %24, %25, %26, %27, %28, %29, %30, %31, %32, %33, %34, %35, %36, %37, %38, %39, %40, %41, %42, %43, %44, %45, %46, %47}, {%52, %53, %54, %55}, tb, p1, 1, 1, 1;\n"
        "add.s64 tb, tb0, 64;\n"
        "wgmma.mma_async.sync.aligned.m64n96k16.f32.bf16.bf16 {%0, %1, %2, %3, %4, %5, %6, %7, %8, %9, %10, %11, %12, %13, %14, %15, %16, %17, %18, %19, %20, %21, %22, %23, %24, %25, %26, %27, %28, %29, %30, %31, %32, %33, %34, %35, %36, %37, %38, %39, %40, %41, %42, %43, %44, %45, %46, %47}, {%56, %57, %58, %59}, tb, p1, 1, 1, 1;\n"
        "}\n"
        : "=f"(d[0]), "=f"(d[1]), "=f"(d[2]), "=f"(d[3]), "=f"(d[4]), "=f"(d[5]), "=f"(d[6]), "=f"(d[7]), "=f"(d[8]), "=f"(d[9]), "=f"(d[10]), "=f"(d[11]), "=f"(d[12]), "=f"(d[13]), "=f"(d[14]), "=f"(d[15]), "=f"(d[16]), "=f"(d[17]), "=f"(d[18]), "=f"(d[19]), "=f"(d[20]), "=f"(d[21]), "=f"(d[22]), "=f"(d[23]), "=f"(d[24]), "=f"(d[25]), "=f"(d[26]), "=f"(d[27]), "=f"(d[28]), "=f"(d[29]), "=f"(d[30]), "=f"(d[31]), "=f"(d[32]), "=f"(d[33]), "=f"(d[34]), "=f"(d[35]), "=f"(d[36]), "=f"(d[37]), "=f"(d[38]), "=f"(d[39]), "=f"(d[40]), "=f"(d[41]), "=f"(d[42]), "=f"(d[43]), "=f"(d[44]), "=f"(d[45]), "=f"(d[46]), "=f"(d[47])
        : "r"(a[AOFF + 0][0]), "r"(a[AOFF + 0][1]), "r"(a[AOFF + 0][2]), "r"(a[AOFF + 0][3]), "r"(a[AOFF + 1][0]), "r"(a[AOFF + 1][1]), "r"(a[AOFF + 1][2]), "r"(a[AOFF + 1][3]), "r"(a[AOFF + 2][0]), "r"(a[AOFF + 2][1]), "r"(a[AOFF + 2][2]), "r"(a[AOFF + 2][3]), "l"(descB), "n"(BOFF >> 4));
}
};
template <> struct Rng<0, 0, 4> {
template <int BOFF, int AOFF, int NA>
static __device__ __forceinline__ void run(float (&d)[48], const uint32_t (&a)[NA][4], uint64_t descB) {
    asm volatile(
        "{\n"
        ".reg .pred p0, p1;\n"
        ".reg .b64 ta, ta0, tb, tb0;\n"
        "setp.ne.b32 p0, 0, 0;\n"
        "setp.eq.b32 p1, 0, 0;\n"
        "add.s64 tb0, %64, %65;\n"
        "add.s64 tb, tb0, 0;\n"
        "wgmma.mma_async.sync.aligned.m64n96k16.f32.bf16.bf16 {%0, %1, %2, %3, %4, %5, %6, %7, %8, %9, %10, %11, %12, %13, %14, %15, %16, %17, %18, %19, %20, %21, %22, %23, %24, %25, %26, %27, %28, %29, %30, %31, %32, %33, %34, %35, %36, %37, %38, %39, %40, %41, %42, %43, %44, %45, %46, %47}, {%48, %49, %50, %51}, tb, p0, 1, 1, 1;\n"
        "add.s64 tb, tb0, 32;\n"
        "wgmma.mma_async.sync.aligned.m64n96k16.f32.bf16.bf16 {%0, %1, %2, %3, %4, %5, %6, %7, %8, %9, %10, %11, %12, %13, %14, %15, %16, %17, %18, %19, %20, %21, %22, %23, %24, %25, %26, %27, %28, %29, %30, %31, %32, %33, %34, %35, %36, %37, %38, %39, %40, %41, %42, %43, %44, %45, %46, %47}, {%52, %53, %54, %55}, tb, p1, 1, 1, 1;\n"
        "add.s64 tb, tb0, 64;\n"
        "wgmma.mma_async.sync.aligned.m64n96k16.f32.bf16.bf16 {%0, %1, %2, %3, %4, %5, %6, %7, %8, %9, %10, %11, %12, %13, %14, %15, %16, %17, %18, %19, %20, %21, %22, %23, %24, %25, %26, %27, %28, %29, %30, %31, %32, %33, %34, %35, %36, %37, %38, %39, %40, %41, %42, %43, %44, %45, %46, %47}, {%56, %57, %58, %59}, tb, p1, 1, 1, 1;\n"
        "add.s64 tb, tb0, 96;\n"
        "wgmma.mma_async.sync.aligned.m64n96k16.f32.bf16.bf16 {%0, %1, %2, %3, %4, %5, %6, %7, %8, %9, %10, %11, %12, %13, %14, %15, %16, %17, %18, %19, %20, %21, %22, %23, %24, %25, %26, %27, %28, %29, %30, %31, %32, %33, %34, %35, %36, %37, %38, %39, %40, %41, %42, %43, %44, %45, %46, %47}, {%60, %61, %62, %63}, tb, p1, 1, 1, 1;\n"
        "}\n"
        : "=f"(d[0]), "=f"(d[1]), "=f"(d[2]), "=f"(d[3]), "=f"(d[4]), "=f"(d[5]), "=f"(d[6]), "=f"(d[7]), "=f"(d[8]), "=f"(d[9]), "=f"(d[10]), "=f"(d[11]), "=f"(d[12]), "=f"(d[13]), "=f"(d[14]), "=f"(d[15]), "=f"(d[16]), "=f"(d[17]), "=f"(d[18]), "=f"(d[19]), "=f"(d[20]), "=f"(d[21]), "=f"(d[22]), "=f"(d[23]), "=f"(d[24]), "=f"(d[25]), "=f"(d[26]), "=f"(d[27]), "=f"(d[28]), "=f"(d[29]), "=f"(d[30]), "=f"(d[31]), "=f"(d[32]), "=f"(d[33]), "=f"(d[34]), "=f"(d[35]), "=f"(d[36]), "=f"(d[37]), "=f"(d[38]), "=f"(d[39]), "=f"(d[40]), "=f"(d[41]), "=f"(d[42]), "=f"(d[43]), "=f"(d[44]), "=f"(d[45]), "=f"(d[46]), "=f"(d[47])
        : "r"(a[AOFF + 0][0]), "r"(a[AOFF + 0][1]), "r"(a[AOFF + 0][2]), "r"(a[AOFF + 0][3]), "r"(a[AOFF + 1][0]), "r"(a[AOFF + 1][1]), "r"(a[AOFF + 1][2]), "r"(a[AOFF + 1][3]), "r"(a[AOFF + 2][0]), "r"(a[AOFF + 2][1]), "r"(a[AOFF + 2][2]), "r"(a[AOFF + 2][3]), "r"(a[AOFF + 3][0]), "r"(a[AOFF + 3][1]), "r"(a[AOFF + 3][2]), "r"(a[AOFF + 3][3]), "l"(descB), "n"(BOFF >> 4));
}
};
template <> struct Rng<1, 0, 4> {
template <int BOFF, int AOFF, int NA>
static __device__ __forceinline__ void run(float (&d)[48], const uint32_t (&a)[NA][4], uint64_t descB) {
    asm volatile(
        "{\n"
        ".reg .pred p0, p1;\n"
        ".reg .b64 ta, ta0, tb, tb0;\n"
        "setp.ne.b32 p0, 0, 0;\n"
        "setp.eq.b32 p1, 0, 0;\n"
        "add.s64 tb0, %64, %65;\n"
        "add.s64 tb, tb0, 0;\n"
        "wgmma.mma_async.sync.aligned.m64n96k16.f32.bf16.bf16 {%0, %1, %2, %3, %4, %5, %6, %7, %8, %9, %10, %11, %12, %13, %14, %15, %16, %17, %18, %19, %20, %21, %22, %23, %24, %25, %26, %27, %28, %29, %30, %31, %32, %33, %34, %35, %36, %37, %38, %39, %40, %41, %42, %43, %44, %45, %46, %47}, {%48, %49, %50, %51}, tb, p0, 1, 1, 1;\n"
        "add.s64 tb, tb0, 32;\n"
        "wgmma.mma_async.sync.aligned.m64n96k16.f32.bf16.bf16 {%0, %1, %2, %3, %4, %5, %6, %7, %8, %9, %10, %11, %12, %13, %14, %15, %16, %17, %18, %19, %20, %21, %22, %23, %24, %25, %26, %27, %28, %29, %30, %31, %32, %33, %34, %35, %36, %37, %38, %39, %40, %41, %42, %43, %44, %45, %46, %47}, {%52, %53, %54, %55}, tb, p1, 1, 1, 1;\n"
        "add.s64 tb, tb0, 64;\n"
        "wgmma.mma_async.sync.aligned.m64n96k16.f32.bf16.bf16 {%0, %1, %2, %3, %4, %5, %6, %7, %8, %9, %10, %11, %12, %13, %14, %15, %16, %17, %18, %19, %20, %21, %22, %23, %24, %25, %26, %27, %28, %29, %30, %31, %32, %33, %34, %35, %36, %37, %38, %39, %40, %41, %42, %43, %44, %45, %46, %47}, {%56, %57, %58, %59}, tb, p1, 1, 1, 1;\n"
        "add.s64 tb, tb0, 96;\n"
        "wgmma.mma_async.sync.aligned.m64n96k16.f32.bf16.bf16 {%0, %1, %2, %3, %4, %5, %6, %7, %8, %9, %10, %11, %12, %13, %14, %15, %16, %17, %18, %19, %20, %21, %22, %23, %24, %25, %26, %27, %28, %29, %30, %31, %32, %33, %34, %35, %36, %37, %38, %39, %40, %41, %42, %43, %44, %45, %46, %47}, {%60, %61, %62, %63}, tb, p1, 1, 1, 1;\n"
        "}\n"
        : "=f"(d[0]), "=f"(d[1]), "=f"(d[2]), "=f"(d[3]), "=f"(d[4]), "=f"(d[5]), "=f"(d[6]), "=f"(d[7]), "=f"(d[8]), "=f"(d[9]), "=f"(d[10]), "=f"(d[11]), "=f"(d[12]), "=f"(d[13]), "=f"(d[14]), "=f"(d[15]), "=f"(d[16]), "=f"(d[17]), "=f"(d[18]), "=f"(d[19]), "=f"(d[20]), "=f"(d[21]), "=f"(d[22]), "=f"(d[23]), "=f"(d[24]), "=f"(d[25]), "=f"(d[26]), "=f"(d[27]), "=f"(d[28]), "=f"(d[29]), "=f"(d[30]), "=f"(d[31]), "=f"(d[32]), "=f"(d[33]), "=f"(d[34]), "=f"(d[35]), "=f"(d[36]), "=f"(d[37]), "=f"(d[38]), "=f"(d[39]), "=f"(d[40]), "=f"(d[41]), "=f"(d[42]), "=f"(d[43]), "=f"(d[44]), "=f"(d[45]), "=f"(d[46]), "=f"(d[47])
        : "r"(a[AOFF + 0][0]), "r"(a[AOFF + 0][1]), "r"(a[AOFF + 0][2]), "r"(a[AOFF + 0][3]), "r"(a[AOFF + 1][0]), "r"(a[AOFF + 1][1]), "r"(a[AOFF + 1][2]), "r"(a[AOFF + 1][3]), "r"(a[AOFF + 2][0]), "r"(a[AOFF + 2][1]), "r"(a[AOFF + 2][2]), "r"(a[AOFF + 2][3]), "r"(a[AOFF + 3][0]), "r"(a[AOFF + 3][1]), "r"(a[AOFF + 3][2]), "r"(a[AOFF + 3][3]), "l"(descB), "n"(BOFF >> 4));
}
};
template <> struct Rng<0, 0, 5> {
template <int BOFF, int AOFF, int NA>
static __device__ __forceinline__ void run(float (&d)[48], const uint32_t (&a)[NA][4], uint64_t descB) {
    asm volatile(
        "{\n"
        ".reg .pred p0, p1;\n"
        ".reg .b64 ta, ta0, tb, tb0;\n"
        "setp.ne.b32 p0, 0, 0;\n"
        "setp.eq.b32 p1, 0, 0;\n"
        "add.s64 tb0, %68, %69;\n"
        "add.s64 tb, tb0, 0;\n"
        "wgmma.mma_async.sync.aligned.m64n96k16.f32.bf16.bf16 {%0, %1, %2, %3, %4, %5, %6, %7, %8, %9, %10, %11, %12, %13, %14, %15, %16, %17, %18, %19, %20, %21, %22, %23, %24, %25, %26, %27, %28, %29, %30, %31, %32, %33, %34, %35, %36, %37, %38, %39, %40, %41, %42, %43, %44, %45, %46, %47}, {%48, %49, %50, %51}, tb, p0, 1, 1, 1;\n"
        "add.s64 tb, tb0, 32;\n"
        "wgmma.mma_async.sync.aligned.m64n96k16.f32.bf16.bf16 {%0, %1, %2, %3, %4, %5, %6, %7, %8, %9, %10, %11, %12, %13, %14, %15, %16, %17, %18, %19, %20, %21, %22, %23, %24, %25, %26, %27, %28, %29, %30, %31, %32, %33, %34, %35, %36, %37, %38, %39, %40, %41, %42, %43, %44, %45, %46, %47}, {%52, %53, %54, %55}, tb, p1, 1, 1, 1;\n"
        "add.s64 tb, tb0, 64;\n"
        "wgmma.mma_async.sync.aligned.m64n96k16.f32.bf16.bf16 {%0, %1, %2, %3, %4, %5, %6, %7, %8, %9, %10, %11, %12, %13, %14, %15, %16, %17, %18, %19, %20, %21, %22, %23, %24, %25, %26, %27, %28, %29, %30, %31, %32, %33, %34, %35, %36, %37, %38, %39, %40, %41, %42, %43, %44, %45, %46, %47}, {%56, %57, %58, %59}, tb, p1, 1, 1, 1;\n"
        "add.s64 tb, tb0, 96;\n"
        "wgmma.mma_async.sync.aligned.m64n96k16.f32.bf16.bf16 {%0, %1, %2, %3, %4, %5, %6, %7, %8, %9, %10, %11, %12, %13, %14, %15, %16, %17, %18, %19, %20, %21, %22, %23, %24, %25, %26, %27, %28, %29, %30, %31, %32, %33, %34, %35, %36, %37, %38, %39, %40, %41, %42, %43, %44, %45, %46, %47}, {%60, %61, %62, %63}, tb, p1, 1, 1, 1;\n"
        "add.s64 tb, tb0, 1536;\n"
        "wgmma.mma_async.sync.aligned.m64n96k16.f32.bf16.bf16 {%0, %1, %2, %3, %4, %5, %6, %7, %8, %9, %10, %11, %12, %13, %14, %15, %16, %17, %18, %19, %20, %21, %22, %23, %24, %25, %26, %27, %28, %29, %30, %31, %32, %33, %34, %35, %36, %37, %38, %39, %40, %41, %42, %43, %44, %45, %46, %47}, {%64, %65, %66, %67}, tb, p1, 1, 1, 1;\n"
        "}\n"
        : "=f"(d[0]), "=f"(d[1]), "=f"(d[2]), "=f"(d[3]), "=f"(d[4]), "=f"(d[5]), "=f"(d[6]), "=f"(d[7]), "=f"(d[8]), "=f"(d[9]), "=f"(d[10]), "=f"(d[11]), "=f"(d[12]), "=f"(d[13]), "=f"(d[14]), "=f"(d[15]), "=f"(d[16]), "=f"(d[17]), "=f"(d[18]), "=f"(d[19]), "=f"(d[20]), "=f"(d[21]), "=f"(d[22]), "=f"(d[23]), "=f"(d[24]), "=f"(d[25]), "=f"(d[26]), "=f"(d[27]), "=f"(d[28]), "=f"(d[29]), "=f"(d[30]), "=f"(d[31]), "=f"(d[32]), "=f"(d[33]), "=f"(d[34]), "=f"(d[35]), "=f"(d[36]), "=f"(d[37]), "=f"(d[38]), "=f"(d[39]), "=f"(d[40]), "=f"(d[41]), "=f"(d[42]), "=f"(d[43]), "=f"(d[44]), "=f"(d[45]), "=f"(d[46]), "=f"(d[47])
        : "r"(a[AOFF + 0][0]), "r"(a[AOFF + 0][1]), "r"(a[AOFF + 0][2]), "r"(a[AOFF + 0][3]), "r"(a[AOFF + 1][0]), "r"(a[AOFF + 1][1]), "r"(a[AOFF + 1][2]), "r"(a[AOFF + 1][3]), "r"(a[AOFF + 2][0]), "r"(a[AOFF + 2][1]), "r"(a[AOFF + 2][2]), "r"(a[AOFF + 2][3]), "r"(a[AOFF + 3][0]), "r"(a[AOFF + 3][1]), "r"(a[AOFF + 3][2]), "r"(a[AOFF + 3][3]), "r"(a[AOFF + 4][0]), "r"(a[AOFF + 4][1]), "r"(a[AOFF + 4][2]), "r"(a[AOFF + 4][3]), "l"(descB), "n"(BOFF >> 4));
}
};
template <> struct Rng<1, 0, 5> {
template <int BOFF, int AOFF, int NA>
static __device__ __forceinline__ void run(float (&d)[48], const uint32_t (&a)[NA][4], uint64_t descB) {
    asm volatile(
        "{\n"
        ".reg .pred p0, p1;\n"
        ".reg .b64 ta, ta0, tb, tb0;\n"
        "setp.ne.b32 p0, 0, 0;\n"
        "setp.eq.b32 p1, 0, 0;\n"
        "add.s64 tb0, %68, %69;\n"
        "add.s64 tb, tb0, 0;\n"
        "wgmma.mma_async.sync.aligned.m64n96k16.f32.bf16.bf16 {%0, %1, %2, %3, %4, %5, %6, %7, %8, %9, %10, %11, %12, %13, %14, %15, %16, %17, %18, %19, %20, %21, %22, %23, %24, %25, %26, %27, %28, %29, %30, %31, %32, %33, %34, %35, %36, %37, %38, %39, %40, %41, %42, %43, %44, %45, %46, %47}, {%48, %49, %50, %51}, tb, p0, 1, 1, 1;\n"
        "add.s64 tb, tb0, 32;\n"
        "wgmma.mma_async.sync.aligned.m64n96k16.f32.bf16.bf16 {%0, %1, %2, %3, %4, %5, %6, %7, %8, %9, %10, %11, %12, %13, %14, %15, %16, %17, %18, %19, %20, %21, %22, %23, %24, %25, %26, %27, %28, %29, %30, %31, %32, %33, %34, %35, %36, %37, %38, %39, %40, %41, %42, %43, %44, %45, %46, %47}, {%52, %53, %54, %55}, tb, p1, 1, 1, 1;\n"
        "add.s64 tb, tb0, 64;\n"
        "wgmma.mma_async.sync.aligned.m64n96k16.f32.bf16.bf16 {%0, %1, %2, %3, %4, %5, %6, %7, %8, %9, %10, %11, %12, %13, %14, %15, %16, %17, %18, %19, %20, %21, %22, %23, %24, %25, %26, %27, %28, %29, %30, %31, %32, %33, %34, %35, %36, %37, %38, %39, %40, %41, %42, %43, %44, %45, %46, %47}, {%56, %57, %58, %59}, tb, p1, 1, 1, 1;\n"
        "add.s64 tb, tb0, 96;\n"
        "wgmma.mma_async.sync.aligned.m64n96k16.f32.bf16.bf16 {%0, %1, %2, %3, %4, %5, %6, %7, %8, %9, %10, %11, %12, %13, %14, %15, %16, %17, %18, %19, %20, %21, %22, %23, %24, %25, %26, %27, %28, %29, %30, %31, %32, %33, %34, %35, %36, %37, %38, %39, %40, %41, %42, %43, %44, %45, %46, %47}, {%60, %61, %62, %63}, tb, p1, 1, 1, 1;\n"
        "add.s64 tb, tb0, 128;\n"
        "wgmma.mma_async.sync.aligned.m64n96k16.f32.bf16.bf16 {%0, %1, %2, %3, %4, %5, %6, %7, %8, %9, %10, %11, %12, %13, %14, %15, %16, %17, %18, %19, %20, %21, %22, %23, %24, %25, %26, %27, %28, %29, %30, %31, %32, %33, %34, %35, %36, %37, %38, %39, %40, %41, %42, %43, %44, %45, %46, %47}, {%64, %65, %66, %67}, tb, p1, 1, 1, 1;\n"
        "}\n"
        : "=f"(d[0]), "=f"(d[1]), "=f"(d[2]), "=f"(d[3]), "=f"(d[4]), "=f"(d[5]), "=f"(d[6]), "=f"(d[7]), "=f"(d[8]), "=f"(d[9]), "=f"(d[10]), "=f"(d[11]), "=f"(d[12]), "=f"(d[13]), "=f"(d[14]), "=f"(d[15]), "=f"(d[16]), "=f"(d[17]), "=f"(d[18]), "=f"(d[19]), "=f"(d[20]), "=f"(d[21]), "=f"(d[22]), "=f"(d[23]), "=f"(d[24]), "=f"(d[25]), "=f"(d[26]), "=f"(d[27]), "=f"(d[28]), "=f"(d[29]), "=f"(d[30]), "=f"(d[31]), "=f"(d[32]), "=f"(d[33]), "=f"(d[34]), "=f"(d[35]), "=f"(d[36]), "=f"(d[37]), "=f"(d[38]), "=f"(d[39]), "=f"(d[40]), "=f"(d[41]), "=f"(d[42]), "=f"(d[43]), "=f"(d[44]), "=f"(d[45]), "=f"(d[46]), "=f"(d[47])
        : "r"(a[AOFF + 0][0]), "r"(a[AOFF + 0][1]), "r"(a[AOFF + 0][2]), "r"(a[AOFF + 0][3]), "r"(a[AOFF + 1][0]), "r"(a[AOFF + 1][1]), "r"(a[AOFF + 1][2]), "r"(a[AOFF + 1][3]), "r"(a[AOFF + 2][0]), "r"(a[AOFF + 2][1]), "r"(a[AOFF + 2][2]), "r"(a[AOFF + 2][3]), "r"(a[AOFF + 3][0]), "r"(a[AOFF + 3][1]), "r"(a[AOFF + 3][2]), "r"(a[AOFF + 3][3]), "r"(a[AOFF + 4][0]), "r"(a[AOFF + 4][1]), "r"(a[AOFF + 4][2]), "r"(a[AOFF + 4][3]), "l"(descB), "n"(BOFF >> 4));
}
};
template <> struct Rng<0, 0, 6> {
template <int BOFF, int AOFF, int NA>
static __device__ __forceinline__ void run(float (&d)[48], const uint32_t (&a)[NA][4], uint64_t descB) {
    asm volatile(
        "{\n"
        ".reg .pred p0, p1;\n"
        ".reg .b64 ta, ta0, tb, tb0;\n"
        "setp.ne.b32 p0, 0, 0;\n"
        "setp.eq.b32 p1, 0, 0;\n"
        "add.s64 tb0, %72, %73;\n"
        "add.s64 tb, tb0, 0;\n"
        "wgmma.mma_async.sync.aligned.m64n96k16.f32.bf16.bf16 {%0, %1, %2, %3, %4, %5, %6, %7, %8, %9, %10, %11, %12, %13, %14, %15, %16, %17, %18, %19, %20, %21, %22, %23, %24, %25, %26, %27, %28, %29, %30, %31, %32, %33, %34, %35, %36, %37, %38, %39, %40, %41, %42, %43, %44, %45, %46, %47}, {%48, %49, %50, %51}, tb, p0, 1, 1, 1;\n"
        "add.s64 tb, tb0, 32;\n"
        "wgmma.mma_async.sync.aligned.m64n96k16.f32.bf16.bf16 {%0, %1, %2, %3, %4, %5, %6, %7, %8, %9, %10, %11, %12, %13, %14, %15, %16, %17, %18, %19, %20, %21, %22, %23, %24, %25, %26, %27, %28, %29, %30, %31, %32, %33, %34, %35, %36, %37, %38, %39, %40, %41, %42, %43, %44, %45, %46, %47}, {%52, %53, %54, %55}, tb, p1, 1, 1, 1;\n"
        "add.s64 tb, tb0, 64;\n"
        "wgmma.mma_async.sync.aligned.m64n96k16.f32.bf16.bf16 {%0, %1, %2, %3, %4, %5, %6, %7, %8, %9, %10, %11, %12, %13, %14, %15, %16, %17, %18, %19, %20, %21, %22, %23, %24, %25, %26, %27, %28, %29, %30, %31, %32, %33, %34, %35, %36, %37, %38, %39, %40, %41, %42, %43, %44, %45, %46, %47}, {%56, %57, %58, %59}, tb, p1, 1, 1, 1;\n"
        "add.s64 tb, tb0, 96;\n"
        "wgmma.mma_async.sync.aligned.m64n96k16.f32.bf16.bf16 {%0, %1, %2, %3, %4, %5, %6, %7, %8, %9, %10, %11, %12, %13, %14, %15, %16, %17, %18, %19, %20, %21, %22, %23, %24, %25, %26, %27, %28, %29, %30, %31, %32, %33, %34, %35, %36, %37, %38, %39, %40, %41, %42, %43, %44, %45, %46, %47}, {%60, %61, %62, %63}, tb, p1, 1, 1, 1;\n"
        "add.s64 tb, tb0, 1536;\n"
        "wgmma.mma_async.sync.aligned.m64n96k16.f32.bf16.bf16 {%0, %1, %2, %3, %4, %5, %6, %7, %8, %9, %10, %11, %12, %13, %14, %15, %16, %17, %18, %19, %20, %21, %22, %23, %24, %25, %26, %27, %28, %29, %30, %31, %32, %33, %34, %35, %36, %37, %38, %39, %40, %41, %42, %43, %44, %45, %46, %47}, {%64, %65, %66, %67}, tb, p1, 1, 1, 1;\n"
        "add.s64 tb, tb0, 1568;\n"
        "wgmma.mma_async.sync.aligned.m64n96k16.f32.bf16.bf16 {%0, %1, %2, %3, %4, %5, %6, %7, %8, %9, %10, %11, %12, %13, %14, %15, %16, %17, %18, %19, %20, %21, %22, %23, %24, %25, %26, %27, %28, %29, %30, %31, %32, %33, %34, %35, %36, %37, %38, %39, %40, %41, %42, %43, %44, %45, %46, %47}, {%68, %69, %70, %71}, tb, p1, 1, 1, 1;\n"
        "}\n"
        : "=f"(d[0]), "=f"(d[1]), "=f"(d[2]), "=f"(d[3]), "=f"(d[4]), "=f"(d[5]), "=f"(d[6]), "=f"(d[7]), "=f"(d[8]), "=f"(d[9]), "=f"(d[10]), "=f"(d[11]), "=f"(d[12]), "=f"(d[13]), "=f"(d[14]), "=f"(d[15]), "=f"(d[16]), "=f"(d[17]), "=f"(d[18]), "=f"(d[19]), "=f"(d[20]), "=f"(d[21]), "=f"(d[22]), "=f"(d[23]), "=f"(d[24]), "=f"(d[25]), "=f"(d[26]), "=f"(d[27]), "=f"(d[28]), "=f"(d[29]), "=f"(d[30]), "=f"(d[31]), "=f"(d[32]), "=f"(d[33]), "=f"(d[34]), "=f"(d[35]), "=f"(d[36]), "=f"(d[37]), "=f"(d[38]), "=f"(d[39]), "=f"(d[40]), "=f"(d[41]), "=f"(d[42]), "=f"(d[43]), "=f"(d[44]), "=f"(d[45]), "=f"(d[46]), "=f"(d[47])
        : "r"(a[AOFF + 0][0]), "r"(a[AOFF + 0][1]), "r"(a[AOFF + 0][2]), "r"(a[AOFF + 0][3]), "r"(a[AOFF + 1][0]), "r"(a[AOFF + 1][1]), "r"(a[AOFF + 1][2]), "r"(a[AOFF + 1][3]), "r"(a[AOFF + 2][0]), "r"(a[AOFF + 2][1]), "r"(a[AOFF + 2][2]), "r"(a[AOFF + 2][3]), "r"(a[AOFF + 3][0]), "r"(a[AOFF + 3][1]), "r"(a[AOFF + 3][2]), "r"(a[AOFF + 3][3]), "r"(a[AOFF + 4][0]), "r"(a[AOFF + 4][1]), "r"(a[AOFF + 4][2]), "r"(a[AOFF + 4][3]), "r"(a[AOFF + 5][0]), "r"(a[AOFF + 5][1]), "r"(a[AOFF + 5][2]), "r"(a[AOFF + 5][3]), "l"(descB), "n"(BOFF >> 4));
}
};
template <> struct Rng<1, 0, 6> {
template <int BOFF, int AOFF, int NA>
static __device__ __forceinline__ void run(float (&d)[48], const uint32_t (&a)[NA][4], uint64_t descB) {
    asm volatile(
        "{\n"
        ".reg .pred p0, p1;\n"
        ".reg .b64 ta, ta0, tb, tb0;\n"
        "setp.ne.b32 p0, 0, 0;\n"
        "setp.eq.b32 p1, 0, 0;\n"
        "add.s64 tb0, %72, %73;\n"
        "add.s64 tb, tb0, 0;\n"
        "wgmma.mma_async.sync.aligned.m64n96k16.f32.bf16.bf16 {%0, %1, %2, %3, %4, %5, %6, %7, %8, %9, %10, %11, %12, %13, %14, %15, %16, %17, %18, %19, %20, %21, %22, %23, %24, %25, %26, %27, %28, %29, %30, %31, %32, %33, %34, %35, %36, %37, %38, %39, %40, %41, %42, %43, %44, %45, %46, %47}, {%48, %49, %50, %51}, tb, p0, 1, 1, 1;\n"
        "add.s64 tb, tb0, 32;\n"
        "wgmma.mma_async.sync.aligned.m64n96k16.f32.bf16.bf16 {%0, %1, %2, %3, %4, %5, %6, %7, %8, %9, %10, %11, %12, %13, %14, %15, %16, %17, %18, %19, %20, %21, %22, %23, %24, %25, %26, %27, %28, %29, %30, %31, %32, %33, %34, %35, %36, %37, %38, %39, %40, %41, %42, %43, %44, %45, %46, %47}, {%52, %53, %54, %55}, tb, p1, 1, 1, 1;\n"
        "add.s64 tb, tb0, 64;\n"
        "wgmma.mma_async.sync.aligned.m64n96k16.f32.bf16.bf16 {%0, %1, %2, %3, %4, %5, %6, %7, %8, %9, %10, %11, %12, %13, %14, %15, %16, %17, %18, %19, %20, %21, %22, %23, %24, %25, %26, %27, %28, %29, %30, %31, %32, %33, %34, %35, %36, %37, %38, %39, %40, %41, %42, %43, %44, %45, %46, %47}, {%56, %57, %58, %59}, tb, p1, 1, 1, 1;\n"
        "add.s64 tb, tb0, 96;\n"
        "wgmma.mma_async.sync.aligned.m64n96k16.f32.bf16.bf16 {%0, %1, %2, %3, %4, %5, %6, %7, %8, %9, %10, %11, %12, %13, %14, %15, %16, %17, %18, %19, %20, %21, %22, %23, %24, %25, %26, %27, %28, %29, %30, %31, %32, %33, %34, %35, %36, %37, %38, %39, %40, %41, %42, %43, %44, %45, %46, %47}, {%60, %61, %62, %63}, tb, p1, 1, 1, 1;\n"
        "add.s64 tb, tb0, 128;\n"
        "wgmma.mma_async.sync.aligned.m64n96k16.f32.bf16.bf16 {%0, %1, %2, %3, %4, %5, %6, %7, %8, %9, %10, %11, %12, %13, %14, %15, %16, %17, %18, %19, %20, %21, %22, %23, %24, %25, %26, %27, %28, %29, %30, %31, %32, %33, %34, %35, %36, %37, %38, %39, %40, %41, %42, %43, %44, %45, %46, %47}, {%64, %65, %66, %67}, tb, p1, 1, 1, 1;\n"
        "add.s64 tb, tb0, 160;\n"
        "wgmma.mma_async.sync.aligned.m64n96k16.f32.bf16.bf16 {%0, %1, %2, %3, %4, %5, %6, %7, %8, %9, %10, %11, %12, %13, %14, %15, %16, %17, %18, %19, %20, %21, %22, %23, %24, %25, %26, %27, %28, %29, %30, %31, %32, %33, %34, %35, %36, %37, %38, %39, %40, %41, %42, %43, %44, %45, %46, %47}, {%68, %69, %70, %71}, tb, p1, 1, 1, 1;\n"
        "}\n"
        : "=f"(d[0]), "=f"(d[1]), "=f"(d[2]), "=f"(d[3]), "=f"(d[4]), "=f"(d[5]), "=f"(d[6]), "=f"(d[7]), "=f"(d[8]), "=f"(d[9]), "=f"(d[10]), "=f"(d[11]), "=f"(d[12]), "=f"(d[13]), "=f"(d[14]), "=f"(d[15]), "=f"(d[16]), "=f"(d[17]), "=f"(d[18]), "=f"(d[19]), "=f"(d[20]), "=f"(d[21]), "=f"(d[22]), "=f"(d[23]), "=f"(d[24]), "=f"(d[25]), "=f"(d[26]), "=f"(d[27]), "=f"(d[28]), "=f"(d[29]), "=f"(d[30]), "=f"(d[31]), "=f"(d[32]), "=f"(d[33]), "=f"(d[34]), "=f"(d[35]), "=f"(d[36]), "=f"(d[37]), "=f"(d[38]), "=f"(d[39]), "=f"(d[40]), "=f"(d[41]), "=f"(d[42]), "=f"(d[43]), "=f"(d[44]), "=f"(d[45]), "=f"(d[46]), "=f"(d[47])
        : "r"(a[AOFF + 0][0]), "r"(a[AOFF + 0][1]), "r"(a[AOFF + 0][2]), "r"(a[AOFF + 0][3]), "r"(a[AOFF + 1][0]), "r"(a[AOFF + 1][1]), "r"(a[AOFF + 1][2]), "r"(a[AOFF + 1][3]), "r"(a[AOFF + 2][0]), "r"(a[AOFF + 2][1]), "r"(a[AOFF + 2][2]), "r"(a[AOFF + 2][3]), "r"(a[AOFF + 3][0]), "r"(a[AOFF + 3][1]), "r"(a[AOFF + 3][2]), "r"(a[AOFF + 3][3]), "r"(a[AOFF + 4][0]), "r"(a[AOFF + 4][1]), "r"(a[AOFF + 4][2]), "r"(a[AOFF + 4][3]), "r"(a[AOFF + 5][0]), "r"(a[AOFF + 5][1]), "r"(a[AOFF + 5][2]), "r"(a[AOFF + 5][3]), "l"(descB), "n"(BOFF >> 4));
}
};
template <> struct Rng<0, 3, 7> {
template <int BOFF, int AOFF, int NA>
static __device__ __forceinline__ void run(float (&d)[48], const uint32_t (&a)[NA][4], uint64_t descB) {
    asm volatile(
        "{\n"
        ".reg .pred p0, p1;\n"
        ".reg .b64 ta, ta0, tb, tb0;\n"
        "setp.ne.b32 p0, 0, 0;\n"
        "setp.eq.b32 p1, 0, 0;\n"
        "add.s64 tb0, %64, %65;\n"
        "add.s64 tb, tb0, 96;\n"
        "wgmma.mma_async.sync.aligned.m64n96k16.f32.bf16.bf16 {%0, %1, %2, %3, %4, %5, %6, %7, %8, %9, %10, %11, %12, %13, %14, %15, %16, %17, %18, %19, %20, %21, %22, %23, %24, %25, %26, %27, %28, %29, %30, %31, %32, %33, %34, %35, %36, %37, %38, %39, %40, %41, %42, %43, %44, %45, %46, %47}, {%48, %49, %50, %51}, tb, p1, 1, 1, 1;\n"
        "add.s64 tb, tb0, 1536;\n"
        "wgmma.mma_async.sync.aligned.m64n96k16.f32.bf16.bf16 {%0, %1, %2, %3, %4, %5, %6, %7, %8, %9, %10, %11, %12, %13, %14, %15, %16, %17, %18, %19, %20, %21, %22, %23, %24, %25, %26, %27, %28, %29, %30, %31, %32, %33, %34, %35, %36, %37, %38, %39, %40, %41, %42, %43, %44, %45, %46, %47}, {%52, %53, %54, %55}, tb, p1, 1, 1, 1;\n"
        "add.s64 tb, tb0, 1568;\n"
        "wgmma.mma_async.sync.aligned.m64n96k16.f32.bf16.bf16 {%0, %1, %2, %3, %4, %5, %6, %7, %8, %9, %10, %11, %12, %13, %14, %15, %16, %17, %18, %19, %20, %21, %22, %23, %24, %25, %26, %27, %28, %29, %30, %31, %32, %33, %34, %35, %36, %37, %38, %39, %40, %41, %42, %43, %44, %45, %46, %47}, {%56, %57, %58, %59}, tb, p1, 1, 1, 1;\n"
        "add.s64 tb, tb0, 1600;\n"
        "wgmma.mma_async.sync.aligned.m64n96k16.f32.bf16.bf16 {%0, %1, %2, %3, %4, %5, %6, %7, %8, %9, %10, %11, %12, %13, %14, %15, %16, %17, %18, %19, %20, %21, %22, %23, %24, %25, %26, %27, %28, %29, %30, %31, %32, %33, %34, %35, %36, %37, %38, %39, %40, %41, %42, %43, %44, %45, %46, %47}, {%60, %61, %62, %63}, tb, p1, 1, 1, 1;\n"
        "}\n"
        : "+f"(d[0]), "+f"(d[1]), "+f"(d[2]), "+f"(d[3]), "+f"(d[4]), "+f"(d[5]), "+f"(d[6]), "+f"(d[7]), "+f"(d[8]), "+f"(d[9]), "+f"(d[10]), "+f"(d[11]), "+f"(d[12]), "+f"(d[13]), "+f"(d[14]), "+f"(d[15]), "+f"(d[16]), "+f"(d[17]), "+f"(d[18]), "+f"(d[19]), "+f"(d[20]), "+f"(d[21]), "+f"(d[22]), "+f"(d[23]), "+f"(d[24]), "+f"(d[25]), "+f"(d[26]), "+f"(d[27]), "+f"(d[28]), "+f"(d[29]), "+f"(d[30]), "+f"(d[31]), "+f"(d[32]), "+f"(d[33]), "+f"(d[34]), "+f"(d[35]), "+f"(d[36]), "+f"(d[37]), "+f"(d[38]), "+f"(d[39]), "+f"(d[40]), "+f"(d[41]), "+f"(d[42]), "+f"(d[43]), "+f"(d[44]), "+f"(d[45]), "+f"(d[46]), "+f"(d[47])
        : "r"(a[AOFF + 0][0]), "r"(a[AOFF + 0][1]), "r"(a[AOFF + 0][2]), "r"(a[AOFF + 0][3]), "r"(a[AOFF + 1][0]), "r"(a[AOFF + 1][1]), "r"(a[AOFF + 1][2]), "r"(a[AOFF + 1][3]), "r"(a[AOFF + 2][0]), "r"(a[AOFF + 2][1]), "r"(a[AOFF + 2][2]), "r"(a[AOFF + 2][3]), "r"(a[AOFF + 3][0]), "r"(a[AOFF + 3][1]), "r"(a[AOFF + 3][2]), "r"(a[AOFF + 3][3]), "l"(descB), "n"(BOFF >> 4));
}
};
template <> struct Rng<1, 3, 7> {
template <int BOFF, int AOFF, int NA>
static __device__ __forceinline__ void run(float (&d)[48], const uint32_t (&a)[NA][4], uint64_t descB) {
    asm volatile(
        "{\n"
        ".reg .pred p0, p1;\n"
        ".reg .b64 ta, ta0, tb, tb0;\n"
        "setp.ne.b32 p0, 0, 0;\n"
        "setp.eq.b32 p1, 0, 0;\n"
        "add.s64 tb0, %64, %65;\n"
        "add.s64 tb, tb0, 96;\n"
        "wgmma.mma_async.sync.aligned.m64n96k16.f32.bf16.bf16 {%0, %1, %2, %3, %4, %5, %6, %7, %8, %9, %10, %11, %12, %13, %14, %15, %16, %17, %18, %19, %20, %21, %22, %23, %24, %25, %26, %27, %28, %29, %30, %31, %32, %33, %34, %35, %36, %37, %38, %39, %40, %41, %42, %43, %44, %45, %46, %47}, {%48, %49, %50, %51}, tb, p1, 1, 1, 1;\n"
        "add.s64 tb, tb0, 128;\n"
        "wgmma.mma_async.sync.aligned.m64n96k16.f32.bf16.bf16 {%0, %1, %2, %3, %4, %5, %6, %7, %8, %9, %10, %11, %12, %13, %14, %15, %16, %17, %18, %19, %20, %21, %22, %23, %24, %25, %26, %27, %28, %29, %30, %31, %32, %33, %34, %35, %36, %37, %38, %39, %40, %41, %42, %43, %44, %45, %46, %47}, {%52, %53, %54, %55}, tb, p1, 1, 1, 1;\n"
        "add.s64 tb, tb0, 160;\n"
        "wgmma.mma_async.sync.aligned.m64n96k16.f32.bf16.bf16 {%0, %1, %2, %3, %4, %5, %6, %7, %8, %9, %10, %11, %12, %13, %14, %15, %16, %17, %18, %19, %20, %21, %22, %23, %24, %25, %26, %27, %28, %29, %30, %31, %32, %33, %34, %35, %36, %37, %38, %39, %40, %41, %42, %43, %44, %45, %46, %47}, {%56, %57, %58, %59}, tb, p1, 1, 1, 1;\n"
        "add.s64 tb, tb0, 192;\n"
        "wgmma.mma_async.sync.aligned.m64n96k16.f32.bf16.bf16 {%0, %1, %2, %3, %4, %5, %6, %7, %8, %9, %10, %11, %12, %13, %14, %15, %16, %17, %18, %19, %20, %21, %22, %23, %24, %25, %26, %27, %28, %29, %30, %31, %32, %33, %34, %35, %36, %37, %38, %39, %40, %41, %42, %43, %44, %45, %46, %47}, {%60, %61, %62, %63}, tb, p1, 1, 1, 1;\n"
        "}\n"
        : "+f"(d[0]), "+f"(d[1]), "+f"(d[2]), "+f"(d[3]), "+f"(d[4]), "+f"(d[5]), "+f"(d[6]), "+f"(d[7]), "+f"(d[8]), "+f"(d[9]), "+f"(d[10]), "+f"(d[11]), "+f"(d[12]), "+f"(d[13]), "+f"(d[14]), "+f"(d[15]), "+f"(d[16]), "+f"(d[17]), "+f"(d[18]), "+f"(d[19]), "+f"(d[20]), "+f"(d[21]), "+f"(d[22]), "+f"(d[23]), "+f"(d[24]), "+f"(d[25]), "+f"(d[26]), "+f"(d[27]), "+f"(d[28]), "+f"(d[29]), "+f"(d[30]), "+f"(d[31]), "+f"(d[32]), "+f"(d[33]), "+f"(d[34]), "+f"(d[35]), "+f"(d[36]), "+f"(d[37]), "+f"(d[38]), "+f"(d[39]), "+f"(d[40]), "+f"(d[41]), "+f"(d[42]), "+f"(d[43]), "+f"(d[44]), "+f"(d[45]), "+f"(d[46]), "+f"(d[47])
        : "r"(a[AOFF + 0][0]), "r"(a[AOFF + 0][1]), "r"(a[AOFF + 0][2]), "r"(a[AOFF + 0][3]), "r"(a[AOFF + 1][0]), "r"(a[AOFF + 1][1]), "r"(a[AOFF + 1][2]), "r"(a[AOFF + 1][3]), "r"(a[AOFF + 2][0]), "r"(a[AOFF + 2][1]), "r"(a[AOFF + 2][2]), "r"(a[AOFF + 2][3]), "r"(a[AOFF + 3][0]), "r"(a[AOFF + 3][1]), "r"(a[AOFF + 3][2]), "r"(a[AOFF + 3][3]), "l"(descB), "n"(BOFF >> 4));
}
};
template <> struct Rng<0, 3, 8> {
template <int BOFF, int AOFF, int NA>
static __device__ __forceinline__ void run(float (&d)[48], const uint32_t (&a)[NA][4], uint64_t descB) {
    asm volatile(
        "{\n"
        ".reg .pred p0, p1;\n"
        ".reg .b64 ta, ta0, tb, tb0;\n"
        "setp.ne.b32 p0, 0, 0;\n"
        "setp.eq.b32 p1, 0, 0;\n"
        "add.s64 tb0, %68, %69;\n"
        "add.s64 tb, tb0, 96;\n"
        "wgmma.mma_async.sync.aligned.m64n96k16.f32.bf16.bf16 {%0, %1, %2, %3, %4, %5, %6, %7, %8, %9, %10, %11, %12, %13, %14, %15, %16, %17, %18, %19, %20, %21, %22, %23, %24, %25, %26, %27, %28, %29, %30, %31, %32, %33, %34, %35, %36, %37, %38, %39, %40, %41, %42, %43, %44, %45, %46, %47}, {%48, %49, %50, %51}, tb, p1, 1, 1, 1;\n"
        "add.s64 tb, tb0, 1536;\n"
        "wgmma.mma_async.sync.aligned.m64n96k16.f32.bf16.bf16 {%0, %1, %2, %3, %4, %5, %6, %7, %8, %9, %10, %11, %12, %13, %14, %15, %16, %17, %18, %19, %20, %21, %22, %23, %24, %25, %26, %27, %28, %29, %30, %31, %32, %33, %34, %35, %36, %37, %38, %39, %40, %41, %42, %43, %44, %45, %46, %47}, {%52, %53, %54, %55}, tb, p1, 1, 1, 1;\n"
        "add.s64 tb, tb0, 1568;\n"
        "wgmma.mma_async.sync.aligned.m64n96k16.f32.bf16.bf16 {%0, %1, %2, %3, %4, %5, %6, %7, %8, %9, %10, %11, %12, %13, %14, %15, %16, %17, %18, %19, %20, %21, %22, %23, %24, %25, %26, %27, %28, %29, %30, %31, %32, %33, %34, %35, %36, %37, %38, %39, %40, %41, %42, %43, %44, %45, %46, %47}, {%56, %57, %58, %59}, tb, p1, 1, 1, 1;\n"
        "add.s64 tb, tb0, 1600;\n"
        "wgmma.mma_async.sync.aligned.m64n96k16.f32.bf16.bf16 {%0, %1, %2, %3, %4, %5, %6, %7, %8, %9, %10, %11, %12, %13, %14, %15, %16, %17, %18, %19, %20, %21, %22, %23, %24, %25, %26, %27, %28, %29, %30, %31, %32, %33, %34, %35, %36, %37, %38, %39, %40, %41, %42, %43, %44, %45, %46, %47}, {%60, %61, %62, %63}, tb, p1, 1, 1, 1;\n"
        "add.s64 tb, tb0, 1632;\n"
        "wgmma.mma_async.sync.aligned.m64n96k16.f32.bf16.bf16 {%0, %1, %2, %3, %4, %5, %6, %7, %8, %9, %10, %11, %12, %13, %14, %15, %16, %17, %18, %19, %20, %21, %22, %23, %24, %25, %26, %27, %28, %29, %30, %31, %32, %33, %34, %35, %36, %37, %38, %39, %40, %41, %42, %43, %44, %45, %46, %47}, {%64, %65, %66, %67}, tb, p1, 1, 1, 1;\n"
        "}\n"
        : "+f"(d[0]), "+f"(d[1]), "+f"(d[2]), "+f"(d[3]), "+f"(d[4]), "+f"(d[5]), "+f"(d[6]), "+f"(d[7]), "+f"(d[8]), "+f"(d[9]), "+f"(d[10]), "+f"(d[11]), "+f"(d[12]), "+f"(d[13]), "+f"(d[14]), "+f"(d[15]), "+f"(d[16]), "+f"(d[17]), "+f"(d[18]), "+f"(d[19]), "+f"(d[20]), "+f"(d[21]), "+f"(d[22]), "+f"(d[23]), "+f"(d[24]), "+f"(d[25]), "+f"(d[26]), "+f"(d[27]), "+f"(d[28]), "+f"(d[29]), "+f"(d[30]), "+f"(d[31]), "+f"(d[32]), "+f"(d[33]), "+f"(d[34]), "+f"(d[35]), "+f"(d[36]), "+f"(d[37]), "+f"(d[38]), "+f"(d[39]), "+f"(d[40]), "+f"(d[41]), "+f"(d[42]), "+f"(d[43]), "+f"(d[44]), "+f"(d[45]), "+f"(d[46]), "+f"(d[47])
        : "r"(a[AOFF + 0][0]), "r"(a[AOFF + 0][1]), "r"(a[AOFF + 0][2]), "r"(a[AOFF + 0][3]), "r"(a[AOFF + 1][0]), "r"(a[AOFF + 1][1]), "r"(a[AOFF + 1][2]), "r"(a[AOFF + 1][3]), "r"(a[AOFF + 2][0]), "r"(a[AOFF + 2][1]), "r"(a[AOFF + 2][2]), "r"(a[AOFF + 2][3]), "r"(a[AOFF + 3][0]), "r"(a[AOFF + 3][1]), "r"(a[AOFF + 3][2]), "r"(a[AOFF + 3][3]), "r"(a[AOFF + 4][0]), "r"(a[AOFF + 4][1]), "r"(a[AOFF + 4][2]), "r"(a[AOFF + 4][3]), "l"(descB), "n"(BOFF >> 4));
}
};
template <> struct Rng<1, 3, 8> {
template <int BOFF, int AOFF, int NA>
static __device__ __forceinline__ void run(float (&d)[48], const uint32_t (&a)[NA][4], uint64_t descB) {
    asm volatile(
        "{\n"
        ".reg .pred p0, p1;\n"
        ".reg .b64 ta, ta0, tb, tb0;\n"
        "setp.ne.b32 p0, 0, 0;\n"
        "setp.eq.b32 p1, 0, 0;\n"
        "add.s64 tb0, %68, %69;\n"
        "add.s64 tb, tb0, 96;\n"
        "wgmma.mma_async.sync.aligned.m64n96k16.f32.bf16.bf16 {%0, %1, %2, %3, %4, %5, %6, %7, %8, %9, %10, %11, %12, %13, %14, %15, %16, %17, %18, %19, %20, %21, %22, %23, %24, %25, %26, %27, %28, %29, %30, %31, %32, %33, %34, %35, %36, %37, %38, %39, %40, %41, %42, %43, %44, %45, %46, %47}, {%48, %49, %50, %51}, tb, p1, 1, 1, 1;\n"
        "add.s64 tb, tb0, 128;\n"
        "wgmma.mma_async.sync.aligned.m64n96k16.f32.bf16.bf16 {%0, %1, %2, %3, %4, %5, %6, %7, %8, %9, %10, %11, %12, %13, %14, %15, %16, %17, %18, %19, %20, %21, %22, %23, %24, %25, %26, %27, %28, %29, %30, %31, %32, %33, %34, %35, %36, %37, %38, %39, %40, %41, %42, %43, %44, %45, %46, %47}, {%52, %53, %54, %55}, tb, p1, 1, 1, 1;\n"
        "add.s64 tb, tb0, 160;\n"
        "wgmma.mma_async.sync.aligned.m64n96k16.f32.bf16.bf16 {%0, %1, %2, %3, %4, %5, %6, %7, %8, %9, %10, %11, %12, %13, %14, %15, %16, %17, %18, %19, %20, %21, %22, %23, %24, %25, %26, %27, %28, %29, %30, %31, %32, %33, %34, %35, %36, %37, %38, %39, %40, %41, %42, %43, %44, %45, %46, %47}, {%56, %57, %58, %59}, tb, p1, 1, 1, 1;\n"
        "add.s64 tb, tb0, 192;\n"
        "wgmma.mma_async.sync.aligned.m64n96k16.f32.bf16.bf16 {%0, %1, %2, %3, %4, %5, %6, %7, %8, %9, %10, %11, %12, %13, %14, %15, %16, %17, %18, %19, %20, %21, %22, %23, %24, %25, %26, %27, %28, %29, %30, %31, %32, %33, %34, %35, %36, %37, %38, %39, %40, %41, %42, %43, %44, %45, %46, %47}, {%60, %61, %62, %63}, tb, p1, 1, 1, 1;\n"
        "add.s64 tb, tb0, 224;\n"
        "wgmma.mma_async.sync.aligned.m64n96k16.f32.bf16.bf16 {%0, %1, %2, %3, %4, %5, %6, %7, %8, %9, %10, %11, %12, %13, %14, %15, %16, %17, %18, %19, %20, %21, %22, %23, %24, %25, %26, %27, %28, %29, %30, %31, %32, %33, %34, %35, %36, %37, %38, %39, %40, %41, %42, %43, %44, %45, %46, %47}, {%64, %65, %66, %67}, tb, p1, 1, 1, 1;\n"
        "}\n"
        : "+f"(d[0]), "+f"(d[1]), "+f"(d[2]), "+f"(d[3]), "+f"(d[4]), "+f"(d[5]), "+f"(d[6]), "+f"(d[7]), "+f"(d[8]), "+f"(d[9]), "+f"(d[10]), "+f"(d[11]), "+f"(d[12]), "+f"(d[13]), "+f"(d[14]), "+f"(d[15]), "+f"(d[16]), "+f"(d[17]), "+f"(d[18]), "+f"(d[19]), "+f"(d[20]), "+f"(d[21]), "+f"(d[22]), "+f"(d[23]), "+f"(d[24]), "+f"(d[25]), "+f"(d[26]), "+f"(d[27]), "+f"(d[28]), "+f"(d[29]), "+f"(d[30]), "+f"(d[31]), "+f"(d[32]), "+f"(d[33]), "+f"(d[34]), "+f"(d[35]), "+f"(d[36]), "+f"(d[37]), "+f"(d[38]), "+f"(d[39]), "+f"(d[40]), "+f"(d[41]), "+f"(d[42]), "+f"(d[43]), "+f"(d[44]), "+f"(d[45]), "+f"(d[46]), "+f"(d[47])
        : "r"(a[AOFF + 0][0]), "r"(a[AOFF + 0][1]), "r"(a[AOFF + 0][2]), "r"(a[AOFF + 0][3]), "r"(a[AOFF + 1][0]), "r"(a[AOFF + 1][1]), "r"(a[AOFF + 1][2]), "r"(a[AOFF + 1][3]), "r"(a[AOFF + 2][0]), "r"(a[AOFF + 2][1]), "r"(a[AOFF + 2][2]), "r"(a[AOFF + 2][3]), "r"(a[AOFF + 3][0]), "r"(a[AOFF + 3][1]), "r"(a[AOFF + 3][2]), "r"(a[AOFF + 3][3]), "r"(a[AOFF + 4][0]), "r"(a[AOFF + 4][1]), "r"(a[AOFF + 4][2]), "r"(a[AOFF + 4][3]), "l"(descB), "n"(BOFF >> 4));
}
};
template <> struct Rng<0, 3, 12> {
template <int BOFF, int AOFF, int NA>
static __device__ __forceinline__ void run(float (&d)[48], const uint32_t (&a)[NA][4], uint64_t descB) {
    asm volatile(
        "{\n"
        ".reg .pred p0, p1;\n"
        ".reg .b64 ta, ta0, tb, tb0;\n"
        "setp.ne.b32 p0, 0, 0;\n"
        "setp.eq.b32 p1, 0, 0;\n"
        "add.s64 tb0, %84, %85;\n"
        "add.s64 tb, tb0, 96;\n"
        "wgmma.mma_async.sync.aligned.m64n96k16.f32.bf16.bf16 {%0, %1, %2, %3, %4, %5, %6, %7, %8, %9, %10, %11, %12, %13, %14, %15, %16, %17, %18, %19, %20, %21, %22, %23, %24, %25, %26, %27, %28, %29, %30, %31, %32, %33, %34, %35, %36, %37, %38, %39, %40, %41, %42, %43, %44, %45, %46, %47}, {%48, %49, %50, %51}, tb, p1, 1, 1, 1;\n"
        "add.s64 tb, tb0, 1536;\n"
        "wgmma.mma_async.sync.aligned.m64n96k16.f32.bf16.bf16 {%0, %1, %2, %3, %4, %5, %6, %7, %8, %9, %10, %11, %12, %13, %14, %15, %16, %17, %18, %19, %20, %21, %22, %23, %24, %25, %26, %27, %28, %29, %30, %31, %32, %33, %34, %35, %36, %37, %38, %39, %40, %41, %42, %43, %44, %45, %46, %47}, {%52, %53, %54, %55}, tb, p1, 1, 1, 1;\n"
        "add.s64 tb, tb0, 1568;\n"
        "wgmma.mma_async.sync.aligned.m64n96k16.f32.bf16.bf16 {%0, %1, %2, %3, %4, %5, %6, %7, %8, %9, %10, %11, %12, %13, %14, %15, %16, %17, %18, %19, %20, %21, %22, %23, %24, %25, %26, %27, %28, %29, %30, %31, %32, %33, %34, %35, %36, %37, %38, %39, %40, %41, %42, %43, %44, %45, %46, %47}, {%56, %57, %58, %59}, tb, p1, 1, 1, 1;\n"
        "add.s64 tb, tb0, 1600;\n"
        "wgmma.mma_async.sync.aligned.m64n96k16.f32.bf16.bf16 {%0, %1, %2, %3, %4, %5, %6, %7, %8, %9, %10, %11, %12, %13, %14, %15, %16, %17, %18, %19, %20, %21, %22, %23, %24, %25, %26, %27, %28, %29, %30, %31, %32, %33, %34, %35, %36, %37, %38, %39, %40, %41, %42, %43, %44, %45, %46, %47}, {%60, %61, %62, %63}, tb, p1, 1, 1, 1;\n"
        "add.s64 tb, tb0, 1632;\n"
        "wgmma.mma_async.sync.aligned.m64n96k16.f32.bf16.bf16 {%0, %1, %2, %3, %4, %5, %6, %7, %8, %9, %10, %11, %12, %13, %14, %15, %16, %17, %18, %19, %20, %21, %22, %23, %24, %25, %26, %27, %28, %29, %30, %31, %32, %33, %34, %35, %36, %37, %38, %39, %40, %41, %42, %43, %44, %45, %46, %47}, {%64, %65, %66, %67}, tb, p1, 1, 1, 1;\n"
        "add.s64 tb, tb0, 3072;\n"
        "wgmma.mma_async.sync.aligned.m64n96k16.f32.bf16.bf16 {%0, %1, %2, %3, %4, %5, %6, %7, %8, %9, %10, %11, %12, %13, %14, %15, %16, %17, %18, %19, %20, %21, %22, %23, %24, %25, %26, %27, %28, %29, %30, %31, %32, %33, %34, %35, %36, %37, %38, %39, %40, %41, %42, %43, %44, %45, %46, %47}, {%68, %69, %70, %71}, tb, p1, 1, 1, 1;\n"
        "add.s64 tb, tb0, 3104;\n"
        "wgmma.mma_async.sync.aligned.m64n96k16.f32.bf16.bf16 {%0, %1, %2, %3, %4, %5, %6, %7, %8, %9, %10, %11, %12, %13, %14, %15, %16, %17, %18, %19, %20, %21, %22, %23, %24, %25, %26, %27, %28, %29, %30, %31, %32, %33, %34, %35, %36, %37, %38, %39, %40, %41, %42, %43, %44, %45, %46, %47}, {%72, %73, %74, %75}, tb, p1, 1, 1, 1;\n"
        "add.s64 tb, tb0, 3136;\n"
        "wgmma.mma_async.sync.aligned.m64n96k16.f32.bf16.bf16 {%0, %1, %2, %3, %4, %5, %6, %7, %8, %9, %10, %11, %12, %13, %14, %15, %16, %17, %18, %19, %20, %21, %22, %23, %24, %25, %26, %27, %28, %29, %30, %31, %32, %33, %34, %35, %36, %37, %38, %39, %40, %41, %42, %43, %44, %45, %46, %47}, {%76, %77, %78, %79}, tb, p1, 1, 1, 1;\n"
        "add.s64 tb, tb0, 3168;\n"
        "wgmma.mma_async.sync.aligned.m64n96k16.f32.bf16.bf16 {%0, %1, %2, %3, %4, %5, %6, %7, %8, %9, %10, %11, %12, %13, %14, %15, %16, %17, %18, %19, %20, %21, %22, %23, %24, %25, %26, %27, %28, %29, %30, %31, %32, %33, %34, %35, %36, %37, %38, %39, %40, %41, %42, %43, %44, %45, %46, %47}, {%80, %81, %82, %83}, tb, p1, 1, 1, 1;\n"
        "}\n"
        : "+f"(d[0]), "+f"(d[1]), "+f"(d[2]), "+f"(d[3]), "+f"(d[4]), "+f"(d[5]), "+f"(d[6]), "+f"(d[7]), "+f"(d[8]), "+f"(d[9]), "+f"(d[10]), "+f"(d[11]), "+f"(d[12]), "+f"(d[13]), "+f"(d[14]), "+f"(d[15]), "+f"(d[16]), "+f"(d[17]), "+f"(d[18]), "+f"(d[19]), "+f"(d[20]), "+f"(d[21]), "+f"(d[22]), "+f"(d[23]), "+f"(d[24]), "+f"(d[25]), "+f"(d[26]), "+f"(d[27]), "+f"(d[28]), "+f"(d[29]), "+f"(d[30]), "+f"(d[31]), "+f"(d[32]), "+f"(d[33]), "+f"(d[34]), "+f"(d[35]), "+f"(d[36]), "+f"(d[37]), "+f"(d[38]), "+f"(d[39]), "+f"(d[40]), "+f"(d[41]), "+f"(d[42]), "+f"(d[43]), "+f"(d[44]), "+f"(d[45]), "+f"(d[46]), "+f"(d[47])
        : "r"(a[AOFF + 0][0]), "r"(a[AOFF + 0][1]), "r"(a[AOFF + 0][2]), "r"(a[AOFF + 0][3]), "r"(a[AOFF + 1][0]), "r"(a[AOFF + 1][1]), "r"(a[AOFF + 1][2]), "r"(a[AOFF + 1][3]), "r"(a[AOFF + 2][0]), "r"(a[AOFF + 2][1]), "r"(a[AOFF + 2][2]), "r"(a[AOFF + 2][3]), "r"(a[AOFF + 3][0]), "r"(a[AOFF + 3][1]), "r"(a[AOFF + 3][2]), "r"(a[AOFF + 3][3]), "r"(a[AOFF + 4][0]), "r"(a[AOFF + 4][1]), "r"(a[AOFF + 4][2]), "r"(a[AOFF + 4][3]), "r"(a[AOFF + 5][0]), "r"(a[AOFF + 5][1]), "r"(a[AOFF + 5][2]), "r"(a[AOFF + 5][3]), "r"(a[AOFF + 6][0]), "r"(a[AOFF + 6][1]), "r"(a[AOFF + 6][2]), "r"(a[AOFF + 6][3]), "r"(a[AOFF + 7][0]), "r"(a[AOFF + 7][1]), "r"(a[AOFF + 7][2]), "r"(a[AOFF + 7][3]), "r"(a[AOFF + 8][0]), "r"(a[AOFF + 8][1]), "r"(a[AOFF + 8][2]), "r"(a[AOFF + 8][3]), "l"(descB), "n"(BOFF >> 4));
}
};
template <> struct Rng<1, 3, 12> {
template <int BOFF, int AOFF, int NA>
static __device__ __forceinline__ void run(float (&d)[48], const uint32_t (&a)[NA][4], uint64_t descB) {
    asm volatile(
        "{\n"
        ".reg .pred p0, p1;\n"
        ".reg .b64 ta, ta0, tb, tb0;\n"
        "setp.ne.b32 p0, 0, 0;\n"
        "setp.eq.b32 p1, 0, 0;\n"
        "add.s64 tb0, %84, %85;\n"
        "add.s64 tb, tb0, 96;\n"
        "wgmma.mma_async.sync.aligned.m64n96k16.f32.bf16.bf16 {%0, %1, %2, %3, %4, %5, %6, %7, %8, %9, %10, %11, %12, %13, %14, %15, %16, %17, %18, %19, %20, %21, %22, %23, %24, %25, %26, %27, %28, %29, %30, %31, %32, %33, %34, %35, %36, %37, %38, %39, %40, %41, %42, %43, %44, %45, %46, %47}, {%48, %49, %50, %51}, tb, p1, 1, 1, 1;\n"
        "add.s64 tb, tb0, 128;\n"
        "wgmma.mma_async.sync.aligned.m64n96k16.f32.bf16.bf16 {%0, %1, %2, %3, %4, %5, %6, %7, %8, %9, %10, %11, %12, %13, %14, %15, %16, %17, %18, %19, %20, %21, %22, %23, %24, %25, %26, %27, %28, %29, %30, %31, %32, %33, %34, %35, %36, %37, %38, %39, %40, %41, %42, %43, %44, %45, %46, %47}, {%52, %53, %54, %55}, tb, p1, 1, 1, 1;\n"
        "add.s64 tb, tb0, 160;\n"
        "wgmma.mma_async.sync.aligned.m64n96k16.f32.bf16.bf16 {%0, %1, %2, %3, %4, %5, %6, %7, %8, %9, %10, %11, %12, %13, %14, %15, %16, %17, %18, %19, %20, %21, %22, %23, %24, %25, %26, %27, %28, %29, %30, %31, %32, %33, %34, %35, %36, %37, %38, %39, %40, %41, %42, %43, %44, %45, %46, %47}, {%56, %57, %58, %59}, tb, p1, 1, 1, 1;\n"
        "add.s64 tb, tb0, 192;\n"
        "wgmma.mma_async.sync.aligned.m64n96k16.f32.bf16.bf16 {%0, %1, %2, %3, %4, %5, %6, %7, %8, %9, %10, %11, %12, %13, %14, %15, %16, %17, %18, %19, %20, %21, %22, %23, %24, %25, %26, %27, %28, %29, %30, %31, %32, %33, %34, %35, %36, %37, %38, %39, %40, %41, %42, %43, %44, %45, %46, %47}, {%60, %61, %62, %63}, tb, p1, 1, 1, 1;\n"
        "add.s64 tb, tb0, 224;\n"
        "wgmma.mma_async.sync.aligned.m64n96k16.f32.bf16.bf16 {%0, %1, %2, %3, %4, %5, %6, %7, %8, %9, %10, %11, %12, %13, %14, %15, %16, %17, %18, %19, %20, %21, %22, %23, %24, %25, %26, %27, %28, %29, %30, %31, %32, %33, %34, %35, %36, %37, %38, %39, %40, %41, %42, %43, %44, %45, %46, %47}, {%64, %65, %66, %67}, tb, p1, 1, 1, 1;\n"
        "add.s64 tb, tb0, 256;\n"
        "wgmma.mma_async.sync.aligned.m64n96k16.f32.bf16.bf16 {%0, %1, %2, %3, %4, %5, %6, %7, %8, %9, %10, %11, %12, %13, %14, %15, %16, %17, %18, %19, %20, %21, %22, %23, %24, %25, %26, %27, %28, %29, %30, %31, %32, %33, %34, %35, %36, %37, %38, %39, %40, %41, %42, %43, %44, %45, %46, %47}, {%68, %69, %70, %71}, tb, p1, 1, 1, 1;\n"
        "add.s64 tb, tb0, 288;\n"
        "wgmma.mma_async.sync.aligned.m64n96k16.f32.bf16.bf16 {%0, %1, %2, %3, %4, %5, %6, %7, %8, %9, %10, %11, %12, %13, %14, %15, %16, %17, %18, %19, %20, %21, %22, %23, %24, %25, %26, %27, %28, %29, %30, %31, %32, %33, %34, %35, %36, %37, %38, %39, %40, %41, %42, %43, %44, %45, %46, %47}, {%72, %73, %74, %75}, tb, p1, 1, 1, 1;\n"
        "add.s64 tb, tb0, 320;\n"
        "wgmma.mma_async.sync.aligned.m64n96k16.f32.bf16.bf16 {%0, %1, %2, %3, %4, %5, %6, %7, %8, %9, %10, %11, %12, %13, %14, %15, %16, %17, %18, %19, %20, %21, %22, %23, %24, %25, %26, %27, %28, %29, %30, %31, %32, %33, %34, %35, %36, %37, %38, %39, %40, %41, %42, %43, %44, %45, %46, %47}, {%76, %77, %78, %79}, tb, p1, 1, 1, 1;\n"
        "add.s64 tb, tb0, 352;\n"
        "wgmma.mma_async.sync.aligned.m64n96k16.f32.bf16.bf16 {%0, %1, %2, %3, %4, %5, %6, %7, %8, %9, %10, %11, %12, %13, %14, %15, %16, %17, %18, %19, %20, %21, %22, %23, %24, %25, %26, %27, %28, %29, %30, %31, %32, %33, %34, %35, %36, %37, %38, %39, %40, %41, %42, %43, %44, %45, %46, %47}, {%80, %81, %82, %83}, tb, p1, 1, 1, 1;\n"
        "}\n"
        : "+f"(d[0]), "+f"(d[1]), "+f"(d[2]), "+f"(d[3]), "+f"(d[4]), "+f"(d[5]), "+f"(d[6]), "+f"(d[7]), "+f"(d[8]), "+f"(d[9]), "+f"(d[10]), "+f"(d[11]), "+f"(d[12]), "+f"(d[13]), "+f"(d[14]), "+f"(d[15]), "+f"(d[16]), "+f"(d[17]), "+f"(d[18]), "+f"(d[19]), "+f"(d[20]), "+f"(d[21]), "+f"(d[22]), "+f"(d[23]), "+f"(d[24]), "+f"(d[25]), "+f"(d[26]), "+f"(d[27]), "+f"(d[28]), "+f"(d[29]), "+f"(d[30]), "+f"(d[31]), "+f"(d[32]), "+f"(d[33]), "+f"(d[34]), "+f"(d[35]), "+f"(d[36]), "+f"(d[37]), "+f"(d[38]), "+f"(d[39]), "+f"(d[40]), "+f"(d[41]), "+f"(d[42]), "+f"(d[43]), "+f"(d[44]), "+f"(d[45]), "+f"(d[46]), "+f"(d[47])
        : "r"(a[AOFF + 0][0]), "r"(a[AOFF + 0][1]), "r"(a[AOFF + 0][2]), "r"(a[AOFF + 0][3]), "r"(a[AOFF + 1][0]), "r"(a[AOFF + 1][1]), "r"(a[AOFF + 1][2]), "r"(a[AOFF + 1][3]), "r"(a[AOFF + 2][0]), "r"(a[AOFF + 2][1]), "r"(a[AOFF + 2][2]), "r"(a[AOFF + 2][3]), "r"(a[AOFF + 3][0]), "r"(a[AOFF + 3][1]), "r"(a[AOFF + 3][2]), "r"(a[AOFF + 3][3]), "r"(a[AOFF + 4][0]), "r"(a[AOFF + 4][1]), "r"(a[AOFF + 4][2]), "r"(a[AOFF + 4][3]), "r"(a[AOFF + 5][0]), "r"(a[AOFF + 5][1]), "r"(a[AOFF + 5][2]), "r"(a[AOFF + 5][3]), "r"(a[AOFF + 6][0]), "r"(a[AOFF + 6][1]), "r"(a[AOFF + 6][2]), "r"(a[AOFF + 6][3]), "r"(a[AOFF + 7][0]), "r"(a[AOFF + 7][1]), "r"(a[AOFF + 7][2]), "r"(a[AOFF + 7][3]), "r"(a[AOFF + 8][0]), "r"(a[AOFF + 8][1]), "r"(a[AOFF + 8][2]), "r"(a[AOFF + 8][3]), "l"(descB), "n"(BOFF >> 4));
}
};
template <> struct Rng<0, 4, 6> {
template <int BOFF, int AOFF, int NA>
static __device__ __forceinline__ void run(float (&d)[48], const uint32_t (&a)[NA][4], uint64_t descB) {
    asm volatile(
        "{\n"
        ".reg .pred p0, p1;\n"
        ".reg .b64 ta, ta0, tb, tb0;\n"
        "setp.ne.b32 p0, 0, 0;\n"
        "setp.eq.b32 p1, 0, 0;\n"
        "add.s64 tb0, %56, %57;\n"
        "add.s64 tb, tb0, 1536;\n"
        "wgmma.mma_async.sync.aligned.m64n96k16.f32.bf16.bf16 {%0, %1, %2, %3, %4, %5, %6, %7, %8, %9, %10, %11, %12, %13, %14, %15, %16, %17, %18, %19, %20, %21, %22, %23, %24, %25, %26, %27, %28, %29, %30, %31, %32, %33, %34, %35, %36, %37, %38, %39, %40, %41, %42, %43, %44, %45, %46, %47}, {%48, %49, %50, %51}, tb, p1, 1, 1, 1;\n"
        "add.s64 tb, tb0, 1568;\n"
        "wgmma.mma_async.sync.aligned.m64n96k16.f32.bf16.bf16 {%0, %1, %2, %3, %4, %5, %6, %7, %8, %9, %10, %11, %12, %13, %14, %15, %16, %17, %18, %19, %20, %21, %22, %23, %24, %25, %26, %27, %28, %29, %30, %31, %32, %33, %34, %35, %36, %37, %38, %39, %40, %41, %42, %43, %44, %45, %46, %47}, {%52, %53, %54, %55}, tb, p1, 1, 1, 1;\n"
        "}\n"
        : "+f"(d[0]), "+f"(d[1]), "+f"(d[2]), "+f"(d[3]), "+f"(d[4]), "+f"(d[5]), "+f"(d[6]), "+f"(d[7]), "+f"(d[8]), "+f"(d[9]), "+f"(d[10]), "+f"(d[11]), "+f"(d[12]), "+f"(d[13]), "+f"(d[14]), "+f"(d[15]), "+f"(d[16]), "+f"(d[17]), "+f"(d[18]), "+f"(d[19]), "+f"(d[20]), "+f"(d[21]), "+f"(d[22]), "+f"(d[23]), "+f"(d[24]), "+f"(d[25]), "+f"(d[26]), "+f"(d[27]), "+f"(d[28]), "+f"(d[29]), "+f"(d[30]), "+f"(d[31]), "+f"(d[32]), "+f"(d[33]), "+f"(d[34]), "+f"(d[35]), "+f"(d[36]), "+f"(d[37]), "+f"(d[38]), "+f"(d[39]), "+f"(d[40]), "+f"(d[41]), "+f"(d[42]), "+f"(d[43]), "+f"(d[44]), "+f"(d[45]), "+f"(d[46]), "+f"(d[47])
        : "r"(a[AOFF + 0][0]), "r"(a[AOFF + 0][1]), "r"(a[AOFF + 0][2]), "r"(a[AOFF + 0][3]), "r"(a[AOFF + 1][0]), "r"(a[AOFF + 1][1]), "r"(a[AOFF + 1][2]), "r"(a[AOFF + 1][3]), "l"(descB), "n"(BOFF >> 4));
}
};
template <> struct Rng<1, 4, 6> {
template <int BOFF, int AOFF, int NA>
static __device__ __forceinline__ void run(float (&d)[48], const uint32_t (&a)[NA][4], uint64_t descB) {
    asm volatile(
        "{\n"
        ".reg .pred p0, p1;\n"
        ".reg .b64 ta, ta0, tb, tb0;\n"
        "setp.ne.b32 p0, 0, 0;\n"
        "setp.eq.b32 p1, 0, 0;\n"
        "add.s64 tb0, %56, %57;\n"
        "add.s64 tb, tb0, 128;\n"
        "wgmma.mma_async.sync.aligned.m64n96k16.f32.bf16.bf16 {%0, %1, %2, %3, %4, %5, %6, %7, %8, %9, %10, %11, %12, %13, %14, %15, %16, %17, %18, %19, %20, %21, %22, %23, %24, %25, %26, %27, %28, %29, %30, %31, %32, %33, %34, %35, %36, %37, %38, %39, %40, %41, %42, %43, %44, %45, %46, %47}, {%48, %49, %50, %51}, tb, p1, 1, 1, 1;\n"
        "add.s64 tb, tb0, 160;\n"
        "wgmma.mma_async.sync.aligned.m64n96k16.f32.bf16.bf16 {%0, %1, %2, %3, %4, %5, %6, %7, %8, %9, %10, %11, %12, %13, %14, %15, %16, %17, %18, %19, %20, %21, %22, %23, %24, %25, %26, %27, %28, %29, %30, %31, %32, %33, %34, %35, %36, %37, %38, %39, %40, %41, %42, %43, %44, %45, %46, %47}, {%52, %53, %54, %55}, tb, p1, 1, 1, 1;\n"
        "}\n"
        : "+f"(d[0]), "+f"(d[1]), "+f"(d[2]), "+f"(d[3]), "+f"(d[4]), "+f"(d[5]), "+f"(d[6]), "+f"(d[7]), "+f"(d[8]), "+f"(d[9]), "+f"(d[10]), "+f"(d[11]), "+f"(d[12]), "+f"(d[13]), "+f"(d[14]), "+f"(d[15]), "+f"(d[16]), "+f"(d[17]), "+f"(d[18]), "+f"(d[19]), "+f"(d[20]), "+f"(d[21]), "+f"(d[22]), "+f"(d[23]), "+f"(d[24]), "+f"(d[25]), "+f"(d[26]), "+f"(d[27]), "+f"(d[28]), "+f"(d[29]), "+f"(d[30]), "+f"(d[31]), "+f"(d[32]), "+f"(d[33]), "+f"(d[34]), "+f"(d[35]), "+f"(d[36]), "+f"(d[37]), "+f"(d[38]), "+f"(d[39]), "+f"(d[40]), "+f"(d[41]), "+f"(d[42]), "+f"(d[43]), "+f"(d[44]), "+f"(d[45]), "+f"(d[46]), "+f"(d[47])
        : "r"(a[AOFF + 0][0]), "r"(a[AOFF + 0][1]), "r"(a[AOFF + 0][2]), "r"(a[AOFF + 0][3]), "r"(a[AOFF + 1][0]), "r"(a[AOFF + 1][1]), "r"(a[AOFF + 1][2]), "r"(a[AOFF + 1][3]), "l"(descB), "n"(BOFF >> 4));
}
};
template <> struct Rng<0, 4, 7> {
template <int BOFF, int AOFF, int NA>
static __device__ __forceinline__ void run(float (&d)[48], const uint32_t (&a)[NA][4], uint64_t descB) {
    asm volatile(
        "{\n"
        ".reg .pred p0, p1;\n"
        ".reg .b64 ta, ta0, tb, tb0;\n"
        "setp.ne.b32 p0, 0, 0;\n"
        "setp.eq.b32 p1, 0, 0;\n"
        "add.s64 tb0, %60, %61;\n"
        "add.s64 tb, tb0, 1536;\n"
        "wgmma.mma_async.sync.aligned.m64n96k16.f32.bf16.bf16 {%0, %1, %2, %3, %4, %5, %6, %7, %8, %9, %10, %11, %12, %13, %14, %15, %16, %17, %18, %19, %20, %21, %22, %23, %24, %25, %26, %27, %28, %29, %30, %31, %32, %33, %34, %35, %36, %37, %38, %39, %40, %41, %42, %43, %44, %45, %46, %47}, {%48, %49, %50, %51}, tb, p1, 1, 1, 1;\n"
        "add.s64 tb, tb0, 1568;\n"
        "wgmma.mma_async.sync.aligned.m64n96k16.f32.bf16.bf16 {%0, %1, %2, %3, %4, %5, %6, %7, %8, %9, %10, %11, %12, %13, %14, %15, %16, %17, %18, %19, %20, %21, %22, %23, %24, %25, %26, %27, %28, %29, %30, %31, %32, %33, %34, %35, %36, %37, %38, %39, %40, %41, %42, %43, %44, %45, %46, %47}, {%52, %53, %54, %55}, tb, p1, 1, 1, 1;\n"
        "add.s64 tb, tb0, 1600;\n"
        "wgmma.mma_async.sync.aligned.m64n96k16.f32.bf16.bf16 {%0, %1, %2, %3, %4, %5, %6, %7, %8, %9, %10, %11, %12, %13, %14, %15, %16, %17, %18, %19, %20, %21, %22, %23, %24, %25, %26, %27, %28, %29, %30, %31, %32, %33, %34, %35, %36, %37, %38, %39, %40, %41, %42, %43, %44, %45, %46, %47}, {%56, %57, %58, %59}, tb, p1, 1, 1, 1;\n"
        "}\n"
        : "+f"(d[0]), "+f"(d[1]), "+f"(d[2]), "+f"(d[3]), "+f"(d[4]), "+f"(d[5]), "+f"(d[6]), "+f"(d[7]), "+f"(d[8]), "+f"(d[9]), "+f"(d[10]), "+f"(d[11]), "+f"(d[12]), "+f"(d[13]), "+f"(d[14]), "+f"(d[15]), "+f"(d[16]), "+f"(d[17]), "+f"(d[18]), "+f"(d[19]), "+f"(d[20]), "+f"(d[21]), "+f"(d[22]), "+f"(d[23]), "+f"(d[24]), "+f"(d[25]), "+f"(d[26]), "+f"(d[27]), "+f"(d[28]), "+f"(d[29]), "+f"(d[30]), "+f"(d[31]), "+f"(d[32]), "+f"(d[33]), "+f"(d[34]), "+f"(d[35]), "+f"(d[36]), "+f"(d[37]), "+f"(d[38]), "+f"(d[39]), "+f"(d[40]), "+f"(d[41]), "+f"(d[42]), "+f"(d[43]), "+f"(d[44]), "+f"(d[45]), "+f"(d[46]), "+f"(d[47])
        : "r"(a[AOFF + 0][0]), "r"(a[AOFF + 0][1]), "r"(a[AOFF + 0][2]), "r"(a[AOFF + 0][3]), "r"(a[AOFF + 1][0]), "r"(a[AOFF + 1][1]), "r"(a[AOFF + 1][2]), "r"(a[AOFF + 1][3]), "r"(a[AOFF + 2][0]), "r"(a[AOFF + 2][1]), "r"(a[AOFF + 2][2]), "r"(a[AOFF + 2][3]), "l"(descB), "n"(BOFF >> 4));
}
};
template <> struct Rng<1, 4, 7> {
template <int BOFF, int AOFF, int NA>
static __device__ __forceinline__ void run(float (&d)[48], const uint32_t (&a)[NA][4], uint64_t descB) {
    asm volatile(
        "{\n"
        ".reg .pred p0, p1;\n"
        ".reg .b64 ta, ta0, tb, tb0;\n"
        "setp.ne.b32 p0, 0, 0;\n"
        "setp.eq.b32 p1, 0, 0;\n"
        "add.s64 tb0, %60, %61;\n"
        "add.s64 tb, tb0, 128;\n"
        "wgmma.mma_async.sync.aligned.m64n96k16.f32.bf16.bf16 {%0, %1, %2, %3, %4, %5, %6, %7, %8, %9, %10, %11, %12, %13, %14, %15, %16, %17, %18, %19, %20, %21, %22, %23, %24, %25, %26, %27, %28, %29, %30, %31, %32, %33, %34, %35, %36, %37, %38, %39, %40, %41, %42, %43, %44, %45, %46, %47}, {%48, %49, %50, %51}, tb, p1, 1, 1, 1;\n"
        "add.s64 tb, tb0, 160;\n"
        "wgmma.mma_async.sync.aligned.m64n96k16.f32.bf16.bf16 {%0, %1, %2, %3, %4, %5, %6, %7, %8, %9, %10, %11, %12, %13, %14, %15, %16, %17, %18, %19, %20, %21, %22, %23, %24, %25, %26, %27, %28, %29, %30, %31, %32, %33, %34, %35, %36, %37, %38, %39, %40, %41, %42, %43, %44, %45, %46, %47}, {%52, %53, %54, %55}, tb, p1, 1, 1, 1;\n"
        "add.s64 tb, tb0, 192;\n"
        "wgmma.mma_async.sync.aligned.m64n96k16.f32.bf16.bf16 {%0, %1, %2, %3, %4, %5, %6, %7, %8, %9, %10, %11, %12, %13, %14, %15, %16, %17, %18, %19, %20, %21, %22, %23, %24, %25, %26, %27, %28, %29, %30, %31, %32, %33, %34, %35, %36, %37, %38, %39, %40, %41, %42, %43, %44, %45, %46, %47}, {%56, %57, %58, %59}, tb, p1, 1, 1, 1;\n"
        "}\n"
        : "+f"(d[0]), "+f"(d[1]), "+f"(d[2]), "+f"(d[3]), "+f"(d[4]), "+f"(d[5]), "+f"(d[6]), "+f"(d[7]), "+f"(d[8]), "+f"(d[9]), "+f"(d[10]), "+f"(d[11]), "+f"(d[12]), "+f"(d[13]), "+f"(d[14]), "+f"(d[15]), "+f"(d[16]), "+f"(d[17]), "+f"(d[18]), "+f"(d[19]), "+f"(d[20]), "+f"(d[21]), "+f"(d[22]), "+f"(d[23]), "+f"(d[24]), "+f"(d[25]), "+f"(d[26]), "+f"(d[27]), "+f"(d[28]), "+f"(d[29]), "+f"(d[30]), "+f"(d[31]), "+f"(d[32]), "+f"(d[33]), "+f"(d[34]), "+f"(d[35]), "+f"(d[36]), "+f"(d[37]), "+f"(d[38]), "+f"(d[39]), "+f"(d[40]), "+f"(d[41]), "+f"(d[42]), "+f"(d[43]), "+f"(d[44]), "+f"(d[45]), "+f"(d[46]), "+f"(d[47])
        : "r"(a[AOFF + 0][0]), "r"(a[AOFF + 0][1]), "r"(a[AOFF + 0][2]), "r"(a[AOFF + 0][3]), "r"(a[AOFF + 1][0]), "r"(a[AOFF + 1][1]), "r"(a[AOFF + 1][2]), "r"(a[AOFF + 1][3]), "r"(a[AOFF + 2][0]), "r"(a[AOFF + 2][1]), "r"(a[AOFF + 2][2]), "r"(a[AOFF + 2][3]), "l"(descB), "n"(BOFF >> 4));
}
};
template <> struct Rng<0, 4, 8> {
template <int BOFF, int AOFF, int NA>
static __device__ __forceinline__ void run(float (&d)[48], const uint32_t (&a)[NA][4], uint64_t descB) {
    asm volatile(
        "{\n"
        ".reg .pred p0, p1;\n"
        ".reg .b64 ta, ta0, tb, tb0;\n"
        "setp.ne.b32 p0, 0, 0;\n"
        "setp.eq.b32 p1, 0, 0;\n"
        "add.s64 tb0, %64, %65;\n"
        "add.s64 tb, tb0, 1536;\n"
        "wgmma.mma_async.sync.aligned.m64n96k16.f32.bf16.bf16 {%0, %1, %2, %3, %4, %5, %6, %7, %8, %9, %10, %11, %12, %13, %14, %15, %16, %17, %18, %19, %20, %21, %22, %23, %24, %25, %26, %27, %28, %29, %30, %31, %32, %33, %34, %35, %36, %37, %38, %39, %40, %41, %42, %43, %44, %45, %46, %47}, {%48, %49, %50, %51}, tb, p1, 1, 1, 1;\n"
        "add.s64 tb, tb0, 1568;\n"
        "wgmma.mma_async.sync.aligned.m64n96k16.f32.bf16.bf16 {%0, %1, %2, %3, %4, %5, %6, %7, %8, %9, %10, %11, %12, %13, %14, %15, %16, %17, %18, %19, %20, %21, %22, %23, %24, %25, %26, %27, %28, %29, %30, %31, %32, %33, %34, %35, %36, %37, %38, %39, %40, %41, %42, %43, %44, %45, %46, %47}, {%52, %53, %54, %55}, tb, p1, 1, 1, 1;\n"
        "add.s64 tb, tb0, 1600;\n"
        "wgmma.mma_async.sync.aligned.m64n96k16.f32.bf16.bf16 {%0, %1, %2, %3, %4, %5, %6, %7, %8, %9, %10, %11, %12, %13, %14, %15, %16, %17, %18, %19, %20, %21, %22, %23, %24, %25, %26, %27, %28, %29, %30, %31, %32, %33, %34, %35, %36, %37, %38, %39, %40, %41, %42, %43, %44, %45, %46, %47}, {%56, %57, %58, %59}, tb, p1, 1, 1, 1;\n"
        "add.s64 tb, tb0, 1632;\n"
        "wgmma.mma_async.sync.aligned.m64n96k16.f32.bf16.bf16 {%0, %1, %2, %3, %4, %5, %6, %7, %8, %9, %10, %11, %12, %13, %14, %15, %16, %17, %18, %19, %20, %21, %22, %23, %24, %25, %26, %27, %28, %29, %30, %31, %32, %33, %34, %35, %36, %37, %38, %39, %40, %41, %42, %43, %44, %45, %46, %47}, {%60, %61, %62, %63}, tb, p1, 1, 1, 1;\n"
        "}\n"
        : "+f"(d[0]), "+f"(d[1]), "+f"(d[2]), "+f"(d[3]), "+f"(d[4]), "+f"(d[5]), "+f"(d[6]), "+f"(d[7]), "+f"(d[8]), "+f"(d[9]), "+f"(d[10]), "+f"(d[11]), "+f"(d[12]), "+f"(d[13]), "+f"(d[14]), "+f"(d[15]), "+f"(d[16]), "+f"(d[17]), "+f"(d[18]), "+f"(d[19]), "+f"(d[20]), "+f"(d[21]), "+f"(d[22]), "+f"(d[23]), "+f"(d[24]), "+f"(d[25]), "+f"(d[26]), "+f"(d[27]), "+f"(d[28]), "+f"(d[29]), "+f"(d[30]), "+f"(d[31]), "+f"(d[32]), "+f"(d[33]), "+f"(d[34]), "+f"(d[35]), "+f"(d[36]), "+f"(d[37]), "+f"(d[38]), "+f"(d[39]), "+f"(d[40]), "+f"(d[41]), "+f"(d[42]), "+f"(d[43]), "+f"(d[44]), "+f"(d[45]), "+f"(d[46]), "+f"(d[47])
        : "r"(a[AOFF + 0][0]), "r"(a[AOFF + 0][1]), "r"(a[AOFF + 0][2]), "r"(a[AOFF + 0][3]), "r"(a[AOFF + 1][0]), "r"(a[AOFF + 1][1]), "r"(a[AOFF + 1][2]), "r"(a[AOFF + 1][3]), "r"(a[AOFF + 2][0]), "r"(a[AOFF + 2][1]), "r"(a[AOFF + 2][2]), "r"(a[AOFF + 2][3]), "r"(a[AOFF + 3][0]), "r"(a[AOFF + 3][1]), "r"(a[AOFF + 3][2]), "r"(a[AOFF + 3][3]), "l"(descB), "n"(BOFF >> 4));
}
};
template <> struct Rng<1, 4, 8> {
template <int BOFF, int AOFF, int NA>
static __device__ __forceinline__ void run(float (&d)[48], const uint32_t (&a)[NA][4], uint64_t descB) {
    asm volatile(
        "{\n"
        ".reg .pred p0, p1;\n"
        ".reg .b64 ta, ta0, tb, tb0;\n"
        "setp.ne.b32 p0, 0, 0;\n"
        "setp.eq.b32 p1, 0, 0;\n"
        "add.s64 tb0, %64, %65;\n"
        "add.s64 tb, tb0, 128;\n"
        "wgmma.mma_async.sync.aligned.m64n96k16.f32.bf16.bf16 {%0, %1, %2, %3, %4, %5, %6, %7, %8, %9, %10, %11, %12, %13, %14, %15, %16, %17, %18, %19, %20, %21, %22, %23, %24, %25, %26, %27, %28, %29, %30, %31, %32, %33, %34, %35, %36, %37, %38, %39, %40, %41, %42, %43, %44, %45, %46, %47}, {%48, %49, %50, %51}, tb, p1, 1, 1, 1;\n"
        "add.s64 tb, tb0, 160;\n"
        "wgmma.mma_async.sync.aligned.m64n96k16.f32.bf16.bf16 {%0, %1, %2, %3, %4, %5, %6, %7, %8, %9, %10, %11, %12, %13, %14, %15, %16, %17, %18, %19, %20, %21, %22, %23, %24, %25, %26, %27, %28, %29, %30, %31, %32, %33, %34, %35, %36, %37, %38, %39, %40, %41, %42, %43, %44, %45, %46, %47}, {%52, %53, %54, %55}, tb, p1, 1, 1, 1;\n"
        "add.s64 tb, tb0, 192;\n"
        "wgmma.mma_async.sync.aligned.m64n96k16.f32.bf16.bf16 {%0, %1, %2, %3, %4, %5, %6, %7, %8, %9, %10, %11, %12, %13, %14, %15, %16, %17, %18, %19, %20, %21, %22, %23, %24, %25, %26, %27, %28, %29, %30, %31, %32, %33, %34, %35, %36, %37, %38, %39, %40, %41, %42, %43, %44, %45, %46, %47}, {%56, %57, %58, %59}, tb, p1, 1, 1, 1;\n"
        "add.s64 tb, tb0, 224;\n"
        "wgmma.mma_async.sync.aligned.m64n96k16.f32.bf16.bf16 {%0, %1, %2, %3, %4, %5, %6, %7, %8, %9, %10, %11, %12, %13, %14, %15, %16, %17, %18, %19, %20, %21, %22, %23, %24, %25, %26, %27, %28, %29, %30, %31, %32, %33, %34, %35, %36, %37, %38, %39, %40, %41, %42, %43, %44, %45, %46, %47}, {%60, %61, %62, %63}, tb, p1, 1, 1, 1;\n"
        "}\n"
        : "+f"(d[0]), "+f"(d[1]), "+f"(d[2]), "+f"(d[3]), "+f"(d[4]), "+f"(d[5]), "+f"(d[6]), "+f"(d[7]), "+f"(d[8]), "+f"(d[9]), "+f"(d[10]), "+f"(d[11]), "+f"(d[12]), "+f"(d[13]), "+f"(d[14]), "+f"(d[15]), "+f"(d[16]), "+f"(d[17]), "+f"(d[18]), "+f"(d[19]), "+f"(d[20]), "+f"(d[21]), "+f"(d[22]), "+f"(d[23]), "+f"(d[24]), "+f"(d[25]), "+f"(d[26]), "+f"(d[27]), "+f"(d[28]), "+f"(d[29]), "+f"(d[30]), "+f"(d[31]), "+f"(d[32]), "+f"(d[33]), "+f"(d[34]), "+f"(d[35]), "+f"(d[36]), "+f"(d[37]), "+f"(d[38]), "+f"(d[39]), "+f"(d[40]), "+f"(d[41]), "+f"(d[42]), "+f"(d[43]), "+f"(d[44]), "+f"(d[45]), "+f"(d[46]), "+f"(d[47])
        : "r"(a[AOFF + 0][0]), "r"(a[AOFF + 0][1]), "r"(a[AOFF + 0][2]), "r"(a[AOFF + 0][3]), "r"(a[AOFF + 1][0]), "r"(a[AOFF + 1][1]), "r"(a[AOFF + 1][2]), "r"(a[AOFF + 1][3]), "r"(a[AOFF + 2][0]), "r"(a[AOFF + 2][1]), "r"(a[AOFF + 2][2]), "r"(a[AOFF + 2][3]), "r"(a[AOFF + 3][0]), "r"(a[AOFF + 3][1]), "r"(a[AOFF + 3][2]), "r"(a[AOFF + 3][3]), "l"(descB), "n"(BOFF >> 4));
}
};
template <> struct Rng<0, 4, 9> {
template <int BOFF, int AOFF, int NA>
static __device__ __forceinline__ void run(float (&d)[48], const uint32_t (&a)[NA][4], uint64_t descB) {
    asm volatile(
        "{\n"
        ".reg .pred p0, p1;\n"
        ".reg .b64 ta, ta0, tb, tb0;\n"
        "setp.ne.b32 p0, 0, 0;\n"
        "setp.eq.b32 p1, 0, 0;\n"
        "add.s64 tb0, %68, %69;\n"
        "add.s64 tb, tb0, 1536;\n"
        "wgmma.mma_async.sync.aligned.m64n96k16.f32.bf16.bf16 {%0, %1, %2, %3, %4, %5, %6, %7, %8, %9, %10, %11, %12, %13, %14, %15, %16, %17, %18, %19, %20, %21, %22, %23, %24, %25, %26, %27, %28, %29, %30, %31, %32, %33, %34, %35, %36, %37, %38, %39, %40, %41, %42, %43, %44, %45, %46, %47}, {%48, %49, %50, %51}, tb, p1, 1, 1, 1;\n"
        "add.s64 tb, tb0, 1568;\n"
        "wgmma.mma_async.sync.aligned.m64n96k16.f32.bf16.bf16 {%0, %1, %2, %3, %4, %5, %6, %7, %8, %9, %10, %11, %12, %13, %14, %15, %16, %17, %18, %19, %20, %21, %22, %23, %24, %25, %26, %27, %28, %29, %30, %31, %32, %33, %34, %35, %36, %37, %38, %39, %40, %41, %42, %43, %44, %45, %46, %47}, {%52, %53, %54, %55}, tb, p1, 1, 1, 1;\n"
        "add.s64 tb, tb0, 1600;\n"
        "wgmma.mma_async.sync.aligned.m64n96k16.f32.bf16.bf16 {%0, %1, %2, %3, %4, %5, %6, %7, %8, %9, %10, %11, %12, %13, %14, %15, %16, %17, %18, %19, %20, %21, %22, %23, %24, %25, %26, %27, %28, %29, %30, %31, %32, %33, %34, %35, %36, %37, %38, %39, %40, %41, %42, %43, %44, %45, %46, %47}, {%56, %57, %58, %59}, tb, p1, 1, 1, 1;\n"
        "add.s64 tb, tb0, 1632;\n"
        "wgmma.mma_async.sync.aligned.m64n96k16.f32.bf16.bf16 {%0, %1, %2, %3, %4, %5, %6, %7, %8, %9, %10, %11, %12, %13, %14, %15, %16, %17, %18, %19, %20, %21, %22, %23, %24, %25, %26, %27, %28, %29, %30, %31, %32, %33, %34, %35, %36, %37, %38, %39, %40, %41, %42, %43, %44, %45, %46, %47}, {%60, %61, %62, %63}, tb, p1, 1, 1, 1;\n"
        "add.s64 tb, tb0, 3072;\n"
        "wgmma.mma_async.sync.aligned.m64n96k16.f32.bf16.bf16 {%0, %1, %2, %3, %4, %5, %6, %7, %8, %9, %10, %11, %12, %13, %14, %15, %16, %17, %18, %19, %20, %21, %22, %23, %24, %25, %26, %27, %28, %29, %30, %31, %32, %33, %34, %35, %36, %37, %38, %39, %40, %41, %42, %43, %44, %45, %46, %47}, {%64, %65, %66, %67}, tb, p1, 1, 1, 1;\n"
        "}\n"
        : "+f"(d[0]), "+f"(d[1]), "+f"(d[2]), "+f"(d[3]), "+f"(d[4]), "+f"(d[5]), "+f"(d[6]), "+f"(d[7]), "+f"(d[8]), "+f"(d[9]), "+f"(d[10]), "+f"(d[11]), "+f"(d[12]), "+f"(d[13]), "+f"(d[14]), "+f"(d[15]), "+f"(d[16]), "+f"(d[17]), "+f"(d[18]), "+f"(d[19]), "+f"(d[20]), "+f"(d[21]), "+f"(d[22]), "+f"(d[23]), "+f"(d[24]), "+f"(d[25]), "+f"(d[26]), "+f"(d[27]), "+f"(d[28]), "+f"(d[29]), "+f"(d[30]), "+f"(d[31]), "+f"(d[32]), "+f"(d[33]), "+f"(d[34]), "+f"(d[35]), "+f"(d[36]), "+f"(d[37]), "+f"(d[38]), "+f"(d[39]), "+f"(d[40]), "+f"(d[41]), "+f"(d[42]), "+f"(d[43]), "+f"(d[44]), "+f"(d[45]), "+f"(d[46]), "+f"(d[47])
        : "r"(a[AOFF + 0][0]), "r"(a[AOFF + 0][1]), "r"(a[AOFF + 0][2]), "r"(a[AOFF + 0][3]), "r"(a[AOFF + 1][0]), "r"(a[AOFF + 1][1]), "r"(a[AOFF + 1][2]), "r"(a[AOFF + 1][3]), "r"(a[AOFF + 2][0]), "r"(a[AOFF + 2][1]), "r"(a[AOFF + 2][2]), "r"(a[AOFF + 2][3]), "r"(a[AOFF + 3][0]), "r"(a[AOFF + 3][1]), "r"(a[AOFF + 3][2]), "r"(a[AOFF + 3][3]), "r"(a[AOFF + 4][0]), "r"(a[AOFF + 4][1]), "r"(a[AOFF + 4][2]), "r"(a[AOFF + 4][3]), "l"(descB), "n"(BOFF >> 4));
}
};
template <> struct Rng<1, 4, 9> {
template <int BOFF, int AOFF, int NA>
static __device__ __forceinline__ void run(float (&d)[48], const uint32_t (&a)[NA][4], uint64_t descB) {
    asm volatile(
        "{\n"
        ".reg .pred p0, p1;\n"
        ".reg .b64 ta, ta0, tb, tb0;\n"
        "setp.ne.b32 p0, 0, 0;\n"
        "setp.eq.b32 p1, 0, 0;\n"
        "add.s64 tb0, %68, %69;\n"
        "add.s64 tb, tb0, 128;\n"
        "wgmma.mma_async.sync.aligned.m64n96k16.f32.bf16.bf16 {%0, %1, %2, %3, %4, %5, %6, %7, %8, %9, %10, %11, %12, %13, %14, %15, %16, %17, %18, %19, %20, %21, %22, %23, %24, %25, %26, %27, %28, %29, %30, %31, %32, %33, %34, %35, %36, %37, %38, %39, %40, %41, %42, %43, %44, %45, %46, %47}, {%48, %49, %50, %51}, tb, p1, 1, 1, 1;\n"
        "add.s64 tb, tb0, 160;\n"
        "wgmma.mma_async.sync.aligned.m64n96k16.f32.bf16.bf16 {%0, %1, %2, %3, %4, %5, %6, %7, %8, %9, %10, %11, %12, %13, %14, %15, %16, %17, %18, %19, %20, %21, %22, %23, %24, %25, %26, %27, %28, %29, %30, %31, %32, %33, %34, %35, %36, %37, %38, %39, %40, %41, %42, %43, %44, %45, %46, %47}, {%52, %53, %54, %55}, tb, p1, 1, 1, 1;\n"
        "add.s64 tb, tb0, 192;\n"
        "wgmma.mma_async.sync.aligned.m64n96k16.f32.bf16.bf16 {%0, %1, %2, %3, %4, %5, %6, %7, %8, %9, %10, %11, %12, %13, %14, %15, %16, %17, %18, %19, %20, %21, %22, %23, %24, %25, %26, %27, %28, %29, %30, %31, %32, %33, %34, %35, %36, %37, %38, %39, %40, %41, %42, %43, %44, %45, %46, %47}, {%56, %57, %58, %59}, tb, p1, 1, 1, 1;\n"
        "add.s64 tb, tb0, 224;\n"
        "wgmma.mma_async.sync.aligned.m64n96k16.f32.bf16.bf16 {%0, %1, %2, %3, %4, %5, %6, %7, %8, %9, %10, %11, %12, %13, %14, %15, %16, %17, %18, %19, %20, %21, %22, %23, %24, %25, %26, %27, %28, %29, %30, %31, %32, %33, %34, %35, %36, %37, %38, %39, %40, %41, %42, %43, %44, %45, %46, %47}, {%60, %61, %62, %63}, tb, p1, 1, 1, 1;\n"
        "add.s64 tb, tb0, 256;\n"
        "wgmma.mma_async.sync.aligned.m64n96k16.f32.bf16.bf16 {%0, %1, %2, %3, %4, %5, %6, %7, %8, %9, %10, %11, %12, %13, %14, %15, %16, %17, %18, %19, %20, %21, %22, %23, %24, %25, %26, %27, %28, %29, %30, %31, %32, %33, %34, %35, %36, %37, %38, %39, %40, %41, %42, %43, %44, %45, %46, %47}, {%64, %65, %66, %67}, tb, p1, 1, 1, 1;\n"
        "}\n"
        : "+f"(d[0]), "+f"(d[1]), "+f"(d[2]), "+f"(d[3]), "+f"(d[4]), "+f"(d[5]), "+f"(d[6]), "+f"(d[7]), "+f"(d[8]), "+f"(d[9]), "+f"(d[10]), "+f"(d[11]), "+f"(d[12]), "+f"(d[13]), "+f"(d[14]), "+f"(d[15]), "+f"(d[16]), "+f"(d[17]), "+f"(d[18]), "+f"(d[19]), "+f"(d[20]), "+f"(d[21]), "+f"(d[22]), "+f"(d[23]), "+f"(d[24]), "+f"(d[25]), "+f"(d[26]), "+f"(d[27]), "+f"(d[28]), "+f"(d[29]), "+f"(d[30]), "+f"(d[31]), "+f"(d[32]), "+f"(d[33]), "+f"(d[34]), "+f"(d[35]), "+f"(d[36]), "+f"(d[37]), "+f"(d[38]), "+f"(d[39]), "+f"(d[40]), "+f"(d[41]), "+f"(d[42]), "+f"(d[43]), "+f"(d[44]), "+f"(d[45]), "+f"(d[46]), "+f"(d[47])
        : "r"(a[AOFF + 0][0]), "r"(a[AOFF + 0][1]), "r"(a[AOFF + 0][2]), "r"(a[AOFF + 0][3]), "r"(a[AOFF + 1][0]), "r"(a[AOFF + 1][1]), "r"(a[AOFF + 1][2]), "r"(a[AOFF + 1][3]), "r"(a[AOFF + 2][0]), "r"(a[AOFF + 2][1]), "r"(a[AOFF + 2][2]), "r"(a[AOFF + 2][3]), "r"(a[AOFF + 3][0]), "r"(a[AOFF + 3][1]), "r"(a[AOFF + 3][2]), "r"(a[AOFF + 3][3]), "r"(a[AOFF + 4][0]), "r"(a[AOFF + 4][1]), "r"(a[AOFF + 4][2]), "r"(a[AOFF + 4][3]), "l"(descB), "n"(BOFF >> 4));
}
};
template <> struct Rng<0, 4, 12> {
template <int BOFF, int AOFF, int NA>
static __device__ __forceinline__ void run(float (&d)[48], const uint32_t (&a)[NA][4], uint64_t descB) {
    asm volatile(
        "{\n"
        ".reg .pred p0, p1;\n"
        ".reg .b64 ta, ta0, tb, tb0;\n"
        "setp.ne.b32 p0, 0, 0;\n"
        "setp.eq.b32 p1, 0, 0;\n"
        "add.s64 tb0, %80, %81;\n"
        "add.s64 tb, tb0, 1536;\n"
        "wgmma.mma_async.sync.aligned.m64n96k16.f32.bf16.bf16 {%0, %1, %2, %3, %4, %5, %6, %7, %8, %9, %10, %11, %12, %13, %14, %15, %16, %17, %18, %19, %20, %21, %22, %23, %24, %25, %26, %27, %28, %29, %30, %31, %32, %33, %34, %35, %36, %37, %38, %39, %40, %41, %42, %43, %44, %45, %46, %47}, {%48, %49, %50, %51}, tb, p1, 1, 1, 1;\n"
        "add.s64 tb, tb0, 1568;\n"
        "wgmma.mma_async.sync.aligned.m64n96k16.f32.bf16.bf16 {%0, %1, %2, %3, %4, %5, %6, %7, %8, %9, %10, %11, %12, %13, %14, %15, %16, %17, %18, %19, %20, %21, %22, %23, %24, %25, %26, %27, %28, %29, %30, %31, %32, %33, %34, %35, %36, %37, %38, %39, %40, %41, %42, %43, %44, %45, %46, %47}, {%52, %53, %54, %55}, tb, p1, 1, 1, 1;\n"
        "add.s64 tb, tb0, 1600;\n"
        "wgmma.mma_async.sync.aligned.m64n96k16.f32.bf16.bf16 {%0, %1, %2, %3, %4, %5, %6, %7, %8, %9, %10, %11, %12, %13, %14, %15, %16, %17, %18, %19, %20, %21, %22, %23, %24, %25, %26, %27, %28, %29, %30, %31, %32, %33, %34, %35, %36, %37, %38, %39, %40, %41, %42, %43, %44, %45, %46, %47}, {%56, %57, %58, %59}, tb, p1, 1, 1, 1;\n"
        "add.s64 tb, tb0, 1632;\n"
        "wgmma.mma_async.sync.aligned.m64n96k16.f32.bf16.bf16 {%0, %1, %2, %3, %4, %5, %6, %7, %8, %9, %10, %11, %12, %13, %14, %15, %16, %17, %18, %19, %20, %21, %22, %23, %24, %25, %26, %27, %28, %29, %30, %31, %32, %33, %34, %35, %36, %37, %38, %39, %40, %41, %42, %43, %44, %45, %46, %47}, {%60, %61, %62, %63}, tb, p1, 1, 1, 1;\n"
        "add.s64 tb, tb0, 3072;\n"
        "wgmma.mma_async.sync.aligned.m64n96k16.f32.bf16.bf16 {%0, %1, %2, %3, %4, %5, %6, %7, %8, %9, %10, %11, %12, %13, %14, %15, %16, %17, %18, %19, %20, %21, %22, %23, %24, %25, %26, %27, %28, %29, %30, %31, %32, %33, %34, %35, %36, %37, %38, %39, %40, %41, %42, %43, %44, %45, %46, %47}, {%64, %65, %66, %67}, tb, p1, 1, 1, 1;\n"
        "add.s64 tb, tb0, 3104;\n"
        "wgmma.mma_async.sync.aligned.m64n96k16.f32.bf16.bf16 {%0, %1, %2, %3, %4, %5, %6, %7, %8, %9, %10, %11, %12, %13, %14, %15, %16, %17, %18, %19, %20, %21, %22, %23, %24, %25, %26, %27, %28, %29, %30, %31, %32, %33, %34, %35, %36, %37, %38, %39, %40, %41, %42, %43, %44, %45, %46, %47}, {%68, %69, %70, %71}, tb, p1, 1, 1, 1;\n"
        "add.s64 tb, tb0, 3136;\n"
        "wgmma.mma_async.sync.aligned.m64n96k16.f32.bf16.bf16 {%0, %1, %2, %3, %4, %5, %6, %7, %8, %9, %10, %11, %12, %13, %14, %15, %16, %17, %18, %19, %20, %21, %22, %23, %24, %25, %26, %27, %28, %29, %30, %31, %32, %33, %34, %35, %36, %37, %38, %39, %40, %41, %42, %43, %44, %45, %46, %47}, {%72, %73, %74, %75}, tb, p1, 1, 1, 1;\n"
        "add.s64 tb, tb0, 3168;\n"
        "wgmma.mma_async.sync.aligned.m64n96k16.f32.bf16.bf16 {%0, %1, %2, %3, %4, %5, %6, %7, %8, %9, %10, %11, %12, %13, %14, %15, %16, %17, %18, %19, %20, %21, %22, %23, %24, %25, %26, %27, %28, %29, %30, %31, %32, %33, %34, %35, %36, %37, %38, %39, %40, %41, %42, %43, %44, %45, %46, %47}, {%76, %77, %78, %79}, tb, p1, 1, 1, 1;\n"
        "}\n"
        : "+f"(d[0]), "+f"(d[1]), "+f"(d[2]), "+f"(d[3]), "+f"(d[4]), "+f"(d[5]), "+f"(d[6]), "+f"(d[7]), "+f"(d[8]), "+f"(d[9]), "+f"(d[10]), "+f"(d[11]), "+f"(d[12]), "+f"(d[13]), "+f"(d[14]), "+f"(d[15]), "+f"(d[16]), "+f"(d[17]), "+f"(d[18]), "+f"(d[19]), "+f"(d[20]), "+f"(d[21]), "+f"(d[22]), "+f"(d[23]), "+f"(d[24]), "+f"(d[25]), "+f"(d[26]), "+f"(d[27]), "+f"(d[28]), "+f"(d[29]), "+f"(d[30]), "+f"(d[31]), "+f"(d[32]), "+f"(d[33]), "+f"(d[34]), "+f"(d[35]), "+f"(d[36]), "+f"(d[37]), "+f"(d[38]), "+f"(d[39]), "+f"(d[40]), "+f"(d[41]), "+f"(d[42]), "+f"(d[43]), "+f"(d[44]), "+f"(d[45]), "+f"(d[46]), "+f"(d[47])
        : "r"(a[AOFF + 0][0]), "r"(a[AOFF + 0][1]), "r"(a[AOFF + 0][2]), "r"(a[AOFF + 0][3]), "r"(a[AOFF + 1][0]), "r"(a[AOFF + 1][1]), "r"(a[AOFF + 1][2]), "r"(a[AOFF + 1][3]), "r"(a[AOFF + 2][0]), "r"(a[AOFF + 2][1]), "r"(a[AOFF + 2][2]), "r"(a[AOFF + 2][3]), "r"(a[AOFF + 3][0]), "r"(a[AOFF + 3][1]), "r"(a[AOFF + 3][2]), "r"(a[AOFF + 3][3]), "r"(a[AOFF + 4][0]), "r"(a[AOFF + 4][1]), "r"(a[AOFF + 4][2]), "r"(a[AOFF + 4][3]), "r"(a[AOFF + 5][0]), "r"(a[AOFF + 5][1]), "r"(a[AOFF + 5][2]), "r"(a[AOFF + 5][3]), "r"(a[AOFF + 6][0]), "r"(a[AOFF + 6][1]), "r"(a[AOFF + 6][2]), "r"(a[AOFF + 6][3]), "r"(a[AOFF + 7][0]), "r"(a[AOFF + 7][1]), "r"(a[AOFF + 7][2]), "r"(a[AOFF + 7][3]), "l"(descB), "n"(BOFF >> 4));
}
};
template <> struct Rng<1, 4, 12> {
template <int BOFF, int AOFF, int NA>
static __device__ __forceinline__ void run(float (&d)[48], const uint32_t (&a)[NA][4], uint64_t descB) {
    asm volatile(
        "{\n"
        ".reg .pred p0, p1;\n"
        ".reg .b64 ta, ta0, tb, tb0;\n"
        "setp.ne.b32 p0, 0, 0;\n"
        "setp.eq.b32 p1, 0, 0;\n"
        "add.s64 tb0, %80, %81;\n"
        "add.s64 tb, tb0, 128;\n"
        "wgmma.mma_async.sync.aligned.m64n96k16.f32.bf16.bf16 {%0, %1, %2, %3, %4, %5, %6, %7, %8, %9, %10, %11, %12, %13, %14, %15, %16, %17, %18, %19, %20, %21, %22, %23, %24, %25, %26, %27, %28, %29, %30, %31, %32, %33, %34, %35, %36, %37, %38, %39, %40, %41, %42, %43, %44, %45, %46, %47}, {%48, %49, %50, %51}, tb, p1, 1, 1, 1;\n"
        "add.s64 tb, tb0, 160;\n"
        "wgmma.mma_async.sync.aligned.m64n96k16.f32.bf16.bf16 {%0, %1, %2, %3, %4, %5, %6, %7, %8, %9, %10, %11, %12, %13, %14, %15, %16, %17, %18, %19, %20, %21, %22, %23, %24, %25, %26, %27, %28, %29, %30, %31, %32, %33, %34, %35, %36, %37, %38, %39, %40, %41, %42, %43, %44, %45, %46, %47}, {%52, %53, %54, %55}, tb, p1, 1, 1, 1;\n"
        "add.s64 tb, tb0, 192;\n"
        "wgmma.mma_async.sync.aligned.m64n96k16.f32.bf16.bf16 {%0, %1, %2, %3, %4, %5, %6, %7, %8, %9, %10, %11, %12, %13, %14, %15, %16, %17, %18, %19, %20, %21, %22, %23, %24, %25, %26, %27, %28, %29, %30, %31, %32, %33, %34, %35, %36, %37, %38, %39, %40, %41, %42, %43, %44, %45, %46, %47}, {%56, %57, %58, %59}, tb, p1, 1, 1, 1;\n"
        "add.s64 tb, tb0, 224;\n"
        "wgmma.mma_async.sync.aligned.m64n96k16.f32.bf16.bf16 {%0, %1, %2, %3, %4, %5, %6, %7, %8, %9, %10, %11, %12, %13, %14, %15, %16, %17, %18, %19, %20, %21, %22, %23, %24, %25, %26, %27, %28, %29, %30, %31, %32, %33, %34, %35, %36, %37, %38, %39, %40, %41, %42, %43, %44, %45, %46, %47}, {%60, %61, %62, %63}, tb, p1, 1, 1, 1;\n"
        "add.s64 tb, tb0, 256;\n"
        "wgmma.mma_async.sync.aligned.m64n96k16.f32.bf16.bf16 {%0, %1, %2, %3, %4, %5, %6, %7, %8, %9, %10, %11, %12, %13, %14, %15, %16, %17, %18, %19, %20, %21, %22, %23, %24, %25, %26, %27, %28, %29, %30, %31, %32, %33, %34, %35, %36, %37, %38, %39, %40, %41, %42, %43, %44, %45, %46, %47}, {%64, %65, %66, %67}, tb, p1, 1, 1, 1;\n"
        "add.s64 tb, tb0, 288;\n"
        "wgmma.mma_async.sync.aligned.m64n96k16.f32.bf16.bf16 {%0, %1, %2, %3, %4, %5, %6, %7, %8, %9, %10, %11, %12, %13, %14, %15, %16, %17, %18, %19, %20, %21, %22, %23, %24, %25, %26, %27, %28, %29, %30, %31, %32, %33, %34, %35, %36, %37, %38, %39, %40, %41, %42, %43, %44, %45, %46, %47}, {%68, %69, %70, %71}, tb, p1, 1, 1, 1;\n"
        "add.s64 tb, tb0, 320;\n"
        "wgmma.mma_async.sync.aligned.m64n96k16.f32.bf16.bf16 {%0, %1, %2, %3, %4, %5, %6, %7, %8, %9, %10, %11, %12, %13, %14, %15, %16, %17, %18, %19, %20, %21, %22, %23, %24, %25, %26, %27, %28, %29, %30, %31, %32, %33, %34, %35, %36, %37, %38, %39, %40, %41, %42, %43, %44, %45, %46, %47}, {%72, %73, %74, %75}, tb, p1, 1, 1, 1;\n"
        "add.s64 tb, tb0, 352;\n"
        "wgmma.mma_async.sync.aligned.m64n96k16.f32.bf16.bf16 {%0, %1, %2, %3, %4, %5, %6, %7, %8, %9, %10, %11, %12, %13, %14, %15, %16, %17, %18, %19, %20, %21, %22, %23, %24, %25, %26, %27, %28, %29, %30, %31, %32, %33, %34, %35, %36, %37, %38, %39, %40, %41, %42, %43, %44, %45, %46, %47}, {%76, %77, %78, %79}, tb, p1, 1, 1, 1;\n"
        "}\n"
        : "+f"(d[0]), "+f"(d[1]), "+f"(d[2]), "+f"(d[3]), "+f"(d[4]), "+f"(d[5]), "+f"(d[6]), "+f"(d[7]), "+f"(d[8]), "+f"(d[9]), "+f"(d[10]), "+f"(d[11]), "+f"(d[12]), "+f"(d[13]), "+f"(d[14]), "+f"(d[15]), "+f"(d[16]), "+f"(d[17]), "+f"(d[18]), "+f"(d[19]), "+f"(d[20]), "+f"(d[21]), "+f"(d[22]), "+f"(d[23]), "+f"(d[24]), "+f"(d[25]), "+f"(d[26]), "+f"(d[27]), "+f"(d[28]), "+f"(d[29]), "+f"(d[30]), "+f"(d[31]), "+f"(d[32]), "+f"(d[33]), "+f"(d[34]), "+f"(d[35]), "+f"(d[36]), "+f"(d[37]), "+f"(d[38]), "+f"(d[39]), "+f"(d[40]), "+f"(d[41]), "+f"(d[42]), "+f"(d[43]), "+f"(d[44]), "+f"(d[45]), "+f"(d[46]), "+f"(d[47])
        : "r"(a[AOFF + 0][0]), "r"(a[AOFF + 0][1]), "r"(a[AOFF + 0][2]), "r"(a[AOFF + 0][3]), "r"(a[AOFF + 1][0]), "r"(a[AOFF + 1][1]), "r"(a[AOFF + 1][2]), "r"(a[AOFF + 1][3]), "r"(a[AOFF + 2][0]), "r"(a[AOFF + 2][1]), "r"(a[AOFF + 2][2]), "r"(a[AOFF + 2][3]), "r"(a[AOFF + 3][0]), "r"(a[AOFF + 3][1]), "r"(a[AOFF + 3][2]), "r"(a[AOFF + 3][3]), "r"(a[AOFF + 4][0]), "r"(a[AOFF + 4][1]), "r"(a[AOFF + 4][2]), "r"(a[AOFF + 4][3]), "r"(a[AOFF + 5][0]), "r"(a[AOFF + 5][1]), "r"(a[AOFF + 5][2]), "r"(a[AOFF + 5][3]), "r"(a[AOFF + 6][0]), "r"(a[AOFF + 6][1]), "r"(a[AOFF + 6][2]), "r"(a[AOFF + 6][3]), "r"(a[AOFF + 7][0]), "r"(a[AOFF + 7][1]), "r"(a[AOFF + 7][2]), "r"(a[AOFF + 7][3]), "l"(descB), "n"(BOFF >> 4));
}
};
template <> struct Rng<0, 5, 8> {
template <int BOFF, int AOFF, int NA>
static __device__ __forceinline__ void run(float (&d)[48], const uint32_t (&a)[NA][4], uint64_t descB) {
    asm volatile(
        "{\n"
        ".reg .pred p0, p1;\n"
        ".reg .b64 ta, ta0, tb, tb0;\n"
        "setp.ne.b32 p0, 0, 0;\n"
        "setp.eq.b32 p1, 0, 0;\n"
        "add.s64 tb0, %60, %61;\n"
        "add.s64 tb, tb0, 1568;\n"
        "wgmma.mma_async.sync.aligned.m64n96k16.f32.bf16.bf16 {%0, %1, %2, %3, %4, %5, %6, %7, %8, %9, %10, %11, %12, %13, %14, %15, %16, %17, %18, %19, %20, %21, %22, %23, %24, %25, %26, %27, %28, %29, %30, %31, %32, %33, %34, %35, %36, %37, %38, %39, %40, %41, %42, %43, %44, %45, %46, %47}, {%48, %49, %50, %51}, tb, p1, 1, 1, 1;\n"
        "add.s64 tb, tb0, 1600;\n"
        "wgmma.mma_async.sync.aligned.m64n96k16.f32.bf16.bf16 {%0, %1, %2, %3, %4, %5, %6, %7, %8, %9, %10, %11, %12, %13, %14, %15, %16, %17, %18, %19, %20, %21, %22, %23, %24, %25, %26, %27, %28, %29, %30, %31, %32, %33, %34, %35, %36, %37, %38, %39, %40, %41, %42, %43, %44, %45, %46, %47}, {%52, %53, %54, %55}, tb, p1, 1, 1, 1;\n"
        "add.s64 tb, tb0, 1632;\n"
        "wgmma.mma_async.sync.aligned.m64n96k16.f32.bf16.bf16 {%0, %1, %2, %3, %4, %5, %6, %7, %8, %9, %10, %11, %12, %13, %14, %15, %16, %17, %18, %19, %20, %21, %22, %23, %24, %25, %26, %27, %28, %29, %30, %31, %32, %33, %34, %35, %36, %37, %38, %39, %40, %41, %42, %43, %44, %45, %46, %47}, {%56, %57, %58, %59}, tb, p1, 1, 1, 1;\n"
        "}\n"
        : "+f"(d[0]), "+f"(d[1]), "+f"(d[2]), "+f"(d[3]), "+f"(d[4]), "+f"(d[5]), "+f"(d[6]), "+f"(d[7]), "+f"(d[8]), "+f"(d[9]), "+f"(d[10]), "+f"(d[11]), "+f"(d[12]), "+f"(d[13]), "+f"(d[14]), "+f"(d[15]), "+f"(d[16]), "+f"(d[17]), "+f"(d[18]), "+f"(d[19]), "+f"(d[20]), "+f"(d[21]), "+f"(d[22]), "+f"(d[23]), "+f"(d[24]), "+f"(d[25]), "+f"(d[26]), "+f"(d[27]), "+f"(d[28]), "+f"(d[29]), "+f"(d[30]), "+f"(d[31]), "+f"(d[32]), "+f"(d[33]), "+f"(d[34]), "+f"(d[35]), "+f"(d[36]), "+f"(d[37]), "+f"(d[38]), "+f"(d[39]), "+f"(d[40]), "+f"(d[41]), "+f"(d[42]), "+f"(d[43]), "+f"(d[44]), "+f"(d[45]), "+f"(d[46]), "+f"(d[47])
        : "r"(a[AOFF + 0][0]), "r"(a[AOFF + 0][1]), "r"(a[AOFF + 0][2]), "r"(a[AOFF + 0][3]), "r"(a[AOFF + 1][0]), "r"(a[AOFF + 1][1]), "r"(a[AOFF + 1][2]), "r"(a[AOFF + 1][3]), "r"(a[AOFF + 2][0]), "r"(a[AOFF + 2][1]), "r"(a[AOFF + 2][2]), "r"(a[AOFF + 2][3]), "l"(descB), "n"(BOFF >> 4));
}
};
template <> struct Rng<1, 5, 8> {
template <int BOFF, int AOFF, int NA>
static __device__ __forceinline__ void run(float (&d)[48], const uint32_t (&a)[NA][4], uint64_t descB) {
    asm volatile(
        "{\n"
        ".reg .pred p0, p1;\n"
        ".reg .b64 ta, ta0, tb, tb0;\n"
        "setp.ne.b32 p0, 0, 0;\n"
        "setp.eq.b32 p1, 0, 0;\n"
        "add.s64 tb0, %60, %61;\n"
        "add.s64 tb, tb0, 160;\n"
        "wgmma.mma_async.sync.aligned.m64n96k16.f32.bf16.bf16 {%0, %1, %2, %3, %4, %5, %6, %7, %8, %9, %10, %11, %12, %13, %14, %15, %16, %17, %18, %19, %20, %21, %22, %23, %24, %25, %26, %27, %28, %29, %30, %31, %32, %33, %34, %35, %36, %37, %38, %39, %40, %41, %42, %43, %44, %45, %46, %47}, {%48, %49, %50, %51}, tb, p1, 1, 1, 1;\n"
        "add.s64 tb, tb0, 192;\n"
        "wgmma.mma_async.sync.aligned.m64n96k16.f32.bf16.bf16 {%0, %1, %2, %3, %4, %5, %6, %7, %8, %9, %10, %11, %12, %13, %14, %15, %16, %17, %18, %19, %20, %21, %22, %23, %24, %25, %26, %27, %28, %29, %30, %31, %32, %33, %34, %35, %36, %37, %38, %39, %40, %41, %42, %43, %44, %45, %46, %47}, {%52, %53, %54, %55}, tb, p1, 1, 1, 1;\n"
        "add.s64 tb, tb0, 224;\n"
        "wgmma.mma_async.sync.aligned.m64n96k16.f32.bf16.bf16 {%0, %1, %2, %3, %4, %5, %6, %7, %8, %9, %10, %11, %12, %13, %14, %15, %16, %17, %18, %19, %20, %21, %22, %23, %24, %25, %26, %27, %28, %29, %30, %31, %32, %33, %34, %35, %36, %37, %38, %39, %40, %41, %42, %43, %44, %45, %46, %47}, {%56, %57, %58, %59}, tb, p1, 1, 1, 1;\n"
        "}\n"
        : "+f"(d[0]), "+f"(d[1]), "+f"(d[2]), "+f"(d[3]), "+f"(d[4]), "+f"(d[5]), "+f"(d[6]), "+f"(d[7]), "+f"(d[8]), "+f"(d[9]), "+f"(d[10]), "+f"(d[11]), "+f"(d[12]), "+f"(d[13]), "+f"(d[14]), "+f"(d[15]), "+f"(d[16]), "+f"(d[17]), "+f"(d[18]), "+f"(d[19]), "+f"(d[20]), "+f"(d[21]), "+f"(d[22]), "+f"(d[23]), "+f"(d[24]), "+f"(d[25]), "+f"(d[26]), "+f"(d[27]), "+f"(d[28]), "+f"(d[29]), "+f"(d[30]), "+f"(d[31]), "+f"(d[32]), "+f"(d[33]), "+f"(d[34]), "+f"(d[35]), "+f"(d[36]), "+f"(d[37]), "+f"(d[38]), "+f"(d[39]), "+f"(d[40]), "+f"(d[41]), "+f"(d[42]), "+f"(d[43]), "+f"(d[44]), "+f"(d[45]), "+f"(d[46]), "+f"(d[47])
        : "r"(a[AOFF + 0][0]), "r"(a[AOFF + 0][1]), "r"(a[AOFF + 0][2]), "r"(a[AOFF + 0][3]), "r"(a[AOFF + 1][0]), "r"(a[AOFF + 1][1]), "r"(a[AOFF + 1][2]), "r"(a[AOFF + 1][3]), "r"(a[AOFF + 2][0]), "r"(a[AOFF + 2][1]), "r"(a[AOFF + 2][2]), "r"(a[AOFF + 2][3]), "l"(descB), "n"(BOFF >> 4));
}
};
template <> struct Rng<0, 5, 9> {
template <int BOFF, int AOFF, int NA>
static __device__ __forceinline__ void run(float (&d)[48], const uint32_t (&a)[NA][4], uint64_t descB) {
    asm volatile(
        "{\n"
        ".reg .pred p0, p1;\n"
        ".reg .b64 ta, ta0, tb, tb0;\n"
        "setp.ne.b32 p0, 0, 0;\n"
        "setp.eq.b32 p1, 0, 0;\n"
        "add.s64 tb0, %64, %65;\n"
        "add.s64 tb, tb0, 1568;\n"
        "wgmma.mma_async.sync.aligned.m64n96k16.f32.bf16.bf16 {%0, %1, %2, %3, %4, %5, %6, %7, %8, %9, %10, %11, %12, %13, %14, %15, %16, %17, %18, %19, %20, %21, %22, %23, %24, %25, %26, %27, %28, %29, %30, %31, %32, %33, %34, %35, %36, %37, %38, %39, %40, %41, %42, %43, %44, %45, %46, %47}, {%48, %49, %50, %51}, tb, p1, 1, 1, 1;\n"
        "add.s64 tb, tb0, 1600;\n"
        "wgmma.mma_async.sync.aligned.m64n96k16.f32.bf16.bf16 {%0, %1, %2, %3, %4, %5, %6, %7, %8, %9, %10, %11, %12, %13, %14, %15, %16, %17, %18, %19, %20, %21, %22, %23, %24, %25, %26, %27, %28, %29, %30, %31, %32, %33, %34, %35, %36, %37, %38, %39, %40, %41, %42, %43, %44, %45, %46, %47}, {%52, %53, %54, %55}, tb, p1, 1, 1, 1;\n"
        "add.s64 tb, tb0, 1632;\n"
        "wgmma.mma_async.sync.aligned.m64n96k16.f32.bf16.bf16 {%0, %1, %2, %3, %4, %5, %6, %7, %8, %9, %10, %11, %12, %13, %14, %15, %16, %17, %18, %19, %20, %21, %22, %23, %24, %25, %26, %27, %28, %29, %30, %31, %32, %33, %34, %35, %36, %37, %38, %39, %40, %41, %42, %43, %44, %45, %46, %47}, {%56, %57, %58, %59}, tb, p1, 1, 1, 1;\n"
        "add.s64 tb, tb0, 3072;\n"
        "wgmma.mma_async.sync.aligned.m64n96k16.f32.bf16.bf16 {%0, %1, %2, %3, %4, %5, %6, %7, %8, %9, %10, %11, %12, %13, %14, %15, %16, %17, %18, %19, %20, %21, %22, %23, %24, %25, %26, %27, %28, %29, %30, %31, %32, %33, %34, %35, %36, %37, %38, %39, %40, %41, %42, %43, %44, %45, %46, %47}, {%60, %61, %62, %63}, tb, p1, 1, 1, 1;\n"
        "}\n"
        : "+f"(d[0]), "+f"(d[1]), "+f"(d[2]), "+f"(d[3]), "+f"(d[4]), "+f"(d[5]), "+f"(d[6]), "+f"(d[7]), "+f"(d[8]), "+f"(d[9]), "+f"(d[10]), "+f"(d[11]), "+f"(d[12]), "+f"(d[13]), "+f"(d[14]), "+f"(d[15]), "+f"(d[16]), "+f"(d[17]), "+f"(d[18]), "+f"(d[19]), "+f"(d[20]), "+f"(d[21]), "+f"(d[22]), "+f"(d[23]), "+f"(d[24]), "+f"(d[25]), "+f"(d[26]), "+f"(d[27]), "+f"(d[28]), "+f"(d[29]), "+f"(d[30]), "+f"(d[31]), "+f"(d[32]), "+f"(d[33]), "+f"(d[34]), "+f"(d[35]), "+f"(d[36]), "+f"(d[37]), "+f"(d[38]), "+f"(d[39]), "+f"(d[40]), "+f"(d[41]), "+f"(d[42]), "+f"(d[43]), "+f"(d[44]), "+f"(d[45]), "+f"(d[46]), "+f"(d[47])
        : "r"(a[AOFF + 0][0]), "r"(a[AOFF + 0][1]), "r"(a[AOFF + 0][2]), "r"(a[AOFF + 0][3]), "r"(a[AOFF + 1][0]), "r"(a[AOFF + 1][1]), "r"(a[AOFF + 1][2]), "r"(a[AOFF + 1][3]), "r"(a[AOFF + 2][0]), "r"(a[AOFF + 2][1]), "r"(a[AOFF + 2][2]), "r"(a[AOFF + 2][3]), "r"(a[AOFF + 3][0]), "r"(a[AOFF + 3][1]), "r"(a[AOFF + 3][2]), "r"(a[AOFF + 3][3]), "l"(descB), "n"(BOFF >> 4));
}
};
template <> struct Rng<1, 5, 9> {
template <int BOFF, int AOFF, int NA>
static __device__ __forceinline__ void run(float (&d)[48], const uint32_t (&a)[NA][4], uint64_t descB) {
    asm volatile(
        "{\n"
        ".reg .pred p0, p1;\n"
        ".reg .b64 ta, ta0, tb, tb0;\n"
        "setp.ne.b32 p0, 0, 0;\n"
        "setp.eq.b32 p1, 0, 0;\n"
        "add.s64 tb0, %64, %65;\n"
        "add.s64 tb, tb0, 160;\n"
        "wgmma.mma_async.sync.aligned.m64n96k16.f32.bf16.bf16 {%0, %1, %2, %3, %4, %5, %6, %7, %8, %9, %10, %11, %12, %13, %14, %15, %16, %17, %18, %19, %20, %21, %22, %23, %24, %25, %26, %27, %28, %29, %30, %31, %32, %33, %34, %35, %36, %37, %38, %39, %40, %41, %42, %43, %44, %45, %46, %47}, {%48, %49, %50, %51}, tb, p1, 1, 1, 1;\n"
        "add.s64 tb, tb0, 192;\n"
        "wgmma.mma_async.sync.aligned.m64n96k16.f32.bf16.bf16 {%0, %1, %2, %3, %4, %5, %6, %7, %8, %9, %10, %11, %12, %13, %14, %15, %16, %17, %18, %19, %20, %21, %22, %23, %24, %25, %26, %27, %28, %29, %30, %31, %32, %33, %34, %35, %36, %37, %38, %39, %40, %41, %42, %43, %44, %45, %46, %47}, {%52, %53, %54, %55}, tb, p1, 1, 1, 1;\n"
        "add.s64 tb, tb0, 224;\n"
        "wgmma.mma_async.sync.aligned.m64n96k16.f32.bf16.bf16 {%0, %1, %2, %3, %4, %5, %6, %7, %8, %9, %10, %11, %12, %13, %14, %15, %16, %17, %18, %19, %20, %21, %22, %23, %24, %25, %26, %27, %28, %29, %30, %31, %32, %33, %34, %35, %36, %37, %38, %39, %40, %41, %42, %43, %44, %45, %46, %47}, {%56, %57, %58, %59}, tb, p1, 1, 1, 1;\n"
        "add.s64 tb, tb0, 256;\n"
        "wgmma.mma_async.sync.aligned.m64n96k16.f32.bf16.bf16 {%0, %1, %2, %3, %4, %5, %6, %7, %8, %9, %10, %11, %12, %13, %14, %15, %16, %17, %18, %19, %20, %21, %22, %23, %24, %25, %26, %27, %28, %29, %30, %31, %32, %33, %34, %35, %36, %37, %38, %39, %40, %41, %42, %43, %44, %45, %46, %47}, {%60, %61, %62, %63}, tb, p1, 1, 1, 1;\n"
        "}\n"
        : "+f"(d[0]), "+f"(d[1]), "+f"(d[2]), "+f"(d[3]), "+f"(d[4]), "+f"(d[5]), "+f"(d[6]), "+f"(d[7]), "+f"(d[8]), "+f"(d[9]), "+f"(d[10]), "+f"(d[11]), "+f"(d[12]), "+f"(d[13]), "+f"(d[14]), "+f"(d[15]), "+f"(d[16]), "+f"(d[17]), "+f"(d[18]), "+f"(d[19]), "+f"(d[20]), "+f"(d[21]), "+f"(d[22]), "+f"(d[23]), "+f"(d[24]), "+f"(d[25]), "+f"(d[26]), "+f"(d[27]), "+f"(d[28]), "+f"(d[29]), "+f"(d[30]), "+f"(d[31]), "+f"(d[32]), "+f"(d[33]), "+f"(d[34]), "+f"(d[35]), "+f"(d[36]), "+f"(d[37]), "+f"(d[38]), "+f"(d[39]), "+f"(d[40]), "+f"(d[41]), "+f"(d[42]), "+f"(d[43]), "+f"(d[44]), "+f"(d[45]), "+f"(d[46]), "+f"(d[47])
        : "r"(a[AOFF + 0][0]), "r"(a[AOFF + 0][1]), "r"(a[AOFF + 0][2]), "r"(a[AOFF + 0][3]), "r"(a[AOFF + 1][0]), "r"(a[AOFF + 1][1]), "r"(a[AOFF + 1][2]), "r"(a[AOFF + 1][3]), "r"(a[AOFF + 2][0]), "r"(a[AOFF + 2][1]), "r"(a[AOFF + 2][2]), "r"(a[AOFF + 2][3]), "r"(a[AOFF + 3][0]), "r"(a[AOFF + 3][1]), "r"(a[AOFF + 3][2]), "r"(a[AOFF + 3][3]), "l"(descB), "n"(BOFF >> 4));
}
};
template <> struct Rng<0, 5, 10> {
template <int BOFF, int AOFF, int NA>
static __device__ __forceinline__ void run(float (&d)[48], const uint32_t (&a)[NA][4], uint64_t descB) {
    asm volatile(
        "{\n"
        ".reg .pred p0, p1;\n"
        ".reg .b64 ta, ta0, tb, tb0;\n"
        "setp.ne.b32 p0, 0, 0;\n"
        "setp.eq.b32 p1, 0, 0;\n"
        "add.s64 tb0, %68, %69;\n"
        "add.s64 tb, tb0, 1568;\n"
        "wgmma.mma_async.sync.aligned.m64n96k16.f32.bf16.bf16 {%0, %1, %2, %3, %4, %5, %6, %7, %8, %9, %10, %11, %12, %13, %14, %15, %16, %17, %18, %19, %20, %21, %22, %23, %24, %25, %26, %27, %28, %29, %30, %31, %32, %33, %34, %35, %36, %37, %38, %39, %40, %41, %42, %43, %44, %45, %46, %47}, {%48, %49, %50, %51}, tb, p1, 1, 1, 1;\n"
        "add.s64 tb, tb0, 1600;\n"
        "wgmma.mma_async.sync.aligned.m64n96k16.f32.bf16.bf16 {%0, %1, %2, %3, %4, %5, %6, %7, %8, %9, %10, %11, %12, %13, %14, %15, %16, %17, %18, %19, %20, %21, %22, %23, %24, %25, %26, %27, %28, %29, %30, %31, %32, %33, %34, %35, %36, %37, %38, %39, %40, %41, %42, %43, %44, %45, %46, %47}, {%52, %53, %54, %55}, tb, p1, 1, 1, 1;\n"
        "add.s64 tb, tb0, 1632;\n"
        "wgmma.mma_async.sync.aligned.m64n96k16.f32.bf16.bf16 {%0, %1, %2, %3, %4, %5, %6, %7, %8, %9, %10, %11, %12, %13, %14, %15, %16, %17, %18, %19, %20, %21, %22, %23, %24, %25, %26, %27, %28, %29, %30, %31, %32, %33, %34, %35, %36, %37, %38, %39, %40, %41, %42, %43, %44, %45, %46, %47}, {%56, %57, %58, %59}, tb, p1, 1, 1, 1;\n"
        "add.s64 tb, tb0, 3072;\n"
        "wgmma.mma_async.sync.aligned.m64n96k16.f32.bf16.bf16 {%0, %1, %2, %3, %4, %5, %6, %7, %8, %9, %10, %11, %12, %13, %14, %15, %16, %17, %18, %19, %20, %21, %22, %23, %24, %25, %26, %27, %28, %29, %30, %31, %32, %33, %34, %35, %36, %37, %38, %39, %40, %41, %42, %43, %44, %45, %46, %47}, {%60, %61, %62, %63}, tb, p1, 1, 1, 1;\n"
        "add.s64 tb, tb0, 3104;\n"
        "wgmma.mma_async.sync.aligned.m64n96k16.f32.bf16.bf16 {%0, %1, %2, %3, %4, %5, %6, %7, %8, %9, %10, %11, %12, %13, %14, %15, %16, %17, %18, %19, %20, %21, %22, %23, %24, %25, %26, %27, %28, %29, %30, %31, %32, %33, %34, %35, %36, %37, %38, %39, %40, %41, %42, %43, %44, %45, %46, %47}, {%64, %65, %66, %67}, tb, p1, 1, 1, 1;\n"
        "}\n"
        : "+f"(d[0]), "+f"(d[1]), "+f"(d[2]), "+f"(d[3]), "+f"(d[4]), "+f"(d[5]), "+f"(d[6]), "+f"(d[7]), "+f"(d[8]), "+f"(d[9]), "+f"(d[10]), "+f"(d[11]), "+f"(d[12]), "+f"(d[13]), "+f"(d[14]), "+f"(d[15]), "+f"(d[16]), "+f"(d[17]), "+f"(d[18]), "+f"(d[19]), "+f"(d[20]), "+f"(d[21]), "+f"(d[22]), "+f"(d[23]), "+f"(d[24]), "+f"(d[25]), "+f"(d[26]), "+f"(d[27]), "+f"(d[28]), "+f"(d[29]), "+f"(d[30]), "+f"(d[31]), "+f"(d[32]), "+f"(d[33]), "+f"(d[34]), "+f"(d[35]), "+f"(d[36]), "+f"(d[37]), "+f"(d[38]), "+f"(d[39]), "+f"(d[40]), "+f"(d[41]), "+f"(d[42]), "+f"(d[43]), "+f"(d[44]), "+f"(d[45]), "+f"(d[46]), "+f"(d[47])
        : "r"(a[AOFF + 0][0]), "r"(a[AOFF + 0][1]), "r"(a[AOFF + 0][2]), "r"(a[AOFF + 0][3]), "r"(a[AOFF + 1][0]), "r"(a[AOFF + 1][1]), "r"(a[AOFF + 1][2]), "r"(a[AOFF + 1][3]), "r"(a[AOFF + 2][0]), "r"(a[AOFF + 2][1]), "r"(a[AOFF + 2][2]), "r"(a[AOFF + 2][3]), "r"(a[AOFF + 3][0]), "r"(a[AOFF + 3][1]), "r"(a[AOFF + 3][2]), "r"(a[AOFF + 3][3]), "r"(a[AOFF + 4][0]), "r"(a[AOFF + 4][1]), "r"(a[AOFF + 4][2]), "r"(a[AOFF + 4][3]), "l"(descB), "n"(BOFF >> 4));
}
};
template <> struct Rng<1, 5, 10> {
template <int BOFF, int AOFF, int NA>
static __device__ __forceinline__ void run(float (&d)[48], const uint32_t (&a)[NA][4], uint64_t descB) {
    asm volatile(
        "{\n"
        ".reg .pred p0, p1;\n"
        ".reg .b64 ta, ta0, tb, tb0;\n"
        "setp.ne.b32 p0, 0, 0;\n"
        "setp.eq.b32 p1, 0, 0;\n"
        "add.s64 tb0, %68, %69;\n"
        "add.s64 tb, tb0, 160;\n"
        "wgmma.mma_async.sync.aligned.m64n96k16.f32.bf16.bf16 {%0, %1, %2, %3, %4, %5, %6, %7, %8, %9, %10, %11, %12, %13, %14, %15, %16, %17, %18, %19, %20, %21, %22, %23, %24, %25, %26, %27, %28, %29, %30, %31, %32, %33, %34, %35, %36, %37, %38, %39, %40, %41, %42, %43, %44, %45, %46, %47}, {%48, %49, %50, %51}, tb, p1, 1, 1, 1;\n"
        "add.s64 tb, tb0, 192;\n"
        "wgmma.mma_async.sync.aligned.m64n96k16.f32.bf16.bf16 {%0, %1, %2, %3, %4, %5, %6, %7, %8, %9, %10, %11, %12, %13, %14, %15, %16, %17, %18, %19, %20, %21, %22, %23, %24, %25, %26, %27, %28, %29, %30, %31, %32, %33, %34, %35, %36, %37, %38, %39, %40, %41, %42, %43, %44, %45, %46, %47}, {%52, %53, %54, %55}, tb, p1, 1, 1, 1;\n"
        "add.s64 tb, tb0, 224;\n"
        "wgmma.mma_async.sync.aligned.m64n96k16.f32.bf16.bf16 {%0, %1, %2, %3, %4, %5, %6, %7, %8, %9, %10, %11, %12, %13, %14, %15, %16, %17, %18, %19, %20, %21, %22, %23, %24, %25, %26, %27, %28, %29, %30, %31, %32, %33, %34, %35, %36, %37, %38, %39, %40, %41, %42, %43, %44, %45, %46, %47}, {%56, %57, %58, %59}, tb, p1, 1, 1, 1;\n"
        "add.s64 tb, tb0, 256;\n"
        "wgmma.mma_async.sync.aligned.m64n96k16.f32.bf16.bf16 {%0, %1, %2, %3, %4, %5, %6, %7, %8, %9, %10, %11, %12, %13, %14, %15, %16, %17, %18, %19, %20, %21, %22, %23, %24, %25, %26, %27, %28, %29, %30, %31, %32, %33, %34, %35, %36, %37, %38, %39, %40, %41, %42, %43, %44, %45, %46, %47}, {%60, %61, %62, %63}, tb, p1, 1, 1, 1;\n"
        "add.s64 tb, tb0, 288;\n"
        "wgmma.mma_async.sync.aligned.m64n96k16.f32.bf16.bf16 {%0, %1, %2, %3, %4, %5, %6, %7, %8, %9, %10, %11, %12, %13, %14, %15, %16, %17, %18, %19, %20, %21, %22, %23, %24, %25, %26, %27, %28, %29, %30, %31, %32, %33, %34, %35, %36, %37, %38, %39, %40, %41, %42, %43, %44, %45, %46, %47}, {%64, %65, %66, %67}, tb, p1, 1, 1, 1;\n"
        "}\n"
        : "+f"(d[0]), "+f"(d[1]), "+f"(d[2]), "+f"(d[3]), "+f"(d[4]), "+f"(d[5]), "+f"(d[6]), "+f"(d[7]), "+f"(d[8]), "+f"(d[9]), "+f"(d[10]), "+f"(d[11]), "+f"(d[12]), "+f"(d[13]), "+f"(d[14]), "+f"(d[15]), "+f"(d[16]), "+f"(d[17]), "+f"(d[18]), "+f"(d[19]), "+f"(d[20]), "+f"(d[21]), "+f"(d[22]), "+f"(d[23]), "+f"(d[24]), "+f"(d[25]), "+f"(d[26]), "+f"(d[27]), "+f"(d[28]), "+f"(d[29]), "+f"(d[30]), "+f"(d[31]), "+f"(d[32]), "+f"(d[33]), "+f"(d[34]), "+f"(d[35]), "+f"(d[36]), "+f"(d[37]), "+f"(d[38]), "+f"(d[39]), "+f"(d[40]), "+f"(d[41]), "+f"(d[42]), "+f"(d[43]), "+f"(d[44]), "+f"(d[45]), "+f"(d[46]), "+f"(d[47])
        : "r"(a[AOFF + 0][0]), "r"(a[AOFF + 0][1]), "r"(a[AOFF + 0][2]), "r"(a[AOFF + 0][3]), "r"(a[AOFF + 1][0]), "r"(a[AOFF + 1][1]), "r"(a[AOFF + 1][2]), "r"(a[AOFF + 1][3]), "r"(a[AOFF + 2][0]), "r"(a[AOFF + 2][1]), "r"(a[AOFF + 2][2]), "r"(a[AOFF + 2][3]), "r"(a[AOFF + 3][0]), "r"(a[AOFF + 3][1]), "r"(a[AOFF + 3][2]), "r"(a[AOFF + 3][3]), "r"(a[AOFF + 4][0]), "r"(a[AOFF + 4][1]), "r"(a[AOFF + 4][2]), "r"(a[AOFF + 4][3]), "l"(descB), "n"(BOFF >> 4));
}
};
template <> struct Rng<0, 5, 12> {
template <int BOFF, int AOFF, int NA>
static __device__ __forceinline__ void run(float (&d)[48], const uint32_t (&a)[NA][4], uint64_t descB) {
    asm volatile(
        "{\n"
        ".reg .pred p0, p1;\n"
        ".reg .b64 ta, ta0, tb, tb0;\n"
        "setp.ne.b32 p0, 0, 0;\n"
        "setp.eq.b32 p1, 0, 0;\n"
        "add.s64 tb0, %76, %77;\n"
        "add.s64 tb, tb0, 1568;\n"
        "wgmma.mma_async.sync.aligned.m64n96k16.f32.bf16.bf16 {%0, %1, %2, %3, %4, %5, %6, %7, %8, %9, %10, %11, %12, %13, %14, %15, %16, %17, %18, %19, %20, %21, %22, %23, %24, %25, %26, %27, %28, %29, %30, %31, %32, %33, %34, %35, %36, %37, %38, %39, %40, %41, %42, %43, %44, %45, %46, %47}, {%48, %49, %50, %51}, tb, p1, 1, 1, 1;\n"
        "add.s64 tb, tb0, 1600;\n"
        "wgmma.mma_async.sync.aligned.m64n96k16.f32.bf16.bf16 {%0, %1, %2, %3, %4, %5, %6, %7, %8, %9, %10, %11, %12, %13, %14, %15, %16, %17, %18, %19, %20, %21, %22, %23, %24, %25, %26, %27, %28, %29, %30, %31, %32, %33, %34, %35, %36, %37, %38, %39, %40, %41, %42, %43, %44, %45, %46, %47}, {%52, %53, %54, %55}, tb, p1, 1, 1, 1;\n"
        "add.s64 tb, tb0, 1632;\n"
        "wgmma.mma_async.sync.aligned.m64n96k16.f32.bf16.bf16 {%0, %1, %2, %3, %4, %5, %6, %7, %8, %9, %10, %11, %12, %13, %14, %15, %16, %17, %18, %19, %20, %21, %22, %23, %24, %25, %26, %27, %28, %29, %30, %31, %32, %33, %34, %35, %36, %37, %38, %39, %40, %41, %42, %43, %44, %45, %46, %47}, {%56, %57, %58, %59}, tb, p1, 1, 1, 1;\n"
        "add.s64 tb, tb0, 3072;\n"
        "wgmma.mma_async.sync.aligned.m64n96k16.f32.bf16.bf16 {%0, %1, %2, %3, %4, %5, %6, %7, %8, %9, %10, %11, %12, %13, %14, %15, %16, %17, %18, %19, %20, %21, %22, %23, %24, %25, %26, %27, %28, %29, %30, %31, %32, %33, %34, %35, %36, %37, %38, %39, %40, %41, %42, %43, %44, %45, %46, %47}, {%60, %61, %62, %63}, tb, p1, 1, 1, 1;\n"
        "add.s64 tb, tb0, 3104;\n"
        "wgmma.mma_async.sync.aligned.m64n96k16.f32.bf16.bf16 {%0, %1, %2, %3, %4, %5, %6, %7, %8, %9, %10, %11, %12, %13, %14, %15, %16, %17, %18, %19, %20, %21, %22, %23, %24, %25, %26, %27, %28, %29, %30, %31, %32, %33, %34, %35, %36, %37, %38, %39, %40, %41, %42, %43, %44, %45, %46, %47}, {%64, %65, %66, %67}, tb, p1, 1, 1, 1;\n"
        "add.s64 tb, tb0, 3136;\n"
        "wgmma.mma_async.sync.aligned.m64n96k16.f32.bf16.bf16 {%0, %1, %2, %3, %4, %5, %6, %7, %8, %9, %10, %11, %12, %13, %14, %15, %16, %17, %18, %19, %20, %21, %22, %23, %24, %25, %26, %27, %28, %29, %30, %31, %32, %33, %34, %35, %36, %37, %38, %39, %40, %41, %42, %43, %44, %45, %46, %47}, {%68, %69, %70, %71}, tb, p1, 1, 1, 1;\n"
        "add.s64 tb, tb0, 3168;\n"
        "wgmma.mma_async.sync.aligned.m64n96k16.f32.bf16.bf16 {%0, %1, %2, %3, %4, %5, %6, %7, %8, %9, %10, %11, %12, %13, %14, %15, %16, %17, %18, %19, %20, %21, %22, %23, %24, %25, %26, %27, %28, %29, %30, %31, %32, %33, %34, %35, %36, %37, %38, %39, %40, %41, %42, %43, %44, %45, %46, %47}, {%72, %73, %74, %75}, tb, p1, 1, 1, 1;\n"
        "}\n"
        : "+f"(d[0]), "+f"(d[1]), "+f"(d[2]), "+f"(d[3]), "+f"(d[4]), "+f"(d[5]), "+f"(d[6]), "+f"(d[7]), "+f"(d[8]), "+f"(d[9]), "+f"(d[10]), "+f"(d[11]), "+f"(d[12]), "+f"(d[13]), "+f"(d[14]), "+f"(d[15]), "+f"(d[16]), "+f"(d[17]), "+f"(d[18]), "+f"(d[19]), "+f"(d[20]), "+f"(d[21]), "+f"(d[22]), "+f"(d[23]), "+f"(d[24]), "+f"(d[25]), "+f"(d[26]), "+f"(d[27]), "+f"(d[28]), "+f"(d[29]), "+f"(d[30]), "+f"(d[31]), "+f"(d[32]), "+f"(d[33]), "+f"(d[34]), "+f"(d[35]), "+f"(d[36]), "+f"(d[37]), "+f"(d[38]), "+f"(d[39]), "+f"(d[40]), "+f"(d[41]), "+f"(d[42]), "+f"(d[43]), "+f"(d[44]), "+f"(d[45]), "+f"(d[46]), "+f"(d[47])
        : "r"(a[AOFF + 0][0]), "r"(a[AOFF + 0][1]), "r"(a[AOFF + 0][2]), "r"(a[AOFF + 0][3]), "r"(a[AOFF + 1][0]), "r"(a[AOFF + 1][1]), "r"(a[AOFF + 1][2]), "r"(a[AOFF + 1][3]), "r"(a[AOFF + 2][0]), "r"(a[AOFF + 2][1]), "r"(a[AOFF + 2][2]), "r"(a[AOFF + 2][3]), "r"(a[AOFF + 3][0]), "r"(a[AOFF + 3][1]), "r"(a[AOFF + 3][2]), "r"(a[AOFF + 3][3]), "r"(a[AOFF + 4][0]), "r"(a[AOFF + 4][1]), "r"(a[AOFF + 4][2]), "r"(a[AOFF + 4][3]), "r"(a[AOFF + 5][0]), "r"(a[AOFF + 5][1]), "r"(a[AOFF + 5][2]), "r"(a[AOFF + 5][3]), "r"(a[AOFF + 6][0]), "r"(a[AOFF + 6][1]), "r"(a[AOFF + 6][2]), "r"(a[AOFF + 6][3]), "l"(descB), "n"(BOFF >> 4));
}
};
template <> struct Rng<1, 5, 12> {
template <int BOFF, int AOFF, int NA>
static __device__ __forceinline__ void run(float (&d)[48], const uint32_t (&a)[NA][4], uint64_t descB) {
    asm volatile(
        "{\n"
        ".reg .pred p0, p1;\n"
        ".reg .b64 ta, ta0, tb, tb0;\n"
        "setp.ne.b32 p0, 0, 0;\n"
        "setp.eq.b32 p1, 0, 0;\n"
        "add.s64 tb0, %76, %77;\n"
        "add.s64 tb, tb0, 160;\n"
        "wgmma.mma_async.sync.aligned.m64n96k16.f32.bf16.bf16 {%0, %1, %2, %3, %4, %5, %6, %7, %8, %9, %10, %11, %12, %13, %14, %15, %16, %17, %18, %19, %20, %21, %22, %23, %24, %25, %26, %27, %28, %29, %30, %31, %32, %33, %34, %35, %36, %37, %38, %39, %40, %41, %42, %43, %44, %45, %46, %47}, {%48, %49, %50, %51}, tb, p1, 1, 1, 1;\n"
        "add.s64 tb, tb0, 192;\n"
        "wgmma.mma_async.sync.aligned.m64n96k16.f32.bf16.bf16 {%0, %1, %2, %3, %4, %5, %6, %7, %8, %9, %10, %11, %12, %13, %14, %15, %16, %17, %18, %19, %20, %21, %22, %23, %24, %25, %26, %27, %28, %29, %30, %31, %32, %33, %34, %35, %36, %37, %38, %39, %40, %41, %42, %43, %44, %45, %46, %47}, {%52, %53, %54, %55}, tb, p1, 1, 1, 1;\n"
        "add.s64 tb, tb0, 224;\n"
        "wgmma.mma_async.sync.aligned.m64n96k16.f32.bf16.bf16 {%0, %1, %2, %3, %4, %5, %6, %7, %8, %9, %10, %11, %12, %13, %14, %15, %16, %17, %18, %19, %20, %21, %22, %23, %24, %25, %26, %27, %28, %29, %30, %31, %32, %33, %34, %35, %36, %37, %38, %39, %40, %41, %42, %43, %44, %45, %46, %47}, {%56, %57, %58, %59}, tb, p1, 1, 1, 1;\n"
        "add.s64 tb, tb0, 256;\n"
        "wgmma.mma_async.sync.aligned.m64n96k16.f32.bf16.bf16 {%0, %1, %2, %3, %4, %5, %6, %7, %8, %9, %10, %11, %12, %13, %14, %15, %16, %17, %18, %19, %20, %21, %22, %23, %24, %25, %26, %27, %28, %29, %30, %31, %32, %33, %34, %35, %36, %37, %38, %39, %40, %41, %42, %43, %44, %45, %46, %47}, {%60, %61, %62, %63}, tb, p1, 1, 1, 1;\n"
        "add.s64 tb, tb0, 288;\n"
        "wgmma.mma_async.sync.aligned.m64n96k16.f32.bf16.bf16 {%0, %1, %2, %3, %4, %5, %6, %7, %8, %9, %10, %11, %12, %13, %14, %15, %16, %17, %18, %19, %20, %21, %22, %23, %24, %25, %26, %27, %28, %29, %30, %31, %32, %33, %34, %35, %36, %37, %38, %39, %40, %41, %42, %43, %44, %45, %46, %47}, {%64, %65, %66, %67}, tb, p1, 1, 1, 1;\n"
        "add.s64 tb, tb0, 320;\n"
        "wgmma.mma_async.sync.aligned.m64n96k16.f32.bf16.bf16 {%0, %1, %2, %3, %4, %5, %6, %7, %8, %9, %10, %11, %12, %13, %14, %15, %16, %17, %18, %19, %20, %21, %22, %23, %24, %25, %26, %27, %28, %29, %30, %31, %32, %33, %34, %35, %36, %37, %38, %39, %40, %41, %42, %43, %44, %45, %46, %47}, {%68, %69, %70, %71}, tb, p1, 1, 1, 1;\n"
        "add.s64 tb, tb0, 352;\n"
        "wgmma.mma_async.sync.aligned.m64n96k16.f32.bf16.bf16 {%0, %1, %2, %3, %4, %5, %6, %7, %8, %9, %10, %11, %12, %13, %14, %15, %16, %17, %18, %19, %20, %21, %22, %23, %24, %25, %26, %27, %28, %29, %30, %31, %32, %33, %34, %35, %36, %37, %38, %39, %40, %41, %42, %43, %44, %45, %46, %47}, {%72, %73, %74, %75}, tb, p1, 1, 1, 1;\n"
        "}\n"
        : "+f"(d[0]), "+f"(d[1]), "+f"(d[2]), "+f"(d[3]), "+f"(d[4]), "+f"(d[5]), "+f"(d[6]), "+f"(d[7]), "+f"(d[8]), "+f"(d[9]), "+f"(d[10]), "+f"(d[11]), "+f"(d[12]), "+f"(d[13]), "+f"(d[14]), "+f"(d[15]), "+f"(d[16]), "+f"(d[17]), "+f"(d[18]), "+f"(d[19]), "+f"(d[20]), "+f"(d[21]), "+f"(d[22]), "+f"(d[23]), "+f"(d[24]), "+f"(d[25]), "+f"(d[26]), "+f"(d[27]), "+f"(d[28]), "+f"(d[29]), "+f"(d[30]), "+f"(d[31]), "+f"(d[32]), "+f"(d[33]), "+f"(d[34]), "+f"(d[35]), "+f"(d[36]), "+f"(d[37]), "+f"(d[38]), "+f"(d[39]), "+f"(d[40]), "+f"(d[41]), "+f"(d[42]), "+f"(d[43]), "+f"(d[44]), "+f"(d[45]), "+f"(d[46]), "+f"(d[47])
        : "r"(a[AOFF + 0][0]), "r"(a[AOFF + 0][1]), "r"(a[AOFF + 0][2]), "r"(a[AOFF + 0][3]), "r"(a[AOFF + 1][0]), "r"(a[AOFF + 1][1]), "r"(a[AOFF + 1][2]), "r"(a[AOFF + 1][3]), "r"(a[AOFF + 2][0]), "r"(a[AOFF + 2][1]), "r"(a[AOFF + 2][2]), "r"(a[AOFF + 2][3]), "r"(a[AOFF + 3][0]), "r"(a[AOFF + 3][1]), "r"(a[AOFF + 3][2]), "r"(a[AOFF + 3][3]), "r"(a[AOFF + 4][0]), "r"(a[AOFF + 4][1]), "r"(a[AOFF + 4][2]), "r"(a[AOFF + 4][3]), "r"(a[AOFF + 5][0]), "r"(a[AOFF + 5][1]), "r"(a[AOFF + 5][2]), "r"(a[AOFF + 5][3]), "r"(a[AOFF + 6][0]), "r"(a[AOFF + 6][1]), "r"(a[AOFF + 6][2]), "r"(a[AOFF + 6][3]), "l"(descB), "n"(BOFF >> 4));
}
};
template <> struct Rng<0, 6, 9> {
template <int BOFF, int AOFF, int NA>
static __device__ __forceinline__ void run(float (&d)[48], const uint32_t (&a)[NA][4], uint64_t descB) {
    asm volatile(
        "{\n"
        ".reg .pred p0, p1;\n"
        ".reg .b64 ta, ta0, tb, tb0;\n"
        "setp.ne.b32 p0, 0, 0;\n"
        "setp.eq.b32 p1, 0, 0;\n"
        "add.s64 tb0, %60, %61;\n"
        "add.s64 tb, tb0, 1600;\n"
        "wgmma.mma_async.sync.aligned.m64n96k16.f32.bf16.bf16 {%0, %1, %2, %3, %4, %5, %6, %7, %8, %9, %10, %11, %12, %13, %14, %15, %16, %17, %18, %19, %20, %21, %22, %23, %24, %25, %26, %27, %28, %29, %30, %31, %32, %33, %34, %35, %36, %37, %38, %39, %40, %41, %42, %43, %44, %45, %46, %47}, {%48, %49, %50, %51}, tb, p1, 1, 1, 1;\n"
        "add.s64 tb, tb0, 1632;\n"
        "wgmma.mma_async.sync.aligned.m64n96k16.f32.bf16.bf16 {%0, %1, %2, %3, %4, %5, %6, %7, %8, %9, %10, %11, %12, %13, %14, %15, %16, %17, %18, %19, %20, %21, %22, %23, %24, %25, %26, %27, %28, %29, %30, %31, %32, %33, %34, %35, %36, %37, %38, %39, %40, %41, %42, %43, %44, %45, %46, %47}, {%52, %53, %54, %55}, tb, p1, 1, 1, 1;\n"
        "add.s64 tb, tb0, 3072;\n"
        "wgmma.mma_async.sync.aligned.m64n96k16.f32.bf16.bf16 {%0, %1, %2, %3, %4, %5, %6, %7, %8, %9, %10, %11, %12, %13, %14, %15, %16, %17, %18, %19, %20, %21, %22, %23, %24, %25, %26, %27, %28, %29, %30, %31, %32, %33, %34, %35, %36, %37, %38, %39, %40, %41, %42, %43, %44, %45, %46, %47}, {%56, %57, %58, %59}, tb, p1, 1, 1, 1;\n"
        "}\n"
        : "+f"(d[0]), "+f"(d[1]), "+f"(d[2]), "+f"(d[3]), "+f"(d[4]), "+f"(d[5]), "+f"(d[6]), "+f"(d[7]), "+f"(d[8]), "+f"(d[9]), "+f"(d[10]), "+f"(d[11]), "+f"(d[12]), "+f"(d[13]), "+f"(d[14]), "+f"(d[15]), "+f"(d[16]), "+f"(d[17]), "+f"(d[18]), "+f"(d[19]), "+f"(d[20]), "+f"(d[21]), "+f"(d[22]), "+f"(d[23]), "+f"(d[24]), "+f"(d[25]), "+f"(d[26]), "+f"(d[27]), "+f"(d[28]), "+f"(d[29]), "+f"(d[30]), "+f"(d[31]), "+f"(d[32]), "+f"(d[33]), "+f"(d[34]), "+f"(d[35]), "+f"(d[36]), "+f"(d[37]), "+f"(d[38]), "+f"(d[39]), "+f"(d[40]), "+f"(d[41]), "+f"(d[42]), "+f"(d[43]), "+f"(d[44]), "+f"(d[45]), "+f"(d[46]), "+f"(d[47])
        : "r"(a[AOFF + 0][0]), "r"(a[AOFF + 0][1]), "r"(a[AOFF + 0][2]), "r"(a[AOFF + 0][3]), "r"(a[AOFF + 1][0]), "r"(a[AOFF + 1][1]), "r"(a[AOFF + 1][2]), "r"(a[AOFF + 1][3]), "r"(a[AOFF + 2][0]), "r"(a[AOFF + 2][1]), "r"(a[AOFF + 2][2]), "r"(a[AOFF + 2][3]), "l"(descB), "n"(BOFF >> 4));
}
};
template <> struct Rng<1, 6, 9> {
template <int BOFF, int AOFF, int NA>
static __device__ __forceinline__ void run(float (&d)[48], const uint32_t (&a)[NA][4], uint64_t descB) {
    asm volatile(
        "{\n"
        ".reg .pred p0, p1;\n"
        ".reg .b64 ta, ta0, tb, tb0;\n"
        "setp.ne.b32 p0, 0, 0;\n"
        "setp.eq.b32 p1, 0, 0;\n"
        "add.s64 tb0, %60, %61;\n"
        "add.s64 tb, tb0, 192;\n"
        "wgmma.mma_async.sync.aligned.m64n96k16.f32.bf16.bf16 {%0, %1, %2, %3, %4, %5, %6, %7, %8, %9, %10, %11, %12, %13, %14, %15, %16, %17, %18, %19, %20, %21, %22, %23, %24, %25, %26, %27, %28, %29, %30, %31, %32, %33, %34, %35, %36, %37, %38, %39, %40, %41, %42, %43, %44, %45, %46, %47}, {%48, %49, %50, %51}, tb, p1, 1, 1, 1;\n"
        "add.s64 tb, tb0, 224;\n"
        "wgmma.mma_async.sync.aligned.m64n96k16.f32.bf16.bf16 {%0, %1, %2, %3, %4, %5, %6, %7, %8, %9, %10, %11, %12, %13, %14, %15, %16, %17, %18, %19, %20, %21, %22, %23, %24, %25, %26, %27, %28, %29, %30, %31, %32, %33, %34, %35, %36, %37, %38, %39, %40, %41, %42, %43, %44, %45, %46, %47}, {%52, %53, %54, %55}, tb, p1, 1, 1, 1;\n"
        "add.s64 tb, tb0, 256;\n"
        "wgmma.mma_async.sync.aligned.m64n96k16.f32.bf16.bf16 {%0, %1, %2, %3, %4, %5, %6, %7, %8, %9, %10, %11, %12, %13, %14, %15, %16, %17, %18, %19, %20, %21, %22, %23, %24, %25, %26, %27, %28, %29, %30, %31, %32, %33, %34, %35, %36, %37, %38, %39, %40, %41, %42, %43, %44, %45, %46, %47}, {%56, %57, %58, %59}, tb, p1, 1, 1, 1;\n"
        "}\n"
        : "+f"(d[0]), "+f"(d[1]), "+f"(d[2]), "+f"(d[3]), "+f"(d[4]), "+f"(d[5]), "+f"(d[6]), "+f"(d[7]), "+f"(d[8]), "+f"(d[9]), "+f"(d[10]), "+f"(d[11]), "+f"(d[12]), "+f"(d[13]), "+f"(d[14]), "+f"(d[15]), "+f"(d[16]), "+f"(d[17]), "+f"(d[18]), "+f"(d[19]), "+f"(d[20]), "+f"(d[21]), "+f"(d[22]), "+f"(d[23]), "+f"(d[24]), "+f"(d[25]), "+f"(d[26]), "+f"(d[27]), "+f"(d[28]), "+f"(d[29]), "+f"(d[30]), "+f"(d[31]), "+f"(d[32]), "+f"(d[33]), "+f"(d[34]), "+f"(d[35]), "+f"(d[36]), "+f"(d[37]), "+f"(d[38]), "+f"(d[39]), "+f"(d[40]), "+f"(d[41]), "+f"(d[42]), "+f"(d[43]), "+f"(d[44]), "+f"(d[45]), "+f"(d[46]), "+f"(d[47])
        : "r"(a[AOFF + 0][0]), "r"(a[AOFF + 0][1]), "r"(a[AOFF + 0][2]), "r"(a[AOFF + 0][3]), "r"(a[AOFF + 1][0]), "r"(a[AOFF + 1][1]), "r"(a[AOFF + 1][2]), "r"(a[AOFF + 1][3]), "r"(a[AOFF + 2][0]), "r"(a[AOFF + 2][1]), "r"(a[AOFF + 2][2]), "r"(a[AOFF + 2][3]), "l"(descB), "n"(BOFF >> 4));
}
};
template <> struct Rng<0, 6, 10> {
template <int BOFF, int AOFF, int NA>
static __device__ __forceinline__ void run(float (&d)[48], const uint32_t (&a)[NA][4], uint64_t descB) {
    asm volatile(
        "{\n"
        ".reg .pred p0, p1;\n"
        ".reg .b64 ta, ta0, tb, tb0;\n"
        "setp.ne.b32 p0, 0, 0;\n"
        "setp.eq.b32 p1, 0, 0;\n"
        "add.s64 tb0, %64, %65;\n"
        "add.s64 tb, tb0, 1600;\n"
        "wgmma.mma_async.sync.aligned.m64n96k16.f32.bf16.bf16 {%0, %1, %2, %3, %4, %5, %6, %7, %8, %9, %10, %11, %12, %13, %14, %15, %16, %17, %18, %19, %20, %21, %22, %23, %24, %25, %26, %27, %28, %29, %30, %31, %32, %33, %34, %35, %36, %37, %38, %39, %40, %41, %42, %43, %44, %45, %46, %47}, {%48, %49, %50, %51}, tb, p1, 1, 1, 1;\n"
        "add.s64 tb, tb0, 1632;\n"
        "wgmma.mma_async.sync.aligned.m64n96k16.f32.bf16.bf16 {%0, %1, %2, %3, %4, %5, %6, %7, %8, %9, %10, %11, %12, %13, %14, %15, %16, %17, %18, %19, %20, %21, %22, %23, %24, %25, %26, %27, %28, %29, %30, %31, %32, %33, %34, %35, %36, %37, %38, %39, %40, %41, %42, %43, %44, %45, %46, %47}, {%52, %53, %54, %55}, tb, p1, 1, 1, 1;\n"
        "add.s64 tb, tb0, 3072;\n"
        "wgmma.mma_async.sync.aligned.m64n96k16.f32.bf16.bf16 {%0, %1, %2, %3, %4, %5, %6, %7, %8, %9, %10, %11, %12, %13, %14, %15, %16, %17, %18, %19, %20, %21, %22, %23, %24, %25, %26, %27, %28, %29, %30, %31, %32, %33, %34, %35, %36, %37, %38, %39, %40, %41, %42, %43, %44, %45, %46, %47}, {%56, %57, %58, %59}, tb, p1, 1, 1, 1;\n"
        "add.s64 tb, tb0, 3104;\n"
        "wgmma.mma_async.sync.aligned.m64n96k16.f32.bf16.bf16 {%0, %1, %2, %3, %4, %5, %6, %7, %8, %9, %10, %11, %12, %13, %14, %15, %16, %17, %18, %19, %20, %21, %22, %23, %24, %25, %26, %27, %28, %29, %30, %31, %32, %33, %34, %35, %36, %37, %38, %39, %40, %41, %42, %43, %44, %45, %46, %47}, {%60, %61, %62, %63}, tb, p1, 1, 1, 1;\n"
        "}\n"
        : "+f"(d[0]), "+f"(d[1]), "+f"(d[2]), "+f"(d[3]), "+f"(d[4]), "+f"(d[5]), "+f"(d[6]), "+f"(d[7]), "+f"(d[8]), "+f"(d[9]), "+f"(d[10]), "+f"(d[11]), "+f"(d[12]), "+f"(d[13]), "+f"(d[14]), "+f"(d[15]), "+f"(d[16]), "+f"(d[17]), "+f"(d[18]), "+f"(d[19]), "+f"(d[20]), "+f"(d[21]), "+f"(d[22]), "+f"(d[23]), "+f"(d[24]), "+f"(d[25]), "+f"(d[26]), "+f"(d[27]), "+f"(d[28]), "+f"(d[29]), "+f"(d[30]), "+f"(d[31]), "+f"(d[32]), "+f"(d[33]), "+f"(d[34]), "+f"(d[35]), "+f"(d[36]), "+f"(d[37]), "+f"(d[38]), "+f"(d[39]), "+f"(d[40]), "+f"(d[41]), "+f"(d[42]), "+f"(d[43]), "+f"(d[44]), "+f"(d[45]), "+f"(d[46]), "+f"(d[47])
        : "r"(a[AOFF + 0][0]), "r"(a[AOFF + 0][1]), "r"(a[AOFF + 0][2]), "r"(a[AOFF + 0][3]), "r"(a[AOFF + 1][0]), "r"(a[AOFF + 1][1]), "r"(a[AOFF + 1][2]), "r"(a[AOFF + 1][3]), "r"(a[AOFF + 2][0]), "r"(a[AOFF + 2][1]), "r"(a[AOFF + 2][2]), "r"(a[AOFF + 2][3]), "r"(a[AOFF + 3][0]), "r"(a[AOFF + 3][1]), "r"(a[AOFF + 3][2]), "r"(a[AOFF + 3][3]), "l"(descB), "n"(BOFF >> 4));
}
};
template <> struct Rng<1, 6, 10> {
template <int BOFF, int AOFF, int NA>
static __device__ __forceinline__ void run(float (&d)[48], const uint32_t (&a)[NA][4], uint64_t descB) {
    asm volatile(
        "{\n"
        ".reg .pred p0, p1;\n"
        ".reg .b64 ta, ta0, tb, tb0;\n"
        "setp.ne.b32 p0, 0, 0;\n"
        "setp.eq.b32 p1, 0, 0;\n"
        "add.s64 tb0, %64, %65;\n"
        "add.s64 tb, tb0, 192;\n"
        "wgmma.mma_async.sync.aligned.m64n96k16.f32.bf16.bf16 {%0, %1, %2, %3, %4, %5, %6, %7, %8, %9, %10, %11, %12, %13, %14, %15, %16, %17, %18, %19, %20, %21, %22, %23, %24, %25, %26, %27, %28, %29, %30, %31, %32, %33, %34, %35, %36, %37, %38, %39, %40, %41, %42, %43, %44, %45, %46, %47}, {%48, %49, %50, %51}, tb, p1, 1, 1, 1;\n"
        "add.s64 tb, tb0, 224;\n"
        "wgmma.mma_async.sync.aligned.m64n96k16.f32.bf16.bf16 {%0, %1, %2, %3, %4, %5, %6, %7, %8, %9, %10, %11, %12, %13, %14, %15, %16, %17, %18, %19, %20, %21, %22, %23, %24, %25, %26, %27, %28, %29, %30, %31, %32, %33, %34, %35, %36, %37, %38, %39, %40, %41, %42, %43, %44, %45, %46, %47}, {%52, %53, %54, %55}, tb, p1, 1, 1, 1;\n"
        "add.s64 tb, tb0, 256;\n"
        "wgmma.mma_async.sync.aligned.m64n96k16.f32.bf16.bf16 {%0, %1, %2, %3, %4, %5, %6, %7, %8, %9, %10, %11, %12, %13, %14, %15, %16, %17, %18, %19, %20, %21, %22, %23, %24, %25, %26, %27, %28, %29, %30, %31, %32, %33, %34, %35, %36, %37, %38, %39, %40, %41, %42, %43, %44, %45, %46, %47}, {%56, %57, %58, %59}, tb, p1, 1, 1, 1;\n"
        "add.s64 tb, tb0, 288;\n"
        "wgmma.mma_async.sync.aligned.m64n96k16.f32.bf16.bf16 {%0, %1, %2, %3, %4, %5, %6, %7, %8, %9, %10, %11, %12, %13, %14, %15, %16, %17, %18, %19, %20, %21, %22, %23, %24, %25, %26, %27, %28, %29, %30, %31, %32, %33, %34, %35, %36, %37, %38, %39, %40, %41, %42, %43, %44, %45, %46, %47}, {%60, %61, %62, %63}, tb, p1, 1, 1, 1;\n"
        "}\n"
        : "+f"(d[0]), "+f"(d[1]), "+f"(d[2]), "+f"(d[3]), "+f"(d[4]), "+f"(d[5]), "+f"(d[6]), "+f"(d[7]), "+f"(d[8]), "+f"(d[9]), "+f"(d[10]), "+f"(d[11]), "+f"(d[12]), "+f"(d[13]), "+f"(d[14]), "+f"(d[15]), "+f"(d[16]), "+f"(d[17]), "+f"(d[18]), "+f"(d[19]), "+f"(d[20]), "+f"(d[21]), "+f"(d[22]), "+f"(d[23]), "+f"(d[24]), "+f"(d[25]), "+f"(d[26]), "+f"(d[27]), "+f"(d[28]), "+f"(d[29]), "+f"(d[30]), "+f"(d[31]), "+f"(d[32]), "+f"(d[33]), "+f"(d[34]), "+f"(d[35]), "+f"(d[36]), "+f"(d[37]), "+f"(d[38]), "+f"(d[39]), "+f"(d[40]), "+f"(d[41]), "+f"(d[42]), "+f"(d[43]), "+f"(d[44]), "+f"(d[45]), "+f"(d[46]), "+f"(d[47])
        : "r"(a[AOFF + 0][0]), "r"(a[AOFF + 0][1]), "r"(a[AOFF + 0][2]), "r"(a[AOFF + 0][3]), "r"(a[AOFF + 1][0]), "r"(a[AOFF + 1][1]), "r"(a[AOFF + 1][2]), "r"(a[AOFF + 1][3]), "r"(a[AOFF + 2][0]), "r"(a[AOFF + 2][1]), "r"(a[AOFF + 2][2]), "r"(a[AOFF + 2][3]), "r"(a[AOFF + 3][0]), "r"(a[AOFF + 3][1]), "r"(a[AOFF + 3][2]), "r"(a[AOFF + 3][3]), "l"(descB), "n"(BOFF >> 4));
}
};
template <> struct Rng<0, 6, 12> {
template <int BOFF, int AOFF, int NA>
static __device__ __forceinline__ void run(float (&d)[48], const uint32_t (&a)[NA][4], uint64_t descB) {
    asm volatile(
        "{\n"
        ".reg .pred p0, p1;\n"
        ".reg .b64 ta, ta0, tb, tb0;\n"
        "setp.ne.b32 p0, 0, 0;\n"
        "setp.eq.b32 p1, 0, 0;\n"
        "add.s64 tb0, %72, %73;\n"
        "add.s64 tb, tb0, 1600;\n"
        "wgmma.mma_async.sync.aligned.m64n96k16.f32.bf16.bf16 {%0, %1, %2, %3, %4, %5, %6, %7, %8, %9, %10, %11, %12, %13, %14, %15, %16, %17, %18, %19, %20, %21, %22, %23, %24, %25, %26, %27, %28, %29, %30, %31, %32, %33, %34, %35, %36, %37, %38, %39, %40, %41, %42, %43, %44, %45, %46, %47}, {%48, %49, %50, %51}, tb, p1, 1, 1, 1;\n"
        "add.s64 tb, tb0, 1632;\n"
        "wgmma.mma_async.sync.aligned.m64n96k16.f32.bf16.bf16 {%0, %1, %2, %3, %4, %5, %6, %7, %8, %9, %10, %11, %12, %13, %14, %15, %16, %17, %18, %19, %20, %21, %22, %23, %24, %25, %26, %27, %28, %29, %30, %31, %32, %33, %34, %35, %36, %37, %38, %39, %40, %41, %42, %43, %44, %45, %46, %47}, {%52, %53, %54, %55}, tb, p1, 1, 1, 1;\n"
        "add.s64 tb, tb0, 3072;\n"
        "wgmma.mma_async.sync.aligned.m64n96k16.f32.bf16.bf16 {%0, %1, %2, %3, %4, %5, %6, %7, %8, %9, %10, %11, %12, %13, %14, %15, %16, %17, %18, %19, %20, %21, %22, %23, %24, %25, %26, %27, %28, %29, %30, %31, %32, %33, %34, %35, %36, %37, %38, %39, %40, %41, %42, %43, %44, %45, %46, %47}, {%56, %57, %58, %59}, tb, p1, 1, 1, 1;\n"
        "add.s64 tb, tb0, 3104;\n"
        "wgmma.mma_async.sync.aligned.m64n96k16.f32.bf16.bf16 {%0, %1, %2, %3, %4, %5, %6, %7, %8, %9, %10, %11, %12, %13, %14, %15, %16, %17, %18, %19, %20, %21, %22, %23, %24, %25, %26, %27, %28, %29, %30, %31, %32, %33, %34, %35, %36, %37, %38, %39, %40, %41, %42, %43, %44, %45, %46, %47}, {%60, %61, %62, %63}, tb, p1, 1, 1, 1;\n"
        "add.s64 tb, tb0, 3136;\n"
        "wgmma.mma_async.sync.aligned.m64n96k16.f32.bf16.bf16 {%0, %1, %2, %3, %4, %5, %6, %7, %8, %9, %10, %11, %12, %13, %14, %15, %16, %17, %18, %19, %20, %21, %22, %23, %24, %25, %26, %27, %28, %29, %30, %31, %32, %33, %34, %35, %36, %37, %38, %39, %40, %41, %42, %43, %44, %45, %46, %47}, {%64, %65, %66, %67}, tb, p1, 1, 1, 1;\n"
        "add.s64 tb, tb0, 3168;\n"
        "wgmma.mma_async.sync.aligned.m64n96k16.f32.bf16.bf16 {%0, %1, %2, %3, %4, %5, %6, %7, %8, %9, %10, %11, %12, %13, %14, %15, %16, %17, %18, %19, %20, %21, %22, %23, %24, %25, %26, %27, %28, %29, %30, %31, %32, %33, %34, %35, %36, %37, %38, %39, %40, %41, %42, %43, %44, %45, %46, %47}, {%68, %69, %70, %71}, tb, p1, 1, 1, 1;\n"
        "}\n"
        : "+f"(d[0]), "+f"(d[1]), "+f"(d[2]), "+f"(d[3]), "+f"(d[4]), "+f"(d[5]), "+f"(d[6]), "+f"(d[7]), "+f"(d[8]), "+f"(d[9]), "+f"(d[10]), "+f"(d[11]), "+f"(d[12]), "+f"(d[13]), "+f"(d[14]), "+f"(d[15]), "+f"(d[16]), "+f"(d[17]), "+f"(d[18]), "+f"(d[19]), "+f"(d[20]), "+f"(d[21]), "+f"(d[22]), "+f"(d[23]), "+f"(d[24]), "+f"(d[25]), "+f"(d[26]), "+f"(d[27]), "+f"(d[28]), "+f"(d[29]), "+f"(d[30]), "+f"(d[31]), "+f"(d[32]), "+f"(d[33]), "+f"(d[34]), "+f"(d[35]), "+f"(d[36]), "+f"(d[37]), "+f"(d[38]), "+f"(d[39]), "+f"(d[40]), "+f"(d[41]), "+f"(d[42]), "+f"(d[43]), "+f"(d[44]), "+f"(d[45]), "+f"(d[46]), "+f"(d[47])
        : "r"(a[AOFF + 0][0]), "r"(a[AOFF + 0][1]), "r"(a[AOFF + 0][2]), "r"(a[AOFF + 0][3]), "r"(a[AOFF + 1][0]), "r"(a[AOFF + 1][1]), "r"(a[AOFF + 1][2]), "r"(a[AOFF + 1][3]), "r"(a[AOFF + 2][0]), "r"(a[AOFF + 2][1]), "r"(a[AOFF + 2][2]), "r"(a[AOFF + 2][3]), "r"(a[AOFF + 3][0]), "r"(a[AOFF + 3][1]), "r"(a[AOFF + 3][2]), "r"(a[AOFF + 3][3]), "r"(a[AOFF + 4][0]), "r"(a[AOFF + 4][1]), "r"(a[AOFF + 4][2]), "r"(a[AOFF + 4][3]), "r"(a[AOFF + 5][0]), "r"(a[AOFF + 5][1]), "r"(a[AOFF + 5][2]), "r"(a[AOFF + 5][3]), "l"(descB), "n"(BOFF >> 4));
}
};
template <> struct Rng<1, 6, 12> {
template <int BOFF, int AOFF, int NA>
static __device__ __forceinline__ void run(float (&d)[48], const uint32_t (&a)[NA][4], uint64_t descB) {
    asm volatile(
        "{\n"
        ".reg .pred p0, p1;\n"
        ".reg .b64 ta, ta0, tb, tb0;\n"
        "setp.ne.b32 p0, 0, 0;\n"
        "setp.eq.b32 p1, 0, 0;\n"
        "add.s64 tb0, %72, %73;\n"
        "add.s64 tb, tb0, 192;\n"
        "wgmma.mma_async.sync.aligned.m64n96k16.f32.bf16.bf16 {%0, %1, %2, %3, %4, %5, %6, %7, %8, %9, %10, %11, %12, %13, %14, %15, %16, %17, %18, %19, %20, %21, %22, %23, %24, %25, %26, %27, %28, %29, %30, %31, %32, %33, %34, %35, %36, %37, %38, %39, %40, %41, %42, %43, %44, %45, %46, %47}, {%48, %49, %50, %51}, tb, p1, 1, 1, 1;\n"
        "add.s64 tb, tb0, 224;\n"
        "wgmma.mma_async.sync.aligned.m64n96k16.f32.bf16.bf16 {%0, %1, %2, %3, %4, %5, %6, %7, %8, %9, %10, %11, %12, %13, %14, %15, %16, %17, %18, %19, %20, %21, %22, %23, %24, %25, %26, %27, %28, %29, %30, %31, %32, %33, %34, %35, %36, %37, %38, %39, %40, %41, %42, %43, %44, %45, %46, %47}, {%52, %53, %54, %55}, tb, p1, 1, 1, 1;\n"
        "add.s64 tb, tb0, 256;\n"
        "wgmma.mma_async.sync.aligned.m64n96k16.f32.bf16.bf16 {%0, %1, %2, %3, %4, %5, %6, %7, %8, %9, %10, %11, %12, %13, %14, %15, %16, %17, %18, %19, %20, %21, %22, %23, %24, %25, %26, %27, %28, %29, %30, %31, %32, %33, %34, %35, %36, %37, %38, %39, %40, %41, %42, %43, %44, %45, %46, %47}, {%56, %57, %58, %59}, tb, p1, 1, 1, 1;\n"
        "add.s64 tb, tb0, 288;\n"
        "wgmma.mma_async.sync.aligned.m64n96k16.f32.bf16.bf16 {%0, %1, %2, %3, %4, %5, %6, %7, %8, %9, %10, %11, %12, %13, %14, %15, %16, %17, %18, %19, %20, %21, %22, %23, %24, %25, %26, %27, %28, %29, %30, %31, %32, %33, %34, %35, %36, %37, %38, %39, %40, %41, %42, %43, %44, %45, %46, %47}, {%60, %61, %62, %63}, tb, p1, 1, 1, 1;\n"
        "add.s64 tb, tb0, 320;\n"
        "wgmma.mma_async.sync.aligned.m64n96k16.f32.bf16.bf16 {%0, %1, %2, %3, %4, %5, %6, %7, %8, %9, %10, %11, %12, %13, %14, %15, %16, %17, %18, %19, %20, %21, %22, %23, %24, %25, %26, %27, %28, %29, %30, %31, %32, %33, %34, %35, %36, %37, %38, %39, %40, %41, %42, %43, %44, %45, %46, %47}, {%64, %65, %66, %67}, tb, p1, 1, 1, 1;\n"
        "add.s64 tb, tb0, 352;\n"
        "wgmma.mma_async.sync.aligned.m64n96k16.f32.bf16.bf16 {%0, %1, %2, %3, %4, %5, %6, %7, %8, %9, %10, %11, %12, %13, %14, %15, %16, %17, %18, %19, %20, %21, %22, %23, %24, %25, %26, %27, %28, %29, %30, %31, %32, %33, %34, %35, %36, %37, %38, %39, %40, %41, %42, %43, %44, %45, %46, %47}, {%68, %69, %70, %71}, tb, p1, 1, 1, 1;\n"
        "}\n"
        : "+f"(d[0]), "+f"(d[1]), "+f"(d[2]), "+f"(d[3]), "+f"(d[4]), "+f"(d[5]), "+f"(d[6]), "+f"(d[7]), "+f"(d[8]), "+f"(d[9]), "+f"(d[10]), "+f"(d[11]), "+f"(d[12]), "+f"(d[13]), "+f"(d[14]), "+f"(d[15]), "+f"(d[16]), "+f"(d[17]), "+f"(d[18]), "+f"(d[19]), "+f"(d[20]), "+f"(d[21]), "+f"(d[22]), "+f"(d[23]), "+f"(d[24]), "+f"(d[25]), "+f"(d[26]), "+f"(d[27]), "+f"(d[28]), "+f"(d[29]), "+f"(d[30]), "+f"(d[31]), "+f"(d[32]), "+f"(d[33]), "+f"(d[34]), "+f"(d[35]), "+f"(d[36]), "+f"(d[37]), "+f"(d[38]), "+f"(d[39]), "+f"(d[40]), "+f"(d[41]), "+f"(d[42]), "+f"(d[43]), "+f"(d[44]), "+f"(d[45]), "+f"(d[46]), "+f"(d[47])
        : "r"(a[AOFF + 0][0]), "r"(a[AOFF + 0][1]), "r"(a[AOFF + 0][2]), "r"(a[AOFF + 0][3]), "r"(a[AOFF + 1][0]), "r"(a[AOFF + 1][1]), "r"(a[AOFF + 1][2]), "r"(a[AOFF + 1][3]), "r"(a[AOFF + 2][0]), "r"(a[AOFF + 2][1]), "r"(a[AOFF + 2][2]), "r"(a[AOFF + 2][3]), "r"(a[AOFF + 3][0]), "r"(a[AOFF + 3][1]), "r"(a[AOFF + 3][2]), "r"(a[AOFF + 3][3]), "r"(a[AOFF + 4][0]), "r"(a[AOFF + 4][1]), "r"(a[AOFF + 4][2]), "r"(a[AOFF + 4][3]), "r"(a[AOFF + 5][0]), "r"(a[AOFF + 5][1]), "r"(a[AOFF + 5][2]), "r"(a[AOFF + 5][3]), "l"(descB), "n"(BOFF >> 4));
}
};
template <> struct Rng<0, 7, 12> {
template <int BOFF, int AOFF, int NA>
static __device__ __forceinline__ void run(float (&d)[48], const uint32_t (&a)[NA][4], uint64_t descB) {
    asm volatile(
        "{\n"
        ".reg .pred p0, p1;\n"
        ".reg .b64 ta, ta0, tb, tb0;\n"
        "setp.ne.b32 p0, 0, 0;\n"
        "setp.eq.b32 p1, 0, 0;\n"
        "add.s64 tb0, %68, %69;\n"
        "add.s64 tb, tb0, 1632;\n"
        "wgmma.mma_async.sync.aligned.m64n96k16.f32.bf16.bf16 {%0, %1, %2, %3, %4, %5, %6, %7, %8, %9, %10, %11, %12, %13, %14, %15, %16, %17, %18, %19, %20, %21, %22, %23, %24, %25, %26, %27, %28, %29, %30, %31, %32, %33, %34, %35, %36, %37, %38, %39, %40, %41, %42, %43, %44, %45, %46, %47}, {%48, %49, %50, %51}, tb, p1, 1, 1, 1;\n"
        "add.s64 tb, tb0, 3072;\n"
        "wgmma.mma_async.sync.aligned.m64n96k16.f32.bf16.bf16 {%0, %1, %2, %3, %4, %5, %6, %7, %8, %9, %10, %11, %12, %13, %14, %15, %16, %17, %18, %19, %20, %21, %22, %23, %24, %25, %26, %27, %28, %29, %30, %31, %32, %33, %34, %35, %36, %37, %38, %39, %40, %41, %42, %43, %44, %45, %46, %47}, {%52, %53, %54, %55}, tb, p1, 1, 1, 1;\n"
        "add.s64 tb, tb0, 3104;\n"
        "wgmma.mma_async.sync.aligned.m64n96k16.f32.bf16.bf16 {%0, %1, %2, %3, %4, %5, %6, %7, %8, %9, %10, %11, %12, %13, %14, %15, %16, %17, %18, %19, %20, %21, %22, %23, %24, %25, %26, %27, %28, %29, %30, %31, %32, %33, %34, %35, %36, %37, %38, %39, %40, %41, %42, %43, %44, %45, %46, %47}, {%56, %57, %58, %59}, tb, p1, 1, 1, 1;\n"
        "add.s64 tb, tb0, 3136;\n"
        "wgmma.mma_async.sync.aligned.m64n96k16.f32.bf16.bf16 {%0, %1, %2, %3, %4, %5, %6, %7, %8, %9, %10, %11, %12, %13, %14, %15, %16, %17, %18, %19, %20, %21, %22, %23, %24, %25, %26, %27, %28, %29, %30, %31, %32, %33, %34, %35, %36, %37, %38, %39, %40, %41, %42, %43, %44, %45, %46, %47}, {%60, %61, %62, %63}, tb, p1, 1, 1, 1;\n"
        "add.s64 tb, tb0, 3168;\n"
        "wgmma.mma_async.sync.aligned.m64n96k16.f32.bf16.bf16 {%0, %1, %2, %3, %4, %5, %6, %7, %8, %9, %10, %11, %12, %13, %14, %15, %16, %17, %18, %19, %20, %21, %22, %23, %24, %25, %26, %27, %28, %29, %30, %31, %32, %33, %34, %35, %36, %37, %38, %39, %40, %41, %42, %43, %44, %45, %46, %47}, {%64, %65, %66, %67}, tb, p1, 1, 1, 1;\n"
        "}\n"
        : "+f"(d[0]), "+f"(d[1]), "+f"(d[2]), "+f"(d[3]), "+f"(d[4]), "+f"(d[5]), "+f"(d[6]), "+f"(d[7]), "+f"(d[8]), "+f"(d[9]), "+f"(d[10]), "+f"(d[11]), "+f"(d[12]), "+f"(d[13]), "+f"(d[14]), "+f"(d[15]), "+f"(d[16]), "+f"(d[17]), "+f"(d[18]), "+f"(d[19]), "+f"(d[20]), "+f"(d[21]), "+f"(d[22]), "+f"(d[23]), "+f"(d[24]), "+f"(d[25]), "+f"(d[26]), "+f"(d[27]), "+f"(d[28]), "+f"(d[29]), "+f"(d[30]), "+f"(d[31]), "+f"(d[32]), "+f"(d[33]), "+f"(d[34]), "+f"(d[35]), "+f"(d[36]), "+f"(d[37]), "+f"(d[38]), "+f"(d[39]), "+f"(d[40]), "+f"(d[41]), "+f"(d[42]), "+f"(d[43]), "+f"(d[44]), "+f"(d[45]), "+f"(d[46]), "+f"(d[47])
        : "r"(a[AOFF + 0][0]), "r"(a[AOFF + 0][1]), "r"(a[AOFF + 0][2]), "r"(a[AOFF + 0][3]), "r"(a[AOFF + 1][0]), "r"(a[AOFF + 1][1]), "r"(a[AOFF + 1][2]), "r"(a[AOFF + 1][3]), "r"(a[AOFF + 2][0]), "r"(a[AOFF + 2][1]), "r"(a[AOFF + 2][2]), "r"(a[AOFF + 2][3]), "r"(a[AOFF + 3][0]), "r"(a[AOFF + 3][1]), "r"(a[AOFF + 3][2]), "r"(a[AOFF + 3][3]), "r"(a[AOFF + 4][0]), "r"(a[AOFF + 4][1]), "r"(a[AOFF + 4][2]), "r"(a[AOFF + 4][3]), "l"(descB), "n"(BOFF >> 4));
}
};
template <> struct Rng<1, 7, 12> {
template <int BOFF, int AOFF, int NA>
static __device__ __forceinline__ void run(float (&d)[48], const uint32_t (&a)[NA][4], uint64_t descB) {
    asm volatile(
        "{\n"
        ".reg .pred p0, p1;\n"
        ".reg .b64 ta, ta0, tb, tb0;\n"
        "setp.ne.b32 p0, 0, 0;\n"
        "setp.eq.b32 p1, 0, 0;\n"
        "add.s64 tb0, %68, %69;\n"
        "add.s64 tb, tb0, 224;\n"
        "wgmma.mma_async.sync.aligned.m64n96k16.f32.bf16.bf16 {%0, %1, %2, %3, %4, %5, %6, %7, %8, %9, %10, %11, %12, %13, %14, %15, %16, %17, %18, %19, %20, %21, %22, %23, %24, %25, %26, %27, %28, %29, %30, %31, %32, %33, %34, %35, %36, %37, %38, %39, %40, %41, %42, %43, %44, %45, %46, %47}, {%48, %49, %50, %51}, tb, p1, 1, 1, 1;\n"
        "add.s64 tb, tb0, 256;\n"
        "wgmma.mma_async.sync.aligned.m64n96k16.f32.bf16.bf16 {%0, %1, %2, %3, %4, %5, %6, %7, %8, %9, %10, %11, %12, %13, %14, %15, %16, %17, %18, %19, %20, %21, %22, %23, %24, %25, %26, %27, %28, %29, %30, %31, %32, %33, %34, %35, %36, %37, %38, %39, %40, %41, %42, %43, %44, %45, %46, %47}, {%52, %53, %54, %55}, tb, p1, 1, 1, 1;\n"
        "add.s64 tb, tb0, 288;\n"
        "wgmma.mma_async.sync.aligned.m64n96k16.f32.bf16.bf16 {%0, %1, %2, %3, %4, %5, %6, %7, %8, %9, %10, %11, %12, %13, %14, %15, %16, %17, %18, %19, %20, %21, %22, %23, %24, %25, %26, %27, %28, %29, %30, %31, %32, %33, %34, %35, %36, %37, %38, %39, %40, %41, %42, %43, %44, %45, %46, %47}, {%56, %57, %58, %59}, tb, p1, 1, 1, 1;\n"
        "add.s64 tb, tb0, 320;\n"
        "wgmma.mma_async.sync.aligned.m64n96k16.f32.bf16.bf16 {%0, %1, %2, %3, %4, %5, %6, %7, %8, %9, %10, %11, %12, %13, %14, %15, %16, %17, %18, %19, %20, %21, %22, %23, %24, %25, %26, %27, %28, %29, %30, %31, %32, %33, %34, %35, %36, %37, %38, %39, %40, %41, %42, %43, %44, %45, %46, %47}, {%60, %61, %62, %63}, tb, p1, 1, 1, 1;\n"
        "add.s64 tb, tb0, 352;\n"
        "wgmma.mma_async.sync.aligned.m64n96k16.f32.bf16.bf16 {%0, %1, %2, %3, %4, %5, %6, %7, %8, %9, %10, %11, %12, %13, %14, %15, %16, %17, %18, %19, %20, %21, %22, %23, %24, %25, %26, %27, %28, %29, %30, %31, %32, %33, %34, %35, %36, %37, %38, %39, %40, %41, %42, %43, %44, %45, %46, %47}, {%64, %65, %66, %67}, tb, p1, 1, 1, 1;\n"
        "}\n"
        : "+f"(d[0]), "+f"(d[1]), "+f"(d[2]), "+f"(d[3]), "+f"(d[4]), "+f"(d[5]), "+f"(d[6]), "+f"(d[7]), "+f"(d[8]), "+f"(d[9]), "+f"(d[10]), "+f"(d[11]), "+f"(d[12]), "+f"(d[13]), "+f"(d[14]), "+f"(d[15]), "+f"(d[16]), "+f"(d[17]), "+f"(d[18]), "+f"(d[19]), "+f"(d[20]), "+f"(d[21]), "+f"(d[22]), "+f"(d[23]), "+f"(d[24]), "+f"(d[25]), "+f"(d[26]), "+f"(d[27]), "+f"(d[28]), "+f"(d[29]), "+f"(d[30]), "+f"(d[31]), "+f"(d[32]), "+f"(d[33]), "+f"(d[34]), "+f"(d[35]), "+f"(d[36]), "+f"(d[37]), "+f"(d[38]), "+f"(d[39]), "+f"(d[40]), "+f"(d[41]), "+f"(d[42]), "+f"(d[43]), "+f"(d[44]), "+f"(d[45]), "+f"(d[46]), "+f"(d[47])
        : "r"(a[AOFF + 0][0]), "r"(a[AOFF + 0][1]), "r"(a[AOFF + 0][2]), "r"(a[AOFF + 0][3]), "r"(a[AOFF + 1][0]), "r"(a[AOFF + 1][1]), "r"(a[AOFF + 1][2]), "r"(a[AOFF + 1][3]), "r"(a[AOFF + 2][0]), "r"(a[AOFF + 2][1]), "r"(a[AOFF + 2][2]), "r"(a[AOFF + 2][3]), "r"(a[AOFF + 3][0]), "r"(a[AOFF + 3][1]), "r"(a[AOFF + 3][2]), "r"(a[AOFF + 3][3]), "r"(a[AOFF + 4][0]), "r"(a[AOFF + 4][1]), "r"(a[AOFF + 4][2]), "r"(a[AOFF + 4][3]), "l"(descB), "n"(BOFF >> 4));
}
};
template <> struct Rng<0, 8, 12> {
template <int BOFF, int AOFF, int NA>
static __device__ __forceinline__ void run(float (&d)[48], const uint32_t (&a)[NA][4], uint64_t descB) {
    asm volatile(
        "{\n"
        ".reg .pred p0, p1;\n"
        ".reg .b64 ta, ta0, tb, tb0;\n"
        "setp.ne.b32 p0, 0, 0;\n"
        "setp.eq.b32 p1, 0, 0;\n"
        "add.s64 tb0, %64, %65;\n"
        "add.s64 tb, tb0, 3072;\n"
        "wgmma.mma_async.sync.aligned.m64n96k16.f32.bf16.bf16 {%0, %1, %2, %3, %4, %5, %6, %7, %8, %9, %10, %11, %12, %13, %14, %15, %16, %17, %18, %19, %20, %21, %22, %23, %24, %25, %26, %27, %28, %29, %30, %31, %32, %33, %34, %35, %36, %37, %38, %39, %40, %41, %42, %43, %44, %45, %46, %47}, {%48, %49, %50, %51}, tb, p1, 1, 1, 1;\n"
        "add.s64 tb, tb0, 3104;\n"
        "wgmma.mma_async.sync.aligned.m64n96k16.f32.bf16.bf16 {%0, %1, %2, %3, %4, %5, %6, %7, %8, %9, %10, %11, %12, %13, %14, %15, %16, %17, %18, %19, %20, %21, %22, %23, %24, %25, %26, %27, %28, %29, %30, %31, %32, %33, %34, %35, %36, %37, %38, %39, %40, %41, %42, %43, %44, %45, %46, %47}, {%52, %53, %54, %55}, tb, p1, 1, 1, 1;\n"
        "add.s64 tb, tb0, 3136;\n"
        "wgmma.mma_async.sync.aligned.m64n96k16.f32.bf16.bf16 {%0, %1, %2, %3, %4, %5, %6, %7, %8, %9, %10, %11, %12, %13, %14, %15, %16, %17, %18, %19, %20, %21, %22, %23, %24, %25, %26, %27, %28, %29, %30, %31, %32, %33, %34, %35, %36, %37, %38, %39, %40, %41, %42, %43, %44, %45, %46, %47}, {%56, %57, %58, %59}, tb, p1, 1, 1, 1;\n"
        "add.s64 tb, tb0, 3168;\n"
        "wgmma.mma_async.sync.aligned.m64n96k16.f32.bf16.bf16 {%0, %1, %2, %3, %4, %5, %6, %7, %8, %9, %10, %11, %12, %13, %14, %15, %16, %17, %18, %19, %20, %21, %22, %23, %24, %25, %26, %27, %28, %29, %30, %31, %32, %33, %34, %35, %36, %37, %38, %39, %40, %41, %42, %43, %44, %45, %46, %47}, {%60, %61, %62, %63}, tb, p1, 1, 1, 1;\n"
        "}\n"
        : "+f"(d[0]), "+f"(d[1]), "+f"(d[2]), "+f"(d[3]), "+f"(d[4]), "+f"(d[5]), "+f"(d[6]), "+f"(d[7]), "+f"(d[8]), "+f"(d[9]), "+f"(d[10]), "+f"(d[11]), "+f"(d[12]), "+f"(d[13]), "+f"(d[14]), "+f"(d[15]), "+f"(d[16]), "+f"(d[17]), "+f"(d[18]), "+f"(d[19]), "+f"(d[20]), "+f"(d[21]), "+f"(d[22]), "+f"(d[23]), "+f"(d[24]), "+f"(d[25]), "+f"(d[26]), "+f"(d[27]), "+f"(d[28]), "+f"(d[29]), "+f"(d[30]), "+f"(d[31]), "+f"(d[32]), "+f"(d[33]), "+f"(d[34]), "+f"(d[35]), "+f"(d[36]), "+f"(d[37]), "+f"(d[38]), "+f"(d[39]), "+f"(d[40]), "+f"(d[41]), "+f"(d[42]), "+f"(d[43]), "+f"(d[44]), "+f"(d[45]), "+f"(d[46]), "+f"(d[47])
        : "r"(a[AOFF + 0][0]), "r"(a[AOFF + 0][1]), "r"(a[AOFF + 0][2]), "r"(a[AOFF + 0][3]), "r"(a[AOFF + 1][0]), "r"(a[AOFF + 1][1]), "r"(a[AOFF + 1][2]), "r"(a[AOFF + 1][3]), "r"(a[AOFF + 2][0]), "r"(a[AOFF + 2][1]), "r"(a[AOFF + 2][2]), "r"(a[AOFF + 2][3]), "r"(a[AOFF + 3][0]), "r"(a[AOFF + 3][1]), "r"(a[AOFF + 3][2]), "r"(a[AOFF + 3][3]), "l"(descB), "n"(BOFF >> 4));
}
};
template <> struct Rng<1, 8, 12> {
template <int BOFF, int AOFF, int NA>
static __device__ __forceinline__ void run(float (&d)[48], const uint32_t (&a)[NA][4], uint64_t descB) {
    asm volatile(
        "{\n"
        ".reg .pred p0, p1;\n"
        ".reg .b64 ta, ta0, tb, tb0;\n"
        "setp.ne.b32 p0, 0, 0;\n"
        "setp.eq.b32 p1, 0, 0;\n"
        "add.s64 tb0, %64, %65;\n"
        "add.s64 tb, tb0, 256;\n"
        "wgmma.mma_async.sync.aligned.m64n96k16.f32.bf16.bf16 {%0, %1, %2, %3, %4, %5, %6, %7, %8, %9, %10, %11, %12, %13, %14, %15, %16, %17, %18, %19, %20, %21, %22, %23, %24, %25, %26, %27, %28, %29, %30, %31, %32, %33, %34, %35, %36, %37, %38, %39, %40, %41, %42, %43, %44, %45, %46, %47}, {%48, %49, %50, %51}, tb, p1, 1, 1, 1;\n"
        "add.s64 tb, tb0, 288;\n"
        "wgmma.mma_async.sync.aligned.m64n96k16.f32.bf16.bf16 {%0, %1, %2, %3, %4, %5, %6, %7, %8, %9, %10, %11, %12, %13, %14, %15, %16, %17, %18, %19, %20, %21, %22, %23, %24, %25, %26, %27, %28, %29, %30, %31, %32, %33, %34, %35, %36, %37, %38, %39, %40, %41, %42, %43, %44, %45, %46, %47}, {%52, %53, %54, %55}, tb, p1, 1, 1, 1;\n"
        "add.s64 tb, tb0, 320;\n"
        "wgmma.mma_async.sync.aligned.m64n96k16.f32.bf16.bf16 {%0, %1, %2, %3, %4, %5, %6, %7, %8, %9, %10, %11, %12, %13, %14, %15, %16, %17, %18, %19, %20, %21, %22, %23, %24, %25, %26, %27, %28, %29, %30, %31, %32, %33, %34, %35, %36, %37, %38, %39, %40, %41, %42, %43, %44, %45, %46, %47}, {%56, %57, %58, %59}, tb, p1, 1, 1, 1;\n"
        "add.s64 tb, tb0, 352;\n"
        "wgmma.mma_async.sync.aligned.m64n96k16.f32.bf16.bf16 {%0, %1, %2, %3, %4, %5, %6, %7, %8, %9, %10, %11, %12, %13, %14, %15, %16, %17, %18, %19, %20, %21, %22, %23, %24, %25, %26, %27, %28, %29, %30, %31, %32, %33, %34, %35, %36, %37, %38, %39, %40, %41, %42, %43, %44, %45, %46, %47}, {%60, %61, %62, %63}, tb, p1, 1, 1, 1;\n"
        "}\n"
        : "+f"(d[0]), "+f"(d[1]), "+f"(d[2]), "+f"(d[3]), "+f"(d[4]), "+f"(d[5]), "+f"(d[6]), "+f"(d[7]), "+f"(d[8]), "+f"(d[9]), "+f"(d[10]), "+f"(d[11]), "+f"(d[12]), "+f"(d[13]), "+f"(d[14]), "+f"(d[15]), "+f"(d[16]), "+f"(d[17]), "+f"(d[18]), "+f"(d[19]), "+f"(d[20]), "+f"(d[21]), "+f"(d[22]), "+f"(d[23]), "+f"(d[24]), "+f"(d[25]), "+f"(d[26]), "+f"(d[27]), "+f"(d[28]), "+f"(d[29]), "+f"(d[30]), "+f"(d[31]), "+f"(d[32]), "+f"(d[33]), "+f"(d[34]), "+f"(d[35]), "+f"(d[36]), "+f"(d[37]), "+f"(d[38]), "+f"(d[39]), "+f"(d[40]), "+f"(d[41]), "+f"(d[42]), "+f"(d[43]), "+f"(d[44]), "+f"(d[45]), "+f"(d[46]), "+f"(d[47])
        : "r"(a[AOFF + 0][0]), "r"(a[AOFF + 0][1]), "r"(a[AOFF + 0][2]), "r"(a[AOFF + 0][3]), "r"(a[AOFF + 1][0]), "r"(a[AOFF + 1][1]), "r"(a[AOFF + 1][2]), "r"(a[AOFF + 1][3]), "r"(a[AOFF + 2][0]), "r"(a[AOFF + 2][1]), "r"(a[AOFF + 2][2]), "r"(a[AOFF + 2][3]), "r"(a[AOFF + 3][0]), "r"(a[AOFF + 3][1]), "r"(a[AOFF + 3][2]), "r"(a[AOFF + 3][3]), "l"(descB), "n"(BOFF >> 4));
}
};
template <> struct Rng<0, 9, 12> {
template <int BOFF, int AOFF, int NA>
static __device__ __forceinline__ void run(float (&d)[48], const uint32_t (&a)[NA][4], uint64_t descB) {
    asm volatile(
        "{\n"
        ".reg .pred p0, p1;\n"
        ".reg .b64 ta, ta0, tb, tb0;\n"
        "setp.ne.b32 p0, 0, 0;\n"
        "setp.eq.b32 p1, 0, 0;\n"
        "add.s64 tb0, %60, %61;\n"
        "add.s64 tb, tb0, 3104;\n"
        "wgmma.mma_async.sync.aligned.m64n96k16.f32.bf16.bf16 {%0, %1, %2, %3, %4, %5, %6, %7, %8, %9, %10, %11, %12, %13, %14, %15, %16, %17, %18, %19, %20, %21, %22, %23, %24, %25, %26, %27, %28, %29, %30, %31, %32, %33, %34, %35, %36, %37, %38, %39, %40, %41, %42, %43, %44, %45, %46, %47}, {%48, %49, %50, %51}, tb, p1, 1, 1, 1;\n"
        "add.s64 tb, tb0, 3136;\n"
        "wgmma.mma_async.sync.aligned.m64n96k16.f32.bf16.bf16 {%0, %1, %2, %3, %4, %5, %6, %7, %8, %9, %10, %11, %12, %13, %14, %15, %16, %17, %18, %19, %20, %21, %22, %23, %24, %25, %26, %27, %28, %29, %30, %31, %32, %33, %34, %35, %36, %37, %38, %39, %40, %41, %42, %43, %44, %45, %46, %47}, {%52, %53, %54, %55}, tb, p1, 1, 1, 1;\n"
        "add.s64 tb, tb0, 3168;\n"
        "wgmma.mma_async.sync.aligned.m64n96k16.f32.bf16.bf16 {%0, %1, %2, %3, %4, %5, %6, %7, %8, %9, %10, %11, %12, %13, %14, %15, %16, %17, %18, %19, %20, %21, %22, %23, %24, %25, %26, %27, %28, %29, %30, %31, %32, %33, %34, %35, %36, %37, %38, %39, %40, %41, %42, %43, %44, %45, %46, %47}, {%56, %57, %58, %59}, tb, p1, 1, 1, 1;\n"
        "}\n"
        : "+f"(d[0]), "+f"(d[1]), "+f"(d[2]), "+f"(d[3]), "+f"(d[4]), "+f"(d[5]), "+f"(d[6]), "+f"(d[7]), "+f"(d[8]), "+f"(d[9]), "+f"(d[10]), "+f"(d[11]), "+f"(d[12]), "+f"(d[13]), "+f"(d[14]), "+f"(d[15]), "+f"(d[16]), "+f"(d[17]), "+f"(d[18]), "+f"(d[19]), "+f"(d[20]), "+f"(d[21]), "+f"(d[22]), "+f"(d[23]), "+f"(d[24]), "+f"(d[25]), "+f"(d[26]), "+f"(d[27]), "+f"(d[28]), "+f"(d[29]), "+f"(d[30]), "+f"(d[31]), "+f"(d[32]), "+f"(d[33]), "+f"(d[34]), "+f"(d[35]), "+f"(d[36]), "+f"(d[37]), "+f"(d[38]), "+f"(d[39]), "+f"(d[40]), "+f"(d[41]), "+f"(d[42]), "+f"(d[43]), "+f"(d[44]), "+f"(d[45]), "+f"(d[46]), "+f"(d[47])
        : "r"(a[AOFF + 0][0]), "r"(a[AOFF + 0][1]), "r"(a[AOFF + 0][2]), "r"(a[AOFF + 0][3]), "r"(a[AOFF + 1][0]), "r"(a[AOFF + 1][1]), "r"(a[AOFF + 1][2]), "r"(a[AOFF + 1][3]), "r"(a[AOFF + 2][0]), "r"(a[AOFF + 2][1]), "r"(a[AOFF + 2][2]), "r"(a[AOFF + 2][3]), "l"(descB), "n"(BOFF >> 4));
}
};
template <> struct Rng<1, 9, 12> {
template <int BOFF, int AOFF, int NA>
static __device__ __forceinline__ void run(float (&d)[48], const uint32_t (&a)[NA][4], uint64_t descB) {
    asm volatile(
        "{\n"
        ".reg .pred p0, p1;\n"
        ".reg .b64 ta, ta0, tb, tb0;\n"
        "setp.ne.b32 p0, 0, 0;\n"
        "setp.eq.b32 p1, 0, 0;\n"
        "add.s64 tb0, %60, %61;\n"
        "add.s64 tb, tb0, 288;\n"
        "wgmma.mma_async.sync.aligned.m64n96k16.f32.bf16.bf16 {%0, %1, %2, %3, %4, %5, %6, %7, %8, %9, %10, %11, %12, %13, %14, %15, %16, %17, %18, %19, %20, %21, %22, %23, %24, %25, %26, %27, %28, %29, %30, %31, %32, %33, %34, %35, %36, %37, %38, %39, %40, %41, %42, %43, %44, %45, %46, %47}, {%48, %49, %50, %51}, tb, p1, 1, 1, 1;\n"
        "add.s64 tb, tb0, 320;\n"
        "wgmma.mma_async.sync.aligned.m64n96k16.f32.bf16.bf16 {%0, %1, %2, %3, %4, %5, %6, %7, %8, %9, %10, %11, %12, %13, %14, %15, %16, %17, %18, %19, %20, %21, %22, %23, %24, %25, %26, %27, %28, %29, %30, %31, %32, %33, %34, %35, %36, %37, %38, %39, %40, %41, %42, %43, %44, %45, %46, %47}, {%52, %53, %54, %55}, tb, p1, 1, 1, 1;\n"
        "add.s64 tb, tb0, 352;\n"
        "wgmma.mma_async.sync.aligned.m64n96k16.f32.bf16.bf16 {%0, %1, %2, %3, %4, %5, %6, %7, %8, %9, %10, %11, %12, %13, %14, %15, %16, %17, %18, %19, %20, %21, %22, %23, %24, %25, %26, %27, %28, %29, %30, %31, %32, %33, %34, %35, %36, %37, %38, %39, %40, %41, %42, %43, %44, %45, %46, %47}, {%56, %57, %58, %59}, tb, p1, 1, 1, 1;\n"
        "}\n"
        : "+f"(d[0]), "+f"(d[1]), "+f"(d[2]), "+f"(d[3]), "+f"(d[4]), "+f"(d[5]), "+f"(d[6]), "+f"(d[7]), "+f"(d[8]), "+f"(d[9]), "+f"(d[10]), "+f"(d[11]), "+f"(d[12]), "+f"(d[13]), "+f"(d[14]), "+f"(d[15]), "+f"(d[16]), "+f"(d[17]), "+f"(d[18]), "+f"(d[19]), "+f"(d[20]), "+f"(d[21]), "+f"(d[22]), "+f"(d[23]), "+f"(d[24]), "+f"(d[25]), "+f"(d[26]), "+f"(d[27]), "+f"(d[28]), "+f"(d[29]), "+f"(d[30]), "+f"(d[31]), "+f"(d[32]), "+f"(d[33]), "+f"(d[34]), "+f"(d[35]), "+f"(d[36]), "+f"(d[37]), "+f"(d[38]), "+f"(d[39]), "+f"(d[40]), "+f"(d[41]), "+f"(d[42]), "+f"(d[43]), "+f"(d[44]), "+f"(d[45]), "+f"(d[46]), "+f"(d[47])
        : "r"(a[AOFF + 0][0]), "r"(a[AOFF + 0][1]), "r"(a[AOFF + 0][2]), "r"(a[AOFF + 0][3]), "r"(a[AOFF + 1][0]), "r"(a[AOFF + 1][1]), "r"(a[AOFF + 1][2]), "r"(a[AOFF + 1][3]), "r"(a[AOFF + 2][0]), "r"(a[AOFF + 2][1]), "r"(a[AOFF + 2][2]), "r"(a[AOFF + 2][3]), "l"(descB), "n"(BOFF >> 4));
}
};
template <> struct Rng<0, 10, 12> {
template <int BOFF, int AOFF, int NA>
static __device__ __forceinline__ void run(float (&d)[48], const uint32_t (&a)[NA][4], uint64_t descB) {
    asm volatile(
        "{\n"
        ".reg .pred p0, p1;\n"
        ".reg .b64 ta, ta0, tb, tb0;\n"
        "setp.ne.b32 p0, 0, 0;\n"
        "setp.eq.b32 p1, 0, 0;\n"
        "add.s64 tb0, %56, %57;\n"
        "add.s64 tb, tb0, 3136;\n"
        "wgmma.mma_async.sync.aligned.m64n96k16.f32.bf16.bf16 {%0, %1, %2, %3, %4, %5, %6, %7, %8, %9, %10, %11, %12, %13, %14, %15, %16, %17, %18, %19, %20, %21, %22, %23, %24, %25, %26, %27, %28, %29, %30, %31, %32, %33, %34, %35, %36, %37, %38, %39, %40, %41, %42, %43, %44, %45, %46, %47}, {%48, %49, %50, %51}, tb, p1, 1, 1, 1;\n"
        "add.s64 tb, tb0, 3168;\n"
        "wgmma.mma_async.sync.aligned.m64n96k16.f32.bf16.bf16 {%0, %1, %2, %3, %4, %5, %6, %7, %8, %9, %10, %11, %12, %13, %14, %15, %16, %17, %18, %19, %20, %21, %22, %23, %24, %25, %26, %27, %28, %29, %30, %31, %32, %33, %34, %35, %36, %37, %38, %39, %40, %41, %42, %43, %44, %45, %46, %47}, {%52, %53, %54, %55}, tb, p1, 1, 1, 1;\n"
        "}\n"
        : "+f"(d[0]), "+f"(d[1]), "+f"(d[2]), "+f"(d[3]), "+f"(d[4]), "+f"(d[5]), "+f"(d[6]), "+f"(d[7]), "+f"(d[8]), "+f"(d[9]), "+f"(d[10]), "+f"(d[11]), "+f"(d[12]), "+f"(d[13]), "+f"(d[14]), "+f"(d[15]), "+f"(d[16]), "+f"(d[17]), "+f"(d[18]), "+f"(d[19]), "+f"(d[20]), "+f"(d[21]), "+f"(d[22]), "+f"(d[23]), "+f"(d[24]), "+f"(d[25]), "+f"(d[26]), "+f"(d[27]), "+f"(d[28]), "+f"(d[29]), "+f"(d[30]), "+f"(d[31]), "+f"(d[32]), "+f"(d[33]), "+f"(d[34]), "+f"(d[35]), "+f"(d[36]), "+f"(d[37]), "+f"(d[38]), "+f"(d[39]), "+f"(d[40]), "+f"(d[41]), "+f"(d[42]), "+f"(d[43]), "+f"(d[44]), "+f"(d[45]), "+f"(d[46]), "+f"(d[47])
        : "r"(a[AOFF + 0][0]), "r"(a[AOFF + 0][1]), "r"(a[AOFF + 0][2]), "r"(a[AOFF + 0][3]), "r"(a[AOFF + 1][0]), "r"(a[AOFF + 1][1]), "r"(a[AOFF + 1][2]), "r"(a[AOFF + 1][3]), "l"(descB), "n"(BOFF >> 4));
}
};
template <> struct Rng<1, 10, 12> {
template <int BOFF, int AOFF, int NA>
static __device__ __forceinline__ void run(float (&d)[48], const uint32_t (&a)[NA][4], uint64_t descB) {
    asm volatile(
        "{\n"
        ".reg .pred p0, p1;\n"
        ".reg .b64 ta, ta0, tb, tb0;\n"
        "setp.ne.b32 p0, 0, 0;\n"
        "setp.eq.b32 p1, 0, 0;\n"
        "add.s64 tb0, %56, %57;\n"
        "add.s64 tb, tb0, 320;\n"
        "wgmma.mma_async.sync.aligned.m64n96k16.f32.bf16.bf16 {%0, %1, %2, %3, %4, %5, %6, %7, %8, %9, %10, %11, %12, %13, %14, %15, %16, %17, %18, %19, %20, %21, %22, %23, %24, %25, %26, %27, %28, %29, %30, %31, %32, %33, %34, %35, %36, %37, %38, %39, %40, %41, %42, %43, %44, %45, %46, %47}, {%48, %49, %50, %51}, tb, p1, 1, 1, 1;\n"
        "add.s64 tb, tb0, 352;\n"
        "wgmma.mma_async.sync.aligned.m64n96k16.f32.bf16.bf16 {%0, %1, %2, %3, %4, %5, %6, %7, %8, %9, %10, %11, %12, %13, %14, %15, %16, %17, %18, %19, %20, %21, %22, %23, %24, %25, %26, %27, %28, %29, %30, %31, %32, %33, %34, %35, %36, %37, %38, %39, %40, %41, %42, %43, %44, %45, %46, %47}, {%52, %53, %54, %55}, tb, p1, 1, 1, 1;\n"
        "}\n"
        : "+f"(d[0]), "+f"(d[1]), "+f"(d[2]), "+f"(d[3]), "+f"(d[4]), "+f"(d[5]), "+f"(d[6]), "+f"(d[7]), "+f"(d[8]), "+f"(d[9]), "+f"(d[10]), "+f"(d[11]), "+f"(d[12]), "+f"(d[13]), "+f"(d[14]), "+f"(d[15]), "+f"(d[16]), "+f"(d[17]), "+f"(d[18]), "+f"(d[19]), "+f"(d[20]), "+f"(d[21]), "+f"(d[22]), "+f"(d[23]), "+f"(d[24]), "+f"(d[25]), "+f"(d[26]), "+f"(d[27]), "+f"(d[28]), "+f"(d[29]), "+f"(d[30]), "+f"(d[31]), "+f"(d[32]), "+f"(d[33]), "+f"(d[34]), "+f"(d[35]), "+f"(d[36]), "+f"(d[37]), "+f"(d[38]), "+f"(d[39]), "+f"(d[40]), "+f"(d[41]), "+f"(d[42]), "+f"(d[43]), "+f"(d[44]), "+f"(d[45]), "+f"(d[46]), "+f"(d[47])
        : "r"(a[AOFF + 0][0]), "r"(a[AOFF + 0][1]), "r"(a[AOFF + 0][2]), "r"(a[AOFF + 0][3]), "r"(a[AOFF + 1][0]), "r"(a[AOFF + 1][1]), "r"(a[AOFF + 1][2]), "r"(a[AOFF + 1][3]), "l"(descB), "n"(BOFF >> 4));
}
};
template <int V, int BOFF, int S0, int S1>
__device__ __forceinline__ void mma_rng(float (&d)[48], const uint32_t (&a)[12][4], uint64_t descB) {
    if constexpr (S0 < S1) Rng<V, S0, S1>::template run<BOFF, S0, 12>(d, a, descB);
}

template <int AOFF, int BOFF>
__device__ __forceinline__ void mma_qk0(float (&d)[28], uint64_t descA, uint64_t descB) {
    asm volatile(
        "{\n"
        ".reg .pred p0, p1;\n"
        ".reg .b64 ta, ta0, tb, tb0;\n"
        "setp.ne.b32 p0, 0, 0;\n"
        "setp.eq.b32 p1, 0, 0;\n"
        "add.s64 tb0, %30, %31;\n"
        "add.s64 ta0, %28, %29;\n"
        "add.s64 tb, tb0, 4;\n"
        "add.s64 ta, ta0, 0;\n"
        "wgmma.mma_async.sync.aligned.m64n56k16.f32.bf16.bf16 {%0, %1, %2, %3, %4, %5, %6, %7, %8, %9, %10, %11, %12, %13, %14, %15, %16, %17, %18, %19, %20, %21, %22, %23, %24, %25, %26, %27}, ta, tb, p0, 1, 1, 0, 0;\n"
        "add.s64 tb, tb0, 1572;\n"
        "add.s64 ta, ta0, 1568;\n"
        "wgmma.mma_async.sync.aligned.m64n56k16.f32.bf16.bf16 {%0, %1, %2, %3, %4, %5, %6, %7, %8, %9, %10, %11, %12, %13, %14, %15, %16, %17, %18, %19, %20, %21, %22, %23, %24, %25, %26, %27}, ta, tb, p1, 1, 1, 0, 0;\n"
        "add.s64 tb, tb0, 3140;\n"
        "add.s64 ta, ta0, 3136;\n"
        "wgmma.mma_async.sync.aligned.m64n56k16.f32.bf16.bf16 {%0, %1, %2, %3, %4, %5, %6, %7, %8, %9, %10, %11, %12, %13, %14, %15, %16, %17, %18, %19, %20, %21, %22, %23, %24, %25, %26, %27}, ta, tb, p1, 1, 1, 0, 0;\n"
        "}\n"
        : "=f"(d[0]), "=f"(d[1]), "=f"(d[2]), "=f"(d[3]), "=f"(d[4]), "=f"(d[5]), "=f"(d[6]), "=f"(d[7]), "=f"(d[8]), "=f"(d[9]), "=f"(d[10]), "=f"(d[11]), "=f"(d[12]), "=f"(d[13]), "=f"(d[14]), "=f"(d[15]), "=f"(d[16]), "=f"(d[17]), "=f"(d[18]), "=f"(d[19]), "=f"(d[20]), "=f"(d[21]), "=f"(d[22]), "=f"(d[23]), "=f"(d[24]), "=f"(d[25]), "=f"(d[26]), "=f"(d[27])
        : "l"(descA), "n"(AOFF >> 4), "l"(descB), "n"(BOFF >> 4));
}

template <int AOFF, int BOFF>
__device__ __forceinline__ void mma_qk1(float (&d)[28], uint64_t descA, uint64_t descB) {
    asm volatile(
        "{\n"
        ".reg .pred p0, p1;\n"
        ".reg .b64 ta, ta0, tb, tb0;\n"
        "setp.ne.b32 p0, 0, 0;\n"
        "setp.eq.b32 p1, 0, 0;\n"
        "add.s64 tb0, %30, %31;\n"
        "add.s64 ta0, %28, %29;\n"
        "add.s64 tb, tb0, 6;\n"
        "add.s64 ta, ta0, 2;\n"
        "wgmma.mma_async.sync.aligned.m64n56k16.f32.bf16.bf16 {%0, %1, %2, %3, %4, %5, %6, %7, %8, %9, %10, %11, %12, %13, %14, %15, %16, %17, %18, %19, %20, %21, %22, %23, %24, %25, %26, %27}, ta, tb, p0, 1, 1, 0, 0;\n"
        "add.s64 tb, tb0, 1574;\n"
        "add.s64 ta, ta0, 1570;\n"
        "wgmma.mma_async.sync.aligned.m64n56k16.f32.bf16.bf16 {%0, %1, %2, %3, %4, %5, %6, %7, %8, %9, %10, %11, %12, %13, %14, %15, %16, %17, %18, %19, %20, %21, %22, %23, %24, %25, %26, %27}, ta, tb, p1, 1, 1, 0, 0;\n"
        "add.s64 tb, tb0, 3142;\n"
        "add.s64 ta, ta0, 3138;\n"
        "wgmma.mma_async.sync.aligned.m64n56k16.f32.bf16.bf16 {%0, %1, %2, %3, %4, %5, %6, %7, %8, %9, %10, %11, %12, %13, %14, %15, %16, %17, %18, %19, %20, %21, %22, %23, %24, %25, %26, %27}, ta, tb, p1, 1, 1, 0, 0;\n"
        "}\n"
        : "=f"(d[0]), "=f"(d[1]), "=f"(d[2]), "=f"(d[3]), "=f"(d[4]), "=f"(d[5]), "=f"(d[6]), "=f"(d[7]), "=f"(d[8]), "=f"(d[9]), "=f"(d[10]), "=f"(d[11]), "=f"(d[12]), "=f"(d[13]), "=f"(d[14]), "=f"(d[15]), "=f"(d[16]), "=f"(d[17]), "=f"(d[18]), "=f"(d[19]), "=f"(d[20]), "=f"(d[21]), "=f"(d[22]), "=f"(d[23]), "=f"(d[24]), "=f"(d[25]), "=f"(d[26]), "=f"(d[27])
        : "l"(descA), "n"(AOFF >> 4), "l"(descB), "n"(BOFF >> 4));
}

template <int BOFF, int AOFF, int NA>
__device__ __forceinline__ void mma_pv(float (&d)[28], const uint32_t (&a)[NA][4], uint64_t descB) {
    asm volatile(
        "{\n"
        ".reg .pred p0, p1;\n"
        ".reg .b64 ta, ta0, tb, tb0;\n"
        "setp.ne.b32 p0, 0, 0;\n"
        "setp.eq.b32 p1, 0, 0;\n"
        "add.s64 tb0, %44, %45;\n"
        "add.s64 tb, tb0, 0;\n"
        "wgmma.mma_async.sync.aligned.m64n56k16.f32.bf16.bf16 {%0, %1, %2, %3, %4, %5, %6, %7, %8, %9, %10, %11, %12, %13, %14, %15, %16, %17, %18, %19, %20, %21, %22, %23, %24, %25, %26, %27}, {%28, %29, %30, %31}, tb, p0, 1, 1, 1;\n"
        "add.s64 tb, tb0, 16;\n"
        "wgmma.mma_async.sync.aligned.m64n56k16.f32.bf16.bf16 {%0, %1, %2, %3, %4, %5, %6, %7, %8, %9, %10, %11, %12, %13, %14, %15, %16, %17, %18, %19, %20, %21, %22, %23, %24, %25, %26, %27}, {%32, %33, %34, %35}, tb, p1, 1, 1, 1;\n"
        "add.s64 tb, tb0, 32;\n"
        "wgmma.mma_async.sync.aligned.m64n56k16.f32.bf16.bf16 {%0, %1, %2, %3, %4, %5, %6, %7, %8, %9, %10, %11, %12, %13, %14, %15, %16, %17, %18, %19, %20, %21, %22, %23, %24, %25, %26, %27}, {%36, %37, %38, %39}, tb, p1, 1, 1, 1;\n"
        "add.s64 tb, tb0, 48;\n"
        "wgmma.mma_async.sync.aligned.m64n56k16.f32.bf16.bf16 {%0, %1, %2, %3, %4, %5, %6, %7, %8, %9, %10, %11, %12, %13, %14, %15, %16, %17, %18, %19, %20, %21, %22, %23, %24, %25, %26, %27}, {%40, %41, %42, %43}, tb, p1, 1, 1, 1;\n"
        "}\n"
        : "=f"(d[0]), "=f"(d[1]), "=f"(d[2]), "=f"(d[3]), "=f"(d[4]), "=f"(d[5]), "=f"(d[6]), "=f"(d[7]), "=f"(d[8]), "=f"(d[9]), "=f"(d[10]), "=f"(d[11]), "=f"(d[12]), "=f"(d[13]), "=f"(d[14]), "=f"(d[15]), "=f"(d[16]), "=f"(d[17]), "=f"(d[18]), "=f"(d[19]), "=f"(d[20]), "=f"(d[21]), "=f"(d[22]), "=f"(d[23]), "=f"(d[24]), "=f"(d[25]), "=f"(d[26]), "=f"(d[27])
        : "r"(a[AOFF + 0][0]), "r"(a[AOFF + 0][1]), "r"(a[AOFF + 0][2]), "r"(a[AOFF + 0][3]), "r"(a[AOFF + 1][0]), "r"(a[AOFF + 1][1]), "r"(a[AOFF + 1][2]), "r"(a[AOFF + 1][3]), "r"(a[AOFF + 2][0]), "r"(a[AOFF + 2][1]), "r"(a[AOFF + 2][2]), "r"(a[AOFF + 2][3]), "r"(a[AOFF + 3][0]), "r"(a[AOFF + 3][1]), "r"(a[AOFF + 3][2]), "r"(a[AOFF + 3][3]), "l"(descB), "n"(BOFF >> 4));
}

template <int AOFF, int BOFF>
__device__ __forceinline__ void mma_proj(float (&d)[96], uint64_t descA, uint64_t descB) {
    asm volatile(
        "{\n"
        ".reg .pred p0, p1;\n"
        ".reg .b64 ta, ta0, tb, tb0;\n"
        "setp.ne.b32 p0, 0, 0;\n"
        "setp.eq.b32 p1, 0, 0;\n"
        "add.s64 tb0, %98, %99;\n"
        "add.s64 ta0, %96, %97;\n"
        "add.s64 tb, tb0, 0;\n"
        "add.s64 ta, ta0, 0;\n"
        "wgmma.mma_async.sync.aligned.m64n192k16.f32.bf16.bf16 {%0, %1, %2, %3, %4, %5, %6, %7, %8, %9, %10, %11, %12, %13, %14, %15, %16, %17, %18, %19, %20, %21, %22, %23, %24, %25, %26, %27, %28, %29, %30, %31, %32, %33, %34, %35, %36, %37, %38, %39, %40, %41, %42, %43, %44, %45, %46, %47, %48, %49, %50, %51, %52, %53, %54, %55, %56, %57, %58, %59, %60, %61, %62, %63, %64, %65, %66, %67, %68, %69, %70, %71, %72, %73, %74, %75, %76, %77, %78, %79, %80, %81, %82, %83, %84, %85, %86, %87, %88, %89, %90, %91, %92, %93, %94, %95}, ta, tb, p0, 1, 1, 0, 1;\n"
        "add.s64 tb, tb0, 64;\n"
        "add.s64 ta, ta0, 2;\n"
        "wgmma.mma_async.sync.aligned.m64n192k16.f32.bf16.bf16 {%0, %1, %2, %3, %4, %5, %6, %7, %8, %9, %10, %11, %12, %13, %14, %15, %16, %17, %18, %19, %20, %21, %22, %23, %24, %25, %26, %27, %28, %29, %30, %31, %32, %33, %34, %35, %36, %37, %38, %39, %40, %41, %42, %43, %44, %45, %46, %47, %48, %49, %50, %51, %52, %53, %54, %55, %56, %57, %58, %59, %60, %61, %62, %63, %64, %65, %66, %67, %68, %69, %70, %71, %72, %73, %74, %75, %76, %77, %78, %79, %80, %81, %82, %83, %84, %85, %86, %87, %88, %89, %90, %91, %92, %93, %94, %95}, ta, tb, p1, 1, 1, 0, 1;\n"
        "add.s64 tb, tb0, 128;\n"
        "add.s64 ta, ta0, 4;\n"
        "wgmma.mma_async.sync.aligned.m64n192k16.f32.bf16.bf16 {%0, %1, %2, %3, %4, %5, %6, %7, %8, %9, %10, %11, %12, %13, %14, %15, %16, %17, %18, %19, %20, %21, %22, %23, %24, %25, %26, %27, %28, %29, %30, %31, %32, %33, %34, %35, %36, %37, %38, %39, %40, %41, %42, %43, %44, %45, %46, %47, %48, %49, %50, %51, %52, %53, %54, %55, %56, %57, %58, %59, %60, %61, %62, %63, %64, %65, %66, %67, %68, %69, %70, %71, %72, %73, %74, %75, %76, %77, %78, %79, %80, %81, %82, %83, %84, %85, %86, %87, %88, %89, %90, %91, %92, %93, %94, %95}, ta, tb, p1, 1, 1, 0, 1;\n"
        "add.s64 tb, tb0, 192;\n"
        "add.s64 ta, ta0, 6;\n"
        "wgmma.mma_async.sync.aligned.m64n192k16.f32.bf16.bf16 {%0, %1, %2, %3, %4, %5, %6, %7, %8, %9, %10, %11, %12, %13, %14, %15, %16, %17, %18, %19, %20, %21, %22, %23, %24, %25, %26, %27, %28, %29, %30, %31, %32, %33, %34, %35, %36, %37, %38, %39, %40, %41, %42, %43, %44, %45, %46, %47, %48, %49, %50, %51, %52, %53, %54, %55, %56, %57, %58, %59, %60, %61, %62, %63, %64, %65, %66, %67, %68, %69, %70, %71, %72, %73, %74, %75, %76, %77, %78, %79, %80, %81, %82, %83, %84, %85, %86, %87, %88, %89, %90, %91, %92, %93, %94, %95}, ta, tb, p1, 1, 1, 0, 1;\n"
        "add.s64 tb, tb0, 256;\n"
        "add.s64 ta, ta0, 512;\n"
        "wgmma.mma_async.sync.aligned.m64n192k16.f32.bf16.bf16 {%0, %1, %2, %3, %4, %5, %6, %7, %8, %9, %10, %11, %12, %13, %14, %15, %16, %17, %18, %19, %20, %21, %22, %23, %24, %25, %26, %27, %28, %29, %30, %31, %32, %33, %34, %35, %36, %37, %38, %39, %40, %41, %42, %43, %44, %45, %46, %47, %48, %49, %50, %51, %52, %53, %54, %55, %56, %57, %58, %59, %60, %61, %62, %63, %64, %65, %66, %67, %68, %69, %70, %71, %72, %73, %74, %75, %76, %77, %78, %79, %80, %81, %82, %83, %84, %85, %86, %87, %88, %89, %90, %91, %92, %93, %94, %95}, ta, tb, p1, 1, 1, 0, 1;\n"
        "add.s64 tb, tb0, 320;\n"
        "add.s64 ta, ta0, 514;\n"
        "wgmma.mma_async.sync.aligned.m64n192k16.f32.bf16.bf16 {%0, %1, %2, %3, %4, %5, %6, %7, %8, %9, %10, %11, %12, %13, %14, %15, %16, %17, %18, %19, %20, %21, %22, %23, %24, %25, %26, %27, %28, %29, %30, %31, %32, %33, %34, %35, %36, %37, %38, %39, %40, %41, %42, %43, %44, %45, %46, %47, %48, %49, %50, %51, %52, %53, %54, %55, %56, %57, %58, %59, %60, %61, %62, %63, %64, %65, %66, %67, %68, %69, %70, %71, %72, %73, %74, %75, %76, %77, %78, %79, %80, %81, %82, %83, %84, %85, %86, %87, %88, %89, %90, %91, %92, %93, %94, %95}, ta, tb, p1, 1, 1, 0, 1;\n"
        "add.s64 tb, tb0, 384;\n"
        "add.s64 ta, ta0, 516;\n"
        "wgmma.mma_async.sync.aligned.m64n192k16.f32.bf16.bf16 {%0, %1, %2, %3, %4, %5, %6, %7, %8, %9, %10, %11, %12, %13, %14, %15, %16, %17, %18, %19, %20, %21, %22, %23, %24, %25, %26, %27, %28, %29, %30, %31, %32, %33, %34, %35, %36, %37, %38, %39, %40, %41, %42, %43, %44, %45, %46, %47, %48, %49, %50, %51, %52, %53, %54, %55, %56, %57, %58, %59, %60, %61, %62, %63, %64, %65, %66, %67, %68, %69, %70, %71, %72, %73, %74, %75, %76, %77, %78, %79, %80, %81, %82, %83, %84, %85, %86, %87, %88, %89, %90, %91, %92, %93, %94, %95}, ta, tb, p1, 1, 1, 0, 1;\n"
        "add.s64 tb, tb0, 448;\n"
        "add.s64 ta, ta0, 518;\n"
        "wgmma.mma_async.sync.aligned.m64n192k16.f32.bf16.bf16 {%0, %1, %2, %3, %4, %5, %6, %7, %8, %9, %10, %11, %12, %13, %14, %15, %16, %17, %18, %19, %20, %21, %22, %23, %24, %25, %26, %27, %28, %29, %30, %31, %32, %33, %34, %35, %36, %37, %38, %39, %40, %41, %42, %43, %44, %45, %46, %47, %48, %49, %50, %51, %52, %53, %54, %55, %56, %57, %58, %59, %60, %61, %62, %63, %64, %65, %66, %67, %68, %69, %70, %71, %72, %73, %74, %75, %76, %77, %78, %79, %80, %81, %82, %83, %84, %85, %86, %87, %88, %89, %90, %91, %92, %93, %94, %95}, ta, tb, p1, 1, 1, 0, 1;\n"
        "add.s64 tb, tb0, 512;\n"
        "add.s64 ta, ta0, 1024;\n"
        "wgmma.mma_async.sync.aligned.m64n192k16.f32.bf16.bf16 {%0, %1, %2, %3, %4, %5, %6, %7, %8, %9, %10, %11, %12, %13, %14, %15, %16, %17, %18, %19, %20, %21, %22, %23, %24, %25, %26, %27, %28, %29, %30, %31, %32, %33, %34, %35, %36, %37, %38, %39, %40, %41, %42, %43, %44, %45, %46, %47, %48, %49, %50, %51, %52, %53, %54, %55, %56, %57, %58, %59, %60, %61, %62, %63, %64, %65, %66, %67, %68, %69, %70, %71, %72, %73, %74, %75, %76, %77, %78, %79, %80, %81, %82, %83, %84, %85, %86, %87, %88, %89, %90, %91, %92, %93, %94, %95}, ta, tb, p1, 1, 1, 0, 1;\n"
        "add.s64 tb, tb0, 576;\n"
        "add.s64 ta, ta0, 1026;\n"
        "wgmma.mma_async.sync.aligned.m64n192k16.f32.bf16.bf16 {%0, %1, %2, %3, %4, %5, %6, %7, %8, %9, %10, %11, %12, %13, %14, %15, %16, %17, %18, %19, %20, %21, %22, %23, %24, %25, %26, %27, %28, %29, %30, %31, %32, %33, %34, %35, %36, %37, %38, %39, %40, %41, %42, %43, %44, %45, %46, %47, %48, %49, %50, %51, %52, %53, %54, %55, %56, %57, %58, %59, %60, %61, %62, %63, %64, %65, %66, %67, %68, %69, %70, %71, %72, %73, %74, %75, %76, %77, %78, %79, %80, %81, %82, %83, %84, %85, %86, %87, %88, %89, %90, %91, %92, %93, %94, %95}, ta, tb, p1, 1, 1, 0, 1;\n"
        "add.s64 tb, tb0, 640;\n"
        "add.s64 ta, ta0, 1028;\n"
        "wgmma.mma_async.sync.aligned.m64n192k16.f32.bf16.bf16 {%0, %1, %2, %3, %4, %5, %6, %7, %8, %9, %10, %11, %12, %13, %14, %15, %16, %17, %18, %19, %20, %21, %22, %23, %24, %25, %26, %27, %28, %29, %30, %31, %32, %33, %34, %35, %36, %37, %38, %39, %40, %41, %42, %43, %44, %45, %46, %47, %48, %49, %50, %51, %52, %53, %54, %55, %56, %57, %58, %59, %60, %61, %62, %63, %64, %65, %66, %67, %68, %69, %70, %71, %72, %73, %74, %75, %76, %77, %78, %79, %80, %81, %82, %83, %84, %85, %86, %87, %88, %89, %90, %91, %92, %93, %94, %95}, ta, tb, p1, 1, 1, 0, 1;\n"
        "add.s64 tb, tb0, 704;\n"
        "add.s64 ta, ta0, 1030;\n"
        "wgmma.mma_async.sync.aligned.m64n192k16.f32.bf16.bf16 {%0, %1, %2, %3, %4, %5, %6, %7, %8, %9, %10, %11, %12, %13, %14, %15, %16, %17, %18, %19, %20, %21, %22, %23, %24, %25, %26, %27, %28, %29, %30, %31, %32, %33, %34, %35, %36, %37, %38, %39, %40, %41, %42, %43, %44, %45, %46, %47, %48, %49, %50, %51, %52, %53, %54, %55, %56, %57, %58, %59, %60, %61, %62, %63, %64, %65, %66, %67, %68, %69, %70, %71, %72, %73, %74, %75, %76, %77, %78, %79, %80, %81, %82, %83, %84, %85, %86, %87, %88, %89, %90, %91, %92, %93, %94, %95}, ta, tb, p1, 1, 1, 0, 1;\n"
        "}\n"
        : "+f"(d[0]), "+f"(d[1]), "+f"(d[2]), "+f"(d[3]), "+f"(d[4]), "+f"(d[5]), "+f"(d[6]), "+f"(d[7]), "+f"(d[8]), "+f"(d[9]), "+f"(d[10]), "+f"(d[11]), "+f"(d[12]), "+f"(d[13]), "+f"(d[14]), "+f"(d[15]), "+f"(d[16]), "+f"(d[17]), "+f"(d[18]), "+f"(d[19]), "+f"(d[20]), "+f"(d[21]), "+f"(d[22]), "+f"(d[23]), "+f"(d[24]), "+f"(d[25]), "+f"(d[26]), "+f"(d[27]), "+f"(d[28]), "+f"(d[29]), "+f"(d[30]), "+f"(d[31]), "+f"(d[32]), "+f"(d[33]), "+f"(d[34]), "+f"(d[35]), "+f"(d[36]), "+f"(d[37]), "+f"(d[38]), "+f"(d[39]), "+f"(d[40]), "+f"(d[41]), "+f"(d[42]), "+f"(d[43]), "+f"(d[44]), "+f"(d[45]), "+f"(d[46]), "+f"(d[47]), "+f"(d[48]), "+f"(d[49]), "+f"(d[50]), "+f"(d[51]), "+f"(d[52]), "+f"(d[53]), "+f"(d[54]), "+f"(d[55]), "+f"(d[56]), "+f"(d[57]), "+f"(d[58]), "+f"(d[59]), "+f"(d[60]), "+f"(d[61]), "+f"(d[62]), "+f"(d[63]), "+f"(d[64]), "+f"(d[65]), "+f"(d[66]), "+f"(d[67]), "+f"(d[68]), "+f"(d[69]), "+f"(d[70]), "+f"(d[71]), "+f"(d[72]), "+f"(d[73]), "+f"(d[74]), "+f"(d[75]), "+f"(d[76]), "+f"(d[77]), "+f"(d[78]), "+f"(d[79]), "+f"(d[80]), "+f"(d[81]), "+f"(d[82]), "+f"(d[83]), "+f"(d[84]), "+f"(d[85]), "+f"(d[86]), "+f"(d[87]), "+f"(d[88]), "+f"(d[89]), "+f"(d[90]), "+f"(d[91]), "+f"(d[92]), "+f"(d[93]), "+f"(d[94]), "+f"(d[95])
        : "l"(descA), "n"(AOFF >> 4), "l"(descB), "n"(BOFF >> 4));
}

struct Params {
    const __nv_bfloat16* x;
    const __nv_bfloat16* wqkv;
    const __nv_bfloat16* wo;
    const __nv_bfloat16* logit_scale;
    const __nv_bfloat16* cpb_w1;
    const __nv_bfloat16* cpb_w2;
    const __nv_bfloat16* rel_coords;
    const int*           rel_idx;
    const __nv_bfloat16* mask;
    __nv_bfloat16*       out;
    unsigned long long   z1;
    int                  npair;
    uint32_t             need;
    int                  nq, nr;
    int                  nr2, nt0, nt1;
    int                  t1;
};

struct Maps {
    CUtensorMap x77, x47, x37, x44, x43, x34, x33;
    CUtensorMap w64, w32, w;
    CUtensorMap s47, s37, s43, s33;
    CUtensorMap o, ob;
};

__device__ __forceinline__ uint32_t row_token(uint32_t r) {
    return r < 28 ? r + 3 * (r >> 2) : r - 24 + 4 * (((r - 28) * 11) >> 5);
}
__device__ __forceinline__ int unrot(int r) { return r ? r - 1 : NWS - 1; }
__device__ __forceinline__ void finish(uint32_t total) {
    __threadfence();
    if (atomicAdd(&g_done, 1u) == total - 1) {
        for (int i = 0; i <= NWS; i++) g_cnt[i] = 0;
        g_done = 0;
    }
}

__global__ void __launch_bounds__(NTHREADS, 1)
swin_window_attn_kernel(const Params P, const __grid_constant__ Maps M) {
    const CUtensorMap &xmap = M.x77, &omap = M.o, &omapb = M.ob, &wmap = M.w;
    extern __shared__ __align__(1024) uint8_t smem[];
    constexpr uint32_t sbase = 1024;
    if (smem_u32(smem) != sbase) return;
    const int tid = threadIdx.x;
    const int wg = __shfl_sync(0xffffffffu, tid >> 7, 0);
    const int warp = __shfl_sync(0xffffffffu, (tid >> 5) & 3, 0);
    const int lane = tid & 31;
    const int g = lane >> 2, c = lane & 3;

    TR(26, wg);
    TP(wg);
    if (tid == 0) TC(0);
    const bool attn = (int)blockIdx.x < 2 * P.npair;
    const int pair = blockIdx.x >> 1, half = blockIdx.x & 1;
    const int nwin = P.nq + (pair < P.nr ? 1 : 0);
    const int ntiles = (nwin * TOK + 63) >> 6;
    const uint32_t bars = sbase + SM_BAR;
    auto load_x = [&](uint32_t dst, uint32_t bar, uint32_t bar2, int wh, int ww) {
        const int x0 = 7 * ww + 3, y0 = 7 * wh + 3, x1 = ww == NWS - 1 ? 0 : x0 + 4;
        if (wh < NWS - 1) {
#pragma unroll
            for (int ch = 0; ch < 3; ch++) tma_3d_x(dst + ch * QK_CHUNK, &M.x47, bar, ch * 64, x0, y0);
#pragma unroll
            for (int ch = 0; ch < 3; ch++) tma_3d_x(dst + ch * QK_CHUNK + 28 * 128, &M.x37, bar2, ch * 64, x1, y0);
        } else {
#pragma unroll
            for (int ch = 0; ch < 3; ch++) {
                tma_3d_x(dst + ch * QK_CHUNK, &M.x44, bar, ch * 64, x0, y0);
                tma_3d_x(dst + ch * QK_CHUNK + 16 * 128, &M.x43, bar, ch * 64, x0, 0);
            }
#pragma unroll
            for (int ch = 0; ch < 3; ch++) {
                tma_3d_x(dst + ch * QK_CHUNK + 28 * 128, &M.x34, bar2, ch * 64, x1, y0);
                tma_3d_x(dst + ch * QK_CHUNK + 40 * 128, &M.x33, bar2, ch * 64, x1, 0);
            }
        }
    };
    uint32_t ls = 0;
    if (wg == 0) {
        TP(28);
        if (attn && warp < (WSEQ ? 1 : 3) && elect_one()) {
#pragma unroll
            for (int i = 0; i < (WSEQ ? 3 : 1); i++) mbar_init(bars + B_WRAW + 16 - 8 * (warp + i), 1);
            fence_async_smem();
            TP(29);
#pragma unroll 1
            for (int i = warp; i < warp + (WSEQ ? 3 : 1); i++) {
                const uint32_t bar = bars + B_WRAW + 16 - 8 * i, dst = sbase + i * 24576;
                mbar_arrive_expect_tx(bar, 24576);
                tma_3d(dst, &M.w64, bar, half * 128, 64 * i, 0);
                tma_3d(dst + 16384, &M.w32, bar, 64 + half * 32, 64 * i, 0);
            }
            TP(30);
        }
        __syncwarp();
        if (WFIRST && warp == 0) asm volatile("bar.arrive 3, 96;\n" ::: "memory");
        if (attn) asm volatile("ld.global.nc.u16 %0, [%1];\n" : "=r"(ls) : "l"(P.logit_scale + 2 * half + (GORD == 2 ? c >> 1 : c & 1)));
    } else if (wg == 3) {
        if (warp == 3) {
            if (elect_one()) {
#pragma unroll
                for (int i = 0; i < 6; i++)
                    asm volatile("prefetch.tensormap [%0];\n" :: "l"(reinterpret_cast<uint64_t>(&M.x44 + (i < 4 ? i : i - 6))) : "memory");
            }
            if (attn)
#pragma unroll
                for (int i = 0; i < 4; i++) sts128(sbase + SM_V + i * V_STRIDE + (lane < 16 ? lane * 16 : V_STRIDE - 64 + (lane & 3) * 16), 0, 0, 0, 0);
            sts32(sbase + SM_FLAG + lane * 4, 0);
            fence_async_smem();
            asm volatile("bar.arrive 0, 256;\nbar.arrive 11, 384;\n" ::: "memory");
        } else if (warp != 1) {
            if (tid == 384) {
                for (int b = 0; b < 4; b++) mbar_init(bars + B_XFULL + b * 8, 2);
                asm volatile("mbarrier.expect_tx.relaxed.cta.shared::cta.b64 [%0], %1;\n" :: "r"(bars + B_XFULL + 8), "r"(3 * 21 * 128) : "memory");
                fence_async_smem();
            }
            __syncwarp();
            asm volatile("bar.arrive 0, 256;\nbar.arrive 11, 384;\n" ::: "memory");
            nb_sync<WFIRST ? 96 : 64>(3);
            if (attn && elect_one()) {
                const int j = warp >> 1, q = pair + j * P.npair, r = q >= NWS;
                mbar_arrive_expect_tx(bars + B_XFULL, j ? 3 * 28 * 128 : 3 * XCH);
                load_x(sbase + SM_QK + j * XCH, bars + B_XFULL, bars + B_XFULL + j * 8, unrot(r), unrot(q - r * NWS));
                TP(26 + j);
            }
            __syncwarp();
        } else {
            if (lane == 0) {
                for (int b = 0; b < 4; b++) {
                    mbar_init(bars + B_QKRAW + b * 8, 4);
                    mbar_init(bars + B_VRAW + b * 8, 4);
                    mbar_init(bars + B_VFREE + b * 8, 2);
                    mbar_init(bars + B_QKFREE + b * 8, (NB & 1) ? 1 : 4);
                    mbar_init(bars + B_ODONE + b * 8, 4);
                }
                mbar_init(bars + B_WFULL, 1);
                mbar_init(bars + B_MFULL, 1);
                mbar_init(bars + B_MCONS, 4);
                sts32(bars + B_PROG, 0);
                for (int b = 0; b < 4; b++) mbar_init(bars + B_STORED + b * 8, 1);
                for (int b = 0; b < 6; b++) {
                    mbar_init(sbase + SM_PBAR + b * 8, 1);
                    mbar_init(sbase + SM_PBAR + 48 + b * 8, PSTORE ? 1 : 4);
                    mbar_init(sbase + SM_PBAR + 104 + b * 8, 4);
                }
                mbar_init(sbase + SM_PBAR + 96, 13);
                fence_async_smem();
            }
            __syncwarp();
            TP(19);
            asm volatile("bar.arrive 0, 256;\nbar.arrive 11, 384;\n" ::: "memory");
        }
        asm volatile("bar.sync 2, 128;\n" ::: "memory");
        if (warp == 3 && lane < 8)
            asm volatile("prefetch.tensormap [%0];\n" :: "l"(reinterpret_cast<uint64_t>(&M.x77 + (lane ? lane + 8 : 0))) : "memory");
        TP(13);
    }
    uint32_t ridx[26];
    uint32_t rc, w2[16];
    uint4 w1[4];
    if (attn && (wg == 1 || wg == 2)) {
        rc = reinterpret_cast<const uint32_t*>(P.rel_coords)[min(tid - 128, 168)];
#pragma unroll
        for (int i = 0; i < 4; i++) w1[i] = reinterpret_cast<const uint4*>(P.cpb_w1)[i];
#pragma unroll
        for (int u = 0; u < 16; u++) w2[u] = reinterpret_cast<const uint32_t*>(P.cpb_w2)[2 * u + half];
        ls = reinterpret_cast<const uint32_t*>(P.logit_scale)[half];
        asm volatile("" ::: "memory");
        uint32_t col[7];
#pragma unroll
        for (int j = 0; j < 7; j++) {
            const uint32_t n = j ? 8 * ((j + 5) >> 1) + ((j + 1) & 1) : 0;
            col[j] = prmt(0, row_token(n) | row_token(n + 2) << 8 | row_token(n + 4) << 16 | row_token(n + 6) << 24, 4 + c);
        }
#pragma unroll
        for (int rh = 0; rh < 2; rh++) {
            const uint32_t* ri = reinterpret_cast<const uint32_t*>(P.rel_idx) + row_token(min(warp * 16 + g + 8 * rh, TOK - 1)) * TOK;
            asm volatile("" : "+l"(ri));
#pragma unroll
            for (int j = 0; j < 12; j++) ridx[13 * rh + j] = j < 6 ? (ri + col[0])[14 * (j >> 1) + (j & 1)] : ri[col[j - 5]];
            ridx[13 * rh + 12] = ri[48];
        }
    }
    if (wg == 1) TP(31);
    if (wg == 0) asm volatile("bar.sync 0, 256;\n" ::: "memory");
    else if (wg < 3) asm volatile("bar.sync 11, 384;\n" ::: "memory");
    TP(4 + wg);

    const uint32_t nfinish = gridDim.x + 4 * P.npair;
#define PROJ_SCHEDULE                                                                                   \
    int bid = blockIdx.x;                                                                               \
    asm volatile("" : "+r"(bid));                      \
    const bool at = bid < 2 * P.npair;                                                                  \
    const int tile0 = at ? P.t1 + 2 * P.npair - 1 - bid : bid - 2 * P.npair;                                              \
    const int tstep = at ? 2 * P.npair : (int)gridDim.x - 2 * P.npair;                                  \
    const int tend = at ? TILES : P.t1;
    if (wg == 3) {
        asm volatile("setmaxnreg.dec.sync.aligned.u32 %0;\n" :: "n"(REG_H));
        if (attn && warp == 1 && !(XP & 1)) {
            uint32_t fph = 0, cph = 0, mis;
            auto load = [&](int k) {
                const int wi = pair + k * P.npair, wr = wi / NWS;
                const uint32_t off = (uint32_t)(unrot(wr) * NWS + unrot(wi - wr * NWS)) * 4802u;
                mis = off & 15;
                if (elect_one()) {
                    uint32_t bytes = 4816;
                    if (wi == 0) {
                        bytes = 4800;
                        asm volatile("st.shared.u16 [%0], %1;\n" :: "r"(sbase + SM_MASK + 4800),
                                     "h"(reinterpret_cast<const uint16_t*>(P.mask)[NWINDOWS * TOK * TOK - 1]) : "memory");
                    }
                    mbar_arrive_expect_tx(bars + B_MFULL, bytes);
                    asm volatile("cp.async.bulk.shared::cluster.global.mbarrier::complete_tx::bytes.L2::cache_hint [%0], [%1], %2, [%3], %4;\n"
                                 :: "r"(sbase + SM_MASK), "l"(reinterpret_cast<const char*>(P.mask) + (off - mis)),
                                    "r"(bytes), "r"(bars + B_MFULL), "l"(EVICT_FIRST) : "memory");
                }
            };
            auto landed = [&]() {
                mbar_wait(bars + B_MFULL, fph);
                fph ^= 1;
            };
            auto flag = [&](int k, uint32_t f) {
                asm volatile("st.volatile.shared.u8 [%0], %1;\n" :: "r"(sbase + SM_FLAG + k), "r"(f) : "memory");
                TR(18, k);
                if (k < 2) TP(14 + k);
            };
            if (MWAIT) mbar_wait(bars + B_XFULL, 0);
            load(2 + half);
            if (MPRE && elect_one()) {
                const int wi = pair + half * P.npair, wr = wi / NWS;
                const uint32_t off = (uint32_t)(unrot(wr) * NWS + unrot(wi - wr * NWS)) * 4802u;
                asm volatile("cp.async.bulk.prefetch.L2.global [%0], 4800;\n" :: "l"(reinterpret_cast<const char*>(P.mask) + (off & ~15u)) : "memory");
            }
            uint32_t todo = 3;
            int sp = 0;
#pragma unroll 1
            for (int k = 2 + half; sp < nwin; k += 2) {
                if (k < nwin) {
#pragma unroll 1
                    for (uint32_t n = 0; n < (1u << 22); n++) {
                        int done;
                        asm volatile("ld.volatile.shared.b32 %0, [%1];\n" : "=r"(done) : "r"(bars + B_PROG) : "memory");
                        if (done >= (k + 2 < nwin ? k - MLEAD : k - 3)) break;
                        __nanosleep(PSLEEP);
                    }
                    landed();
                    TR(17, k);
                    uint32_t any;
                    asm volatile("ld.shared.u16 %0, [%1];\n" : "=r"(any)
                                 : "r"(sbase + SM_MASK + mis + ((lane & 8) ? 4800 - 14 : 0) + (lane & 7) * 2) : "memory");
#pragma unroll
                    for (int i = 0; i < 10; i++) {
                        uint32_t v[4];
                        asm volatile("ld.shared.v4.b32 {%0, %1, %2, %3}, [%4];\n" : "=r"(v[0]), "=r"(v[1]), "=r"(v[2]), "=r"(v[3])
                                     : "r"(sbase + SM_MASK + lane * 16 + (i < 9 ? 16 + i * 512 : 4800 - 512)) : "memory");
                        any |= (v[0] | v[1]) | (v[2] | v[3]);
                    }
                    const uint32_t masked = __any_sync(0xffffffffu, any & 0x7FFF7FFFu);
                    asm volatile("st.relaxed.gpu.global.u32 [%0], %1;\n" :: "l"(g_flag + pair * 128 + k), "r"(1 + masked) : "memory");
                    if (masked) todo |= 1u << (k - sp);
                    else flag(k, 1);
                }
                if (k > 2 && k <= nwin) {
                    uint32_t f;
#pragma unroll 1
                    for (uint32_t n = 0; n < (1u << 22); n++) {
                        asm volatile("ld.relaxed.gpu.global.u32 %0, [%1];\n" : "=r"(f) : "l"(g_flag + pair * 128 + k - 1) : "memory");
                        if (__all_sync(0xffffffffu, f)) break;
                        __nanosleep(PSLEEP);
                    }
                    g_flag[pair * 128 + k - 1] = 0;
                    if (f != 1) todo |= 1u << (k - 1 - sp);
                    else flag(k - 1, 1);
                }
#pragma unroll 1
                for (; sp < k; sp++, todo >>= 1)
                    if (todo & 1) {
                        load(sp);
                        landed();
                        __threadfence_block();
                        flag(sp, 2);
                        mbar_wait(bars + B_MCONS, cph);
                        cph ^= 1;
                        fence_async_smem();
                    }
                if (k + 2 < nwin) load(k + 2);
            }
        }
        if (!elect_one()) return;
        if (warp == 0) {
          if (attn) {
            const int kmax = (64 * ntiles + 63) / TOK;
            int wr = 0, wq = pair;
            int pr2 = (pair + PF_DIST * P.npair) / NWS, pq2 = pair + PF_DIST * P.npair - pr2 * NWS;
#pragma unroll 1
            for (int k = -4; k + 4 <= kmax; k++) {
                const int row0 = (k + 4) * TOK;
                const uint32_t dst = sbase + SM_QK + (k & 3) * XCH, bar = bars + B_XFULL + ((row0 >> 6) & 3) * 8;
                const bool alone = (row0 & 63) >= 64 - TOK && (row0 & 63) < TOK;
                const int wh = unrot(wr), ww = unrot(wq), ph2 = unrot(pr2), pw2 = unrot(pq2);
                const bool done = k < -2;
                if (k == WVK) {
                    TP(24);
                    mbar_arrive_expect_tx(bars + B_WFULL, 6 * W_ATOM);
                    tma_3d(sbase + SM_WV, &wmap, bars + B_WFULL, 0, 0, 24 + half * 6);
                }
                if (NB & 1) {
                    if (k >= 0) nb_sync<160>(NB_QKFREE + (k & 1));
                } else mbar_wait(bars + B_QKFREE + (k & 3) * 8, (k >> 2) & 1);
                if (alone && !done) mbar_arrive(bar);
                if (k + 4 >= nwin) {
                    mbar_arrive(bar);
                    continue;
                }
                TR(20, k + 4);
                if (k < 0) TP(44 + k);
                if (!done) {
                    uint32_t bar2 = bar;
                    if ((row0 & 63) >= 64 - 28) {
                        bar2 = bars + B_XFULL + (((row0 >> 6) + 1) & 3) * 8;
                        asm volatile("mbarrier.expect_tx.relaxed.cta.shared::cta.b64 [%0], %1;\n" :: "r"(bar2), "r"(3 * 21 * 128) : "memory");
                    }
                    mbar_arrive_expect_tx(bar, bar2 != bar ? 3 * 28 * 128 : 3 * XCH);
                    load_x(dst, bar, bar2, wh, ww);
                }
                asm volatile("st.volatile.shared.b32 [%0], %1;\n" :: "r"(bars + B_PROG), "r"(max(k + 1, 0)) : "memory");
                if (NOPF) {
                } else if (PFM == 2) {
                    if (pr2 < NWS && half == 0) {
                        const char* xp = reinterpret_cast<const char*>(P.x) + (size_t)((7 * ph2 + 3) * IMG + 7 * pw2 + 3) * 384;
#pragma unroll 1
                        for (int r = 0; r < (ph2 == NWS - 1 ? 3 : 7); r++)
                            asm volatile("cp.async.bulk.prefetch.L2.global [%0], 2688;\n" :: "l"(xp + r * (IMG * 384)) : "memory");
                    }
                } else if (PFM == 1 ? ((k ^ half) & 1) : PFM == 4 ? half == 1 : PFM == 5 ? 1 : half == 0) {
                    if (pr2 < NWS) {
#pragma unroll
                        for (int ch = 0; ch < (PF1 ? 1 : 3); ch++)
                            if (CH & 8)
                            asm volatile("cp.async.bulk.prefetch.tensor.3d.L2.global.tile.L2::cache_hint [%0, {%1, %2, %3}], %4;\n"
                                         :: "l"(reinterpret_cast<uint64_t>(&xmap)), "r"(ch * 64), "r"(7 * pw2 + 3), "r"(7 * ph2 + 3), "l"(EVICT_FIRST)
                                         : "memory");
                            else
                            asm volatile("cp.async.bulk.prefetch.tensor.3d.L2.global.tile [%0, {%1, %2, %3}];\n"
                                         :: "l"(reinterpret_cast<uint64_t>(&xmap)), "r"(ch * 64), "r"(7 * pw2 + 3), "r"(7 * ph2 + 3)
                                         : "memory");
                    }
                }
                wq += P.npair; if (wq >= NWS) { wq -= NWS; wr++; }
                pq2 += P.npair; if (pq2 >= NWS) { pq2 -= NWS; pr2++; }
            }
            mbar_wait(bars + B_VRAW + ((ntiles - 1) & 3) * 8, ((ntiles - 1) >> 2) & 1);
          }
            PROJ_SCHEDULE
            int st = 0, ready = -1;
            uint32_t ph = 1;
#pragma unroll 1
            for (int t = tile0; t < tend; t += tstep) {
                const int p0 = (t < TILES_A) ? SEG_B + 64 * t : 64 * (t - TILES_A);
                const int w1 = (t < TILES_A) ? 0 : min((p0 + 63 + 4 * IMG) / (7 * IMG), NWS - 1);
                if (at && t == tile0 + tstep) {
                    mbar_wait(sbase + SM_PBAR + 96, 0);
                    fence_async_smem();
                }
                if (ready < w1) {
                    ready = max(ready, w1 - 2);
#pragma unroll 1
                    while (ready < w1) {
                        ready++;
#pragma unroll 1
                        for (uint32_t n = 0; n < (1u << 22); n++) {
                            uint32_t a;
                            asm volatile("ld.acquire.gpu.global.u32 %0, [%1];\n" : "=r"(a) : "l"(g_cnt + ready) : "memory");
                            if (a >= P.need) break;
                            __nanosleep(64);
                        }
                    }
                    asm volatile("fence.proxy.async.global;\n" ::: "memory");
                }
                TRH(9, (t - tile0) / tstep);
                mbar_wait(sbase + SM_PBAR + 48 + st * 8, ph);
                TRH(5, (t - tile0) / tstep);
                if (PEXP & 2) mbar_arrive(sbase + SM_PBAR + st * 8); else {
                mbar_arrive_expect_tx(sbase + SM_PBAR + st * 8, STAGE_BYTES);
#pragma unroll
                for (int ch = 0; ch < 3; ch++)
                    tma_2d(sbase + SM_STAGE + st * STAGE_BYTES + ch * 8192, &omap, sbase + SM_PBAR + st * 8, ch * 64, (PEXP & 4) ? p0 & 8191 : p0);
                }
                if (++st == 6) { st = 0; ph ^= 1; }
            }
            finish(nfinish);
        } else if (!attn) {
        } else if (warp == 1) {
          {
            if (P.t1 < TILES) {
#pragma unroll 1
                for (uint32_t n = 0; n < (1u << 22); n++) {
                    uint32_t a;
                    asm volatile("ld.acquire.gpu.global.u32 %0, [%1];\n" : "=r"(a) : "l"(g_cnt + NWS) : "memory");
                    if (a) break;
                    __nanosleep(64);
                }
                asm volatile("fence.proxy.async.global;\n" ::: "memory");
                if (blockIdx.x % 6 == 0)
                    asm volatile("cp.async.bulk.prefetch.L2.global [%0], 4096;\n" :: "l"(g_wo + blockIdx.x / 6 % 18 * 4096) : "memory");
                if (NB & 4) mbar_wait(bars + B_QKRAW, 0);
                else mbar_wait(bars + B_QKRAW + ((ntiles - 1) & 3) * 8, ((ntiles - 1) >> 2) & 1);
                mbar_arrive_expect_tx(bars + B_WRAW, 73728);
#pragma unroll
                for (int i = 0; i < 4; i++) {
                    const uint32_t o = ((i + pair) & 3) * 18432;
                    asm volatile("cp.async.bulk.shared::cluster.global.mbarrier::complete_tx::bytes [%0], [%1], 18432, [%2];\n"
                                 :: "r"(sbase + SM_WO + o), "l"(g_wo + o), "r"(bars + B_WRAW) : "memory");
                }
            }
            finish(nfinish);
          }
        } else if (warp == 2) {
            int wh = 0, ww = pair, nb = 1;
#pragma unroll 1
            for (int j = 0; wh < NWS; j++) {
                mbar_wait(bars + B_STORED + (j & 1) * 8, (j >> 1) & 1);
                mbar_arrive(bars + B_PUBD + (j & 1) * 8);
                asm volatile("fence.release.gpu;\n" ::: "memory");
#pragma unroll 1
                while (wh < nb) {
                    asm volatile("red.relaxed.gpu.global.add.u32 [%0], 1;\n" :: "l"(g_cnt + wh) : "memory");
                    ww += P.npair; if (ww >= NWS) { ww -= NWS; wh++; }
                }
                nb = wh >= PBE ? wh + 1 : (wh | 1) + 1;
            }
            TC(7);
            finish(nfinish);
        } else {
            for (int t = 0; t < 2; t++) mbar_arrive_n(bars + B_VFREE + t * 8, 2);
            int wr = 0, wq = pair, nb = 1, j = 0;
#pragma unroll 1
            for (int k = 0; k < nwin; k++) {
                const uint32_t src = sbase + SM_V + (k & 3) * V_STRIDE;
                const int wh = unrot(wr), ww = unrot(wq);
                const int x0 = 7 * ww + 3, y0 = 7 * wh + 3;
                if (NB & 2) nb_sync<160>(NB_ODONE + (k & 3));
                else mbar_wait(bars + B_ODONE + (k & 3) * 8, (k >> 2) & 1);
                fence_async_smem();
                TR(22, k);
                const int x1 = ww == NWS - 1 ? 0 : x0 + 4;
                if (!(XP & 2)) tma_store_4d(&M.s47, src, 0, half, x0, y0);
                if (!(XP & 2)) tma_store_4d(&M.s37, src + 28 * O_PITCH, 0, half, x1, y0);
                if (wh == NWS - 1) {
                    tma_store_4d(&M.s43, src + 16 * O_PITCH, 0, half, x0, 0);
                    tma_store_4d(&M.s33, src + 40 * O_PITCH, 0, half, x1, 0);
                }
                asm volatile("cp.async.bulk.commit_group;\n" ::: "memory");
                asm volatile("cp.async.bulk.wait_group.read 0;\n" ::: "memory");
                {
                    const int row0 = (k + 4) * TOK;
                    mbar_arrive_n(bars + B_VFREE + ((row0 >> 6) & 3) * 8, ((row0 & 63) >= 64 - TOK && (row0 & 63) < TOK) ? 2 : 1);
                }
                TR(23, k);
                if (k == nwin - 1) mbar_arrive(sbase + SM_PBAR + 96);
                wq += P.npair; if (wq >= NWS) { wq -= NWS; wr++; }
                if (wr >= nb) {
                    nb = wr >= PBE ? wr + 1 : (wr | 1) + 1;
                    asm volatile("cp.async.bulk.wait_group 0;\n" ::: "memory");
                    if (WFEN) asm volatile("fence.proxy.async.global;\n" ::: "memory");
                    mbar_wait(bars + B_PUBD + (j & 1) * 8, ((j >> 1) + 1) & 1);
                    mbar_arrive(bars + B_STORED + (j & 1) * 8);
                    j++;
                }
            }
        }
        if (PSTORE && warp == 1) {
            PROJ_SCHEDULE
            int st = 0, prev = -1;
            uint32_t ph = 0;
#pragma unroll 1
            for (int t = tile0; t < tend; t += tstep) {
                const int p0 = (t < TILES_A) ? SEG_B + 64 * t : 64 * (t - TILES_A);
                mbar_wait(sbase + SM_PBAR + 104 + st * 8, ph);
                fence_async_smem();
#pragma unroll
                for (int ch = 0; ch < ((PEXP & 1) ? 0 : 3); ch++)
                    if (CH & 1)
                    asm volatile("cp.async.bulk.tensor.2d.global.shared::cta.tile.bulk_group.L2::cache_hint [%0, {%2, %3}], [%1], %4;\n"
                                 :: "l"(reinterpret_cast<uint64_t>(t < TILES_A ? &omap : &omapb)),
                                    "r"(sbase + SM_STAGE + st * STAGE_BYTES + ch * 8192), "r"(ch * 64), "r"(p0), "l"(EVICT_FIRST) : "memory");
                    else
                    asm volatile("cp.async.bulk.tensor.2d.global.shared::cta.tile.bulk_group [%0, {%2, %3}], [%1];\n"
                                 :: "l"(reinterpret_cast<uint64_t>(t < TILES_A ? &omap : &omapb)),
                                    "r"(sbase + SM_STAGE + st * STAGE_BYTES + ch * 8192), "r"(ch * 64), "r"((PEXP & 8) ? (p0 & 8191) + 16384 : p0) : "memory");
                asm volatile("cp.async.bulk.commit_group;\n" ::: "memory");
                TRH(6, (t - tile0) / tstep);
                if (prev >= 0) {
                    asm volatile("cp.async.bulk.wait_group.read 1;\n" ::: "memory");
                    mbar_arrive(sbase + SM_PBAR + 48 + prev * 8);
                    TRH(21, (t - tile0) / tstep - 1);
                }
                prev = st;
                if (++st == 6) { st = 0; ph ^= 1; }
            }
            if (ENDR) asm volatile("cp.async.bulk.wait_group.read 0;\n" ::: "memory");
            else asm volatile("cp.async.bulk.wait_group 0;\n" ::: "memory");
            TR(30, 0);
            TC(1);
        }
        return;
    }
    if (!attn) {
        asm volatile("setmaxnreg.inc.sync.aligned.u32 160;\n");
    } else if (wg == 0) {
        {
            uint32_t src[3][4], dst[3];
#pragma unroll
            for (int it = 0; it < 3; it++) {
                const int o = warp * 12 + it * 4 + (lane >> 3), r = (o / 6) * 8 + (lane & 7), u = o % 6;
#pragma unroll
                for (int h = 0; h < (GORD == 2 ? 0 : 2); h++) {
                    const int v = u + 6 * h + 4 * half;
                    const bool wide = v >> 3 == half;
                    src[it][h] = wide ? r * 128 + (((v ^ r) & 7) << 4) : 16384 + r * 64 + (((v ^ (r >> 1)) & 3) << 4);
                    src[it][2 + h] = src[it][h] + (wide ? 8192 : 4096);
                }
                dst[it] = sbase + u * 4096 + r * 32 + ((lane >> 2) & 1) * 16;
            }
            TP(16);
#pragma unroll 1
            for (int i = 0; i < 3; i++) {
                uint4 w[3][4];
                mbar_wait(bars + B_WRAW + 16 - 8 * i, 0);
                TP(20 + i);
#pragma unroll
                for (int it = 0; it < 3; it++)
#pragma unroll
                    for (int m = 0; m < 4; m++) w[it][m] = *reinterpret_cast<const uint4*>(smem + src[it][m] + i * 24576);
                wg_bar(7);
#pragma unroll
                for (int it = 0; it < 3; it++) {
                    const uint32_t d = dst[it] + i * 24576;
                    sts128(d, w[it][0].x, w[it][1].x, w[it][2].x, w[it][3].x);
                    sts128(d ^ 16, w[it][0].y, w[it][1].y, w[it][2].y, w[it][3].y);
                    sts128(d + 2048, w[it][0].z, w[it][1].z, w[it][2].z, w[it][3].z);
                    sts128((d ^ 16) + 2048, w[it][0].w, w[it][1].w, w[it][2].w, w[it][3].w);
                }
            }
        }
        asm volatile("setmaxnreg.inc.sync.aligned.u32 %0;\n" :: "n"(REG_G));
        float qs = 1.f;
        if (GORD == 2 || c < 2) qs = round_bf16(expf(round_bf16(fminf(fmaxf(bf16lo(ls), -100.f), 4.6052f)))) * LOG2E;
        uint32_t xa[12][4];
        float accA[48], accB[48], accV[48];
        uint32_t rho = warp * 16 + (lane & 15), rq = warp * 16 + g;
        uint32_t hi = lane >> 4, lane0 = lane == 0, c2 = 2 * c;
        asm volatile("" : "+r"(hi), "+r"(lane0), "+r"(c2));
        auto row_addr = [&](uint32_t (&ax)[4], uint32_t r) {
            ax[0] = sbase + SM_QK + r * 128 + (((r & 7) ^ hi) << 4);
#pragma unroll
            for (int i = 1; i < 4; i++) ax[i] = ax[0] ^ (32 * i);
        };
#define XADDR(ax, s) ((ax)[((s) & 3) ^ (((s) >> 1) & 2)] + ((s) >> 2) * QK_CHUNK)
        uint64_t descW = make_desc(sbase, 2048, 256, 3);
        const uint32_t zero = (uint32_t)P.z1;
        const uint32_t vbase = sbase + SM_V + (lane >> 4) * GRP;
        const uint32_t ones = 0x3F803F80u, ones2 = ones;
        TP(10);
        {
            uint32_t ax[4];
            row_addr(ax, rho);
            mbar_wait(bars + B_XFULL, 0);
#pragma unroll
            for (int s = 0; s < 12; s++) ldsm_x4(xa[s], XADDR(ax, s));
        }
        TP(8);
        wg_bar(7);
        fence_async_smem();
        TP(9);
        wgmma_fence();
        mma_qkv_a<SM_WA, 0>(accA, xa, descW);
        mma_qkv_b<SM_WA, KLO>(accA, xa, descW);
        wgmma_commit();
        mma_qkv_a<SM_WB, 0>(accB, xa, descW);
        wgmma_commit();
        TP(11);
        mbar_wait(bars + B_WFULL, 0);
        TP(12);
        if (tid == 0) TC(3);
        const int nt = (int)blockIdx.x < P.nr2 ? P.nt1 : P.nt0;
        for (int t = 0; t < nt; t++) {
            descW += P.z1;
            float ss[4];
            uint32_t pk[2][24];
            wgmma_wait<1>();
            reg_fence(accA);
            TR(0, t);
            TA(1, 0);
            if (t < 12 && (t < 4 || (t & 1))) TP(t < 4 ? 32 + t : 34 + (t >> 1));
#pragma unroll
            for (int i = 0; i < 4; i++) ss[i] = accA[i] * accA[i];
#pragma unroll
            for (int i = 4; i < 48; i++) ss[i & 3] = fmaf(accA[i], accA[i], ss[i & 3]);
            mma_qkv_b<SM_WB, KLO>(accB, xa, descW);
            wgmma_commit();
            TA(1, 1);
            sched_fence(zero, __float_as_uint(ss[0]), __float_as_uint(ss[1]), __float_as_uint(ss[2]), __float_as_uint(ss[3]));
#pragma unroll
            for (int j = 0; j < 12; j++) {
                pk[0][j] = pack_bf16(accA[4 * j], accA[4 * j + 1]);
                pk[1][j] = pack_bf16(accA[4 * j + 2], accA[4 * j + 3]);
                asm volatile("" : "+r"(pk[0][j]), "+r"(pk[1][j]));
            }
            wgmma_fence();
            mma_v_a<D_WV, 0>(accV, xa, descW);
            wgmma_commit();
            TA(1, 2);
            uint32_t av = vbase + rho * 16 + ((rho * 1338) >> 16) * (V_STRIDE - GRP);
            uint32_t aq[2];
            aq[0] = sbase + SM_QK + rq * 128 + (((rq & 7) ^ c2) << 4);
            aq[1] = aq[0] + 1024;
            if (rq >= 4 * TOK - 8) aq[1] = (aq[1] - QK_CHUNK) ^ 64;
            rho += 64;
            if (rho >= 4 * TOK) rho -= 4 * TOK;
            rq += 64;
            if (rq >= 4 * TOK) rq -= 4 * TOK;
            uint32_t an[4];
            row_addr(an, rho);
            const uint32_t bt = bars + (t & 3) * 8, pt = (t >> 2) & 1, bn = bars + ((t + 1) & 3) * 8, pn = ((t + 1) >> 2) & 1;
            const uint32_t xok = mbar_test(bn + B_XFULL, pn) & mbar_test(bt + B_VFREE, pt);
            wgmma_wait<1>();
            reg_fence(accB);
            TA(1, 3);
#pragma unroll
            for (int i = 0; i < 48; i++) ss[i & 3] = fmaf(accB[i], accB[i], ss[i & 3]);
            ss[0] += ss[1]; ss[2] += ss[3];
            mma_v_b<D_WV, KLO>(accV, xa, descW);
            wgmma_commit();
            TA(1, 4);
            sched_fence(zero, __float_as_uint(ss[0]), __float_as_uint(ss[2]), av, aq[0], aq[1], an[0], an[1], an[2], an[3], rho, rq);
            const float f0 = rsqrt_ftz(ss[0] + 1e-12f) * qs, f1 = rsqrt_ftz(ss[2] + 1e-12f) * qs;
            const uint32_t f2[2] = {pack_bf16(f0, f0), pack_bf16(f1, f1)};
#pragma unroll
            for (int j = 0; j < 12; j++) {
                pk[0][12 + j] = (FM & 1) ? pack_bf16(accB[4 * j] * f0, accB[4 * j + 1] * f0) : pack_bf16(accB[4 * j], accB[4 * j + 1]);
                pk[1][12 + j] = (FM & 1) ? pack_bf16(accB[4 * j + 2] * f1, accB[4 * j + 3] * f1) : pack_bf16(accB[4 * j + 2], accB[4 * j + 3]);
            }
            auto qk_store = [&](int u0, int u1) {
#pragma unroll
                for (int u = u0; u < u1; u++)
#pragma unroll
                    for (int r = 0; r < 2; r++)
                        if ((FM & 1) && u >= 3)
                        sts128((aq[r] ^ ((u & 1) * 16 + (u & 2) * 32)) + (u >> 1) * QK_CHUNK, pk[r][4 * u], pk[r][4 * u + 1], pk[r][4 * u + 2], pk[r][4 * u + 3]);
                        else
                        sts128((aq[r] ^ ((u & 1) * 16 + (u & 2) * 32)) + (u >> 1) * QK_CHUNK,
                               hmul2_bf16(pk[r][4 * u], f2[r]), hmul2_bf16(pk[r][4 * u + 1], f2[r]),
                               hmul2_bf16(pk[r][4 * u + 2], f2[r]), hmul2_bf16(pk[r][4 * u + 3], f2[r]));
            };
            qk_store(0, QSPLIT);
            if (EARLYQ) {
                __syncwarp();
                mbar_arrive_if(bt + B_QKRAW, lane0);
            }
            TR(1, t);
            TA(1, 5);
            mbar_wait2_unless(xok, bn + B_XFULL, pn, bt + B_VFREE, pt);
            TR(2, t);
            wgmma_wait<1>();
            TA(1, 6);
#pragma unroll
            for (int s = 0; s < KLO; s++) ldsm_x4(xa[s], XADDR(an, s));
            qk_store(QSPLIT, 6 - QPOST);
            if (QPOST) {
                wgmma_fence();
                mma_qkv_a<SM_WA, 0>(accA, xa, descW);
                wgmma_commit();
                qk_store(6 - QPOST, 6);
            }
            if (!EARLYQ) {
                __syncwarp();
                mbar_arrive_if(bt + B_QKRAW, lane0);
            }
            TR(3, t);
            TA(1, 7);
            if (!QPOST) {
                wgmma_fence();
                mma_qkv_a<SM_WA, 0>(accA, xa, descW);
                wgmma_commit();
            }
            TA(1, 8);
            wgmma_wait<1>();
            reg_fence(accV);
            TA(1, 9);
#pragma unroll
            for (int s = KLO; s < 12; s++) ldsm_x4(xa[s], XADDR(an, s));
            uint32_t vp[24];
#pragma unroll
            for (int j = 0; j < 24; j++) vp[j] = pack_bf16(accV[2 * j], accV[2 * j + 1]);
            reg_fence(vp);
            wgmma_fence();
            mma_qkv_b<SM_WA, KLO>(accA, xa, descW);
            wgmma_commit();
            TA(1, 10);
#pragma unroll
            for (int p = 0; p < 6; p++)
                stsm_x4(av + (p < 3 ? 2 * p : 2 * p + 1) * GRP, vp[4 * p], vp[4 * p + 1], vp[4 * p + 2], vp[4 * p + 3]);
            stsm_x2(av + 6 * GRP, ones, ones2);
            __syncwarp();
            mbar_arrive_if(bt + B_VRAW, lane0);
            TR(4, t);
            if (!MERGEW) wgmma_fence();
            mma_qkv_a<SM_WB, 0>(accB, xa, descW);
            wgmma_commit();
            TA(1, 11);
        }
        TAEND(1);
        wgmma_wait<0>();
        reg_fence(accA);
        reg_fence(accB);
        asm volatile("setmaxnreg.dec.sync.aligned.u32 160;\n");
    } else {
        if (REG_A > 128) asm volatile("setmaxnreg.inc.sync.aligned.u32 %0;\n" :: "n"(REG_A));
        {
            const float c0 = bf16lo(rc), c1 = bf16hi(rc);
            float a0 = 0.f, a1 = 0.f;
#pragma unroll
            for (int u = 0; u < 16; u += 2) {
                const uint32_t p = reinterpret_cast<const uint32_t*>(w1)[u >> 1], q = reinterpret_cast<const uint32_t*>(w1)[8 + (u >> 1)];
                uint32_t h;
                asm("cvt.rn.relu.bf16x2.f32 %0, %1, %2;\n" : "=r"(h) : "f"(c0 * bf16hi(p) + c1 * bf16hi(q)), "f"(c0 * bf16lo(p) + c1 * bf16lo(q)));
                a0 += bf16lo(h) * bf16lo(w2[u]);
                a1 += bf16lo(h) * bf16hi(w2[u]);
                a0 += bf16hi(h) * bf16lo(w2[u + 1]);
                a1 += bf16hi(h) * bf16hi(w2[u + 1]);
            }
            const float s0 = round_bf16(__fdividef(1.f, 1.f + expf(-round_bf16(a0))));
            const float s1 = round_bf16(__fdividef(1.f, 1.f + expf(-round_bf16(a1))));
            if (tid - 128 < 169) sts32(sbase + SM_TAB + (tid - 128) * 4, pack_bf16(exp2f(fmaf(s0, 16.f * LOG2E, -12.f)), exp2f(fmaf(s1, 16.f * LOG2E, -12.f))));
        }
        asm volatile("bar.sync 1, 256;\n" ::: "memory");
        uint32_t eb[26];
        {
            const uint32_t* tab = reinterpret_cast<const uint32_t*>(smem + SM_TAB);
#pragma unroll
            for (int i = 0; i < 13; i++) {
                const uint32_t lo = tab[min(ridx[i < 12 ? 13 * (i & 1) + (i & ~1) : 12], 168u)];
                const uint32_t hi = tab[min(ridx[i < 12 ? 13 * (i & 1) + (i | 1) : 25], 168u)];
                eb[i]      = prmt(lo, hi, 0x5410);
                eb[13 + i] = prmt(lo, hi, 0x7632);
            }
            if (c != 0) eb[12] = eb[25] = 0;
            if (EBZ) {
                const uint32_t k0 = warp * 16 + g < TOK ? ~0u : 0u, k1 = warp < 3 ? ~0u : 0u;
#pragma unroll
                for (int i = 0; i < 26; i++) eb[i] &= i % 13 == 12 ? (k0 & 0xFFFFu) | (k1 & 0xFFFF0000u) : ((i % 13) & 1) ? k1 : k0;
            }
        }
        uint32_t slow = (bf16lo(ls) <= LS_FAST ? 0 : 1) | (bf16hi(ls) <= LS_FAST ? 0 : 2);
        reg_fence(eb);
        if (SLOWH == 2) sts32(bars + B_PROG + 4, slow);
        wg_bar(3 + wg);
        if ((tid & 127) == 0) mbar_arrive(bars + B_VFREE + 16);
        const uint32_t ov0 = warp * 16 + g < TOK, ov1 = warp < 3;
        const uint64_t descK0 = make_desc(sbase + SM_QK, 16, 1024, 1);
        const uint64_t descV0 = make_desc(sbase + SM_V, 128, GRP, 0);
        slow = __shfl_sync(0xffffffffu, slow, 0);
        const uint32_t barw = bars + (wg - 1) * 8;
        const uint64_t descKw = descK0 + (uint64_t)((wg - 1) * (XCH >> 4)), descVw = descV0 + (uint64_t)((wg - 1) * (V_STRIDE >> 4));
        const uint32_t oa = sbase + SM_V + (wg - 1) * V_STRIDE + (warp * 16 + g) * O_PITCH + c * 48;
        uint32_t qok = 0;
        const uint32_t zero = (uint32_t)P.z1;
        auto window = [&](auto IT_, int k) {
            constexpr int IT = decltype(IT_)::value;
            const uint32_t bar = barw + 16 * IT;
            const int tl = (k * TOK + TOK - 1) >> 6, tn = ((k + 2) * TOK + TOK - 1) >> 6;
            const uint32_t bt = bars + (tl & 3) * 8, pt = (tl >> 2) & 1;
            TR(8, k);
            if (k < 2) TP(44 + k);
            float sc0[28], sc1[28];
            TR(10, k);
            TA(2, 0);
            if (NB & 4) nb_sync<256>(NB_QKRAW + 2 * IT - 1 + wg);
            else mbar_wait_unless(qok, bt + B_QKRAW, pt);
            fence_async_smem();
            TR(11, k);
            TA(2, 1);
            if (k == 0) TP(17);
            wgmma_fence();
            mma_qk0<2 * IT * XCH, 2 * IT * XCH>(sc0, descKw, descKw);
            mma_qk1<2 * IT * XCH, 2 * IT * XCH>(sc1, descKw, descKw);
            wgmma_commit();
            TA(2, 2);
            const uint32_t vok = mbar_test(bt + B_VRAW, pt);
            uint32_t mflag = 1;
            if (!(XP & 1)) asm volatile("ld.volatile.shared.u8 %0, [%1];\n" : "=r"(mflag) : "r"(sbase + SM_FLAG + k) : "memory");
            wgmma_wait<0>();
            reg_fence(sc0);
            reg_fence(sc1);
            if (NB & 1) nb_arrive<160>(NB_QKFREE - 1 + wg);
            else if (lane == 0) mbar_arrive(bar + B_QKFREE);
            TR(12, k);
            TA(2, 3);
            if (k == 0) TP(18);
            if (mflag != 1) {
              asm volatile(
                "{\n.reg .pred p;\n.reg .u32 n;\nmov.u32 n, 0;\n"
                "WAIT_%=:\n"
                "ld.volatile.shared.u8 %0, [%1];\n"
                "setp.ne.u32 p, %0, 0;\n"
                "@p bra DONE_%=;\n"
                "add.u32 n, n, 1;\n"
                "setp.lt.u32 p, n, 16777216;\n"
                "@p bra WAIT_%=;\n"
                "trap;\n"
                "DONE_%=:\n}\n" : "=r"(mflag) : "r"(sbase + SM_FLAG + k) : "memory");
              if (mflag == 2) {
                uint32_t mk[13];
                __threadfence_block();
                uint32_t u = threadIdx.x, bid = blockIdx.x;
                asm volatile("" : "+r"(u), "+r"(bid));
                const uint32_t r0 = ((u >> 1) & 48) + ((u >> 2) & 7);
                const int wi = (bid >> 1) + k * P.npair, wr = wi / NWS;
                const uint32_t mp = sbase + SM_MASK + (((unrot(wr) * NWS + unrot(wi - wr * NWS)) * 2) & 15);
                const uint32_t mr[2] = {mp + row_token(min(r0, TOK - 1u)) * (2 * TOK), mp + row_token(min(r0 + 8, TOK - 1u)) * (2 * TOK)};
                const uint32_t c0 = 2 * row_token(2 * (u & 3));
#pragma unroll
                for (int i = 0; i < 13; i++) {
                    const uint32_t a0 = i < 6 ? mr[i & 1] + c0 + 28 * (i >> 1) : i < 12 ? mr[i & 1] + 2 * row_token(2 * (u & 3) + 8 * (i >> 1)) : mr[0] + 2 * TOK - 2;
                    const uint32_t a1 = i < 6 ? a0 + 2 : i < 12 ? mr[i & 1] + 2 * row_token(2 * (u & 3) + 8 * (i >> 1) + 1) : mr[1] + 2 * TOK - 2;
                    uint32_t lo, hi;
                    asm volatile("ld.shared.u16 %0, [%1];\n" : "=r"(lo) : "r"(a0) : "memory");
                    asm volatile("ld.shared.u16 %0, [%1];\n" : "=r"(hi) : "r"(a1) : "memory");
                    mk[i] = prmt(lo, hi, 0x5410);
                }
                reg_fence(mk);
                __syncwarp();
                if (lane == 0) mbar_arrive(bars + B_MCONS);
                uint32_t m0 = mk[0], m1 = mk[1];
#pragma unroll
                for (int i = 2; i < 12; i += 2) { m0 = hmax2_bf16(m0, mk[i]); m1 = hmax2_bf16(m1, mk[i + 1]); }
                m0 = hmax2_bf16(hmax2_bf16(prmt(m0, m1, 0x5410), prmt(m0, m1, 0x7632)), mk[12]);
                m0 = hmax2_bf16(m0, __shfl_xor_sync(0xffffffffu, m0, 1));
                m0 = hmax2_bf16(m0, __shfl_xor_sync(0xffffffffu, m0, 2));
                const float m[2] = {bf16lo(m0), bf16hi(m0)};
#pragma unroll
                for (int i = 0; i < 13; i++) {
                    const float lo = bf16lo(mk[i]) - m[i & 1], hi = bf16hi(mk[i]) - m[i < 12 ? i & 1 : 1];
                    const int j = i < 12 ? 2 * i + 1 : 26;
                    sc0[2 * i] = fmaf(lo, LOG2E, sc0[2 * i]); sc0[j] = fmaf(hi, LOG2E, sc0[j]);
                    sc1[2 * i] = fmaf(lo, LOG2E, sc1[2 * i]); sc1[j] = fmaf(hi, LOG2E, sc1[j]);
                }
              }
            }
            if (slow) {
                auto shift = [&](float (&S)[28], int h) {
                    float m[2];
#pragma unroll
                    for (int i = 12; i >= 0; i--) {
                        uint32_t e = eb[13 * h + i];
                        asm volatile("" : "+r"(e));
                        const float a = S[2 * i] + lg2_ftz(bf16lo(e)), b = S[i < 12 ? 2 * i + 1 : 26] + lg2_ftz(bf16hi(e));
                        if (i == 12) { m[0] = a; m[1] = b; }
                        else m[i & 1] = fmaxf(m[i & 1], fmaxf(a, b));
                    }
#pragma unroll
                    for (int r = 0; r < 2; r++) {
                        m[r] = fmaxf(m[r], __shfl_xor_sync(0xffffffffu, m[r], 1));
                        m[r] = fmaxf(m[r], __shfl_xor_sync(0xffffffffu, m[r], 2));
                    }
#pragma unroll
                    for (int i = 0; i < 27; i++) S[i] -= m[(i >> 1) & 1];
                };
                uint32_t sl = slow;
                if (SLOWH == 2) asm volatile("ld.volatile.shared.u32 %0, [%1];\n" : "=r"(sl) : "r"(bars + B_PROG + 4) : "memory");
                if (!SLOWH || (sl & 1)) shift(sc0, 0);
                if (!SLOWH || (sl & 2)) shift(sc1, 1);
            }
            auto exps = [&](const float (&S)[28], uint32_t (&e)[13]) {
#pragma unroll
                for (int i = 0; i < 12; i++) e[i] = pack_bf16(ex2_ftz(S[2 * i]), ex2_ftz(S[2 * i + 1]));
                e[12] = hmin2_bf16(pack_bf16(ex2_ftz(S[24]), ex2_ftz(S[26])), 0x7F7F7F7Fu);
            };
            auto probs = [&](const uint32_t (&e)[13], int h, uint32_t (&pa)[4][4]) {
#pragma unroll
                for (int i = 0; i < 12; i++) pa[i >> 2][i & 3] = hmul2_bf16(e[i], eb[13 * h + i]);
                const uint32_t l = hmul2_bf16(e[12], eb[13 * h + 12]);
                pa[3][0] = l & 0xFFFFu;
                pa[3][1] = l >> 16;
                pa[3][2] = 0u; pa[3][3] = 0u;
                reg_fence(pa);
            };
            uint32_t pa0[4][4], pa1[4][4], e[13];
            float o0[28], o1[28];
            TR(13, k);
            TA(2, 10);
            if (k == 0) TP(23);
            exps(sc0, e);
            probs(e, 0, pa0);
            TA(2, 4);
            mbar_wait_unless(vok, bt + B_VRAW, pt);
            fence_async_smem();
            TR(14, k);
            TA(2, 5);
            wgmma_fence();
            mma_pv<2 * IT * V_STRIDE, 0>(o0, pa0, descVw);
            wgmma_commit();
            exps(sc1, e);
            reg_fence(e);
            TA(2, 6);
            wgmma_wait<0>();
            reg_fence(o0);
            TA(2, 7);
            sched_fence_rw(zero, e);
            probs(e, 1, pa1);
            wgmma_fence();
            mma_pv<2 * IT * V_STRIDE + 6 * GRP, 0>(o1, pa1, descVw);
            wgmma_commit();
            uint32_t w[24];
            {
                const float il0 = rcp_ftz(o0[24]), il1 = rcp_ftz(o0[26]);
                const uint32_t l0 = pack_bf16(il0, il0), l1 = pack_bf16(il1, il1);
#pragma unroll
                for (int j = 0; j < 12; j++) w[j] = (FM & 2) ? pack_bf16(o0[2 * j] * ((j & 1) ? il1 : il0), o0[2 * j + 1] * ((j & 1) ? il1 : il0)) : hmul2_bf16(pack_bf16(o0[2 * j], o0[2 * j + 1]), (j & 1) ? l1 : l0);
            }
            TA(2, 8);
            wgmma_wait<0>();
            reg_fence(o1);
            TA(2, 9);
            TR(15, k);
            if (k == 0) TP(25);
            wg_bar(3 + wg);
            if (!(NB & 4)) qok = mbar_test(bars + (tn & 3) * 8 + B_QKRAW, (tn >> 2) & 1);
            {
                const float il2 = rcp_ftz(o1[0]), il3 = rcp_ftz(o1[2]);
                const uint32_t l2 = pack_bf16(il2, il2), l3 = pack_bf16(il3, il3);
#pragma unroll
                for (int j = 0; j < 12; j++) w[12 + j] = (FM & 4) ? pack_bf16(o1[2 * j + 4] * ((j & 1) ? il3 : il2), o1[2 * j + 5] * ((j & 1) ? il3 : il2)) : hmul2_bf16(pack_bf16(o1[2 * j + 4], o1[2 * j + 5]), (j & 1) ? l3 : l2);
#pragma unroll
                for (int p = 0; p < 6; p++) {
                    const int j = 8 * (p >> 1) + (p & 1);
                    sts128_if((p & 1) ? ov1 : ov0, oa + 2 * IT * V_STRIDE + (p & 1) * 8 * O_PITCH + (p >> 1) * 16, w[j], w[j + 2], w[j + 4], w[j + 6]);
                }
            }
            if (NB & 2) nb_arrive<160>(NB_ODONE + 2 * IT - 1 + wg);
            else {
                __syncwarp();
                if (lane == 0) mbar_arrive(bar + B_ODONE);
            }
            TR(16, k);
            TA(2, 11);
            if (k < 2) TP(46 + k);
        };
        for (int k = wg - 1;; k += 4) {
            window(std::integral_constant<int, 0>(), k);
            if (k + 2 >= nwin) break;
            window(std::integral_constant<int, 1>(), k + 2);
            if (k + 4 >= nwin) break;
        }
        TAEND(2);
        (void)zero;
        asm volatile("setmaxnreg.inc.sync.aligned.u32 160;\n");
    }

    TR(27, wg);
    if ((tid & 127) == 0) TC(4 + wg);
    if (attn) {
        __syncwarp();
        if (lane == 0) mbar_arrive(sbase + SM_PBAR + 96);
    }
    if (!attn) {
#pragma unroll
        for (int row = tid >> 2; row < 192; row += 96) {
            uint4 w[6];
            const int pr = row % 96, srow = row - pr + (pr % 24) / 12 * 48 + (pr % 12) / 2 * 8 + pr / 24 * 2 + (pr & 1);
#pragma unroll
            for (int a = 0; a < 6; a++) w[a] = *reinterpret_cast<const uint4*>(P.wo + srow * 192 + 32 * a + 8 * c);
            float s = 0.f;
#pragma unroll
            for (int a = 0; a < 6; a++)
                s += ((bf16lo(w[a].x) + bf16hi(w[a].x)) + (bf16lo(w[a].y) + bf16hi(w[a].y))) +
                     ((bf16lo(w[a].z) + bf16hi(w[a].z)) + (bf16lo(w[a].w) + bf16hi(w[a].w)));
            s += __shfl_xor_sync(0xffffffffu, s, 1);
            s += __shfl_xor_sync(0xffffffffu, s, 2);
            s *= (1.f / 192.f);
            const uint32_t d = sbase + SM_WO + row * 64 + ((c ^ ((row >> 1) & 3)) << 4);
#pragma unroll
            for (int a = 0; a < 6; a++)
                sts128(d + a * 12288, pack_bf16(bf16lo(w[a].x) - s, bf16hi(w[a].x) - s), pack_bf16(bf16lo(w[a].y) - s, bf16hi(w[a].y) - s),
                       pack_bf16(bf16lo(w[a].z) - s, bf16hi(w[a].z) - s), pack_bf16(bf16lo(w[a].w) - s, bf16hi(w[a].w) - s));
        }
        fence_async_smem();
        asm volatile("bar.sync 6, 384;\n" ::: "memory");
        if (tid == 0 && (int)blockIdx.x == 2 * P.npair) {
            asm volatile("cp.async.bulk.global.shared::cta.bulk_group [%0], [%1], 73728;\n" :: "l"(g_wo), "r"(sbase + SM_WO) : "memory");
            asm volatile("cp.async.bulk.commit_group;\n" ::: "memory");
            asm volatile("cp.async.bulk.wait_group 0;\n" ::: "memory");
            asm volatile("fence.proxy.async.global;\n" ::: "memory");
            asm volatile("red.release.gpu.global.add.u32 [%0], 1;\n" :: "l"(g_cnt + NWS) : "memory");
        }
        __syncwarp();
    } else if (P.t1 < TILES) {
        mbar_wait(sbase + SM_BAR + B_WRAW, 1);
    }
    TR(27, 4 + wg);
    if (tid == 0) TC(2);
    {
        PROJ_SCHEDULE
        uint64_t descW = make_desc(sbase + SM_WO, 12288, 512, 2);
        const uint64_t descA = make_desc(sbase + SM_STAGE + wg * STAGE_BYTES, 16, 1024, 1);
        const uint32_t bar = sbase + SM_PBAR + wg * 8;
        const uint32_t yrel = sbase + SM_STAGE + wg * STAGE_BYTES + (warp * 16 + (lane & 15)) * 128 + (((lane & 7) ^ (lane >> 4)) << 4);
        float acc[96];
#pragma unroll
        for (int i = 0; i < 96; i++) acc[i] = 0.f;
        uint32_t it = 0;
        for (int tile = tile0 + wg * tstep; tile < tend; tile += 3 * tstep, it++) {
            descW += P.z1;
            mbar_wait(bar + (it & 1) * 24, (it >> 1) & 1);
            TR(28, it * 3 + wg);
            if (it > 0 || wg > 0) asm volatile("bar.sync %0, 256;\n" :: "r"(8 + wg) : "memory");
            wgmma_fence();
            mma_proj<0, 0>(acc, descA + (uint64_t)((it & 1) * (3 * STAGE_BYTES >> 4)), descW);
            wgmma_commit();
            if (tile + tstep < tend) asm volatile("bar.arrive %0, 256;\n" :: "r"(wg == 2 ? 8 : 9 + wg) : "memory");
            wgmma_wait<0>();
            reg_fence(acc);
            float a[4];
#pragma unroll
            for (int i = 0; i < 4; i++) a[i] = acc[i] * acc[i];
#pragma unroll
            for (int j = 1; j < 24; j++)
#pragma unroll
                for (int i = 0; i < 4; i++) a[i] = fmaf(acc[4 * j + i], acc[4 * j + i], a[i]);
            float s0 = a[0] + a[1], s1 = a[2] + a[3];
            s0 += __shfl_xor_sync(0xffffffffu, s0, 1);
            s1 += __shfl_xor_sync(0xffffffffu, s1, 1);
            s0 += __shfl_xor_sync(0xffffffffu, s0, 2);
            s1 += __shfl_xor_sync(0xffffffffu, s1, 2);
            const float rs0 = rsqrt_ftz(fmaf(s0, 1.f / 192.f, 1e-5f));
            const float rs1 = rsqrt_ftz(fmaf(s1, 1.f / 192.f, 1e-5f));
            const uint32_t ya = yrel + (it & 1) * 3 * STAGE_BYTES;
#pragma unroll
            for (int p = 0; p < 12; p++)
                stsm_x4((ya ^ (32 * (p & 3))) + (p >> 2) * 8192,
                        pack_bf16(acc[8 * p] * rs0, acc[8 * p + 1] * rs0), pack_bf16(acc[8 * p + 2] * rs1, acc[8 * p + 3] * rs1),
                        pack_bf16(acc[8 * p + 4] * rs0, acc[8 * p + 5] * rs0), pack_bf16(acc[8 * p + 6] * rs1, acc[8 * p + 7] * rs1));
            __syncwarp();
            if (lane == 0) mbar_arrive(bar + 104 + (it & 1) * 24);
            TR(29, it * 3 + wg);
        }
    }
}

}

typedef CUresult (*PFN_encodeTiled)(CUtensorMap*, CUtensorMapDataType, cuuint32_t, void*, const cuuint64_t*,
                                    const cuuint64_t*, const cuuint32_t*, const cuuint32_t*, CUtensorMapInterleave,
                                    CUtensorMapSwizzle, CUtensorMapL2promotion, CUtensorMapFloatOOBfill);

extern "C" void kernel_launch(void* const* d_in, const int* in_sizes, int n_in, void* d_out, int out_size) {
    swin::Params P;
    P.x           = (const __nv_bfloat16*)d_in[0];
    P.wqkv        = (const __nv_bfloat16*)d_in[1];
    P.wo          = (const __nv_bfloat16*)d_in[2];
    P.logit_scale = (const __nv_bfloat16*)d_in[3];
    P.cpb_w1      = (const __nv_bfloat16*)d_in[4];
    P.cpb_w2      = (const __nv_bfloat16*)d_in[5];
    P.rel_coords  = (const __nv_bfloat16*)d_in[6];
    P.rel_idx     = (const int*)d_in[7];
    P.mask        = (const __nv_bfloat16*)d_in[8];
    P.out         = (__nv_bfloat16*)d_out;
    P.z1 = 0;
    static PFN_encodeTiled encode = nullptr;
    if (!encode) {
        cudaFuncSetAttribute(swin::swin_window_attn_kernel, cudaFuncAttributeMaxDynamicSharedMemorySize, swin::SM_TOTAL);
        cudaDriverEntryPointQueryResult qr;
        cudaGetDriverEntryPoint("cuTensorMapEncodeTiled", (void**)&encode, cudaEnableDefault, &qr);
    }
    swin::Maps M;
    const cuuint32_t estr[4] = {1, 1, 1, 1};
    auto make = [&](CUtensorMap* m, const void* base, int rank, const cuuint64_t* gdim, const cuuint64_t* gstr,
                    const cuuint32_t* box, CUtensorMapSwizzle swz = CU_TENSOR_MAP_SWIZZLE_128B) {
        CUresult r = encode(m, CU_TENSOR_MAP_DATA_TYPE_BFLOAT16, rank, const_cast<void*>(base), gdim, gstr, box, estr,
               CU_TENSOR_MAP_INTERLEAVE_NONE, swz, CU_TENSOR_MAP_L2_PROMOTION_L2_128B,
               CU_TENSOR_MAP_FLOAT_OOB_FILL_NONE);
        (void)r;
    };
    {
        const cuuint64_t gdim[3] = {192, swin::IMG, swin::IMG}, gstr[2] = {384, swin::IMG * 384};
        const cuuint32_t box[7][3] = {{64, 7, 7}, {64, 4, 7}, {64, 3, 7}, {64, 4, 4}, {64, 4, 3}, {64, 3, 4}, {64, 3, 3}};
        for (int i = 0; i < 7; i++) make(&M.x77 + i, P.x, 3, gdim, gstr, box[i]);
        const cuuint32_t boxp[3] = {192, 7, 7};
        if (PF1) make(&M.x77, P.x, 3, gdim, gstr, boxp, CU_TENSOR_MAP_SWIZZLE_NONE);
    }
    {
        const cuuint64_t gdim[2] = {192, (cuuint64_t)swin::NPIX}, gstr[1] = {384};
        const cuuint32_t box64[2] = {64, 64};
        make(&M.o, d_out, 2, gdim, gstr, box64);
        const cuuint64_t gdimb[2] = {192, (cuuint64_t)swin::SEG_B};
        make(&M.ob, d_out, 2, gdimb, gstr, box64);
    }
    {
        const cuuint64_t gdim[3] = {16, 192, 36}, gstr[2] = {1152, 32};
        const cuuint32_t box[3] = {16, 192, 6};
        make(&M.w, P.wqkv, 3, gdim, gstr, box, CU_TENSOR_MAP_SWIZZLE_32B);
        const cuuint64_t gdim3[3] = {192, 192, 3}, gstr3[2] = {1152, 384};
        const cuuint32_t box64[3] = {64, 64, 2}, box32[3] = {32, 64, 2};
        make(&M.w64, P.wqkv, 3, gdim3, gstr3, box64);
        make(&M.w32, P.wqkv, 3, gdim3, gstr3, box32, CU_TENSOR_MAP_SWIZZLE_64B);
    }
    {
        const cuuint64_t gdim[4] = {96, 2, swin::IMG, swin::IMG}, gstr[3] = {192, 384, swin::IMG * 384};
        const cuuint32_t box[4][4] = {{96, 1, 4, 7}, {96, 1, 3, 7}, {96, 1, 4, 3}, {96, 1, 3, 3}};
        for (int i = 0; i < 4; i++) make(&M.s47 + i, d_out, 4, gdim, gstr, box[i], CU_TENSOR_MAP_SWIZZLE_NONE);
    }
    P.npair = NPAIR; P.need = swin::ROW_DONE; P.nq = swin::NWINDOWS / NPAIR; P.nr = swin::NWINDOWS % NPAIR;
    P.nr2 = 2 * P.nr; P.nt0 = (P.nq * swin::TOK + 63) / 64; P.nt1 = ((P.nq + 1) * swin::TOK + 63) / 64;
    P.t1 = swin::TILES - NTAIL;
    swin::swin_window_attn_kernel<<<132, swin::NTHREADS, swin::SM_TOTAL>>>(P, M);
}
```

```cpp
#include <cuda_runtime.h>
#include <cuda.h>
#include <cuda_bf16.h>
#include <stdint.h>
#include <type_traits>

namespace swin {
#define STR_(x) #x
#define STR(x) STR_(x)
#define HINT ""

#define NPAIR 53
#define PF_DIST 3
#define QSPLIT 4
#define CLUSTER 0
#define NOPF 0
#define NTAIL 345
#define PSTORE 1
#define PORDER 1
#define GORD 0
#define GF1 1
#define MERGEW 1
#define MWAIT 0
#define PSLEEP 200
#define CH 5
#define NB 1
#define SCM 0
#define MPF 2
#define MLEAD 4
#define PFM 0
#define PFK 4
#define XP 0
#define KLO 6
#define VPOS 1
#define XSPLIT 1
#define SEQ 1
#define PREL 0
#define PEXP 0
#define PFD 0
#define PFW 0
#define WVK -4
#define WSEQ 1
#define PF1 1
#define WFIRST 1
#define MPRE 1
#define SLOWH 2
#define LS_FAST 4.f
#define ENDR 1
#define EBZ 1
#define HSQ 0
#define AFENCE 0
#define FM 0
#define QPOST 0
#define EARLYQ 0
#define KL 4
#define VB1 4
#define VA0 1
#define K1 3
#define Q1 2
#define RWF 3
#define PUBM 2
#define NH 12
#define HW 29
#define HDEL 0
#define CONSTQ 1
#define V64 1
#define M01 2
#define PPAR 1
#define EPF 0
#define EPW 1
#define HS 0
#define MP2 0
#define PBE 70
#define WFEN 1
#define REG_G 224
#define REG_A 128
#define REG_H 32
constexpr int IMG      = 511;
constexpr int NWS      = 73;
constexpr int NWINDOWS = NWS * NWS;
constexpr int TOK      = 49;
constexpr int NPIX     = IMG * IMG;
constexpr int NTHREADS = 512;

constexpr int W_ATOM = 6144;
constexpr int SM_WA = 0, SM_WB = 6 * 2048, SM_WV = 12 * W_ATOM, D_WV = SM_WV + ((W_ATOM - 2048) << 16);
constexpr int GRP   = TOK * 16;
constexpr int XCH   = TOK * 128;
constexpr int SM_V  = 18 * W_ATOM, V_STRIDE = 10240, O_PITCH = 192;
constexpr int SM_QK = SM_V + 4 * V_STRIDE, QK_CHUNK = 4 * XCH;
constexpr int SM_MASK = SM_QK + 3 * QK_CHUNK;
constexpr int SM_TAB  = SM_V + 3 * V_STRIDE + 256;
constexpr int SM_BAR  = SM_MASK + 4816;
constexpr int B_XFULL = 0, B_WRAW = 32, B_QKRAW = 64, B_QKFREE = 96, B_VFREE = 128, B_ODONE = 160,
              B_PROG = 192, B_VRAW = 224, B_MFULL = 256, B_MCONS = 272, B_WFULL = 280, B_STORED = 288, B_PUBD = 304;
constexpr int SM_FLAG = SM_BAR + 320;
constexpr int SM_A_END = SM_FLAG + 128;
static_assert(SM_QK % 1024 == 0 && 13 * GRP <= V_STRIDE && V_STRIDE % 128 == 0, "layout");
constexpr int SM_WO    = 0;
constexpr int SM_STAGE = 73728;
constexpr int STAGE_BYTES = 24576;
constexpr int SM_PBAR  = SM_A_END;
#define TA(role, idx)
#define TAEND(role)
constexpr int SM_TOTAL = SM_PBAR + 152;
#define TP(idx)
static_assert(SM_STAGE + 6 * STAGE_BYTES <= SM_BAR, "smem");
static_assert(SM_TOTAL <= 232448, "smem");
static_assert(SM_BAR % 8 == 0 && NWINDOWS / NPAIR < 127, "barrier alignment, flags");

constexpr int SEG_B   = (IMG - 4) * IMG;
constexpr int TILES_A = (NPIX - SEG_B + 63) / 64;
constexpr int TILES   = TILES_A + (SEG_B + 63) / 64;
constexpr uint32_t ROW_DONE = NWS * 2;

__device__ uint32_t g_cnt[NWS + 7];
__device__ __align__(128) uint8_t g_wo[73728];
__device__ uint32_t g_flag[66 * 128];
__device__ uint32_t g_done;

#define TR(ev, idx)
#define TC(slot)
#define TS(i)
#define TRH(ev, idx)
constexpr float LOG2E = 1.4426950408889634f;

__device__ __forceinline__ uint32_t smem_u32(const void* p) {
    return (uint32_t)__cvta_generic_to_shared(p);
}
__device__ __forceinline__ uint64_t make_desc(uint32_t saddr, uint32_t lbo, uint32_t sbo, uint32_t swz = 0) {
    return (uint64_t)((saddr & 0x3FFFF) >> 4) | ((uint64_t)(lbo >> 4) << 16) | ((uint64_t)(sbo >> 4) << 32) |
           ((uint64_t)swz << 62);
}
__host__ __device__ constexpr uint64_t make_desc_c(uint32_t saddr, uint32_t lbo, uint32_t sbo, uint32_t swz) {
    return (uint64_t)(saddr >> 4) | ((uint64_t)(lbo >> 4) << 16) | ((uint64_t)(sbo >> 4) << 32) | ((uint64_t)swz << 62);
}
constexpr uint64_t D_WV64 = make_desc_c(SM_WV, 12288, 512, 2) - make_desc_c(0, 2048, 256, 3);
__device__ __forceinline__ void wgmma_fence()  { asm volatile("wgmma.fence.sync.aligned;\n" ::: "memory"); }
__device__ __forceinline__ void wgmma_commit() { asm volatile("wgmma.commit_group.sync.aligned;\n" ::: "memory"); }
template <int N> __device__ __forceinline__ void wgmma_wait() {
    asm volatile("wgmma.wait_group.sync.aligned %0;\n" :: "n"(N) : "memory");
}
__device__ __forceinline__ void fence_async_smem() { asm volatile("fence.proxy.async.shared::cta;\n" ::: "memory"); }
template <int N> __device__ __forceinline__ void nb_sync(int id) { asm volatile("bar.sync %0, %1;\n" :: "r"(id), "n"(N) : "memory"); }
template <int N> __device__ __forceinline__ void nb_arrive(int id) { asm volatile("bar.arrive %0, %1;\n" :: "r"(id), "n"(N) : "memory"); }
constexpr int NB_ODONE = 0, NB_QKFREE = 6, NB_QKRAW = 12;
__device__ __forceinline__ void wg_bar(int id) { asm volatile("bar.sync %0, 128;\n" :: "r"(id) : "memory"); }

template <int N> __device__ __forceinline__ void reg_fence(float (&v)[N]) {
#pragma unroll
    for (int i = 0; i < N; i++) asm volatile("" : "+f"(v[i]) :: "memory");
}
template <int N> __device__ __forceinline__ void reg_fence(uint32_t (&v)[N]) {
#pragma unroll
    for (int i = 0; i < N; i++) asm volatile("" : "+r"(v[i]) :: "memory");
}
template <int N, int M> __device__ __forceinline__ void reg_fence(uint32_t (&v)[N][M]) {
#pragma unroll
    for (int i = 0; i < N; i++) reg_fence(v[i]);
}

__device__ __forceinline__ uint32_t pack_bf16(float lo, float hi) {
    uint32_t r;
    asm("cvt.rn.bf16x2.f32 %0, %1, %2;\n" : "=r"(r) : "f"(hi), "f"(lo));
    return r;
}
__device__ __forceinline__ float bf16lo(uint32_t v) { return __uint_as_float(v << 16); }
__device__ __forceinline__ float bf16hi(uint32_t v) { return __uint_as_float(v & 0xFFFF0000u); }
__device__ __forceinline__ uint32_t hadd2_bf16(uint32_t a, uint32_t b) {
    uint32_t r;
    asm("add.rn.bf16x2 %0, %1, %2;\n" : "=r"(r) : "r"(a), "r"(b));
    return r;
}
__device__ __forceinline__ uint32_t hmul2_bf16(uint32_t a, uint32_t b) {
    uint32_t r;
    asm("mul.rn.bf16x2 %0, %1, %2;\n" : "=r"(r) : "r"(a), "r"(b));
    return r;
}
__device__ __forceinline__ uint32_t hsub2_bf16(uint32_t a, uint32_t b) {
    uint32_t r;
    asm("sub.rn.bf16x2 %0, %1, %2;\n" : "=r"(r) : "r"(a), "r"(b));
    return r;
}
__device__ __forceinline__ uint32_t hfma2_bf16(uint32_t a, uint32_t b, uint32_t c) {
    uint32_t r;
    asm("fma.rn.bf16x2 %0, %1, %2, %3;\n" : "=r"(r) : "r"(a), "r"(b), "r"(c));
    return r;
}
__device__ __forceinline__ uint32_t hmax2_bf16(uint32_t a, uint32_t b) {
    uint32_t r;
    asm("max.bf16x2 %0, %1, %2;\n" : "=r"(r) : "r"(a), "r"(b));
    return r;
}
__device__ __forceinline__ uint32_t hmin2_bf16(uint32_t a, uint32_t b) {
    uint32_t r;
    asm("min.bf16x2 %0, %1, %2;\n" : "=r"(r) : "r"(a), "r"(b));
    return r;
}
__device__ __forceinline__ uint32_t ex2_bf16x2(uint32_t a) {
    uint32_t r;
    asm("ex2.approx.ftz.bf16x2 %0, %1;\n" : "=r"(r) : "r"(a));
    return r;
}
__device__ __forceinline__ uint32_t ex2_bf16lo(uint32_t a) {
    uint32_t r;
    asm("{\n.reg .b16 l, h;\nmov.b32 {l, h}, %1;\nex2.approx.ftz.bf16 l, l;\ncvt.u32.u16 %0, l;\n}\n" : "=r"(r) : "r"(a));
    return r;
}
__device__ __forceinline__ uint32_t mbar_test(uint32_t bar, uint32_t parity) {
    uint32_t ok;
    asm volatile("{\n.reg .pred p;\nmbarrier.test_wait.parity.shared::cta.b64 p, [%1], %2;\nselp.u32 %0, 1, 0, p;\n}\n"
                 : "=r"(ok) : "r"(bar), "r"(parity) : "memory");
    return ok;
}
__device__ __forceinline__ uint32_t prmt(uint32_t a, uint32_t b, uint32_t sel) {
    uint32_t r;
    asm("prmt.b32 %0, %1, %2, %3;\n" : "=r"(r) : "r"(a), "r"(b), "r"(sel));
    return r;
}
__device__ __forceinline__ float round_bf16(float x) { return __bfloat162float(__float2bfloat16_rn(x)); }

__device__ __forceinline__ void mbar_init(uint32_t bar, uint32_t count) {
    asm volatile("mbarrier.init.shared::cta.b64 [%0], %1;\n" :: "r"(bar), "r"(count) : "memory");
}
__device__ __forceinline__ void mbar_wait(uint32_t bar, uint32_t parity) {
    asm volatile(
        "{\n"
        ".reg .pred p;\n"
        ".reg .u32 n;\n"
        "mov.u32 n, 0;\n"
        "WAIT_%=:\n"
        "mbarrier.try_wait.parity.shared::cta.b64 p, [%0], %1" HINT ";\n"
        "@p bra DONE_%=;\n"
        "add.u32 n, n, 1;\n"
        "setp.lt.u32 p, n, 4194304;\n"
        "@p bra WAIT_%=;\n"
        "trap;\n"
        "DONE_%=:\n"
        "}\n" :: "r"(bar), "r"(parity) : "memory");
}
template <bool S> __device__ __forceinline__ void mbar_wait_s(uint32_t bar, uint32_t parity) {
    if (!S) mbar_wait(bar, parity);
    else asm volatile(
        "{\n"
        ".reg .pred p;\n"
        ".reg .u32 n;\n"
        "mov.u32 n, 0;\n"
        "WAIT_%=:\n"
        "mbarrier.try_wait.parity.shared::cta.b64 p, [%0], %1, 4000;\n"
        "@p bra DONE_%=;\n"
        "add.u32 n, n, 1;\n"
        "setp.lt.u32 p, n, 262144;\n"
        "@p bra WAIT_%=;\n"
        "trap;\n"
        "DONE_%=:\n"
        "}\n" :: "r"(bar), "r"(parity) : "memory");
}
__device__ __forceinline__ void mbar_wait4(uint32_t b0, uint32_t p0, uint32_t b1, uint32_t p1, uint32_t b2, uint32_t p2,
                                           uint32_t b3, uint32_t p3) {
    asm volatile(
        "{\n"
        ".reg .pred p, q, r, s;\n"
        ".reg .u32 n;\n"
        "mov.u32 n, 0;\n"
        "WAIT_%=:\n"
        "mbarrier.try_wait.parity.shared::cta.b64 p, [%0], %1" HINT ";\n"
        "mbarrier.try_wait.parity.shared::cta.b64 q, [%2], %3" HINT ";\n"
        "mbarrier.try_wait.parity.shared::cta.b64 r, [%4], %5" HINT ";\n"
        "mbarrier.try_wait.parity.shared::cta.b64 s, [%6], %7" HINT ";\n"
        "and.pred p, p, q;\n"
        "and.pred r, r, s;\n"
        "and.pred p, p, r;\n"
        "@p bra DONE_%=;\n"
        "add.u32 n, n, 1;\n"
        "setp.lt.u32 p, n, 4194304;\n"
        "@p bra WAIT_%=;\n"
        "trap;\n"
        "DONE_%=:\n"
        "}\n" :: "r"(b0), "r"(p0), "r"(b1), "r"(p1), "r"(b2), "r"(p2), "r"(b3), "r"(p3) : "memory");
}
__device__ __forceinline__ void mbar_wait2(uint32_t b0, uint32_t p0, uint32_t b1, uint32_t p1) {
    asm volatile(
        "{\n"
        ".reg .pred p, q;\n"
        ".reg .u32 n;\n"
        "mov.u32 n, 0;\n"
        "WAIT_%=:\n"
        "mbarrier.try_wait.parity.shared::cta.b64 p, [%0], %1" HINT ";\n"
        "mbarrier.try_wait.parity.shared::cta.b64 q, [%2], %3" HINT ";\n"
        "and.pred p, p, q;\n"
        "@p bra DONE_%=;\n"
        "add.u32 n, n, 1;\n"
        "setp.lt.u32 p, n, 4194304;\n"
        "@p bra WAIT_%=;\n"
        "trap;\n"
        "DONE_%=:\n"
        "}\n" :: "r"(b0), "r"(p0), "r"(b1), "r"(p1) : "memory");
}
#define HINTA ""
__device__ __forceinline__ void mbar_wait_unless(uint32_t ok, uint32_t bar, uint32_t parity) {
    asm volatile(
        "{\n"
        ".reg .pred p;\n"
        ".reg .u32 n;\n"
        "setp.ne.u32 p, %2, 0;\n"
        "vote.sync.all.pred p, p, 0xffffffff;\n"
        "@p bra DONE_%=;\n"
        "mov.u32 n, 0;\n"
        "WAIT_%=:\n"
        "mbarrier.try_wait.parity.shared::cta.b64 p, [%0], %1" HINTA ";\n"
        "@p bra DONE_%=;\n"
        "add.u32 n, n, 1;\n"
        "setp.lt.u32 p, n, 4194304;\n"
        "@p bra WAIT_%=;\n"
        "trap;\n"
        "DONE_%=:\n"
        "}\n" :: "r"(bar), "r"(parity), "r"(ok) : "memory");
}
__device__ __forceinline__ void mbar_wait2_unless(uint32_t ok, uint32_t b0, uint32_t p0, uint32_t b1, uint32_t p1) {
    asm volatile(
        "{\n"
        ".reg .pred p, q;\n"
        ".reg .u32 n;\n"
        "setp.ne.u32 p, %4, 0;\n"
        "vote.sync.all.pred p, p, 0xffffffff;\n"
        "@p bra DONE_%=;\n"
        "mov.u32 n, 0;\n"
        "WAIT_%=:\n"
        "mbarrier.try_wait.parity.shared::cta.b64 p, [%0], %1" HINT ";\n"
        "mbarrier.try_wait.parity.shared::cta.b64 q, [%2], %3" HINT ";\n"
        "and.pred p, p, q;\n"
        "@p bra DONE_%=;\n"
        "add.u32 n, n, 1;\n"
        "setp.lt.u32 p, n, 4194304;\n"
        "@p bra WAIT_%=;\n"
        "trap;\n"
        "DONE_%=:\n"
        "}\n" :: "r"(b0), "r"(p0), "r"(b1), "r"(p1), "r"(ok) : "memory");
}
__device__ __forceinline__ void mbar_wait4_unless(uint32_t ok, uint32_t b0, uint32_t p0, uint32_t b1, uint32_t p1, uint32_t b2,
                                                  uint32_t p2, uint32_t b3, uint32_t p3) {
    asm volatile(
        "{\n"
        ".reg .pred p, q, r, s;\n"
        ".reg .u32 n;\n"
        "setp.ne.u32 p, %8, 0;\n"
        "vote.sync.all.pred p, p, 0xffffffff;\n"
        "@p bra DONE_%=;\n"
        "mov.u32 n, 0;\n"
        "WAIT_%=:\n"
        "mbarrier.try_wait.parity.shared::cta.b64 p, [%0], %1" HINT ";\n"
        "mbarrier.try_wait.parity.shared::cta.b64 q, [%2], %3" HINT ";\n"
        "mbarrier.try_wait.parity.shared::cta.b64 r, [%4], %5" HINT ";\n"
        "mbarrier.try_wait.parity.shared::cta.b64 s, [%6], %7" HINT ";\n"
        "and.pred p, p, q;\n"
        "and.pred r, r, s;\n"
        "and.pred p, p, r;\n"
        "@p bra DONE_%=;\n"
        "add.u32 n, n, 1;\n"
        "setp.lt.u32 p, n, 4194304;\n"
        "@p bra WAIT_%=;\n"
        "trap;\n"
        "DONE_%=:\n"
        "}\n" :: "r"(b0), "r"(p0), "r"(b1), "r"(p1), "r"(b2), "r"(p2), "r"(b3), "r"(p3), "r"(ok) : "memory");
}
__device__ __forceinline__ void sched_fence(uint32_t zero, uint32_t a, uint32_t b, uint32_t c, uint32_t d, uint32_t e = 0,
                                            uint32_t f = 0, uint32_t g = 0, uint32_t h = 0, uint32_t i = 0, uint32_t j = 0,
                                            uint32_t k = 0) {
    asm volatile("{\n.reg .pred p;\n.reg .u32 n;\nsetp.eq.u32 p, %0, 0;\n@p bra.uni DONE_%=;\nmov.u32 n, %0;\nSPIN_%=:\n"
                 "nanosleep.u32 %1;\nnanosleep.u32 %2;\nnanosleep.u32 %3;\nnanosleep.u32 %4;\nnanosleep.u32 %5;\n"
                 "nanosleep.u32 %6;\nnanosleep.u32 %7;\nnanosleep.u32 %8;\nnanosleep.u32 %9;\nnanosleep.u32 %10;\n"
                 "nanosleep.u32 %11;\nsub.u32 n, n, 1;\nsetp.ne.u32 p, n, 0;\n@p bra.uni SPIN_%=;\nDONE_%=:\n}\n"
                 :: "r"(zero), "r"(a), "r"(b), "r"(c), "r"(d), "r"(e), "r"(f), "r"(g), "r"(h), "r"(i), "r"(j), "r"(k) : "memory");
}
__device__ __forceinline__ void sched_fence2(uint32_t zero, float& x, float& y, uint32_t a, uint32_t b, uint32_t c, uint32_t d = 0,
                                             uint32_t e = 0, uint32_t f = 0) {
    asm volatile("{\n.reg .pred p;\n.reg .u32 n;\nsetp.eq.u32 p, %2, 0;\n@p bra.uni DONE_%=;\nmov.u32 n, %2;\nSPIN_%=:\n"
                 "add.f32 %0, %0, %1;\nadd.f32 %1, %1, %0;\nnanosleep.u32 %3;\nnanosleep.u32 %4;\nnanosleep.u32 %5;\n"
                 "nanosleep.u32 %6;\nnanosleep.u32 %7;\nnanosleep.u32 %8;\n"
                 "sub.u32 n, n, 1;\nsetp.ne.u32 p, n, 0;\n@p bra.uni SPIN_%=;\nDONE_%=:\n}\n"
                 : "+f"(x), "+f"(y) : "r"(zero), "r"(a), "r"(b), "r"(c), "r"(d), "r"(e), "r"(f) : "memory");
}
template <int N> __device__ __forceinline__ void use_regs(const uint32_t* v) {
    if constexpr (N >= 4) {
        asm volatile("nanosleep.u32 %0;\nnanosleep.u32 %1;\nnanosleep.u32 %2;\nnanosleep.u32 %3;\n" :: "r"(v[0]), "r"(v[1]), "r"(v[2]), "r"(v[3]) : "memory");
        use_regs<N - 4>(v + 4);
    } else if constexpr (N > 0) {
        asm volatile("nanosleep.u32 %0;\n" :: "r"(v[0]) : "memory");
        use_regs<N - 1>(v + 1);
    }
}
template <int N> __device__ __forceinline__ void sched_fence_n(uint32_t zero, const uint32_t (&v)[N]) {
    if (__builtin_expect(zero != 0, 0)) {
#pragma unroll 1
        for (uint32_t n = zero; n; n--) use_regs<N>(v);
    }
}
__device__ __forceinline__ void sched_fence_rw(uint32_t zero, uint32_t (&v)[13]) {
    asm volatile("{\n.reg .pred p;\n.reg .u32 n;\nsetp.eq.u32 p, %13, 0;\n@p bra.uni DONE_%=;\nmov.u32 n, %13;\nSPIN_%=:\n"
                 "add.u32 %0, %0, %1;\nadd.u32 %1, %1, %2;\nadd.u32 %2, %2, %3;\nadd.u32 %3, %3, %4;\nadd.u32 %4, %4, %5;\n"
                 "add.u32 %5, %5, %6;\nadd.u32 %6, %6, %7;\nadd.u32 %7, %7, %8;\nadd.u32 %8, %8, %9;\nadd.u32 %9, %9, %10;\n"
                 "add.u32 %10, %10, %11;\nadd.u32 %11, %11, %12;\nadd.u32 %12, %12, %0;\n"
                 "sub.u32 n, n, 1;\nsetp.ne.u32 p, n, 0;\n@p bra.uni SPIN_%=;\nDONE_%=:\n}\n"
                 : "+r"(v[0]), "+r"(v[1]), "+r"(v[2]), "+r"(v[3]), "+r"(v[4]), "+r"(v[5]), "+r"(v[6]), "+r"(v[7]), "+r"(v[8]),
                   "+r"(v[9]), "+r"(v[10]), "+r"(v[11]), "+r"(v[12]) : "r"(zero) : "memory");
}
__device__ __forceinline__ void mbar_arrive(uint32_t bar) {
    asm volatile("mbarrier.arrive.shared::cta.b64 _, [%0];\n" :: "r"(bar) : "memory");
}
__device__ __forceinline__ void mbar_arrive_n(uint32_t bar, uint32_t n) {
    asm volatile("mbarrier.arrive.shared::cta.b64 _, [%0], %1;\n" :: "r"(bar), "r"(n) : "memory");
}
__device__ __forceinline__ void mbar_arrive_expect_tx(uint32_t bar, uint32_t bytes) {
    asm volatile("mbarrier.arrive.expect_tx.shared::cta.b64 _, [%0], %1;\n" :: "r"(bar), "r"(bytes) : "memory");
}
__device__ __forceinline__ void stg128_if(bool p, void* addr, uint32_t x, uint32_t y, uint32_t z, uint32_t w) {
    asm volatile("{\n.reg .pred q;\nsetp.ne.b32 q, %5, 0;\n@q st.global.L1::no_allocate.v4.b32 [%0], {%1, %2, %3, %4};\n}\n"
                 :: "l"(addr), "r"(x), "r"(y), "r"(z), "r"(w), "r"((uint32_t)p) : "memory");
}
__device__ __forceinline__ void stsm_x4(uint32_t addr, uint32_t r0, uint32_t r1, uint32_t r2, uint32_t r3) {
    asm volatile("stmatrix.sync.aligned.m8n8.x4.shared.b16 [%0], {%1, %2, %3, %4};\n"
                 :: "r"(addr), "r"(r0), "r"(r1), "r"(r2), "r"(r3) : "memory");
}
__device__ __forceinline__ void stsm_x2(uint32_t addr, uint32_t r0, uint32_t r1) {
    asm volatile("stmatrix.sync.aligned.m8n8.x2.shared.b16 [%0], {%1, %2};\n" :: "r"(addr), "r"(r0), "r"(r1) : "memory");
}
__device__ __forceinline__ void sts128(uint32_t addr, uint32_t r0, uint32_t r1, uint32_t r2, uint32_t r3) {
    asm volatile("st.shared.v4.b32 [%0], {%1, %2, %3, %4};\n" :: "r"(addr), "r"(r0), "r"(r1), "r"(r2), "r"(r3) : "memory");
}
__device__ __forceinline__ void sts128_if(uint32_t p, uint32_t addr, uint32_t r0, uint32_t r1, uint32_t r2, uint32_t r3) {
    asm volatile("{\n.reg .pred q;\nsetp.ne.b32 q, %5, 0;\n@q st.shared.v4.b32 [%0], {%1, %2, %3, %4};\n}\n"
                 :: "r"(addr), "r"(r0), "r"(r1), "r"(r2), "r"(r3), "r"(p) : "memory");
}
__device__ __forceinline__ void sts32(uint32_t addr, uint32_t v) {
    asm volatile("st.shared.b32 [%0], %1;\n" :: "r"(addr), "r"(v) : "memory");
}
__device__ __forceinline__ uint32_t lds32(uint32_t addr) {
    uint32_t v;
    asm volatile("ld.shared.b32 %0, [%1];\n" : "=r"(v) : "r"(addr) : "memory");
    return v;
}
__device__ __forceinline__ void ldg_nc_v4(uint32_t (&r)[4], const void* p) {
    asm volatile("ld.global.nc.L1::no_allocate.v4.u32 {%0, %1, %2, %3}, [%4];\n"
                 : "=r"(r[0]), "=r"(r[1]), "=r"(r[2]), "=r"(r[3]) : "l"(p));
}
__device__ __forceinline__ uint32_t ldg_u32(const void* p) {
    uint32_t v;
    asm volatile("ld.global.nc.L1::evict_first.u32 %0, [%1];\n" : "=r"(v) : "l"(p));
    return v;
}
__device__ __forceinline__ void ldg_u64(const void* p, uint32_t& a, uint32_t& b) {
    asm volatile("ld.global.nc.L1::evict_first.v2.u32 {%0, %1}, [%2];\n" : "=r"(a), "=r"(b) : "l"(p));
}
__device__ __forceinline__ void prefetch_l2(const void* p) {
    asm volatile("prefetch.global.L2 [%0];\n" :: "l"(p));
}
__device__ __forceinline__ void cp_async16(uint32_t dst, const void* src) {
    asm volatile("cp.async.cg.shared.global [%0], [%1], 16;\n" :: "r"(dst), "l"(src) : "memory");
}
__device__ __forceinline__ float ex2_ftz(float x) {
    float y;
    asm("ex2.approx.ftz.f32 %0, %1;\n" : "=f"(y) : "f"(x));
    return y;
}
__device__ __forceinline__ float lg2_ftz(float x) {
    float y;
    asm("lg2.approx.ftz.f32 %0, %1;\n" : "=f"(y) : "f"(x));
    return y;
}
__device__ __forceinline__ float rcp_ftz(float x) {
    float y;
    asm("rcp.approx.ftz.f32 %0, %1;\n" : "=f"(y) : "f"(x));
    return y;
}
__device__ __forceinline__ float rsqrt_ftz(float x) {
    float y;
    asm("rsqrt.approx.ftz.f32 %0, %1;\n" : "=f"(y) : "f"(x));
    return y;
}

__device__ __forceinline__ bool elect_one() {
    uint32_t p;
    asm volatile("{\n.reg .pred q;\nelect.sync _|q, 0xffffffff;\nselp.u32 %0, 1, 0, q;\n}\n" : "=r"(p));
    return p != 0;
}
__device__ __forceinline__ void ldsm_x4(uint32_t (&r)[4], uint32_t addr) {
    asm volatile("ldmatrix.sync.aligned.m8n8.x4.shared.b16 {%0, %1, %2, %3}, [%4];\n"
                 : "=r"(r[0]), "=r"(r[1]), "=r"(r[2]), "=r"(r[3]) : "r"(addr) : "memory");
}
__device__ __forceinline__ void ldsm_x2(uint32_t& r0, uint32_t& r1, uint32_t addr) {
    asm volatile("ldmatrix.sync.aligned.m8n8.x2.shared.b16 {%0, %1}, [%2];\n" : "=r"(r0), "=r"(r1) : "r"(addr) : "memory");
}
__device__ __forceinline__ void tma_2d(uint32_t dst, const CUtensorMap* map, uint32_t bar, int c0, int c1) {
    asm volatile("cp.async.bulk.tensor.2d.shared::cluster.global.mbarrier::complete_tx::bytes [%0], [%1, {%3, %4}], [%2];\n"
                 :: "r"(dst), "l"(reinterpret_cast<uint64_t>(map)), "r"(bar), "r"(c0), "r"(c1) : "memory");
}
__device__ __forceinline__ void tma_3d(uint32_t dst, const CUtensorMap* map, uint32_t bar, int c0, int c1, int c2) {
    asm volatile("cp.async.bulk.tensor.3d.shared::cluster.global.mbarrier::complete_tx::bytes [%0], [%1, {%3, %4, %5}], [%2];\n"
                 :: "r"(dst), "l"(reinterpret_cast<uint64_t>(map)), "r"(bar), "r"(c0), "r"(c1), "r"(c2) : "memory");
}
constexpr uint64_t EVICT_FIRST = 0x12F0000000000000ull;
__device__ __forceinline__ void tma_3d_x(uint32_t dst, const CUtensorMap* map, uint32_t bar, int c0, int c1, int c2) {
    if (CH & 50)
        asm volatile("cp.async.bulk.tensor.3d.shared::cluster.global.mbarrier::complete_tx::bytes.L2::cache_hint [%0], [%1, {%3, %4, %5}], [%2], %6;\n"
                     :: "r"(dst), "l"(reinterpret_cast<uint64_t>(map)), "r"(bar), "r"(c0), "r"(c1), "r"(c2),
                        "l"((CH & 2) || (blockIdx.x & 1) == ((CH >> 5) & 1) ? EVICT_FIRST : 0x1000000000000000ull) : "memory");
    else tma_3d(dst, map, bar, c0, c1, c2);
}
__device__ __forceinline__ void tma_store_4d(const CUtensorMap* map, uint32_t src, int c0, int c1, int c2, int c3) {
    asm volatile("cp.async.bulk.tensor.4d.global.shared::cta.tile.bulk_group [%0, {%2, %3, %4, %5}], [%1];\n"
                 :: "l"(reinterpret_cast<uint64_t>(map)), "r"(src), "r"(c0), "r"(c1), "r"(c2), "r"(c3) : "memory");
}
__device__ __forceinline__ void mbar_arrive_if(uint32_t bar, uint32_t cnt) {
    asm volatile("{\n.reg .pred q;\nsetp.ne.b32 q, %1, 0;\n@q mbarrier.arrive.shared::cta.b64 _, [%0], %1;\n}\n"
                 :: "r"(bar), "r"(cnt) : "memory");
}

template <int BOFF, int AOFF, int NA>
__device__ __forceinline__ void mma_qkv_a(float (&d)[48], const uint32_t (&a)[NA][4], uint64_t descB) {
    asm volatile(
        "{\n"
        ".reg .pred p0, p1;\n"
        ".reg .b64 ta, ta0, tb, tb0;\n"
        "setp.ne.b32 p0, 0, 0;\n"
        "setp.eq.b32 p1, 0, 0;\n"
        "add.s64 tb0, %72, %73;\n"
        "add.s64 tb, tb0, 0;\n"
        "wgmma.mma_async.sync.aligned.m64n96k16.f32.bf16.bf16 {%0, %1, %2, %3, %4, %5, %6, %7, %8, %9, %10, %11, %12, %13, %14, %15, %16, %17, %18, %19, %20, %21, %22, %23, %24, %25, %26, %27, %28, %29, %30, %31, %32, %33, %34, %35, %36, %37, %38, %39, %40, %41, %42, %43, %44, %45, %46, %47}, {%48, %49, %50, %51}, tb, p0, 1, 1, 1;\n"
        "add.s64 tb, tb0, 32;\n"
        "wgmma.mma_async.sync.aligned.m64n96k16.f32.bf16.bf16 {%0, %1, %2, %3, %4, %5, %6, %7, %8, %9, %10, %11, %12, %13, %14, %15, %16, %17, %18, %19, %20, %21, %22, %23, %24, %25, %26, %27, %28, %29, %30, %31, %32, %33, %34, %35, %36, %37, %38, %39, %40, %41, %42, %43, %44, %45, %46, %47}, {%52, %53, %54, %55}, tb, p1, 1, 1, 1;\n"
        "add.s64 tb, tb0, 64;\n"
        "wgmma.mma_async.sync.aligned.m64n96k16.f32.bf16.bf16 {%0, %1, %2, %3, %4, %5, %6, %7, %8, %9, %10, %11, %12, %13, %14, %15, %16, %17, %18, %19, %20, %21, %22, %23, %24, %25, %26, %27, %28, %29, %30, %31, %32, %33, %34, %35, %36, %37, %38, %39, %40, %41, %42, %43, %44, %45, %46, %47}, {%56, %57, %58, %59}, tb, p1, 1, 1, 1;\n"
        "add.s64 tb, tb0, 96;\n"
        "wgmma.mma_async.sync.aligned.m64n96k16.f32.bf16.bf16 {%0, %1, %2, %3, %4, %5, %6, %7, %8, %9, %10, %11, %12, %13, %14, %15, %16, %17, %18, %19, %20, %21, %22, %23, %24, %25, %26, %27, %28, %29, %30, %31, %32, %33, %34, %35, %36, %37, %38, %39, %40, %41, %42, %43, %44, %45, %46, %47}, {%60, %61, %62, %63}, tb, p1, 1, 1, 1;\n"
        "add.s64 tb, tb0, 1536;\n"
        "wgmma.mma_async.sync.aligned.m64n96k16.f32.bf16.bf16 {%0, %1, %2, %3, %4, %5, %6, %7, %8, %9, %10, %11, %12, %13, %14, %15, %16, %17, %18, %19, %20, %21, %22, %23, %24, %25, %26, %27, %28, %29, %30, %31, %32, %33, %34, %35, %36, %37, %38, %39, %40, %41, %42, %43, %44, %45, %46, %47}, {%64, %65, %66, %67}, tb, p1, 1, 1, 1;\n"
        "add.s64 tb, tb0, 1568;\n"
        "wgmma.mma_async.sync.aligned.m64n96k16.f32.bf16.bf16 {%0, %1, %2, %3, %4, %5, %6, %7, %8, %9, %10, %11, %12, %13, %14, %15, %16, %17, %18, %19, %20, %21, %22, %23, %24, %25, %26, %27, %28, %29, %30, %31, %32, %33, %34, %35, %36, %37, %38, %39, %40, %41, %42, %43, %44, %45, %46, %47}, {%68, %69, %70, %71}, tb, p1, 1, 1, 1;\n"
        "}\n"
        : "=f"(d[0]), "=f"(d[1]), "=f"(d[2]), "=f"(d[3]), "=f"(d[4]), "=f"(d[5]), "=f"(d[6]), "=f"(d[7]), "=f"(d[8]), "=f"(d[9]), "=f"(d[10]), "=f"(d[11]), "=f"(d[12]), "=f"(d[13]), "=f"(d[14]), "=f"(d[15]), "=f"(d[16]), "=f"(d[17]), "=f"(d[18]), "=f"(d[19]), "=f"(d[20]), "=f"(d[21]), "=f"(d[22]), "=f"(d[23]), "=f"(d[24]), "=f"(d[25]), "=f"(d[26]), "=f"(d[27]), "=f"(d[28]), "=f"(d[29]), "=f"(d[30]), "=f"(d[31]), "=f"(d[32]), "=f"(d[33]), "=f"(d[34]), "=f"(d[35]), "=f"(d[36]), "=f"(d[37]), "=f"(d[38]), "=f"(d[39]), "=f"(d[40]), "=f"(d[41]), "=f"(d[42]), "=f"(d[43]), "=f"(d[44]), "=f"(d[45]), "=f"(d[46]), "=f"(d[47])
        : "r"(a[AOFF + 0][0]), "r"(a[AOFF + 0][1]), "r"(a[AOFF + 0][2]), "r"(a[AOFF + 0][3]), "r"(a[AOFF + 1][0]), "r"(a[AOFF + 1][1]), "r"(a[AOFF + 1][2]), "r"(a[AOFF + 1][3]), "r"(a[AOFF + 2][0]), "r"(a[AOFF + 2][1]), "r"(a[AOFF + 2][2]), "r"(a[AOFF + 2][3]), "r"(a[AOFF + 3][0]), "r"(a[AOFF + 3][1]), "r"(a[AOFF + 3][2]), "r"(a[AOFF + 3][3]), "r"(a[AOFF + 4][0]), "r"(a[AOFF + 4][1]), "r"(a[AOFF + 4][2]), "r"(a[AOFF + 4][3]), "r"(a[AOFF + 5][0]), "r"(a[AOFF + 5][1]), "r"(a[AOFF + 5][2]), "r"(a[AOFF + 5][3]), "l"(descB), "n"(BOFF >> 4));
}

template <int BOFF, int AOFF, int NA>
__device__ __forceinline__ void mma_qkv_b(float (&d)[48], const uint32_t (&a)[NA][4], uint64_t descB) {
    asm volatile(
        "{\n"
        ".reg .pred p0, p1;\n"
        ".reg .b64 ta, ta0, tb, tb0;\n"
        "setp.ne.b32 p0, 0, 0;\n"
        "setp.eq.b32 p1, 0, 0;\n"
        "add.s64 tb0, %72, %73;\n"
        "add.s64 tb, tb0, 1600;\n"
        "wgmma.mma_async.sync.aligned.m64n96k16.f32.bf16.bf16 {%0, %1, %2, %3, %4, %5, %6, %7, %8, %9, %10, %11, %12, %13, %14, %15, %16, %17, %18, %19, %20, %21, %22, %23, %24, %25, %26, %27, %28, %29, %30, %31, %32, %33, %34, %35, %36, %37, %38, %39, %40, %41, %42, %43, %44, %45, %46, %47}, {%48, %49, %50, %51}, tb, p1, 1, 1, 1;\n"
        "add.s64 tb, tb0, 1632;\n"
        "wgmma.mma_async.sync.aligned.m64n96k16.f32.bf16.bf16 {%0, %1, %2, %3, %4, %5, %6, %7, %8, %9, %10, %11, %12, %13, %14, %15, %16, %17, %18, %19, %20, %21, %22, %23, %24, %25, %26, %27, %28, %29, %30, %31, %32, %33, %34, %35, %36, %37, %38, %39, %40, %41, %42, %43, %44, %45, %46, %47}, {%52, %53, %54, %55}, tb, p1, 1, 1, 1;\n"
        "add.s64 tb, tb0, 3072;\n"
        "wgmma.mma_async.sync.aligned.m64n96k16.f32.bf16.bf16 {%0, %1, %2, %3, %4, %5, %6, %7, %8, %9, %10, %11, %12, %13, %14, %15, %16, %17, %18, %19, %20, %21, %22, %23, %24, %25, %26, %27, %28, %29, %30, %31, %32, %33, %34, %35, %36, %37, %38, %39, %40, %41, %42, %43, %44, %45, %46, %47}, {%56, %57, %58, %59}, tb, p1, 1, 1, 1;\n"
        "add.s64 tb, tb0, 3104;\n"
        "wgmma.mma_async.sync.aligned.m64n96k16.f32.bf16.bf16 {%0, %1, %2, %3, %4, %5, %6, %7, %8, %9, %10, %11, %12, %13, %14, %15, %16, %17, %18, %19, %20, %21, %22, %23, %24, %25, %26, %27, %28, %29, %30, %31, %32, %33, %34, %35, %36, %37, %38, %39, %40, %41, %42, %43, %44, %45, %46, %47}, {%60, %61, %62, %63}, tb, p1, 1, 1, 1;\n"
        "add.s64 tb, tb0, 3136;\n"
        "wgmma.mma_async.sync.aligned.m64n96k16.f32.bf16.bf16 {%0, %1, %2, %3, %4, %5, %6, %7, %8, %9, %10, %11, %12, %13, %14, %15, %16, %17, %18, %19, %20, %21, %22, %23, %24, %25, %26, %27, %28, %29, %30, %31, %32, %33, %34, %35, %36, %37, %38, %39, %40, %41, %42, %43, %44, %45, %46, %47}, {%64, %65, %66, %67}, tb, p1, 1, 1, 1;\n"
        "add.s64 tb, tb0, 3168;\n"
        "wgmma.mma_async.sync.aligned.m64n96k16.f32.bf16.bf16 {%0, %1, %2, %3, %4, %5, %6, %7, %8, %9, %10, %11, %12, %13, %14, %15, %16, %17, %18, %19, %20, %21, %22, %23, %24, %25, %26, %27, %28, %29, %30, %31, %32, %33, %34, %35, %36, %37, %38, %39, %40, %41, %42, %43, %44, %45, %46, %47}, {%68, %69, %70, %71}, tb, p1, 1, 1, 1;\n"
        "}\n"
        : "+f"(d[0]), "+f"(d[1]), "+f"(d[2]), "+f"(d[3]), "+f"(d[4]), "+f"(d[5]), "+f"(d[6]), "+f"(d[7]), "+f"(d[8]), "+f"(d[9]), "+f"(d[10]), "+f"(d[11]), "+f"(d[12]), "+f"(d[13]), "+f"(d[14]), "+f"(d[15]), "+f"(d[16]), "+f"(d[17]), "+f"(d[18]), "+f"(d[19]), "+f"(d[20]), "+f"(d[21]), "+f"(d[22]), "+f"(d[23]), "+f"(d[24]), "+f"(d[25]), "+f"(d[26]), "+f"(d[27]), "+f"(d[28]), "+f"(d[29]), "+f"(d[30]), "+f"(d[31]), "+f"(d[32]), "+f"(d[33]), "+f"(d[34]), "+f"(d[35]), "+f"(d[36]), "+f"(d[37]), "+f"(d[38]), "+f"(d[39]), "+f"(d[40]), "+f"(d[41]), "+f"(d[42]), "+f"(d[43]), "+f"(d[44]), "+f"(d[45]), "+f"(d[46]), "+f"(d[47])
        : "r"(a[AOFF + 0][0]), "r"(a[AOFF + 0][1]), "r"(a[AOFF + 0][2]), "r"(a[AOFF + 0][3]), "r"(a[AOFF + 1][0]), "r"(a[AOFF + 1][1]), "r"(a[AOFF + 1][2]), "r"(a[AOFF + 1][3]), "r"(a[AOFF + 2][0]), "r"(a[AOFF + 2][1]), "r"(a[AOFF + 2][2]), "r"(a[AOFF + 2][3]), "r"(a[AOFF + 3][0]), "r"(a[AOFF + 3][1]), "r"(a[AOFF + 3][2]), "r"(a[AOFF + 3][3]), "r"(a[AOFF + 4][0]), "r"(a[AOFF + 4][1]), "r"(a[AOFF + 4][2]), "r"(a[AOFF + 4][3]), "r"(a[AOFF + 5][0]), "r"(a[AOFF + 5][1]), "r"(a[AOFF + 5][2]), "r"(a[AOFF + 5][3]), "l"(descB), "n"(BOFF >> 4));
}

template <int BOFF, int AOFF, int NA>
__device__ __forceinline__ void mma_v_a(float (&d)[48], const uint32_t (&a)[NA][4], uint64_t descB) {
    asm volatile(
        "{\n"
        ".reg .pred p0, p1;\n"
        ".reg .b64 ta, ta0, tb, tb0;\n"
        "setp.ne.b32 p0, 0, 0;\n"
        "setp.eq.b32 p1, 0, 0;\n"
        "add.s64 tb0, %72, %73;\n"
        "add.s64 tb, tb0, 0;\n"
        "wgmma.mma_async.sync.aligned.m64n96k16.f32.bf16.bf16 {%0, %1, %2, %3, %4, %5, %6, %7, %8, %9, %10, %11, %12, %13, %14, %15, %16, %17, %18, %19, %20, %21, %22, %23, %24, %25, %26, %27, %28, %29, %30, %31, %32, %33, %34, %35, %36, %37, %38, %39, %40, %41, %42, %43, %44, %45, %46, %47}, {%48, %49, %50, %51}, tb, p0, 1, 1, 1;\n"
        "add.s64 tb, tb0, 32;\n"
        "wgmma.mma_async.sync.aligned.m64n96k16.f32.bf16.bf16 {%0, %1, %2, %3, %4, %5, %6, %7, %8, %9, %10, %11, %12, %13, %14, %15, %16, %17, %18, %19, %20, %21, %22, %23, %24, %25, %26, %27, %28, %29, %30, %31, %32, %33, %34, %35, %36, %37, %38, %39, %40, %41, %42, %43, %44, %45, %46, %47}, {%52, %53, %54, %55}, tb, p1, 1, 1, 1;\n"
        "add.s64 tb, tb0, 64;\n"
        "wgmma.mma_async.sync.aligned.m64n96k16.f32.bf16.bf16 {%0, %1, %2, %3, %4, %5, %6, %7, %8, %9, %10, %11, %12, %13, %14, %15, %16, %17, %18, %19, %20, %21, %22, %23, %24, %25, %26, %27, %28, %29, %30, %31, %32, %33, %34, %35, %36, %37, %38, %39, %40, %41, %42, %43, %44, %45, %46, %47}, {%56, %57, %58, %59}, tb, p1, 1, 1, 1;\n"
        "add.s64 tb, tb0, 96;\n"
        "wgmma.mma_async.sync.aligned.m64n96k16.f32.bf16.bf16 {%0, %1, %2, %3, %4, %5, %6, %7, %8, %9, %10, %11, %12, %13, %14, %15, %16, %17, %18, %19, %20, %21, %22, %23, %24, %25, %26, %27, %28, %29, %30, %31, %32, %33, %34, %35, %36, %37, %38, %39, %40, %41, %42, %43, %44, %45, %46, %47}, {%60, %61, %62, %63}, tb, p1, 1, 1, 1;\n"
        "add.s64 tb, tb0, 128;\n"
        "wgmma.mma_async.sync.aligned.m64n96k16.f32.bf16.bf16 {%0, %1, %2, %3, %4, %5, %6, %7, %8, %9, %10, %11, %12, %13, %14, %15, %16, %17, %18, %19, %20, %21, %22, %23, %24, %25, %26, %27, %28, %29, %30, %31, %32, %33, %34, %35, %36, %37, %38, %39, %40, %41, %42, %43, %44, %45, %46, %47}, {%64, %65, %66, %67}, tb, p1, 1, 1, 1;\n"
        "add.s64 tb, tb0, 160;\n"
        "wgmma.mma_async.sync.aligned.m64n96k16.f32.bf16.bf16 {%0, %1, %2, %3, %4, %5, %6, %7, %8, %9, %10, %11, %12, %13, %14, %15, %16, %17, %18, %19, %20, %21, %22, %23, %24, %25, %26, %27, %28, %29, %30, %31, %32, %33, %34, %35, %36, %37, %38, %39, %40, %41, %42, %43, %44, %45, %46, %47}, {%68, %69, %70, %71}, tb, p1, 1, 1, 1;\n"
        "}\n"
        : "=f"(d[0]), "=f"(d[1]), "=f"(d[2]), "=f"(d[3]), "=f"(d[4]), "=f"(d[5]), "=f"(d[6]), "=f"(d[7]), "=f"(d[8]), "=f"(d[9]), "=f"(d[10]), "=f"(d[11]), "=f"(d[12]), "=f"(d[13]), "=f"(d[14]), "=f"(d[15]), "=f"(d[16]), "=f"(d[17]), "=f"(d[18]), "=f"(d[19]), "=f"(d[20]), "=f"(d[21]), "=f"(d[22]), "=f"(d[23]), "=f"(d[24]), "=f"(d[25]), "=f"(d[26]), "=f"(d[27]), "=f"(d[28]), "=f"(d[29]), "=f"(d[30]), "=f"(d[31]), "=f"(d[32]), "=f"(d[33]), "=f"(d[34]), "=f"(d[35]), "=f"(d[36]), "=f"(d[37]), "=f"(d[38]), "=f"(d[39]), "=f"(d[40]), "=f"(d[41]), "=f"(d[42]), "=f"(d[43]), "=f"(d[44]), "=f"(d[45]), "=f"(d[46]), "=f"(d[47])
        : "r"(a[AOFF + 0][0]), "r"(a[AOFF + 0][1]), "r"(a[AOFF + 0][2]), "r"(a[AOFF + 0][3]), "r"(a[AOFF + 1][0]), "r"(a[AOFF + 1][1]), "r"(a[AOFF + 1][2]), "r"(a[AOFF + 1][3]), "r"(a[AOFF + 2][0]), "r"(a[AOFF + 2][1]), "r"(a[AOFF + 2][2]), "r"(a[AOFF + 2][3]), "r"(a[AOFF + 3][0]), "r"(a[AOFF + 3][1]), "r"(a[AOFF + 3][2]), "r"(a[AOFF + 3][3]), "r"(a[AOFF + 4][0]), "r"(a[AOFF + 4][1]), "r"(a[AOFF + 4][2]), "r"(a[AOFF + 4][3]), "r"(a[AOFF + 5][0]), "r"(a[AOFF + 5][1]), "r"(a[AOFF + 5][2]), "r"(a[AOFF + 5][3]), "l"(descB), "n"(BOFF >> 4));
}

template <int BOFF, int AOFF, int NA>
__device__ __forceinline__ void mma_v_b(float (&d)[48], const uint32_t (&a)[NA][4], uint64_t descB) {
    asm volatile(
        "{\n"
        ".reg .pred p0, p1;\n"
        ".reg .b64 ta, ta0, tb, tb0;\n"
        "setp.ne.b32 p0, 0, 0;\n"
        "setp.eq.b32 p1, 0, 0;\n"
        "add.s64 tb0, %72, %73;\n"
        "add.s64 tb, tb0, 192;\n"
        "wgmma.mma_async.sync.aligned.m64n96k16.f32.bf16.bf16 {%0, %1, %2, %3, %4, %5, %6, %7, %8, %9, %10, %11, %12, %13, %14, %15, %16, %17, %18, %19, %20, %21, %22, %23, %24, %25, %26, %27, %28, %29, %30, %31, %32, %33, %34, %35, %36, %37, %38, %39, %40, %41, %42, %43, %44, %45, %46, %47}, {%48, %49, %50, %51}, tb, p1, 1, 1, 1;\n"
        "add.s64 tb, tb0, 224;\n"
        "wgmma.mma_async.sync.aligned.m64n96k16.f32.bf16.bf16 {%0, %1, %2, %3, %4, %5, %6, %7, %8, %9, %10, %11, %12, %13, %14, %15, %16, %17, %18, %19, %20, %21, %22, %23, %24, %25, %26, %27, %28, %29, %30, %31, %32, %33, %34, %35, %36, %37, %38, %39, %40, %41, %42, %43, %44, %45, %46, %47}, {%52, %53, %54, %55}, tb, p1, 1, 1, 1;\n"
        "add.s64 tb, tb0, 256;\n"
        "wgmma.mma_async.sync.aligned.m64n96k16.f32.bf16.bf16 {%0, %1, %2, %3, %4, %5, %6, %7, %8, %9, %10, %11, %12, %13, %14, %15, %16, %17, %18, %19, %20, %21, %22, %23, %24, %25, %26, %27, %28, %29, %30, %31, %32, %33, %34, %35, %36, %37, %38, %39, %40, %41, %42, %43, %44, %45, %46, %47}, {%56, %57, %58, %59}, tb, p1, 1, 1, 1;\n"
        "add.s64 tb, tb0, 288;\n"
        "wgmma.mma_async.sync.aligned.m64n96k16.f32.bf16.bf16 {%0, %1, %2, %3, %4, %5, %6, %7, %8, %9, %10, %11, %12, %13, %14, %15, %16, %17, %18, %19, %20, %21, %22, %23, %24, %25, %26, %27, %28, %29, %30, %31, %32, %33, %34, %35, %36, %37, %38, %39, %40, %41, %42, %43, %44, %45, %46, %47}, {%60, %61, %62, %63}, tb, p1, 1, 1, 1;\n"
        "add.s64 tb, tb0, 320;\n"
        "wgmma.mma_async.sync.aligned.m64n96k16.f32.bf16.bf16 {%0, %1, %2, %3, %4, %5, %6, %7, %8, %9, %10, %11, %12, %13, %14, %15, %16, %17, %18, %19, %20, %21, %22, %23, %24, %25, %26, %27, %28, %29, %30, %31, %32, %33, %34, %35, %36, %37, %38, %39, %40, %41, %42, %43, %44, %45, %46, %47}, {%64, %65, %66, %67}, tb, p1, 1, 1, 1;\n"
        "add.s64 tb, tb0, 352;\n"
        "wgmma.mma_async.sync.aligned.m64n96k16.f32.bf16.bf16 {%0, %1, %2, %3, %4, %5, %6, %7, %8, %9, %10, %11, %12, %13, %14, %15, %16, %17, %18, %19, %20, %21, %22, %23, %24, %25, %26, %27, %28, %29, %30, %31, %32, %33, %34, %35, %36, %37, %38, %39, %40, %41, %42, %43, %44, %45, %46, %47}, {%68, %69, %70, %71}, tb, p1, 1, 1, 1;\n"
        "}\n"
        : "+f"(d[0]), "+f"(d[1]), "+f"(d[2]), "+f"(d[3]), "+f"(d[4]), "+f"(d[5]), "+f"(d[6]), "+f"(d[7]), "+f"(d[8]), "+f"(d[9]), "+f"(d[10]), "+f"(d[11]), "+f"(d[12]), "+f"(d[13]), "+f"(d[14]), "+f"(d[15]), "+f"(d[16]), "+f"(d[17]), "+f"(d[18]), "+f"(d[19]), "+f"(d[20]), "+f"(d[21]), "+f"(d[22]), "+f"(d[23]), "+f"(d[24]), "+f"(d[25]), "+f"(d[26]), "+f"(d[27]), "+f"(d[28]), "+f"(d[29]), "+f"(d[30]), "+f"(d[31]), "+f"(d[32]), "+f"(d[33]), "+f"(d[34]), "+f"(d[35]), "+f"(d[36]), "+f"(d[37]), "+f"(d[38]), "+f"(d[39]), "+f"(d[40]), "+f"(d[41]), "+f"(d[42]), "+f"(d[43]), "+f"(d[44]), "+f"(d[45]), "+f"(d[46]), "+f"(d[47])
        : "r"(a[AOFF + 0][0]), "r"(a[AOFF + 0][1]), "r"(a[AOFF + 0][2]), "r"(a[AOFF + 0][3]), "r"(a[AOFF + 1][0]), "r"(a[AOFF + 1][1]), "r"(a[AOFF + 1][2]), "r"(a[AOFF + 1][3]), "r"(a[AOFF + 2][0]), "r"(a[AOFF + 2][1]), "r"(a[AOFF + 2][2]), "r"(a[AOFF + 2][3]), "r"(a[AOFF + 3][0]), "r"(a[AOFF + 3][1]), "r"(a[AOFF + 3][2]), "r"(a[AOFF + 3][3]), "r"(a[AOFF + 4][0]), "r"(a[AOFF + 4][1]), "r"(a[AOFF + 4][2]), "r"(a[AOFF + 4][3]), "r"(a[AOFF + 5][0]), "r"(a[AOFF + 5][1]), "r"(a[AOFF + 5][2]), "r"(a[AOFF + 5][3]), "l"(descB), "n"(BOFF >> 4));
}

template <int BOFF, int AOFF, int NA>
__device__ __forceinline__ void mma_w_a(float (&d)[48], const uint32_t (&a)[NA][4], uint64_t descB) {
    asm volatile(
        "{\n"
        ".reg .pred p0, p1;\n"
        ".reg .b64 ta, ta0, tb, tb0;\n"
        "setp.ne.b32 p0, 0, 0;\n"
        "setp.eq.b32 p1, 0, 0;\n"
        "add.s64 tb0, %72, %73;\n"
        "add.s64 tb, tb0, 0;\n"
        "wgmma.mma_async.sync.aligned.m64n96k16.f32.bf16.bf16 {%0, %1, %2, %3, %4, %5, %6, %7, %8, %9, %10, %11, %12, %13, %14, %15, %16, %17, %18, %19, %20, %21, %22, %23, %24, %25, %26, %27, %28, %29, %30, %31, %32, %33, %34, %35, %36, %37, %38, %39, %40, %41, %42, %43, %44, %45, %46, %47}, {%48, %49, %50, %51}, tb, p0, 1, 1, 1;\n"
        "add.s64 tb, tb0, 64;\n"
        "wgmma.mma_async.sync.aligned.m64n96k16.f32.bf16.bf16 {%0, %1, %2, %3, %4, %5, %6, %7, %8, %9, %10, %11, %12, %13, %14, %15, %16, %17, %18, %19, %20, %21, %22, %23, %24, %25, %26, %27, %28, %29, %30, %31, %32, %33, %34, %35, %36, %37, %38, %39, %40, %41, %42, %43, %44, %45, %46, %47}, {%52, %53, %54, %55}, tb, p1, 1, 1, 1;\n"
        "add.s64 tb, tb0, 128;\n"
        "wgmma.mma_async.sync.aligned.m64n96k16.f32.bf16.bf16 {%0, %1, %2, %3, %4, %5, %6, %7, %8, %9, %10, %11, %12, %13, %14, %15, %16, %17, %18, %19, %20, %21, %22, %23, %24, %25, %26, %27, %28, %29, %30, %31, %32, %33, %34, %35, %36, %37, %38, %39, %40, %41, %42, %43, %44, %45, %46, %47}, {%56, %57, %58, %59}, tb, p1, 1, 1, 1;\n"
        "add.s64 tb, tb0, 192;\n"
        "wgmma.mma_async.sync.aligned.m64n96k16.f32.bf16.bf16 {%0, %1, %2, %3, %4, %5, %6, %7, %8, %9, %10, %11, %12, %13, %14, %15, %16, %17, %18, %19, %20, %21, %22, %23, %24, %25, %26, %27, %28, %29, %30, %31, %32, %33, %34, %35, %36, %37, %38, %39, %40, %41, %42, %43, %44, %45, %46, %47}, {%60, %61, %62, %63}, tb, p1, 1, 1, 1;\n"
        "add.s64 tb, tb0, 256;\n"
        "wgmma.mma_async.sync.aligned.m64n96k16.f32.bf16.bf16 {%0, %1, %2, %3, %4, %5, %6, %7, %8, %9, %10, %11, %12, %13, %14, %15, %16, %17, %18, %19, %20, %21, %22, %23, %24, %25, %26, %27, %28, %29, %30, %31, %32, %33, %34, %35, %36, %37, %38, %39, %40, %41, %42, %43, %44, %45, %46, %47}, {%64, %65, %66, %67}, tb, p1, 1, 1, 1;\n"
        "add.s64 tb, tb0, 320;\n"
        "wgmma.mma_async.sync.aligned.m64n96k16.f32.bf16.bf16 {%0, %1, %2, %3, %4, %5, %6, %7, %8, %9, %10, %11, %12, %13, %14, %15, %16, %17, %18, %19, %20, %21, %22, %23, %24, %25, %26, %27, %28, %29, %30, %31, %32, %33, %34, %35, %36, %37, %38, %39, %40, %41, %42, %43, %44, %45, %46, %47}, {%68, %69, %70, %71}, tb, p1, 1, 1, 1;\n"
        "}\n"
        : "=f"(d[0]), "=f"(d[1]), "=f"(d[2]), "=f"(d[3]), "=f"(d[4]), "=f"(d[5]), "=f"(d[6]), "=f"(d[7]), "=f"(d[8]), "=f"(d[9]), "=f"(d[10]), "=f"(d[11]), "=f"(d[12]), "=f"(d[13]), "=f"(d[14]), "=f"(d[15]), "=f"(d[16]), "=f"(d[17]), "=f"(d[18]), "=f"(d[19]), "=f"(d[20]), "=f"(d[21]), "=f"(d[22]), "=f"(d[23]), "=f"(d[24]), "=f"(d[25]), "=f"(d[26]), "=f"(d[27]), "=f"(d[28]), "=f"(d[29]), "=f"(d[30]), "=f"(d[31]), "=f"(d[32]), "=f"(d[33]), "=f"(d[34]), "=f"(d[35]), "=f"(d[36]), "=f"(d[37]), "=f"(d[38]), "=f"(d[39]), "=f"(d[40]), "=f"(d[41]), "=f"(d[42]), "=f"(d[43]), "=f"(d[44]), "=f"(d[45]), "=f"(d[46]), "=f"(d[47])
        : "r"(a[AOFF + 0][0]), "r"(a[AOFF + 0][1]), "r"(a[AOFF + 0][2]), "r"(a[AOFF + 0][3]), "r"(a[AOFF + 1][0]), "r"(a[AOFF + 1][1]), "r"(a[AOFF + 1][2]), "r"(a[AOFF + 1][3]), "r"(a[AOFF + 2][0]), "r"(a[AOFF + 2][1]), "r"(a[AOFF + 2][2]), "r"(a[AOFF + 2][3]), "r"(a[AOFF + 3][0]), "r"(a[AOFF + 3][1]), "r"(a[AOFF + 3][2]), "r"(a[AOFF + 3][3]), "r"(a[AOFF + 4][0]), "r"(a[AOFF + 4][1]), "r"(a[AOFF + 4][2]), "r"(a[AOFF + 4][3]), "r"(a[AOFF + 5][0]), "r"(a[AOFF + 5][1]), "r"(a[AOFF + 5][2]), "r"(a[AOFF + 5][3]), "l"(descB), "n"(BOFF >> 4));
}

template <int BOFF, int AOFF, int NA>
__device__ __forceinline__ void mma_w_b(float (&d)[48], const uint32_t (&a)[NA][4], uint64_t descB) {
    asm volatile(
        "{\n"
        ".reg .pred p0, p1;\n"
        ".reg .b64 ta, ta0, tb, tb0;\n"
        "setp.ne.b32 p0, 0, 0;\n"
        "setp.eq.b32 p1, 0, 0;\n"
        "add.s64 tb0, %72, %73;\n"
        "add.s64 tb, tb0, 384;\n"
        "wgmma.mma_async.sync.aligned.m64n96k16.f32.bf16.bf16 {%0, %1, %2, %3, %4, %5, %6, %7, %8, %9, %10, %11, %12, %13, %14, %15, %16, %17, %18, %19, %20, %21, %22, %23, %24, %25, %26, %27, %28, %29, %30, %31, %32, %33, %34, %35, %36, %37, %38, %39, %40, %41, %42, %43, %44, %45, %46, %47}, {%48, %49, %50, %51}, tb, p1, 1, 1, 1;\n"
        "add.s64 tb, tb0, 448;\n"
        "wgmma.mma_async.sync.aligned.m64n96k16.f32.bf16.bf16 {%0, %1, %2, %3, %4, %5, %6, %7, %8, %9, %10, %11, %12, %13, %14, %15, %16, %17, %18, %19, %20, %21, %22, %23, %24, %25, %26, %27, %28, %29, %30, %31, %32, %33, %34, %35, %36, %37, %38, %39, %40, %41, %42, %43, %44, %45, %46, %47}, {%52, %53, %54, %55}, tb, p1, 1, 1, 1;\n"
        "add.s64 tb, tb0, 512;\n"
        "wgmma.mma_async.sync.aligned.m64n96k16.f32.bf16.bf16 {%0, %1, %2, %3, %4, %5, %6, %7, %8, %9, %10, %11, %12, %13, %14, %15, %16, %17, %18, %19, %20, %21, %22, %23, %24, %25, %26, %27, %28, %29, %30, %31, %32, %33, %34, %35, %36, %37, %38, %39, %40, %41, %42, %43, %44, %45, %46, %47}, {%56, %57, %58, %59}, tb, p1, 1, 1, 1;\n"
        "add.s64 tb, tb0, 576;\n"
        "wgmma.mma_async.sync.aligned.m64n96k16.f32.bf16.bf16 {%0, %1, %2, %3, %4, %5, %6, %7, %8, %9, %10, %11, %12, %13, %14, %15, %16, %17, %18, %19, %20, %21, %22, %23, %24, %25, %26, %27, %28, %29, %30, %31, %32, %33, %34, %35, %36, %37, %38, %39, %40, %41, %42, %43, %44, %45, %46, %47}, {%60, %61, %62, %63}, tb, p1, 1, 1, 1;\n"
        "add.s64 tb, tb0, 640;\n"
        "wgmma.mma_async.sync.aligned.m64n96k16.f32.bf16.bf16 {%0, %1, %2, %3, %4, %5, %6, %7, %8, %9, %10, %11, %12, %13, %14, %15, %16, %17, %18, %19, %20, %21, %22, %23, %24, %25, %26, %27, %28, %29, %30, %31, %32, %33, %34, %35, %36, %37, %38, %39, %40, %41, %42, %43, %44, %45, %46, %47}, {%64, %65, %66, %67}, tb, p1, 1, 1, 1;\n"
        "add.s64 tb, tb0, 704;\n"
        "wgmma.mma_async.sync.aligned.m64n96k16.f32.bf16.bf16 {%0, %1, %2, %3, %4, %5, %6, %7, %8, %9, %10, %11, %12, %13, %14, %15, %16, %17, %18, %19, %20, %21, %22, %23, %24, %25, %26, %27, %28, %29, %30, %31, %32, %33, %34, %35, %36, %37, %38, %39, %40, %41, %42, %43, %44, %45, %46, %47}, {%68, %69, %70, %71}, tb, p1, 1, 1, 1;\n"
        "}\n"
        : "+f"(d[0]), "+f"(d[1]), "+f"(d[2]), "+f"(d[3]), "+f"(d[4]), "+f"(d[5]), "+f"(d[6]), "+f"(d[7]), "+f"(d[8]), "+f"(d[9]), "+f"(d[10]), "+f"(d[11]), "+f"(d[12]), "+f"(d[13]), "+f"(d[14]), "+f"(d[15]), "+f"(d[16]), "+f"(d[17]), "+f"(d[18]), "+f"(d[19]), "+f"(d[20]), "+f"(d[21]), "+f"(d[22]), "+f"(d[23]), "+f"(d[24]), "+f"(d[25]), "+f"(d[26]), "+f"(d[27]), "+f"(d[28]), "+f"(d[29]), "+f"(d[30]), "+f"(d[31]), "+f"(d[32]), "+f"(d[33]), "+f"(d[34]), "+f"(d[35]), "+f"(d[36]), "+f"(d[37]), "+f"(d[38]), "+f"(d[39]), "+f"(d[40]), "+f"(d[41]), "+f"(d[42]), "+f"(d[43]), "+f"(d[44]), "+f"(d[45]), "+f"(d[46]), "+f"(d[47])
        : "r"(a[AOFF + 0][0]), "r"(a[AOFF + 0][1]), "r"(a[AOFF + 0][2]), "r"(a[AOFF + 0][3]), "r"(a[AOFF + 1][0]), "r"(a[AOFF + 1][1]), "r"(a[AOFF + 1][2]), "r"(a[AOFF + 1][3]), "r"(a[AOFF + 2][0]), "r"(a[AOFF + 2][1]), "r"(a[AOFF + 2][2]), "r"(a[AOFF + 2][3]), "r"(a[AOFF + 3][0]), "r"(a[AOFF + 3][1]), "r"(a[AOFF + 3][2]), "r"(a[AOFF + 3][3]), "r"(a[AOFF + 4][0]), "r"(a[AOFF + 4][1]), "r"(a[AOFF + 4][2]), "r"(a[AOFF + 4][3]), "r"(a[AOFF + 5][0]), "r"(a[AOFF + 5][1]), "r"(a[AOFF + 5][2]), "r"(a[AOFF + 5][3]), "l"(descB), "n"(BOFF >> 4));
}
template <int V, int S0, int S1> struct Rng;
template <> struct Rng<0, 0, 3> {
template <int BOFF, int AOFF, int NA>
static __device__ __forceinline__ void run(float (&d)[48], const uint32_t (&a)[NA][4], uint64_t descB) {
    asm volatile(
        "{\n"
        ".reg .pred p0, p1;\n"
        ".reg .b64 ta, ta0, tb, tb0;\n"
        "setp.ne.b32 p0, 0, 0;\n"
        "setp.eq.b32 p1, 0, 0;\n"
        "add.s64 tb0, %60, %61;\n"
        "add.s64 tb, tb0, 0;\n"
        "wgmma.mma_async.sync.aligned.m64n96k16.f32.bf16.bf16 {%0, %1, %2, %3, %4, %5, %6, %7, %8, %9, %10, %11, %12, %13, %14, %15, %16, %17, %18, %19, %20, %21, %22, %23, %24, %25, %26, %27, %28, %29, %30, %31, %32, %33, %34, %35, %36, %37, %38, %39, %40, %41, %42, %43, %44, %45, %46, %47}, {%48, %49, %50, %51}, tb, p0, 1, 1, 1;\n"
        "add.s64 tb, tb0, 32;\n"
        "wgmma.mma_async.sync.aligned.m64n96k16.f32.bf16.bf16 {%0, %1, %2, %3, %4, %5, %6, %7, %8, %9, %10, %11, %12, %13, %14, %15, %16, %17, %18, %19, %20, %21, %22, %23, %24, %25, %26, %27, %28, %29, %30, %31, %32, %33, %34, %35, %36, %37, %38, %39, %40, %41, %42, %43, %44, %45, %46, %47}, {%52, %53, %54, %55}, tb, p1, 1, 1, 1;\n"
        "add.s64 tb, tb0, 64;\n"
        "wgmma.mma_async.sync.aligned.m64n96k16.f32.bf16.bf16 {%0, %1, %2, %3, %4, %5, %6, %7, %8, %9, %10, %11, %12, %13, %14, %15, %16, %17, %18, %19, %20, %21, %22, %23, %24, %25, %26, %27, %28, %29, %30, %31, %32, %33, %34, %35, %36, %37, %38, %39, %40, %41, %42, %43, %44, %45, %46, %47}, {%56, %57, %58, %59}, tb, p1, 1, 1, 1;\n"
        "}\n"
        : "=f"(d[0]), "=f"(d[1]), "=f"(d[2]), "=f"(d[3]), "=f"(d[4]), "=f"(d[5]), "=f"(d[6]), "=f"(d[7]), "=f"(d[8]), "=f"(d[9]), "=f"(d[10]), "=f"(d[11]), "=f"(d[12]), "=f"(d[13]), "=f"(d[14]), "=f"(d[15]), "=f"(d[16]), "=f"(d[17]), "=f"(d[18]), "=f"(d[19]), "=f"(d[20]), "=f"(d[21]), "=f"(d[22]), "=f"(d[23]), "=f"(d[24]), "=f"(d[25]), "=f"(d[26]), "=f"(d[27]), "=f"(d[28]), "=f"(d[29]), "=f"(d[30]), "=f"(d[31]), "=f"(d[32]), "=f"(d[33]), "=f"(d[34]), "=f"(d[35]), "=f"(d[36]), "=f"(d[37]), "=f"(d[38]), "=f"(d[39]), "=f"(d[40]), "=f"(d[41]), "=f"(d[42]), "=f"(d[43]), "=f"(d[44]), "=f"(d[45]), "=f"(d[46]), "=f"(d[47])
        : "r"(a[AOFF + 0][0]), "r"(a[AOFF + 0][1]), "r"(a[AOFF + 0][2]), "r"(a[AOFF + 0][3]), "r"(a[AOFF + 1][0]), "r"(a[AOFF + 1][1]), "r"(a[AOFF + 1][2]), "r"(a[AOFF + 1][3]), "r"(a[AOFF + 2][0]), "r"(a[AOFF + 2][1]), "r"(a[AOFF + 2][2]), "r"(a[AOFF + 2][3]), "l"(descB), "n"(BOFF >> 4));
}
};
template <> struct Rng<1, 0, 3> {
template <int BOFF, int AOFF, int NA>
static __device__ __forceinline__ void run(float (&d)[48], const uint32_t (&a)[NA][4], uint64_t descB) {
    asm volatile(
        "{\n"
        ".reg .pred p0, p1;\n"
        ".reg .b64 ta, ta0, tb, tb0;\n"
        "setp.ne.b32 p0, 0, 0;\n"
        "setp.eq.b32 p1, 0, 0;\n"
        "add.s64 tb0, %60, %61;\n"
        "add.s64 tb, tb0, 0;\n"
        "wgmma.mma_async.sync.aligned.m64n96k16.f32.bf16.bf16 {%0, %1, %2, %3, %4, %5, %6, %7, %8, %9, %10, %11, %12, %13, %14, %15, %16, %17, %18, %19, %20, %21, %22, %23, %24, %25, %26, %27, %28, %29, %30, %31, %32, %33, %34, %35, %36, %37, %38, %39, %40, %41, %42, %43, %44, %45, %46, %47}, {%48, %49, %50, %51}, tb, p0, 1, 1, 1;\n"
        "add.s64 tb, tb0, 32;\n"
        "wgmma.mma_async.sync.aligned.m64n96k16.f32.bf16.bf16 {%0, %1, %2, %3, %4, %5, %6, %7, %8, %9, %10, %11, %12, %13, %14, %15, %16, %17, %18, %19, %20, %21, %22, %23, %24, %25, %26, %27, %28, %29, %30, %31, %32, %33, %34, %35, %36, %37, %38, %39, %40, %41, %42, %43, %44, %45, %46, %47}, {%52, %53, %54, %55}, tb, p1, 1, 1, 1;\n"
        "add.s64 tb, tb0, 64;\n"
        "wgmma.mma_async.sync.aligned.m64n96k16.f32.bf16.bf16 {%0, %1, %2, %3, %4, %5, %6, %7, %8, %9, %10, %11, %12, %13, %14, %15, %16, %17, %18, %19, %20, %21, %22, %23, %24, %25, %26, %27, %28, %29, %30, %31, %32, %33, %34, %35, %36, %37, %38, %39, %40, %41, %42, %43, %44, %45, %46, %47}, {%56, %57, %58, %59}, tb, p1, 1, 1, 1;\n"
        "}\n"
        : "=f"(d[0]), "=f"(d[1]), "=f"(d[2]), "=f"(d[3]), "=f"(d[4]), "=f"(d[5]), "=f"(d[6]), "=f"(d[7]), "=f"(d[8]), "=f"(d[9]), "=f"(d[10]), "=f"(d[11]), "=f"(d[12]), "=f"(d[13]), "=f"(d[14]), "=f"(d[15]), "=f"(d[16]), "=f"(d[17]), "=f"(d[18]), "=f"(d[19]), "=f"(d[20]), "=f"(d[21]), "=f"(d[22]), "=f"(d[23]), "=f"(d[24]), "=f"(d[25]), "=f"(d[26]), "=f"(d[27]), "=f"(d[28]), "=f"(d[29]), "=f"(d[30]), "=f"(d[31]), "=f"(d[32]), "=f"(d[33]), "=f"(d[34]), "=f"(d[35]), "=f"(d[36]), "=f"(d[37]), "=f"(d[38]), "=f"(d[39]), "=f"(d[40]), "=f"(d[41]), "=f"(d[42]), "=f"(d[43]), "=f"(d[44]), "=f"(d[45]), "=f"(d[46]), "=f"(d[47])
        : "r"(a[AOFF + 0][0]), "r"(a[AOFF + 0][1]), "r"(a[AOFF + 0][2]), "r"(a[AOFF + 0][3]), "r"(a[AOFF + 1][0]), "r"(a[AOFF + 1][1]), "r"(a[AOFF + 1][2]), "r"(a[AOFF + 1][3]), "r"(a[AOFF + 2][0]), "r"(a[AOFF + 2][1]), "r"(a[AOFF + 2][2]), "r"(a[AOFF + 2][3]), "l"(descB), "n"(BOFF >> 4));
}
};
template <> struct Rng<0, 0, 4> {
template <int BOFF, int AOFF, int NA>
static __device__ __forceinline__ void run(float (&d)[48], const uint32_t (&a)[NA][4], uint64_t descB) {
    asm volatile(
        "{\n"
        ".reg .pred p0, p1;\n"
        ".reg .b64 ta, ta0, tb, tb0;\n"
        "setp.ne.b32 p0, 0, 0;\n"
        "setp.eq.b32 p1, 0, 0;\n"
        "add.s64 tb0, %64, %65;\n"
        "add.s64 tb, tb0, 0;\n"
        "wgmma.mma_async.sync.aligned.m64n96k16.f32.bf16.bf16 {%0, %1, %2, %3, %4, %5, %6, %7, %8, %9, %10, %11, %12, %13, %14, %15, %16, %17, %18, %19, %20, %21, %22, %23, %24, %25, %26, %27, %28, %29, %30, %31, %32, %33, %34, %35, %36, %37, %38, %39, %40, %41, %42, %43, %44, %45, %46, %47}, {%48, %49, %50, %51}, tb, p0, 1, 1, 1;\n"
        "add.s64 tb, tb0, 32;\n"
        "wgmma.mma_async.sync.aligned.m64n96k16.f32.bf16.bf16 {%0, %1, %2, %3, %4, %5, %6, %7, %8, %9, %10, %11, %12, %13, %14, %15, %16, %17, %18, %19, %20, %21, %22, %23, %24, %25, %26, %27, %28, %29, %30, %31, %32, %33, %34, %35, %36, %37, %38, %39, %40, %41, %42, %43, %44, %45, %46, %47}, {%52, %53, %54, %55}, tb, p1, 1, 1, 1;\n"
        "add.s64 tb, tb0, 64;\n"
        "wgmma.mma_async.sync.aligned.m64n96k16.f32.bf16.bf16 {%0, %1, %2, %3, %4, %5, %6, %7, %8, %9, %10, %11, %12, %13, %14, %15, %16, %17, %18, %19, %20, %21, %22, %23, %24, %25, %26, %27, %28, %29, %30, %31, %32, %33, %34, %35, %36, %37, %38, %39, %40, %41, %42, %43, %44, %45, %46, %47}, {%56, %57, %58, %59}, tb, p1, 1, 1, 1;\n"
        "add.s64 tb, tb0, 96;\n"
        "wgmma.mma_async.sync.aligned.m64n96k16.f32.bf16.bf16 {%0, %1, %2, %3, %4, %5, %6, %7, %8, %9, %10, %11, %12, %13, %14, %15, %16, %17, %18, %19, %20, %21, %22, %23, %24, %25, %26, %27, %28, %29, %30, %31, %32, %33, %34, %35, %36, %37, %38, %39, %40, %41, %42, %43, %44, %45, %46, %47}, {%60, %61, %62, %63}, tb, p1, 1, 1, 1;\n"
        "}\n"
        : "=f"(d[0]), "=f"(d[1]), "=f"(d[2]), "=f"(d[3]), "=f"(d[4]), "=f"(d[5]), "=f"(d[6]), "=f"(d[7]), "=f"(d[8]), "=f"(d[9]), "=f"(d[10]), "=f"(d[11]), "=f"(d[12]), "=f"(d[13]), "=f"(d[14]), "=f"(d[15]), "=f"(d[16]), "=f"(d[17]), "=f"(d[18]), "=f"(d[19]), "=f"(d[20]), "=f"(d[21]), "=f"(d[22]), "=f"(d[23]), "=f"(d[24]), "=f"(d[25]), "=f"(d[26]), "=f"(d[27]), "=f"(d[28]), "=f"(d[29]), "=f"(d[30]), "=f"(d[31]), "=f"(d[32]), "=f"(d[33]), "=f"(d[34]), "=f"(d[35]), "=f"(d[36]), "=f"(d[37]), "=f"(d[38]), "=f"(d[39]), "=f"(d[40]), "=f"(d[41]), "=f"(d[42]), "=f"(d[43]), "=f"(d[44]), "=f"(d[45]), "=f"(d[46]), "=f"(d[47])
        : "r"(a[AOFF + 0][0]), "r"(a[AOFF + 0][1]), "r"(a[AOFF + 0][2]), "r"(a[AOFF + 0][3]), "r"(a[AOFF + 1][0]), "r"(a[AOFF + 1][1]), "r"(a[AOFF + 1][2]), "r"(a[AOFF + 1][3]), "r"(a[AOFF + 2][0]), "r"(a[AOFF + 2][1]), "r"(a[AOFF + 2][2]), "r"(a[AOFF + 2][3]), "r"(a[AOFF + 3][0]), "r"(a[AOFF + 3][1]), "r"(a[AOFF + 3][2]), "r"(a[AOFF + 3][3]), "l"(descB), "n"(BOFF >> 4));
}
};
template <> struct Rng<1, 0, 4> {
template <int BOFF, int AOFF, int NA>
static __device__ __forceinline__ void run(float (&d)[48], const uint32_t (&a)[NA][4], uint64_t descB) {
    asm volatile(
        "{\n"
        ".reg .pred p0, p1;\n"
        ".reg .b64 ta, ta0, tb, tb0;\n"
        "setp.ne.b32 p0, 0, 0;\n"
        "setp.eq.b32 p1, 0, 0;\n"
        "add.s64 tb0, %64, %65;\n"
        "add.s64 tb, tb0, 0;\n"
        "wgmma.mma_async.sync.aligned.m64n96k16.f32.bf16.bf16 {%0, %1, %2, %3, %4, %5, %6, %7, %8, %9, %10, %11, %12, %13, %14, %15, %16, %17, %18, %19, %20, %21, %22, %23, %24, %25, %26, %27, %28, %29, %30, %31, %32, %33, %34, %35, %36, %37, %38, %39, %40, %41, %42, %43, %44, %45, %46, %47}, {%48, %49, %50, %51}, tb, p0, 1, 1, 1;\n"
        "add.s64 tb, tb0, 32;\n"
        "wgmma.mma_async.sync.aligned.m64n96k16.f32.bf16.bf16 {%0, %1, %2, %3, %4, %5, %6, %7, %8, %9, %10, %11, %12, %13, %14, %15, %16, %17, %18, %19, %20, %21, %22, %23, %24, %25, %26, %27, %28, %29, %30, %31, %32, %33, %34, %35, %36, %37, %38, %39, %40, %41, %42, %43, %44, %45, %46, %47}, {%52, %53, %54, %55}, tb, p1, 1, 1, 1;\n"
        "add.s64 tb, tb0, 64;\n"
        "wgmma.mma_async.sync.aligned.m64n96k16.f32.bf16.bf16 {%0, %1, %2, %3, %4, %5, %6, %7, %8, %9, %10, %11, %12, %13, %14, %15, %16, %17, %18, %19, %20, %21, %22, %23, %24, %25, %26, %27, %28, %29, %30, %31, %32, %33, %34, %35, %36, %37, %38, %39, %40, %41, %42, %43, %44, %45, %46, %47}, {%56, %57, %58, %59}, tb, p1, 1, 1, 1;\n"
        "add.s64 tb, tb0, 96;\n"
        "wgmma.mma_async.sync.aligned.m64n96k16.f32.bf16.bf16 {%0, %1, %2, %3, %4, %5, %6, %7, %8, %9, %10, %11, %12, %13, %14, %15, %16, %17, %18, %19, %20, %21, %22, %23, %24, %25, %26, %27, %28, %29, %30, %31, %32, %33, %34, %35, %36, %37, %38, %39, %40, %41, %42, %43, %44, %45, %46, %47}, {%60, %61, %62, %63}, tb, p1, 1, 1, 1;\n"
        "}\n"
        : "=f"(d[0]), "=f"(d[1]), "=f"(d[2]), "=f"(d[3]), "=f"(d[4]), "=f"(d[5]), "=f"(d[6]), "=f"(d[7]), "=f"(d[8]), "=f"(d[9]), "=f"(d[10]), "=f"(d[11]), "=f"(d[12]), "=f"(d[13]), "=f"(d[14]), "=f"(d[15]), "=f"(d[16]), "=f"(d[17]), "=f"(d[18]), "=f"(d[19]), "=f"(d[20]), "=f"(d[21]), "=f"(d[22]), "=f"(d[23]), "=f"(d[24]), "=f"(d[25]), "=f"(d[26]), "=f"(d[27]), "=f"(d[28]), "=f"(d[29]), "=f"(d[30]), "=f"(d[31]), "=f"(d[32]), "=f"(d[33]), "=f"(d[34]), "=f"(d[35]), "=f"(d[36]), "=f"(d[37]), "=f"(d[38]), "=f"(d[39]), "=f"(d[40]), "=f"(d[41]), "=f"(d[42]), "=f"(d[43]), "=f"(d[44]), "=f"(d[45]), "=f"(d[46]), "=f"(d[47])
        : "r"(a[AOFF + 0][0]), "r"(a[AOFF + 0][1]), "r"(a[AOFF + 0][2]), "r"(a[AOFF + 0][3]), "r"(a[AOFF + 1][0]), "r"(a[AOFF + 1][1]), "r"(a[AOFF + 1][2]), "r"(a[AOFF + 1][3]), "r"(a[AOFF + 2][0]), "r"(a[AOFF + 2][1]), "r"(a[AOFF + 2][2]), "r"(a[AOFF + 2][3]), "r"(a[AOFF + 3][0]), "r"(a[AOFF + 3][1]), "r"(a[AOFF + 3][2]), "r"(a[AOFF + 3][3]), "l"(descB), "n"(BOFF >> 4));
}
};
template <> struct Rng<0, 0, 5> {
template <int BOFF, int AOFF, int NA>
static __device__ __forceinline__ void run(float (&d)[48], const uint32_t (&a)[NA][4], uint64_t descB) {
    asm volatile(
        "{\n"
        ".reg .pred p0, p1;\n"
        ".reg .b64 ta, ta0, tb, tb0;\n"
        "setp.ne.b32 p0, 0, 0;\n"
        "setp.eq.b32 p1, 0, 0;\n"
        "add.s64 tb0, %68, %69;\n"
        "add.s64 tb, tb0, 0;\n"
        "wgmma.mma_async.sync.aligned.m64n96k16.f32.bf16.bf16 {%0, %1, %2, %3, %4, %5, %6, %7, %8, %9, %10, %11, %12, %13, %14, %15, %16, %17, %18, %19, %20, %21, %22, %23, %24, %25, %26, %27, %28, %29, %30, %31, %32, %33, %34, %35, %36, %37, %38, %39, %40, %41, %42, %43, %44, %45, %46, %47}, {%48, %49, %50, %51}, tb, p0, 1, 1, 1;\n"
        "add.s64 tb, tb0, 32;\n"
        "wgmma.mma_async.sync.aligned.m64n96k16.f32.bf16.bf16 {%0, %1, %2, %3, %4, %5, %6, %7, %8, %9, %10, %11, %12, %13, %14, %15, %16, %17, %18, %19, %20, %21, %22, %23, %24, %25, %26, %27, %28, %29, %30, %31, %32, %33, %34, %35, %36, %37, %38, %39, %40, %41, %42, %43, %44, %45, %46, %47}, {%52, %53, %54, %55}, tb, p1, 1, 1, 1;\n"
        "add.s64 tb, tb0, 64;\n"
        "wgmma.mma_async.sync.aligned.m64n96k16.f32.bf16.bf16 {%0, %1, %2, %3, %4, %5, %6, %7, %8, %9, %10, %11, %12, %13, %14, %15, %16, %17, %18, %19, %20, %21, %22, %23, %24, %25, %26, %27, %28, %29, %30, %31, %32, %33, %34, %35, %36, %37, %38, %39, %40, %41, %42, %43, %44, %45, %46, %47}, {%56, %57, %58, %59}, tb, p1, 1, 1, 1;\n"
        "add.s64 tb, tb0, 96;\n"
        "wgmma.mma_async.sync.aligned.m64n96k16.f32.bf16.bf16 {%0, %1, %2, %3, %4, %5, %6, %7, %8, %9, %10, %11, %12, %13, %14, %15, %16, %17, %18, %19, %20, %21, %22, %23, %24, %25, %26, %27, %28, %29, %30, %31, %32, %33, %34, %35, %36, %37, %38, %39, %40, %41, %42, %43, %44, %45, %46, %47}, {%60, %61, %62, %63}, tb, p1, 1, 1, 1;\n"
        "add.s64 tb, tb0, 1536;\n"
        "wgmma.mma_async.sync.aligned.m64n96k16.f32.bf16.bf16 {%0, %1, %2, %3, %4, %5, %6, %7, %8, %9, %10, %11, %12, %13, %14, %15, %16, %17, %18, %19, %20, %21, %22, %23, %24, %25, %26, %27, %28, %29, %30, %31, %32, %33, %34, %35, %36, %37, %38, %39, %40, %41, %42, %43, %44, %45, %46, %47}, {%64, %65, %66, %67}, tb, p1, 1, 1, 1;\n"
        "}\n"
        : "=f"(d[0]), "=f"(d[1]), "=f"(d[2]), "=f"(d[3]), "=f"(d[4]), "=f"(d[5]), "=f"(d[6]), "=f"(d[7]), "=f"(d[8]), "=f"(d[9]), "=f"(d[10]), "=f"(d[11]), "=f"(d[12]), "=f"(d[13]), "=f"(d[14]), "=f"(d[15]), "=f"(d[16]), "=f"(d[17]), "=f"(d[18]), "=f"(d[19]), "=f"(d[20]), "=f"(d[21]), "=f"(d[22]), "=f"(d[23]), "=f"(d[24]), "=f"(d[25]), "=f"(d[26]), "=f"(d[27]), "=f"(d[28]), "=f"(d[29]), "=f"(d[30]), "=f"(d[31]), "=f"(d[32]), "=f"(d[33]), "=f"(d[34]), "=f"(d[35]), "=f"(d[36]), "=f"(d[37]), "=f"(d[38]), "=f"(d[39]), "=f"(d[40]), "=f"(d[41]), "=f"(d[42]), "=f"(d[43]), "=f"(d[44]), "=f"(d[45]), "=f"(d[46]), "=f"(d[47])
        : "r"(a[AOFF + 0][0]), "r"(a[AOFF + 0][1]), "r"(a[AOFF + 0][2]), "r"(a[AOFF + 0][3]), "r"(a[AOFF + 1][0]), "r"(a[AOFF + 1][1]), "r"(a[AOFF + 1][2]), "r"(a[AOFF + 1][3]), "r"(a[AOFF + 2][0]), "r"(a[AOFF + 2][1]), "r"(a[AOFF + 2][2]), "r"(a[AOFF + 2][3]), "r"(a[AOFF + 3][0]), "r"(a[AOFF + 3][1]), "r"(a[AOFF + 3][2]), "r"(a[AOFF + 3][3]), "r"(a[AOFF + 4][0]), "r"(a[AOFF + 4][1]), "r"(a[AOFF + 4][2]), "r"(a[AOFF + 4][3]), "l"(descB), "n"(BOFF >> 4));
}
};
template <> struct Rng<1, 0, 5> {
template <int BOFF, int AOFF, int NA>
static __device__ __forceinline__ void run(float (&d)[48], const uint32_t (&a)[NA][4], uint64_t descB) {
    asm volatile(
        "{\n"
        ".reg .pred p0, p1;\n"
        ".reg .b64 ta, ta0, tb, tb0;\n"
        "setp.ne.b32 p0, 0, 0;\n"
        "setp.eq.b32 p1, 0, 0;\n"
        "add.s64 tb0, %68, %69;\n"
        "add.s64 tb, tb0, 0;\n"
        "wgmma.mma_async.sync.aligned.m64n96k16.f32.bf16.bf16 {%0, %1, %2, %3, %4, %5, %6, %7, %8, %9, %10, %11, %12, %13, %14, %15, %16, %17, %18, %19, %20, %21, %22, %23, %24, %25, %26, %27, %28, %29, %30, %31, %32, %33, %34, %35, %36, %37, %38, %39, %40, %41, %42, %43, %44, %45, %46, %47}, {%48, %49, %50, %51}, tb, p0, 1, 1, 1;\n"
        "add.s64 tb, tb0, 32;\n"
        "wgmma.mma_async.sync.aligned.m64n96k16.f32.bf16.bf16 {%0, %1, %2, %3, %4, %5, %6, %7, %8, %9, %10, %11, %12, %13, %14, %15, %16, %17, %18, %19, %20, %21, %22, %23, %24, %25, %26, %27, %28, %29, %30, %31, %32, %33, %34, %35, %36, %37, %38, %39, %40, %41, %42, %43, %44, %45, %46, %47}, {%52, %53, %54, %55}, tb, p1, 1, 1, 1;\n"
        "add.s64 tb, tb0, 64;\n"
        "wgmma.mma_async.sync.aligned.m64n96k16.f32.bf16.bf16 {%0, %1, %2, %3, %4, %5, %6, %7, %8, %9, %10, %11, %12, %13, %14, %15, %16, %17, %18, %19, %20, %21, %22, %23, %24, %25, %26, %27, %28, %29, %30, %31, %32, %33, %34, %35, %36, %37, %38, %39, %40, %41, %42, %43, %44, %45, %46, %47}, {%56, %57, %58, %59}, tb, p1, 1, 1, 1;\n"
        "add.s64 tb, tb0, 96;\n"
        "wgmma.mma_async.sync.aligned.m64n96k16.f32.bf16.bf16 {%0, %1, %2, %3, %4, %5, %6, %7, %8, %9, %10, %11, %12, %13, %14, %15, %16, %17, %18, %19, %20, %21, %22, %23, %24, %25, %26, %27, %28, %29, %30, %31, %32, %33, %34, %35, %36, %37, %38, %39, %40, %41, %42, %43, %44, %45, %46, %47}, {%60, %61, %62, %63}, tb, p1, 1, 1, 1;\n"
        "add.s64 tb, tb0, 128;\n"
        "wgmma.mma_async.sync.aligned.m64n96k16.f32.bf16.bf16 {%0, %1, %2, %3, %4, %5, %6, %7, %8, %9, %10, %11, %12, %13, %14, %15, %16, %17, %18, %19, %20, %21, %22, %23, %24, %25, %26, %27, %28, %29, %30, %31, %32, %33, %34, %35, %36, %37, %38, %39, %40, %41, %42, %43, %44, %45, %46, %47}, {%64, %65, %66, %67}, tb, p1, 1, 1, 1;\n"
        "}\n"
        : "=f"(d[0]), "=f"(d[1]), "=f"(d[2]), "=f"(d[3]), "=f"(d[4]), "=f"(d[5]), "=f"(d[6]), "=f"(d[7]), "=f"(d[8]), "=f"(d[9]), "=f"(d[10]), "=f"(d[11]), "=f"(d[12]), "=f"(d[13]), "=f"(d[14]), "=f"(d[15]), "=f"(d[16]), "=f"(d[17]), "=f"(d[18]), "=f"(d[19]), "=f"(d[20]), "=f"(d[21]), "=f"(d[22]), "=f"(d[23]), "=f"(d[24]), "=f"(d[25]), "=f"(d[26]), "=f"(d[27]), "=f"(d[28]), "=f"(d[29]), "=f"(d[30]), "=f"(d[31]), "=f"(d[32]), "=f"(d[33]), "=f"(d[34]), "=f"(d[35]), "=f"(d[36]), "=f"(d[37]), "=f"(d[38]), "=f"(d[39]), "=f"(d[40]), "=f"(d[41]), "=f"(d[42]), "=f"(d[43]), "=f"(d[44]), "=f"(d[45]), "=f"(d[46]), "=f"(d[47])
        : "r"(a[AOFF + 0][0]), "r"(a[AOFF + 0][1]), "r"(a[AOFF + 0][2]), "r"(a[AOFF + 0][3]), "r"(a[AOFF + 1][0]), "r"(a[AOFF + 1][1]), "r"(a[AOFF + 1][2]), "r"(a[AOFF + 1][3]), "r"(a[AOFF + 2][0]), "r"(a[AOFF + 2][1]), "r"(a[AOFF + 2][2]), "r"(a[AOFF + 2][3]), "r"(a[AOFF + 3][0]), "r"(a[AOFF + 3][1]), "r"(a[AOFF + 3][2]), "r"(a[AOFF + 3][3]), "r"(a[AOFF + 4][0]), "r"(a[AOFF + 4][1]), "r"(a[AOFF + 4][2]), "r"(a[AOFF + 4][3]), "l"(descB), "n"(BOFF >> 4));
}
};
template <> struct Rng<0, 0, 6> {
template <int BOFF, int AOFF, int NA>
static __device__ __forceinline__ void run(float (&d)[48], const uint32_t (&a)[NA][4], uint64_t descB) {
    asm volatile(
        "{\n"
        ".reg .pred p0, p1;\n"
        ".reg .b64 ta, ta0, tb, tb0;\n"
        "setp.ne.b32 p0, 0, 0;\n"
        "setp.eq.b32 p1, 0, 0;\n"
        "add.s64 tb0, %72, %73;\n"
        "add.s64 tb, tb0, 0;\n"
        "wgmma.mma_async.sync.aligned.m64n96k16.f32.bf16.bf16 {%0, %1, %2, %3, %4, %5, %6, %7, %8, %9, %10, %11, %12, %13, %14, %15, %16, %17, %18, %19, %20, %21, %22, %23, %24, %25, %26, %27, %28, %29, %30, %31, %32, %33, %34, %35, %36, %37, %38, %39, %40, %41, %42, %43, %44, %45, %46, %47}, {%48, %49, %50, %51}, tb, p0, 1, 1, 1;\n"
        "add.s64 tb, tb0, 32;\n"
        "wgmma.mma_async.sync.aligned.m64n96k16.f32.bf16.bf16 {%0, %1, %2, %3, %4, %5, %6, %7, %8, %9, %10, %11, %12, %13, %14, %15, %16, %17, %18, %19, %20, %21, %22, %23, %24, %25, %26, %27, %28, %29, %30, %31, %32, %33, %34, %35, %36, %37, %38, %39, %40, %41, %42, %43, %44, %45, %46, %47}, {%52, %53, %54, %55}, tb, p1, 1, 1, 1;\n"
        "add.s64 tb, tb0, 64;\n"
        "wgmma.mma_async.sync.aligned.m64n96k16.f32.bf16.bf16 {%0, %1, %2, %3, %4, %5, %6, %7, %8, %9, %10, %11, %12, %13, %14, %15, %16, %17, %18, %19, %20, %21, %22, %23, %24, %25, %26, %27, %28, %29, %30, %31, %32, %33, %34, %35, %36, %37, %38, %39, %40, %41, %42, %43, %44, %45, %46, %47}, {%56, %57, %58, %59}, tb, p1, 1, 1, 1;\n"
        "add.s64 tb, tb0, 96;\n"
        "wgmma.mma_async.sync.aligned.m64n96k16.f32.bf16.bf16 {%0, %1, %2, %3, %4, %5, %6, %7, %8, %9, %10, %11, %12, %13, %14, %15, %16, %17, %18, %19, %20, %21, %22, %23, %24, %25, %26, %27, %28, %29, %30, %31, %32, %33, %34, %35, %36, %37, %38, %39, %40, %41, %42, %43, %44, %45, %46, %47}, {%60, %61, %62, %63}, tb, p1, 1, 1, 1;\n"
        "add.s64 tb, tb0, 1536;\n"
        "wgmma.mma_async.sync.aligned.m64n96k16.f32.bf16.bf16 {%0, %1, %2, %3, %4, %5, %6, %7, %8, %9, %10, %11, %12, %13, %14, %15, %16, %17, %18, %19, %20, %21, %22, %23, %24, %25, %26, %27, %28, %29, %30, %31, %32, %33, %34, %35, %36, %37, %38, %39, %40, %41, %42, %43, %44, %45, %46, %47}, {%64, %65, %66, %67}, tb, p1, 1, 1, 1;\n"
        "add.s64 tb, tb0, 1568;\n"
        "wgmma.mma_async.sync.aligned.m64n96k16.f32.bf16.bf16 {%0, %1, %2, %3, %4, %5, %6, %7, %8, %9, %10, %11, %12, %13, %14, %15, %16, %17, %18, %19, %20, %21, %22, %23, %24, %25, %26, %27, %28, %29, %30, %31, %32, %33, %34, %35, %36, %37, %38, %39, %40, %41, %42, %43, %44, %45, %46, %47}, {%68, %69, %70, %71}, tb, p1, 1, 1, 1;\n"
        "}\n"
        : "=f"(d[0]), "=f"(d[1]), "=f"(d[2]), "=f"(d[3]), "=f"(d[4]), "=f"(d[5]), "=f"(d[6]), "=f"(d[7]), "=f"(d[8]), "=f"(d[9]), "=f"(d[10]), "=f"(d[11]), "=f"(d[12]), "=f"(d[13]), "=f"(d[14]), "=f"(d[15]), "=f"(d[16]), "=f"(d[17]), "=f"(d[18]), "=f"(d[19]), "=f"(d[20]), "=f"(d[21]), "=f"(d[22]), "=f"(d[23]), "=f"(d[24]), "=f"(d[25]), "=f"(d[26]), "=f"(d[27]), "=f"(d[28]), "=f"(d[29]), "=f"(d[30]), "=f"(d[31]), "=f"(d[32]), "=f"(d[33]), "=f"(d[34]), "=f"(d[35]), "=f"(d[36]), "=f"(d[37]), "=f"(d[38]), "=f"(d[39]), "=f"(d[40]), "=f"(d[41]), "=f"(d[42]), "=f"(d[43]), "=f"(d[44]), "=f"(d[45]), "=f"(d[46]), "=f"(d[47])
        : "r"(a[AOFF + 0][0]), "r"(a[AOFF + 0][1]), "r"(a[AOFF + 0][2]), "r"(a[AOFF + 0][3]), "r"(a[AOFF + 1][0]), "r"(a[AOFF + 1][1]), "r"(a[AOFF + 1][2]), "r"(a[AOFF + 1][3]), "r"(a[AOFF + 2][0]), "r"(a[AOFF + 2][1]), "r"(a[AOFF + 2][2]), "r"(a[AOFF + 2][3]), "r"(a[AOFF + 3][0]), "r"(a[AOFF + 3][1]), "r"(a[AOFF + 3][2]), "r"(a[AOFF + 3][3]), "r"(a[AOFF + 4][0]), "r"(a[AOFF + 4][1]), "r"(a[AOFF + 4][2]), "r"(a[AOFF + 4][3]), "r"(a[AOFF + 5][0]), "r"(a[AOFF + 5][1]), "r"(a[AOFF + 5][2]), "r"(a[AOFF + 5][3]), "l"(descB), "n"(BOFF >> 4));
}
};
template <> struct Rng<1, 0, 6> {
template <int BOFF, int AOFF, int NA>
static __device__ __forceinline__ void run(float (&d)[48], const uint32_t (&a)[NA][4], uint64_t descB) {
    asm volatile(
        "{\n"
        ".reg .pred p0, p1;\n"
        ".reg .b64 ta, ta0, tb, tb0;\n"
        "setp.ne.b32 p0, 0, 0;\n"
        "setp.eq.b32 p1, 0, 0;\n"
        "add.s64 tb0, %72, %73;\n"
        "add.s64 tb, tb0, 0;\n"
        "wgmma.mma_async.sync.aligned.m64n96k16.f32.bf16.bf16 {%0, %1, %2, %3, %4, %5, %6, %7, %8, %9, %10, %11, %12, %13, %14, %15, %16, %17, %18, %19, %20, %21, %22, %23, %24, %25, %26, %27, %28, %29, %30, %31, %32, %33, %34, %35, %36, %37, %38, %39, %40, %41, %42, %43, %44, %45, %46, %47}, {%48, %49, %50, %51}, tb, p0, 1, 1, 1;\n"
        "add.s64 tb, tb0, 32;\n"
        "wgmma.mma_async.sync.aligned.m64n96k16.f32.bf16.bf16 {%0, %1, %2, %3, %4, %5, %6, %7, %8, %9, %10, %11, %12, %13, %14, %15, %16, %17, %18, %19, %20, %21, %22, %23, %24, %25, %26, %27, %28, %29, %30, %31, %32, %33, %34, %35, %36, %37, %38, %39, %40, %41, %42, %43, %44, %45, %46, %47}, {%52, %53, %54, %55}, tb, p1, 1, 1, 1;\n"
        "add.s64 tb, tb0, 64;\n"
        "wgmma.mma_async.sync.aligned.m64n96k16.f32.bf16.bf16 {%0, %1, %2, %3, %4, %5, %6, %7, %8, %9, %10, %11, %12, %13, %14, %15, %16, %17, %18, %19, %20, %21, %22, %23, %24, %25, %26, %27, %28, %29, %30, %31, %32, %33, %34, %35, %36, %37, %38, %39, %40, %41, %42, %43, %44, %45, %46, %47}, {%56, %57, %58, %59}, tb, p1, 1, 1, 1;\n"
        "add.s64 tb, tb0, 96;\n"
        "wgmma.mma_async.sync.aligned.m64n96k16.f32.bf16.bf16 {%0, %1, %2, %3, %4, %5, %6, %7, %8, %9, %10, %11, %12, %13, %14, %15, %16, %17, %18, %19, %20, %21, %22, %23, %24, %25, %26, %27, %28, %29, %30, %31, %32, %33, %34, %35, %36, %37, %38, %39, %40, %41, %42, %43, %44, %45, %46, %47}, {%60, %61, %62, %63}, tb, p1, 1, 1, 1;\n"
        "add.s64 tb, tb0, 128;\n"
        "wgmma.mma_async.sync.aligned.m64n96k16.f32.bf16.bf16 {%0, %1, %2, %3, %4, %5, %6, %7, %8, %9, %10, %11, %12, %13, %14, %15, %16, %17, %18, %19, %20, %21, %22, %23, %24, %25, %26, %27, %28, %29, %30, %31, %32, %33, %34, %35, %36, %37, %38, %39, %40, %41, %42, %43, %44, %45, %46, %47}, {%64, %65, %66, %67}, tb, p1, 1, 1, 1;\n"
        "add.s64 tb, tb0, 160;\n"
        "wgmma.mma_async.sync.aligned.m64n96k16.f32.bf16.bf16 {%0, %1, %2, %3, %4, %5, %6, %7, %8, %9, %10, %11, %12, %13, %14, %15, %16, %17, %18, %19, %20, %21, %22, %23, %24, %25, %26, %27, %28, %29, %30, %31, %32, %33, %34, %35, %36, %37, %38, %39, %40, %41, %42, %43, %44, %45, %46, %47}, {%68, %69, %70, %71}, tb, p1, 1, 1, 1;\n"
        "}\n"
        : "=f"(d[0]), "=f"(d[1]), "=f"(d[2]), "=f"(d[3]), "=f"(d[4]), "=f"(d[5]), "=f"(d[6]), "=f"(d[7]), "=f"(d[8]), "=f"(d[9]), "=f"(d[10]), "=f"(d[11]), "=f"(d[12]), "=f"(d[13]), "=f"(d[14]), "=f"(d[15]), "=f"(d[16]), "=f"(d[17]), "=f"(d[18]), "=f"(d[19]), "=f"(d[20]), "=f"(d[21]), "=f"(d[22]), "=f"(d[23]), "=f"(d[24]), "=f"(d[25]), "=f"(d[26]), "=f"(d[27]), "=f"(d[28]), "=f"(d[29]), "=f"(d[30]), "=f"(d[31]), "=f"(d[32]), "=f"(d[33]), "=f"(d[34]), "=f"(d[35]), "=f"(d[36]), "=f"(d[37]), "=f"(d[38]), "=f"(d[39]), "=f"(d[40]), "=f"(d[41]), "=f"(d[42]), "=f"(d[43]), "=f"(d[44]), "=f"(d[45]), "=f"(d[46]), "=f"(d[47])
        : "r"(a[AOFF + 0][0]), "r"(a[AOFF + 0][1]), "r"(a[AOFF + 0][2]), "r"(a[AOFF + 0][3]), "r"(a[AOFF + 1][0]), "r"(a[AOFF + 1][1]), "r"(a[AOFF + 1][2]), "r"(a[AOFF + 1][3]), "r"(a[AOFF + 2][0]), "r"(a[AOFF + 2][1]), "r"(a[AOFF + 2][2]), "r"(a[AOFF + 2][3]), "r"(a[AOFF + 3][0]), "r"(a[AOFF + 3][1]), "r"(a[AOFF + 3][2]), "r"(a[AOFF + 3][3]), "r"(a[AOFF + 4][0]), "r"(a[AOFF + 4][1]), "r"(a[AOFF + 4][2]), "r"(a[AOFF + 4][3]), "r"(a[AOFF + 5][0]), "r"(a[AOFF + 5][1]), "r"(a[AOFF + 5][2]), "r"(a[AOFF + 5][3]), "l"(descB), "n"(BOFF >> 4));
}
};
template <> struct Rng<0, 3, 7> {
template <int BOFF, int AOFF, int NA>
static __device__ __forceinline__ void run(float (&d)[48], const uint32_t (&a)[NA][4], uint64_t descB) {
    asm volatile(
        "{\n"
        ".reg .pred p0, p1;\n"
        ".reg .b64 ta, ta0, tb, tb0;\n"
        "setp.ne.b32 p0, 0, 0;\n"
        "setp.eq.b32 p1, 0, 0;\n"
        "add.s64 tb0, %64, %65;\n"
        "add.s64 tb, tb0, 96;\n"
        "wgmma.mma_async.sync.aligned.m64n96k16.f32.bf16.bf16 {%0, %1, %2, %3, %4, %5, %6, %7, %8, %9, %10, %11, %12, %13, %14, %15, %16, %17, %18, %19, %20, %21, %22, %23, %24, %25, %26, %27, %28, %29, %30, %31, %32, %33, %34, %35, %36, %37, %38, %39, %40, %41, %42, %43, %44, %45, %46, %47}, {%48, %49, %50, %51}, tb, p1, 1, 1, 1;\n"
        "add.s64 tb, tb0, 1536;\n"
        "wgmma.mma_async.sync.aligned.m64n96k16.f32.bf16.bf16 {%0, %1, %2, %3, %4, %5, %6, %7, %8, %9, %10, %11, %12, %13, %14, %15, %16, %17, %18, %19, %20, %21, %22, %23, %24, %25, %26, %27, %28, %29, %30, %31, %32, %33, %34, %35, %36, %37, %38, %39, %40, %41, %42, %43, %44, %45, %46, %47}, {%52, %53, %54, %55}, tb, p1, 1, 1, 1;\n"
        "add.s64 tb, tb0, 1568;\n"
        "wgmma.mma_async.sync.aligned.m64n96k16.f32.bf16.bf16 {%0, %1, %2, %3, %4, %5, %6, %7, %8, %9, %10, %11, %12, %13, %14, %15, %16, %17, %18, %19, %20, %21, %22, %23, %24, %25, %26, %27, %28, %29, %30, %31, %32, %33, %34, %35, %36, %37, %38, %39, %40, %41, %42, %43, %44, %45, %46, %47}, {%56, %57, %58, %59}, tb, p1, 1, 1, 1;\n"
        "add.s64 tb, tb0, 1600;\n"
        "wgmma.mma_async.sync.aligned.m64n96k16.f32.bf16.bf16 {%0, %1, %2, %3, %4, %5, %6, %7, %8, %9, %10, %11, %12, %13, %14, %15, %16, %17, %18, %19, %20, %21, %22, %23, %24, %25, %26, %27, %28, %29, %30, %31, %32, %33, %34, %35, %36, %37, %38, %39, %40, %41, %42, %43, %44, %45, %46, %47}, {%60, %61, %62, %63}, tb, p1, 1, 1, 1;\n"
        "}\n"
        : "+f"(d[0]), "+f"(d[1]), "+f"(d[2]), "+f"(d[3]), "+f"(d[4]), "+f"(d[5]), "+f"(d[6]), "+f"(d[7]), "+f"(d[8]), "+f"(d[9]), "+f"(d[10]), "+f"(d[11]), "+f"(d[12]), "+f"(d[13]), "+f"(d[14]), "+f"(d[15]), "+f"(d[16]), "+f"(d[17]), "+f"(d[18]), "+f"(d[19]), "+f"(d[20]), "+f"(d[21]), "+f"(d[22]), "+f"(d[23]), "+f"(d[24]), "+f"(d[25]), "+f"(d[26]), "+f"(d[27]), "+f"(d[28]), "+f"(d[29]), "+f"(d[30]), "+f"(d[31]), "+f"(d[32]), "+f"(d[33]), "+f"(d[34]), "+f"(d[35]), "+f"(d[36]), "+f"(d[37]), "+f"(d[38]), "+f"(d[39]), "+f"(d[40]), "+f"(d[41]), "+f"(d[42]), "+f"(d[43]), "+f"(d[44]), "+f"(d[45]), "+f"(d[46]), "+f"(d[47])
        : "r"(a[AOFF + 0][0]), "r"(a[AOFF + 0][1]), "r"(a[AOFF + 0][2]), "r"(a[AOFF + 0][3]), "r"(a[AOFF + 1][0]), "r"(a[AOFF + 1][1]), "r"(a[AOFF + 1][2]), "r"(a[AOFF + 1][3]), "r"(a[AOFF + 2][0]), "r"(a[AOFF + 2][1]), "r"(a[AOFF + 2][2]), "r"(a[AOFF + 2][3]), "r"(a[AOFF + 3][0]), "r"(a[AOFF + 3][1]), "r"(a[AOFF + 3][2]), "r"(a[AOFF + 3][3]), "l"(descB), "n"(BOFF >> 4));
}
};
template <> struct Rng<1, 3, 7> {
template <int BOFF, int AOFF, int NA>
static __device__ __forceinline__ void run(float (&d)[48], const uint32_t (&a)[NA][4], uint64_t descB) {
    asm volatile(
        "{\n"
        ".reg .pred p0, p1;\n"
        ".reg .b64 ta, ta0, tb, tb0;\n"
        "setp.ne.b32 p0, 0, 0;\n"
        "setp.eq.b32 p1, 0, 0;\n"
        "add.s64 tb0, %64, %65;\n"
        "add.s64 tb, tb0, 96;\n"
        "wgmma.mma_async.sync.aligned.m64n96k16.f32.bf16.bf16 {%0, %1, %2, %3, %4, %5, %6, %7, %8, %9, %10, %11, %12, %13, %14, %15, %16, %17, %18, %19, %20, %21, %22, %23, %24, %25, %26, %27, %28, %29, %30, %31, %32, %33, %34, %35, %36, %37, %38, %39, %40, %41, %42, %43, %44, %45, %46, %47}, {%48, %49, %50, %51}, tb, p1, 1, 1, 1;\n"
        "add.s64 tb, tb0, 128;\n"
        "wgmma.mma_async.sync.aligned.m64n96k16.f32.bf16.bf16 {%0, %1, %2, %3, %4, %5, %6, %7, %8, %9, %10, %11, %12, %13, %14, %15, %16, %17, %18, %19, %20, %21, %22, %23, %24, %25, %26, %27, %28, %29, %30, %31, %32, %33, %34, %35, %36, %37, %38, %39, %40, %41, %42, %43, %44, %45, %46, %47}, {%52, %53, %54, %55}, tb, p1, 1, 1, 1;\n"
        "add.s64 tb, tb0, 160;\n"
        "wgmma.mma_async.sync.aligned.m64n96k16.f32.bf16.bf16 {%0, %1, %2, %3, %4, %5, %6, %7, %8, %9, %10, %11, %12, %13, %14, %15, %16, %17, %18, %19, %20, %21, %22, %23, %24, %25, %26, %27, %28, %29, %30, %31, %32, %33, %34, %35, %36, %37, %38, %39, %40, %41, %42, %43, %44, %45, %46, %47}, {%56, %57, %58, %59}, tb, p1, 1, 1, 1;\n"
        "add.s64 tb, tb0, 192;\n"
        "wgmma.mma_async.sync.aligned.m64n96k16.f32.bf16.bf16 {%0, %1, %2, %3, %4, %5, %6, %7, %8, %9, %10, %11, %12, %13, %14, %15, %16, %17, %18, %19, %20, %21, %22, %23, %24, %25, %26, %27, %28, %29, %30, %31, %32, %33, %34, %35, %36, %37, %38, %39, %40, %41, %42, %43, %44, %45, %46, %47}, {%60, %61, %62, %63}, tb, p1, 1, 1, 1;\n"
        "}\n"
        : "+f"(d[0]), "+f"(d[1]), "+f"(d[2]), "+f"(d[3]), "+f"(d[4]), "+f"(d[5]), "+f"(d[6]), "+f"(d[7]), "+f"(d[8]), "+f"(d[9]), "+f"(d[10]), "+f"(d[11]), "+f"(d[12]), "+f"(d[13]), "+f"(d[14]), "+f"(d[15]), "+f"(d[16]), "+f"(d[17]), "+f"(d[18]), "+f"(d[19]), "+f"(d[20]), "+f"(d[21]), "+f"(d[22]), "+f"(d[23]), "+f"(d[24]), "+f"(d[25]), "+f"(d[26]), "+f"(d[27]), "+f"(d[28]), "+f"(d[29]), "+f"(d[30]), "+f"(d[31]), "+f"(d[32]), "+f"(d[33]), "+f"(d[34]), "+f"(d[35]), "+f"(d[36]), "+f"(d[37]), "+f"(d[38]), "+f"(d[39]), "+f"(d[40]), "+f"(d[41]), "+f"(d[42]), "+f"(d[43]), "+f"(d[44]), "+f"(d[45]), "+f"(d[46]), "+f"(d[47])
        : "r"(a[AOFF + 0][0]), "r"(a[AOFF + 0][1]), "r"(a[AOFF + 0][2]), "r"(a[AOFF + 0][3]), "r"(a[AOFF + 1][0]), "r"(a[AOFF + 1][1]), "r"(a[AOFF + 1][2]), "r"(a[AOFF + 1][3]), "r"(a[AOFF + 2][0]), "r"(a[AOFF + 2][1]), "r"(a[AOFF + 2][2]), "r"(a[AOFF + 2][3]), "r"(a[AOFF + 3][0]), "r"(a[AOFF + 3][1]), "r"(a[AOFF + 3][2]), "r"(a[AOFF + 3][3]), "l"(descB), "n"(BOFF >> 4));
}
};
template <> struct Rng<0, 3, 8> {
template <int BOFF, int AOFF, int NA>
static __device__ __forceinline__ void run(float (&d)[48], const uint32_t (&a)[NA][4], uint64_t descB) {
    asm volatile(
        "{\n"
        ".reg .pred p0, p1;\n"
        ".reg .b64 ta, ta0, tb, tb0;\n"
        "setp.ne.b32 p0, 0, 0;\n"
        "setp.eq.b32 p1, 0, 0;\n"
        "add.s64 tb0, %68, %69;\n"
        "add.s64 tb, tb0, 96;\n"
        "wgmma.mma_async.sync.aligned.m64n96k16.f32.bf16.bf16 {%0, %1, %2, %3, %4, %5, %6, %7, %8, %9, %10, %11, %12, %13, %14, %15, %16, %17, %18, %19, %20, %21, %22, %23, %24, %25, %26, %27, %28, %29, %30, %31, %32, %33, %34, %35, %36, %37, %38, %39, %40, %41, %42, %43, %44, %45, %46, %47}, {%48, %49, %50, %51}, tb, p1, 1, 1, 1;\n"
        "add.s64 tb, tb0, 1536;\n"
        "wgmma.mma_async.sync.aligned.m64n96k16.f32.bf16.bf16 {%0, %1, %2, %3, %4, %5, %6, %7, %8, %9, %10, %11, %12, %13, %14, %15, %16, %17, %18, %19, %20, %21, %22, %23, %24, %25, %26, %27, %28, %29, %30, %31, %32, %33, %34, %35, %36, %37, %38, %39, %40, %41, %42, %43, %44, %45, %46, %47}, {%52, %53, %54, %55}, tb, p1, 1, 1, 1;\n"
        "add.s64 tb, tb0, 1568;\n"
        "wgmma.mma_async.sync.aligned.m64n96k16.f32.bf16.bf16 {%0, %1, %2, %3, %4, %5, %6, %7, %8, %9, %10, %11, %12, %13, %14, %15, %16, %17, %18, %19, %20, %21, %22, %23, %24, %25, %26, %27, %28, %29, %30, %31, %32, %33, %34, %35, %36, %37, %38, %39, %40, %41, %42, %43, %44, %45, %46, %47}, {%56, %57, %58, %59}, tb, p1, 1, 1, 1;\n"
        "add.s64 tb, tb0, 1600;\n"
        "wgmma.mma_async.sync.aligned.m64n96k16.f32.bf16.bf16 {%0, %1, %2, %3, %4, %5, %6, %7, %8, %9, %10, %11, %12, %13, %14, %15, %16, %17, %18, %19, %20, %21, %22, %23, %24, %25, %26, %27, %28, %29, %30, %31, %32, %33, %34, %35, %36, %37, %38, %39, %40, %41, %42, %43, %44, %45, %46, %47}, {%60, %61, %62, %63}, tb, p1, 1, 1, 1;\n"
        "add.s64 tb, tb0, 1632;\n"
        "wgmma.mma_async.sync.aligned.m64n96k16.f32.bf16.bf16 {%0, %1, %2, %3, %4, %5, %6, %7, %8, %9, %10, %11, %12, %13, %14, %15, %16, %17, %18, %19, %20, %21, %22, %23, %24, %25, %26, %27, %28, %29, %30, %31, %32, %33, %34, %35, %36, %37, %38, %39, %40, %41, %42, %43, %44, %45, %46, %47}, {%64, %65, %66, %67}, tb, p1, 1, 1, 1;\n"
        "}\n"
        : "+f"(d[0]), "+f"(d[1]), "+f"(d[2]), "+f"(d[3]), "+f"(d[4]), "+f"(d[5]), "+f"(d[6]), "+f"(d[7]), "+f"(d[8]), "+f"(d[9]), "+f"(d[10]), "+f"(d[11]), "+f"(d[12]), "+f"(d[13]), "+f"(d[14]), "+f"(d[15]), "+f"(d[16]), "+f"(d[17]), "+f"(d[18]), "+f"(d[19]), "+f"(d[20]), "+f"(d[21]), "+f"(d[22]), "+f"(d[23]), "+f"(d[24]), "+f"(d[25]), "+f"(d[26]), "+f"(d[27]), "+f"(d[28]), "+f"(d[29]), "+f"(d[30]), "+f"(d[31]), "+f"(d[32]), "+f"(d[33]), "+f"(d[34]), "+f"(d[35]), "+f"(d[36]), "+f"(d[37]), "+f"(d[38]), "+f"(d[39]), "+f"(d[40]), "+f"(d[41]), "+f"(d[42]), "+f"(d[43]), "+f"(d[44]), "+f"(d[45]), "+f"(d[46]), "+f"(d[47])
        : "r"(a[AOFF + 0][0]), "r"(a[AOFF + 0][1]), "r"(a[AOFF + 0][2]), "r"(a[AOFF + 0][3]), "r"(a[AOFF + 1][0]), "r"(a[AOFF + 1][1]), "r"(a[AOFF + 1][2]), "r"(a[AOFF + 1][3]), "r"(a[AOFF + 2][0]), "r"(a[AOFF + 2][1]), "r"(a[AOFF + 2][2]), "r"(a[AOFF + 2][3]), "r"(a[AOFF + 3][0]), "r"(a[AOFF + 3][1]), "r"(a[AOFF + 3][2]), "r"(a[AOFF + 3][3]), "r"(a[AOFF + 4][0]), "r"(a[AOFF + 4][1]), "r"(a[AOFF + 4][2]), "r"(a[AOFF + 4][3]), "l"(descB), "n"(BOFF >> 4));
}
};
template <> struct Rng<1, 3, 8> {
template <int BOFF, int AOFF, int NA>
static __device__ __forceinline__ void run(float (&d)[48], const uint32_t (&a)[NA][4], uint64_t descB) {
    asm volatile(
        "{\n"
        ".reg .pred p0, p1;\n"
        ".reg .b64 ta, ta0, tb, tb0;\n"
        "setp.ne.b32 p0, 0, 0;\n"
        "setp.eq.b32 p1, 0, 0;\n"
        "add.s64 tb0, %68, %69;\n"
        "add.s64 tb, tb0, 96;\n"
        "wgmma.mma_async.sync.aligned.m64n96k16.f32.bf16.bf16 {%0, %1, %2, %3, %4, %5, %6, %7, %8, %9, %10, %11, %12, %13, %14, %15, %16, %17, %18, %19, %20, %21, %22, %23, %24, %25, %26, %27, %28, %29, %30, %31, %32, %33, %34, %35, %36, %37, %38, %39, %40, %41, %42, %43, %44, %45, %46, %47}, {%48, %49, %50, %51}, tb, p1, 1, 1, 1;\n"
        "add.s64 tb, tb0, 128;\n"
        "wgmma.mma_async.sync.aligned.m64n96k16.f32.bf16.bf16 {%0, %1, %2, %3, %4, %5, %6, %7, %8, %9, %10, %11, %12, %13, %14, %15, %16, %17, %18, %19, %20, %21, %22, %23, %24, %25, %26, %27, %28, %29, %30, %31, %32, %33, %34, %35, %36, %37, %38, %39, %40, %41, %42, %43, %44, %45, %46, %47}, {%52, %53, %54, %55}, tb, p1, 1, 1, 1;\n"
        "add.s64 tb, tb0, 160;\n"
        "wgmma.mma_async.sync.aligned.m64n96k16.f32.bf16.bf16 {%0, %1, %2, %3, %4, %5, %6, %7, %8, %9, %10, %11, %12, %13, %14, %15, %16, %17, %18, %19, %20, %21, %22, %23, %24, %25, %26, %27, %28, %29, %30, %31, %32, %33, %34, %35, %36, %37, %38, %39, %40, %41, %42, %43, %44, %45, %46, %47}, {%56, %57, %58, %59}, tb, p1, 1, 1, 1;\n"
        "add.s64 tb, tb0, 192;\n"
        "wgmma.mma_async.sync.aligned.m64n96k16.f32.bf16.bf16 {%0, %1, %2, %3, %4, %5, %6, %7, %8, %9, %10, %11, %12, %13, %14, %15, %16, %17, %18, %19, %20, %21, %22, %23, %24, %25, %26, %27, %28, %29, %30, %31, %32, %33, %34, %35, %36, %37, %38, %39, %40, %41, %42, %43, %44, %45, %46, %47}, {%60, %61, %62, %63}, tb, p1, 1, 1, 1;\n"
        "add.s64 tb, tb0, 224;\n"
        "wgmma.mma_async.sync.aligned.m64n96k16.f32.bf16.bf16 {%0, %1, %2, %3, %4, %5, %6, %7, %8, %9, %10, %11, %12, %13, %14, %15, %16, %17, %18, %19, %20, %21, %22, %23, %24, %25, %26, %27, %28, %29, %30, %31, %32, %33, %34, %35, %36, %37, %38, %39, %40, %41, %42, %43, %44, %45, %46, %47}, {%64, %65, %66, %67}, tb, p1, 1, 1, 1;\n"
        "}\n"
        : "+f"(d[0]), "+f"(d[1]), "+f"(d[2]), "+f"(d[3]), "+f"(d[4]), "+f"(d[5]), "+f"(d[6]), "+f"(d[7]), "+f"(d[8]), "+f"(d[9]), "+f"(d[10]), "+f"(d[11]), "+f"(d[12]), "+f"(d[13]), "+f"(d[14]), "+f"(d[15]), "+f"(d[16]), "+f"(d[17]), "+f"(d[18]), "+f"(d[19]), "+f"(d[20]), "+f"(d[21]), "+f"(d[22]), "+f"(d[23]), "+f"(d[24]), "+f"(d[25]), "+f"(d[26]), "+f"(d[27]), "+f"(d[28]), "+f"(d[29]), "+f"(d[30]), "+f"(d[31]), "+f"(d[32]), "+f"(d[33]), "+f"(d[34]), "+f"(d[35]), "+f"(d[36]), "+f"(d[37]), "+f"(d[38]), "+f"(d[39]), "+f"(d[40]), "+f"(d[41]), "+f"(d[42]), "+f"(d[43]), "+f"(d[44]), "+f"(d[45]), "+f"(d[46]), "+f"(d[47])
        : "r"(a[AOFF + 0][0]), "r"(a[AOFF + 0][1]), "r"(a[AOFF + 0][2]), "r"(a[AOFF + 0][3]), "r"(a[AOFF + 1][0]), "r"(a[AOFF + 1][1]), "r"(a[AOFF + 1][2]), "r"(a[AOFF + 1][3]), "r"(a[AOFF + 2][0]), "r"(a[AOFF + 2][1]), "r"(a[AOFF + 2][2]), "r"(a[AOFF + 2][3]), "r"(a[AOFF + 3][0]), "r"(a[AOFF + 3][1]), "r"(a[AOFF + 3][2]), "r"(a[AOFF + 3][3]), "r"(a[AOFF + 4][0]), "r"(a[AOFF + 4][1]), "r"(a[AOFF + 4][2]), "r"(a[AOFF + 4][3]), "l"(descB), "n"(BOFF >> 4));
}
};
template <> struct Rng<0, 3, 12> {
template <int BOFF, int AOFF, int NA>
static __device__ __forceinline__ void run(float (&d)[48], const uint32_t (&a)[NA][4], uint64_t descB) {
    asm volatile(
        "{\n"
        ".reg .pred p0, p1;\n"
        ".reg .b64 ta, ta0, tb, tb0;\n"
        "setp.ne.b32 p0, 0, 0;\n"
        "setp.eq.b32 p1, 0, 0;\n"
        "add.s64 tb0, %84, %85;\n"
        "add.s64 tb, tb0, 96;\n"
        "wgmma.mma_async.sync.aligned.m64n96k16.f32.bf16.bf16 {%0, %1, %2, %3, %4, %5, %6, %7, %8, %9, %10, %11, %12, %13, %14, %15, %16, %17, %18, %19, %20, %21, %22, %23, %24, %25, %26, %27, %28, %29, %30, %31, %32, %33, %34, %35, %36, %37, %38, %39, %40, %41, %42, %43, %44, %45, %46, %47}, {%48, %49, %50, %51}, tb, p1, 1, 1, 1;\n"
        "add.s64 tb, tb0, 1536;\n"
        "wgmma.mma_async.sync.aligned.m64n96k16.f32.bf16.bf16 {%0, %1, %2, %3, %4, %5, %6, %7, %8, %9, %10, %11, %12, %13, %14, %15, %16, %17, %18, %19, %20, %21, %22, %23, %24, %25, %26, %27, %28, %29, %30, %31, %32, %33, %34, %35, %36, %37, %38, %39, %40, %41, %42, %43, %44, %45, %46, %47}, {%52, %53, %54, %55}, tb, p1, 1, 1, 1;\n"
        "add.s64 tb, tb0, 1568;\n"
        "wgmma.mma_async.sync.aligned.m64n96k16.f32.bf16.bf16 {%0, %1, %2, %3, %4, %5, %6, %7, %8, %9, %10, %11, %12, %13, %14, %15, %16, %17, %18, %19, %20, %21, %22, %23, %24, %25, %26, %27, %28, %29, %30, %31, %32, %33, %34, %35, %36, %37, %38, %39, %40, %41, %42, %43, %44, %45, %46, %47}, {%56, %57, %58, %59}, tb, p1, 1, 1, 1;\n"
        "add.s64 tb, tb0, 1600;\n"
        "wgmma.mma_async.sync.aligned.m64n96k16.f32.bf16.bf16 {%0, %1, %2, %3, %4, %5, %6, %7, %8, %9, %10, %11, %12, %13, %14, %15, %16, %17, %18, %19, %20, %21, %22, %23, %24, %25, %26, %27, %28, %29, %30, %31, %32, %33, %34, %35, %36, %37, %38, %39, %40, %41, %42, %43, %44, %45, %46, %47}, {%60, %61, %62, %63}, tb, p1, 1, 1, 1;\n"
        "add.s64 tb, tb0, 1632;\n"
        "wgmma.mma_async.sync.aligned.m64n96k16.f32.bf16.bf16 {%0, %1, %2, %3, %4, %5, %6, %7, %8, %9, %10, %11, %12, %13, %14, %15, %16, %17, %18, %19, %20, %21, %22, %23, %24, %25, %26, %27, %28, %29, %30, %31, %32, %33, %34, %35, %36, %37, %38, %39, %40, %41, %42, %43, %44, %45, %46, %47}, {%64, %65, %66, %67}, tb, p1, 1, 1, 1;\n"
        "add.s64 tb, tb0, 3072;\n"
        "wgmma.mma_async.sync.aligned.m64n96k16.f32.bf16.bf16 {%0, %1, %2, %3, %4, %5, %6, %7, %8, %9, %10, %11, %12, %13, %14, %15, %16, %17, %18, %19, %20, %21, %22, %23, %24, %25, %26, %27, %28, %29, %30, %31, %32, %33, %34, %35, %36, %37, %38, %39, %40, %41, %42, %43, %44, %45, %46, %47}, {%68, %69, %70, %71}, tb, p1, 1, 1, 1;\n"
        "add.s64 tb, tb0, 3104;\n"
        "wgmma.mma_async.sync.aligned.m64n96k16.f32.bf16.bf16 {%0, %1, %2, %3, %4, %5, %6, %7, %8, %9, %10, %11, %12, %13, %14, %15, %16, %17, %18, %19, %20, %21, %22, %23, %24, %25, %26, %27, %28, %29, %30, %31, %32, %33, %34, %35, %36, %37, %38, %39, %40, %41, %42, %43, %44, %45, %46, %47}, {%72, %73, %74, %75}, tb, p1, 1, 1, 1;\n"
        "add.s64 tb, tb0, 3136;\n"
        "wgmma.mma_async.sync.aligned.m64n96k16.f32.bf16.bf16 {%0, %1, %2, %3, %4, %5, %6, %7, %8, %9, %10, %11, %12, %13, %14, %15, %16, %17, %18, %19, %20, %21, %22, %23, %24, %25, %26, %27, %28, %29, %30, %31, %32, %33, %34, %35, %36, %37, %38, %39, %40, %41, %42, %43, %44, %45, %46, %47}, {%76, %77, %78, %79}, tb, p1, 1, 1, 1;\n"
        "add.s64 tb, tb0, 3168;\n"
        "wgmma.mma_async.sync.aligned.m64n96k16.f32.bf16.bf16 {%0, %1, %2, %3, %4, %5, %6, %7, %8, %9, %10, %11, %12, %13, %14, %15, %16, %17, %18, %19, %20, %21, %22, %23, %24, %25, %26, %27, %28, %29, %30, %31, %32, %33, %34, %35, %36, %37, %38, %39, %40, %41, %42, %43, %44, %45, %46, %47}, {%80, %81, %82, %83}, tb, p1, 1, 1, 1;\n"
        "}\n"
        : "+f"(d[0]), "+f"(d[1]), "+f"(d[2]), "+f"(d[3]), "+f"(d[4]), "+f"(d[5]), "+f"(d[6]), "+f"(d[7]), "+f"(d[8]), "+f"(d[9]), "+f"(d[10]), "+f"(d[11]), "+f"(d[12]), "+f"(d[13]), "+f"(d[14]), "+f"(d[15]), "+f"(d[16]), "+f"(d[17]), "+f"(d[18]), "+f"(d[19]), "+f"(d[20]), "+f"(d[21]), "+f"(d[22]), "+f"(d[23]), "+f"(d[24]), "+f"(d[25]), "+f"(d[26]), "+f"(d[27]), "+f"(d[28]), "+f"(d[29]), "+f"(d[30]), "+f"(d[31]), "+f"(d[32]), "+f"(d[33]), "+f"(d[34]), "+f"(d[35]), "+f"(d[36]), "+f"(d[37]), "+f"(d[38]), "+f"(d[39]), "+f"(d[40]), "+f"(d[41]), "+f"(d[42]), "+f"(d[43]), "+f"(d[44]), "+f"(d[45]), "+f"(d[46]), "+f"(d[47])
        : "r"(a[AOFF + 0][0]), "r"(a[AOFF + 0][1]), "r"(a[AOFF + 0][2]), "r"(a[AOFF + 0][3]), "r"(a[AOFF + 1][0]), "r"(a[AOFF + 1][1]), "r"(a[AOFF + 1][2]), "r"(a[AOFF + 1][3]), "r"(a[AOFF + 2][0]), "r"(a[AOFF + 2][1]), "r"(a[AOFF + 2][2]), "r"(a[AOFF + 2][3]), "r"(a[AOFF + 3][0]), "r"(a[AOFF + 3][1]), "r"(a[AOFF + 3][2]), "r"(a[AOFF + 3][3]), "r"(a[AOFF + 4][0]), "r"(a[AOFF + 4][1]), "r"(a[AOFF + 4][2]), "r"(a[AOFF + 4][3]), "r"(a[AOFF + 5][0]), "r"(a[AOFF + 5][1]), "r"(a[AOFF + 5][2]), "r"(a[AOFF + 5][3]), "r"(a[AOFF + 6][0]), "r"(a[AOFF + 6][1]), "r"(a[AOFF + 6][2]), "r"(a[AOFF + 6][3]), "r"(a[AOFF + 7][0]), "r"(a[AOFF + 7][1]), "r"(a[AOFF + 7][2]), "r"(a[AOFF + 7][3]), "r"(a[AOFF + 8][0]), "r"(a[AOFF + 8][1]), "r"(a[AOFF + 8][2]), "r"(a[AOFF + 8][3]), "l"(descB), "n"(BOFF >> 4));
}
};
template <> struct Rng<1, 3, 12> {
template <int BOFF, int AOFF, int NA>
static __device__ __forceinline__ void run(float (&d)[48], const uint32_t (&a)[NA][4], uint64_t descB) {
    asm volatile(
        "{\n"
        ".reg .pred p0, p1;\n"
        ".reg .b64 ta, ta0, tb, tb0;\n"
        "setp.ne.b32 p0, 0, 0;\n"
        "setp.eq.b32 p1, 0, 0;\n"
        "add.s64 tb0, %84, %85;\n"
        "add.s64 tb, tb0, 96;\n"
        "wgmma.mma_async.sync.aligned.m64n96k16.f32.bf16.bf16 {%0, %1, %2, %3, %4, %5, %6, %7, %8, %9, %10, %11, %12, %13, %14, %15, %16, %17, %18, %19, %20, %21, %22, %23, %24, %25, %26, %27, %28, %29, %30, %31, %32, %33, %34, %35, %36, %37, %38, %39, %40, %41, %42, %43, %44, %45, %46, %47}, {%48, %49, %50, %51}, tb, p1, 1, 1, 1;\n"
        "add.s64 tb, tb0, 128;\n"
        "wgmma.mma_async.sync.aligned.m64n96k16.f32.bf16.bf16 {%0, %1, %2, %3, %4, %5, %6, %7, %8, %9, %10, %11, %12, %13, %14, %15, %16, %17, %18, %19, %20, %21, %22, %23, %24, %25, %26, %27, %28, %29, %30, %31, %32, %33, %34, %35, %36, %37, %38, %39, %40, %41, %42, %43, %44, %45, %46, %47}, {%52, %53, %54, %55}, tb, p1, 1, 1, 1;\n"
        "add.s64 tb, tb0, 160;\n"
        "wgmma.mma_async.sync.aligned.m64n96k16.f32.bf16.bf16 {%0, %1, %2, %3, %4, %5, %6, %7, %8, %9, %10, %11, %12, %13, %14, %15, %16, %17, %18, %19, %20, %21, %22, %23, %24, %25, %26, %27, %28, %29, %30, %31, %32, %33, %34, %35, %36, %37, %38, %39, %40, %41, %42, %43, %44, %45, %46, %47}, {%56, %57, %58, %59}, tb, p1, 1, 1, 1;\n"
        "add.s64 tb, tb0, 192;\n"
        "wgmma.mma_async.sync.aligned.m64n96k16.f32.bf16.bf16 {%0, %1, %2, %3, %4, %5, %6, %7, %8, %9, %10, %11, %12, %13, %14, %15, %16, %17, %18, %19, %20, %21, %22, %23, %24, %25, %26, %27, %28, %29, %30, %31, %32, %33, %34, %35, %36, %37, %38, %39, %40, %41, %42, %43, %44, %45, %46, %47}, {%60, %61, %62, %63}, tb, p1, 1, 1, 1;\n"
        "add.s64 tb, tb0, 224;\n"
        "wgmma.mma_async.sync.aligned.m64n96k16.f32.bf16.bf16 {%0, %1, %2, %3, %4, %5, %6, %7, %8, %9, %10, %11, %12, %13, %14, %15, %16, %17, %18, %19, %20, %21, %22, %23, %24, %25, %26, %27, %28, %29, %30, %31, %32, %33, %34, %35, %36, %37, %38, %39, %40, %41, %42, %43, %44, %45, %46, %47}, {%64, %65, %66, %67}, tb, p1, 1, 1, 1;\n"
        "add.s64 tb, tb0, 256;\n"
        "wgmma.mma_async.sync.aligned.m64n96k16.f32.bf16.bf16 {%0, %1, %2, %3, %4, %5, %6, %7, %8, %9, %10, %11, %12, %13, %14, %15, %16, %17, %18, %19, %20, %21, %22, %23, %24, %25, %26, %27, %28, %29, %30, %31, %32, %33, %34, %35, %36, %37, %38, %39, %40, %41, %42, %43, %44, %45, %46, %47}, {%68, %69, %70, %71}, tb, p1, 1, 1, 1;\n"
        "add.s64 tb, tb0, 288;\n"
        "wgmma.mma_async.sync.aligned.m64n96k16.f32.bf16.bf16 {%0, %1, %2, %3, %4, %5, %6, %7, %8, %9, %10, %11, %12, %13, %14, %15, %16, %17, %18, %19, %20, %21, %22, %23, %24, %25, %26, %27, %28, %29, %30, %31, %32, %33, %34, %35, %36, %37, %38, %39, %40, %41, %42, %43, %44, %45, %46, %47}, {%72, %73, %74, %75}, tb, p1, 1, 1, 1;\n"
        "add.s64 tb, tb0, 320;\n"
        "wgmma.mma_async.sync.aligned.m64n96k16.f32.bf16.bf16 {%0, %1, %2, %3, %4, %5, %6, %7, %8, %9, %10, %11, %12, %13, %14, %15, %16, %17, %18, %19, %20, %21, %22, %23, %24, %25, %26, %27, %28, %29, %30, %31, %32, %33, %34, %35, %36, %37, %38, %39, %40, %41, %42, %43, %44, %45, %46, %47}, {%76, %77, %78, %79}, tb, p1, 1, 1, 1;\n"
        "add.s64 tb, tb0, 352;\n"
        "wgmma.mma_async.sync.aligned.m64n96k16.f32.bf16.bf16 {%0, %1, %2, %3, %4, %5, %6, %7, %8, %9, %10, %11, %12, %13, %14, %15, %16, %17, %18, %19, %20, %21, %22, %23, %24, %25, %26, %27, %28, %29, %30, %31, %32, %33, %34, %35, %36, %37, %38, %39, %40, %41, %42, %43, %44, %45, %46, %47}, {%80, %81, %82, %83}, tb, p1, 1, 1, 1;\n"
        "}\n"
        : "+f"(d[0]), "+f"(d[1]), "+f"(d[2]), "+f"(d[3]), "+f"(d[4]), "+f"(d[5]), "+f"(d[6]), "+f"(d[7]), "+f"(d[8]), "+f"(d[9]), "+f"(d[10]), "+f"(d[11]), "+f"(d[12]), "+f"(d[13]), "+f"(d[14]), "+f"(d[15]), "+f"(d[16]), "+f"(d[17]), "+f"(d[18]), "+f"(d[19]), "+f"(d[20]), "+f"(d[21]), "+f"(d[22]), "+f"(d[23]), "+f"(d[24]), "+f"(d[25]), "+f"(d[26]), "+f"(d[27]), "+f"(d[28]), "+f"(d[29]), "+f"(d[30]), "+f"(d[31]), "+f"(d[32]), "+f"(d[33]), "+f"(d[34]), "+f"(d[35]), "+f"(d[36]), "+f"(d[37]), "+f"(d[38]), "+f"(d[39]), "+f"(d[40]), "+f"(d[41]), "+f"(d[42]), "+f"(d[43]), "+f"(d[44]), "+f"(d[45]), "+f"(d[46]), "+f"(d[47])
        : "r"(a[AOFF + 0][0]), "r"(a[AOFF + 0][1]), "r"(a[AOFF + 0][2]), "r"(a[AOFF + 0][3]), "r"(a[AOFF + 1][0]), "r"(a[AOFF + 1][1]), "r"(a[AOFF + 1][2]), "r"(a[AOFF + 1][3]), "r"(a[AOFF + 2][0]), "r"(a[AOFF + 2][1]), "r"(a[AOFF + 2][2]), "r"(a[AOFF + 2][3]), "r"(a[AOFF + 3][0]), "r"(a[AOFF + 3][1]), "r"(a[AOFF + 3][2]), "r"(a[AOFF + 3][3]), "r"(a[AOFF + 4][0]), "r"(a[AOFF + 4][1]), "r"(a[AOFF + 4][2]), "r"(a[AOFF + 4][3]), "r"(a[AOFF + 5][0]), "r"(a[AOFF + 5][1]), "r"(a[AOFF + 5][2]), "r"(a[AOFF + 5][3]), "r"(a[AOFF + 6][0]), "r"(a[AOFF + 6][1]), "r"(a[AOFF + 6][2]), "r"(a[AOFF + 6][3]), "r"(a[AOFF + 7][0]), "r"(a[AOFF + 7][1]), "r"(a[AOFF + 7][2]), "r"(a[AOFF + 7][3]), "r"(a[AOFF + 8][0]), "r"(a[AOFF + 8][1]), "r"(a[AOFF + 8][2]), "r"(a[AOFF + 8][3]), "l"(descB), "n"(BOFF >> 4));
}
};
template <> struct Rng<0, 4, 6> {
template <int BOFF, int AOFF, int NA>
static __device__ __forceinline__ void run(float (&d)[48], const uint32_t (&a)[NA][4], uint64_t descB) {
    asm volatile(
        "{\n"
        ".reg .pred p0, p1;\n"
        ".reg .b64 ta, ta0, tb, tb0;\n"
        "setp.ne.b32 p0, 0, 0;\n"
        "setp.eq.b32 p1, 0, 0;\n"
        "add.s64 tb0, %56, %57;\n"
        "add.s64 tb, tb0, 1536;\n"
        "wgmma.mma_async.sync.aligned.m64n96k16.f32.bf16.bf16 {%0, %1, %2, %3, %4, %5, %6, %7, %8, %9, %10, %11, %12, %13, %14, %15, %16, %17, %18, %19, %20, %21, %22, %23, %24, %25, %26, %27, %28, %29, %30, %31, %32, %33, %34, %35, %36, %37, %38, %39, %40, %41, %42, %43, %44, %45, %46, %47}, {%48, %49, %50, %51}, tb, p1, 1, 1, 1;\n"
        "add.s64 tb, tb0, 1568;\n"
        "wgmma.mma_async.sync.aligned.m64n96k16.f32.bf16.bf16 {%0, %1, %2, %3, %4, %5, %6, %7, %8, %9, %10, %11, %12, %13, %14, %15, %16, %17, %18, %19, %20, %21, %22, %23, %24, %25, %26, %27, %28, %29, %30, %31, %32, %33, %34, %35, %36, %37, %38, %39, %40, %41, %42, %43, %44, %45, %46, %47}, {%52, %53, %54, %55}, tb, p1, 1, 1, 1;\n"
        "}\n"
        : "+f"(d[0]), "+f"(d[1]), "+f"(d[2]), "+f"(d[3]), "+f"(d[4]), "+f"(d[5]), "+f"(d[6]), "+f"(d[7]), "+f"(d[8]), "+f"(d[9]), "+f"(d[10]), "+f"(d[11]), "+f"(d[12]), "+f"(d[13]), "+f"(d[14]), "+f"(d[15]), "+f"(d[16]), "+f"(d[17]), "+f"(d[18]), "+f"(d[19]), "+f"(d[20]), "+f"(d[21]), "+f"(d[22]), "+f"(d[23]), "+f"(d[24]), "+f"(d[25]), "+f"(d[26]), "+f"(d[27]), "+f"(d[28]), "+f"(d[29]), "+f"(d[30]), "+f"(d[31]), "+f"(d[32]), "+f"(d[33]), "+f"(d[34]), "+f"(d[35]), "+f"(d[36]), "+f"(d[37]), "+f"(d[38]), "+f"(d[39]), "+f"(d[40]), "+f"(d[41]), "+f"(d[42]), "+f"(d[43]), "+f"(d[44]), "+f"(d[45]), "+f"(d[46]), "+f"(d[47])
        : "r"(a[AOFF + 0][0]), "r"(a[AOFF + 0][1]), "r"(a[AOFF + 0][2]), "r"(a[AOFF + 0][3]), "r"(a[AOFF + 1][0]), "r"(a[AOFF + 1][1]), "r"(a[AOFF + 1][2]), "r"(a[AOFF + 1][3]), "l"(descB), "n"(BOFF >> 4));
}
};
template <> struct Rng<1, 4, 6> {
template <int BOFF, int AOFF, int NA>
static __device__ __forceinline__ void run(float (&d)[48], const uint32_t (&a)[NA][4], uint64_t descB) {
    asm volatile(
        "{\n"
        ".reg .pred p0, p1;\n"
        ".reg .b64 ta, ta0, tb, tb0;\n"
        "setp.ne.b32 p0, 0, 0;\n"
        "setp.eq.b32 p1, 0, 0;\n"
        "add.s64 tb0, %56, %57;\n"
        "add.s64 tb, tb0, 128;\n"
        "wgmma.mma_async.sync.aligned.m64n96k16.f32.bf16.bf16 {%0, %1, %2, %3, %4, %5, %6, %7, %8, %9, %10, %11, %12, %13, %14, %15, %16, %17, %18, %19, %20, %21, %22, %23, %24, %25, %26, %27, %28, %29, %30, %31, %32, %33, %34, %35, %36, %37, %38, %39, %40, %41, %42, %43, %44, %45, %46, %47}, {%48, %49, %50, %51}, tb, p1, 1, 1, 1;\n"
        "add.s64 tb, tb0, 160;\n"
        "wgmma.mma_async.sync.aligned.m64n96k16.f32.bf16.bf16 {%0, %1, %2, %3, %4, %5, %6, %7, %8, %9, %10, %11, %12, %13, %14, %15, %16, %17, %18, %19, %20, %21, %22, %23, %24, %25, %26, %27, %28, %29, %30, %31, %32, %33, %34, %35, %36, %37, %38, %39, %40, %41, %42, %43, %44, %45, %46, %47}, {%52, %53, %54, %55}, tb, p1, 1, 1, 1;\n"
        "}\n"
        : "+f"(d[0]), "+f"(d[1]), "+f"(d[2]), "+f"(d[3]), "+f"(d[4]), "+f"(d[5]), "+f"(d[6]), "+f"(d[7]), "+f"(d[8]), "+f"(d[9]), "+f"(d[10]), "+f"(d[11]), "+f"(d[12]), "+f"(d[13]), "+f"(d[14]), "+f"(d[15]), "+f"(d[16]), "+f"(d[17]), "+f"(d[18]), "+f"(d[19]), "+f"(d[20]), "+f"(d[21]), "+f"(d[22]), "+f"(d[23]), "+f"(d[24]), "+f"(d[25]), "+f"(d[26]), "+f"(d[27]), "+f"(d[28]), "+f"(d[29]), "+f"(d[30]), "+f"(d[31]), "+f"(d[32]), "+f"(d[33]), "+f"(d[34]), "+f"(d[35]), "+f"(d[36]), "+f"(d[37]), "+f"(d[38]), "+f"(d[39]), "+f"(d[40]), "+f"(d[41]), "+f"(d[42]), "+f"(d[43]), "+f"(d[44]), "+f"(d[45]), "+f"(d[46]), "+f"(d[47])
        : "r"(a[AOFF + 0][0]), "r"(a[AOFF + 0][1]), "r"(a[AOFF + 0][2]), "r"(a[AOFF + 0][3]), "r"(a[AOFF + 1][0]), "r"(a[AOFF + 1][1]), "r"(a[AOFF + 1][2]), "r"(a[AOFF + 1][3]), "l"(descB), "n"(BOFF >> 4));
}
};
template <> struct Rng<0, 4, 7> {
template <int BOFF, int AOFF, int NA>
static __device__ __forceinline__ void run(float (&d)[48], const uint32_t (&a)[NA][4], uint64_t descB) {
    asm volatile(
        "{\n"
        ".reg .pred p0, p1;\n"
        ".reg .b64 ta, ta0, tb, tb0;\n"
        "setp.ne.b32 p0, 0, 0;\n"
        "setp.eq.b32 p1, 0, 0;\n"
        "add.s64 tb0, %60, %61;\n"
        "add.s64 tb, tb0, 1536;\n"
        "wgmma.mma_async.sync.aligned.m64n96k16.f32.bf16.bf16 {%0, %1, %2, %3, %4, %5, %6, %7, %8, %9, %10, %11, %12, %13, %14, %15, %16, %17, %18, %19, %20, %21, %22, %23, %24, %25, %26, %27, %28, %29, %30, %31, %32, %33, %34, %35, %36, %37, %38, %39, %40, %41, %42, %43, %44, %45, %46, %47}, {%48, %49, %50, %51}, tb, p1, 1, 1, 1;\n"
        "add.s64 tb, tb0, 1568;\n"
        "wgmma.mma_async.sync.aligned.m64n96k16.f32.bf16.bf16 {%0, %1, %2, %3, %4, %5, %6, %7, %8, %9, %10, %11, %12, %13, %14, %15, %16, %17, %18, %19, %20, %21, %22, %23, %24, %25, %26, %27, %28, %29, %30, %31, %32, %33, %34, %35, %36, %37, %38, %39, %40, %41, %42, %43, %44, %45, %46, %47}, {%52, %53, %54, %55}, tb, p1, 1, 1, 1;\n"
        "add.s64 tb, tb0, 1600;\n"
        "wgmma.mma_async.sync.aligned.m64n96k16.f32.bf16.bf16 {%0, %1, %2, %3, %4, %5, %6, %7, %8, %9, %10, %11, %12, %13, %14, %15, %16, %17, %18, %19, %20, %21, %22, %23, %24, %25, %26, %27, %28, %29, %30, %31, %32, %33, %34, %35, %36, %37, %38, %39, %40, %41, %42, %43, %44, %45, %46, %47}, {%56, %57, %58, %59}, tb, p1, 1, 1, 1;\n"
        "}\n"
        : "+f"(d[0]), "+f"(d[1]), "+f"(d[2]), "+f"(d[3]), "+f"(d[4]), "+f"(d[5]), "+f"(d[6]), "+f"(d[7]), "+f"(d[8]), "+f"(d[9]), "+f"(d[10]), "+f"(d[11]), "+f"(d[12]), "+f"(d[13]), "+f"(d[14]), "+f"(d[15]), "+f"(d[16]), "+f"(d[17]), "+f"(d[18]), "+f"(d[19]), "+f"(d[20]), "+f"(d[21]), "+f"(d[22]), "+f"(d[23]), "+f"(d[24]), "+f"(d[25]), "+f"(d[26]), "+f"(d[27]), "+f"(d[28]), "+f"(d[29]), "+f"(d[30]), "+f"(d[31]), "+f"(d[32]), "+f"(d[33]), "+f"(d[34]), "+f"(d[35]), "+f"(d[36]), "+f"(d[37]), "+f"(d[38]), "+f"(d[39]), "+f"(d[40]), "+f"(d[41]), "+f"(d[42]), "+f"(d[43]), "+f"(d[44]), "+f"(d[45]), "+f"(d[46]), "+f"(d[47])
        : "r"(a[AOFF + 0][0]), "r"(a[AOFF + 0][1]), "r"(a[AOFF + 0][2]), "r"(a[AOFF + 0][3]), "r"(a[AOFF + 1][0]), "r"(a[AOFF + 1][1]), "r"(a[AOFF + 1][2]), "r"(a[AOFF + 1][3]), "r"(a[AOFF + 2][0]), "r"(a[AOFF + 2][1]), "r"(a[AOFF + 2][2]), "r"(a[AOFF + 2][3]), "l"(descB), "n"(BOFF >> 4));
}
};
template <> struct Rng<1, 4, 7> {
template <int BOFF, int AOFF, int NA>
static __device__ __forceinline__ void run(float (&d)[48], const uint32_t (&a)[NA][4], uint64_t descB) {
    asm volatile(
        "{\n"
        ".reg .pred p0, p1;\n"
        ".reg .b64 ta, ta0, tb, tb0;\n"
        "setp.ne.b32 p0, 0, 0;\n"
        "setp.eq.b32 p1, 0, 0;\n"
        "add.s64 tb0, %60, %61;\n"
        "add.s64 tb, tb0, 128;\n"
        "wgmma.mma_async.sync.aligned.m64n96k16.f32.bf16.bf16 {%0, %1, %2, %3, %4, %5, %6, %7, %8, %9, %10, %11, %12, %13, %14, %15, %16, %17, %18, %19, %20, %21, %22, %23, %24, %25, %26, %27, %28, %29, %30, %31, %32, %33, %34, %35, %36, %37, %38, %39, %40, %41, %42, %43, %44, %45, %46, %47}, {%48, %49, %50, %51}, tb, p1, 1, 1, 1;\n"
        "add.s64 tb, tb0, 160;\n"
        "wgmma.mma_async.sync.aligned.m64n96k16.f32.bf16.bf16 {%0, %1, %2, %3, %4, %5, %6, %7, %8, %9, %10, %11, %12, %13, %14, %15, %16, %17, %18, %19, %20, %21, %22, %23, %24, %25, %26, %27, %28, %29, %30, %31, %32, %33, %34, %35, %36, %37, %38, %39, %40, %41, %42, %43, %44, %45, %46, %47}, {%52, %53, %54, %55}, tb, p1, 1, 1, 1;\n"
        "add.s64 tb, tb0, 192;\n"
        "wgmma.mma_async.sync.aligned.m64n96k16.f32.bf16.bf16 {%0, %1, %2, %3, %4, %5, %6, %7, %8, %9, %10, %11, %12, %13, %14, %15, %16, %17, %18, %19, %20, %21, %22, %23, %24, %25, %26, %27, %28, %29, %30, %31, %32, %33, %34, %35, %36, %37, %38, %39, %40, %41, %42, %43, %44, %45, %46, %47}, {%56, %57, %58, %59}, tb, p1, 1, 1, 1;\n"
        "}\n"
        : "+f"(d[0]), "+f"(d[1]), "+f"(d[2]), "+f"(d[3]), "+f"(d[4]), "+f"(d[5]), "+f"(d[6]), "+f"(d[7]), "+f"(d[8]), "+f"(d[9]), "+f"(d[10]), "+f"(d[11]), "+f"(d[12]), "+f"(d[13]), "+f"(d[14]), "+f"(d[15]), "+f"(d[16]), "+f"(d[17]), "+f"(d[18]), "+f"(d[19]), "+f"(d[20]), "+f"(d[21]), "+f"(d[22]), "+f"(d[23]), "+f"(d[24]), "+f"(d[25]), "+f"(d[26]), "+f"(d[27]), "+f"(d[28]), "+f"(d[29]), "+f"(d[30]), "+f"(d[31]), "+f"(d[32]), "+f"(d[33]), "+f"(d[34]), "+f"(d[35]), "+f"(d[36]), "+f"(d[37]), "+f"(d[38]), "+f"(d[39]), "+f"(d[40]), "+f"(d[41]), "+f"(d[42]), "+f"(d[43]), "+f"(d[44]), "+f"(d[45]), "+f"(d[46]), "+f"(d[47])
        : "r"(a[AOFF + 0][0]), "r"(a[AOFF + 0][1]), "r"(a[AOFF + 0][2]), "r"(a[AOFF + 0][3]), "r"(a[AOFF + 1][0]), "r"(a[AOFF + 1][1]), "r"(a[AOFF + 1][2]), "r"(a[AOFF + 1][3]), "r"(a[AOFF + 2][0]), "r"(a[AOFF + 2][1]), "r"(a[AOFF + 2][2]), "r"(a[AOFF + 2][3]), "l"(descB), "n"(BOFF >> 4));
}
};
template <> struct Rng<0, 4, 8> {
template <int BOFF, int AOFF, int NA>
static __device__ __forceinline__ void run(float (&d)[48], const uint32_t (&a)[NA][4], uint64_t descB) {
    asm volatile(
        "{\n"
        ".reg .pred p0, p1;\n"
        ".reg .b64 ta, ta0, tb, tb0;\n"
        "setp.ne.b32 p0, 0, 0;\n"
        "setp.eq.b32 p1, 0, 0;\n"
        "add.s64 tb0, %64, %65;\n"
        "add.s64 tb, tb0, 1536;\n"
        "wgmma.mma_async.sync.aligned.m64n96k16.f32.bf16.bf16 {%0, %1, %2, %3, %4, %5, %6, %7, %8, %9, %10, %11, %12, %13, %14, %15, %16, %17, %18, %19, %20, %21, %22, %23, %24, %25, %26, %27, %28, %29, %30, %31, %32, %33, %34, %35, %36, %37, %38, %39, %40, %41, %42, %43, %44, %45, %46, %47}, {%48, %49, %50, %51}, tb, p1, 1, 1, 1;\n"
        "add.s64 tb, tb0, 1568;\n"
        "wgmma.mma_async.sync.aligned.m64n96k16.f32.bf16.bf16 {%0, %1, %2, %3, %4, %5, %6, %7, %8, %9, %10, %11, %12, %13, %14, %15, %16, %17, %18, %19, %20, %21, %22, %23, %24, %25, %26, %27, %28, %29, %30, %31, %32, %33, %34, %35, %36, %37, %38, %39, %40, %41, %42, %43, %44, %45, %46, %47}, {%52, %53, %54, %55}, tb, p1, 1, 1, 1;\n"
        "add.s64 tb, tb0, 1600;\n"
        "wgmma.mma_async.sync.aligned.m64n96k16.f32.bf16.bf16 {%0, %1, %2, %3, %4, %5, %6, %7, %8, %9, %10, %11, %12, %13, %14, %15, %16, %17, %18, %19, %20, %21, %22, %23, %24, %25, %26, %27, %28, %29, %30, %31, %32, %33, %34, %35, %36, %37, %38, %39, %40, %41, %42, %43, %44, %45, %46, %47}, {%56, %57, %58, %59}, tb, p1, 1, 1, 1;\n"
        "add.s64 tb, tb0, 1632;\n"
        "wgmma.mma_async.sync.aligned.m64n96k16.f32.bf16.bf16 {%0, %1, %2, %3, %4, %5, %6, %7, %8, %9, %10, %11, %12, %13, %14, %15, %16, %17, %18, %19, %20, %21, %22, %23, %24, %25, %26, %27, %28, %29, %30, %31, %32, %33, %34, %35, %36, %37, %38, %39, %40, %41, %42, %43, %44, %45, %46, %47}, {%60, %61, %62, %63}, tb, p1, 1, 1, 1;\n"
        "}\n"
        : "+f"(d[0]), "+f"(d[1]), "+f"(d[2]), "+f"(d[3]), "+f"(d[4]), "+f"(d[5]), "+f"(d[6]), "+f"(d[7]), "+f"(d[8]), "+f"(d[9]), "+f"(d[10]), "+f"(d[11]), "+f"(d[12]), "+f"(d[13]), "+f"(d[14]), "+f"(d[15]), "+f"(d[16]), "+f"(d[17]), "+f"(d[18]), "+f"(d[19]), "+f"(d[20]), "+f"(d[21]), "+f"(d[22]), "+f"(d[23]), "+f"(d[24]), "+f"(d[25]), "+f"(d[26]), "+f"(d[27]), "+f"(d[28]), "+f"(d[29]), "+f"(d[30]), "+f"(d[31]), "+f"(d[32]), "+f"(d[33]), "+f"(d[34]), "+f"(d[35]), "+f"(d[36]), "+f"(d[37]), "+f"(d[38]), "+f"(d[39]), "+f"(d[40]), "+f"(d[41]), "+f"(d[42]), "+f"(d[43]), "+f"(d[44]), "+f"(d[45]), "+f"(d[46]), "+f"(d[47])
        : "r"(a[AOFF + 0][0]), "r"(a[AOFF + 0][1]), "r"(a[AOFF + 0][2]), "r"(a[AOFF + 0][3]), "r"(a[AOFF + 1][0]), "r"(a[AOFF + 1][1]), "r"(a[AOFF + 1][2]), "r"(a[AOFF + 1][3]), "r"(a[AOFF + 2][0]), "r"(a[AOFF + 2][1]), "r"(a[AOFF + 2][2]), "r"(a[AOFF + 2][3]), "r"(a[AOFF + 3][0]), "r"(a[AOFF + 3][1]), "r"(a[AOFF + 3][2]), "r"(a[AOFF + 3][3]), "l"(descB), "n"(BOFF >> 4));
}
};
template <> struct Rng<1, 4, 8> {
template <int BOFF, int AOFF, int NA>
static __device__ __forceinline__ void run(float (&d)[48], const uint32_t (&a)[NA][4], uint64_t descB) {
    asm volatile(
        "{\n"
        ".reg .pred p0, p1;\n"
        ".reg .b64 ta, ta0, tb, tb0;\n"
        "setp.ne.b32 p0, 0, 0;\n"
        "setp.eq.b32 p1, 0, 0;\n"
        "add.s64 tb0, %64, %65;\n"
        "add.s64 tb, tb0, 128;\n"
        "wgmma.mma_async.sync.aligned.m64n96k16.f32.bf16.bf16 {%0, %1, %2, %3, %4, %5, %6, %7, %8, %9, %10, %11, %12, %13, %14, %15, %16, %17, %18, %19, %20, %21, %22, %23, %24, %25, %26, %27, %28, %29, %30, %31, %32, %33, %34, %35, %36, %37, %38, %39, %40, %41, %42, %43, %44, %45, %46, %47}, {%48, %49, %50, %51}, tb, p1, 1, 1, 1;\n"
        "add.s64 tb, tb0, 160;\n"
        "wgmma.mma_async.sync.aligned.m64n96k16.f32.bf16.bf16 {%0, %1, %2, %3, %4, %5, %6, %7, %8, %9, %10, %11, %12, %13, %14, %15, %16, %17, %18, %19, %20, %21, %22, %23, %24, %25, %26, %27, %28, %29, %30, %31, %32, %33, %34, %35, %36, %37, %38, %39, %40, %41, %42, %43, %44, %45, %46, %47}, {%52, %53, %54, %55}, tb, p1, 1, 1, 1;\n"
        "add.s64 tb, tb0, 192;\n"
        "wgmma.mma_async.sync.aligned.m64n96k16.f32.bf16.bf16 {%0, %1, %2, %3, %4, %5, %6, %7, %8, %9, %10, %11, %12, %13, %14, %15, %16, %17, %18, %19, %20, %21, %22, %23, %24, %25, %26, %27, %28, %29, %30, %31, %32, %33, %34, %35, %36, %37, %38, %39, %40, %41, %42, %43, %44, %45, %46, %47}, {%56, %57, %58, %59}, tb, p1, 1, 1, 1;\n"
        "add.s64 tb, tb0, 224;\n"
        "wgmma.mma_async.sync.aligned.m64n96k16.f32.bf16.bf16 {%0, %1, %2, %3, %4, %5, %6, %7, %8, %9, %10, %11, %12, %13, %14, %15, %16, %17, %18, %19, %20, %21, %22, %23, %24, %25, %26, %27, %28, %29, %30, %31, %32, %33, %34, %35, %36, %37, %38, %39, %40, %41, %42, %43, %44, %45, %46, %47}, {%60, %61, %62, %63}, tb, p1, 1, 1, 1;\n"
        "}\n"
        : "+f"(d[0]), "+f"(d[1]), "+f"(d[2]), "+f"(d[3]), "+f"(d[4]), "+f"(d[5]), "+f"(d[6]), "+f"(d[7]), "+f"(d[8]), "+f"(d[9]), "+f"(d[10]), "+f"(d[11]), "+f"(d[12]), "+f"(d[13]), "+f"(d[14]), "+f"(d[15]), "+f"(d[16]), "+f"(d[17]), "+f"(d[18]), "+f"(d[19]), "+f"(d[20]), "+f"(d[21]), "+f"(d[22]), "+f"(d[23]), "+f"(d[24]), "+f"(d[25]), "+f"(d[26]), "+f"(d[27]), "+f"(d[28]), "+f"(d[29]), "+f"(d[30]), "+f"(d[31]), "+f"(d[32]), "+f"(d[33]), "+f"(d[34]), "+f"(d[35]), "+f"(d[36]), "+f"(d[37]), "+f"(d[38]), "+f"(d[39]), "+f"(d[40]), "+f"(d[41]), "+f"(d[42]), "+f"(d[43]), "+f"(d[44]), "+f"(d[45]), "+f"(d[46]), "+f"(d[47])
        : "r"(a[AOFF + 0][0]), "r"(a[AOFF + 0][1]), "r"(a[AOFF + 0][2]), "r"(a[AOFF + 0][3]), "r"(a[AOFF + 1][0]), "r"(a[AOFF + 1][1]), "r"(a[AOFF + 1][2]), "r"(a[AOFF + 1][3]), "r"(a[AOFF + 2][0]), "r"(a[AOFF + 2][1]), "r"(a[AOFF + 2][2]), "r"(a[AOFF + 2][3]), "r"(a[AOFF + 3][0]), "r"(a[AOFF + 3][1]), "r"(a[AOFF + 3][2]), "r"(a[AOFF + 3][3]), "l"(descB), "n"(BOFF >> 4));
}
};
template <> struct Rng<0, 4, 9> {
template <int BOFF, int AOFF, int NA>
static __device__ __forceinline__ void run(float (&d)[48], const uint32_t (&a)[NA][4], uint64_t descB) {
    asm volatile(
        "{\n"
        ".reg .pred p0, p1;\n"
        ".reg .b64 ta, ta0, tb, tb0;\n"
        "setp.ne.b32 p0, 0, 0;\n"
        "setp.eq.b32 p1, 0, 0;\n"
        "add.s64 tb0, %68, %69;\n"
        "add.s64 tb, tb0, 1536;\n"
        "wgmma.mma_async.sync.aligned.m64n96k16.f32.bf16.bf16 {%0, %1, %2, %3, %4, %5, %6, %7, %8, %9, %10, %11, %12, %13, %14, %15, %16, %17, %18, %19, %20, %21, %22, %23, %24, %25, %26, %27, %28, %29, %30, %31, %32, %33, %34, %35, %36, %37, %38, %39, %40, %41, %42, %43, %44, %45, %46, %47}, {%48, %49, %50, %51}, tb, p1, 1, 1, 1;\n"
        "add.s64 tb, tb0, 1568;\n"
        "wgmma.mma_async.sync.aligned.m64n96k16.f32.bf16.bf16 {%0, %1, %2, %3, %4, %5, %6, %7, %8, %9, %10, %11, %12, %13, %14, %15, %16, %17, %18, %19, %20, %21, %22, %23, %24, %25, %26, %27, %28, %29, %30, %31, %32, %33, %34, %35, %36, %37, %38, %39, %40, %41, %42, %43, %44, %45, %46, %47}, {%52, %53, %54, %55}, tb, p1, 1, 1, 1;\n"
        "add.s64 tb, tb0, 1600;\n"
        "wgmma.mma_async.sync.aligned.m64n96k16.f32.bf16.bf16 {%0, %1, %2, %3, %4, %5, %6, %7, %8, %9, %10, %11, %12, %13, %14, %15, %16, %17, %18, %19, %20, %21, %22, %23, %24, %25, %26, %27, %28, %29, %30, %31, %32, %33, %34, %35, %36, %37, %38, %39, %40, %41, %42, %43, %44, %45, %46, %47}, {%56, %57, %58, %59}, tb, p1, 1, 1, 1;\n"
        "add.s64 tb, tb0, 1632;\n"
        "wgmma.mma_async.sync.aligned.m64n96k16.f32.bf16.bf16 {%0, %1, %2, %3, %4, %5, %6, %7, %8, %9, %10, %11, %12, %13, %14, %15, %16, %17, %18, %19, %20, %21, %22, %23, %24, %25, %26, %27, %28, %29, %30, %31, %32, %33, %34, %35, %36, %37, %38, %39, %40, %41, %42, %43, %44, %45, %46, %47}, {%60, %61, %62, %63}, tb, p1, 1, 1, 1;\n"
        "add.s64 tb, tb0, 3072;\n"
        "wgmma.mma_async.sync.aligned.m64n96k16.f32.bf16.bf16 {%0, %1, %2, %3, %4, %5, %6, %7, %8, %9, %10, %11, %12, %13, %14, %15, %16, %17, %18, %19, %20, %21, %22, %23, %24, %25, %26, %27, %28, %29, %30, %31, %32, %33, %34, %35, %36, %37, %38, %39, %40, %41, %42, %43, %44, %45, %46, %47}, {%64, %65, %66, %67}, tb, p1, 1, 1, 1;\n"
        "}\n"
        : "+f"(d[0]), "+f"(d[1]), "+f"(d[2]), "+f"(d[3]), "+f"(d[4]), "+f"(d[5]), "+f"(d[6]), "+f"(d[7]), "+f"(d[8]), "+f"(d[9]), "+f"(d[10]), "+f"(d[11]), "+f"(d[12]), "+f"(d[13]), "+f"(d[14]), "+f"(d[15]), "+f"(d[16]), "+f"(d[17]), "+f"(d[18]), "+f"(d[19]), "+f"(d[20]), "+f"(d[21]), "+f"(d[22]), "+f"(d[23]), "+f"(d[24]), "+f"(d[25]), "+f"(d[26]), "+f"(d[27]), "+f"(d[28]), "+f"(d[29]), "+f"(d[30]), "+f"(d[31]), "+f"(d[32]), "+f"(d[33]), "+f"(d[34]), "+f"(d[35]), "+f"(d[36]), "+f"(d[37]), "+f"(d[38]), "+f"(d[39]), "+f"(d[40]), "+f"(d[41]), "+f"(d[42]), "+f"(d[43]), "+f"(d[44]), "+f"(d[45]), "+f"(d[46]), "+f"(d[47])
        : "r"(a[AOFF + 0][0]), "r"(a[AOFF + 0][1]), "r"(a[AOFF + 0][2]), "r"(a[AOFF + 0][3]), "r"(a[AOFF + 1][0]), "r"(a[AOFF + 1][1]), "r"(a[AOFF + 1][2]), "r"(a[AOFF + 1][3]), "r"(a[AOFF + 2][0]), "r"(a[AOFF + 2][1]), "r"(a[AOFF + 2][2]), "r"(a[AOFF + 2][3]), "r"(a[AOFF + 3][0]), "r"(a[AOFF + 3][1]), "r"(a[AOFF + 3][2]), "r"(a[AOFF + 3][3]), "r"(a[AOFF + 4][0]), "r"(a[AOFF + 4][1]), "r"(a[AOFF + 4][2]), "r"(a[AOFF + 4][3]), "l"(descB), "n"(BOFF >> 4));
}
};
template <> struct Rng<1, 4, 9> {
template <int BOFF, int AOFF, int NA>
static __device__ __forceinline__ void run(float (&d)[48], const uint32_t (&a)[NA][4], uint64_t descB) {
    asm volatile(
        "{\n"
        ".reg .pred p0, p1;\n"
        ".reg .b64 ta, ta0, tb, tb0;\n"
        "setp.ne.b32 p0, 0, 0;\n"
        "setp.eq.b32 p1, 0, 0;\n"
        "add.s64 tb0, %68, %69;\n"
        "add.s64 tb, tb0, 128;\n"
        "wgmma.mma_async.sync.aligned.m64n96k16.f32.bf16.bf16 {%0, %1, %2, %3, %4, %5, %6, %7, %8, %9, %10, %11, %12, %13, %14, %15, %16, %17, %18, %19, %20, %21, %22, %23, %24, %25, %26, %27, %28, %29, %30, %31, %32, %33, %34, %35, %36, %37, %38, %39, %40, %41, %42, %43, %44, %45, %46, %47}, {%48, %49, %50, %51}, tb, p1, 1, 1, 1;\n"
        "add.s64 tb, tb0, 160;\n"
        "wgmma.mma_async.sync.aligned.m64n96k16.f32.bf16.bf16 {%0, %1, %2, %3, %4, %5, %6, %7, %8, %9, %10, %11, %12, %13, %14, %15, %16, %17, %18, %19, %20, %21, %22, %23, %24, %25, %26, %27, %28, %29, %30, %31, %32, %33, %34, %35, %36, %37, %38, %39, %40, %41, %42, %43, %44, %45, %46, %47}, {%52, %53, %54, %55}, tb, p1, 1, 1, 1;\n"
        "add.s64 tb, tb0, 192;\n"
        "wgmma.mma_async.sync.aligned.m64n96k16.f32.bf16.bf16 {%0, %1, %2, %3, %4, %5, %6, %7, %8, %9, %10, %11, %12, %13, %14, %15, %16, %17, %18, %19, %20, %21, %22, %23, %24, %25, %26, %27, %28, %29, %30, %31, %32, %33, %34, %35, %36, %37, %38, %39, %40, %41, %42, %43, %44, %45, %46, %47}, {%56, %57, %58, %59}, tb, p1, 1, 1, 1;\n"
        "add.s64 tb, tb0, 224;\n"
        "wgmma.mma_async.sync.aligned.m64n96k16.f32.bf16.bf16 {%0, %1, %2, %3, %4, %5, %6, %7, %8, %9, %10, %11, %12, %13, %14, %15, %16, %17, %18, %19, %20, %21, %22, %23, %24, %25, %26, %27, %28, %29, %30, %31, %32, %33, %34, %35, %36, %37, %38, %39, %40, %41, %42, %43, %44, %45, %46, %47}, {%60, %61, %62, %63}, tb, p1, 1, 1, 1;\n"
        "add.s64 tb, tb0, 256;\n"
        "wgmma.mma_async.sync.aligned.m64n96k16.f32.bf16.bf16 {%0, %1, %2, %3, %4, %5, %6, %7, %8, %9, %10, %11, %12, %13, %14, %15, %16, %17, %18, %19, %20, %21, %22, %23, %24, %25, %26, %27, %28, %29, %30, %31, %32, %33, %34, %35, %36, %37, %38, %39, %40, %41, %42, %43, %44, %45, %46, %47}, {%64, %65, %66, %67}, tb, p1, 1, 1, 1;\n"
        "}\n"
        : "+f"(d[0]), "+f"(d[1]), "+f"(d[2]), "+f"(d[3]), "+f"(d[4]), "+f"(d[5]), "+f"(d[6]), "+f"(d[7]), "+f"(d[8]), "+f"(d[9]), "+f"(d[10]), "+f"(d[11]), "+f"(d[12]), "+f"(d[13]), "+f"(d[14]), "+f"(d[15]), "+f"(d[16]), "+f"(d[17]), "+f"(d[18]), "+f"(d[19]), "+f"(d[20]), "+f"(d[21]), "+f"(d[22]), "+f"(d[23]), "+f"(d[24]), "+f"(d[25]), "+f"(d[26]), "+f"(d[27]), "+f"(d[28]), "+f"(d[29]), "+f"(d[30]), "+f"(d[31]), "+f"(d[32]), "+f"(d[33]), "+f"(d[34]), "+f"(d[35]), "+f"(d[36]), "+f"(d[37]), "+f"(d[38]), "+f"(d[39]), "+f"(d[40]), "+f"(d[41]), "+f"(d[42]), "+f"(d[43]), "+f"(d[44]), "+f"(d[45]), "+f"(d[46]), "+f"(d[47])
        : "r"(a[AOFF + 0][0]), "r"(a[AOFF + 0][1]), "r"(a[AOFF + 0][2]), "r"(a[AOFF + 0][3]), "r"(a[AOFF + 1][0]), "r"(a[AOFF + 1][1]), "r"(a[AOFF + 1][2]), "r"(a[AOFF + 1][3]), "r"(a[AOFF + 2][0]), "r"(a[AOFF + 2][1]), "r"(a[AOFF + 2][2]), "r"(a[AOFF + 2][3]), "r"(a[AOFF + 3][0]), "r"(a[AOFF + 3][1]), "r"(a[AOFF + 3][2]), "r"(a[AOFF + 3][3]), "r"(a[AOFF + 4][0]), "r"(a[AOFF + 4][1]), "r"(a[AOFF + 4][2]), "r"(a[AOFF + 4][3]), "l"(descB), "n"(BOFF >> 4));
}
};
template <> struct Rng<0, 4, 12> {
template <int BOFF, int AOFF, int NA>
static __device__ __forceinline__ void run(float (&d)[48], const uint32_t (&a)[NA][4], uint64_t descB) {
    asm volatile(
        "{\n"
        ".reg .pred p0, p1;\n"
        ".reg .b64 ta, ta0, tb, tb0;\n"
        "setp.ne.b32 p0, 0, 0;\n"
        "setp.eq.b32 p1, 0, 0;\n"
        "add.s64 tb0, %80, %81;\n"
        "add.s64 tb, tb0, 1536;\n"
        "wgmma.mma_async.sync.aligned.m64n96k16.f32.bf16.bf16 {%0, %1, %2, %3, %4, %5, %6, %7, %8, %9, %10, %11, %12, %13, %14, %15, %16, %17, %18, %19, %20, %21, %22, %23, %24, %25, %26, %27, %28, %29, %30, %31, %32, %33, %34, %35, %36, %37, %38, %39, %40, %41, %42, %43, %44, %45, %46, %47}, {%48, %49, %50, %51}, tb, p1, 1, 1, 1;\n"
        "add.s64 tb, tb0, 1568;\n"
        "wgmma.mma_async.sync.aligned.m64n96k16.f32.bf16.bf16 {%0, %1, %2, %3, %4, %5, %6, %7, %8, %9, %10, %11, %12, %13, %14, %15, %16, %17, %18, %19, %20, %21, %22, %23, %24, %25, %26, %27, %28, %29, %30, %31, %32, %33, %34, %35, %36, %37, %38, %39, %40, %41, %42, %43, %44, %45, %46, %47}, {%52, %53, %54, %55}, tb, p1, 1, 1, 1;\n"
        "add.s64 tb, tb0, 1600;\n"
        "wgmma.mma_async.sync.aligned.m64n96k16.f32.bf16.bf16 {%0, %1, %2, %3, %4, %5, %6, %7, %8, %9, %10, %11, %12, %13, %14, %15, %16, %17, %18, %19, %20, %21, %22, %23, %24, %25, %26, %27, %28, %29, %30, %31, %32, %33, %34, %35, %36, %37, %38, %39, %40, %41, %42, %43, %44, %45, %46, %47}, {%56, %57, %58, %59}, tb, p1, 1, 1, 1;\n"
        "add.s64 tb, tb0, 1632;\n"
        "wgmma.mma_async.sync.aligned.m64n96k16.f32.bf16.bf16 {%0, %1, %2, %3, %4, %5, %6, %7, %8, %9, %10, %11, %12, %13, %14, %15, %16, %17, %18, %19, %20, %21, %22, %23, %24, %25, %26, %27, %28, %29, %30, %31, %32, %33, %34, %35, %36, %37, %38, %39, %40, %41, %42, %43, %44, %45, %46, %47}, {%60, %61, %62, %63}, tb, p1, 1, 1, 1;\n"
        "add.s64 tb, tb0, 3072;\n"
        "wgmma.mma_async.sync.aligned.m64n96k16.f32.bf16.bf16 {%0, %1, %2, %3, %4, %5, %6, %7, %8, %9, %10, %11, %12, %13, %14, %15, %16, %17, %18, %19, %20, %21, %22, %23, %24, %25, %26, %27, %28, %29, %30, %31, %32, %33, %34, %35, %36, %37, %38, %39, %40, %41, %42, %43, %44, %45, %46, %47}, {%64, %65, %66, %67}, tb, p1, 1, 1, 1;\n"
        "add.s64 tb, tb0, 3104;\n"
        "wgmma.mma_async.sync.aligned.m64n96k16.f32.bf16.bf16 {%0, %1, %2, %3, %4, %5, %6, %7, %8, %9, %10, %11, %12, %13, %14, %15, %16, %17, %18, %19, %20, %21, %22, %23, %24, %25, %26, %27, %28, %29, %30, %31, %32, %33, %34, %35, %36, %37, %38, %39, %40, %41, %42, %43, %44, %45, %46, %47}, {%68, %69, %70, %71}, tb, p1, 1, 1, 1;\n"
        "add.s64 tb, tb0, 3136;\n"
        "wgmma.mma_async.sync.aligned.m64n96k16.f32.bf16.bf16 {%0, %1, %2, %3, %4, %5, %6, %7, %8, %9, %10, %11, %12, %13, %14, %15, %16, %17, %18, %19, %20, %21, %22, %23, %24, %25, %26, %27, %28, %29, %30, %31, %32, %33, %34, %35, %36, %37, %38, %39, %40, %41, %42, %43, %44, %45, %46, %47}, {%72, %73, %74, %75}, tb, p1, 1, 1, 1;\n"
        "add.s64 tb, tb0, 3168;\n"
        "wgmma.mma_async.sync.aligned.m64n96k16.f32.bf16.bf16 {%0, %1, %2, %3, %4, %5, %6, %7, %8, %9, %10, %11, %12, %13, %14, %15, %16, %17, %18, %19, %20, %21, %22, %23, %24, %25, %26, %27, %28, %29, %30, %31, %32, %33, %34, %35, %36, %37, %38, %39, %40, %41, %42, %43, %44, %45, %46, %47}, {%76, %77, %78, %79}, tb, p1, 1, 1, 1;\n"
        "}\n"
        : "+f"(d[0]), "+f"(d[1]), "+f"(d[2]), "+f"(d[3]), "+f"(d[4]), "+f"(d[5]), "+f"(d[6]), "+f"(d[7]), "+f"(d[8]), "+f"(d[9]), "+f"(d[10]), "+f"(d[11]), "+f"(d[12]), "+f"(d[13]), "+f"(d[14]), "+f"(d[15]), "+f"(d[16]), "+f"(d[17]), "+f"(d[18]), "+f"(d[19]), "+f"(d[20]), "+f"(d[21]), "+f"(d[22]), "+f"(d[23]), "+f"(d[24]), "+f"(d[25]), "+f"(d[26]), "+f"(d[27]), "+f"(d[28]), "+f"(d[29]), "+f"(d[30]), "+f"(d[31]), "+f"(d[32]), "+f"(d[33]), "+f"(d[34]), "+f"(d[35]), "+f"(d[36]), "+f"(d[37]), "+f"(d[38]), "+f"(d[39]), "+f"(d[40]), "+f"(d[41]), "+f"(d[42]), "+f"(d[43]), "+f"(d[44]), "+f"(d[45]), "+f"(d[46]), "+f"(d[47])
        : "r"(a[AOFF + 0][0]), "r"(a[AOFF + 0][1]), "r"(a[AOFF + 0][2]), "r"(a[AOFF + 0][3]), "r"(a[AOFF + 1][0]), "r"(a[AOFF + 1][1]), "r"(a[AOFF + 1][2]), "r"(a[AOFF + 1][3]), "r"(a[AOFF + 2][0]), "r"(a[AOFF + 2][1]), "r"(a[AOFF + 2][2]), "r"(a[AOFF + 2][3]), "r"(a[AOFF + 3][0]), "r"(a[AOFF + 3][1]), "r"(a[AOFF + 3][2]), "r"(a[AOFF + 3][3]), "r"(a[AOFF + 4][0]), "r"(a[AOFF + 4][1]), "r"(a[AOFF + 4][2]), "r"(a[AOFF + 4][3]), "r"(a[AOFF + 5][0]), "r"(a[AOFF + 5][1]), "r"(a[AOFF + 5][2]), "r"(a[AOFF + 5][3]), "r"(a[AOFF + 6][0]), "r"(a[AOFF + 6][1]), "r"(a[AOFF + 6][2]), "r"(a[AOFF + 6][3]), "r"(a[AOFF + 7][0]), "r"(a[AOFF + 7][1]), "r"(a[AOFF + 7][2]), "r"(a[AOFF + 7][3]), "l"(descB), "n"(BOFF >> 4));
}
};
template <> struct Rng<1, 4, 12> {
template <int BOFF, int AOFF, int NA>
static __device__ __forceinline__ void run(float (&d)[48], const uint32_t (&a)[NA][4], uint64_t descB) {
    asm volatile(
        "{\n"
        ".reg .pred p0, p1;\n"
        ".reg .b64 ta, ta0, tb, tb0;\n"
        "setp.ne.b32 p0, 0, 0;\n"
        "setp.eq.b32 p1, 0, 0;\n"
        "add.s64 tb0, %80, %81;\n"
        "add.s64 tb, tb0, 128;\n"
        "wgmma.mma_async.sync.aligned.m64n96k16.f32.bf16.bf16 {%0, %1, %2, %3, %4, %5, %6, %7, %8, %9, %10, %11, %12, %13, %14, %15, %16, %17, %18, %19, %20, %21, %22, %23, %24, %25, %26, %27, %28, %29, %30, %31, %32, %33, %34, %35, %36, %37, %38, %39, %40, %41, %42, %43, %44, %45, %46, %47}, {%48, %49, %50, %51}, tb, p1, 1, 1, 1;\n"
        "add.s64 tb, tb0, 160;\n"
        "wgmma.mma_async.sync.aligned.m64n96k16.f32.bf16.bf16 {%0, %1, %2, %3, %4, %5, %6, %7, %8, %9, %10, %11, %12, %13, %14, %15, %16, %17, %18, %19, %20, %21, %22, %23, %24, %25, %26, %27, %28, %29, %30, %31, %32, %33, %34, %35, %36, %37, %38, %39, %40, %41, %42, %43, %44, %45, %46, %47}, {%52, %53, %54, %55}, tb, p1, 1, 1, 1;\n"
        "add.s64 tb, tb0, 192;\n"
        "wgmma.mma_async.sync.aligned.m64n96k16.f32.bf16.bf16 {%0, %1, %2, %3, %4, %5, %6, %7, %8, %9, %10, %11, %12, %13, %14, %15, %16, %17, %18, %19, %20, %21, %22, %23, %24, %25, %26, %27, %28, %29, %30, %31, %32, %33, %34, %35, %36, %37, %38, %39, %40, %41, %42, %43, %44, %45, %46, %47}, {%56, %57, %58, %59}, tb, p1, 1, 1, 1;\n"
        "add.s64 tb, tb0, 224;\n"
        "wgmma.mma_async.sync.aligned.m64n96k16.f32.bf16.bf16 {%0, %1, %2, %3, %4, %5, %6, %7, %8, %9, %10, %11, %12, %13, %14, %15, %16, %17, %18, %19, %20, %21, %22, %23, %24, %25, %26, %27, %28, %29, %30, %31, %32, %33, %34, %35, %36, %37, %38, %39, %40, %41, %42, %43, %44, %45, %46, %47}, {%60, %61, %62, %63}, tb, p1, 1, 1, 1;\n"
        "add.s64 tb, tb0, 256;\n"
        "wgmma.mma_async.sync.aligned.m64n96k16.f32.bf16.bf16 {%0, %1, %2, %3, %4, %5, %6, %7, %8, %9, %10, %11, %12, %13, %14, %15, %16, %17, %18, %19, %20, %21, %22, %23, %24, %25, %26, %27, %28, %29, %30, %31, %32, %33, %34, %35, %36, %37, %38, %39, %40, %41, %42, %43, %44, %45, %46, %47}, {%64, %65, %66, %67}, tb, p1, 1, 1, 1;\n"
        "add.s64 tb, tb0, 288;\n"
        "wgmma.mma_async.sync.aligned.m64n96k16.f32.bf16.bf16 {%0, %1, %2, %3, %4, %5, %6, %7, %8, %9, %10, %11, %12, %13, %14, %15, %16, %17, %18, %19, %20, %21, %22, %23, %24, %25, %26, %27, %28, %29, %30, %31, %32, %33, %34, %35, %36, %37, %38, %39, %40, %41, %42, %43, %44, %45, %46, %47}, {%68, %69, %70, %71}, tb, p1, 1, 1, 1;\n"
        "add.s64 tb, tb0, 320;\n"
        "wgmma.mma_async.sync.aligned.m64n96k16.f32.bf16.bf16 {%0, %1, %2, %3, %4, %5, %6, %7, %8, %9, %10, %11, %12, %13, %14, %15, %16, %17, %18, %19, %20, %21, %22, %23, %24, %25, %26, %27, %28, %29, %30, %31, %32, %33, %34, %35, %36, %37, %38, %39, %40, %41, %42, %43, %44, %45, %46, %47}, {%72, %73, %74, %75}, tb, p1, 1, 1, 1;\n"
        "add.s64 tb, tb0, 352;\n"
        "wgmma.mma_async.sync.aligned.m64n96k16.f32.bf16.bf16 {%0, %1, %2, %3, %4, %5, %6, %7, %8, %9, %10, %11, %12, %13, %14, %15, %16, %17, %18, %19, %20, %21, %22, %23, %24, %25, %26, %27, %28, %29, %30, %31, %32, %33, %34, %35, %36, %37, %38, %39, %40, %41, %42, %43, %44, %45, %46, %47}, {%76, %77, %78, %79}, tb, p1, 1, 1, 1;\n"
        "}\n"
        : "+f"(d[0]), "+f"(d[1]), "+f"(d[2]), "+f"(d[3]), "+f"(d[4]), "+f"(d[5]), "+f"(d[6]), "+f"(d[7]), "+f"(d[8]), "+f"(d[9]), "+f"(d[10]), "+f"(d[11]), "+f"(d[12]), "+f"(d[13]), "+f"(d[14]), "+f"(d[15]), "+f"(d[16]), "+f"(d[17]), "+f"(d[18]), "+f"(d[19]), "+f"(d[20]), "+f"(d[21]), "+f"(d[22]), "+f"(d[23]), "+f"(d[24]), "+f"(d[25]), "+f"(d[26]), "+f"(d[27]), "+f"(d[28]), "+f"(d[29]), "+f"(d[30]), "+f"(d[31]), "+f"(d[32]), "+f"(d[33]), "+f"(d[34]), "+f"(d[35]), "+f"(d[36]), "+f"(d[37]), "+f"(d[38]), "+f"(d[39]), "+f"(d[40]), "+f"(d[41]), "+f"(d[42]), "+f"(d[43]), "+f"(d[44]), "+f"(d[45]), "+f"(d[46]), "+f"(d[47])
        : "r"(a[AOFF + 0][0]), "r"(a[AOFF + 0][1]), "r"(a[AOFF + 0][2]), "r"(a[AOFF + 0][3]), "r"(a[AOFF + 1][0]), "r"(a[AOFF + 1][1]), "r"(a[AOFF + 1][2]), "r"(a[AOFF + 1][3]), "r"(a[AOFF + 2][0]), "r"(a[AOFF + 2][1]), "r"(a[AOFF + 2][2]), "r"(a[AOFF + 2][3]), "r"(a[AOFF + 3][0]), "r"(a[AOFF + 3][1]), "r"(a[AOFF + 3][2]), "r"(a[AOFF + 3][3]), "r"(a[AOFF + 4][0]), "r"(a[AOFF + 4][1]), "r"(a[AOFF + 4][2]), "r"(a[AOFF + 4][3]), "r"(a[AOFF + 5][0]), "r"(a[AOFF + 5][1]), "r"(a[AOFF + 5][2]), "r"(a[AOFF + 5][3]), "r"(a[AOFF + 6][0]), "r"(a[AOFF + 6][1]), "r"(a[AOFF + 6][2]), "r"(a[AOFF + 6][3]), "r"(a[AOFF + 7][0]), "r"(a[AOFF + 7][1]), "r"(a[AOFF + 7][2]), "r"(a[AOFF + 7][3]), "l"(descB), "n"(BOFF >> 4));
}
};
template <> struct Rng<0, 5, 8> {
template <int BOFF, int AOFF, int NA>
static __device__ __forceinline__ void run(float (&d)[48], const uint32_t (&a)[NA][4], uint64_t descB) {
    asm volatile(
        "{\n"
        ".reg .pred p0, p1;\n"
        ".reg .b64 ta, ta0, tb, tb0;\n"
        "setp.ne.b32 p0, 0, 0;\n"
        "setp.eq.b32 p1, 0, 0;\n"
        "add.s64 tb0, %60, %61;\n"
        "add.s64 tb, tb0, 1568;\n"
        "wgmma.mma_async.sync.aligned.m64n96k16.f32.bf16.bf16 {%0, %1, %2, %3, %4, %5, %6, %7, %8, %9, %10, %11, %12, %13, %14, %15, %16, %17, %18, %19, %20, %21, %22, %23, %24, %25, %26, %27, %28, %29, %30, %31, %32, %33, %34, %35, %36, %37, %38, %39, %40, %41, %42, %43, %44, %45, %46, %47}, {%48, %49, %50, %51}, tb, p1, 1, 1, 1;\n"
        "add.s64 tb, tb0, 1600;\n"
        "wgmma.mma_async.sync.aligned.m64n96k16.f32.bf16.bf16 {%0, %1, %2, %3, %4, %5, %6, %7, %8, %9, %10, %11, %12, %13, %14, %15, %16, %17, %18, %19, %20, %21, %22, %23, %24, %25, %26, %27, %28, %29, %30, %31, %32, %33, %34, %35, %36, %37, %38, %39, %40, %41, %42, %43, %44, %45, %46, %47}, {%52, %53, %54, %55}, tb, p1, 1, 1, 1;\n"
        "add.s64 tb, tb0, 1632;\n"
        "wgmma.mma_async.sync.aligned.m64n96k16.f32.bf16.bf16 {%0, %1, %2, %3, %4, %5, %6, %7, %8, %9, %10, %11, %12, %13, %14, %15, %16, %17, %18, %19, %20, %21, %22, %23, %24, %25, %26, %27, %28, %29, %30, %31, %32, %33, %34, %35, %36, %37, %38, %39, %40, %41, %42, %43, %44, %45, %46, %47}, {%56, %57, %58, %59}, tb, p1, 1, 1, 1;\n"
        "}\n"
        : "+f"(d[0]), "+f"(d[1]), "+f"(d[2]), "+f"(d[3]), "+f"(d[4]), "+f"(d[5]), "+f"(d[6]), "+f"(d[7]), "+f"(d[8]), "+f"(d[9]), "+f"(d[10]), "+f"(d[11]), "+f"(d[12]), "+f"(d[13]), "+f"(d[14]), "+f"(d[15]), "+f"(d[16]), "+f"(d[17]), "+f"(d[18]), "+f"(d[19]), "+f"(d[20]), "+f"(d[21]), "+f"(d[22]), "+f"(d[23]), "+f"(d[24]), "+f"(d[25]), "+f"(d[26]), "+f"(d[27]), "+f"(d[28]), "+f"(d[29]), "+f"(d[30]), "+f"(d[31]), "+f"(d[32]), "+f"(d[33]), "+f"(d[34]), "+f"(d[35]), "+f"(d[36]), "+f"(d[37]), "+f"(d[38]), "+f"(d[39]), "+f"(d[40]), "+f"(d[41]), "+f"(d[42]), "+f"(d[43]), "+f"(d[44]), "+f"(d[45]), "+f"(d[46]), "+f"(d[47])
        : "r"(a[AOFF + 0][0]), "r"(a[AOFF + 0][1]), "r"(a[AOFF + 0][2]), "r"(a[AOFF + 0][3]), "r"(a[AOFF + 1][0]), "r"(a[AOFF + 1][1]), "r"(a[AOFF + 1][2]), "r"(a[AOFF + 1][3]), "r"(a[AOFF + 2][0]), "r"(a[AOFF + 2][1]), "r"(a[AOFF + 2][2]), "r"(a[AOFF + 2][3]), "l"(descB), "n"(BOFF >> 4));
}
};
template <> struct Rng<1, 5, 8> {
template <int BOFF, int AOFF, int NA>
static __device__ __forceinline__ void run(float (&d)[48], const uint32_t (&a)[NA][4], uint64_t descB) {
    asm volatile(
        "{\n"
        ".reg .pred p0, p1;\n"
        ".reg .b64 ta, ta0, tb, tb0;\n"
        "setp.ne.b32 p0, 0, 0;\n"
        "setp.eq.b32 p1, 0, 0;\n"
        "add.s64 tb0, %60, %61;\n"
        "add.s64 tb, tb0, 160;\n"
        "wgmma.mma_async.sync.aligned.m64n96k16.f32.bf16.bf16 {%0, %1, %2, %3, %4, %5, %6, %7, %8, %9, %10, %11, %12, %13, %14, %15, %16, %17, %18, %19, %20, %21, %22, %23, %24, %25, %26, %27, %28, %29, %30, %31, %32, %33, %34, %35, %36, %37, %38, %39, %40, %41, %42, %43, %44, %45, %46, %47}, {%48, %49, %50, %51}, tb, p1, 1, 1, 1;\n"
        "add.s64 tb, tb0, 192;\n"
        "wgmma.mma_async.sync.aligned.m64n96k16.f32.bf16.bf16 {%0, %1, %2, %3, %4, %5, %6, %7, %8, %9, %10, %11, %12, %13, %14, %15, %16, %17, %18, %19, %20, %21, %22, %23, %24, %25, %26, %27, %28, %29, %30, %31, %32, %33, %34, %35, %36, %37, %38, %39, %40, %41, %42, %43, %44, %45, %46, %47}, {%52, %53, %54, %55}, tb, p1, 1, 1, 1;\n"
        "add.s64 tb, tb0, 224;\n"
        "wgmma.mma_async.sync.aligned.m64n96k16.f32.bf16.bf16 {%0, %1, %2, %3, %4, %5, %6, %7, %8, %9, %10, %11, %12, %13, %14, %15, %16, %17, %18, %19, %20, %21, %22, %23, %24, %25, %26, %27, %28, %29, %30, %31, %32, %33, %34, %35, %36, %37, %38, %39, %40, %41, %42, %43, %44, %45, %46, %47}, {%56, %57, %58, %59}, tb, p1, 1, 1, 1;\n"
        "}\n"
        : "+f"(d[0]), "+f"(d[1]), "+f"(d[2]), "+f"(d[3]), "+f"(d[4]), "+f"(d[5]), "+f"(d[6]), "+f"(d[7]), "+f"(d[8]), "+f"(d[9]), "+f"(d[10]), "+f"(d[11]), "+f"(d[12]), "+f"(d[13]), "+f"(d[14]), "+f"(d[15]), "+f"(d[16]), "+f"(d[17]), "+f"(d[18]), "+f"(d[19]), "+f"(d[20]), "+f"(d[21]), "+f"(d[22]), "+f"(d[23]), "+f"(d[24]), "+f"(d[25]), "+f"(d[26]), "+f"(d[27]), "+f"(d[28]), "+f"(d[29]), "+f"(d[30]), "+f"(d[31]), "+f"(d[32]), "+f"(d[33]), "+f"(d[34]), "+f"(d[35]), "+f"(d[36]), "+f"(d[37]), "+f"(d[38]), "+f"(d[39]), "+f"(d[40]), "+f"(d[41]), "+f"(d[42]), "+f"(d[43]), "+f"(d[44]), "+f"(d[45]), "+f"(d[46]), "+f"(d[47])
        : "r"(a[AOFF + 0][0]), "r"(a[AOFF + 0][1]), "r"(a[AOFF + 0][2]), "r"(a[AOFF + 0][3]), "r"(a[AOFF + 1][0]), "r"(a[AOFF + 1][1]), "r"(a[AOFF + 1][2]), "r"(a[AOFF + 1][3]), "r"(a[AOFF + 2][0]), "r"(a[AOFF + 2][1]), "r"(a[AOFF + 2][2]), "r"(a[AOFF + 2][3]), "l"(descB), "n"(BOFF >> 4));
}
};
template <> struct Rng<0, 5, 9> {
template <int BOFF, int AOFF, int NA>
static __device__ __forceinline__ void run(float (&d)[48], const uint32_t (&a)[NA][4], uint64_t descB) {
    asm volatile(
        "{\n"
        ".reg .pred p0, p1;\n"
        ".reg .b64 ta, ta0, tb, tb0;\n"
        "setp.ne.b32 p0, 0, 0;\n"
        "setp.eq.b32 p1, 0, 0;\n"
        "add.s64 tb0, %64, %65;\n"
        "add.s64 tb, tb0, 1568;\n"
        "wgmma.mma_async.sync.aligned.m64n96k16.f32.bf16.bf16 {%0, %1, %2, %3, %4, %5, %6, %7, %8, %9, %10, %11, %12, %13, %14, %15, %16, %17, %18, %19, %20, %21, %22, %23, %24, %25, %26, %27, %28, %29, %30, %31, %32, %33, %34, %35, %36, %37, %38, %39, %40, %41, %42, %43, %44, %45, %46, %47}, {%48, %49, %50, %51}, tb, p1, 1, 1, 1;\n"
        "add.s64 tb, tb0, 1600;\n"
        "wgmma.mma_async.sync.aligned.m64n96k16.f32.bf16.bf16 {%0, %1, %2, %3, %4, %5, %6, %7, %8, %9, %10, %11, %12, %13, %14, %15, %16, %17, %18, %19, %20, %21, %22, %23, %24, %25, %26, %27, %28, %29, %30, %31, %32, %33, %34, %35, %36, %37, %38, %39, %40, %41, %42, %43, %44, %45, %46, %47}, {%52, %53, %54, %55}, tb, p1, 1, 1, 1;\n"
        "add.s64 tb, tb0, 1632;\n"
        "wgmma.mma_async.sync.aligned.m64n96k16.f32.bf16.bf16 {%0, %1, %2, %3, %4, %5, %6, %7, %8, %9, %10, %11, %12, %13, %14, %15, %16, %17, %18, %19, %20, %21, %22, %23, %24, %25, %26, %27, %28, %29, %30, %31, %32, %33, %34, %35, %36, %37, %38, %39, %40, %41, %42, %43, %44, %45, %46, %47}, {%56, %57, %58, %59}, tb, p1, 1, 1, 1;\n"
        "add.s64 tb, tb0, 3072;\n"
        "wgmma.mma_async.sync.aligned.m64n96k16.f32.bf16.bf16 {%0, %1, %2, %3, %4, %5, %6, %7, %8, %9, %10, %11, %12, %13, %14, %15, %16, %17, %18, %19, %20, %21, %22, %23, %24, %25, %26, %27, %28, %29, %30, %31, %32, %33, %34, %35, %36, %37, %38, %39, %40, %41, %42, %43, %44, %45, %46, %47}, {%60, %61, %62, %63}, tb, p1, 1, 1, 1;\n"
        "}\n"
        : "+f"(d[0]), "+f"(d[1]), "+f"(d[2]), "+f"(d[3]), "+f"(d[4]), "+f"(d[5]), "+f"(d[6]), "+f"(d[7]), "+f"(d[8]), "+f"(d[9]), "+f"(d[10]), "+f"(d[11]), "+f"(d[12]), "+f"(d[13]), "+f"(d[14]), "+f"(d[15]), "+f"(d[16]), "+f"(d[17]), "+f"(d[18]), "+f"(d[19]), "+f"(d[20]), "+f"(d[21]), "+f"(d[22]), "+f"(d[23]), "+f"(d[24]), "+f"(d[25]), "+f"(d[26]), "+f"(d[27]), "+f"(d[28]), "+f"(d[29]), "+f"(d[30]), "+f"(d[31]), "+f"(d[32]), "+f"(d[33]), "+f"(d[34]), "+f"(d[35]), "+f"(d[36]), "+f"(d[37]), "+f"(d[38]), "+f"(d[39]), "+f"(d[40]), "+f"(d[41]), "+f"(d[42]), "+f"(d[43]), "+f"(d[44]), "+f"(d[45]), "+f"(d[46]), "+f"(d[47])
        : "r"(a[AOFF + 0][0]), "r"(a[AOFF + 0][1]), "r"(a[AOFF + 0][2]), "r"(a[AOFF + 0][3]), "r"(a[AOFF + 1][0]), "r"(a[AOFF + 1][1]), "r"(a[AOFF + 1][2]), "r"(a[AOFF + 1][3]), "r"(a[AOFF + 2][0]), "r"(a[AOFF + 2][1]), "r"(a[AOFF + 2][2]), "r"(a[AOFF + 2][3]), "r"(a[AOFF + 3][0]), "r"(a[AOFF + 3][1]), "r"(a[AOFF + 3][2]), "r"(a[AOFF + 3][3]), "l"(descB), "n"(BOFF >> 4));
}
};
template <> struct Rng<1, 5, 9> {
template <int BOFF, int AOFF, int NA>
static __device__ __forceinline__ void run(float (&d)[48], const uint32_t (&a)[NA][4], uint64_t descB) {
    asm volatile(
        "{\n"
        ".reg .pred p0, p1;\n"
        ".reg .b64 ta, ta0, tb, tb0;\n"
        "setp.ne.b32 p0, 0, 0;\n"
        "setp.eq.b32 p1, 0, 0;\n"
        "add.s64 tb0, %64, %65;\n"
        "add.s64 tb, tb0, 160;\n"
        "wgmma.mma_async.sync.aligned.m64n96k16.f32.bf16.bf16 {%0, %1, %2, %3, %4, %5, %6, %7, %8, %9, %10, %11, %12, %13, %14, %15, %16, %17, %18, %19, %20, %21, %22, %23, %24, %25, %26, %27, %28, %29, %30, %31, %32, %33, %34, %35, %36, %37, %38, %39, %40, %41, %42, %43, %44, %45, %46, %47}, {%48, %49, %50, %51}, tb, p1, 1, 1, 1;\n"
        "add.s64 tb, tb0, 192;\n"
        "wgmma.mma_async.sync.aligned.m64n96k16.f32.bf16.bf16 {%0, %1, %2, %3, %4, %5, %6, %7, %8, %9, %10, %11, %12, %13, %14, %15, %16, %17, %18, %19, %20, %21, %22, %23, %24, %25, %26, %27, %28, %29, %30, %31, %32, %33, %34, %35, %36, %37, %38, %39, %40, %41, %42, %43, %44, %45, %46, %47}, {%52, %53, %54, %55}, tb, p1, 1, 1, 1;\n"
        "add.s64 tb, tb0, 224;\n"
        "wgmma.mma_async.sync.aligned.m64n96k16.f32.bf16.bf16 {%0, %1, %2, %3, %4, %5, %6, %7, %8, %9, %10, %11, %12, %13, %14, %15, %16, %17, %18, %19, %20, %21, %22, %23, %24, %25, %26, %27, %28, %29, %30, %31, %32, %33, %34, %35, %36, %37, %38, %39, %40, %41, %42, %43, %44, %45, %46, %47}, {%56, %57, %58, %59}, tb, p1, 1, 1, 1;\n"
        "add.s64 tb, tb0, 256;\n"
        "wgmma.mma_async.sync.aligned.m64n96k16.f32.bf16.bf16 {%0, %1, %2, %3, %4, %5, %6, %7, %8, %9, %10, %11, %12, %13, %14, %15, %16, %17, %18, %19, %20, %21, %22, %23, %24, %25, %26, %27, %28, %29, %30, %31, %32, %33, %34, %35, %36, %37, %38, %39, %40, %41, %42, %43, %44, %45, %46, %47}, {%60, %61, %62, %63}, tb, p1, 1, 1, 1;\n"
        "}\n"
        : "+f"(d[0]), "+f"(d[1]), "+f"(d[2]), "+f"(d[3]), "+f"(d[4]), "+f"(d[5]), "+f"(d[6]), "+f"(d[7]), "+f"(d[8]), "+f"(d[9]), "+f"(d[10]), "+f"(d[11]), "+f"(d[12]), "+f"(d[13]), "+f"(d[14]), "+f"(d[15]), "+f"(d[16]), "+f"(d[17]), "+f"(d[18]), "+f"(d[19]), "+f"(d[20]), "+f"(d[21]), "+f"(d[22]), "+f"(d[23]), "+f"(d[24]), "+f"(d[25]), "+f"(d[26]), "+f"(d[27]), "+f"(d[28]), "+f"(d[29]), "+f"(d[30]), "+f"(d[31]), "+f"(d[32]), "+f"(d[33]), "+f"(d[34]), "+f"(d[35]), "+f"(d[36]), "+f"(d[37]), "+f"(d[38]), "+f"(d[39]), "+f"(d[40]), "+f"(d[41]), "+f"(d[42]), "+f"(d[43]), "+f"(d[44]), "+f"(d[45]), "+f"(d[46]), "+f"(d[47])
        : "r"(a[AOFF + 0][0]), "r"(a[AOFF + 0][1]), "r"(a[AOFF + 0][2]), "r"(a[AOFF + 0][3]), "r"(a[AOFF + 1][0]), "r"(a[AOFF + 1][1]), "r"(a[AOFF + 1][2]), "r"(a[AOFF + 1][3]), "r"(a[AOFF + 2][0]), "r"(a[AOFF + 2][1]), "r"(a[AOFF + 2][2]), "r"(a[AOFF + 2][3]), "r"(a[AOFF + 3][0]), "r"(a[AOFF + 3][1]), "r"(a[AOFF + 3][2]), "r"(a[AOFF + 3][3]), "l"(descB), "n"(BOFF >> 4));
}
};
template <> struct Rng<0, 5, 10> {
template <int BOFF, int AOFF, int NA>
static __device__ __forceinline__ void run(float (&d)[48], const uint32_t (&a)[NA][4], uint64_t descB) {
    asm volatile(
        "{\n"
        ".reg .pred p0, p1;\n"
        ".reg .b64 ta, ta0, tb, tb0;\n"
        "setp.ne.b32 p0, 0, 0;\n"
        "setp.eq.b32 p1, 0, 0;\n"
        "add.s64 tb0, %68, %69;\n"
        "add.s64 tb, tb0, 1568;\n"
        "wgmma.mma_async.sync.aligned.m64n96k16.f32.bf16.bf16 {%0, %1, %2, %3, %4, %5, %6, %7, %8, %9, %10, %11, %12, %13, %14, %15, %16, %17, %18, %19, %20, %21, %22, %23, %24, %25, %26, %27, %28, %29, %30, %31, %32, %33, %34, %35, %36, %37, %38, %39, %40, %41, %42, %43, %44, %45, %46, %47}, {%48, %49, %50, %51}, tb, p1, 1, 1, 1;\n"
        "add.s64 tb, tb0, 1600;\n"
        "wgmma.mma_async.sync.aligned.m64n96k16.f32.bf16.bf16 {%0, %1, %2, %3, %4, %5, %6, %7, %8, %9, %10, %11, %12, %13, %14, %15, %16, %17, %18, %19, %20, %21, %22, %23, %24, %25, %26, %27, %28, %29, %30, %31, %32, %33, %34, %35, %36, %37, %38, %39, %40, %41, %42, %43, %44, %45, %46, %47}, {%52, %53, %54, %55}, tb, p1, 1, 1, 1;\n"
        "add.s64 tb, tb0, 1632;\n"
        "wgmma.mma_async.sync.aligned.m64n96k16.f32.bf16.bf16 {%0, %1, %2, %3, %4, %5, %6, %7, %8, %9, %10, %11, %12, %13, %14, %15, %16, %17, %18, %19, %20, %21, %22, %23, %24, %25, %26, %27, %28, %29, %30, %31, %32, %33, %34, %35, %36, %37, %38, %39, %40, %41, %42, %43, %44, %45, %46, %47}, {%56, %57, %58, %59}, tb, p1, 1, 1, 1;\n"
        "add.s64 tb, tb0, 3072;\n"
        "wgmma.mma_async.sync.aligned.m64n96k16.f32.bf16.bf16 {%0, %1, %2, %3, %4, %5, %6, %7, %8, %9, %10, %11, %12, %13, %14, %15, %16, %17, %18, %19, %20, %21, %22, %23, %24, %25, %26, %27, %28, %29, %30, %31, %32, %33, %34, %35, %36, %37, %38, %39, %40, %41, %42, %43, %44, %45, %46, %47}, {%60, %61, %62, %63}, tb, p1, 1, 1, 1;\n"
        "add.s64 tb, tb0, 3104;\n"
        "wgmma.mma_async.sync.aligned.m64n96k16.f32.bf16.bf16 {%0, %1, %2, %3, %4, %5, %6, %7, %8, %9, %10, %11, %12, %13, %14, %15, %16, %17, %18, %19, %20, %21, %22, %23, %24, %25, %26, %27, %28, %29, %30, %31, %32, %33, %34, %35, %36, %37, %38, %39, %40, %41, %42, %43, %44, %45, %46, %47}, {%64, %65, %66, %67}, tb, p1, 1, 1, 1;\n"
        "}\n"
        : "+f"(d[0]), "+f"(d[1]), "+f"(d[2]), "+f"(d[3]), "+f"(d[4]), "+f"(d[5]), "+f"(d[6]), "+f"(d[7]), "+f"(d[8]), "+f"(d[9]), "+f"(d[10]), "+f"(d[11]), "+f"(d[12]), "+f"(d[13]), "+f"(d[14]), "+f"(d[15]), "+f"(d[16]), "+f"(d[17]), "+f"(d[18]), "+f"(d[19]), "+f"(d[20]), "+f"(d[21]), "+f"(d[22]), "+f"(d[23]), "+f"(d[24]), "+f"(d[25]), "+f"(d[26]), "+f"(d[27]), "+f"(d[28]), "+f"(d[29]), "+f"(d[30]), "+f"(d[31]), "+f"(d[32]), "+f"(d[33]), "+f"(d[34]), "+f"(d[35]), "+f"(d[36]), "+f"(d[37]), "+f"(d[38]), "+f"(d[39]), "+f"(d[40]), "+f"(d[41]), "+f"(d[42]), "+f"(d[43]), "+f"(d[44]), "+f"(d[45]), "+f"(d[46]), "+f"(d[47])
        : "r"(a[AOFF + 0][0]), "r"(a[AOFF + 0][1]), "r"(a[AOFF + 0][2]), "r"(a[AOFF + 0][3]), "r"(a[AOFF + 1][0]), "r"(a[AOFF + 1][1]), "r"(a[AOFF + 1][2]), "r"(a[AOFF + 1][3]), "r"(a[AOFF + 2][0]), "r"(a[AOFF + 2][1]), "r"(a[AOFF + 2][2]), "r"(a[AOFF + 2][3]), "r"(a[AOFF + 3][0]), "r"(a[AOFF + 3][1]), "r"(a[AOFF + 3][2]), "r"(a[AOFF + 3][3]), "r"(a[AOFF + 4][0]), "r"(a[AOFF + 4][1]), "r"(a[AOFF + 4][2]), "r"(a[AOFF + 4][3]), "l"(descB), "n"(BOFF >> 4));
}
};
template <> struct Rng<1, 5, 10> {
template <int BOFF, int AOFF, int NA>
static __device__ __forceinline__ void run(float (&d)[48], const uint32_t (&a)[NA][4], uint64_t descB) {
    asm volatile(
        "{\n"
        ".reg .pred p0, p1;\n"
        ".reg .b64 ta, ta0, tb, tb0;\n"
        "setp.ne.b32 p0, 0, 0;\n"
        "setp.eq.b32 p1, 0, 0;\n"
        "add.s64 tb0, %68, %69;\n"
        "add.s64 tb, tb0, 160;\n"
        "wgmma.mma_async.sync.aligned.m64n96k16.f32.bf16.bf16 {%0, %1, %2, %3, %4, %5, %6, %7, %8, %9, %10, %11, %12, %13, %14, %15, %16, %17, %18, %19, %20, %21, %22, %23, %24, %25, %26, %27, %28, %29, %30, %31, %32, %33, %34, %35, %36, %37, %38, %39, %40, %41, %42, %43, %44, %45, %46, %47}, {%48, %49, %50, %51}, tb, p1, 1, 1, 1;\n"
        "add.s64 tb, tb0, 192;\n"
        "wgmma.mma_async.sync.aligned.m64n96k16.f32.bf16.bf16 {%0, %1, %2, %3, %4, %5, %6, %7, %8, %9, %10, %11, %12, %13, %14, %15, %16, %17, %18, %19, %20, %21, %22, %23, %24, %25, %26, %27, %28, %29, %30, %31, %32, %33, %34, %35, %36, %37, %38, %39, %40, %41, %42, %43, %44, %45, %46, %47}, {%52, %53, %54, %55}, tb, p1, 1, 1, 1;\n"
        "add.s64 tb, tb0, 224;\n"
        "wgmma.mma_async.sync.aligned.m64n96k16.f32.bf16.bf16 {%0, %1, %2, %3, %4, %5, %6, %7, %8, %9, %10, %11, %12, %13, %14, %15, %16, %17, %18, %19, %20, %21, %22, %23, %24, %25, %26, %27, %28, %29, %30, %31, %32, %33, %34, %35, %36, %37, %38, %39, %40, %41, %42, %43, %44, %45, %46, %47}, {%56, %57, %58, %59}, tb, p1, 1, 1, 1;\n"
        "add.s64 tb, tb0, 256;\n"
        "wgmma.mma_async.sync.aligned.m64n96k16.f32.bf16.bf16 {%0, %1, %2, %3, %4, %5, %6, %7, %8, %9, %10, %11, %12, %13, %14, %15, %16, %17, %18, %19, %20, %21, %22, %23, %24, %25, %26, %27, %28, %29, %30, %31, %32, %33, %34, %35, %36, %37, %38, %39, %40, %41, %42, %43, %44, %45, %46, %47}, {%60, %61, %62, %63}, tb, p1, 1, 1, 1;\n"
        "add.s64 tb, tb0, 288;\n"
        "wgmma.mma_async.sync.aligned.m64n96k16.f32.bf16.bf16 {%0, %1, %2, %3, %4, %5, %6, %7, %8, %9, %10, %11, %12, %13, %14, %15, %16, %17, %18, %19, %20, %21, %22, %23, %24, %25, %26, %27, %28, %29, %30, %31, %32, %33, %34, %35, %36, %37, %38, %39, %40, %41, %42, %43, %44, %45, %46, %47}, {%64, %65, %66, %67}, tb, p1, 1, 1, 1;\n"
        "}\n"
        : "+f"(d[0]), "+f"(d[1]), "+f"(d[2]), "+f"(d[3]), "+f"(d[4]), "+f"(d[5]), "+f"(d[6]), "+f"(d[7]), "+f"(d[8]), "+f"(d[9]), "+f"(d[10]), "+f"(d[11]), "+f"(d[12]), "+f"(d[13]), "+f"(d[14]), "+f"(d[15]), "+f"(d[16]), "+f"(d[17]), "+f"(d[18]), "+f"(d[19]), "+f"(d[20]), "+f"(d[21]), "+f"(d[22]), "+f"(d[23]), "+f"(d[24]), "+f"(d[25]), "+f"(d[26]), "+f"(d[27]), "+f"(d[28]), "+f"(d[29]), "+f"(d[30]), "+f"(d[31]), "+f"(d[32]), "+f"(d[33]), "+f"(d[34]), "+f"(d[35]), "+f"(d[36]), "+f"(d[37]), "+f"(d[38]), "+f"(d[39]), "+f"(d[40]), "+f"(d[41]), "+f"(d[42]), "+f"(d[43]), "+f"(d[44]), "+f"(d[45]), "+f"(d[46]), "+f"(d[47])
        : "r"(a[AOFF + 0][0]), "r"(a[AOFF + 0][1]), "r"(a[AOFF + 0][2]), "r"(a[AOFF + 0][3]), "r"(a[AOFF + 1][0]), "r"(a[AOFF + 1][1]), "r"(a[AOFF + 1][2]), "r"(a[AOFF + 1][3]), "r"(a[AOFF + 2][0]), "r"(a[AOFF + 2][1]), "r"(a[AOFF + 2][2]), "r"(a[AOFF + 2][3]), "r"(a[AOFF + 3][0]), "r"(a[AOFF + 3][1]), "r"(a[AOFF + 3][2]), "r"(a[AOFF + 3][3]), "r"(a[AOFF + 4][0]), "r"(a[AOFF + 4][1]), "r"(a[AOFF + 4][2]), "r"(a[AOFF + 4][3]), "l"(descB), "n"(BOFF >> 4));
}
};
template <> struct Rng<0, 5, 12> {
template <int BOFF, int AOFF, int NA>
static __device__ __forceinline__ void run(float (&d)[48], const uint32_t (&a)[NA][4], uint64_t descB) {
    asm volatile(
        "{\n"
        ".reg .pred p0, p1;\n"
        ".reg .b64 ta, ta0, tb, tb0;\n"
        "setp.ne.b32 p0, 0, 0;\n"
        "setp.eq.b32 p1, 0, 0;\n"
        "add.s64 tb0, %76, %77;\n"
        "add.s64 tb, tb0, 1568;\n"
        "wgmma.mma_async.sync.aligned.m64n96k16.f32.bf16.bf16 {%0, %1, %2, %3, %4, %5, %6, %7, %8, %9, %10, %11, %12, %13, %14, %15, %16, %17, %18, %19, %20, %21, %22, %23, %24, %25, %26, %27, %28, %29, %30, %31, %32, %33, %34, %35, %36, %37, %38, %39, %40, %41, %42, %43, %44, %45, %46, %47}, {%48, %49, %50, %51}, tb, p1, 1, 1, 1;\n"
        "add.s64 tb, tb0, 1600;\n"
        "wgmma.mma_async.sync.aligned.m64n96k16.f32.bf16.bf16 {%0, %1, %2, %3, %4, %5, %6, %7, %8, %9, %10, %11, %12, %13, %14, %15, %16, %17, %18, %19, %20, %21, %22, %23, %24, %25, %26, %27, %28, %29, %30, %31, %32, %33, %34, %35, %36, %37, %38, %39, %40, %41, %42, %43, %44, %45, %46, %47}, {%52, %53, %54, %55}, tb, p1, 1, 1, 1;\n"
        "add.s64 tb, tb0, 1632;\n"
        "wgmma.mma_async.sync.aligned.m64n96k16.f32.bf16.bf16 {%0, %1, %2, %3, %4, %5, %6, %7, %8, %9, %10, %11, %12, %13, %14, %15, %16, %17, %18, %19, %20, %21, %22, %23, %24, %25, %26, %27, %28, %29, %30, %31, %32, %33, %34, %35, %36, %37, %38, %39, %40, %41, %42, %43, %44, %45, %46, %47}, {%56, %57, %58, %59}, tb, p1, 1, 1, 1;\n"
        "add.s64 tb, tb0, 3072;\n"
        "wgmma.mma_async.sync.aligned.m64n96k16.f32.bf16.bf16 {%0, %1, %2, %3, %4, %5, %6, %7, %8, %9, %10, %11, %12, %13, %14, %15, %16, %17, %18, %19, %20, %21, %22, %23, %24, %25, %26, %27, %28, %29, %30, %31, %32, %33, %34, %35, %36, %37, %38, %39, %40, %41, %42, %43, %44, %45, %46, %47}, {%60, %61, %62, %63}, tb, p1, 1, 1, 1;\n"
        "add.s64 tb, tb0, 3104;\n"
        "wgmma.mma_async.sync.aligned.m64n96k16.f32.bf16.bf16 {%0, %1, %2, %3, %4, %5, %6, %7, %8, %9, %10, %11, %12, %13, %14, %15, %16, %17, %18, %19, %20, %21, %22, %23, %24, %25, %26, %27, %28, %29, %30, %31, %32, %33, %34, %35, %36, %37, %38, %39, %40, %41, %42, %43, %44, %45, %46, %47}, {%64, %65, %66, %67}, tb, p1, 1, 1, 1;\n"
        "add.s64 tb, tb0, 3136;\n"
        "wgmma.mma_async.sync.aligned.m64n96k16.f32.bf16.bf16 {%0, %1, %2, %3, %4, %5, %6, %7, %8, %9, %10, %11, %12, %13, %14, %15, %16, %17, %18, %19, %20, %21, %22, %23, %24, %25, %26, %27, %28, %29, %30, %31, %32, %33, %34, %35, %36, %37, %38, %39, %40, %41, %42, %43, %44, %45, %46, %47}, {%68, %69, %70, %71}, tb, p1, 1, 1, 1;\n"
        "add.s64 tb, tb0, 3168;\n"
        "wgmma.mma_async.sync.aligned.m64n96k16.f32.bf16.bf16 {%0, %1, %2, %3, %4, %5, %6, %7, %8, %9, %10, %11, %12, %13, %14, %15, %16, %17, %18, %19, %20, %21, %22, %23, %24, %25, %26, %27, %28, %29, %30, %31, %32, %33, %34, %35, %36, %37, %38, %39, %40, %41, %42, %43, %44, %45, %46, %47}, {%72, %73, %74, %75}, tb, p1, 1, 1, 1;\n"
        "}\n"
        : "+f"(d[0]), "+f"(d[1]), "+f"(d[2]), "+f"(d[3]), "+f"(d[4]), "+f"(d[5]), "+f"(d[6]), "+f"(d[7]), "+f"(d[8]), "+f"(d[9]), "+f"(d[10]), "+f"(d[11]), "+f"(d[12]), "+f"(d[13]), "+f"(d[14]), "+f"(d[15]), "+f"(d[16]), "+f"(d[17]), "+f"(d[18]), "+f"(d[19]), "+f"(d[20]), "+f"(d[21]), "+f"(d[22]), "+f"(d[23]), "+f"(d[24]), "+f"(d[25]), "+f"(d[26]), "+f"(d[27]), "+f"(d[28]), "+f"(d[29]), "+f"(d[30]), "+f"(d[31]), "+f"(d[32]), "+f"(d[33]), "+f"(d[34]), "+f"(d[35]), "+f"(d[36]), "+f"(d[37]), "+f"(d[38]), "+f"(d[39]), "+f"(d[40]), "+f"(d[41]), "+f"(d[42]), "+f"(d[43]), "+f"(d[44]), "+f"(d[45]), "+f"(d[46]), "+f"(d[47])
        : "r"(a[AOFF + 0][0]), "r"(a[AOFF + 0][1]), "r"(a[AOFF + 0][2]), "r"(a[AOFF + 0][3]), "r"(a[AOFF + 1][0]), "r"(a[AOFF + 1][1]), "r"(a[AOFF + 1][2]), "r"(a[AOFF + 1][3]), "r"(a[AOFF + 2][0]), "r"(a[AOFF + 2][1]), "r"(a[AOFF + 2][2]), "r"(a[AOFF + 2][3]), "r"(a[AOFF + 3][0]), "r"(a[AOFF + 3][1]), "r"(a[AOFF + 3][2]), "r"(a[AOFF + 3][3]), "r"(a[AOFF + 4][0]), "r"(a[AOFF + 4][1]), "r"(a[AOFF + 4][2]), "r"(a[AOFF + 4][3]), "r"(a[AOFF + 5][0]), "r"(a[AOFF + 5][1]), "r"(a[AOFF + 5][2]), "r"(a[AOFF + 5][3]), "r"(a[AOFF + 6][0]), "r"(a[AOFF + 6][1]), "r"(a[AOFF + 6][2]), "r"(a[AOFF + 6][3]), "l"(descB), "n"(BOFF >> 4));
}
};
template <> struct Rng<1, 5, 12> {
template <int BOFF, int AOFF, int NA>
static __device__ __forceinline__ void run(float (&d)[48], const uint32_t (&a)[NA][4], uint64_t descB) {
    asm volatile(
        "{\n"
        ".reg .pred p0, p1;\n"
        ".reg .b64 ta, ta0, tb, tb0;\n"
        "setp.ne.b32 p0, 0, 0;\n"
        "setp.eq.b32 p1, 0, 0;\n"
        "add.s64 tb0, %76, %77;\n"
        "add.s64 tb, tb0, 160;\n"
        "wgmma.mma_async.sync.aligned.m64n96k16.f32.bf16.bf16 {%0, %1, %2, %3, %4, %5, %6, %7, %8, %9, %10, %11, %12, %13, %14, %15, %16, %17, %18, %19, %20, %21, %22, %23, %24, %25, %26, %27, %28, %29, %30, %31, %32, %33, %34, %35, %36, %37, %38, %39, %40, %41, %42, %43, %44, %45, %46, %47}, {%48, %49, %50, %51}, tb, p1, 1, 1, 1;\n"
        "add.s64 tb, tb0, 192;\n"
        "wgmma.mma_async.sync.aligned.m64n96k16.f32.bf16.bf16 {%0, %1, %2, %3, %4, %5, %6, %7, %8, %9, %10, %11, %12, %13, %14, %15, %16, %17, %18, %19, %20, %21, %22, %23, %24, %25, %26, %27, %28, %29, %30, %31, %32, %33, %34, %35, %36, %37, %38, %39, %40, %41, %42, %43, %44, %45, %46, %47}, {%52, %53, %54, %55}, tb, p1, 1, 1, 1;\n"
        "add.s64 tb, tb0, 224;\n"
        "wgmma.mma_async.sync.aligned.m64n96k16.f32.bf16.bf16 {%0, %1, %2, %3, %4, %5, %6, %7, %8, %9, %10, %11, %12, %13, %14, %15, %16, %17, %18, %19, %20, %21, %22, %23, %24, %25, %26, %27, %28, %29, %30, %31, %32, %33, %34, %35, %36, %37, %38, %39, %40, %41, %42, %43, %44, %45, %46, %47}, {%56, %57, %58, %59}, tb, p1, 1, 1, 1;\n"
        "add.s64 tb, tb0, 256;\n"
        "wgmma.mma_async.sync.aligned.m64n96k16.f32.bf16.bf16 {%0, %1, %2, %3, %4, %5, %6, %7, %8, %9, %10, %11, %12, %13, %14, %15, %16, %17, %18, %19, %20, %21, %22, %23, %24, %25, %26, %27, %28, %29, %30, %31, %32, %33, %34, %35, %36, %37, %38, %39, %40, %41, %42, %43, %44, %45, %46, %47}, {%60, %61, %62, %63}, tb, p1, 1, 1, 1;\n"
        "add.s64 tb, tb0, 288;\n"
        "wgmma.mma_async.sync.aligned.m64n96k16.f32.bf16.bf16 {%0, %1, %2, %3, %4, %5, %6, %7, %8, %9, %10, %11, %12, %13, %14, %15, %16, %17, %18, %19, %20, %21, %22, %23, %24, %25, %26, %27, %28, %29, %30, %31, %32, %33, %34, %35, %36, %37, %38, %39, %40, %41, %42, %43, %44, %45, %46, %47}, {%64, %65, %66, %67}, tb, p1, 1, 1, 1;\n"
        "add.s64 tb, tb0, 320;\n"
        "wgmma.mma_async.sync.aligned.m64n96k16.f32.bf16.bf16 {%0, %1, %2, %3, %4, %5, %6, %7, %8, %9, %10, %11, %12, %13, %14, %15, %16, %17, %18, %19, %20, %21, %22, %23, %24, %25, %26, %27, %28, %29, %30, %31, %32, %33, %34, %35, %36, %37, %38, %39, %40, %41, %42, %43, %44, %45, %46, %47}, {%68, %69, %70, %71}, tb, p1, 1, 1, 1;\n"
        "add.s64 tb, tb0, 352;\n"
        "wgmma.mma_async.sync.aligned.m64n96k16.f32.bf16.bf16 {%0, %1, %2, %3, %4, %5, %6, %7, %8, %9, %10, %11, %12, %13, %14, %15, %16, %17, %18, %19, %20, %21, %22, %23, %24, %25, %26, %27, %28, %29, %30, %31, %32, %33, %34, %35, %36, %37, %38, %39, %40, %41, %42, %43, %44, %45, %46, %47}, {%72, %73, %74, %75}, tb, p1, 1, 1, 1;\n"
        "}\n"
        : "+f"(d[0]), "+f"(d[1]), "+f"(d[2]), "+f"(d[3]), "+f"(d[4]), "+f"(d[5]), "+f"(d[6]), "+f"(d[7]), "+f"(d[8]), "+f"(d[9]), "+f"(d[10]), "+f"(d[11]), "+f"(d[12]), "+f"(d[13]), "+f"(d[14]), "+f"(d[15]), "+f"(d[16]), "+f"(d[17]), "+f"(d[18]), "+f"(d[19]), "+f"(d[20]), "+f"(d[21]), "+f"(d[22]), "+f"(d[23]), "+f"(d[24]), "+f"(d[25]), "+f"(d[26]), "+f"(d[27]), "+f"(d[28]), "+f"(d[29]), "+f"(d[30]), "+f"(d[31]), "+f"(d[32]), "+f"(d[33]), "+f"(d[34]), "+f"(d[35]), "+f"(d[36]), "+f"(d[37]), "+f"(d[38]), "+f"(d[39]), "+f"(d[40]), "+f"(d[41]), "+f"(d[42]), "+f"(d[43]), "+f"(d[44]), "+f"(d[45]), "+f"(d[46]), "+f"(d[47])
        : "r"(a[AOFF + 0][0]), "r"(a[AOFF + 0][1]), "r"(a[AOFF + 0][2]), "r"(a[AOFF + 0][3]), "r"(a[AOFF + 1][0]), "r"(a[AOFF + 1][1]), "r"(a[AOFF + 1][2]), "r"(a[AOFF + 1][3]), "r"(a[AOFF + 2][0]), "r"(a[AOFF + 2][1]), "r"(a[AOFF + 2][2]), "r"(a[AOFF + 2][3]), "r"(a[AOFF + 3][0]), "r"(a[AOFF + 3][1]), "r"(a[AOFF + 3][2]), "r"(a[AOFF + 3][3]), "r"(a[AOFF + 4][0]), "r"(a[AOFF + 4][1]), "r"(a[AOFF + 4][2]), "r"(a[AOFF + 4][3]), "r"(a[AOFF + 5][0]), "r"(a[AOFF + 5][1]), "r"(a[AOFF + 5][2]), "r"(a[AOFF + 5][3]), "r"(a[AOFF + 6][0]), "r"(a[AOFF + 6][1]), "r"(a[AOFF + 6][2]), "r"(a[AOFF + 6][3]), "l"(descB), "n"(BOFF >> 4));
}
};
template <> struct Rng<0, 6, 9> {
template <int BOFF, int AOFF, int NA>
static __device__ __forceinline__ void run(float (&d)[48], const uint32_t (&a)[NA][4], uint64_t descB) {
    asm volatile(
        "{\n"
        ".reg .pred p0, p1;\n"
        ".reg .b64 ta, ta0, tb, tb0;\n"
        "setp.ne.b32 p0, 0, 0;\n"
        "setp.eq.b32 p1, 0, 0;\n"
        "add.s64 tb0, %60, %61;\n"
        "add.s64 tb, tb0, 1600;\n"
        "wgmma.mma_async.sync.aligned.m64n96k16.f32.bf16.bf16 {%0, %1, %2, %3, %4, %5, %6, %7, %8, %9, %10, %11, %12, %13, %14, %15, %16, %17, %18, %19, %20, %21, %22, %23, %24, %25, %26, %27, %28, %29, %30, %31, %32, %33, %34, %35, %36, %37, %38, %39, %40, %41, %42, %43, %44, %45, %46, %47}, {%48, %49, %50, %51}, tb, p1, 1, 1, 1;\n"
        "add.s64 tb, tb0, 1632;\n"
        "wgmma.mma_async.sync.aligned.m64n96k16.f32.bf16.bf16 {%0, %1, %2, %3, %4, %5, %6, %7, %8, %9, %10, %11, %12, %13, %14, %15, %16, %17, %18, %19, %20, %21, %22, %23, %24, %25, %26, %27, %28, %29, %30, %31, %32, %33, %34, %35, %36, %37, %38, %39, %40, %41, %42, %43, %44, %45, %46, %47}, {%52, %53, %54, %55}, tb, p1, 1, 1, 1;\n"
        "add.s64 tb, tb0, 3072;\n"
        "wgmma.mma_async.sync.aligned.m64n96k16.f32.bf16.bf16 {%0, %1, %2, %3, %4, %5, %6, %7, %8, %9, %10, %11, %12, %13, %14, %15, %16, %17, %18, %19, %20, %21, %22, %23, %24, %25, %26, %27, %28, %29, %30, %31, %32, %33, %34, %35, %36, %37, %38, %39, %40, %41, %42, %43, %44, %45, %46, %47}, {%56, %57, %58, %59}, tb, p1, 1, 1, 1;\n"
        "}\n"
        : "+f"(d[0]), "+f"(d[1]), "+f"(d[2]), "+f"(d[3]), "+f"(d[4]), "+f"(d[5]), "+f"(d[6]), "+f"(d[7]), "+f"(d[8]), "+f"(d[9]), "+f"(d[10]), "+f"(d[11]), "+f"(d[12]), "+f"(d[13]), "+f"(d[14]), "+f"(d[15]), "+f"(d[16]), "+f"(d[17]), "+f"(d[18]), "+f"(d[19]), "+f"(d[20]), "+f"(d[21]), "+f"(d[22]), "+f"(d[23]), "+f"(d[24]), "+f"(d[25]), "+f"(d[26]), "+f"(d[27]), "+f"(d[28]), "+f"(d[29]), "+f"(d[30]), "+f"(d[31]), "+f"(d[32]), "+f"(d[33]), "+f"(d[34]), "+f"(d[35]), "+f"(d[36]), "+f"(d[37]), "+f"(d[38]), "+f"(d[39]), "+f"(d[40]), "+f"(d[41]), "+f"(d[42]), "+f"(d[43]), "+f"(d[44]), "+f"(d[45]), "+f"(d[46]), "+f"(d[47])
        : "r"(a[AOFF + 0][0]), "r"(a[AOFF + 0][1]), "r"(a[AOFF + 0][2]), "r"(a[AOFF + 0][3]), "r"(a[AOFF + 1][0]), "r"(a[AOFF + 1][1]), "r"(a[AOFF + 1][2]), "r"(a[AOFF + 1][3]), "r"(a[AOFF + 2][0]), "r"(a[AOFF + 2][1]), "r"(a[AOFF + 2][2]), "r"(a[AOFF + 2][3]), "l"(descB), "n"(BOFF >> 4));
}
};
template <> struct Rng<1, 6, 9> {
template <int BOFF, int AOFF, int NA>
static __device__ __forceinline__ void run(float (&d)[48], const uint32_t (&a)[NA][4], uint64_t descB) {
    asm volatile(
        "{\n"
        ".reg .pred p0, p1;\n"
        ".reg .b64 ta, ta0, tb, tb0;\n"
        "setp.ne.b32 p0, 0, 0;\n"
        "setp.eq.b32 p1, 0, 0;\n"
        "add.s64 tb0, %60, %61;\n"
        "add.s64 tb, tb0, 192;\n"
        "wgmma.mma_async.sync.aligned.m64n96k16.f32.bf16.bf16 {%0, %1, %2, %3, %4, %5, %6, %7, %8, %9, %10, %11, %12, %13, %14, %15, %16, %17, %18, %19, %20, %21, %22, %23, %24, %25, %26, %27, %28, %29, %30, %31, %32, %33, %34, %35, %36, %37, %38, %39, %40, %41, %42, %43, %44, %45, %46, %47}, {%48, %49, %50, %51}, tb, p1, 1, 1, 1;\n"
        "add.s64 tb, tb0, 224;\n"
        "wgmma.mma_async.sync.aligned.m64n96k16.f32.bf16.bf16 {%0, %1, %2, %3, %4, %5, %6, %7, %8, %9, %10, %11, %12, %13, %14, %15, %16, %17, %18, %19, %20, %21, %22, %23, %24, %25, %26, %27, %28, %29, %30, %31, %32, %33, %34, %35, %36, %37, %38, %39, %40, %41, %42, %43, %44, %45, %46, %47}, {%52, %53, %54, %55}, tb, p1, 1, 1, 1;\n"
        "add.s64 tb, tb0, 256;\n"
        "wgmma.mma_async.sync.aligned.m64n96k16.f32.bf16.bf16 {%0, %1, %2, %3, %4, %5, %6, %7, %8, %9, %10, %11, %12, %13, %14, %15, %16, %17, %18, %19, %20, %21, %22, %23, %24, %25, %26, %27, %28, %29, %30, %31, %32, %33, %34, %35, %36, %37, %38, %39, %40, %41, %42, %43, %44, %45, %46, %47}, {%56, %57, %58, %59}, tb, p1, 1, 1, 1;\n"
        "}\n"
        : "+f"(d[0]), "+f"(d[1]), "+f"(d[2]), "+f"(d[3]), "+f"(d[4]), "+f"(d[5]), "+f"(d[6]), "+f"(d[7]), "+f"(d[8]), "+f"(d[9]), "+f"(d[10]), "+f"(d[11]), "+f"(d[12]), "+f"(d[13]), "+f"(d[14]), "+f"(d[15]), "+f"(d[16]), "+f"(d[17]), "+f"(d[18]), "+f"(d[19]), "+f"(d[20]), "+f"(d[21]), "+f"(d[22]), "+f"(d[23]), "+f"(d[24]), "+f"(d[25]), "+f"(d[26]), "+f"(d[27]), "+f"(d[28]), "+f"(d[29]), "+f"(d[30]), "+f"(d[31]), "+f"(d[32]), "+f"(d[33]), "+f"(d[34]), "+f"(d[35]), "+f"(d[36]), "+f"(d[37]), "+f"(d[38]), "+f"(d[39]), "+f"(d[40]), "+f"(d[41]), "+f"(d[42]), "+f"(d[43]), "+f"(d[44]), "+f"(d[45]), "+f"(d[46]), "+f"(d[47])
        : "r"(a[AOFF + 0][0]), "r"(a[AOFF + 0][1]), "r"(a[AOFF + 0][2]), "r"(a[AOFF + 0][3]), "r"(a[AOFF + 1][0]), "r"(a[AOFF + 1][1]), "r"(a[AOFF + 1][2]), "r"(a[AOFF + 1][3]), "r"(a[AOFF + 2][0]), "r"(a[AOFF + 2][1]), "r"(a[AOFF + 2][2]), "r"(a[AOFF + 2][3]), "l"(descB), "n"(BOFF >> 4));
}
};
template <> struct Rng<0, 6, 10> {
template <int BOFF, int AOFF, int NA>
static __device__ __forceinline__ void run(float (&d)[48], const uint32_t (&a)[NA][4], uint64_t descB) {
    asm volatile(
        "{\n"
        ".reg .pred p0, p1;\n"
        ".reg .b64 ta, ta0, tb, tb0;\n"
        "setp.ne.b32 p0, 0, 0;\n"
        "setp.eq.b32 p1, 0, 0;\n"
        "add.s64 tb0, %64, %65;\n"
        "add.s64 tb, tb0, 1600;\n"
        "wgmma.mma_async.sync.aligned.m64n96k16.f32.bf16.bf16 {%0, %1, %2, %3, %4, %5, %6, %7, %8, %9, %10, %11, %12, %13, %14, %15, %16, %17, %18, %19, %20, %21, %22, %23, %24, %25, %26, %27, %28, %29, %30, %31, %32, %33, %34, %35, %36, %37, %38, %39, %40, %41, %42, %43, %44, %45, %46, %47}, {%48, %49, %50, %51}, tb, p1, 1, 1, 1;\n"
        "add.s64 tb, tb0, 1632;\n"
        "wgmma.mma_async.sync.aligned.m64n96k16.f32.bf16.bf16 {%0, %1, %2, %3, %4, %5, %6, %7, %8, %9, %10, %11, %12, %13, %14, %15, %16, %17, %18, %19, %20, %21, %22, %23, %24, %25, %26, %27, %28, %29, %30, %31, %32, %33, %34, %35, %36, %37, %38, %39, %40, %41, %42, %43, %44, %45, %46, %47}, {%52, %53, %54, %55}, tb, p1, 1, 1, 1;\n"
        "add.s64 tb, tb0, 3072;\n"
        "wgmma.mma_async.sync.aligned.m64n96k16.f32.bf16.bf16 {%0, %1, %2, %3, %4, %5, %6, %7, %8, %9, %10, %11, %12, %13, %14, %15, %16, %17, %18, %19, %20, %21, %22, %23, %24, %25, %26, %27, %28, %29, %30, %31, %32, %33, %34, %35, %36, %37, %38, %39, %40, %41, %42, %43, %44, %45, %46, %47}, {%56, %57, %58, %59}, tb, p1, 1, 1, 1;\n"
        "add.s64 tb, tb0, 3104;\n"
        "wgmma.mma_async.sync.aligned.m64n96k16.f32.bf16.bf16 {%0, %1, %2, %3, %4, %5, %6, %7, %8, %9, %10, %11, %12, %13, %14, %15, %16, %17, %18, %19, %20, %21, %22, %23, %24, %25, %26, %27, %28, %29, %30, %31, %32, %33, %34, %35, %36, %37, %38, %39, %40, %41, %42, %43, %44, %45, %46, %47}, {%60, %61, %62, %63}, tb, p1, 1, 1, 1;\n"
        "}\n"
        : "+f"(d[0]), "+f"(d[1]), "+f"(d[2]), "+f"(d[3]), "+f"(d[4]), "+f"(d[5]), "+f"(d[6]), "+f"(d[7]), "+f"(d[8]), "+f"(d[9]), "+f"(d[10]), "+f"(d[11]), "+f"(d[12]), "+f"(d[13]), "+f"(d[14]), "+f"(d[15]), "+f"(d[16]), "+f"(d[17]), "+f"(d[18]), "+f"(d[19]), "+f"(d[20]), "+f"(d[21]), "+f"(d[22]), "+f"(d[23]), "+f"(d[24]), "+f"(d[25]), "+f"(d[26]), "+f"(d[27]), "+f"(d[28]), "+f"(d[29]), "+f"(d[30]), "+f"(d[31]), "+f"(d[32]), "+f"(d[33]), "+f"(d[34]), "+f"(d[35]), "+f"(d[36]), "+f"(d[37]), "+f"(d[38]), "+f"(d[39]), "+f"(d[40]), "+f"(d[41]), "+f"(d[42]), "+f"(d[43]), "+f"(d[44]), "+f"(d[45]), "+f"(d[46]), "+f"(d[47])
        : "r"(a[AOFF + 0][0]), "r"(a[AOFF + 0][1]), "r"(a[AOFF + 0][2]), "r"(a[AOFF + 0][3]), "r"(a[AOFF + 1][0]), "r"(a[AOFF + 1][1]), "r"(a[AOFF + 1][2]), "r"(a[AOFF + 1][3]), "r"(a[AOFF + 2][0]), "r"(a[AOFF + 2][1]), "r"(a[AOFF + 2][2]), "r"(a[AOFF + 2][3]), "r"(a[AOFF + 3][0]), "r"(a[AOFF + 3][1]), "r"(a[AOFF + 3][2]), "r"(a[AOFF + 3][3]), "l"(descB), "n"(BOFF >> 4));
}
};
template <> struct Rng<1, 6, 10> {
template <int BOFF, int AOFF, int NA>
static __device__ __forceinline__ void run(float (&d)[48], const uint32_t (&a)[NA][4], uint64_t descB) {
    asm volatile(
        "{\n"
        ".reg .pred p0, p1;\n"
        ".reg .b64 ta, ta0, tb, tb0;\n"
        "setp.ne.b32 p0, 0, 0;\n"
        "setp.eq.b32 p1, 0, 0;\n"
        "add.s64 tb0, %64, %65;\n"
        "add.s64 tb, tb0, 192;\n"
        "wgmma.mma_async.sync.aligned.m64n96k16.f32.bf16.bf16 {%0, %1, %2, %3, %4, %5, %6, %7, %8, %9, %10, %11, %12, %13, %14, %15, %16, %17, %18, %19, %20, %21, %22, %23, %24, %25, %26, %27, %28, %29, %30, %31, %32, %33, %34, %35, %36, %37, %38, %39, %40, %41, %42, %43, %44, %45, %46, %47}, {%48, %49, %50, %51}, tb, p1, 1, 1, 1;\n"
        "add.s64 tb, tb0, 224;\n"
        "wgmma.mma_async.sync.aligned.m64n96k16.f32.bf16.bf16 {%0, %1, %2, %3, %4, %5, %6, %7, %8, %9, %10, %11, %12, %13, %14, %15, %16, %17, %18, %19, %20, %21, %22, %23, %24, %25, %26, %27, %28, %29, %30, %31, %32, %33, %34, %35, %36, %37, %38, %39, %40, %41, %42, %43, %44, %45, %46, %47}, {%52, %53, %54, %55}, tb, p1, 1, 1, 1;\n"
        "add.s64 tb, tb0, 256;\n"
        "wgmma.mma_async.sync.aligned.m64n96k16.f32.bf16.bf16 {%0, %1, %2, %3, %4, %5, %6, %7, %8, %9, %10, %11, %12, %13, %14, %15, %16, %17, %18, %19, %20, %21, %22, %23, %24, %25, %26, %27, %28, %29, %30, %31, %32, %33, %34, %35, %36, %37, %38, %39, %40, %41, %42, %43, %44, %45, %46, %47}, {%56, %57, %58, %59}, tb, p1, 1, 1, 1;\n"
        "add.s64 tb, tb0, 288;\n"
        "wgmma.mma_async.sync.aligned.m64n96k16.f32.bf16.bf16 {%0, %1, %2, %3, %4, %5, %6, %7, %8, %9, %10, %11, %12, %13, %14, %15, %16, %17, %18, %19, %20, %21, %22, %23, %24, %25, %26, %27, %28, %29, %30, %31, %32, %33, %34, %35, %36, %37, %38, %39, %40, %41, %42, %43, %44, %45, %46, %47}, {%60, %61, %62, %63}, tb, p1, 1, 1, 1;\n"
        "}\n"
        : "+f"(d[0]), "+f"(d[1]), "+f"(d[2]), "+f"(d[3]), "+f"(d[4]), "+f"(d[5]), "+f"(d[6]), "+f"(d[7]), "+f"(d[8]), "+f"(d[9]), "+f"(d[10]), "+f"(d[11]), "+f"(d[12]), "+f"(d[13]), "+f"(d[14]), "+f"(d[15]), "+f"(d[16]), "+f"(d[17]), "+f"(d[18]), "+f"(d[19]), "+f"(d[20]), "+f"(d[21]), "+f"(d[22]), "+f"(d[23]), "+f"(d[24]), "+f"(d[25]), "+f"(d[26]), "+f"(d[27]), "+f"(d[28]), "+f"(d[29]), "+f"(d[30]), "+f"(d[31]), "+f"(d[32]), "+f"(d[33]), "+f"(d[34]), "+f"(d[35]), "+f"(d[36]), "+f"(d[37]), "+f"(d[38]), "+f"(d[39]), "+f"(d[40]), "+f"(d[41]), "+f"(d[42]), "+f"(d[43]), "+f"(d[44]), "+f"(d[45]), "+f"(d[46]), "+f"(d[47])
        : "r"(a[AOFF + 0][0]), "r"(a[AOFF + 0][1]), "r"(a[AOFF + 0][2]), "r"(a[AOFF + 0][3]), "r"(a[AOFF + 1][0]), "r"(a[AOFF + 1][1]), "r"(a[AOFF + 1][2]), "r"(a[AOFF + 1][3]), "r"(a[AOFF + 2][0]), "r"(a[AOFF + 2][1]), "r"(a[AOFF + 2][2]), "r"(a[AOFF + 2][3]), "r"(a[AOFF + 3][0]), "r"(a[AOFF + 3][1]), "r"(a[AOFF + 3][2]), "r"(a[AOFF + 3][3]), "l"(descB), "n"(BOFF >> 4));
}
};
template <> struct Rng<0, 6, 12> {
template <int BOFF, int AOFF, int NA>
static __device__ __forceinline__ void run(float (&d)[48], const uint32_t (&a)[NA][4], uint64_t descB) {
    asm volatile(
        "{\n"
        ".reg .pred p0, p1;\n"
        ".reg .b64 ta, ta0, tb, tb0;\n"
        "setp.ne.b32 p0, 0, 0;\n"
        "setp.eq.b32 p1, 0, 0;\n"
        "add.s64 tb0, %72, %73;\n"
        "add.s64 tb, tb0, 1600;\n"
        "wgmma.mma_async.sync.aligned.m64n96k16.f32.bf16.bf16 {%0, %1, %2, %3, %4, %5, %6, %7, %8, %9, %10, %11, %12, %13, %14, %15, %16, %17, %18, %19, %20, %21, %22, %23, %24, %25, %26, %27, %28, %29, %30, %31, %32, %33, %34, %35, %36, %37, %38, %39, %40, %41, %42, %43, %44, %45, %46, %47}, {%48, %49, %50, %51}, tb, p1, 1, 1, 1;\n"
        "add.s64 tb, tb0, 1632;\n"
        "wgmma.mma_async.sync.aligned.m64n96k16.f32.bf16.bf16 {%0, %1, %2, %3, %4, %5, %6, %7, %8, %9, %10, %11, %12, %13, %14, %15, %16, %17, %18, %19, %20, %21, %22, %23, %24, %25, %26, %27, %28, %29, %30, %31, %32, %33, %34, %35, %36, %37, %38, %39, %40, %41, %42, %43, %44, %45, %46, %47}, {%52, %53, %54, %55}, tb, p1, 1, 1, 1;\n"
        "add.s64 tb, tb0, 3072;\n"
        "wgmma.mma_async.sync.aligned.m64n96k16.f32.bf16.bf16 {%0, %1, %2, %3, %4, %5, %6, %7, %8, %9, %10, %11, %12, %13, %14, %15, %16, %17, %18, %19, %20, %21, %22, %23, %24, %25, %26, %27, %28, %29, %30, %31, %32, %33, %34, %35, %36, %37, %38, %39, %40, %41, %42, %43, %44, %45, %46, %47}, {%56, %57, %58, %59}, tb, p1, 1, 1, 1;\n"
        "add.s64 tb, tb0, 3104;\n"
        "wgmma.mma_async.sync.aligned.m64n96k16.f32.bf16.bf16 {%0, %1, %2, %3, %4, %5, %6, %7, %8, %9, %10, %11, %12, %13, %14, %15, %16, %17, %18, %19, %20, %21, %22, %23, %24, %25, %26, %27, %28, %29, %30, %31, %32, %33, %34, %35, %36, %37, %38, %39, %40, %41, %42, %43, %44, %45, %46, %47}, {%60, %61, %62, %63}, tb, p1, 1, 1, 1;\n"
        "add.s64 tb, tb0, 3136;\n"
        "wgmma.mma_async.sync.aligned.m64n96k16.f32.bf16.bf16 {%0, %1, %2, %3, %4, %5, %6, %7, %8, %9, %10, %11, %12, %13, %14, %15, %16, %17, %18, %19, %20, %21, %22, %23, %24, %25, %26, %27, %28, %29, %30, %31, %32, %33, %34, %35, %36, %37, %38, %39, %40, %41, %42, %43, %44, %45, %46, %47}, {%64, %65, %66, %67}, tb, p1, 1, 1, 1;\n"
        "add.s64 tb, tb0, 3168;\n"
        "wgmma.mma_async.sync.aligned.m64n96k16.f32.bf16.bf16 {%0, %1, %2, %3, %4, %5, %6, %7, %8, %9, %10, %11, %12, %13, %14, %15, %16, %17, %18, %19, %20, %21, %22, %23, %24, %25, %26, %27, %28, %29, %30, %31, %32, %33, %34, %35, %36, %37, %38, %39, %40, %41, %42, %43, %44, %45, %46, %47}, {%68, %69, %70, %71}, tb, p1, 1, 1, 1;\n"
        "}\n"
        : "+f"(d[0]), "+f"(d[1]), "+f"(d[2]), "+f"(d[3]), "+f"(d[4]), "+f"(d[5]), "+f"(d[6]), "+f"(d[7]), "+f"(d[8]), "+f"(d[9]), "+f"(d[10]), "+f"(d[11]), "+f"(d[12]), "+f"(d[13]), "+f"(d[14]), "+f"(d[15]), "+f"(d[16]), "+f"(d[17]), "+f"(d[18]), "+f"(d[19]), "+f"(d[20]), "+f"(d[21]), "+f"(d[22]), "+f"(d[23]), "+f"(d[24]), "+f"(d[25]), "+f"(d[26]), "+f"(d[27]), "+f"(d[28]), "+f"(d[29]), "+f"(d[30]), "+f"(d[31]), "+f"(d[32]), "+f"(d[33]), "+f"(d[34]), "+f"(d[35]), "+f"(d[36]), "+f"(d[37]), "+f"(d[38]), "+f"(d[39]), "+f"(d[40]), "+f"(d[41]), "+f"(d[42]), "+f"(d[43]), "+f"(d[44]), "+f"(d[45]), "+f"(d[46]), "+f"(d[47])
        : "r"(a[AOFF + 0][0]), "r"(a[AOFF + 0][1]), "r"(a[AOFF + 0][2]), "r"(a[AOFF + 0][3]), "r"(a[AOFF + 1][0]), "r"(a[AOFF + 1][1]), "r"(a[AOFF + 1][2]), "r"(a[AOFF + 1][3]), "r"(a[AOFF + 2][0]), "r"(a[AOFF + 2][1]), "r"(a[AOFF + 2][2]), "r"(a[AOFF + 2][3]), "r"(a[AOFF + 3][0]), "r"(a[AOFF + 3][1]), "r"(a[AOFF + 3][2]), "r"(a[AOFF + 3][3]), "r"(a[AOFF + 4][0]), "r"(a[AOFF + 4][1]), "r"(a[AOFF + 4][2]), "r"(a[AOFF + 4][3]), "r"(a[AOFF + 5][0]), "r"(a[AOFF + 5][1]), "r"(a[AOFF + 5][2]), "r"(a[AOFF + 5][3]), "l"(descB), "n"(BOFF >> 4));
}
};
template <> struct Rng<1, 6, 12> {
template <int BOFF, int AOFF, int NA>
static __device__ __forceinline__ void run(float (&d)[48], const uint32_t (&a)[NA][4], uint64_t descB) {
    asm volatile(
        "{\n"
        ".reg .pred p0, p1;\n"
        ".reg .b64 ta, ta0, tb, tb0;\n"
        "setp.ne.b32 p0, 0, 0;\n"
        "setp.eq.b32 p1, 0, 0;\n"
        "add.s64 tb0, %72, %73;\n"
        "add.s64 tb, tb0, 192;\n"
        "wgmma.mma_async.sync.aligned.m64n96k16.f32.bf16.bf16 {%0, %1, %2, %3, %4, %5, %6, %7, %8, %9, %10, %11, %12, %13, %14, %15, %16, %17, %18, %19, %20, %21, %22, %23, %24, %25, %26, %27, %28, %29, %30, %31, %32, %33, %34, %35, %36, %37, %38, %39, %40, %41, %42, %43, %44, %45, %46, %47}, {%48, %49, %50, %51}, tb, p1, 1, 1, 1;\n"
        "add.s64 tb, tb0, 224;\n"
        "wgmma.mma_async.sync.aligned.m64n96k16.f32.bf16.bf16 {%0, %1, %2, %3, %4, %5, %6, %7, %8, %9, %10, %11, %12, %13, %14, %15, %16, %17, %18, %19, %20, %21, %22, %23, %24, %25, %26, %27, %28, %29, %30, %31, %32, %33, %34, %35, %36, %37, %38, %39, %40, %41, %42, %43, %44, %45, %46, %47}, {%52, %53, %54, %55}, tb, p1, 1, 1, 1;\n"
        "add.s64 tb, tb0, 256;\n"
        "wgmma.mma_async.sync.aligned.m64n96k16.f32.bf16.bf16 {%0, %1, %2, %3, %4, %5, %6, %7, %8, %9, %10, %11, %12, %13, %14, %15, %16, %17, %18, %19, %20, %21, %22, %23, %24, %25, %26, %27, %28, %29, %30, %31, %32, %33, %34, %35, %36, %37, %38, %39, %40, %41, %42, %43, %44, %45, %46, %47}, {%56, %57, %58, %59}, tb, p1, 1, 1, 1;\n"
        "add.s64 tb, tb0, 288;\n"
        "wgmma.mma_async.sync.aligned.m64n96k16.f32.bf16.bf16 {%0, %1, %2, %3, %4, %5, %6, %7, %8, %9, %10, %11, %12, %13, %14, %15, %16, %17, %18, %19, %20, %21, %22, %23, %24, %25, %26, %27, %28, %29, %30, %31, %32, %33, %34, %35, %36, %37, %38, %39, %40, %41, %42, %43, %44, %45, %46, %47}, {%60, %61, %62, %63}, tb, p1, 1, 1, 1;\n"
        "add.s64 tb, tb0, 320;\n"
        "wgmma.mma_async.sync.aligned.m64n96k16.f32.bf16.bf16 {%0, %1, %2, %3, %4, %5, %6, %7, %8, %9, %10, %11, %12, %13, %14, %15, %16, %17, %18, %19, %20, %21, %22, %23, %24, %25, %26, %27, %28, %29, %30, %31, %32, %33, %34, %35, %36, %37, %38, %39, %40, %41, %42, %43, %44, %45, %46, %47}, {%64, %65, %66, %67}, tb, p1, 1, 1, 1;\n"
        "add.s64 tb, tb0, 352;\n"
        "wgmma.mma_async.sync.aligned.m64n96k16.f32.bf16.bf16 {%0, %1, %2, %3, %4, %5, %6, %7, %8, %9, %10, %11, %12, %13, %14, %15, %16, %17, %18, %19, %20, %21, %22, %23, %24, %25, %26, %27, %28, %29, %30, %31, %32, %33, %34, %35, %36, %37, %38, %39, %40, %41, %42, %43, %44, %45, %46, %47}, {%68, %69, %70, %71}, tb, p1, 1, 1, 1;\n"
        "}\n"
        : "+f"(d[0]), "+f"(d[1]), "+f"(d[2]), "+f"(d[3]), "+f"(d[4]), "+f"(d[5]), "+f"(d[6]), "+f"(d[7]), "+f"(d[8]), "+f"(d[9]), "+f"(d[10]), "+f"(d[11]), "+f"(d[12]), "+f"(d[13]), "+f"(d[14]), "+f"(d[15]), "+f"(d[16]), "+f"(d[17]), "+f"(d[18]), "+f"(d[19]), "+f"(d[20]), "+f"(d[21]), "+f"(d[22]), "+f"(d[23]), "+f"(d[24]), "+f"(d[25]), "+f"(d[26]), "+f"(d[27]), "+f"(d[28]), "+f"(d[29]), "+f"(d[30]), "+f"(d[31]), "+f"(d[32]), "+f"(d[33]), "+f"(d[34]), "+f"(d[35]), "+f"(d[36]), "+f"(d[37]), "+f"(d[38]), "+f"(d[39]), "+f"(d[40]), "+f"(d[41]), "+f"(d[42]), "+f"(d[43]), "+f"(d[44]), "+f"(d[45]), "+f"(d[46]), "+f"(d[47])
        : "r"(a[AOFF + 0][0]), "r"(a[AOFF + 0][1]), "r"(a[AOFF + 0][2]), "r"(a[AOFF + 0][3]), "r"(a[AOFF + 1][0]), "r"(a[AOFF + 1][1]), "r"(a[AOFF + 1][2]), "r"(a[AOFF + 1][3]), "r"(a[AOFF + 2][0]), "r"(a[AOFF + 2][1]), "r"(a[AOFF + 2][2]), "r"(a[AOFF + 2][3]), "r"(a[AOFF + 3][0]), "r"(a[AOFF + 3][1]), "r"(a[AOFF + 3][2]), "r"(a[AOFF + 3][3]), "r"(a[AOFF + 4][0]), "r"(a[AOFF + 4][1]), "r"(a[AOFF + 4][2]), "r"(a[AOFF + 4][3]), "r"(a[AOFF + 5][0]), "r"(a[AOFF + 5][1]), "r"(a[AOFF + 5][2]), "r"(a[AOFF + 5][3]), "l"(descB), "n"(BOFF >> 4));
}
};
template <> struct Rng<0, 7, 12> {
template <int BOFF, int AOFF, int NA>
static __device__ __forceinline__ void run(float (&d)[48], const uint32_t (&a)[NA][4], uint64_t descB) {
    asm volatile(
        "{\n"
        ".reg .pred p0, p1;\n"
        ".reg .b64 ta, ta0, tb, tb0;\n"
        "setp.ne.b32 p0, 0, 0;\n"
        "setp.eq.b32 p1, 0, 0;\n"
        "add.s64 tb0, %68, %69;\n"
        "add.s64 tb, tb0, 1632;\n"
        "wgmma.mma_async.sync.aligned.m64n96k16.f32.bf16.bf16 {%0, %1, %2, %3, %4, %5, %6, %7, %8, %9, %10, %11, %12, %13, %14, %15, %16, %17, %18, %19, %20, %21, %22, %23, %24, %25, %26, %27, %28, %29, %30, %31, %32, %33, %34, %35, %36, %37, %38, %39, %40, %41, %42, %43, %44, %45, %46, %47}, {%48, %49, %50, %51}, tb, p1, 1, 1, 1;\n"
        "add.s64 tb, tb0, 3072;\n"
        "wgmma.mma_async.sync.aligned.m64n96k16.f32.bf16.bf16 {%0, %1, %2, %3, %4, %5, %6, %7, %8, %9, %10, %11, %12, %13, %14, %15, %16, %17, %18, %19, %20, %21, %22, %23, %24, %25, %26, %27, %28, %29, %30, %31, %32, %33, %34, %35, %36, %37, %38, %39, %40, %41, %42, %43, %44, %45, %46, %47}, {%52, %53, %54, %55}, tb, p1, 1, 1, 1;\n"
        "add.s64 tb, tb0, 3104;\n"
        "wgmma.mma_async.sync.aligned.m64n96k16.f32.bf16.bf16 {%0, %1, %2, %3, %4, %5, %6, %7, %8, %9, %10, %11, %12, %13, %14, %15, %16, %17, %18, %19, %20, %21, %22, %23, %24, %25, %26, %27, %28, %29, %30, %31, %32, %33, %34, %35, %36, %37, %38, %39, %40, %41, %42, %43, %44, %45, %46, %47}, {%56, %57, %58, %59}, tb, p1, 1, 1, 1;\n"
        "add.s64 tb, tb0, 3136;\n"
        "wgmma.mma_async.sync.aligned.m64n96k16.f32.bf16.bf16 {%0, %1, %2, %3, %4, %5, %6, %7, %8, %9, %10, %11, %12, %13, %14, %15, %16, %17, %18, %19, %20, %21, %22, %23, %24, %25, %26, %27, %28, %29, %30, %31, %32, %33, %34, %35, %36, %37, %38, %39, %40, %41, %42, %43, %44, %45, %46, %47}, {%60, %61, %62, %63}, tb, p1, 1, 1, 1;\n"
        "add.s64 tb, tb0, 3168;\n"
        "wgmma.mma_async.sync.aligned.m64n96k16.f32.bf16.bf16 {%0, %1, %2, %3, %4, %5, %6, %7, %8, %9, %10, %11, %12, %13, %14, %15, %16, %17, %18, %19, %20, %21, %22, %23, %24, %25, %26, %27, %28, %29, %30, %31, %32, %33, %34, %35, %36, %37, %38, %39, %40, %41, %42, %43, %44, %45, %46, %47}, {%64, %65, %66, %67}, tb, p1, 1, 1, 1;\n"
        "}\n"
        : "+f"(d[0]), "+f"(d[1]), "+f"(d[2]), "+f"(d[3]), "+f"(d[4]), "+f"(d[5]), "+f"(d[6]), "+f"(d[7]), "+f"(d[8]), "+f"(d[9]), "+f"(d[10]), "+f"(d[11]), "+f"(d[12]), "+f"(d[13]), "+f"(d[14]), "+f"(d[15]), "+f"(d[16]), "+f"(d[17]), "+f"(d[18]), "+f"(d[19]), "+f"(d[20]), "+f"(d[21]), "+f"(d[22]), "+f"(d[23]), "+f"(d[24]), "+f"(d[25]), "+f"(d[26]), "+f"(d[27]), "+f"(d[28]), "+f"(d[29]), "+f"(d[30]), "+f"(d[31]), "+f"(d[32]), "+f"(d[33]), "+f"(d[34]), "+f"(d[35]), "+f"(d[36]), "+f"(d[37]), "+f"(d[38]), "+f"(d[39]), "+f"(d[40]), "+f"(d[41]), "+f"(d[42]), "+f"(d[43]), "+f"(d[44]), "+f"(d[45]), "+f"(d[46]), "+f"(d[47])
        : "r"(a[AOFF + 0][0]), "r"(a[AOFF + 0][1]), "r"(a[AOFF + 0][2]), "r"(a[AOFF + 0][3]), "r"(a[AOFF + 1][0]), "r"(a[AOFF + 1][1]), "r"(a[AOFF + 1][2]), "r"(a[AOFF + 1][3]), "r"(a[AOFF + 2][0]), "r"(a[AOFF + 2][1]), "r"(a[AOFF + 2][2]), "r"(a[AOFF + 2][3]), "r"(a[AOFF + 3][0]), "r"(a[AOFF + 3][1]), "r"(a[AOFF + 3][2]), "r"(a[AOFF + 3][3]), "r"(a[AOFF + 4][0]), "r"(a[AOFF + 4][1]), "r"(a[AOFF + 4][2]), "r"(a[AOFF + 4][3]), "l"(descB), "n"(BOFF >> 4));
}
};
template <> struct Rng<1, 7, 12> {
template <int BOFF, int AOFF, int NA>
static __device__ __forceinline__ void run(float (&d)[48], const uint32_t (&a)[NA][4], uint64_t descB) {
    asm volatile(
        "{\n"
        ".reg .pred p0, p1;\n"
        ".reg .b64 ta, ta0, tb, tb0;\n"
        "setp.ne.b32 p0, 0, 0;\n"
        "setp.eq.b32 p1, 0, 0;\n"
        "add.s64 tb0, %68, %69;\n"
        "add.s64 tb, tb0, 224;\n"
        "wgmma.mma_async.sync.aligned.m64n96k16.f32.bf16.bf16 {%0, %1, %2, %3, %4, %5, %6, %7, %8, %9, %10, %11, %12, %13, %14, %15, %16, %17, %18, %19, %20, %21, %22, %23, %24, %25, %26, %27, %28, %29, %30, %31, %32, %33, %34, %35, %36, %37, %38, %39, %40, %41, %42, %43, %44, %45, %46, %47}, {%48, %49, %50, %51}, tb, p1, 1, 1, 1;\n"
        "add.s64 tb, tb0, 256;\n"
        "wgmma.mma_async.sync.aligned.m64n96k16.f32.bf16.bf16 {%0, %1, %2, %3, %4, %5, %6, %7, %8, %9, %10, %11, %12, %13, %14, %15, %16, %17, %18, %19, %20, %21, %22, %23, %24, %25, %26, %27, %28, %29, %30, %31, %32, %33, %34, %35, %36, %37, %38, %39, %40, %41, %42, %43, %44, %45, %46, %47}, {%52, %53, %54, %55}, tb, p1, 1, 1, 1;\n"
        "add.s64 tb, tb0, 288;\n"
        "wgmma.mma_async.sync.aligned.m64n96k16.f32.bf16.bf16 {%0, %1, %2, %3, %4, %5, %6, %7, %8, %9, %10, %11, %12, %13, %14, %15, %16, %17, %18, %19, %20, %21, %22, %23, %24, %25, %26, %27, %28, %29, %30, %31, %32, %33, %34, %35, %36, %37, %38, %39, %40, %41, %42, %43, %44, %45, %46, %47}, {%56, %57, %58, %59}, tb, p1, 1, 1, 1;\n"
        "add.s64 tb, tb0, 320;\n"
        "wgmma.mma_async.sync.aligned.m64n96k16.f32.bf16.bf16 {%0, %1, %2, %3, %4, %5, %6, %7, %8, %9, %10, %11, %12, %13, %14, %15, %16, %17, %18, %19, %20, %21, %22, %23, %24, %25, %26, %27, %28, %29, %30, %31, %32, %33, %34, %35, %36, %37, %38, %39, %40, %41, %42, %43, %44, %45, %46, %47}, {%60, %61, %62, %63}, tb, p1, 1, 1, 1;\n"
        "add.s64 tb, tb0, 352;\n"
        "wgmma.mma_async.sync.aligned.m64n96k16.f32.bf16.bf16 {%0, %1, %2, %3, %4, %5, %6, %7, %8, %9, %10, %11, %12, %13, %14, %15, %16, %17, %18, %19, %20, %21, %22, %23, %24, %25, %26, %27, %28, %29, %30, %31, %32, %33, %34, %35, %36, %37, %38, %39, %40, %41, %42, %43, %44, %45, %46, %47}, {%64, %65, %66, %67}, tb, p1, 1, 1, 1;\n"
        "}\n"
        : "+f"(d[0]), "+f"(d[1]), "+f"(d[2]), "+f"(d[3]), "+f"(d[4]), "+f"(d[5]), "+f"(d[6]), "+f"(d[7]), "+f"(d[8]), "+f"(d[9]), "+f"(d[10]), "+f"(d[11]), "+f"(d[12]), "+f"(d[13]), "+f"(d[14]), "+f"(d[15]), "+f"(d[16]), "+f"(d[17]), "+f"(d[18]), "+f"(d[19]), "+f"(d[20]), "+f"(d[21]), "+f"(d[22]), "+f"(d[23]), "+f"(d[24]), "+f"(d[25]), "+f"(d[26]), "+f"(d[27]), "+f"(d[28]), "+f"(d[29]), "+f"(d[30]), "+f"(d[31]), "+f"(d[32]), "+f"(d[33]), "+f"(d[34]), "+f"(d[35]), "+f"(d[36]), "+f"(d[37]), "+f"(d[38]), "+f"(d[39]), "+f"(d[40]), "+f"(d[41]), "+f"(d[42]), "+f"(d[43]), "+f"(d[44]), "+f"(d[45]), "+f"(d[46]), "+f"(d[47])
        : "r"(a[AOFF + 0][0]), "r"(a[AOFF + 0][1]), "r"(a[AOFF + 0][2]), "r"(a[AOFF + 0][3]), "r"(a[AOFF + 1][0]), "r"(a[AOFF + 1][1]), "r"(a[AOFF + 1][2]), "r"(a[AOFF + 1][3]), "r"(a[AOFF + 2][0]), "r"(a[AOFF + 2][1]), "r"(a[AOFF + 2][2]), "r"(a[AOFF + 2][3]), "r"(a[AOFF + 3][0]), "r"(a[AOFF + 3][1]), "r"(a[AOFF + 3][2]), "r"(a[AOFF + 3][3]), "r"(a[AOFF + 4][0]), "r"(a[AOFF + 4][1]), "r"(a[AOFF + 4][2]), "r"(a[AOFF + 4][3]), "l"(descB), "n"(BOFF >> 4));
}
};
template <> struct Rng<0, 8, 12> {
template <int BOFF, int AOFF, int NA>
static __device__ __forceinline__ void run(float (&d)[48], const uint32_t (&a)[NA][4], uint64_t descB) {
    asm volatile(
        "{\n"
        ".reg .pred p0, p1;\n"
        ".reg .b64 ta, ta0, tb, tb0;\n"
        "setp.ne.b32 p0, 0, 0;\n"
        "setp.eq.b32 p1, 0, 0;\n"
        "add.s64 tb0, %64, %65;\n"
        "add.s64 tb, tb0, 3072;\n"
        "wgmma.mma_async.sync.aligned.m64n96k16.f32.bf16.bf16 {%0, %1, %2, %3, %4, %5, %6, %7, %8, %9, %10, %11, %12, %13, %14, %15, %16, %17, %18, %19, %20, %21, %22, %23, %24, %25, %26, %27, %28, %29, %30, %31, %32, %33, %34, %35, %36, %37, %38, %39, %40, %41, %42, %43, %44, %45, %46, %47}, {%48, %49, %50, %51}, tb, p1, 1, 1, 1;\n"
        "add.s64 tb, tb0, 3104;\n"
        "wgmma.mma_async.sync.aligned.m64n96k16.f32.bf16.bf16 {%0, %1, %2, %3, %4, %5, %6, %7, %8, %9, %10, %11, %12, %13, %14, %15, %16, %17, %18, %19, %20, %21, %22, %23, %24, %25, %26, %27, %28, %29, %30, %31, %32, %33, %34, %35, %36, %37, %38, %39, %40, %41, %42, %43, %44, %45, %46, %47}, {%52, %53, %54, %55}, tb, p1, 1, 1, 1;\n"
        "add.s64 tb, tb0, 3136;\n"
        "wgmma.mma_async.sync.aligned.m64n96k16.f32.bf16.bf16 {%0, %1, %2, %3, %4, %5, %6, %7, %8, %9, %10, %11, %12, %13, %14, %15, %16, %17, %18, %19, %20, %21, %22, %23, %24, %25, %26, %27, %28, %29, %30, %31, %32, %33, %34, %35, %36, %37, %38, %39, %40, %41, %42, %43, %44, %45, %46, %47}, {%56, %57, %58, %59}, tb, p1, 1, 1, 1;\n"
        "add.s64 tb, tb0, 3168;\n"
        "wgmma.mma_async.sync.aligned.m64n96k16.f32.bf16.bf16 {%0, %1, %2, %3, %4, %5, %6, %7, %8, %9, %10, %11, %12, %13, %14, %15, %16, %17, %18, %19, %20, %21, %22, %23, %24, %25, %26, %27, %28, %29, %30, %31, %32, %33, %34, %35, %36, %37, %38, %39, %40, %41, %42, %43, %44, %45, %46, %47}, {%60, %61, %62, %63}, tb, p1, 1, 1, 1;\n"
        "}\n"
        : "+f"(d[0]), "+f"(d[1]), "+f"(d[2]), "+f"(d[3]), "+f"(d[4]), "+f"(d[5]), "+f"(d[6]), "+f"(d[7]), "+f"(d[8]), "+f"(d[9]), "+f"(d[10]), "+f"(d[11]), "+f"(d[12]), "+f"(d[13]), "+f"(d[14]), "+f"(d[15]), "+f"(d[16]), "+f"(d[17]), "+f"(d[18]), "+f"(d[19]), "+f"(d[20]), "+f"(d[21]), "+f"(d[22]), "+f"(d[23]), "+f"(d[24]), "+f"(d[25]), "+f"(d[26]), "+f"(d[27]), "+f"(d[28]), "+f"(d[29]), "+f"(d[30]), "+f"(d[31]), "+f"(d[32]), "+f"(d[33]), "+f"(d[34]), "+f"(d[35]), "+f"(d[36]), "+f"(d[37]), "+f"(d[38]), "+f"(d[39]), "+f"(d[40]), "+f"(d[41]), "+f"(d[42]), "+f"(d[43]), "+f"(d[44]), "+f"(d[45]), "+f"(d[46]), "+f"(d[47])
        : "r"(a[AOFF + 0][0]), "r"(a[AOFF + 0][1]), "r"(a[AOFF + 0][2]), "r"(a[AOFF + 0][3]), "r"(a[AOFF + 1][0]), "r"(a[AOFF + 1][1]), "r"(a[AOFF + 1][2]), "r"(a[AOFF + 1][3]), "r"(a[AOFF + 2][0]), "r"(a[AOFF + 2][1]), "r"(a[AOFF + 2][2]), "r"(a[AOFF + 2][3]), "r"(a[AOFF + 3][0]), "r"(a[AOFF + 3][1]), "r"(a[AOFF + 3][2]), "r"(a[AOFF + 3][3]), "l"(descB), "n"(BOFF >> 4));
}
};
template <> struct Rng<1, 8, 12> {
template <int BOFF, int AOFF, int NA>
static __device__ __forceinline__ void run(float (&d)[48], const uint32_t (&a)[NA][4], uint64_t descB) {
    asm volatile(
        "{\n"
        ".reg .pred p0, p1;\n"
        ".reg .b64 ta, ta0, tb, tb0;\n"
        "setp.ne.b32 p0, 0, 0;\n"
        "setp.eq.b32 p1, 0, 0;\n"
        "add.s64 tb0, %64, %65;\n"
        "add.s64 tb, tb0, 256;\n"
        "wgmma.mma_async.sync.aligned.m64n96k16.f32.bf16.bf16 {%0, %1, %2, %3, %4, %5, %6, %7, %8, %9, %10, %11, %12, %13, %14, %15, %16, %17, %18, %19, %20, %21, %22, %23, %24, %25, %26, %27, %28, %29, %30, %31, %32, %33, %34, %35, %36, %37, %38, %39, %40, %41, %42, %43, %44, %45, %46, %47}, {%48, %49, %50, %51}, tb, p1, 1, 1, 1;\n"
        "add.s64 tb, tb0, 288;\n"
        "wgmma.mma_async.sync.aligned.m64n96k16.f32.bf16.bf16 {%0, %1, %2, %3, %4, %5, %6, %7, %8, %9, %10, %11, %12, %13, %14, %15, %16, %17, %18, %19, %20, %21, %22, %23, %24, %25, %26, %27, %28, %29, %30, %31, %32, %33, %34, %35, %36, %37, %38, %39, %40, %41, %42, %43, %44, %45, %46, %47}, {%52, %53, %54, %55}, tb, p1, 1, 1, 1;\n"
        "add.s64 tb, tb0, 320;\n"
        "wgmma.mma_async.sync.aligned.m64n96k16.f32.bf16.bf16 {%0, %1, %2, %3, %4, %5, %6, %7, %8, %9, %10, %11, %12, %13, %14, %15, %16, %17, %18, %19, %20, %21, %22, %23, %24, %25, %26, %27, %28, %29, %30, %31, %32, %33, %34, %35, %36, %37, %38, %39, %40, %41, %42, %43, %44, %45, %46, %47}, {%56, %57, %58, %59}, tb, p1, 1, 1, 1;\n"
        "add.s64 tb, tb0, 352;\n"
        "wgmma.mma_async.sync.aligned.m64n96k16.f32.bf16.bf16 {%0, %1, %2, %3, %4, %5, %6, %7, %8, %9, %10, %11, %12, %13, %14, %15, %16, %17, %18, %19, %20, %21, %22, %23, %24, %25, %26, %27, %28, %29, %30, %31, %32, %33, %34, %35, %36, %37, %38, %39, %40, %41, %42, %43, %44, %45, %46, %47}, {%60, %61, %62, %63}, tb, p1, 1, 1, 1;\n"
        "}\n"
        : "+f"(d[0]), "+f"(d[1]), "+f"(d[2]), "+f"(d[3]), "+f"(d[4]), "+f"(d[5]), "+f"(d[6]), "+f"(d[7]), "+f"(d[8]), "+f"(d[9]), "+f"(d[10]), "+f"(d[11]), "+f"(d[12]), "+f"(d[13]), "+f"(d[14]), "+f"(d[15]), "+f"(d[16]), "+f"(d[17]), "+f"(d[18]), "+f"(d[19]), "+f"(d[20]), "+f"(d[21]), "+f"(d[22]), "+f"(d[23]), "+f"(d[24]), "+f"(d[25]), "+f"(d[26]), "+f"(d[27]), "+f"(d[28]), "+f"(d[29]), "+f"(d[30]), "+f"(d[31]), "+f"(d[32]), "+f"(d[33]), "+f"(d[34]), "+f"(d[35]), "+f"(d[36]), "+f"(d[37]), "+f"(d[38]), "+f"(d[39]), "+f"(d[40]), "+f"(d[41]), "+f"(d[42]), "+f"(d[43]), "+f"(d[44]), "+f"(d[45]), "+f"(d[46]), "+f"(d[47])
        : "r"(a[AOFF + 0][0]), "r"(a[AOFF + 0][1]), "r"(a[AOFF + 0][2]), "r"(a[AOFF + 0][3]), "r"(a[AOFF + 1][0]), "r"(a[AOFF + 1][1]), "r"(a[AOFF + 1][2]), "r"(a[AOFF + 1][3]), "r"(a[AOFF + 2][0]), "r"(a[AOFF + 2][1]), "r"(a[AOFF + 2][2]), "r"(a[AOFF + 2][3]), "r"(a[AOFF + 3][0]), "r"(a[AOFF + 3][1]), "r"(a[AOFF + 3][2]), "r"(a[AOFF + 3][3]), "l"(descB), "n"(BOFF >> 4));
}
};
template <> struct Rng<0, 9, 12> {
template <int BOFF, int AOFF, int NA>
static __device__ __forceinline__ void run(float (&d)[48], const uint32_t (&a)[NA][4], uint64_t descB) {
    asm volatile(
        "{\n"
        ".reg .pred p0, p1;\n"
        ".reg .b64 ta, ta0, tb, tb0;\n"
        "setp.ne.b32 p0, 0, 0;\n"
        "setp.eq.b32 p1, 0, 0;\n"
        "add.s64 tb0, %60, %61;\n"
        "add.s64 tb, tb0, 3104;\n"
        "wgmma.mma_async.sync.aligned.m64n96k16.f32.bf16.bf16 {%0, %1, %2, %3, %4, %5, %6, %7, %8, %9, %10, %11, %12, %13, %14, %15, %16, %17, %18, %19, %20, %21, %22, %23, %24, %25, %26, %27, %28, %29, %30, %31, %32, %33, %34, %35, %36, %37, %38, %39, %40, %41, %42, %43, %44, %45, %46, %47}, {%48, %49, %50, %51}, tb, p1, 1, 1, 1;\n"
        "add.s64 tb, tb0, 3136;\n"
        "wgmma.mma_async.sync.aligned.m64n96k16.f32.bf16.bf16 {%0, %1, %2, %3, %4, %5, %6, %7, %8, %9, %10, %11, %12, %13, %14, %15, %16, %17, %18, %19, %20, %21, %22, %23, %24, %25, %26, %27, %28, %29, %30, %31, %32, %33, %34, %35, %36, %37, %38, %39, %40, %41, %42, %43, %44, %45, %46, %47}, {%52, %53, %54, %55}, tb, p1, 1, 1, 1;\n"
        "add.s64 tb, tb0, 3168;\n"
        "wgmma.mma_async.sync.aligned.m64n96k16.f32.bf16.bf16 {%0, %1, %2, %3, %4, %5, %6, %7, %8, %9, %10, %11, %12, %13, %14, %15, %16, %17, %18, %19, %20, %21, %22, %23, %24, %25, %26, %27, %28, %29, %30, %31, %32, %33, %34, %35, %36, %37, %38, %39, %40, %41, %42, %43, %44, %45, %46, %47}, {%56, %57, %58, %59}, tb, p1, 1, 1, 1;\n"
        "}\n"
        : "+f"(d[0]), "+f"(d[1]), "+f"(d[2]), "+f"(d[3]), "+f"(d[4]), "+f"(d[5]), "+f"(d[6]), "+f"(d[7]), "+f"(d[8]), "+f"(d[9]), "+f"(d[10]), "+f"(d[11]), "+f"(d[12]), "+f"(d[13]), "+f"(d[14]), "+f"(d[15]), "+f"(d[16]), "+f"(d[17]), "+f"(d[18]), "+f"(d[19]), "+f"(d[20]), "+f"(d[21]), "+f"(d[22]), "+f"(d[23]), "+f"(d[24]), "+f"(d[25]), "+f"(d[26]), "+f"(d[27]), "+f"(d[28]), "+f"(d[29]), "+f"(d[30]), "+f"(d[31]), "+f"(d[32]), "+f"(d[33]), "+f"(d[34]), "+f"(d[35]), "+f"(d[36]), "+f"(d[37]), "+f"(d[38]), "+f"(d[39]), "+f"(d[40]), "+f"(d[41]), "+f"(d[42]), "+f"(d[43]), "+f"(d[44]), "+f"(d[45]), "+f"(d[46]), "+f"(d[47])
        : "r"(a[AOFF + 0][0]), "r"(a[AOFF + 0][1]), "r"(a[AOFF + 0][2]), "r"(a[AOFF + 0][3]), "r"(a[AOFF + 1][0]), "r"(a[AOFF + 1][1]), "r"(a[AOFF + 1][2]), "r"(a[AOFF + 1][3]), "r"(a[AOFF + 2][0]), "r"(a[AOFF + 2][1]), "r"(a[AOFF + 2][2]), "r"(a[AOFF + 2][3]), "l"(descB), "n"(BOFF >> 4));
}
};
template <> struct Rng<1, 9, 12> {
template <int BOFF, int AOFF, int NA>
static __device__ __forceinline__ void run(float (&d)[48], const uint32_t (&a)[NA][4], uint64_t descB) {
    asm volatile(
        "{\n"
        ".reg .pred p0, p1;\n"
        ".reg .b64 ta, ta0, tb, tb0;\n"
        "setp.ne.b32 p0, 0, 0;\n"
        "setp.eq.b32 p1, 0, 0;\n"
        "add.s64 tb0, %60, %61;\n"
        "add.s64 tb, tb0, 288;\n"
        "wgmma.mma_async.sync.aligned.m64n96k16.f32.bf16.bf16 {%0, %1, %2, %3, %4, %5, %6, %7, %8, %9, %10, %11, %12, %13, %14, %15, %16, %17, %18, %19, %20, %21, %22, %23, %24, %25, %26, %27, %28, %29, %30, %31, %32, %33, %34, %35, %36, %37, %38, %39, %40, %41, %42, %43, %44, %45, %46, %47}, {%48, %49, %50, %51}, tb, p1, 1, 1, 1;\n"
        "add.s64 tb, tb0, 320;\n"
        "wgmma.mma_async.sync.aligned.m64n96k16.f32.bf16.bf16 {%0, %1, %2, %3, %4, %5, %6, %7, %8, %9, %10, %11, %12, %13, %14, %15, %16, %17, %18, %19, %20, %21, %22, %23, %24, %25, %26, %27, %28, %29, %30, %31, %32, %33, %34, %35, %36, %37, %38, %39, %40, %41, %42, %43, %44, %45, %46, %47}, {%52, %53, %54, %55}, tb, p1, 1, 1, 1;\n"
        "add.s64 tb, tb0, 352;\n"
        "wgmma.mma_async.sync.aligned.m64n96k16.f32.bf16.bf16 {%0, %1, %2, %3, %4, %5, %6, %7, %8, %9, %10, %11, %12, %13, %14, %15, %16, %17, %18, %19, %20, %21, %22, %23, %24, %25, %26, %27, %28, %29, %30, %31, %32, %33, %34, %35, %36, %37, %38, %39, %40, %41, %42, %43, %44, %45, %46, %47}, {%56, %57, %58, %59}, tb, p1, 1, 1, 1;\n"
        "}\n"
        : "+f"(d[0]), "+f"(d[1]), "+f"(d[2]), "+f"(d[3]), "+f"(d[4]), "+f"(d[5]), "+f"(d[6]), "+f"(d[7]), "+f"(d[8]), "+f"(d[9]), "+f"(d[10]), "+f"(d[11]), "+f"(d[12]), "+f"(d[13]), "+f"(d[14]), "+f"(d[15]), "+f"(d[16]), "+f"(d[17]), "+f"(d[18]), "+f"(d[19]), "+f"(d[20]), "+f"(d[21]), "+f"(d[22]), "+f"(d[23]), "+f"(d[24]), "+f"(d[25]), "+f"(d[26]), "+f"(d[27]), "+f"(d[28]), "+f"(d[29]), "+f"(d[30]), "+f"(d[31]), "+f"(d[32]), "+f"(d[33]), "+f"(d[34]), "+f"(d[35]), "+f"(d[36]), "+f"(d[37]), "+f"(d[38]), "+f"(d[39]), "+f"(d[40]), "+f"(d[41]), "+f"(d[42]), "+f"(d[43]), "+f"(d[44]), "+f"(d[45]), "+f"(d[46]), "+f"(d[47])
        : "r"(a[AOFF + 0][0]), "r"(a[AOFF + 0][1]), "r"(a[AOFF + 0][2]), "r"(a[AOFF + 0][3]), "r"(a[AOFF + 1][0]), "r"(a[AOFF + 1][1]), "r"(a[AOFF + 1][2]), "r"(a[AOFF + 1][3]), "r"(a[AOFF + 2][0]), "r"(a[AOFF + 2][1]), "r"(a[AOFF + 2][2]), "r"(a[AOFF + 2][3]), "l"(descB), "n"(BOFF >> 4));
}
};
template <> struct Rng<0, 10, 12> {
template <int BOFF, int AOFF, int NA>
static __device__ __forceinline__ void run(float (&d)[48], const uint32_t (&a)[NA][4], uint64_t descB) {
    asm volatile(
        "{\n"
        ".reg .pred p0, p1;\n"
        ".reg .b64 ta, ta0, tb, tb0;\n"
        "setp.ne.b32 p0, 0, 0;\n"
        "setp.eq.b32 p1, 0, 0;\n"
        "add.s64 tb0, %56, %57;\n"
        "add.s64 tb, tb0, 3136;\n"
        "wgmma.mma_async.sync.aligned.m64n96k16.f32.bf16.bf16 {%0, %1, %2, %3, %4, %5, %6, %7, %8, %9, %10, %11, %12, %13, %14, %15, %16, %17, %18, %19, %20, %21, %22, %23, %24, %25, %26, %27, %28, %29, %30, %31, %32, %33, %34, %35, %36, %37, %38, %39, %40, %41, %42, %43, %44, %45, %46, %47}, {%48, %49, %50, %51}, tb, p1, 1, 1, 1;\n"
        "add.s64 tb, tb0, 3168;\n"
        "wgmma.mma_async.sync.aligned.m64n96k16.f32.bf16.bf16 {%0, %1, %2, %3, %4, %5, %6, %7, %8, %9, %10, %11, %12, %13, %14, %15, %16, %17, %18, %19, %20, %21, %22, %23, %24, %25, %26, %27, %28, %29, %30, %31, %32, %33, %34, %35, %36, %37, %38, %39, %40, %41, %42, %43, %44, %45, %46, %47}, {%52, %53, %54, %55}, tb, p1, 1, 1, 1;\n"
        "}\n"
        : "+f"(d[0]), "+f"(d[1]), "+f"(d[2]), "+f"(d[3]), "+f"(d[4]), "+f"(d[5]), "+f"(d[6]), "+f"(d[7]), "+f"(d[8]), "+f"(d[9]), "+f"(d[10]), "+f"(d[11]), "+f"(d[12]), "+f"(d[13]), "+f"(d[14]), "+f"(d[15]), "+f"(d[16]), "+f"(d[17]), "+f"(d[18]), "+f"(d[19]), "+f"(d[20]), "+f"(d[21]), "+f"(d[22]), "+f"(d[23]), "+f"(d[24]), "+f"(d[25]), "+f"(d[26]), "+f"(d[27]), "+f"(d[28]), "+f"(d[29]), "+f"(d[30]), "+f"(d[31]), "+f"(d[32]), "+f"(d[33]), "+f"(d[34]), "+f"(d[35]), "+f"(d[36]), "+f"(d[37]), "+f"(d[38]), "+f"(d[39]), "+f"(d[40]), "+f"(d[41]), "+f"(d[42]), "+f"(d[43]), "+f"(d[44]), "+f"(d[45]), "+f"(d[46]), "+f"(d[47])
        : "r"(a[AOFF + 0][0]), "r"(a[AOFF + 0][1]), "r"(a[AOFF + 0][2]), "r"(a[AOFF + 0][3]), "r"(a[AOFF + 1][0]), "r"(a[AOFF + 1][1]), "r"(a[AOFF + 1][2]), "r"(a[AOFF + 1][3]), "l"(descB), "n"(BOFF >> 4));
}
};
template <> struct Rng<1, 10, 12> {
template <int BOFF, int AOFF, int NA>
static __device__ __forceinline__ void run(float (&d)[48], const uint32_t (&a)[NA][4], uint64_t descB) {
    asm volatile(
        "{\n"
        ".reg .pred p0, p1;\n"
        ".reg .b64 ta, ta0, tb, tb0;\n"
        "setp.ne.b32 p0, 0, 0;\n"
        "setp.eq.b32 p1, 0, 0;\n"
        "add.s64 tb0, %56, %57;\n"
        "add.s64 tb, tb0, 320;\n"
        "wgmma.mma_async.sync.aligned.m64n96k16.f32.bf16.bf16 {%0, %1, %2, %3, %4, %5, %6, %7, %8, %9, %10, %11, %12, %13, %14, %15, %16, %17, %18, %19, %20, %21, %22, %23, %24, %25, %26, %27, %28, %29, %30, %31, %32, %33, %34, %35, %36, %37, %38, %39, %40, %41, %42, %43, %44, %45, %46, %47}, {%48, %49, %50, %51}, tb, p1, 1, 1, 1;\n"
        "add.s64 tb, tb0, 352;\n"
        "wgmma.mma_async.sync.aligned.m64n96k16.f32.bf16.bf16 {%0, %1, %2, %3, %4, %5, %6, %7, %8, %9, %10, %11, %12, %13, %14, %15, %16, %17, %18, %19, %20, %21, %22, %23, %24, %25, %26, %27, %28, %29, %30, %31, %32, %33, %34, %35, %36, %37, %38, %39, %40, %41, %42, %43, %44, %45, %46, %47}, {%52, %53, %54, %55}, tb, p1, 1, 1, 1;\n"
        "}\n"
        : "+f"(d[0]), "+f"(d[1]), "+f"(d[2]), "+f"(d[3]), "+f"(d[4]), "+f"(d[5]), "+f"(d[6]), "+f"(d[7]), "+f"(d[8]), "+f"(d[9]), "+f"(d[10]), "+f"(d[11]), "+f"(d[12]), "+f"(d[13]), "+f"(d[14]), "+f"(d[15]), "+f"(d[16]), "+f"(d[17]), "+f"(d[18]), "+f"(d[19]), "+f"(d[20]), "+f"(d[21]), "+f"(d[22]), "+f"(d[23]), "+f"(d[24]), "+f"(d[25]), "+f"(d[26]), "+f"(d[27]), "+f"(d[28]), "+f"(d[29]), "+f"(d[30]), "+f"(d[31]), "+f"(d[32]), "+f"(d[33]), "+f"(d[34]), "+f"(d[35]), "+f"(d[36]), "+f"(d[37]), "+f"(d[38]), "+f"(d[39]), "+f"(d[40]), "+f"(d[41]), "+f"(d[42]), "+f"(d[43]), "+f"(d[44]), "+f"(d[45]), "+f"(d[46]), "+f"(d[47])
        : "r"(a[AOFF + 0][0]), "r"(a[AOFF + 0][1]), "r"(a[AOFF + 0][2]), "r"(a[AOFF + 0][3]), "r"(a[AOFF + 1][0]), "r"(a[AOFF + 1][1]), "r"(a[AOFF + 1][2]), "r"(a[AOFF + 1][3]), "l"(descB), "n"(BOFF >> 4));
}
};
template <int V, int BOFF, int S0, int S1>
__device__ __forceinline__ void mma_rng(float (&d)[48], const uint32_t (&a)[12][4], uint64_t descB) {
    if constexpr (S0 < S1) Rng<V, S0, S1>::template run<BOFF, S0, 12>(d, a, descB);
}

template <int AOFF, int BOFF>
__device__ __forceinline__ void mma_qk0(float (&d)[28], uint64_t descA, uint64_t descB) {
    asm volatile(
        "{\n"
        ".reg .pred p0, p1;\n"
        ".reg .b64 ta, ta0, tb, tb0;\n"
        "setp.ne.b32 p0, 0, 0;\n"
        "setp.eq.b32 p1, 0, 0;\n"
        "add.s64 tb0, %30, %31;\n"
        "add.s64 ta0, %28, %29;\n"
        "add.s64 tb, tb0, 4;\n"
        "add.s64 ta, ta0, 0;\n"
        "wgmma.mma_async.sync.aligned.m64n56k16.f32.bf16.bf16 {%0, %1, %2, %3, %4, %5, %6, %7, %8, %9, %10, %11, %12, %13, %14, %15, %16, %17, %18, %19, %20, %21, %22, %23, %24, %25, %26, %27}, ta, tb, p0, 1, 1, 0, 0;\n"
        "add.s64 tb, tb0, 1572;\n"
        "add.s64 ta, ta0, 1568;\n"
        "wgmma.mma_async.sync.aligned.m64n56k16.f32.bf16.bf16 {%0, %1, %2, %3, %4, %5, %6, %7, %8, %9, %10, %11, %12, %13, %14, %15, %16, %17, %18, %19, %20, %21, %22, %23, %24, %25, %26, %27}, ta, tb, p1, 1, 1, 0, 0;\n"
        "add.s64 tb, tb0, 3140;\n"
        "add.s64 ta, ta0, 3136;\n"
        "wgmma.mma_async.sync.aligned.m64n56k16.f32.bf16.bf16 {%0, %1, %2, %3, %4, %5, %6, %7, %8, %9, %10, %11, %12, %13, %14, %15, %16, %17, %18, %19, %20, %21, %22, %23, %24, %25, %26, %27}, ta, tb, p1, 1, 1, 0, 0;\n"
        "}\n"
        : "=f"(d[0]), "=f"(d[1]), "=f"(d[2]), "=f"(d[3]), "=f"(d[4]), "=f"(d[5]), "=f"(d[6]), "=f"(d[7]), "=f"(d[8]), "=f"(d[9]), "=f"(d[10]), "=f"(d[11]), "=f"(d[12]), "=f"(d[13]), "=f"(d[14]), "=f"(d[15]), "=f"(d[16]), "=f"(d[17]), "=f"(d[18]), "=f"(d[19]), "=f"(d[20]), "=f"(d[21]), "=f"(d[22]), "=f"(d[23]), "=f"(d[24]), "=f"(d[25]), "=f"(d[26]), "=f"(d[27])
        : "l"(descA), "n"(AOFF >> 4), "l"(descB), "n"(BOFF >> 4));
}

template <int AOFF, int BOFF>
__device__ __forceinline__ void mma_qk1(float (&d)[28], uint64_t descA, uint64_t descB) {
    asm volatile(
        "{\n"
        ".reg .pred p0, p1;\n"
        ".reg .b64 ta, ta0, tb, tb0;\n"
        "setp.ne.b32 p0, 0, 0;\n"
        "setp.eq.b32 p1, 0, 0;\n"
        "add.s64 tb0, %30, %31;\n"
        "add.s64 ta0, %28, %29;\n"
        "add.s64 tb, tb0, 6;\n"
        "add.s64 ta, ta0, 2;\n"
        "wgmma.mma_async.sync.aligned.m64n56k16.f32.bf16.bf16 {%0, %1, %2, %3, %4, %5, %6, %7, %8, %9, %10, %11, %12, %13, %14, %15, %16, %17, %18, %19, %20, %21, %22, %23, %24, %25, %26, %27}, ta, tb, p0, 1, 1, 0, 0;\n"
        "add.s64 tb, tb0, 1574;\n"
        "add.s64 ta, ta0, 1570;\n"
        "wgmma.mma_async.sync.aligned.m64n56k16.f32.bf16.bf16 {%0, %1, %2, %3, %4, %5, %6, %7, %8, %9, %10, %11, %12, %13, %14, %15, %16, %17, %18, %19, %20, %21, %22, %23, %24, %25, %26, %27}, ta, tb, p1, 1, 1, 0, 0;\n"
        "add.s64 tb, tb0, 3142;\n"
        "add.s64 ta, ta0, 3138;\n"
        "wgmma.mma_async.sync.aligned.m64n56k16.f32.bf16.bf16 {%0, %1, %2, %3, %4, %5, %6, %7, %8, %9, %10, %11, %12, %13, %14, %15, %16, %17, %18, %19, %20, %21, %22, %23, %24, %25, %26, %27}, ta, tb, p1, 1, 1, 0, 0;\n"
        "}\n"
        : "=f"(d[0]), "=f"(d[1]), "=f"(d[2]), "=f"(d[3]), "=f"(d[4]), "=f"(d[5]), "=f"(d[6]), "=f"(d[7]), "=f"(d[8]), "=f"(d[9]), "=f"(d[10]), "=f"(d[11]), "=f"(d[12]), "=f"(d[13]), "=f"(d[14]), "=f"(d[15]), "=f"(d[16]), "=f"(d[17]), "=f"(d[18]), "=f"(d[19]), "=f"(d[20]), "=f"(d[21]), "=f"(d[22]), "=f"(d[23]), "=f"(d[24]), "=f"(d[25]), "=f"(d[26]), "=f"(d[27])
        : "l"(descA), "n"(AOFF >> 4), "l"(descB), "n"(BOFF >> 4));
}

template <int BOFF, int AOFF, int NA>
__device__ __forceinline__ void mma_pv(float (&d)[28], const uint32_t (&a)[NA][4], uint64_t descB) {
    asm volatile(
        "{\n"
        ".reg .pred p0, p1;\n"
        ".reg .b64 ta, ta0, tb, tb0;\n"
        "setp.ne.b32 p0, 0, 0;\n"
        "setp.eq.b32 p1, 0, 0;\n"
        "add.s64 tb0, %44, %45;\n"
        "add.s64 tb, tb0, 0;\n"
        "wgmma.mma_async.sync.aligned.m64n56k16.f32.bf16.bf16 {%0, %1, %2, %3, %4, %5, %6, %7, %8, %9, %10, %11, %12, %13, %14, %15, %16, %17, %18, %19, %20, %21, %22, %23, %24, %25, %26, %27}, {%28, %29, %30, %31}, tb, p0, 1, 1, 1;\n"
        "add.s64 tb, tb0, 16;\n"
        "wgmma.mma_async.sync.aligned.m64n56k16.f32.bf16.bf16 {%0, %1, %2, %3, %4, %5, %6, %7, %8, %9, %10, %11, %12, %13, %14, %15, %16, %17, %18, %19, %20, %21, %22, %23, %24, %25, %26, %27}, {%32, %33, %34, %35}, tb, p1, 1, 1, 1;\n"
        "add.s64 tb, tb0, 32;\n"
        "wgmma.mma_async.sync.aligned.m64n56k16.f32.bf16.bf16 {%0, %1, %2, %3, %4, %5, %6, %7, %8, %9, %10, %11, %12, %13, %14, %15, %16, %17, %18, %19, %20, %21, %22, %23, %24, %25, %26, %27}, {%36, %37, %38, %39}, tb, p1, 1, 1, 1;\n"
        "add.s64 tb, tb0, 48;\n"
        "wgmma.mma_async.sync.aligned.m64n56k16.f32.bf16.bf16 {%0, %1, %2, %3, %4, %5, %6, %7, %8, %9, %10, %11, %12, %13, %14, %15, %16, %17, %18, %19, %20, %21, %22, %23, %24, %25, %26, %27}, {%40, %41, %42, %43}, tb, p1, 1, 1, 1;\n"
        "}\n"
        : "=f"(d[0]), "=f"(d[1]), "=f"(d[2]), "=f"(d[3]), "=f"(d[4]), "=f"(d[5]), "=f"(d[6]), "=f"(d[7]), "=f"(d[8]), "=f"(d[9]), "=f"(d[10]), "=f"(d[11]), "=f"(d[12]), "=f"(d[13]), "=f"(d[14]), "=f"(d[15]), "=f"(d[16]), "=f"(d[17]), "=f"(d[18]), "=f"(d[19]), "=f"(d[20]), "=f"(d[21]), "=f"(d[22]), "=f"(d[23]), "=f"(d[24]), "=f"(d[25]), "=f"(d[26]), "=f"(d[27])
        : "r"(a[AOFF + 0][0]), "r"(a[AOFF + 0][1]), "r"(a[AOFF + 0][2]), "r"(a[AOFF + 0][3]), "r"(a[AOFF + 1][0]), "r"(a[AOFF + 1][1]), "r"(a[AOFF + 1][2]), "r"(a[AOFF + 1][3]), "r"(a[AOFF + 2][0]), "r"(a[AOFF + 2][1]), "r"(a[AOFF + 2][2]), "r"(a[AOFF + 2][3]), "r"(a[AOFF + 3][0]), "r"(a[AOFF + 3][1]), "r"(a[AOFF + 3][2]), "r"(a[AOFF + 3][3]), "l"(descB), "n"(BOFF >> 4));
}

template <int AOFF, int BOFF>
__device__ __forceinline__ void mma_proj(float (&d)[96], uint64_t descA, uint64_t descB) {
    asm volatile(
        "{\n"
        ".reg .pred p0, p1;\n"
        ".reg .b64 ta, ta0, tb, tb0;\n"
        "setp.ne.b32 p0, 0, 0;\n"
        "setp.eq.b32 p1, 0, 0;\n"
        "add.s64 tb0, %98, %99;\n"
        "add.s64 ta0, %96, %97;\n"
        "add.s64 tb, tb0, 0;\n"
        "add.s64 ta, ta0, 0;\n"
        "wgmma.mma_async.sync.aligned.m64n192k16.f32.bf16.bf16 {%0, %1, %2, %3, %4, %5, %6, %7, %8, %9, %10, %11, %12, %13, %14, %15, %16, %17, %18, %19, %20, %21, %22, %23, %24, %25, %26, %27, %28, %29, %30, %31, %32, %33, %34, %35, %36, %37, %38, %39, %40, %41, %42, %43, %44, %45, %46, %47, %48, %49, %50, %51, %52, %53, %54, %55, %56, %57, %58, %59, %60, %61, %62, %63, %64, %65, %66, %67, %68, %69, %70, %71, %72, %73, %74, %75, %76, %77, %78, %79, %80, %81, %82, %83, %84, %85, %86, %87, %88, %89, %90, %91, %92, %93, %94, %95}, ta, tb, p0, 1, 1, 0, 1;\n"
        "add.s64 tb, tb0, 64;\n"
        "add.s64 ta, ta0, 2;\n"
        "wgmma.mma_async.sync.aligned.m64n192k16.f32.bf16.bf16 {%0, %1, %2, %3, %4, %5, %6, %7, %8, %9, %10, %11, %12, %13, %14, %15, %16, %17, %18, %19, %20, %21, %22, %23, %24, %25, %26, %27, %28, %29, %30, %31, %32, %33, %34, %35, %36, %37, %38, %39, %40, %41, %42, %43, %44, %45, %46, %47, %48, %49, %50, %51, %52, %53, %54, %55, %56, %57, %58, %59, %60, %61, %62, %63, %64, %65, %66, %67, %68, %69, %70, %71, %72, %73, %74, %75, %76, %77, %78, %79, %80, %81, %82, %83, %84, %85, %86, %87, %88, %89, %90, %91, %92, %93, %94, %95}, ta, tb, p1, 1, 1, 0, 1;\n"
        "add.s64 tb, tb0, 128;\n"
        "add.s64 ta, ta0, 4;\n"
        "wgmma.mma_async.sync.aligned.m64n192k16.f32.bf16.bf16 {%0, %1, %2, %3, %4, %5, %6, %7, %8, %9, %10, %11, %12, %13, %14, %15, %16, %17, %18, %19, %20, %21, %22, %23, %24, %25, %26, %27, %28, %29, %30, %31, %32, %33, %34, %35, %36, %37, %38, %39, %40, %41, %42, %43, %44, %45, %46, %47, %48, %49, %50, %51, %52, %53, %54, %55, %56, %57, %58, %59, %60, %61, %62, %63, %64, %65, %66, %67, %68, %69, %70, %71, %72, %73, %74, %75, %76, %77, %78, %79, %80, %81, %82, %83, %84, %85, %86, %87, %88, %89, %90, %91, %92, %93, %94, %95}, ta, tb, p1, 1, 1, 0, 1;\n"
        "add.s64 tb, tb0, 192;\n"
        "add.s64 ta, ta0, 6;\n"
        "wgmma.mma_async.sync.aligned.m64n192k16.f32.bf16.bf16 {%0, %1, %2, %3, %4, %5, %6, %7, %8, %9, %10, %11, %12, %13, %14, %15, %16, %17, %18, %19, %20, %21, %22, %23, %24, %25, %26, %27, %28, %29, %30, %31, %32, %33, %34, %35, %36, %37, %38, %39, %40, %41, %42, %43, %44, %45, %46, %47, %48, %49, %50, %51, %52, %53, %54, %55, %56, %57, %58, %59, %60, %61, %62, %63, %64, %65, %66, %67, %68, %69, %70, %71, %72, %73, %74, %75, %76, %77, %78, %79, %80, %81, %82, %83, %84, %85, %86, %87, %88, %89, %90, %91, %92, %93, %94, %95}, ta, tb, p1, 1, 1, 0, 1;\n"
        "add.s64 tb, tb0, 256;\n"
        "add.s64 ta, ta0, 512;\n"
        "wgmma.mma_async.sync.aligned.m64n192k16.f32.bf16.bf16 {%0, %1, %2, %3, %4, %5, %6, %7, %8, %9, %10, %11, %12, %13, %14, %15, %16, %17, %18, %19, %20, %21, %22, %23, %24, %25, %26, %27, %28, %29, %30, %31, %32, %33, %34, %35, %36, %37, %38, %39, %40, %41, %42, %43, %44, %45, %46, %47, %48, %49, %50, %51, %52, %53, %54, %55, %56, %57, %58, %59, %60, %61, %62, %63, %64, %65, %66, %67, %68, %69, %70, %71, %72, %73, %74, %75, %76, %77, %78, %79, %80, %81, %82, %83, %84, %85, %86, %87, %88, %89, %90, %91, %92, %93, %94, %95}, ta, tb, p1, 1, 1, 0, 1;\n"
        "add.s64 tb, tb0, 320;\n"
        "add.s64 ta, ta0, 514;\n"
        "wgmma.mma_async.sync.aligned.m64n192k16.f32.bf16.bf16 {%0, %1, %2, %3, %4, %5, %6, %7, %8, %9, %10, %11, %12, %13, %14, %15, %16, %17, %18, %19, %20, %21, %22, %23, %24, %25, %26, %27, %28, %29, %30, %31, %32, %33, %34, %35, %36, %37, %38, %39, %40, %41, %42, %43, %44, %45, %46, %47, %48, %49, %50, %51, %52, %53, %54, %55, %56, %57, %58, %59, %60, %61, %62, %63, %64, %65, %66, %67, %68, %69, %70, %71, %72, %73, %74, %75, %76, %77, %78, %79, %80, %81, %82, %83, %84, %85, %86, %87, %88, %89, %90, %91, %92, %93, %94, %95}, ta, tb, p1, 1, 1, 0, 1;\n"
        "add.s64 tb, tb0, 384;\n"
        "add.s64 ta, ta0, 516;\n"
        "wgmma.mma_async.sync.aligned.m64n192k16.f32.bf16.bf16 {%0, %1, %2, %3, %4, %5, %6, %7, %8, %9, %10, %11, %12, %13, %14, %15, %16, %17, %18, %19, %20, %21, %22, %23, %24, %25, %26, %27, %28, %29, %30, %31, %32, %33, %34, %35, %36, %37, %38, %39, %40, %41, %42, %43, %44, %45, %46, %47, %48, %49, %50, %51, %52, %53, %54, %55, %56, %57, %58, %59, %60, %61, %62, %63, %64, %65, %66, %67, %68, %69, %70, %71, %72, %73, %74, %75, %76, %77, %78, %79, %80, %81, %82, %83, %84, %85, %86, %87, %88, %89, %90, %91, %92, %93, %94, %95}, ta, tb, p1, 1, 1, 0, 1;\n"
        "add.s64 tb, tb0, 448;\n"
        "add.s64 ta, ta0, 518;\n"
        "wgmma.mma_async.sync.aligned.m64n192k16.f32.bf16.bf16 {%0, %1, %2, %3, %4, %5, %6, %7, %8, %9, %10, %11, %12, %13, %14, %15, %16, %17, %18, %19, %20, %21, %22, %23, %24, %25, %26, %27, %28, %29, %30, %31, %32, %33, %34, %35, %36, %37, %38, %39, %40, %41, %42, %43, %44, %45, %46, %47, %48, %49, %50, %51, %52, %53, %54, %55, %56, %57, %58, %59, %60, %61, %62, %63, %64, %65, %66, %67, %68, %69, %70, %71, %72, %73, %74, %75, %76, %77, %78, %79, %80, %81, %82, %83, %84, %85, %86, %87, %88, %89, %90, %91, %92, %93, %94, %95}, ta, tb, p1, 1, 1, 0, 1;\n"
        "add.s64 tb, tb0, 512;\n"
        "add.s64 ta, ta0, 1024;\n"
        "wgmma.mma_async.sync.aligned.m64n192k16.f32.bf16.bf16 {%0, %1, %2, %3, %4, %5, %6, %7, %8, %9, %10, %11, %12, %13, %14, %15, %16, %17, %18, %19, %20, %21, %22, %23, %24, %25, %26, %27, %28, %29, %30, %31, %32, %33, %34, %35, %36, %37, %38, %39, %40, %41, %42, %43, %44, %45, %46, %47, %48, %49, %50, %51, %52, %53, %54, %55, %56, %57, %58, %59, %60, %61, %62, %63, %64, %65, %66, %67, %68, %69, %70, %71, %72, %73, %74, %75, %76, %77, %78, %79, %80, %81, %82, %83, %84, %85, %86, %87, %88, %89, %90, %91, %92, %93, %94, %95}, ta, tb, p1, 1, 1, 0, 1;\n"
        "add.s64 tb, tb0, 576;\n"
        "add.s64 ta, ta0, 1026;\n"
        "wgmma.mma_async.sync.aligned.m64n192k16.f32.bf16.bf16 {%0, %1, %2, %3, %4, %5, %6, %7, %8, %9, %10, %11, %12, %13, %14, %15, %16, %17, %18, %19, %20, %21, %22, %23, %24, %25, %26, %27, %28, %29, %30, %31, %32, %33, %34, %35, %36, %37, %38, %39, %40, %41, %42, %43, %44, %45, %46, %47, %48, %49, %50, %51, %52, %53, %54, %55, %56, %57, %58, %59, %60, %61, %62, %63, %64, %65, %66, %67, %68, %69, %70, %71, %72, %73, %74, %75, %76, %77, %78, %79, %80, %81, %82, %83, %84, %85, %86, %87, %88, %89, %90, %91, %92, %93, %94, %95}, ta, tb, p1, 1, 1, 0, 1;\n"
        "add.s64 tb, tb0, 640;\n"
        "add.s64 ta, ta0, 1028;\n"
        "wgmma.mma_async.sync.aligned.m64n192k16.f32.bf16.bf16 {%0, %1, %2, %3, %4, %5, %6, %7, %8, %9, %10, %11, %12, %13, %14, %15, %16, %17, %18, %19, %20, %21, %22, %23, %24, %25, %26, %27, %28, %29, %30, %31, %32, %33, %34, %35, %36, %37, %38, %39, %40, %41, %42, %43, %44, %45, %46, %47, %48, %49, %50, %51, %52, %53, %54, %55, %56, %57, %58, %59, %60, %61, %62, %63, %64, %65, %66, %67, %68, %69, %70, %71, %72, %73, %74, %75, %76, %77, %78, %79, %80, %81, %82, %83, %84, %85, %86, %87, %88, %89, %90, %91, %92, %93, %94, %95}, ta, tb, p1, 1, 1, 0, 1;\n"
        "add.s64 tb, tb0, 704;\n"
        "add.s64 ta, ta0, 1030;\n"
        "wgmma.mma_async.sync.aligned.m64n192k16.f32.bf16.bf16 {%0, %1, %2, %3, %4, %5, %6, %7, %8, %9, %10, %11, %12, %13, %14, %15, %16, %17, %18, %19, %20, %21, %22, %23, %24, %25, %26, %27, %28, %29, %30, %31, %32, %33, %34, %35, %36, %37, %38, %39, %40, %41, %42, %43, %44, %45, %46, %47, %48, %49, %50, %51, %52, %53, %54, %55, %56, %57, %58, %59, %60, %61, %62, %63, %64, %65, %66, %67, %68, %69, %70, %71, %72, %73, %74, %75, %76, %77, %78, %79, %80, %81, %82, %83, %84, %85, %86, %87, %88, %89, %90, %91, %92, %93, %94, %95}, ta, tb, p1, 1, 1, 0, 1;\n"
        "}\n"
        : "+f"(d[0]), "+f"(d[1]), "+f"(d[2]), "+f"(d[3]), "+f"(d[4]), "+f"(d[5]), "+f"(d[6]), "+f"(d[7]), "+f"(d[8]), "+f"(d[9]), "+f"(d[10]), "+f"(d[11]), "+f"(d[12]), "+f"(d[13]), "+f"(d[14]), "+f"(d[15]), "+f"(d[16]), "+f"(d[17]), "+f"(d[18]), "+f"(d[19]), "+f"(d[20]), "+f"(d[21]), "+f"(d[22]), "+f"(d[23]), "+f"(d[24]), "+f"(d[25]), "+f"(d[26]), "+f"(d[27]), "+f"(d[28]), "+f"(d[29]), "+f"(d[30]), "+f"(d[31]), "+f"(d[32]), "+f"(d[33]), "+f"(d[34]), "+f"(d[35]), "+f"(d[36]), "+f"(d[37]), "+f"(d[38]), "+f"(d[39]), "+f"(d[40]), "+f"(d[41]), "+f"(d[42]), "+f"(d[43]), "+f"(d[44]), "+f"(d[45]), "+f"(d[46]), "+f"(d[47]), "+f"(d[48]), "+f"(d[49]), "+f"(d[50]), "+f"(d[51]), "+f"(d[52]), "+f"(d[53]), "+f"(d[54]), "+f"(d[55]), "+f"(d[56]), "+f"(d[57]), "+f"(d[58]), "+f"(d[59]), "+f"(d[60]), "+f"(d[61]), "+f"(d[62]), "+f"(d[63]), "+f"(d[64]), "+f"(d[65]), "+f"(d[66]), "+f"(d[67]), "+f"(d[68]), "+f"(d[69]), "+f"(d[70]), "+f"(d[71]), "+f"(d[72]), "+f"(d[73]), "+f"(d[74]), "+f"(d[75]), "+f"(d[76]), "+f"(d[77]), "+f"(d[78]), "+f"(d[79]), "+f"(d[80]), "+f"(d[81]), "+f"(d[82]), "+f"(d[83]), "+f"(d[84]), "+f"(d[85]), "+f"(d[86]), "+f"(d[87]), "+f"(d[88]), "+f"(d[89]), "+f"(d[90]), "+f"(d[91]), "+f"(d[92]), "+f"(d[93]), "+f"(d[94]), "+f"(d[95])
        : "l"(descA), "n"(AOFF >> 4), "l"(descB), "n"(BOFF >> 4));
}

struct Params {
    const __nv_bfloat16* x;
    const __nv_bfloat16* wqkv;
    const __nv_bfloat16* wo;
    const __nv_bfloat16* logit_scale;
    const __nv_bfloat16* cpb_w1;
    const __nv_bfloat16* cpb_w2;
    const __nv_bfloat16* rel_coords;
    const int*           rel_idx;
    const __nv_bfloat16* mask;
    __nv_bfloat16*       out;
    unsigned long long   z1;
};

struct Q {
    static constexpr int npair = NPAIR, nh = NH, hw = NH ? HW : 0;
    static constexpr uint32_t need = ROW_DONE;
    static constexpr int nq = (NWINDOWS - hw) / NPAIR, nr = (NWINDOWS - hw) % NPAIR;
    static constexpr int nr2 = 2 * nr, nt0 = (nq * TOK + 63) / 64, nt1 = ((nq + 1) * TOK + 63) / 64;
    static constexpr int hq = NH ? HW / (NH ? NH : 1) : 0, hr = NPAIR + (NH ? HW % (NH ? NH : 1) : 0), hr2 = 2 * hr;
    static constexpr int ht0 = (hq * TOK + 63) / 64, ht1 = ((hq + 1) * TOK + 63) / 64;
    static constexpr int t1 = TILES - NTAIL;
};
#define PQ(f) Q::f
#define GRID 132

struct Maps {
    CUtensorMap x77, x47, x37, x44, x43, x34, x33;
    CUtensorMap w64, w32, w;
    CUtensorMap s47, s37, s43, s33;
    CUtensorMap o, ob;
};

__device__ __forceinline__ uint32_t row_token(uint32_t r) {
    return r < 28 ? r + 3 * (r >> 2) : r - 24 + 4 * (((r - 28) * 11) >> 5);
}
__device__ __forceinline__ int unrot(int r) { return r ? r - 1 : NWS - 1; }
__device__ __forceinline__ void finish(uint32_t total) {
    __threadfence();
    if (atomicAdd(&g_done, 1u) == total - 1) {
        for (int i = 0; i <= NWS; i++) g_cnt[i] = 0;
        g_done = 0;
    }
}

__global__ void __launch_bounds__(NTHREADS, 1)
swin_window_attn_kernel(const Params P, const __grid_constant__ Maps M) {
    const CUtensorMap &xmap = M.x77, &omap = M.o, &omapb = M.ob, &wmap = M.w;
    extern __shared__ __align__(1024) uint8_t smem[];
    constexpr uint32_t sbase = 1024;
    if (smem_u32(smem) != sbase) return;
    const int tid = threadIdx.x;
    const int wg = __shfl_sync(0xffffffffu, tid >> 7, 0);
    const int warp = __shfl_sync(0xffffffffu, (tid >> 5) & 3, 0);
    const int lane = tid & 31;
    const int g = lane >> 2, c = lane & 3;

    TR(26, wg);
    TP(wg);
    if (tid == 0) TC(0);
    const bool attn = (int)blockIdx.x < 2 * (PQ(npair) + PQ(nh));
    const int pair = blockIdx.x >> 1, half = blockIdx.x & 1;
    const int nwin = pair < PQ(npair) ? PQ(nq) + (pair < PQ(nr) ? 1 : 0) : PQ(hq) + (pair < PQ(hr) ? 1 : 0);
    const int w0 = pair < PQ(npair) ? PQ(hw) + pair : pair - PQ(npair), wstep = pair < PQ(npair) ? PQ(npair) : PQ(nh);
    const int wr0 = w0 >= NWS, wq0 = w0 - wr0 * NWS;
    const int ntiles = (nwin * TOK + 63) >> 6;
    const uint32_t bars = sbase + SM_BAR;
    auto load_x = [&](uint32_t dst, uint32_t bar, uint32_t bar2, int wh, int ww) {
        const int x0 = 7 * ww + 3, y0 = 7 * wh + 3, x1 = ww == NWS - 1 ? 0 : x0 + 4;
        if (wh < NWS - 1) {
#pragma unroll
            for (int ch = 0; ch < 3; ch++) tma_3d_x(dst + ch * QK_CHUNK, &M.x47, bar, ch * 64, x0, y0);
#pragma unroll
            for (int ch = 0; ch < 3; ch++) tma_3d_x(dst + ch * QK_CHUNK + 28 * 128, &M.x37, bar2, ch * 64, x1, y0);
        } else {
#pragma unroll
            for (int ch = 0; ch < 3; ch++) {
                tma_3d_x(dst + ch * QK_CHUNK, &M.x44, bar, ch * 64, x0, y0);
                tma_3d_x(dst + ch * QK_CHUNK + 16 * 128, &M.x43, bar, ch * 64, x0, 0);
            }
#pragma unroll
            for (int ch = 0; ch < 3; ch++) {
                tma_3d_x(dst + ch * QK_CHUNK + 28 * 128, &M.x34, bar2, ch * 64, x1, y0);
                tma_3d_x(dst + ch * QK_CHUNK + 40 * 128, &M.x33, bar2, ch * 64, x1, 0);
            }
        }
    };
    if (EPF && (wg == 1 || wg == 2)) {
        const int i = tid - 128, q = w0 + half * wstep, r = q >= NWS;
        const int px = (i * 171) >> 9, py = (px * 37) >> 8;
        int y = 7 * unrot(r) + 3 + py, x = 7 * unrot(q - r * NWS) + 3 + px - 7 * py;
        if (y >= IMG) y -= IMG;
        if (x >= IMG) x -= IMG;
        const char* p = reinterpret_cast<const char*>(P.x) + (size_t)(y * IMG + x) * 384 + (i - 3 * px) * 128;
        if (EPW && i >= 147) p = reinterpret_cast<const char*>(P.wqkv) + min((int)blockIdx.x * 14 + i - 147, 1727) * 128;
        if (i < 147 ? attn : EPW && i < 161) {
            if (EPF == 1) asm volatile("prefetch.global.L2 [%0];\n" :: "l"(p) : "memory");
            if (EPF == 2) { uint32_t d; asm volatile("ld.global.nc.L2::128B.b32 %0, [%1];\n" : "=r"(d) : "l"(p) : "memory"); }
            if (EPF == 3) for (int j = 0; j < 4; j++) asm volatile("prefetch.global.L2 [%0];\n" :: "l"(p + 32 * j) : "memory");
        }
    }
    uint32_t ls = 0;
    if (wg == 0) {
        TP(28);
        if (attn && warp < (WSEQ ? 1 : 3) && elect_one()) {
#pragma unroll
            for (int i = 0; i < (WSEQ ? 3 : 1); i++) mbar_init(bars + B_WRAW + 16 - 8 * (warp + i), 1);
            fence_async_smem();
            if (HDEL && pair >= PQ(npair)) {
                const uint32_t c0 = clock();
                while (clock() - c0 < HDEL) __nanosleep(100);
            }
            TP(29);
#pragma unroll 1
            for (int i = warp; i < warp + (WSEQ ? 3 : 1); i++) {
                const uint32_t bar = bars + B_WRAW + 16 - 8 * i, dst = sbase + i * 24576;
                mbar_arrive_expect_tx(bar, 24576);
                tma_3d(dst, &M.w64, bar, half * 128, 64 * i, 0);
                tma_3d(dst + 16384, &M.w32, bar, 64 + half * 32, 64 * i, 0);
            }
            TP(30);
        }
        __syncwarp();
        if (WFIRST && warp == 0) asm volatile("bar.arrive 3, 96;\n" ::: "memory");
        if (PPAR && warp == 0) nb_arrive<416>(11);
        if (attn) asm volatile("ld.global.nc.u16 %0, [%1];\n" : "=r"(ls) : "l"(P.logit_scale + 2 * half + (GORD == 2 ? c >> 1 : c & 1)));
    } else if (wg == 3) {
        if (warp == 3) {
            if (elect_one()) {
#pragma unroll
                for (int i = 0; i < 6; i++)
                    asm volatile("prefetch.tensormap [%0];\n" :: "l"(reinterpret_cast<uint64_t>(&M.x44 + (i < 4 ? i : i - 6))) : "memory");
            }
            if (attn)
#pragma unroll
                for (int i = 0; i < 4; i++) sts128(sbase + SM_V + i * V_STRIDE + (lane < 16 ? lane * 16 : V_STRIDE - 64 + (lane & 3) * 16), 0, 0, 0, 0);
            sts32(sbase + SM_FLAG + lane * 4, 0);
            fence_async_smem();
            asm volatile("bar.arrive 0, 256;\nbar.arrive 11, %0;\n" :: "n"(PPAR ? 416 : 384) : "memory");
        } else if (warp != 1) {
            if (tid == 384) {
                for (int b = 0; b < 4; b++) mbar_init(bars + B_XFULL + b * 8, 2);
                asm volatile("mbarrier.expect_tx.relaxed.cta.shared::cta.b64 [%0], %1;\n" :: "r"(bars + B_XFULL + 8), "r"(3 * 21 * 128) : "memory");
                fence_async_smem();
            }
            __syncwarp();
            asm volatile("bar.arrive 0, 256;\nbar.arrive 11, %0;\n" :: "n"(PPAR ? 416 : 384) : "memory");
            nb_sync<WFIRST ? 96 : 64>(3);
            if (attn && elect_one()) {
                const int j = warp >> 1, q = w0 + j * wstep, r = q >= NWS;
                mbar_arrive_expect_tx(bars + B_XFULL, j ? 3 * 28 * 128 : 3 * XCH);
                load_x(sbase + SM_QK + j * XCH, bars + B_XFULL, bars + B_XFULL + j * 8, unrot(r), unrot(q - r * NWS));
                TP(26 + j);
            }
            __syncwarp();
        } else {
            if (lane == 0) {
                for (int b = 0; b < 4; b++) {
                    mbar_init(bars + B_QKRAW + b * 8, 4);
                    mbar_init(bars + B_VRAW + b * 8, 4);
                    mbar_init(bars + B_VFREE + b * 8, 2);
                    mbar_init(bars + B_QKFREE + b * 8, (NB & 1) ? 1 : 4);
                    mbar_init(bars + B_ODONE + b * 8, 4);
                }
                mbar_init(bars + B_WFULL, 1);
                mbar_init(bars + B_MFULL, 1);
                mbar_init(bars + B_MCONS, 4);
                sts32(bars + B_PROG, 0);
                for (int b = 0; b < 4; b++) mbar_init(bars + B_STORED + b * 8, 1);
                for (int b = 0; b < 6; b++) {
                    mbar_init(sbase + SM_PBAR + b * 8, 1);
                    mbar_init(sbase + SM_PBAR + 48 + b * 8, PSTORE ? 1 : 4);
                    mbar_init(sbase + SM_PBAR + 104 + b * 8, 4);
                }
                mbar_init(sbase + SM_PBAR + 96, 13);
                fence_async_smem();
            }
            __syncwarp();
            TP(19);
            asm volatile("bar.arrive 0, 256;\nbar.arrive 11, %0;\n" :: "n"(PPAR ? 416 : 384) : "memory");
        }
        asm volatile("bar.sync 2, 128;\n" ::: "memory");
        if (warp == 3 && lane < 8)
            asm volatile("prefetch.tensormap [%0];\n" :: "l"(reinterpret_cast<uint64_t>(&M.x77 + (lane ? lane + 8 : 0))) : "memory");
        TP(13);
    }
    uint32_t ridx[26];
    uint32_t rc, w2[16];
    uint4 w1[4];
    if (attn && (wg == 1 || wg == 2)) {
        rc = reinterpret_cast<const uint32_t*>(P.rel_coords)[min(tid - 128, 168)];
#pragma unroll
        for (int i = 0; i < 4; i++) w1[i] = reinterpret_cast<const uint4*>(P.cpb_w1)[i];
#pragma unroll
        for (int u = 0; u < 16; u++) w2[u] = reinterpret_cast<const uint32_t*>(P.cpb_w2)[2 * u + half];
        ls = reinterpret_cast<const uint32_t*>(P.logit_scale)[half];
        asm volatile("" ::: "memory");
        uint32_t col[7];
#pragma unroll
        for (int j = 0; j < 7; j++) {
            const uint32_t n = j ? 8 * ((j + 5) >> 1) + ((j + 1) & 1) : 0;
            col[j] = prmt(0, row_token(n) | row_token(n + 2) << 8 | row_token(n + 4) << 16 | row_token(n + 6) << 24, 4 + c);
        }
#pragma unroll
        for (int rh = 0; rh < 2; rh++) {
            const uint32_t* ri = reinterpret_cast<const uint32_t*>(P.rel_idx) + row_token(min(warp * 16 + g + 8 * rh, TOK - 1)) * TOK;
            asm volatile("" : "+l"(ri));
#pragma unroll
            for (int j = 0; j < 12; j++) ridx[13 * rh + j] = j < 6 ? (ri + col[0])[14 * (j >> 1) + (j & 1)] : ri[col[j - 5]];
            ridx[13 * rh + 12] = ri[48];
        }
    }
    if (wg == 1) TP(31);
    if (wg == 0) asm volatile("bar.sync 0, 256;\n" ::: "memory");
    else if (wg < 3) nb_sync<PPAR ? 416 : 384>(11);
    TP(4 + wg);

    const uint32_t nfinish = GRID + 4 * (PQ(npair) + PQ(nh));
#define PROJ_SCHEDULE                                                                                   \
    int bid = blockIdx.x;                                                                               \
    asm volatile("" : "+r"(bid));                      \
    const bool at = bid < 2 * PQ(npair);                                                                  \
    const int tile0 = at ? PQ(t1) + 2 * PQ(npair) - 1 - bid : bid - 2 * PQ(npair);                                              \
    const int tstep = at ? 2 * PQ(npair) : GRID - 2 * PQ(npair);                                  \
    const int tend = at ? TILES : PQ(t1);
    if (wg == 3) {
        asm volatile("setmaxnreg.dec.sync.aligned.u32 %0;\n" :: "n"(REG_H));
        if (attn && warp == 1 && !(XP & 1)) {
            uint32_t fph = 0, cph = 0, mis = 0, busy = 0;
            auto load = [&](int k, uint32_t dst) {
                const int wi = w0 + k * wstep, wr = wi / NWS;
                const uint32_t off = (uint32_t)(unrot(wr) * NWS + unrot(wi - wr * NWS)) * 4802u;
                mis = mis << 4 | (off & 15);
                if (busy) {
                    mbar_wait(bars + B_MCONS, cph);
                    cph ^= 1;
                    fence_async_smem();
                    busy = 0;
                }
                if (elect_one()) {
                    uint32_t bytes = 4816;
                    if (wi == 0) {
                        bytes = 4800;
                        asm volatile("st.shared.u16 [%0], %1;\n" :: "r"(sbase + SM_MASK + 4800),
                                     "h"(reinterpret_cast<const uint16_t*>(P.mask)[NWINDOWS * TOK * TOK - 1]) : "memory");
                    }
                    asm volatile("mbarrier.expect_tx.relaxed.cta.shared::cta.b64 [%0], %1;\n" :: "r"(bars + B_MFULL), "r"(bytes) : "memory");
                    if (dst == sbase + SM_MASK) mbar_arrive(bars + B_MFULL);
                    asm volatile("cp.async.bulk.shared::cluster.global.mbarrier::complete_tx::bytes.L2::cache_hint [%0], [%1], %2, [%3], %4;\n"
                                 :: "r"(dst), "l"(reinterpret_cast<const char*>(P.mask) + (off & ~15u)),
                                    "r"(bytes), "r"(bars + B_MFULL), "l"(EVICT_FIRST) : "memory");
                }
            };
            auto landed = [&]() {
                mbar_wait_s<HS & 1>(bars + B_MFULL, fph);
                fph ^= 1;
            };
            auto flag = [&](int k, uint32_t f) {
                asm volatile("st.volatile.shared.u8 [%0], %1;\n" :: "r"(sbase + SM_FLAG + k), "r"(f) : "memory");
                TR(18, k);
                if (k < 2) TP(14 + k);
            };
            auto buffer = [&](int k) { return sbase + (k == 0 || k > 3 ? SM_MASK : SM_V + 2 * V_STRIDE + 256 + (k >> 1) * 4816); };
#pragma unroll 1
            for (int k = 2 + half; k >= 0; k = (k >> 1) - (k == 0)) load(k, buffer(k));
            uint32_t todo = 0;
            int sp = 0;
#pragma unroll 1
            for (int k = 0, kn; sp < nwin; k = kn) {
                if (k < nwin) {
#pragma unroll 1
                    for (uint32_t n = 0; n < (1u << 22); n++) {
                        int done;
                        asm volatile("ld.volatile.shared.b32 %0, [%1];\n" : "=r"(done) : "r"(bars + B_PROG) : "memory");
                        if (done >= (k + 2 < nwin ? k - MLEAD : k - 3)) break;
                        __nanosleep(PSLEEP);
                    }
                    const uint32_t buf = buffer(k);
                    if (buf == sbase + SM_MASK) landed();
                    TR(17, k);
                    uint32_t any;
                    asm volatile("ld.shared.u16 %0, [%1];\n" : "=r"(any)
                                 : "r"(buf + (mis & 15) + ((lane & 8) ? 4800 - 14 : 0) + (lane & 7) * 2) : "memory");
                    mis >>= 4;
#pragma unroll
                    for (int i = 0; i < 10; i++) {
                        uint32_t v[4];
                        asm volatile("ld.shared.v4.b32 {%0, %1, %2, %3}, [%4];\n" : "=r"(v[0]), "=r"(v[1]), "=r"(v[2]), "=r"(v[3])
                                     : "r"(buf + lane * 16 + (i < 9 ? 16 + i * 512 : 4800 - 512)) : "memory");
                        any |= (v[0] | v[1]) | (v[2] | v[3]);
                    }
                    const uint32_t masked = __any_sync(0xffffffffu, any & 0x7FFF7FFFu);
                    if (k >= 2) asm volatile("st.relaxed.gpu.global.u32 [%0], %1;\n" :: "l"(g_flag + pair * 128 + k), "r"(1 + masked) : "memory");
                    if (masked && k) todo |= 1u << (k - sp);
                    else {
                        if (k == 0) __threadfence_block();
                        flag(k, 1 + masked);
                        busy |= masked;
                    }
                }
                if ((k >> 1) == 1 && lane == 0) mbar_arrive(bars + B_VFREE + 8);
                if (k > 2 && k <= nwin) {
                    uint32_t f;
#pragma unroll 1
                    for (uint32_t n = 0; n < (1u << 22); n++) {
                        asm volatile("ld.relaxed.gpu.global.u32 %0, [%1];\n" : "=r"(f) : "l"(g_flag + pair * 128 + k - 1) : "memory");
                        if (__all_sync(0xffffffffu, f)) break;
                        __nanosleep(PSLEEP);
                    }
                    g_flag[pair * 128 + k - 1] = 0;
                    if (f != 1) todo |= 1u << (k - 1 - sp);
                    else flag(k - 1, 1);
                }
#pragma unroll 1
                for (; sp < k; sp++, todo >>= 1)
                    if (todo & 1) {
                        load(sp, sbase + SM_MASK);
                        landed();
                        __threadfence_block();
                        flag(sp, 2);
                        busy = 1;
                    }
                kn = k >= 2 ? k + 2 : k + 1 + (k & half);
                if (kn < nwin && kn > 3) load(kn, sbase + SM_MASK);
                if (MP2 && kn + 2 * MP2 < nwin && kn > 1) {
                    const int wi = w0 + (kn + 2 * MP2) * wstep, wr = wi / NWS;
                    const uint32_t off = (uint32_t)(unrot(wr) * NWS + unrot(wi - wr * NWS)) * 4802u;
                    if (elect_one())
                        asm volatile("cp.async.bulk.prefetch.L2.global [%0], 4816;\n" :: "l"(reinterpret_cast<const char*>(P.mask) + (off & ~15u)) : "memory");
                }
            }
        }
        if (!elect_one()) return;
        if (warp == 0) {
          if (attn) {
            const int kmax = (64 * ntiles + 63) / TOK;
            int wr = wr0, wq = wq0;
            int pr2 = (w0 + PF_DIST * wstep) / NWS, pq2 = w0 + PF_DIST * wstep - pr2 * NWS;
#pragma unroll 1
            for (int k = -4; k + 4 <= kmax; k++) {
                const int row0 = (k + 4) * TOK;
                const uint32_t dst = sbase + SM_QK + (k & 3) * XCH, bar = bars + B_XFULL + ((row0 >> 6) & 3) * 8;
                const bool alone = (row0 & 63) >= 64 - TOK && (row0 & 63) < TOK;
                const int wh = unrot(wr), ww = unrot(wq), ph2 = unrot(pr2), pw2 = unrot(pq2);
                const bool done = k < -2;
                if (k == WVK) {
                    TP(24);
                    mbar_arrive_expect_tx(bars + B_WFULL, 6 * W_ATOM);
                    tma_3d(sbase + SM_WV, &wmap, bars + B_WFULL, 0, 0, V64 ? 12 + half * 3 : 24 + half * 6);
                }
                if (NB & 1) {
                    if (k >= 0) nb_sync<160>(NB_QKFREE + (k & 1));
                } else mbar_wait(bars + B_QKFREE + (k & 3) * 8, (k >> 2) & 1);
                if (alone && !done) mbar_arrive(bar);
                if (k + 4 >= nwin && k >= 0) {
                    mbar_arrive(bar);
                    continue;
                }
                TR(20, k + 4);
                if (k < 0) TP(44 + k);
                if (!done) {
                    uint32_t bar2 = bar;
                    if ((row0 & 63) >= 64 - 28) {
                        bar2 = bars + B_XFULL + (((row0 >> 6) + 1) & 3) * 8;
                        asm volatile("mbarrier.expect_tx.relaxed.cta.shared::cta.b64 [%0], %1;\n" :: "r"(bar2), "r"(3 * 21 * 128) : "memory");
                    }
                    mbar_arrive_expect_tx(bar, bar2 != bar ? 3 * 28 * 128 : 3 * XCH);
                    load_x(dst, bar, bar2, wh, ww);
                }
                asm volatile("st.volatile.shared.b32 [%0], %1;\n" :: "r"(bars + B_PROG), "r"(max(k + 1, 0)) : "memory");
                if (NOPF) {
                } else if (PFM == 2) {
                    if (pr2 < NWS && half == 0) {
                        const char* xp = reinterpret_cast<const char*>(P.x) + (size_t)((7 * ph2 + 3) * IMG + 7 * pw2 + 3) * 384;
#pragma unroll 1
                        for (int r = 0; r < (ph2 == NWS - 1 ? 3 : 7); r++)
                            asm volatile("cp.async.bulk.prefetch.L2.global [%0], 2688;\n" :: "l"(xp + r * (IMG * 384)) : "memory");
                    }
                } else if (PFM == 1 ? ((k ^ half) & 1) : PFM == 4 ? half == 1 : PFM == 5 ? 1 : half == 0) {
                    if (pr2 < NWS) {
#pragma unroll
                        for (int ch = 0; ch < (PF1 ? 1 : 3); ch++)
                            if (CH & 8)
                            asm volatile("cp.async.bulk.prefetch.tensor.3d.L2.global.tile.L2::cache_hint [%0, {%1, %2, %3}], %4;\n"
                                         :: "l"(reinterpret_cast<uint64_t>(&xmap)), "r"(ch * 64), "r"(7 * pw2 + 3), "r"(7 * ph2 + 3), "l"(EVICT_FIRST)
                                         : "memory");
                            else
                            asm volatile("cp.async.bulk.prefetch.tensor.3d.L2.global.tile [%0, {%1, %2, %3}];\n"
                                         :: "l"(reinterpret_cast<uint64_t>(&xmap)), "r"(ch * 64), "r"(7 * pw2 + 3), "r"(7 * ph2 + 3)
                                         : "memory");
                    }
                }
                wq += wstep; if (wq >= NWS) { wq -= NWS; wr++; }
                pq2 += wstep; if (pq2 >= NWS) { pq2 -= NWS; pr2++; }
            }
            mbar_wait(bars + B_VRAW + ((ntiles - 1) & 3) * 8, ((ntiles - 1) >> 2) & 1);
          }
            PROJ_SCHEDULE
            int st = 0, ready = -1;
            uint32_t ph = 1;
#pragma unroll 1
            for (int t = tile0; t < tend; t += tstep) {
                const int p0 = (t < TILES_A) ? SEG_B + 64 * t : 64 * (t - TILES_A);
                const int w1 = (t < TILES_A) ? 0 : min((p0 + 63 + 4 * IMG) / (7 * IMG), NWS - 1);
                if (bid < 2 * (PQ(npair) + PQ(nh)) && t == tile0 + tstep) {
                    mbar_wait(sbase + SM_PBAR + 96, 0);
                    fence_async_smem();
                }
                if (ready < w1) {
                    ready = max(ready, w1 - 2);
#pragma unroll 1
                    while (ready < w1) {
                        ready++;
#pragma unroll 1
                        for (uint32_t n = 0; n < (1u << 22); n++) {
                            uint32_t a;
                            asm volatile("ld.acquire.gpu.global.u32 %0, [%1];\n" : "=r"(a) : "l"(g_cnt + ready) : "memory");
                            if (a >= PQ(need)) break;
                            __nanosleep(64);
                        }
                    }
                    asm volatile("fence.proxy.async.global;\n" ::: "memory");
                }
                TRH(9, (t - tile0) / tstep);
                mbar_wait_s<(HS & 4) != 0>(sbase + SM_PBAR + 48 + st * 8, ph);
                TRH(5, (t - tile0) / tstep);
                if (PEXP & 2) mbar_arrive(sbase + SM_PBAR + st * 8); else {
                mbar_arrive_expect_tx(sbase + SM_PBAR + st * 8, STAGE_BYTES);
#pragma unroll
                for (int ch = 0; ch < 3; ch++)
                    tma_2d(sbase + SM_STAGE + st * STAGE_BYTES + ch * 8192, &omap, sbase + SM_PBAR + st * 8, ch * 64, (PEXP & 4) ? p0 & 8191 : p0);
                }
                if (++st == 6) { st = 0; ph ^= 1; }
            }
            finish(nfinish);
        } else if (!attn) {
        } else if (warp == 1) {
          {
            if (PQ(t1) < TILES) {
#pragma unroll 1
                for (uint32_t n = 0; n < (1u << 22); n++) {
                    uint32_t a;
                    asm volatile("ld.acquire.gpu.global.u32 %0, [%1];\n" : "=r"(a) : "l"(g_cnt + NWS) : "memory");
                    if (a) break;
                    __nanosleep(64);
                }
                asm volatile("fence.proxy.async.global;\n" ::: "memory");
                if (blockIdx.x % 6 == 0)
                    asm volatile("cp.async.bulk.prefetch.L2.global [%0], 4096;\n" :: "l"(g_wo + blockIdx.x / 6 % 18 * 4096) : "memory");
                if (NB & 4) mbar_wait(bars + B_QKRAW, 0);
                else mbar_wait(bars + B_QKRAW + ((ntiles - 1) & 3) * 8, ((ntiles - 1) >> 2) & 1);
                mbar_arrive_expect_tx(bars + B_WRAW, 73728);
#pragma unroll
                for (int i = 0; i < 4; i++) {
                    const uint32_t o = ((i + pair) & 3) * 18432;
                    asm volatile("cp.async.bulk.shared::cluster.global.mbarrier::complete_tx::bytes [%0], [%1], 18432, [%2];\n"
                                 :: "r"(sbase + SM_WO + o), "l"(g_wo + o), "r"(bars + B_WRAW) : "memory");
                }
            }
            finish(nfinish);
          }
        } else if (warp == 2) {
            int wh = wr0, ww = wq0, nb = wr0 + 1, k = 0;
#pragma unroll 1
            for (int j = 0; k < nwin; j++) {
                mbar_wait_s<HS & 1>(bars + B_STORED + (j & 1) * 8, (j >> 1) & 1);
                mbar_arrive(bars + B_PUBD + (j & 1) * 8);
                if (PUBM != 1) asm volatile("fence.release.gpu;\n" ::: "memory");
#pragma unroll 1
                for (; wh < nb && k < nwin; k++) {
                    asm volatile("red.relaxed.gpu.global.add.u32 [%0], 1;\n" :: "l"(g_cnt + wh) : "memory");
                    ww += wstep; if (ww >= NWS) { ww -= NWS; wh++; }
                }
                nb = wh >= PBE ? wh + 1 : (wh | 1) + 1;
            }
            TC(7);
            finish(nfinish);
        } else {
            for (int t = 0; t < 2; t++) mbar_arrive_n(bars + B_VFREE + t * 8, M01 == 2 ? 2 - t : 2);
            int wr = wr0, wq = wq0, nb = wr0 + 1, j = 0;
#pragma unroll 1
            for (int k = 0; k < nwin; k++) {
                const uint32_t src = sbase + SM_V + (k & 3) * V_STRIDE;
                const int wh = unrot(wr), ww = unrot(wq);
                const int x0 = 7 * ww + 3, y0 = 7 * wh + 3;
                if (NB & 2) nb_sync<160>(NB_ODONE + (k & 3));
                else mbar_wait_s<(HS & 2) != 0>(bars + B_ODONE + (k & 3) * 8, (k >> 2) & 1);
                fence_async_smem();
                TR(22, k);
                const int x1 = ww == NWS - 1 ? 0 : x0 + 4;
                if (!(XP & 2)) tma_store_4d(&M.s47, src, 0, half, x0, y0);
                if (!(XP & 2)) tma_store_4d(&M.s37, src + 28 * O_PITCH, 0, half, x1, y0);
                if (wh == NWS - 1) {
                    tma_store_4d(&M.s43, src + 16 * O_PITCH, 0, half, x0, 0);
                    tma_store_4d(&M.s33, src + 40 * O_PITCH, 0, half, x1, 0);
                }
                asm volatile("cp.async.bulk.commit_group;\n" ::: "memory");
                asm volatile("cp.async.bulk.wait_group.read 0;\n" ::: "memory");
                {
                    const int row0 = (k + 4) * TOK;
                    mbar_arrive_n(bars + B_VFREE + ((row0 >> 6) & 3) * 8, ((row0 & 63) >= 64 - TOK && (row0 & 63) < TOK) ? 2 : 1);
                }
                TR(23, k);
                if (k == nwin - 1) mbar_arrive(sbase + SM_PBAR + 96);
                wq += wstep; if (wq >= NWS) { wq -= NWS; wr++; }
                if (wr >= nb || k == nwin - 1) {
                    nb = wr >= PBE ? wr + 1 : (wr | 1) + 1;
                    asm volatile("cp.async.bulk.wait_group 0;\n" ::: "memory");
                    if (WFEN) asm volatile("fence.proxy.async.global;\n" ::: "memory");
                    mbar_wait(bars + B_PUBD + (j & 1) * 8, ((j >> 1) + 1) & 1);
                    mbar_arrive(bars + B_STORED + (j & 1) * 8);
                    j++;
                }
            }
        }
        if (PSTORE && warp == 1) {
            PROJ_SCHEDULE
            int st = 0, prev = -1;
            uint32_t ph = 0;
#pragma unroll 1
            for (int t = tile0; t < tend; t += tstep) {
                const int p0 = (t < TILES_A) ? SEG_B + 64 * t : 64 * (t - TILES_A);
                mbar_wait_s<(HS & 4) != 0>(sbase + SM_PBAR + 104 + st * 8, ph);
                fence_async_smem();
#pragma unroll
                for (int ch = 0; ch < ((PEXP & 1) ? 0 : 3); ch++)
                    if (CH & 1)
                    asm volatile("cp.async.bulk.tensor.2d.global.shared::cta.tile.bulk_group.L2::cache_hint [%0, {%2, %3}], [%1], %4;\n"
                                 :: "l"(reinterpret_cast<uint64_t>(t < TILES_A ? &omap : &omapb)),
                                    "r"(sbase + SM_STAGE + st * STAGE_BYTES + ch * 8192), "r"(ch * 64), "r"(p0), "l"(EVICT_FIRST) : "memory");
                    else
                    asm volatile("cp.async.bulk.tensor.2d.global.shared::cta.tile.bulk_group [%0, {%2, %3}], [%1];\n"
                                 :: "l"(reinterpret_cast<uint64_t>(t < TILES_A ? &omap : &omapb)),
                                    "r"(sbase + SM_STAGE + st * STAGE_BYTES + ch * 8192), "r"(ch * 64), "r"((PEXP & 8) ? (p0 & 8191) + 16384 : p0) : "memory");
                asm volatile("cp.async.bulk.commit_group;\n" ::: "memory");
                TRH(6, (t - tile0) / tstep);
                if (prev >= 0) {
                    asm volatile("cp.async.bulk.wait_group.read 1;\n" ::: "memory");
                    mbar_arrive(sbase + SM_PBAR + 48 + prev * 8);
                    TRH(21, (t - tile0) / tstep - 1);
                }
                prev = st;
                if (++st == 6) { st = 0; ph ^= 1; }
            }
            if (ENDR) asm volatile("cp.async.bulk.wait_group.read 0;\n" ::: "memory");
            else asm volatile("cp.async.bulk.wait_group 0;\n" ::: "memory");
            TR(30, 0);
            TC(1);
        }
        return;
    }
    auto permute = [&](int i0, int i1) {
            uint32_t src[3][4], dst[3];
#pragma unroll
            for (int it = 0; it < 3; it++) {
                const int o = warp * 12 + it * 4 + (lane >> 3), r = (o / 6) * 8 + (lane & 7), u = o % 6;
#pragma unroll
                for (int h = 0; h < (GORD == 2 ? 0 : 2); h++) {
                    const int v = u + 6 * h + 4 * half;
                    const bool wide = v >> 3 == half;
                    src[it][h] = wide ? r * 128 + (((v ^ r) & 7) << 4) : 16384 + r * 64 + (((v ^ (r >> 1)) & 3) << 4);
                    src[it][2 + h] = src[it][h] + (wide ? 8192 : 4096);
                }
                dst[it] = sbase + u * 4096 + r * 32 + ((lane >> 2) & 1) * 16;
            }
            TP(16);
#pragma unroll 1
            for (int i = i0; i < i1; i++) {
                uint4 w[3][4];
                mbar_wait(bars + B_WRAW + 16 - 8 * i, 0);
                TP(20 + i);
#pragma unroll
                for (int it = 0; it < 3; it++)
#pragma unroll
                    for (int m = 0; m < 4; m++) w[it][m] = *reinterpret_cast<const uint4*>(smem + src[it][m] + i * 24576);
                wg_bar(PPAR ? 12 + wg : 7);
#pragma unroll
                for (int it = 0; it < 3; it++) {
                    const uint32_t d = dst[it] + i * 24576;
                    sts128(d, w[it][0].x, w[it][1].x, w[it][2].x, w[it][3].x);
                    sts128(d ^ 16, w[it][0].y, w[it][1].y, w[it][2].y, w[it][3].y);
                    sts128(d + 2048, w[it][0].z, w[it][1].z, w[it][2].z, w[it][3].z);
                    sts128((d ^ 16) + 2048, w[it][0].w, w[it][1].w, w[it][2].w, w[it][3].w);
                }
            }
        };
    if (PPAR && attn) {
        permute(wg, wg + 1);
        if (wg) nb_arrive<384>(15);
    }
    if (!attn) {
        asm volatile("setmaxnreg.inc.sync.aligned.u32 160;\n");
    } else if (wg == 0) {
        if (!PPAR) permute(0, 3);
        asm volatile("setmaxnreg.inc.sync.aligned.u32 %0;\n" :: "n"(REG_G));
        float qs = 1.f;
        if (GORD == 2 || c < 2) qs = round_bf16(expf(round_bf16(fminf(fmaxf(bf16lo(ls), -100.f), 4.6052f)))) * LOG2E;
        uint32_t xa[12][4];
        float accA[48], accB[48], accV[48];
        uint32_t rho = warp * 16 + (lane & 15), rq = warp * 16 + g;
        uint32_t hi = lane >> 4, lane0 = lane == 0, c2 = 2 * c;
        asm volatile("" : "+r"(hi), "+r"(lane0), "+r"(c2));
        auto row_addr = [&](uint32_t (&ax)[4], uint32_t r) {
            ax[0] = sbase + SM_QK + r * 128 + (((r & 7) ^ hi) << 4);
#pragma unroll
            for (int i = 1; i < 4; i++) ax[i] = ax[0] ^ (32 * i);
        };
#define XADDR(ax, s) ((ax)[((s) & 3) ^ (((s) >> 1) & 2)] + ((s) >> 2) * QK_CHUNK)
        uint64_t descW = make_desc(sbase, 2048, 256, 3);
        const uint32_t zero = (uint32_t)P.z1;
        const uint32_t vbase = sbase + SM_V + (lane >> 4) * GRP;
        const uint32_t ones = 0x3F803F80u, ones2 = ones;
        TP(10);
        {
            uint32_t ax[4];
            row_addr(ax, rho);
            mbar_wait(bars + B_XFULL, 0);
#pragma unroll
            for (int s = 0; s < 12; s++) ldsm_x4(xa[s], XADDR(ax, s));
        }
        TP(8);
        if (PPAR) nb_sync<384>(15); else wg_bar(7);
        fence_async_smem();
        TP(9);
        wgmma_fence();
        mma_qkv_a<SM_WA, 0>(accA, xa, descW);
        mma_qkv_b<SM_WA, KLO>(accA, xa, descW);
        wgmma_commit();
        mma_qkv_a<SM_WB, 0>(accB, xa, descW);
        wgmma_commit();
        TP(11);
        mbar_wait(bars + B_WFULL, 0);
        TP(12);
        if (tid == 0) TC(3);
        const int nt = (int)blockIdx.x < 2 * PQ(npair) ? ((int)blockIdx.x < PQ(nr2) ? PQ(nt1) : PQ(nt0)) : ((int)blockIdx.x < PQ(hr2) ? PQ(ht1) : PQ(ht0));
        for (int t = 0; t < nt; t++) {
            descW += P.z1;
            float ss[4];
            uint32_t pk[2][24];
            wgmma_wait<1>();
            reg_fence(accA);
            TR(0, t);
            TA(1, 0);
            if (t < 12 && (t < 4 || (t & 1))) TP(t < 4 ? 32 + t : 34 + (t >> 1));
#pragma unroll
            for (int i = 0; i < 4; i++) ss[i] = accA[i] * accA[i];
#pragma unroll
            for (int i = 4; i < 48; i++) ss[i & 3] = fmaf(accA[i], accA[i], ss[i & 3]);
            mma_qkv_b<SM_WB, KLO>(accB, xa, descW);
            wgmma_commit();
            TA(1, 1);
            sched_fence(zero, __float_as_uint(ss[0]), __float_as_uint(ss[1]), __float_as_uint(ss[2]), __float_as_uint(ss[3]));
#pragma unroll
            for (int j = 0; j < 12; j++) {
                pk[0][j] = pack_bf16(accA[4 * j], accA[4 * j + 1]);
                pk[1][j] = pack_bf16(accA[4 * j + 2], accA[4 * j + 3]);
                asm volatile("" : "+r"(pk[0][j]), "+r"(pk[1][j]));
            }
            wgmma_fence();
            if (V64) mma_w_a<0, 0>(accV, xa, descW + D_WV64); else mma_v_a<D_WV, 0>(accV, xa, descW);
            wgmma_commit();
            TA(1, 2);
            uint32_t av = vbase + rho * 16 + ((rho * 1338) >> 16) * (V_STRIDE - GRP);
            uint32_t aq[2];
            aq[0] = sbase + SM_QK + rq * 128 + (((rq & 7) ^ c2) << 4);
            aq[1] = aq[0] + 1024;
            if (rq >= 4 * TOK - 8) aq[1] = (aq[1] - QK_CHUNK) ^ 64;
            rho += 64;
            if (rho >= 4 * TOK) rho -= 4 * TOK;
            rq += 64;
            if (rq >= 4 * TOK) rq -= 4 * TOK;
            uint32_t an[4];
            row_addr(an, rho);
            const uint32_t bt = bars + (t & 3) * 8, pt = (t >> 2) & 1, bn = bars + ((t + 1) & 3) * 8, pn = ((t + 1) >> 2) & 1;
            const uint32_t xok = mbar_test(bn + B_XFULL, pn) & mbar_test(bt + B_VFREE, pt);
            wgmma_wait<1>();
            reg_fence(accB);
            TA(1, 3);
#pragma unroll
            for (int i = 0; i < 48; i++) ss[i & 3] = fmaf(accB[i], accB[i], ss[i & 3]);
            ss[0] += ss[1]; ss[2] += ss[3];
            if (V64) mma_w_b<0, KLO>(accV, xa, descW + D_WV64); else mma_v_b<D_WV, KLO>(accV, xa, descW);
            wgmma_commit();
            TA(1, 4);
            sched_fence(zero, __float_as_uint(ss[0]), __float_as_uint(ss[2]), av, aq[0], aq[1], an[0], an[1], an[2], an[3], rho, rq);
            const float f0 = rsqrt_ftz(ss[0] + 1e-12f) * qs, f1 = rsqrt_ftz(ss[2] + 1e-12f) * qs;
            const uint32_t f2[2] = {pack_bf16(f0, f0), pack_bf16(f1, f1)};
#pragma unroll
            for (int j = 0; j < 12; j++) {
                pk[0][12 + j] = (FM & 1) ? pack_bf16(accB[4 * j] * f0, accB[4 * j + 1] * f0) : pack_bf16(accB[4 * j], accB[4 * j + 1]);
                pk[1][12 + j] = (FM & 1) ? pack_bf16(accB[4 * j + 2] * f1, accB[4 * j + 3] * f1) : pack_bf16(accB[4 * j + 2], accB[4 * j + 3]);
            }
            auto qk_store = [&](int u0, int u1) {
#pragma unroll
                for (int u = u0; u < u1; u++)
#pragma unroll
                    for (int r = 0; r < 2; r++)
                        if ((FM & 1) && u >= 3)
                        sts128((aq[r] ^ ((u & 1) * 16 + (u & 2) * 32)) + (u >> 1) * QK_CHUNK, pk[r][4 * u], pk[r][4 * u + 1], pk[r][4 * u + 2], pk[r][4 * u + 3]);
                        else
                        sts128((aq[r] ^ ((u & 1) * 16 + (u & 2) * 32)) + (u >> 1) * QK_CHUNK,
                               hmul2_bf16(pk[r][4 * u], f2[r]), hmul2_bf16(pk[r][4 * u + 1], f2[r]),
                               hmul2_bf16(pk[r][4 * u + 2], f2[r]), hmul2_bf16(pk[r][4 * u + 3], f2[r]));
            };
            qk_store(0, QSPLIT);
            if (EARLYQ) {
                __syncwarp();
                mbar_arrive_if(bt + B_QKRAW, lane0);
            }
            TR(1, t);
            TA(1, 5);
            mbar_wait2_unless(xok, bn + B_XFULL, pn, bt + B_VFREE, pt);
            TR(2, t);
            wgmma_wait<1>();
            TA(1, 6);
#pragma unroll
            for (int s = 0; s < KLO; s++) ldsm_x4(xa[s], XADDR(an, s));
            qk_store(QSPLIT, 6 - QPOST);
            if (QPOST) {
                wgmma_fence();
                mma_qkv_a<SM_WA, 0>(accA, xa, descW);
                wgmma_commit();
                qk_store(6 - QPOST, 6);
            }
            if (!EARLYQ) {
                __syncwarp();
                mbar_arrive_if(bt + B_QKRAW, lane0);
            }
            TR(3, t);
            TA(1, 7);
            if (!QPOST) {
                wgmma_fence();
                mma_qkv_a<SM_WA, 0>(accA, xa, descW);
                wgmma_commit();
            }
            TA(1, 8);
            wgmma_wait<1>();
            reg_fence(accV);
            TA(1, 9);
#pragma unroll
            for (int s = KLO; s < 12; s++) ldsm_x4(xa[s], XADDR(an, s));
            uint32_t vp[24];
#pragma unroll
            for (int j = 0; j < 24; j++) vp[j] = pack_bf16(accV[2 * j], accV[2 * j + 1]);
            reg_fence(vp);
            wgmma_fence();
            mma_qkv_b<SM_WA, KLO>(accA, xa, descW);
            wgmma_commit();
            TA(1, 10);
#pragma unroll
            for (int p = 0; p < 6; p++)
                stsm_x4(av + (p < 3 ? 2 * p : 2 * p + 1) * GRP, vp[4 * p], vp[4 * p + 1], vp[4 * p + 2], vp[4 * p + 3]);
            stsm_x2(av + 6 * GRP, ones, ones2);
            __syncwarp();
            mbar_arrive_if(bt + B_VRAW, lane0);
            TR(4, t);
            if (!MERGEW) wgmma_fence();
            mma_qkv_a<SM_WB, 0>(accB, xa, descW);
            wgmma_commit();
            TA(1, 11);
        }
        TAEND(1);
        wgmma_wait<0>();
        reg_fence(accA);
        reg_fence(accB);
        asm volatile("setmaxnreg.dec.sync.aligned.u32 160;\n");
    } else {
        if (REG_A > 128) asm volatile("setmaxnreg.inc.sync.aligned.u32 %0;\n" :: "n"(REG_A));
        {
            const float c0 = bf16lo(rc), c1 = bf16hi(rc);
            float a0 = 0.f, a1 = 0.f;
#pragma unroll
            for (int u = 0; u < 16; u += 2) {
                const uint32_t p = reinterpret_cast<const uint32_t*>(w1)[u >> 1], q = reinterpret_cast<const uint32_t*>(w1)[8 + (u >> 1)];
                uint32_t h;
                asm("cvt.rn.relu.bf16x2.f32 %0, %1, %2;\n" : "=r"(h) : "f"(c0 * bf16hi(p) + c1 * bf16hi(q)), "f"(c0 * bf16lo(p) + c1 * bf16lo(q)));
                a0 += bf16lo(h) * bf16lo(w2[u]);
                a1 += bf16lo(h) * bf16hi(w2[u]);
                a0 += bf16hi(h) * bf16lo(w2[u + 1]);
                a1 += bf16hi(h) * bf16hi(w2[u + 1]);
            }
            const float s0 = round_bf16(__fdividef(1.f, 1.f + expf(-round_bf16(a0))));
            const float s1 = round_bf16(__fdividef(1.f, 1.f + expf(-round_bf16(a1))));
            if (tid - 128 < 169) sts32(sbase + SM_TAB + (tid - 128) * 4, pack_bf16(exp2f(fmaf(s0, 16.f * LOG2E, -12.f)), exp2f(fmaf(s1, 16.f * LOG2E, -12.f))));
        }
        asm volatile("bar.sync 1, 256;\n" ::: "memory");
        uint32_t eb[26];
        {
            const uint32_t* tab = reinterpret_cast<const uint32_t*>(smem + SM_TAB);
#pragma unroll
            for (int i = 0; i < 13; i++) {
                const uint32_t lo = tab[min(ridx[i < 12 ? 13 * (i & 1) + (i & ~1) : 12], 168u)];
                const uint32_t hi = tab[min(ridx[i < 12 ? 13 * (i & 1) + (i | 1) : 25], 168u)];
                eb[i]      = prmt(lo, hi, 0x5410);
                eb[13 + i] = prmt(lo, hi, 0x7632);
            }
            if (c != 0) eb[12] = eb[25] = 0;
            if (EBZ) {
                const uint32_t k0 = warp * 16 + g < TOK ? ~0u : 0u, k1 = warp < 3 ? ~0u : 0u;
#pragma unroll
                for (int i = 0; i < 26; i++) eb[i] &= i % 13 == 12 ? (k0 & 0xFFFFu) | (k1 & 0xFFFF0000u) : ((i % 13) & 1) ? k1 : k0;
            }
        }
        uint32_t slow = (bf16lo(ls) <= LS_FAST ? 0 : 1) | (bf16hi(ls) <= LS_FAST ? 0 : 2);
        reg_fence(eb);
        if (SLOWH == 2) sts32(bars + B_PROG + 4, slow);
        wg_bar(3 + wg);
        if ((tid & 127) == 0) mbar_arrive(bars + B_VFREE + 16);
        const uint32_t ov0 = warp * 16 + g < TOK, ov1 = warp < 3;
        const uint64_t descK0 = make_desc(sbase + SM_QK, 16, 1024, 1);
        const uint64_t descV0 = make_desc(sbase + SM_V, 128, GRP, 0);
        slow = __shfl_sync(0xffffffffu, slow, 0);
        const uint32_t barw = bars + (wg - 1) * 8;
        const uint64_t descKw = descK0 + (uint64_t)((wg - 1) * (XCH >> 4)), descVw = descV0 + (uint64_t)((wg - 1) * (V_STRIDE >> 4));
        const uint32_t oa = sbase + SM_V + (wg - 1) * V_STRIDE + (warp * 16 + g) * O_PITCH + c * 48;
        uint32_t qok = 0;
        const uint32_t zero = (uint32_t)P.z1;
        auto window = [&](auto IT_, int k) {
            constexpr int IT = decltype(IT_)::value;
            const uint32_t bar = barw + 16 * IT;
            const int tl = (k * TOK + TOK - 1) >> 6, tn = ((k + 2) * TOK + TOK - 1) >> 6;
            const uint32_t bt = bars + (tl & 3) * 8, pt = (tl >> 2) & 1;
            TR(8, k);
            if (k < 2) TP(44 + k);
            float sc0[28], sc1[28];
            TR(10, k);
            TA(2, 0);
            if (NB & 4) nb_sync<256>(NB_QKRAW + 2 * IT - 1 + wg);
            else mbar_wait_unless(qok, bt + B_QKRAW, pt);
            fence_async_smem();
            TR(11, k);
            TA(2, 1);
            if (k == 0) TP(17);
            wgmma_fence();
            mma_qk0<2 * IT * XCH, 2 * IT * XCH>(sc0, descKw, descKw);
            mma_qk1<2 * IT * XCH, 2 * IT * XCH>(sc1, descKw, descKw);
            wgmma_commit();
            TA(2, 2);
            const uint32_t vok = mbar_test(bt + B_VRAW, pt);
            uint32_t mflag = 1;
            if (!(XP & 1)) asm volatile("ld.volatile.shared.u8 %0, [%1];\n" : "=r"(mflag) : "r"(sbase + SM_FLAG + k) : "memory");
            wgmma_wait<0>();
            reg_fence(sc0);
            reg_fence(sc1);
            if (NB & 1) nb_arrive<160>(NB_QKFREE - 1 + wg);
            else if (lane == 0) mbar_arrive(bar + B_QKFREE);
            TR(12, k);
            TA(2, 3);
            if (k == 0) TP(18);
            if (mflag != 1) {
              asm volatile(
                "{\n.reg .pred p;\n.reg .u32 n;\nmov.u32 n, 0;\n"
                "WAIT_%=:\n"
                "ld.volatile.shared.u8 %0, [%1];\n"
                "setp.ne.u32 p, %0, 0;\n"
                "@p bra DONE_%=;\n"
                "add.u32 n, n, 1;\n"
                "setp.lt.u32 p, n, 16777216;\n"
                "@p bra WAIT_%=;\n"
                "trap;\n"
                "DONE_%=:\n}\n" : "=r"(mflag) : "r"(sbase + SM_FLAG + k) : "memory");
              if (mflag == 2) {
                uint32_t mk[13];
                __threadfence_block();
                uint32_t u = threadIdx.x, bid = blockIdx.x;
                asm volatile("" : "+r"(u), "+r"(bid));
                const uint32_t r0 = ((u >> 1) & 48) + ((u >> 2) & 7);
                const int pr = bid >> 1, wi = pr < PQ(npair) ? PQ(hw) + pr + k * PQ(npair) : pr - PQ(npair) + k * PQ(nh), wr = wi / NWS;
                const uint32_t mp = sbase + SM_MASK + (((unrot(wr) * NWS + unrot(wi - wr * NWS)) * 2) & 15);
                const uint32_t mr[2] = {mp + row_token(min(r0, TOK - 1u)) * (2 * TOK), mp + row_token(min(r0 + 8, TOK - 1u)) * (2 * TOK)};
                const uint32_t c0 = 2 * row_token(2 * (u & 3));
#pragma unroll
                for (int i = 0; i < 13; i++) {
                    const uint32_t a0 = i < 6 ? mr[i & 1] + c0 + 28 * (i >> 1) : i < 12 ? mr[i & 1] + 2 * row_token(2 * (u & 3) + 8 * (i >> 1)) : mr[0] + 2 * TOK - 2;
                    const uint32_t a1 = i < 6 ? a0 + 2 : i < 12 ? mr[i & 1] + 2 * row_token(2 * (u & 3) + 8 * (i >> 1) + 1) : mr[1] + 2 * TOK - 2;
                    uint32_t lo, hi;
                    asm volatile("ld.shared.u16 %0, [%1];\n" : "=r"(lo) : "r"(a0) : "memory");
                    asm volatile("ld.shared.u16 %0, [%1];\n" : "=r"(hi) : "r"(a1) : "memory");
                    mk[i] = prmt(lo, hi, 0x5410);
                }
                reg_fence(mk);
                __syncwarp();
                if (lane == 0) mbar_arrive(bars + B_MCONS);
                uint32_t m0 = mk[0], m1 = mk[1];
#pragma unroll
                for (int i = 2; i < 12; i += 2) { m0 = hmax2_bf16(m0, mk[i]); m1 = hmax2_bf16(m1, mk[i + 1]); }
                m0 = hmax2_bf16(hmax2_bf16(prmt(m0, m1, 0x5410), prmt(m0, m1, 0x7632)), mk[12]);
                m0 = hmax2_bf16(m0, __shfl_xor_sync(0xffffffffu, m0, 1));
                m0 = hmax2_bf16(m0, __shfl_xor_sync(0xffffffffu, m0, 2));
                const float m[2] = {bf16lo(m0), bf16hi(m0)};
#pragma unroll
                for (int i = 0; i < 13; i++) {
                    const float lo = bf16lo(mk[i]) - m[i & 1], hi = bf16hi(mk[i]) - m[i < 12 ? i & 1 : 1];
                    const int j = i < 12 ? 2 * i + 1 : 26;
                    sc0[2 * i] = fmaf(lo, LOG2E, sc0[2 * i]); sc0[j] = fmaf(hi, LOG2E, sc0[j]);
                    sc1[2 * i] = fmaf(lo, LOG2E, sc1[2 * i]); sc1[j] = fmaf(hi, LOG2E, sc1[j]);
                }
              }
            }
            if (slow) {
                auto shift = [&](float (&S)[28], int h) {
                    float m[2];
#pragma unroll
                    for (int i = 12; i >= 0; i--) {
                        uint32_t e = eb[13 * h + i];
                        asm volatile("" : "+r"(e));
                        const float a = S[2 * i] + lg2_ftz(bf16lo(e)), b = S[i < 12 ? 2 * i + 1 : 26] + lg2_ftz(bf16hi(e));
                        if (i == 12) { m[0] = a; m[1] = b; }
                        else m[i & 1] = fmaxf(m[i & 1], fmaxf(a, b));
                    }
#pragma unroll
                    for (int r = 0; r < 2; r++) {
                        m[r] = fmaxf(m[r], __shfl_xor_sync(0xffffffffu, m[r], 1));
                        m[r] = fmaxf(m[r], __shfl_xor_sync(0xffffffffu, m[r], 2));
                    }
#pragma unroll
                    for (int i = 0; i < 27; i++) S[i] -= m[(i >> 1) & 1];
                };
                uint32_t sl = slow;
                if (SLOWH == 2) asm volatile("ld.volatile.shared.u32 %0, [%1];\n" : "=r"(sl) : "r"(bars + B_PROG + 4) : "memory");
                if (!SLOWH || (sl & 1)) shift(sc0, 0);
                if (!SLOWH || (sl & 2)) shift(sc1, 1);
            }
            auto exps = [&](const float (&S)[28], uint32_t (&e)[13]) {
#pragma unroll
                for (int i = 0; i < 12; i++) e[i] = pack_bf16(ex2_ftz(S[2 * i]), ex2_ftz(S[2 * i + 1]));
                e[12] = hmin2_bf16(pack_bf16(ex2_ftz(S[24]), ex2_ftz(S[26])), 0x7F7F7F7Fu);
            };
            auto probs = [&](const uint32_t (&e)[13], int h, uint32_t (&pa)[4][4]) {
#pragma unroll
                for (int i = 0; i < 12; i++) pa[i >> 2][i & 3] = hmul2_bf16(e[i], eb[13 * h + i]);
                const uint32_t l = hmul2_bf16(e[12], eb[13 * h + 12]);
                pa[3][0] = l & 0xFFFFu;
                pa[3][1] = l >> 16;
                pa[3][2] = 0u; pa[3][3] = 0u;
                reg_fence(pa);
            };
            uint32_t pa0[4][4], pa1[4][4], e[13];
            float o0[28], o1[28];
            TR(13, k);
            TA(2, 10);
            if (k == 0) TP(23);
            exps(sc0, e);
            probs(e, 0, pa0);
            TA(2, 4);
            mbar_wait_unless(vok, bt + B_VRAW, pt);
            fence_async_smem();
            TR(14, k);
            TA(2, 5);
            wgmma_fence();
            mma_pv<2 * IT * V_STRIDE, 0>(o0, pa0, descVw);
            wgmma_commit();
            exps(sc1, e);
            reg_fence(e);
            TA(2, 6);
            wgmma_wait<0>();
            reg_fence(o0);
            TA(2, 7);
            sched_fence_rw(zero, e);
            probs(e, 1, pa1);
            wgmma_fence();
            mma_pv<2 * IT * V_STRIDE + 6 * GRP, 0>(o1, pa1, descVw);
            wgmma_commit();
            uint32_t w[24];
            {
                const float il0 = rcp_ftz(o0[24]), il1 = rcp_ftz(o0[26]);
                const uint32_t l0 = pack_bf16(il0, il0), l1 = pack_bf16(il1, il1);
#pragma unroll
                for (int j = 0; j < 12; j++) w[j] = (FM & 2) ? pack_bf16(o0[2 * j] * ((j & 1) ? il1 : il0), o0[2 * j + 1] * ((j & 1) ? il1 : il0)) : hmul2_bf16(pack_bf16(o0[2 * j], o0[2 * j + 1]), (j & 1) ? l1 : l0);
            }
            TA(2, 8);
            wgmma_wait<0>();
            reg_fence(o1);
            TA(2, 9);
            TR(15, k);
            if (k == 0) TP(25);
            wg_bar(3 + wg);
            if (!(NB & 4)) qok = mbar_test(bars + (tn & 3) * 8 + B_QKRAW, (tn >> 2) & 1);
            {
                const float il2 = rcp_ftz(o1[0]), il3 = rcp_ftz(o1[2]);
                const uint32_t l2 = pack_bf16(il2, il2), l3 = pack_bf16(il3, il3);
#pragma unroll
                for (int j = 0; j < 12; j++) w[12 + j] = (FM & 4) ? pack_bf16(o1[2 * j + 4] * ((j & 1) ? il3 : il2), o1[2 * j + 5] * ((j & 1) ? il3 : il2)) : hmul2_bf16(pack_bf16(o1[2 * j + 4], o1[2 * j + 5]), (j & 1) ? l3 : l2);
#pragma unroll
                for (int p = 0; p < 6; p++) {
                    const int j = 8 * (p >> 1) + (p & 1);
                    sts128_if((p & 1) ? ov1 : ov0, oa + 2 * IT * V_STRIDE + (p & 1) * 8 * O_PITCH + (p >> 1) * 16, w[j], w[j + 2], w[j + 4], w[j + 6]);
                }
            }
            if (NB & 2) nb_arrive<160>(NB_ODONE + 2 * IT - 1 + wg);
            else {
                __syncwarp();
                if (lane == 0) mbar_arrive(bar + B_ODONE);
            }
            TR(16, k);
            TA(2, 11);
            if (k < 2) TP(46 + k);
        };
        for (int k = wg - 1;; k += 4) {
            window(std::integral_constant<int, 0>(), k);
            if (k + 2 >= nwin) break;
            window(std::integral_constant<int, 1>(), k + 2);
            if (k + 4 >= nwin) break;
        }
        TAEND(2);
        (void)zero;
        asm volatile("setmaxnreg.inc.sync.aligned.u32 160;\n");
    }

    TR(27, wg);
    if ((tid & 127) == 0) TC(4 + wg);
    if (attn) {
        __syncwarp();
        if (lane == 0) mbar_arrive(sbase + SM_PBAR + 96);
    }
    if (!attn) {
#pragma unroll
        for (int row = tid >> 2; row < 192; row += 96) {
            uint4 w[6];
            const int pr = row % 96, srow = row - pr + (pr % 24) / 12 * 48 + (pr % 12) / 2 * 8 + pr / 24 * 2 + (pr & 1);
#pragma unroll
            for (int a = 0; a < 6; a++) w[a] = *reinterpret_cast<const uint4*>(P.wo + srow * 192 + 32 * a + 8 * c);
            float s = 0.f;
#pragma unroll
            for (int a = 0; a < 6; a++)
                s += ((bf16lo(w[a].x) + bf16hi(w[a].x)) + (bf16lo(w[a].y) + bf16hi(w[a].y))) +
                     ((bf16lo(w[a].z) + bf16hi(w[a].z)) + (bf16lo(w[a].w) + bf16hi(w[a].w)));
            s += __shfl_xor_sync(0xffffffffu, s, 1);
            s += __shfl_xor_sync(0xffffffffu, s, 2);
            s *= (1.f / 192.f);
            const uint32_t d = sbase + SM_WO + row * 64 + ((c ^ ((row >> 1) & 3)) << 4);
#pragma unroll
            for (int a = 0; a < 6; a++)
                sts128(d + a * 12288, pack_bf16(bf16lo(w[a].x) - s, bf16hi(w[a].x) - s), pack_bf16(bf16lo(w[a].y) - s, bf16hi(w[a].y) - s),
                       pack_bf16(bf16lo(w[a].z) - s, bf16hi(w[a].z) - s), pack_bf16(bf16lo(w[a].w) - s, bf16hi(w[a].w) - s));
        }
        fence_async_smem();
        asm volatile("bar.sync 6, 384;\n" ::: "memory");
        if (tid == 0 && (int)blockIdx.x == 2 * (PQ(npair) + PQ(nh))) {
            asm volatile("cp.async.bulk.global.shared::cta.bulk_group [%0], [%1], 73728;\n" :: "l"(g_wo), "r"(sbase + SM_WO) : "memory");
            asm volatile("cp.async.bulk.commit_group;\n" ::: "memory");
            asm volatile("cp.async.bulk.wait_group 0;\n" ::: "memory");
            asm volatile("fence.proxy.async.global;\n" ::: "memory");
            asm volatile("red.release.gpu.global.add.u32 [%0], 1;\n" :: "l"(g_cnt + NWS) : "memory");
        }
        __syncwarp();
    } else if (PQ(t1) < TILES) {
        mbar_wait(sbase + SM_BAR + B_WRAW, 1);
    }
    TR(27, 4 + wg);
    if (tid == 0) TC(2);
    {
        PROJ_SCHEDULE
        uint64_t descW = make_desc(sbase + SM_WO, 12288, 512, 2);
        const uint64_t descA = make_desc(sbase + SM_STAGE + wg * STAGE_BYTES, 16, 1024, 1);
        const uint32_t bar = sbase + SM_PBAR + wg * 8;
        const uint32_t yrel = sbase + SM_STAGE + wg * STAGE_BYTES + (warp * 16 + (lane & 15)) * 128 + (((lane & 7) ^ (lane >> 4)) << 4);
        float acc[96];
#pragma unroll
        for (int i = 0; i < 96; i++) acc[i] = 0.f;
        uint32_t it = 0;
        for (int tile = tile0 + wg * tstep; tile < tend; tile += 3 * tstep, it++) {
            descW += P.z1;
            mbar_wait_s<(HS & 8) != 0>(bar + (it & 1) * 24, (it >> 1) & 1);
            TR(28, it * 3 + wg);
            if (it > 0 || wg > 0) asm volatile("bar.sync %0, 256;\n" :: "r"(8 + wg) : "memory");
            wgmma_fence();
            mma_proj<0, 0>(acc, descA + (uint64_t)((it & 1) * (3 * STAGE_BYTES >> 4)), descW);
            wgmma_commit();
            if (tile + tstep < tend) asm volatile("bar.arrive %0, 256;\n" :: "r"(wg == 2 ? 8 : 9 + wg) : "memory");
            wgmma_wait<0>();
            reg_fence(acc);
            float a[4];
#pragma unroll
            for (int i = 0; i < 4; i++) a[i] = acc[i] * acc[i];
#pragma unroll
            for (int j = 1; j < 24; j++)
#pragma unroll
                for (int i = 0; i < 4; i++) a[i] = fmaf(acc[4 * j + i], acc[4 * j + i], a[i]);
            float s0 = a[0] + a[1], s1 = a[2] + a[3];
            s0 += __shfl_xor_sync(0xffffffffu, s0, 1);
            s1 += __shfl_xor_sync(0xffffffffu, s1, 1);
            s0 += __shfl_xor_sync(0xffffffffu, s0, 2);
            s1 += __shfl_xor_sync(0xffffffffu, s1, 2);
            const float rs0 = rsqrt_ftz(fmaf(s0, 1.f / 192.f, 1e-5f));
            const float rs1 = rsqrt_ftz(fmaf(s1, 1.f / 192.f, 1e-5f));
            const uint32_t ya = yrel + (it & 1) * 3 * STAGE_BYTES;
#pragma unroll
            for (int p = 0; p < 12; p++)
                stsm_x4((ya ^ (32 * (p & 3))) + (p >> 2) * 8192,
                        pack_bf16(acc[8 * p] * rs0, acc[8 * p + 1] * rs0), pack_bf16(acc[8 * p + 2] * rs1, acc[8 * p + 3] * rs1),
                        pack_bf16(acc[8 * p + 4] * rs0, acc[8 * p + 5] * rs0), pack_bf16(acc[8 * p + 6] * rs1, acc[8 * p + 7] * rs1));
            __syncwarp();
            if (lane == 0) mbar_arrive(bar + 104 + (it & 1) * 24);
            TR(29, it * 3 + wg);
        }
    }
}

}

typedef CUresult (*PFN_encodeTiled)(CUtensorMap*, CUtensorMapDataType, cuuint32_t, void*, const cuuint64_t*,
                                    const cuuint64_t*, const cuuint32_t*, const cuuint32_t*, CUtensorMapInterleave,
                                    CUtensorMapSwizzle, CUtensorMapL2promotion, CUtensorMapFloatOOBfill);

extern "C" void kernel_launch(void* const* d_in, const int* in_sizes, int n_in, void* d_out, int out_size) {
    swin::Params P;
    P.x           = (const __nv_bfloat16*)d_in[0];
    P.wqkv        = (const __nv_bfloat16*)d_in[1];
    P.wo          = (const __nv_bfloat16*)d_in[2];
    P.logit_scale = (const __nv_bfloat16*)d_in[3];
    P.cpb_w1      = (const __nv_bfloat16*)d_in[4];
    P.cpb_w2      = (const __nv_bfloat16*)d_in[5];
    P.rel_coords  = (const __nv_bfloat16*)d_in[6];
    P.rel_idx     = (const int*)d_in[7];
    P.mask        = (const __nv_bfloat16*)d_in[8];
    P.out         = (__nv_bfloat16*)d_out;
    P.z1 = 0;
    static PFN_encodeTiled encode = nullptr;
    if (!encode) {
        cudaFuncSetAttribute(swin::swin_window_attn_kernel, cudaFuncAttributeMaxDynamicSharedMemorySize, swin::SM_TOTAL);
        cudaDriverEntryPointQueryResult qr;
        cudaGetDriverEntryPoint("cuTensorMapEncodeTiled", (void**)&encode, cudaEnableDefault, &qr);
    }
    swin::Maps M;
    const cuuint32_t estr[4] = {1, 1, 1, 1};
    auto make = [&](CUtensorMap* m, const void* base, int rank, const cuuint64_t* gdim, const cuuint64_t* gstr,
                    const cuuint32_t* box, CUtensorMapSwizzle swz = CU_TENSOR_MAP_SWIZZLE_128B) {
        CUresult r = encode(m, CU_TENSOR_MAP_DATA_TYPE_BFLOAT16, rank, const_cast<void*>(base), gdim, gstr, box, estr,
               CU_TENSOR_MAP_INTERLEAVE_NONE, swz, CU_TENSOR_MAP_L2_PROMOTION_L2_128B,
               CU_TENSOR_MAP_FLOAT_OOB_FILL_NONE);
        (void)r;
    };
    {
        const cuuint64_t gdim[3] = {192, swin::IMG, swin::IMG}, gstr[2] = {384, swin::IMG * 384};
        const cuuint32_t box[7][3] = {{64, 7, 7}, {64, 4, 7}, {64, 3, 7}, {64, 4, 4}, {64, 4, 3}, {64, 3, 4}, {64, 3, 3}};
        for (int i = 0; i < 7; i++) make(&M.x77 + i, P.x, 3, gdim, gstr, box[i]);
        const cuuint32_t boxp[3] = {192, 7, 7};
        if (PF1) make(&M.x77, P.x, 3, gdim, gstr, boxp, CU_TENSOR_MAP_SWIZZLE_NONE);
    }
    {
        const cuuint64_t gdim[2] = {192, (cuuint64_t)swin::NPIX}, gstr[1] = {384};
        const cuuint32_t box64[2] = {64, 64};
        make(&M.o, d_out, 2, gdim, gstr, box64);
        const cuuint64_t gdimb[2] = {192, (cuuint64_t)swin::SEG_B};
        make(&M.ob, d_out, 2, gdimb, gstr, box64);
    }
    {
        const cuuint64_t gdim[3] = {V64 ? 32 : 16, 192, V64 ? 18 : 36}, gstr[2] = {1152, V64 ? 64 : 32};
        const cuuint32_t box[3] = {V64 ? 32 : 16, 192, V64 ? 3 : 6};
        make(&M.w, P.wqkv, 3, gdim, gstr, box, V64 ? CU_TENSOR_MAP_SWIZZLE_64B : CU_TENSOR_MAP_SWIZZLE_32B);
        const cuuint64_t gdim3[3] = {192, 192, 3}, gstr3[2] = {1152, 384};
        const cuuint32_t box64[3] = {64, 64, 2}, box32[3] = {32, 64, 2};
        make(&M.w64, P.wqkv, 3, gdim3, gstr3, box64);
        make(&M.w32, P.wqkv, 3, gdim3, gstr3, box32, CU_TENSOR_MAP_SWIZZLE_64B);
    }
    {
        const cuuint64_t gdim[4] = {96, 2, swin::IMG, swin::IMG}, gstr[3] = {192, 384, swin::IMG * 384};
        const cuuint32_t box[4][4] = {{96, 1, 4, 7}, {96, 1, 3, 7}, {96, 1, 4, 3}, {96, 1, 3, 3}};
        for (int i = 0; i < 4; i++) make(&M.s47 + i, d_out, 4, gdim, gstr, box[i], CU_TENSOR_MAP_SWIZZLE_NONE);
    }
    swin::swin_window_attn_kernel<<<132, swin::NTHREADS, swin::SM_TOTAL>>>(P, M);
}
```

```cpp
#include <cuda_runtime.h>
#include <cuda.h>
#include <cuda_bf16.h>
#include <stdint.h>
#include <type_traits>

namespace swin {
#define STR_(x) #x
#define STR(x) STR_(x)
#define HINT ""

#define NPAIR 53
#define PF_DIST 3
#define QSPLIT 4
#define CLUSTER 0
#define NOPF 0
#define NTAIL 345
#define PSTORE 1
#define PORDER 1
#define GORD 0
#define GF1 1
#define MERGEW 0
#define MWAIT 0
#define PSLEEP 200
#define CH 5
#define NB 1
#define SCM 0
#define MPF 2
#define MLEAD 4
#define PFM 0
#define PFK 4
#define XP 0
#define KLO 6
#define VPOS 1
#define XSPLIT 1
#define SEQ 1
#define PREL 0
#define PEXP 0
#define PFD 0
#define PFW 0
#define WVK -4
#define WSEQ 1
#define PF1 1
#define WFIRST 1
#define MPRE 1
#define SLOWH 2
#define LS_FAST 4.f
#define ENDR 1
#define EBZ 1
#define HSQ 0
#define AFENCE 0
#define FM 0
#define QPOST 0
#define EARLYQ 0
#define KL 4
#define VB1 4
#define VA0 1
#define K1 3
#define Q1 2
#define RWF 3
#define PUBM 2
#define NH 12
#define HW 29
#define HDEL 0
#define CONSTQ 1
#define V64 1
#define M01 2
#define PPAR 1
#define EPF 0
#define EPW 1
#define HS 0
#define MP2 0
#define SDEF 1
#define EXH 2
#define EXD 1
#define STH 200
#define STP 100
#define SDN 32
#define XPOS 4
#define PBE 70
#define WFEN 1
#define REG_G 224
#define REG_A 128
#define REG_H 32
constexpr int IMG      = 511;
constexpr int NWS      = 73;
constexpr int NWINDOWS = NWS * NWS;
constexpr int TOK      = 49;
constexpr int NPIX     = IMG * IMG;
constexpr int NTHREADS = 512;

constexpr int W_ATOM = 6144;
constexpr int SM_WA = 0, SM_WB = 6 * 2048, SM_WV = 12 * W_ATOM, D_WV = SM_WV + ((W_ATOM - 2048) << 16);
constexpr int GRP   = TOK * 16;
constexpr int XCH   = TOK * 128;
constexpr int SM_V  = 18 * W_ATOM, V_STRIDE = 10240, O_PITCH = 192;
constexpr int SM_QK = SM_V + 4 * V_STRIDE, QK_CHUNK = 4 * XCH;
constexpr int SM_MASK = SM_QK + 3 * QK_CHUNK;
constexpr int SM_TAB  = SM_V + 3 * V_STRIDE + 256;
constexpr int SM_BAR  = SM_MASK + 4816;
constexpr int B_XFULL = 0, B_WRAW = 32, B_QKRAW = 64, B_QKFREE = 96, B_VFREE = 128, B_ODONE = 160,
              B_PROG = 192, B_VRAW = 224, B_MFULL = 256, B_MCONS = 272, B_WFULL = 280, B_STORED = 288, B_PUBD = 304;
constexpr int SM_FLAG = SM_BAR + 320;
constexpr int SM_A_END = SM_FLAG + 128;
static_assert(SM_QK % 1024 == 0 && 13 * GRP <= V_STRIDE && V_STRIDE % 128 == 0, "layout");
constexpr int SM_WO    = 0;
constexpr int SM_STAGE = 73728;
constexpr int STAGE_BYTES = 24576;
constexpr int SM_PBAR  = SM_A_END;
#define TA(role, idx)
#define TAEND(role)
constexpr int SM_TOTAL = SM_PBAR + 152;
#define TP(idx)
static_assert(SM_STAGE + 6 * STAGE_BYTES <= SM_BAR, "smem");
static_assert(SM_TOTAL <= 232448, "smem");
static_assert(SM_BAR % 8 == 0 && NWINDOWS / NPAIR < 127, "barrier alignment, flags");

constexpr int SEG_B   = (IMG - 4) * IMG;
constexpr int TILES_A = (NPIX - SEG_B + 63) / 64;
constexpr int TILES   = TILES_A + (SEG_B + 63) / 64;
constexpr uint32_t ROW_DONE = NWS * 2;

__device__ uint32_t g_cnt[NWS + 7];
__device__ __align__(128) uint8_t g_wo[73728];
__device__ uint32_t g_flag[66 * 128];
__device__ uint32_t g_done;

#define TR(ev, idx)
#define TC(slot)
#define TS(i)
#define TRH(ev, idx)
constexpr float LOG2E = 1.4426950408889634f;
__device__ __forceinline__ int clock32() { int c; asm volatile("mov.u32 %0, %%clock;" : "=r"(c) :: "memory"); return c; }

__device__ __forceinline__ uint32_t smem_u32(const void* p) {
    return (uint32_t)__cvta_generic_to_shared(p);
}
__device__ __forceinline__ uint64_t make_desc(uint32_t saddr, uint32_t lbo, uint32_t sbo, uint32_t swz = 0) {
    return (uint64_t)((saddr & 0x3FFFF) >> 4) | ((uint64_t)(lbo >> 4) << 16) | ((uint64_t)(sbo >> 4) << 32) |
           ((uint64_t)swz << 62);
}
__host__ __device__ constexpr uint64_t make_desc_c(uint32_t saddr, uint32_t lbo, uint32_t sbo, uint32_t swz) {
    return (uint64_t)(saddr >> 4) | ((uint64_t)(lbo >> 4) << 16) | ((uint64_t)(sbo >> 4) << 32) | ((uint64_t)swz << 62);
}
constexpr uint64_t D_WV64 = make_desc_c(SM_WV, 12288, 512, 2) - make_desc_c(0, 2048, 256, 3);
__device__ __forceinline__ void wgmma_fence()  { asm volatile("wgmma.fence.sync.aligned;\n" ::: "memory"); }
__device__ __forceinline__ void wgmma_commit() { asm volatile("wgmma.commit_group.sync.aligned;\n" ::: "memory"); }
template <int N> __device__ __forceinline__ void wgmma_wait() {
    asm volatile("wgmma.wait_group.sync.aligned %0;\n" :: "n"(N) : "memory");
}
__device__ __forceinline__ void fence_async_smem() { asm volatile("fence.proxy.async.shared::cta;\n" ::: "memory"); }
template <int N> __device__ __forceinline__ void nb_sync(int id) { asm volatile("bar.sync %0, %1;\n" :: "r"(id), "n"(N) : "memory"); }
template <int N> __device__ __forceinline__ void nb_arrive(int id) { asm volatile("bar.arrive %0, %1;\n" :: "r"(id), "n"(N) : "memory"); }
constexpr int NB_ODONE = 0, NB_QKFREE = 6, NB_QKRAW = 12;
__device__ __forceinline__ void wg_bar(int id) { asm volatile("bar.sync %0, 128;\n" :: "r"(id) : "memory"); }

template <int N> __device__ __forceinline__ void reg_fence(float (&v)[N]) {
#pragma unroll
    for (int i = 0; i < N; i++) asm volatile("" : "+f"(v[i]) :: "memory");
}
template <int N> __device__ __forceinline__ void reg_fence(uint32_t (&v)[N]) {
#pragma unroll
    for (int i = 0; i < N; i++) asm volatile("" : "+r"(v[i]) :: "memory");
}
template <int N, int M> __device__ __forceinline__ void reg_fence(uint32_t (&v)[N][M]) {
#pragma unroll
    for (int i = 0; i < N; i++) reg_fence(v[i]);
}

__device__ __forceinline__ uint32_t pack_bf16(float lo, float hi) {
    uint32_t r;
    asm("cvt.rn.bf16x2.f32 %0, %1, %2;\n" : "=r"(r) : "f"(hi), "f"(lo));
    return r;
}
__device__ __forceinline__ float bf16lo(uint32_t v) { return __uint_as_float(v << 16); }
__device__ __forceinline__ float bf16hi(uint32_t v) { return __uint_as_float(v & 0xFFFF0000u); }
__device__ __forceinline__ uint32_t hadd2_bf16(uint32_t a, uint32_t b) {
    uint32_t r;
    asm("add.rn.bf16x2 %0, %1, %2;\n" : "=r"(r) : "r"(a), "r"(b));
    return r;
}
__device__ __forceinline__ uint32_t hmul2_bf16(uint32_t a, uint32_t b) {
    uint32_t r;
    asm("mul.rn.bf16x2 %0, %1, %2;\n" : "=r"(r) : "r"(a), "r"(b));
    return r;
}
__device__ __forceinline__ uint32_t hsub2_bf16(uint32_t a, uint32_t b) {
    uint32_t r;
    asm("sub.rn.bf16x2 %0, %1, %2;\n" : "=r"(r) : "r"(a), "r"(b));
    return r;
}
__device__ __forceinline__ uint32_t hfma2_bf16(uint32_t a, uint32_t b, uint32_t c) {
    uint32_t r;
    asm("fma.rn.bf16x2 %0, %1, %2, %3;\n" : "=r"(r) : "r"(a), "r"(b), "r"(c));
    return r;
}
__device__ __forceinline__ uint32_t hmax2_bf16(uint32_t a, uint32_t b) {
    uint32_t r;
    asm("max.bf16x2 %0, %1, %2;\n" : "=r"(r) : "r"(a), "r"(b));
    return r;
}
__device__ __forceinline__ uint32_t hmin2_bf16(uint32_t a, uint32_t b) {
    uint32_t r;
    asm("min.bf16x2 %0, %1, %2;\n" : "=r"(r) : "r"(a), "r"(b));
    return r;
}
__device__ __forceinline__ uint32_t ex2_bf16x2(uint32_t a) {
    uint32_t r;
    asm("ex2.approx.ftz.bf16x2 %0, %1;\n" : "=r"(r) : "r"(a));
    return r;
}
__device__ __forceinline__ uint32_t ex2_bf16lo(uint32_t a) {
    uint32_t r;
    asm("{\n.reg .b16 l, h;\nmov.b32 {l, h}, %1;\nex2.approx.ftz.bf16 l, l;\ncvt.u32.u16 %0, l;\n}\n" : "=r"(r) : "r"(a));
    return r;
}
__device__ __forceinline__ uint32_t mbar_test(uint32_t bar, uint32_t parity) {
    uint32_t ok;
    asm volatile("{\n.reg .pred p;\nmbarrier.test_wait.parity.shared::cta.b64 p, [%1], %2;\nselp.u32 %0, 1, 0, p;\n}\n"
                 : "=r"(ok) : "r"(bar), "r"(parity) : "memory");
    return ok;
}
__device__ __forceinline__ uint32_t prmt(uint32_t a, uint32_t b, uint32_t sel) {
    uint32_t r;
    asm("prmt.b32 %0, %1, %2, %3;\n" : "=r"(r) : "r"(a), "r"(b), "r"(sel));
    return r;
}
__device__ __forceinline__ float round_bf16(float x) { return __bfloat162float(__float2bfloat16_rn(x)); }

__device__ __forceinline__ void mbar_init(uint32_t bar, uint32_t count) {
    asm volatile("mbarrier.init.shared::cta.b64 [%0], %1;\n" :: "r"(bar), "r"(count) : "memory");
}
__device__ __forceinline__ void mbar_wait(uint32_t bar, uint32_t parity) {
    asm volatile(
        "{\n"
        ".reg .pred p;\n"
        ".reg .u32 n;\n"
        "mov.u32 n, 0;\n"
        "WAIT_%=:\n"
        "mbarrier.try_wait.parity.shared::cta.b64 p, [%0], %1" HINT ";\n"
        "@p bra DONE_%=;\n"
        "add.u32 n, n, 1;\n"
        "setp.lt.u32 p, n, 4194304;\n"
        "@p bra WAIT_%=;\n"
        "trap;\n"
        "DONE_%=:\n"
        "}\n" :: "r"(bar), "r"(parity) : "memory");
}
template <bool S> __device__ __forceinline__ void mbar_wait_s(uint32_t bar, uint32_t parity) {
    if (!S) mbar_wait(bar, parity);
    else asm volatile(
        "{\n"
        ".reg .pred p;\n"
        ".reg .u32 n;\n"
        "mov.u32 n, 0;\n"
        "WAIT_%=:\n"
        "mbarrier.try_wait.parity.shared::cta.b64 p, [%0], %1, 4000;\n"
        "@p bra DONE_%=;\n"
        "add.u32 n, n, 1;\n"
        "setp.lt.u32 p, n, 262144;\n"
        "@p bra WAIT_%=;\n"
        "trap;\n"
        "DONE_%=:\n"
        "}\n" :: "r"(bar), "r"(parity) : "memory");
}
__device__ __forceinline__ void mbar_wait4(uint32_t b0, uint32_t p0, uint32_t b1, uint32_t p1, uint32_t b2, uint32_t p2,
                                           uint32_t b3, uint32_t p3) {
    asm volatile(
        "{\n"
        ".reg .pred p, q, r, s;\n"
        ".reg .u32 n;\n"
        "mov.u32 n, 0;\n"
        "WAIT_%=:\n"
        "mbarrier.try_wait.parity.shared::cta.b64 p, [%0], %1" HINT ";\n"
        "mbarrier.try_wait.parity.shared::cta.b64 q, [%2], %3" HINT ";\n"
        "mbarrier.try_wait.parity.shared::cta.b64 r, [%4], %5" HINT ";\n"
        "mbarrier.try_wait.parity.shared::cta.b64 s, [%6], %7" HINT ";\n"
        "and.pred p, p, q;\n"
        "and.pred r, r, s;\n"
        "and.pred p, p, r;\n"
        "@p bra DONE_%=;\n"
        "add.u32 n, n, 1;\n"
        "setp.lt.u32 p, n, 4194304;\n"
        "@p bra WAIT_%=;\n"
        "trap;\n"
        "DONE_%=:\n"
        "}\n" :: "r"(b0), "r"(p0), "r"(b1), "r"(p1), "r"(b2), "r"(p2), "r"(b3), "r"(p3) : "memory");
}
__device__ __forceinline__ void mbar_wait2(uint32_t b0, uint32_t p0, uint32_t b1, uint32_t p1) {
    asm volatile(
        "{\n"
        ".reg .pred p, q;\n"
        ".reg .u32 n;\n"
        "mov.u32 n, 0;\n"
        "WAIT_%=:\n"
        "mbarrier.try_wait.parity.shared::cta.b64 p, [%0], %1" HINT ";\n"
        "mbarrier.try_wait.parity.shared::cta.b64 q, [%2], %3" HINT ";\n"
        "and.pred p, p, q;\n"
        "@p bra DONE_%=;\n"
        "add.u32 n, n, 1;\n"
        "setp.lt.u32 p, n, 4194304;\n"
        "@p bra WAIT_%=;\n"
        "trap;\n"
        "DONE_%=:\n"
        "}\n" :: "r"(b0), "r"(p0), "r"(b1), "r"(p1) : "memory");
}
#define HINTA ""
__device__ __forceinline__ void mbar_wait_unless(uint32_t ok, uint32_t bar, uint32_t parity) {
    asm volatile(
        "{\n"
        ".reg .pred p;\n"
        ".reg .u32 n;\n"
        "setp.ne.u32 p, %2, 0;\n"
        "vote.sync.all.pred p, p, 0xffffffff;\n"
        "@p bra DONE_%=;\n"
        "mov.u32 n, 0;\n"
        "WAIT_%=:\n"
        "mbarrier.try_wait.parity.shared::cta.b64 p, [%0], %1" HINTA ";\n"
        "@p bra DONE_%=;\n"
        "add.u32 n, n, 1;\n"
        "setp.lt.u32 p, n, 4194304;\n"
        "@p bra WAIT_%=;\n"
        "trap;\n"
        "DONE_%=:\n"
        "}\n" :: "r"(bar), "r"(parity), "r"(ok) : "memory");
}
__device__ __forceinline__ void mbar_wait2_unless(uint32_t ok, uint32_t b0, uint32_t p0, uint32_t b1, uint32_t p1) {
    asm volatile(
        "{\n"
        ".reg .pred p, q;\n"
        ".reg .u32 n;\n"
        "setp.ne.u32 p, %4, 0;\n"
        "vote.sync.all.pred p, p, 0xffffffff;\n"
        "@p bra DONE_%=;\n"
        "mov.u32 n, 0;\n"
        "WAIT_%=:\n"
        "mbarrier.try_wait.parity.shared::cta.b64 p, [%0], %1" HINT ";\n"
        "mbarrier.try_wait.parity.shared::cta.b64 q, [%2], %3" HINT ";\n"
        "and.pred p, p, q;\n"
        "@p bra DONE_%=;\n"
        "add.u32 n, n, 1;\n"
        "setp.lt.u32 p, n, 4194304;\n"
        "@p bra WAIT_%=;\n"
        "trap;\n"
        "DONE_%=:\n"
        "}\n" :: "r"(b0), "r"(p0), "r"(b1), "r"(p1), "r"(ok) : "memory");
}
__device__ __forceinline__ void mbar_wait4_unless(uint32_t ok, uint32_t b0, uint32_t p0, uint32_t b1, uint32_t p1, uint32_t b2,
                                                  uint32_t p2, uint32_t b3, uint32_t p3) {
    asm volatile(
        "{\n"
        ".reg .pred p, q, r, s;\n"
        ".reg .u32 n;\n"
        "setp.ne.u32 p, %8, 0;\n"
        "vote.sync.all.pred p, p, 0xffffffff;\n"
        "@p bra DONE_%=;\n"
        "mov.u32 n, 0;\n"
        "WAIT_%=:\n"
        "mbarrier.try_wait.parity.shared::cta.b64 p, [%0], %1" HINT ";\n"
        "mbarrier.try_wait.parity.shared::cta.b64 q, [%2], %3" HINT ";\n"
        "mbarrier.try_wait.parity.shared::cta.b64 r, [%4], %5" HINT ";\n"
        "mbarrier.try_wait.parity.shared::cta.b64 s, [%6], %7" HINT ";\n"
        "and.pred p, p, q;\n"
        "and.pred r, r, s;\n"
        "and.pred p, p, r;\n"
        "@p bra DONE_%=;\n"
        "add.u32 n, n, 1;\n"
        "setp.lt.u32 p, n, 4194304;\n"
        "@p bra WAIT_%=;\n"
        "trap;\n"
        "DONE_%=:\n"
        "}\n" :: "r"(b0), "r"(p0), "r"(b1), "r"(p1), "r"(b2), "r"(p2), "r"(b3), "r"(p3), "r"(ok) : "memory");
}
__device__ __forceinline__ void sched_fence(uint32_t zero, uint32_t a, uint32_t b, uint32_t c, uint32_t d, uint32_t e = 0,
                                            uint32_t f = 0, uint32_t g = 0, uint32_t h = 0, uint32_t i = 0, uint32_t j = 0,
                                            uint32_t k = 0) {
    asm volatile("{\n.reg .pred p;\n.reg .u32 n;\nsetp.eq.u32 p, %0, 0;\n@p bra.uni DONE_%=;\nmov.u32 n, %0;\nSPIN_%=:\n"
                 "nanosleep.u32 %1;\nnanosleep.u32 %2;\nnanosleep.u32 %3;\nnanosleep.u32 %4;\nnanosleep.u32 %5;\n"
                 "nanosleep.u32 %6;\nnanosleep.u32 %7;\nnanosleep.u32 %8;\nnanosleep.u32 %9;\nnanosleep.u32 %10;\n"
                 "nanosleep.u32 %11;\nsub.u32 n, n, 1;\nsetp.ne.u32 p, n, 0;\n@p bra.uni SPIN_%=;\nDONE_%=:\n}\n"
                 :: "r"(zero), "r"(a), "r"(b), "r"(c), "r"(d), "r"(e), "r"(f), "r"(g), "r"(h), "r"(i), "r"(j), "r"(k) : "memory");
}
__device__ __forceinline__ void sched_fence2(uint32_t zero, float& x, float& y, uint32_t a, uint32_t b, uint32_t c, uint32_t d = 0,
                                             uint32_t e = 0, uint32_t f = 0) {
    asm volatile("{\n.reg .pred p;\n.reg .u32 n;\nsetp.eq.u32 p, %2, 0;\n@p bra.uni DONE_%=;\nmov.u32 n, %2;\nSPIN_%=:\n"
                 "add.f32 %0, %0, %1;\nadd.f32 %1, %1, %0;\nnanosleep.u32 %3;\nnanosleep.u32 %4;\nnanosleep.u32 %5;\n"
                 "nanosleep.u32 %6;\nnanosleep.u32 %7;\nnanosleep.u32 %8;\n"
                 "sub.u32 n, n, 1;\nsetp.ne.u32 p, n, 0;\n@p bra.uni SPIN_%=;\nDONE_%=:\n}\n"
                 : "+f"(x), "+f"(y) : "r"(zero), "r"(a), "r"(b), "r"(c), "r"(d), "r"(e), "r"(f) : "memory");
}
template <int N> __device__ __forceinline__ void use_regs(const uint32_t* v) {
    if constexpr (N >= 4) {
        asm volatile("nanosleep.u32 %0;\nnanosleep.u32 %1;\nnanosleep.u32 %2;\nnanosleep.u32 %3;\n" :: "r"(v[0]), "r"(v[1]), "r"(v[2]), "r"(v[3]) : "memory");
        use_regs<N - 4>(v + 4);
    } else if constexpr (N > 0) {
        asm volatile("nanosleep.u32 %0;\n" :: "r"(v[0]) : "memory");
        use_regs<N - 1>(v + 1);
    }
}
template <int N> __device__ __forceinline__ void sched_fence_n(uint32_t zero, const uint32_t (&v)[N]) {
    if (__builtin_expect(zero != 0, 0)) {
#pragma unroll 1
        for (uint32_t n = zero; n; n--) use_regs<N>(v);
    }
}
__device__ __forceinline__ void sched_fence_rw(uint32_t zero, uint32_t (&v)[13]) {
    asm volatile("{\n.reg .pred p;\n.reg .u32 n;\nsetp.eq.u32 p, %13, 0;\n@p bra.uni DONE_%=;\nmov.u32 n, %13;\nSPIN_%=:\n"
                 "add.u32 %0, %0, %1;\nadd.u32 %1, %1, %2;\nadd.u32 %2, %2, %3;\nadd.u32 %3, %3, %4;\nadd.u32 %4, %4, %5;\n"
                 "add.u32 %5, %5, %6;\nadd.u32 %6, %6, %7;\nadd.u32 %7, %7, %8;\nadd.u32 %8, %8, %9;\nadd.u32 %9, %9, %10;\n"
                 "add.u32 %10, %10, %11;\nadd.u32 %11, %11, %12;\nadd.u32 %12, %12, %0;\n"
                 "sub.u32 n, n, 1;\nsetp.ne.u32 p, n, 0;\n@p bra.uni SPIN_%=;\nDONE_%=:\n}\n"
                 : "+r"(v[0]), "+r"(v[1]), "+r"(v[2]), "+r"(v[3]), "+r"(v[4]), "+r"(v[5]), "+r"(v[6]), "+r"(v[7]), "+r"(v[8]),
                   "+r"(v[9]), "+r"(v[10]), "+r"(v[11]), "+r"(v[12]) : "r"(zero) : "memory");
}
__device__ __forceinline__ void mbar_arrive(uint32_t bar) {
    asm volatile("mbarrier.arrive.shared::cta.b64 _, [%0];\n" :: "r"(bar) : "memory");
}
__device__ __forceinline__ void mbar_arrive_n(uint32_t bar, uint32_t n) {
    asm volatile("mbarrier.arrive.shared::cta.b64 _, [%0], %1;\n" :: "r"(bar), "r"(n) : "memory");
}
__device__ __forceinline__ void mbar_arrive_expect_tx(uint32_t bar, uint32_t bytes) {
    asm volatile("mbarrier.arrive.expect_tx.shared::cta.b64 _, [%0], %1;\n" :: "r"(bar), "r"(bytes) : "memory");
}
__device__ __forceinline__ void stg128_if(bool p, void* addr, uint32_t x, uint32_t y, uint32_t z, uint32_t w) {
    asm volatile("{\n.reg .pred q;\nsetp.ne.b32 q, %5, 0;\n@q st.global.L1::no_allocate.v4.b32 [%0], {%1, %2, %3, %4};\n}\n"
                 :: "l"(addr), "r"(x), "r"(y), "r"(z), "r"(w), "r"((uint32_t)p) : "memory");
}
__device__ __forceinline__ void stsm_x4(uint32_t addr, uint32_t r0, uint32_t r1, uint32_t r2, uint32_t r3) {
    asm volatile("stmatrix.sync.aligned.m8n8.x4.shared.b16 [%0], {%1, %2, %3, %4};\n"
                 :: "r"(addr), "r"(r0), "r"(r1), "r"(r2), "r"(r3) : "memory");
}
__device__ __forceinline__ void stsm_x2(uint32_t addr, uint32_t r0, uint32_t r1) {
    asm volatile("stmatrix.sync.aligned.m8n8.x2.shared.b16 [%0], {%1, %2};\n" :: "r"(addr), "r"(r0), "r"(r1) : "memory");
}
__device__ __forceinline__ void sts128(uint32_t addr, uint32_t r0, uint32_t r1, uint32_t r2, uint32_t r3) {
    asm volatile("st.shared.v4.b32 [%0], {%1, %2, %3, %4};\n" :: "r"(addr), "r"(r0), "r"(r1), "r"(r2), "r"(r3) : "memory");
}
__device__ __forceinline__ void sts128_if(uint32_t p, uint32_t addr, uint32_t r0, uint32_t r1, uint32_t r2, uint32_t r3) {
    asm volatile("{\n.reg .pred q;\nsetp.ne.b32 q, %5, 0;\n@q st.shared.v4.b32 [%0], {%1, %2, %3, %4};\n}\n"
                 :: "r"(addr), "r"(r0), "r"(r1), "r"(r2), "r"(r3), "r"(p) : "memory");
}
__device__ __forceinline__ void sts32(uint32_t addr, uint32_t v) {
    asm volatile("st.shared.b32 [%0], %1;\n" :: "r"(addr), "r"(v) : "memory");
}
__device__ __forceinline__ uint32_t lds32(uint32_t addr) {
    uint32_t v;
    asm volatile("ld.shared.b32 %0, [%1];\n" : "=r"(v) : "r"(addr) : "memory");
    return v;
}
__device__ __forceinline__ void ldg_nc_v4(uint32_t (&r)[4], const void* p) {
    asm volatile("ld.global.nc.L1::no_allocate.v4.u32 {%0, %1, %2, %3}, [%4];\n"
                 : "=r"(r[0]), "=r"(r[1]), "=r"(r[2]), "=r"(r[3]) : "l"(p));
}
__device__ __forceinline__ uint32_t ldg_u32(const void* p) {
    uint32_t v;
    asm volatile("ld.global.nc.L1::evict_first.u32 %0, [%1];\n" : "=r"(v) : "l"(p));
    return v;
}
__device__ __forceinline__ void ldg_u64(const void* p, uint32_t& a, uint32_t& b) {
    asm volatile("ld.global.nc.L1::evict_first.v2.u32 {%0, %1}, [%2];\n" : "=r"(a), "=r"(b) : "l"(p));
}
__device__ __forceinline__ void prefetch_l2(const void* p) {
    asm volatile("prefetch.global.L2 [%0];\n" :: "l"(p));
}
__device__ __forceinline__ void cp_async16(uint32_t dst, const void* src) {
    asm volatile("cp.async.cg.shared.global [%0], [%1], 16;\n" :: "r"(dst), "l"(src) : "memory");
}
__device__ __forceinline__ float ex2_ftz(float x) {
    float y;
    asm("ex2.approx.ftz.f32 %0, %1;\n" : "=f"(y) : "f"(x));
    return y;
}
__device__ __forceinline__ float lg2_ftz(float x) {
    float y;
    asm("lg2.approx.ftz.f32 %0, %1;\n" : "=f"(y) : "f"(x));
    return y;
}
__device__ __forceinline__ float rcp_ftz(float x) {
    float y;
    asm("rcp.approx.ftz.f32 %0, %1;\n" : "=f"(y) : "f"(x));
    return y;
}
__device__ __forceinline__ float rsqrt_ftz(float x) {
    float y;
    asm("rsqrt.approx.ftz.f32 %0, %1;\n" : "=f"(y) : "f"(x));
    return y;
}

__device__ __forceinline__ bool elect_one() {
    uint32_t p;
    asm volatile("{\n.reg .pred q;\nelect.sync _|q, 0xffffffff;\nselp.u32 %0, 1, 0, q;\n}\n" : "=r"(p));
    return p != 0;
}
__device__ __forceinline__ void ldsm_x4(uint32_t (&r)[4], uint32_t addr) {
    asm volatile("ldmatrix.sync.aligned.m8n8.x4.shared.b16 {%0, %1, %2, %3}, [%4];\n"
                 : "=r"(r[0]), "=r"(r[1]), "=r"(r[2]), "=r"(r[3]) : "r"(addr) : "memory");
}
__device__ __forceinline__ void ldsm_x2(uint32_t& r0, uint32_t& r1, uint32_t addr) {
    asm volatile("ldmatrix.sync.aligned.m8n8.x2.shared.b16 {%0, %1}, [%2];\n" : "=r"(r0), "=r"(r1) : "r"(addr) : "memory");
}
__device__ __forceinline__ void tma_2d(uint32_t dst, const CUtensorMap* map, uint32_t bar, int c0, int c1) {
    asm volatile("cp.async.bulk.tensor.2d.shared::cluster.global.mbarrier::complete_tx::bytes [%0], [%1, {%3, %4}], [%2];\n"
                 :: "r"(dst), "l"(reinterpret_cast<uint64_t>(map)), "r"(bar), "r"(c0), "r"(c1) : "memory");
}
__device__ __forceinline__ void tma_3d(uint32_t dst, const CUtensorMap* map, uint32_t bar, int c0, int c1, int c2) {
    asm volatile("cp.async.bulk.tensor.3d.shared::cluster.global.mbarrier::complete_tx::bytes [%0], [%1, {%3, %4, %5}], [%2];\n"
                 :: "r"(dst), "l"(reinterpret_cast<uint64_t>(map)), "r"(bar), "r"(c0), "r"(c1), "r"(c2) : "memory");
}
constexpr uint64_t EVICT_FIRST = 0x12F0000000000000ull;
__device__ __forceinline__ void tma_3d_x(uint32_t dst, const CUtensorMap* map, uint32_t bar, int c0, int c1, int c2) {
    if (CH & 50)
        asm volatile("cp.async.bulk.tensor.3d.shared::cluster.global.mbarrier::complete_tx::bytes.L2::cache_hint [%0], [%1, {%3, %4, %5}], [%2], %6;\n"
                     :: "r"(dst), "l"(reinterpret_cast<uint64_t>(map)), "r"(bar), "r"(c0), "r"(c1), "r"(c2),
                        "l"((CH & 2) || (blockIdx.x & 1) == ((CH >> 5) & 1) ? EVICT_FIRST : 0x1000000000000000ull) : "memory");
    else tma_3d(dst, map, bar, c0, c1, c2);
}
__device__ __forceinline__ void tma_store_4d(const CUtensorMap* map, uint32_t src, int c0, int c1, int c2, int c3) {
    asm volatile("cp.async.bulk.tensor.4d.global.shared::cta.tile.bulk_group [%0, {%2, %3, %4, %5}], [%1];\n"
                 :: "l"(reinterpret_cast<uint64_t>(map)), "r"(src), "r"(c0), "r"(c1), "r"(c2), "r"(c3) : "memory");
}
__device__ __forceinline__ void mbar_arrive_if(uint32_t bar, uint32_t cnt) {
    asm volatile("{\n.reg .pred q;\nsetp.ne.b32 q, %1, 0;\n@q mbarrier.arrive.shared::cta.b64 _, [%0], %1;\n}\n"
                 :: "r"(bar), "r"(cnt) : "memory");
}

template <int BOFF, int AOFF, int NA>
__device__ __forceinline__ void mma_qkv_a(float (&d)[48], const uint32_t (&a)[NA][4], uint64_t descB) {
    asm volatile(
        "{\n"
        ".reg .pred p0, p1;\n"
        ".reg .b64 ta, ta0, tb, tb0;\n"
        "setp.ne.b32 p0, 0, 0;\n"
        "setp.eq.b32 p1, 0, 0;\n"
        "add.s64 tb0, %72, %73;\n"
        "add.s64 tb, tb0, 0;\n"
        "wgmma.mma_async.sync.aligned.m64n96k16.f32.bf16.bf16 {%0, %1, %2, %3, %4, %5, %6, %7, %8, %9, %10, %11, %12, %13, %14, %15, %16, %17, %18, %19, %20, %21, %22, %23, %24, %25, %26, %27, %28, %29, %30, %31, %32, %33, %34, %35, %36, %37, %38, %39, %40, %41, %42, %43, %44, %45, %46, %47}, {%48, %49, %50, %51}, tb, p0, 1, 1, 1;\n"
        "add.s64 tb, tb0, 32;\n"
        "wgmma.mma_async.sync.aligned.m64n96k16.f32.bf16.bf16 {%0, %1, %2, %3, %4, %5, %6, %7, %8, %9, %10, %11, %12, %13, %14, %15, %16, %17, %18, %19, %20, %21, %22, %23, %24, %25, %26, %27, %28, %29, %30, %31, %32, %33, %34, %35, %36, %37, %38, %39, %40, %41, %42, %43, %44, %45, %46, %47}, {%52, %53, %54, %55}, tb, p1, 1, 1, 1;\n"
        "add.s64 tb, tb0, 64;\n"
        "wgmma.mma_async.sync.aligned.m64n96k16.f32.bf16.bf16 {%0, %1, %2, %3, %4, %5, %6, %7, %8, %9, %10, %11, %12, %13, %14, %15, %16, %17, %18, %19, %20, %21, %22, %23, %24, %25, %26, %27, %28, %29, %30, %31, %32, %33, %34, %35, %36, %37, %38, %39, %40, %41, %42, %43, %44, %45, %46, %47}, {%56, %57, %58, %59}, tb, p1, 1, 1, 1;\n"
        "add.s64 tb, tb0, 96;\n"
        "wgmma.mma_async.sync.aligned.m64n96k16.f32.bf16.bf16 {%0, %1, %2, %3, %4, %5, %6, %7, %8, %9, %10, %11, %12, %13, %14, %15, %16, %17, %18, %19, %20, %21, %22, %23, %24, %25, %26, %27, %28, %29, %30, %31, %32, %33, %34, %35, %36, %37, %38, %39, %40, %41, %42, %43, %44, %45, %46, %47}, {%60, %61, %62, %63}, tb, p1, 1, 1, 1;\n"
        "add.s64 tb, tb0, 1536;\n"
        "wgmma.mma_async.sync.aligned.m64n96k16.f32.bf16.bf16 {%0, %1, %2, %3, %4, %5, %6, %7, %8, %9, %10, %11, %12, %13, %14, %15, %16, %17, %18, %19, %20, %21, %22, %23, %24, %25, %26, %27, %28, %29, %30, %31, %32, %33, %34, %35, %36, %37, %38, %39, %40, %41, %42, %43, %44, %45, %46, %47}, {%64, %65, %66, %67}, tb, p1, 1, 1, 1;\n"
        "add.s64 tb, tb0, 1568;\n"
        "wgmma.mma_async.sync.aligned.m64n96k16.f32.bf16.bf16 {%0, %1, %2, %3, %4, %5, %6, %7, %8, %9, %10, %11, %12, %13, %14, %15, %16, %17, %18, %19, %20, %21, %22, %23, %24, %25, %26, %27, %28, %29, %30, %31, %32, %33, %34, %35, %36, %37, %38, %39, %40, %41, %42, %43, %44, %45, %46, %47}, {%68, %69, %70, %71}, tb, p1, 1, 1, 1;\n"
        "}\n"
        : "=f"(d[0]), "=f"(d[1]), "=f"(d[2]), "=f"(d[3]), "=f"(d[4]), "=f"(d[5]), "=f"(d[6]), "=f"(d[7]), "=f"(d[8]), "=f"(d[9]), "=f"(d[10]), "=f"(d[11]), "=f"(d[12]), "=f"(d[13]), "=f"(d[14]), "=f"(d[15]), "=f"(d[16]), "=f"(d[17]), "=f"(d[18]), "=f"(d[19]), "=f"(d[20]), "=f"(d[21]), "=f"(d[22]), "=f"(d[23]), "=f"(d[24]), "=f"(d[25]), "=f"(d[26]), "=f"(d[27]), "=f"(d[28]), "=f"(d[29]), "=f"(d[30]), "=f"(d[31]), "=f"(d[32]), "=f"(d[33]), "=f"(d[34]), "=f"(d[35]), "=f"(d[36]), "=f"(d[37]), "=f"(d[38]), "=f"(d[39]), "=f"(d[40]), "=f"(d[41]), "=f"(d[42]), "=f"(d[43]), "=f"(d[44]), "=f"(d[45]), "=f"(d[46]), "=f"(d[47])
        : "r"(a[AOFF + 0][0]), "r"(a[AOFF + 0][1]), "r"(a[AOFF + 0][2]), "r"(a[AOFF + 0][3]), "r"(a[AOFF + 1][0]), "r"(a[AOFF + 1][1]), "r"(a[AOFF + 1][2]), "r"(a[AOFF + 1][3]), "r"(a[AOFF + 2][0]), "r"(a[AOFF + 2][1]), "r"(a[AOFF + 2][2]), "r"(a[AOFF + 2][3]), "r"(a[AOFF + 3][0]), "r"(a[AOFF + 3][1]), "r"(a[AOFF + 3][2]), "r"(a[AOFF + 3][3]), "r"(a[AOFF + 4][0]), "r"(a[AOFF + 4][1]), "r"(a[AOFF + 4][2]), "r"(a[AOFF + 4][3]), "r"(a[AOFF + 5][0]), "r"(a[AOFF + 5][1]), "r"(a[AOFF + 5][2]), "r"(a[AOFF + 5][3]), "l"(descB), "n"(BOFF >> 4));
}

template <int BOFF, int AOFF, int NA>
__device__ __forceinline__ void mma_qkv_b(float (&d)[48], const uint32_t (&a)[NA][4], uint64_t descB) {
    asm volatile(
        "{\n"
        ".reg .pred p0, p1;\n"
        ".reg .b64 ta, ta0, tb, tb0;\n"
        "setp.ne.b32 p0, 0, 0;\n"
        "setp.eq.b32 p1, 0, 0;\n"
        "add.s64 tb0, %72, %73;\n"
        "add.s64 tb, tb0, 1600;\n"
        "wgmma.mma_async.sync.aligned.m64n96k16.f32.bf16.bf16 {%0, %1, %2, %3, %4, %5, %6, %7, %8, %9, %10, %11, %12, %13, %14, %15, %16, %17, %18, %19, %20, %21, %22, %23, %24, %25, %26, %27, %28, %29, %30, %31, %32, %33, %34, %35, %36, %37, %38, %39, %40, %41, %42, %43, %44, %45, %46, %47}, {%48, %49, %50, %51}, tb, p1, 1, 1, 1;\n"
        "add.s64 tb, tb0, 1632;\n"
        "wgmma.mma_async.sync.aligned.m64n96k16.f32.bf16.bf16 {%0, %1, %2, %3, %4, %5, %6, %7, %8, %9, %10, %11, %12, %13, %14, %15, %16, %17, %18, %19, %20, %21, %22, %23, %24, %25, %26, %27, %28, %29, %30, %31, %32, %33, %34, %35, %36, %37, %38, %39, %40, %41, %42, %43, %44, %45, %46, %47}, {%52, %53, %54, %55}, tb, p1, 1, 1, 1;\n"
        "add.s64 tb, tb0, 3072;\n"
        "wgmma.mma_async.sync.aligned.m64n96k16.f32.bf16.bf16 {%0, %1, %2, %3, %4, %5, %6, %7, %8, %9, %10, %11, %12, %13, %14, %15, %16, %17, %18, %19, %20, %21, %22, %23, %24, %25, %26, %27, %28, %29, %30, %31, %32, %33, %34, %35, %36, %37, %38, %39, %40, %41, %42, %43, %44, %45, %46, %47}, {%56, %57, %58, %59}, tb, p1, 1, 1, 1;\n"
        "add.s64 tb, tb0, 3104;\n"
        "wgmma.mma_async.sync.aligned.m64n96k16.f32.bf16.bf16 {%0, %1, %2, %3, %4, %5, %6, %7, %8, %9, %10, %11, %12, %13, %14, %15, %16, %17, %18, %19, %20, %21, %22, %23, %24, %25, %26, %27, %28, %29, %30, %31, %32, %33, %34, %35, %36, %37, %38, %39, %40, %41, %42, %43, %44, %45, %46, %47}, {%60, %61, %62, %63}, tb, p1, 1, 1, 1;\n"
        "add.s64 tb, tb0, 3136;\n"
        "wgmma.mma_async.sync.aligned.m64n96k16.f32.bf16.bf16 {%0, %1, %2, %3, %4, %5, %6, %7, %8, %9, %10, %11, %12, %13, %14, %15, %16, %17, %18, %19, %20, %21, %22, %23, %24, %25, %26, %27, %28, %29, %30, %31, %32, %33, %34, %35, %36, %37, %38, %39, %40, %41, %42, %43, %44, %45, %46, %47}, {%64, %65, %66, %67}, tb, p1, 1, 1, 1;\n"
        "add.s64 tb, tb0, 3168;\n"
        "wgmma.mma_async.sync.aligned.m64n96k16.f32.bf16.bf16 {%0, %1, %2, %3, %4, %5, %6, %7, %8, %9, %10, %11, %12, %13, %14, %15, %16, %17, %18, %19, %20, %21, %22, %23, %24, %25, %26, %27, %28, %29, %30, %31, %32, %33, %34, %35, %36, %37, %38, %39, %40, %41, %42, %43, %44, %45, %46, %47}, {%68, %69, %70, %71}, tb, p1, 1, 1, 1;\n"
        "}\n"
        : "+f"(d[0]), "+f"(d[1]), "+f"(d[2]), "+f"(d[3]), "+f"(d[4]), "+f"(d[5]), "+f"(d[6]), "+f"(d[7]), "+f"(d[8]), "+f"(d[9]), "+f"(d[10]), "+f"(d[11]), "+f"(d[12]), "+f"(d[13]), "+f"(d[14]), "+f"(d[15]), "+f"(d[16]), "+f"(d[17]), "+f"(d[18]), "+f"(d[19]), "+f"(d[20]), "+f"(d[21]), "+f"(d[22]), "+f"(d[23]), "+f"(d[24]), "+f"(d[25]), "+f"(d[26]), "+f"(d[27]), "+f"(d[28]), "+f"(d[29]), "+f"(d[30]), "+f"(d[31]), "+f"(d[32]), "+f"(d[33]), "+f"(d[34]), "+f"(d[35]), "+f"(d[36]), "+f"(d[37]), "+f"(d[38]), "+f"(d[39]), "+f"(d[40]), "+f"(d[41]), "+f"(d[42]), "+f"(d[43]), "+f"(d[44]), "+f"(d[45]), "+f"(d[46]), "+f"(d[47])
        : "r"(a[AOFF + 0][0]), "r"(a[AOFF + 0][1]), "r"(a[AOFF + 0][2]), "r"(a[AOFF + 0][3]), "r"(a[AOFF + 1][0]), "r"(a[AOFF + 1][1]), "r"(a[AOFF + 1][2]), "r"(a[AOFF + 1][3]), "r"(a[AOFF + 2][0]), "r"(a[AOFF + 2][1]), "r"(a[AOFF + 2][2]), "r"(a[AOFF + 2][3]), "r"(a[AOFF + 3][0]), "r"(a[AOFF + 3][1]), "r"(a[AOFF + 3][2]), "r"(a[AOFF + 3][3]), "r"(a[AOFF + 4][0]), "r"(a[AOFF + 4][1]), "r"(a[AOFF + 4][2]), "r"(a[AOFF + 4][3]), "r"(a[AOFF + 5][0]), "r"(a[AOFF + 5][1]), "r"(a[AOFF + 5][2]), "r"(a[AOFF + 5][3]), "l"(descB), "n"(BOFF >> 4));
}

template <int BOFF, int AOFF, int NA>
__device__ __forceinline__ void mma_v_a(float (&d)[48], const uint32_t (&a)[NA][4], uint64_t descB) {
    asm volatile(
        "{\n"
        ".reg .pred p0, p1;\n"
        ".reg .b64 ta, ta0, tb, tb0;\n"
        "setp.ne.b32 p0, 0, 0;\n"
        "setp.eq.b32 p1, 0, 0;\n"
        "add.s64 tb0, %72, %73;\n"
        "add.s64 tb, tb0, 0;\n"
        "wgmma.mma_async.sync.aligned.m64n96k16.f32.bf16.bf16 {%0, %1, %2, %3, %4, %5, %6, %7, %8, %9, %10, %11, %12, %13, %14, %15, %16, %17, %18, %19, %20, %21, %22, %23, %24, %25, %26, %27, %28, %29, %30, %31, %32, %33, %34, %35, %36, %37, %38, %39, %40, %41, %42, %43, %44, %45, %46, %47}, {%48, %49, %50, %51}, tb, p0, 1, 1, 1;\n"
        "add.s64 tb, tb0, 32;\n"
        "wgmma.mma_async.sync.aligned.m64n96k16.f32.bf16.bf16 {%0, %1, %2, %3, %4, %5, %6, %7, %8, %9, %10, %11, %12, %13, %14, %15, %16, %17, %18, %19, %20, %21, %22, %23, %24, %25, %26, %27, %28, %29, %30, %31, %32, %33, %34, %35, %36, %37, %38, %39, %40, %41, %42, %43, %44, %45, %46, %47}, {%52, %53, %54, %55}, tb, p1, 1, 1, 1;\n"
        "add.s64 tb, tb0, 64;\n"
        "wgmma.mma_async.sync.aligned.m64n96k16.f32.bf16.bf16 {%0, %1, %2, %3, %4, %5, %6, %7, %8, %9, %10, %11, %12, %13, %14, %15, %16, %17, %18, %19, %20, %21, %22, %23, %24, %25, %26, %27, %28, %29, %30, %31, %32, %33, %34, %35, %36, %37, %38, %39, %40, %41, %42, %43, %44, %45, %46, %47}, {%56, %57, %58, %59}, tb, p1, 1, 1, 1;\n"
        "add.s64 tb, tb0, 96;\n"
        "wgmma.mma_async.sync.aligned.m64n96k16.f32.bf16.bf16 {%0, %1, %2, %3, %4, %5, %6, %7, %8, %9, %10, %11, %12, %13, %14, %15, %16, %17, %18, %19, %20, %21, %22, %23, %24, %25, %26, %27, %28, %29, %30, %31, %32, %33, %34, %35, %36, %37, %38, %39, %40, %41, %42, %43, %44, %45, %46, %47}, {%60, %61, %62, %63}, tb, p1, 1, 1, 1;\n"
        "add.s64 tb, tb0, 128;\n"
        "wgmma.mma_async.sync.aligned.m64n96k16.f32.bf16.bf16 {%0, %1, %2, %3, %4, %5, %6, %7, %8, %9, %10, %11, %12, %13, %14, %15, %16, %17, %18, %19, %20, %21, %22, %23, %24, %25, %26, %27, %28, %29, %30, %31, %32, %33, %34, %35, %36, %37, %38, %39, %40, %41, %42, %43, %44, %45, %46, %47}, {%64, %65, %66, %67}, tb, p1, 1, 1, 1;\n"
        "add.s64 tb, tb0, 160;\n"
        "wgmma.mma_async.sync.aligned.m64n96k16.f32.bf16.bf16 {%0, %1, %2, %3, %4, %5, %6, %7, %8, %9, %10, %11, %12, %13, %14, %15, %16, %17, %18, %19, %20, %21, %22, %23, %24, %25, %26, %27, %28, %29, %30, %31, %32, %33, %34, %35, %36, %37, %38, %39, %40, %41, %42, %43, %44, %45, %46, %47}, {%68, %69, %70, %71}, tb, p1, 1, 1, 1;\n"
        "}\n"
        : "=f"(d[0]), "=f"(d[1]), "=f"(d[2]), "=f"(d[3]), "=f"(d[4]), "=f"(d[5]), "=f"(d[6]), "=f"(d[7]), "=f"(d[8]), "=f"(d[9]), "=f"(d[10]), "=f"(d[11]), "=f"(d[12]), "=f"(d[13]), "=f"(d[14]), "=f"(d[15]), "=f"(d[16]), "=f"(d[17]), "=f"(d[18]), "=f"(d[19]), "=f"(d[20]), "=f"(d[21]), "=f"(d[22]), "=f"(d[23]), "=f"(d[24]), "=f"(d[25]), "=f"(d[26]), "=f"(d[27]), "=f"(d[28]), "=f"(d[29]), "=f"(d[30]), "=f"(d[31]), "=f"(d[32]), "=f"(d[33]), "=f"(d[34]), "=f"(d[35]), "=f"(d[36]), "=f"(d[37]), "=f"(d[38]), "=f"(d[39]), "=f"(d[40]), "=f"(d[41]), "=f"(d[42]), "=f"(d[43]), "=f"(d[44]), "=f"(d[45]), "=f"(d[46]), "=f"(d[47])
        : "r"(a[AOFF + 0][0]), "r"(a[AOFF + 0][1]), "r"(a[AOFF + 0][2]), "r"(a[AOFF + 0][3]), "r"(a[AOFF + 1][0]), "r"(a[AOFF + 1][1]), "r"(a[AOFF + 1][2]), "r"(a[AOFF + 1][3]), "r"(a[AOFF + 2][0]), "r"(a[AOFF + 2][1]), "r"(a[AOFF + 2][2]), "r"(a[AOFF + 2][3]), "r"(a[AOFF + 3][0]), "r"(a[AOFF + 3][1]), "r"(a[AOFF + 3][2]), "r"(a[AOFF + 3][3]), "r"(a[AOFF + 4][0]), "r"(a[AOFF + 4][1]), "r"(a[AOFF + 4][2]), "r"(a[AOFF + 4][3]), "r"(a[AOFF + 5][0]), "r"(a[AOFF + 5][1]), "r"(a[AOFF + 5][2]), "r"(a[AOFF + 5][3]), "l"(descB), "n"(BOFF >> 4));
}

template <int BOFF, int AOFF, int NA>
__device__ __forceinline__ void mma_v_b(float (&d)[48], const uint32_t (&a)[NA][4], uint64_t descB) {
    asm volatile(
        "{\n"
        ".reg .pred p0, p1;\n"
        ".reg .b64 ta, ta0, tb, tb0;\n"
        "setp.ne.b32 p0, 0, 0;\n"
        "setp.eq.b32 p1, 0, 0;\n"
        "add.s64 tb0, %72, %73;\n"
        "add.s64 tb, tb0, 192;\n"
        "wgmma.mma_async.sync.aligned.m64n96k16.f32.bf16.bf16 {%0, %1, %2, %3, %4, %5, %6, %7, %8, %9, %10, %11, %12, %13, %14, %15, %16, %17, %18, %19, %20, %21, %22, %23, %24, %25, %26, %27, %28, %29, %30, %31, %32, %33, %34, %35, %36, %37, %38, %39, %40, %41, %42, %43, %44, %45, %46, %47}, {%48, %49, %50, %51}, tb, p1, 1, 1, 1;\n"
        "add.s64 tb, tb0, 224;\n"
        "wgmma.mma_async.sync.aligned.m64n96k16.f32.bf16.bf16 {%0, %1, %2, %3, %4, %5, %6, %7, %8, %9, %10, %11, %12, %13, %14, %15, %16, %17, %18, %19, %20, %21, %22, %23, %24, %25, %26, %27, %28, %29, %30, %31, %32, %33, %34, %35, %36, %37, %38, %39, %40, %41, %42, %43, %44, %45, %46, %47}, {%52, %53, %54, %55}, tb, p1, 1, 1, 1;\n"
        "add.s64 tb, tb0, 256;\n"
        "wgmma.mma_async.sync.aligned.m64n96k16.f32.bf16.bf16 {%0, %1, %2, %3, %4, %5, %6, %7, %8, %9, %10, %11, %12, %13, %14, %15, %16, %17, %18, %19, %20, %21, %22, %23, %24, %25, %26, %27, %28, %29, %30, %31, %32, %33, %34, %35, %36, %37, %38, %39, %40, %41, %42, %43, %44, %45, %46, %47}, {%56, %57, %58, %59}, tb, p1, 1, 1, 1;\n"
        "add.s64 tb, tb0, 288;\n"
        "wgmma.mma_async.sync.aligned.m64n96k16.f32.bf16.bf16 {%0, %1, %2, %3, %4, %5, %6, %7, %8, %9, %10, %11, %12, %13, %14, %15, %16, %17, %18, %19, %20, %21, %22, %23, %24, %25, %26, %27, %28, %29, %30, %31, %32, %33, %34, %35, %36, %37, %38, %39, %40, %41, %42, %43, %44, %45, %46, %47}, {%60, %61, %62, %63}, tb, p1, 1, 1, 1;\n"
        "add.s64 tb, tb0, 320;\n"
        "wgmma.mma_async.sync.aligned.m64n96k16.f32.bf16.bf16 {%0, %1, %2, %3, %4, %5, %6, %7, %8, %9, %10, %11, %12, %13, %14, %15, %16, %17, %18, %19, %20, %21, %22, %23, %24, %25, %26, %27, %28, %29, %30, %31, %32, %33, %34, %35, %36, %37, %38, %39, %40, %41, %42, %43, %44, %45, %46, %47}, {%64, %65, %66, %67}, tb, p1, 1, 1, 1;\n"
        "add.s64 tb, tb0, 352;\n"
        "wgmma.mma_async.sync.aligned.m64n96k16.f32.bf16.bf16 {%0, %1, %2, %3, %4, %5, %6, %7, %8, %9, %10, %11, %12, %13, %14, %15, %16, %17, %18, %19, %20, %21, %22, %23, %24, %25, %26, %27, %28, %29, %30, %31, %32, %33, %34, %35, %36, %37, %38, %39, %40, %41, %42, %43, %44, %45, %46, %47}, {%68, %69, %70, %71}, tb, p1, 1, 1, 1;\n"
        "}\n"
        : "+f"(d[0]), "+f"(d[1]), "+f"(d[2]), "+f"(d[3]), "+f"(d[4]), "+f"(d[5]), "+f"(d[6]), "+f"(d[7]), "+f"(d[8]), "+f"(d[9]), "+f"(d[10]), "+f"(d[11]), "+f"(d[12]), "+f"(d[13]), "+f"(d[14]), "+f"(d[15]), "+f"(d[16]), "+f"(d[17]), "+f"(d[18]), "+f"(d[19]), "+f"(d[20]), "+f"(d[21]), "+f"(d[22]), "+f"(d[23]), "+f"(d[24]), "+f"(d[25]), "+f"(d[26]), "+f"(d[27]), "+f"(d[28]), "+f"(d[29]), "+f"(d[30]), "+f"(d[31]), "+f"(d[32]), "+f"(d[33]), "+f"(d[34]), "+f"(d[35]), "+f"(d[36]), "+f"(d[37]), "+f"(d[38]), "+f"(d[39]), "+f"(d[40]), "+f"(d[41]), "+f"(d[42]), "+f"(d[43]), "+f"(d[44]), "+f"(d[45]), "+f"(d[46]), "+f"(d[47])
        : "r"(a[AOFF + 0][0]), "r"(a[AOFF + 0][1]), "r"(a[AOFF + 0][2]), "r"(a[AOFF + 0][3]), "r"(a[AOFF + 1][0]), "r"(a[AOFF + 1][1]), "r"(a[AOFF + 1][2]), "r"(a[AOFF + 1][3]), "r"(a[AOFF + 2][0]), "r"(a[AOFF + 2][1]), "r"(a[AOFF + 2][2]), "r"(a[AOFF + 2][3]), "r"(a[AOFF + 3][0]), "r"(a[AOFF + 3][1]), "r"(a[AOFF + 3][2]), "r"(a[AOFF + 3][3]), "r"(a[AOFF + 4][0]), "r"(a[AOFF + 4][1]), "r"(a[AOFF + 4][2]), "r"(a[AOFF + 4][3]), "r"(a[AOFF + 5][0]), "r"(a[AOFF + 5][1]), "r"(a[AOFF + 5][2]), "r"(a[AOFF + 5][3]), "l"(descB), "n"(BOFF >> 4));
}

template <int BOFF, int AOFF, int NA>
__device__ __forceinline__ void mma_w_a(float (&d)[48], const uint32_t (&a)[NA][4], uint64_t descB) {
    asm volatile(
        "{\n"
        ".reg .pred p0, p1;\n"
        ".reg .b64 ta, ta0, tb, tb0;\n"
        "setp.ne.b32 p0, 0, 0;\n"
        "setp.eq.b32 p1, 0, 0;\n"
        "add.s64 tb0, %72, %73;\n"
        "add.s64 tb, tb0, 0;\n"
        "wgmma.mma_async.sync.aligned.m64n96k16.f32.bf16.bf16 {%0, %1, %2, %3, %4, %5, %6, %7, %8, %9, %10, %11, %12, %13, %14, %15, %16, %17, %18, %19, %20, %21, %22, %23, %24, %25, %26, %27, %28, %29, %30, %31, %32, %33, %34, %35, %36, %37, %38, %39, %40, %41, %42, %43, %44, %45, %46, %47}, {%48, %49, %50, %51}, tb, p0, 1, 1, 1;\n"
        "add.s64 tb, tb0, 64;\n"
        "wgmma.mma_async.sync.aligned.m64n96k16.f32.bf16.bf16 {%0, %1, %2, %3, %4, %5, %6, %7, %8, %9, %10, %11, %12, %13, %14, %15, %16, %17, %18, %19, %20, %21, %22, %23, %24, %25, %26, %27, %28, %29, %30, %31, %32, %33, %34, %35, %36, %37, %38, %39, %40, %41, %42, %43, %44, %45, %46, %47}, {%52, %53, %54, %55}, tb, p1, 1, 1, 1;\n"
        "add.s64 tb, tb0, 128;\n"
        "wgmma.mma_async.sync.aligned.m64n96k16.f32.bf16.bf16 {%0, %1, %2, %3, %4, %5, %6, %7, %8, %9, %10, %11, %12, %13, %14, %15, %16, %17, %18, %19, %20, %21, %22, %23, %24, %25, %26, %27, %28, %29, %30, %31, %32, %33, %34, %35, %36, %37, %38, %39, %40, %41, %42, %43, %44, %45, %46, %47}, {%56, %57, %58, %59}, tb, p1, 1, 1, 1;\n"
        "add.s64 tb, tb0, 192;\n"
        "wgmma.mma_async.sync.aligned.m64n96k16.f32.bf16.bf16 {%0, %1, %2, %3, %4, %5, %6, %7, %8, %9, %10, %11, %12, %13, %14, %15, %16, %17, %18, %19, %20, %21, %22, %23, %24, %25, %26, %27, %28, %29, %30, %31, %32, %33, %34, %35, %36, %37, %38, %39, %40, %41, %42, %43, %44, %45, %46, %47}, {%60, %61, %62, %63}, tb, p1, 1, 1, 1;\n"
        "add.s64 tb, tb0, 256;\n"
        "wgmma.mma_async.sync.aligned.m64n96k16.f32.bf16.bf16 {%0, %1, %2, %3, %4, %5, %6, %7, %8, %9, %10, %11, %12, %13, %14, %15, %16, %17, %18, %19, %20, %21, %22, %23, %24, %25, %26, %27, %28, %29, %30, %31, %32, %33, %34, %35, %36, %37, %38, %39, %40, %41, %42, %43, %44, %45, %46, %47}, {%64, %65, %66, %67}, tb, p1, 1, 1, 1;\n"
        "add.s64 tb, tb0, 320;\n"
        "wgmma.mma_async.sync.aligned.m64n96k16.f32.bf16.bf16 {%0, %1, %2, %3, %4, %5, %6, %7, %8, %9, %10, %11, %12, %13, %14, %15, %16, %17, %18, %19, %20, %21, %22, %23, %24, %25, %26, %27, %28, %29, %30, %31, %32, %33, %34, %35, %36, %37, %38, %39, %40, %41, %42, %43, %44, %45, %46, %47}, {%68, %69, %70, %71}, tb, p1, 1, 1, 1;\n"
        "}\n"
        : "=f"(d[0]), "=f"(d[1]), "=f"(d[2]), "=f"(d[3]), "=f"(d[4]), "=f"(d[5]), "=f"(d[6]), "=f"(d[7]), "=f"(d[8]), "=f"(d[9]), "=f"(d[10]), "=f"(d[11]), "=f"(d[12]), "=f"(d[13]), "=f"(d[14]), "=f"(d[15]), "=f"(d[16]), "=f"(d[17]), "=f"(d[18]), "=f"(d[19]), "=f"(d[20]), "=f"(d[21]), "=f"(d[22]), "=f"(d[23]), "=f"(d[24]), "=f"(d[25]), "=f"(d[26]), "=f"(d[27]), "=f"(d[28]), "=f"(d[29]), "=f"(d[30]), "=f"(d[31]), "=f"(d[32]), "=f"(d[33]), "=f"(d[34]), "=f"(d[35]), "=f"(d[36]), "=f"(d[37]), "=f"(d[38]), "=f"(d[39]), "=f"(d[40]), "=f"(d[41]), "=f"(d[42]), "=f"(d[43]), "=f"(d[44]), "=f"(d[45]), "=f"(d[46]), "=f"(d[47])
        : "r"(a[AOFF + 0][0]), "r"(a[AOFF + 0][1]), "r"(a[AOFF + 0][2]), "r"(a[AOFF + 0][3]), "r"(a[AOFF + 1][0]), "r"(a[AOFF + 1][1]), "r"(a[AOFF + 1][2]), "r"(a[AOFF + 1][3]), "r"(a[AOFF + 2][0]), "r"(a[AOFF + 2][1]), "r"(a[AOFF + 2][2]), "r"(a[AOFF + 2][3]), "r"(a[AOFF + 3][0]), "r"(a[AOFF + 3][1]), "r"(a[AOFF + 3][2]), "r"(a[AOFF + 3][3]), "r"(a[AOFF + 4][0]), "r"(a[AOFF + 4][1]), "r"(a[AOFF + 4][2]), "r"(a[AOFF + 4][3]), "r"(a[AOFF + 5][0]), "r"(a[AOFF + 5][1]), "r"(a[AOFF + 5][2]), "r"(a[AOFF + 5][3]), "l"(descB), "n"(BOFF >> 4));
}

template <int BOFF, int AOFF, int NA>
__device__ __forceinline__ void mma_w_b(float (&d)[48], const uint32_t (&a)[NA][4], uint64_t descB) {
    asm volatile(
        "{\n"
        ".reg .pred p0, p1;\n"
        ".reg .b64 ta, ta0, tb, tb0;\n"
        "setp.ne.b32 p0, 0, 0;\n"
        "setp.eq.b32 p1, 0, 0;\n"
        "add.s64 tb0, %72, %73;\n"
        "add.s64 tb, tb0, 384;\n"
        "wgmma.mma_async.sync.aligned.m64n96k16.f32.bf16.bf16 {%0, %1, %2, %3, %4, %5, %6, %7, %8, %9, %10, %11, %12, %13, %14, %15, %16, %17, %18, %19, %20, %21, %22, %23, %24, %25, %26, %27, %28, %29, %30, %31, %32, %33, %34, %35, %36, %37, %38, %39, %40, %41, %42, %43, %44, %45, %46, %47}, {%48, %49, %50, %51}, tb, p1, 1, 1, 1;\n"
        "add.s64 tb, tb0, 448;\n"
        "wgmma.mma_async.sync.aligned.m64n96k16.f32.bf16.bf16 {%0, %1, %2, %3, %4, %5, %6, %7, %8, %9, %10, %11, %12, %13, %14, %15, %16, %17, %18, %19, %20, %21, %22, %23, %24, %25, %26, %27, %28, %29, %30, %31, %32, %33, %34, %35, %36, %37, %38, %39, %40, %41, %42, %43, %44, %45, %46, %47}, {%52, %53, %54, %55}, tb, p1, 1, 1, 1;\n"
        "add.s64 tb, tb0, 512;\n"
        "wgmma.mma_async.sync.aligned.m64n96k16.f32.bf16.bf16 {%0, %1, %2, %3, %4, %5, %6, %7, %8, %9, %10, %11, %12, %13, %14, %15, %16, %17, %18, %19, %20, %21, %22, %23, %24, %25, %26, %27, %28, %29, %30, %31, %32, %33, %34, %35, %36, %37, %38, %39, %40, %41, %42, %43, %44, %45, %46, %47}, {%56, %57, %58, %59}, tb, p1, 1, 1, 1;\n"
        "add.s64 tb, tb0, 576;\n"
        "wgmma.mma_async.sync.aligned.m64n96k16.f32.bf16.bf16 {%0, %1, %2, %3, %4, %5, %6, %7, %8, %9, %10, %11, %12, %13, %14, %15, %16, %17, %18, %19, %20, %21, %22, %23, %24, %25, %26, %27, %28, %29, %30, %31, %32, %33, %34, %35, %36, %37, %38, %39, %40, %41, %42, %43, %44, %45, %46, %47}, {%60, %61, %62, %63}, tb, p1, 1, 1, 1;\n"
        "add.s64 tb, tb0, 640;\n"
        "wgmma.mma_async.sync.aligned.m64n96k16.f32.bf16.bf16 {%0, %1, %2, %3, %4, %5, %6, %7, %8, %9, %10, %11, %12, %13, %14, %15, %16, %17, %18, %19, %20, %21, %22, %23, %24, %25, %26, %27, %28, %29, %30, %31, %32, %33, %34, %35, %36, %37, %38, %39, %40, %41, %42, %43, %44, %45, %46, %47}, {%64, %65, %66, %67}, tb, p1, 1, 1, 1;\n"
        "add.s64 tb, tb0, 704;\n"
        "wgmma.mma_async.sync.aligned.m64n96k16.f32.bf16.bf16 {%0, %1, %2, %3, %4, %5, %6, %7, %8, %9, %10, %11, %12, %13, %14, %15, %16, %17, %18, %19, %20, %21, %22, %23, %24, %25, %26, %27, %28, %29, %30, %31, %32, %33, %34, %35, %36, %37, %38, %39, %40, %41, %42, %43, %44, %45, %46, %47}, {%68, %69, %70, %71}, tb, p1, 1, 1, 1;\n"
        "}\n"
        : "+f"(d[0]), "+f"(d[1]), "+f"(d[2]), "+f"(d[3]), "+f"(d[4]), "+f"(d[5]), "+f"(d[6]), "+f"(d[7]), "+f"(d[8]), "+f"(d[9]), "+f"(d[10]), "+f"(d[11]), "+f"(d[12]), "+f"(d[13]), "+f"(d[14]), "+f"(d[15]), "+f"(d[16]), "+f"(d[17]), "+f"(d[18]), "+f"(d[19]), "+f"(d[20]), "+f"(d[21]), "+f"(d[22]), "+f"(d[23]), "+f"(d[24]), "+f"(d[25]), "+f"(d[26]), "+f"(d[27]), "+f"(d[28]), "+f"(d[29]), "+f"(d[30]), "+f"(d[31]), "+f"(d[32]), "+f"(d[33]), "+f"(d[34]), "+f"(d[35]), "+f"(d[36]), "+f"(d[37]), "+f"(d[38]), "+f"(d[39]), "+f"(d[40]), "+f"(d[41]), "+f"(d[42]), "+f"(d[43]), "+f"(d[44]), "+f"(d[45]), "+f"(d[46]), "+f"(d[47])
        : "r"(a[AOFF + 0][0]), "r"(a[AOFF + 0][1]), "r"(a[AOFF + 0][2]), "r"(a[AOFF + 0][3]), "r"(a[AOFF + 1][0]), "r"(a[AOFF + 1][1]), "r"(a[AOFF + 1][2]), "r"(a[AOFF + 1][3]), "r"(a[AOFF + 2][0]), "r"(a[AOFF + 2][1]), "r"(a[AOFF + 2][2]), "r"(a[AOFF + 2][3]), "r"(a[AOFF + 3][0]), "r"(a[AOFF + 3][1]), "r"(a[AOFF + 3][2]), "r"(a[AOFF + 3][3]), "r"(a[AOFF + 4][0]), "r"(a[AOFF + 4][1]), "r"(a[AOFF + 4][2]), "r"(a[AOFF + 4][3]), "r"(a[AOFF + 5][0]), "r"(a[AOFF + 5][1]), "r"(a[AOFF + 5][2]), "r"(a[AOFF + 5][3]), "l"(descB), "n"(BOFF >> 4));
}
template <int V, int S0, int S1> struct Rng;
template <> struct Rng<0, 0, 3> {
template <int BOFF, int AOFF, int NA>
static __device__ __forceinline__ void run(float (&d)[48], const uint32_t (&a)[NA][4], uint64_t descB) {
    asm volatile(
        "{\n"
        ".reg .pred p0, p1;\n"
        ".reg .b64 ta, ta0, tb, tb0;\n"
        "setp.ne.b32 p0, 0, 0;\n"
        "setp.eq.b32 p1, 0, 0;\n"
        "add.s64 tb0, %60, %61;\n"
        "add.s64 tb, tb0, 0;\n"
        "wgmma.mma_async.sync.aligned.m64n96k16.f32.bf16.bf16 {%0, %1, %2, %3, %4, %5, %6, %7, %8, %9, %10, %11, %12, %13, %14, %15, %16, %17, %18, %19, %20, %21, %22, %23, %24, %25, %26, %27, %28, %29, %30, %31, %32, %33, %34, %35, %36, %37, %38, %39, %40, %41, %42, %43, %44, %45, %46, %47}, {%48, %49, %50, %51}, tb, p0, 1, 1, 1;\n"
        "add.s64 tb, tb0, 32;\n"
        "wgmma.mma_async.sync.aligned.m64n96k16.f32.bf16.bf16 {%0, %1, %2, %3, %4, %5, %6, %7, %8, %9, %10, %11, %12, %13, %14, %15, %16, %17, %18, %19, %20, %21, %22, %23, %24, %25, %26, %27, %28, %29, %30, %31, %32, %33, %34, %35, %36, %37, %38, %39, %40, %41, %42, %43, %44, %45, %46, %47}, {%52, %53, %54, %55}, tb, p1, 1, 1, 1;\n"
        "add.s64 tb, tb0, 64;\n"
        "wgmma.mma_async.sync.aligned.m64n96k16.f32.bf16.bf16 {%0, %1, %2, %3, %4, %5, %6, %7, %8, %9, %10, %11, %12, %13, %14, %15, %16, %17, %18, %19, %20, %21, %22, %23, %24, %25, %26, %27, %28, %29, %30, %31, %32, %33, %34, %35, %36, %37, %38, %39, %40, %41, %42, %43, %44, %45, %46, %47}, {%56, %57, %58, %59}, tb, p1, 1, 1, 1;\n"
        "}\n"
        : "=f"(d[0]), "=f"(d[1]), "=f"(d[2]), "=f"(d[3]), "=f"(d[4]), "=f"(d[5]), "=f"(d[6]), "=f"(d[7]), "=f"(d[8]), "=f"(d[9]), "=f"(d[10]), "=f"(d[11]), "=f"(d[12]), "=f"(d[13]), "=f"(d[14]), "=f"(d[15]), "=f"(d[16]), "=f"(d[17]), "=f"(d[18]), "=f"(d[19]), "=f"(d[20]), "=f"(d[21]), "=f"(d[22]), "=f"(d[23]), "=f"(d[24]), "=f"(d[25]), "=f"(d[26]), "=f"(d[27]), "=f"(d[28]), "=f"(d[29]), "=f"(d[30]), "=f"(d[31]), "=f"(d[32]), "=f"(d[33]), "=f"(d[34]), "=f"(d[35]), "=f"(d[36]), "=f"(d[37]), "=f"(d[38]), "=f"(d[39]), "=f"(d[40]), "=f"(d[41]), "=f"(d[42]), "=f"(d[43]), "=f"(d[44]), "=f"(d[45]), "=f"(d[46]), "=f"(d[47])
        : "r"(a[AOFF + 0][0]), "r"(a[AOFF + 0][1]), "r"(a[AOFF + 0][2]), "r"(a[AOFF + 0][3]), "r"(a[AOFF + 1][0]), "r"(a[AOFF + 1][1]), "r"(a[AOFF + 1][2]), "r"(a[AOFF + 1][3]), "r"(a[AOFF + 2][0]), "r"(a[AOFF + 2][1]), "r"(a[AOFF + 2][2]), "r"(a[AOFF + 2][3]), "l"(descB), "n"(BOFF >> 4));
}
};
template <> struct Rng<1, 0, 3> {
template <int BOFF, int AOFF, int NA>
static __device__ __forceinline__ void run(float (&d)[48], const uint32_t (&a)[NA][4], uint64_t descB) {
    asm volatile(
        "{\n"
        ".reg .pred p0, p1;\n"
        ".reg .b64 ta, ta0, tb, tb0;\n"
        "setp.ne.b32 p0, 0, 0;\n"
        "setp.eq.b32 p1, 0, 0;\n"
        "add.s64 tb0, %60, %61;\n"
        "add.s64 tb, tb0, 0;\n"
        "wgmma.mma_async.sync.aligned.m64n96k16.f32.bf16.bf16 {%0, %1, %2, %3, %4, %5, %6, %7, %8, %9, %10, %11, %12, %13, %14, %15, %16, %17, %18, %19, %20, %21, %22, %23, %24, %25, %26, %27, %28, %29, %30, %31, %32, %33, %34, %35, %36, %37, %38, %39, %40, %41, %42, %43, %44, %45, %46, %47}, {%48, %49, %50, %51}, tb, p0, 1, 1, 1;\n"
        "add.s64 tb, tb0, 32;\n"
        "wgmma.mma_async.sync.aligned.m64n96k16.f32.bf16.bf16 {%0, %1, %2, %3, %4, %5, %6, %7, %8, %9, %10, %11, %12, %13, %14, %15, %16, %17, %18, %19, %20, %21, %22, %23, %24, %25, %26, %27, %28, %29, %30, %31, %32, %33, %34, %35, %36, %37, %38, %39, %40, %41, %42, %43, %44, %45, %46, %47}, {%52, %53, %54, %55}, tb, p1, 1, 1, 1;\n"
        "add.s64 tb, tb0, 64;\n"
        "wgmma.mma_async.sync.aligned.m64n96k16.f32.bf16.bf16 {%0, %1, %2, %3, %4, %5, %6, %7, %8, %9, %10, %11, %12, %13, %14, %15, %16, %17, %18, %19, %20, %21, %22, %23, %24, %25, %26, %27, %28, %29, %30, %31, %32, %33, %34, %35, %36, %37, %38, %39, %40, %41, %42, %43, %44, %45, %46, %47}, {%56, %57, %58, %59}, tb, p1, 1, 1, 1;\n"
        "}\n"
        : "=f"(d[0]), "=f"(d[1]), "=f"(d[2]), "=f"(d[3]), "=f"(d[4]), "=f"(d[5]), "=f"(d[6]), "=f"(d[7]), "=f"(d[8]), "=f"(d[9]), "=f"(d[10]), "=f"(d[11]), "=f"(d[12]), "=f"(d[13]), "=f"(d[14]), "=f"(d[15]), "=f"(d[16]), "=f"(d[17]), "=f"(d[18]), "=f"(d[19]), "=f"(d[20]), "=f"(d[21]), "=f"(d[22]), "=f"(d[23]), "=f"(d[24]), "=f"(d[25]), "=f"(d[26]), "=f"(d[27]), "=f"(d[28]), "=f"(d[29]), "=f"(d[30]), "=f"(d[31]), "=f"(d[32]), "=f"(d[33]), "=f"(d[34]), "=f"(d[35]), "=f"(d[36]), "=f"(d[37]), "=f"(d[38]), "=f"(d[39]), "=f"(d[40]), "=f"(d[41]), "=f"(d[42]), "=f"(d[43]), "=f"(d[44]), "=f"(d[45]), "=f"(d[46]), "=f"(d[47])
        : "r"(a[AOFF + 0][0]), "r"(a[AOFF + 0][1]), "r"(a[AOFF + 0][2]), "r"(a[AOFF + 0][3]), "r"(a[AOFF + 1][0]), "r"(a[AOFF + 1][1]), "r"(a[AOFF + 1][2]), "r"(a[AOFF + 1][3]), "r"(a[AOFF + 2][0]), "r"(a[AOFF + 2][1]), "r"(a[AOFF + 2][2]), "r"(a[AOFF + 2][3]), "l"(descB), "n"(BOFF >> 4));
}
};
template <> struct Rng<0, 0, 4> {
template <int BOFF, int AOFF, int NA>
static __device__ __forceinline__ void run(float (&d)[48], const uint32_t (&a)[NA][4], uint64_t descB) {
    asm volatile(
        "{\n"
        ".reg .pred p0, p1;\n"
        ".reg .b64 ta, ta0, tb, tb0;\n"
        "setp.ne.b32 p0, 0, 0;\n"
        "setp.eq.b32 p1, 0, 0;\n"
        "add.s64 tb0, %64, %65;\n"
        "add.s64 tb, tb0, 0;\n"
        "wgmma.mma_async.sync.aligned.m64n96k16.f32.bf16.bf16 {%0, %1, %2, %3, %4, %5, %6, %7, %8, %9, %10, %11, %12, %13, %14, %15, %16, %17, %18, %19, %20, %21, %22, %23, %24, %25, %26, %27, %28, %29, %30, %31, %32, %33, %34, %35, %36, %37, %38, %39, %40, %41, %42, %43, %44, %45, %46, %47}, {%48, %49, %50, %51}, tb, p0, 1, 1, 1;\n"
        "add.s64 tb, tb0, 32;\n"
        "wgmma.mma_async.sync.aligned.m64n96k16.f32.bf16.bf16 {%0, %1, %2, %3, %4, %5, %6, %7, %8, %9, %10, %11, %12, %13, %14, %15, %16, %17, %18, %19, %20, %21, %22, %23, %24, %25, %26, %27, %28, %29, %30, %31, %32, %33, %34, %35, %36, %37, %38, %39, %40, %41, %42, %43, %44, %45, %46, %47}, {%52, %53, %54, %55}, tb, p1, 1, 1, 1;\n"
        "add.s64 tb, tb0, 64;\n"
        "wgmma.mma_async.sync.aligned.m64n96k16.f32.bf16.bf16 {%0, %1, %2, %3, %4, %5, %6, %7, %8, %9, %10, %11, %12, %13, %14, %15, %16, %17, %18, %19, %20, %21, %22, %23, %24, %25, %26, %27, %28, %29, %30, %31, %32, %33, %34, %35, %36, %37, %38, %39, %40, %41, %42, %43, %44, %45, %46, %47}, {%56, %57, %58, %59}, tb, p1, 1, 1, 1;\n"
        "add.s64 tb, tb0, 96;\n"
        "wgmma.mma_async.sync.aligned.m64n96k16.f32.bf16.bf16 {%0, %1, %2, %3, %4, %5, %6, %7, %8, %9, %10, %11, %12, %13, %14, %15, %16, %17, %18, %19, %20, %21, %22, %23, %24, %25, %26, %27, %28, %29, %30, %31, %32, %33, %34, %35, %36, %37, %38, %39, %40, %41, %42, %43, %44, %45, %46, %47}, {%60, %61, %62, %63}, tb, p1, 1, 1, 1;\n"
        "}\n"
        : "=f"(d[0]), "=f"(d[1]), "=f"(d[2]), "=f"(d[3]), "=f"(d[4]), "=f"(d[5]), "=f"(d[6]), "=f"(d[7]), "=f"(d[8]), "=f"(d[9]), "=f"(d[10]), "=f"(d[11]), "=f"(d[12]), "=f"(d[13]), "=f"(d[14]), "=f"(d[15]), "=f"(d[16]), "=f"(d[17]), "=f"(d[18]), "=f"(d[19]), "=f"(d[20]), "=f"(d[21]), "=f"(d[22]), "=f"(d[23]), "=f"(d[24]), "=f"(d[25]), "=f"(d[26]), "=f"(d[27]), "=f"(d[28]), "=f"(d[29]), "=f"(d[30]), "=f"(d[31]), "=f"(d[32]), "=f"(d[33]), "=f"(d[34]), "=f"(d[35]), "=f"(d[36]), "=f"(d[37]), "=f"(d[38]), "=f"(d[39]), "=f"(d[40]), "=f"(d[41]), "=f"(d[42]), "=f"(d[43]), "=f"(d[44]), "=f"(d[45]), "=f"(d[46]), "=f"(d[47])
        : "r"(a[AOFF + 0][0]), "r"(a[AOFF + 0][1]), "r"(a[AOFF + 0][2]), "r"(a[AOFF + 0][3]), "r"(a[AOFF + 1][0]), "r"(a[AOFF + 1][1]), "r"(a[AOFF + 1][2]), "r"(a[AOFF + 1][3]), "r"(a[AOFF + 2][0]), "r"(a[AOFF + 2][1]), "r"(a[AOFF + 2][2]), "r"(a[AOFF + 2][3]), "r"(a[AOFF + 3][0]), "r"(a[AOFF + 3][1]), "r"(a[AOFF + 3][2]), "r"(a[AOFF + 3][3]), "l"(descB), "n"(BOFF >> 4));
}
};
template <> struct Rng<1, 0, 4> {
template <int BOFF, int AOFF, int NA>
static __device__ __forceinline__ void run(float (&d)[48], const uint32_t (&a)[NA][4], uint64_t descB) {
    asm volatile(
        "{\n"
        ".reg .pred p0, p1;\n"
        ".reg .b64 ta, ta0, tb, tb0;\n"
        "setp.ne.b32 p0, 0, 0;\n"
        "setp.eq.b32 p1, 0, 0;\n"
        "add.s64 tb0, %64, %65;\n"
        "add.s64 tb, tb0, 0;\n"
        "wgmma.mma_async.sync.aligned.m64n96k16.f32.bf16.bf16 {%0, %1, %2, %3, %4, %5, %6, %7, %8, %9, %10, %11, %12, %13, %14, %15, %16, %17, %18, %19, %20, %21, %22, %23, %24, %25, %26, %27, %28, %29, %30, %31, %32, %33, %34, %35, %36, %37, %38, %39, %40, %41, %42, %43, %44, %45, %46, %47}, {%48, %49, %50, %51}, tb, p0, 1, 1, 1;\n"
        "add.s64 tb, tb0, 32;\n"
        "wgmma.mma_async.sync.aligned.m64n96k16.f32.bf16.bf16 {%0, %1, %2, %3, %4, %5, %6, %7, %8, %9, %10, %11, %12, %13, %14, %15, %16, %17, %18, %19, %20, %21, %22, %23, %24, %25, %26, %27, %28, %29, %30, %31, %32, %33, %34, %35, %36, %37, %38, %39, %40, %41, %42, %43, %44, %45, %46, %47}, {%52, %53, %54, %55}, tb, p1, 1, 1, 1;\n"
        "add.s64 tb, tb0, 64;\n"
        "wgmma.mma_async.sync.aligned.m64n96k16.f32.bf16.bf16 {%0, %1, %2, %3, %4, %5, %6, %7, %8, %9, %10, %11, %12, %13, %14, %15, %16, %17, %18, %19, %20, %21, %22, %23, %24, %25, %26, %27, %28, %29, %30, %31, %32, %33, %34, %35, %36, %37, %38, %39, %40, %41, %42, %43, %44, %45, %46, %47}, {%56, %57, %58, %59}, tb, p1, 1, 1, 1;\n"
        "add.s64 tb, tb0, 96;\n"
        "wgmma.mma_async.sync.aligned.m64n96k16.f32.bf16.bf16 {%0, %1, %2, %3, %4, %5, %6, %7, %8, %9, %10, %11, %12, %13, %14, %15, %16, %17, %18, %19, %20, %21, %22, %23, %24, %25, %26, %27, %28, %29, %30, %31, %32, %33, %34, %35, %36, %37, %38, %39, %40, %41, %42, %43, %44, %45, %46, %47}, {%60, %61, %62, %63}, tb, p1, 1, 1, 1;\n"
        "}\n"
        : "=f"(d[0]), "=f"(d[1]), "=f"(d[2]), "=f"(d[3]), "=f"(d[4]), "=f"(d[5]), "=f"(d[6]), "=f"(d[7]), "=f"(d[8]), "=f"(d[9]), "=f"(d[10]), "=f"(d[11]), "=f"(d[12]), "=f"(d[13]), "=f"(d[14]), "=f"(d[15]), "=f"(d[16]), "=f"(d[17]), "=f"(d[18]), "=f"(d[19]), "=f"(d[20]), "=f"(d[21]), "=f"(d[22]), "=f"(d[23]), "=f"(d[24]), "=f"(d[25]), "=f"(d[26]), "=f"(d[27]), "=f"(d[28]), "=f"(d[29]), "=f"(d[30]), "=f"(d[31]), "=f"(d[32]), "=f"(d[33]), "=f"(d[34]), "=f"(d[35]), "=f"(d[36]), "=f"(d[37]), "=f"(d[38]), "=f"(d[39]), "=f"(d[40]), "=f"(d[41]), "=f"(d[42]), "=f"(d[43]), "=f"(d[44]), "=f"(d[45]), "=f"(d[46]), "=f"(d[47])
        : "r"(a[AOFF + 0][0]), "r"(a[AOFF + 0][1]), "r"(a[AOFF + 0][2]), "r"(a[AOFF + 0][3]), "r"(a[AOFF + 1][0]), "r"(a[AOFF + 1][1]), "r"(a[AOFF + 1][2]), "r"(a[AOFF + 1][3]), "r"(a[AOFF + 2][0]), "r"(a[AOFF + 2][1]), "r"(a[AOFF + 2][2]), "r"(a[AOFF + 2][3]), "r"(a[AOFF + 3][0]), "r"(a[AOFF + 3][1]), "r"(a[AOFF + 3][2]), "r"(a[AOFF + 3][3]), "l"(descB), "n"(BOFF >> 4));
}
};
template <> struct Rng<0, 0, 5> {
template <int BOFF, int AOFF, int NA>
static __device__ __forceinline__ void run(float (&d)[48], const uint32_t (&a)[NA][4], uint64_t descB) {
    asm volatile(
        "{\n"
        ".reg .pred p0, p1;\n"
        ".reg .b64 ta, ta0, tb, tb0;\n"
        "setp.ne.b32 p0, 0, 0;\n"
        "setp.eq.b32 p1, 0, 0;\n"
        "add.s64 tb0, %68, %69;\n"
        "add.s64 tb, tb0, 0;\n"
        "wgmma.mma_async.sync.aligned.m64n96k16.f32.bf16.bf16 {%0, %1, %2, %3, %4, %5, %6, %7, %8, %9, %10, %11, %12, %13, %14, %15, %16, %17, %18, %19, %20, %21, %22, %23, %24, %25, %26, %27, %28, %29, %30, %31, %32, %33, %34, %35, %36, %37, %38, %39, %40, %41, %42, %43, %44, %45, %46, %47}, {%48, %49, %50, %51}, tb, p0, 1, 1, 1;\n"
        "add.s64 tb, tb0, 32;\n"
        "wgmma.mma_async.sync.aligned.m64n96k16.f32.bf16.bf16 {%0, %1, %2, %3, %4, %5, %6, %7, %8, %9, %10, %11, %12, %13, %14, %15, %16, %17, %18, %19, %20, %21, %22, %23, %24, %25, %26, %27, %28, %29, %30, %31, %32, %33, %34, %35, %36, %37, %38, %39, %40, %41, %42, %43, %44, %45, %46, %47}, {%52, %53, %54, %55}, tb, p1, 1, 1, 1;\n"
        "add.s64 tb, tb0, 64;\n"
        "wgmma.mma_async.sync.aligned.m64n96k16.f32.bf16.bf16 {%0, %1, %2, %3, %4, %5, %6, %7, %8, %9, %10, %11, %12, %13, %14, %15, %16, %17, %18, %19, %20, %21, %22, %23, %24, %25, %26, %27, %28, %29, %30, %31, %32, %33, %34, %35, %36, %37, %38, %39, %40, %41, %42, %43, %44, %45, %46, %47}, {%56, %57, %58, %59}, tb, p1, 1, 1, 1;\n"
        "add.s64 tb, tb0, 96;\n"
        "wgmma.mma_async.sync.aligned.m64n96k16.f32.bf16.bf16 {%0, %1, %2, %3, %4, %5, %6, %7, %8, %9, %10, %11, %12, %13, %14, %15, %16, %17, %18, %19, %20, %21, %22, %23, %24, %25, %26, %27, %28, %29, %30, %31, %32, %33, %34, %35, %36, %37, %38, %39, %40, %41, %42, %43, %44, %45, %46, %47}, {%60, %61, %62, %63}, tb, p1, 1, 1, 1;\n"
        "add.s64 tb, tb0, 1536;\n"
        "wgmma.mma_async.sync.aligned.m64n96k16.f32.bf16.bf16 {%0, %1, %2, %3, %4, %5, %6, %7, %8, %9, %10, %11, %12, %13, %14, %15, %16, %17, %18, %19, %20, %21, %22, %23, %24, %25, %26, %27, %28, %29, %30, %31, %32, %33, %34, %35, %36, %37, %38, %39, %40, %41, %42, %43, %44, %45, %46, %47}, {%64, %65, %66, %67}, tb, p1, 1, 1, 1;\n"
        "}\n"
        : "=f"(d[0]), "=f"(d[1]), "=f"(d[2]), "=f"(d[3]), "=f"(d[4]), "=f"(d[5]), "=f"(d[6]), "=f"(d[7]), "=f"(d[8]), "=f"(d[9]), "=f"(d[10]), "=f"(d[11]), "=f"(d[12]), "=f"(d[13]), "=f"(d[14]), "=f"(d[15]), "=f"(d[16]), "=f"(d[17]), "=f"(d[18]), "=f"(d[19]), "=f"(d[20]), "=f"(d[21]), "=f"(d[22]), "=f"(d[23]), "=f"(d[24]), "=f"(d[25]), "=f"(d[26]), "=f"(d[27]), "=f"(d[28]), "=f"(d[29]), "=f"(d[30]), "=f"(d[31]), "=f"(d[32]), "=f"(d[33]), "=f"(d[34]), "=f"(d[35]), "=f"(d[36]), "=f"(d[37]), "=f"(d[38]), "=f"(d[39]), "=f"(d[40]), "=f"(d[41]), "=f"(d[42]), "=f"(d[43]), "=f"(d[44]), "=f"(d[45]), "=f"(d[46]), "=f"(d[47])
        : "r"(a[AOFF + 0][0]), "r"(a[AOFF + 0][1]), "r"(a[AOFF + 0][2]), "r"(a[AOFF + 0][3]), "r"(a[AOFF + 1][0]), "r"(a[AOFF + 1][1]), "r"(a[AOFF + 1][2]), "r"(a[AOFF + 1][3]), "r"(a[AOFF + 2][0]), "r"(a[AOFF + 2][1]), "r"(a[AOFF + 2][2]), "r"(a[AOFF + 2][3]), "r"(a[AOFF + 3][0]), "r"(a[AOFF + 3][1]), "r"(a[AOFF + 3][2]), "r"(a[AOFF + 3][3]), "r"(a[AOFF + 4][0]), "r"(a[AOFF + 4][1]), "r"(a[AOFF + 4][2]), "r"(a[AOFF + 4][3]), "l"(descB), "n"(BOFF >> 4));
}
};
template <> struct Rng<1, 0, 5> {
template <int BOFF, int AOFF, int NA>
static __device__ __forceinline__ void run(float (&d)[48], const uint32_t (&a)[NA][4], uint64_t descB) {
    asm volatile(
        "{\n"
        ".reg .pred p0, p1;\n"
        ".reg .b64 ta, ta0, tb, tb0;\n"
        "setp.ne.b32 p0, 0, 0;\n"
        "setp.eq.b32 p1, 0, 0;\n"
        "add.s64 tb0, %68, %69;\n"
        "add.s64 tb, tb0, 0;\n"
        "wgmma.mma_async.sync.aligned.m64n96k16.f32.bf16.bf16 {%0, %1, %2, %3, %4, %5, %6, %7, %8, %9, %10, %11, %12, %13, %14, %15, %16, %17, %18, %19, %20, %21, %22, %23, %24, %25, %26, %27, %28, %29, %30, %31, %32, %33, %34, %35, %36, %37, %38, %39, %40, %41, %42, %43, %44, %45, %46, %47}, {%48, %49, %50, %51}, tb, p0, 1, 1, 1;\n"
        "add.s64 tb, tb0, 32;\n"
        "wgmma.mma_async.sync.aligned.m64n96k16.f32.bf16.bf16 {%0, %1, %2, %3, %4, %5, %6, %7, %8, %9, %10, %11, %12, %13, %14, %15, %16, %17, %18, %19, %20, %21, %22, %23, %24, %25, %26, %27, %28, %29, %30, %31, %32, %33, %34, %35, %36, %37, %38, %39, %40, %41, %42, %43, %44, %45, %46, %47}, {%52, %53, %54, %55}, tb, p1, 1, 1, 1;\n"
        "add.s64 tb, tb0, 64;\n"
        "wgmma.mma_async.sync.aligned.m64n96k16.f32.bf16.bf16 {%0, %1, %2, %3, %4, %5, %6, %7, %8, %9, %10, %11, %12, %13, %14, %15, %16, %17, %18, %19, %20, %21, %22, %23, %24, %25, %26, %27, %28, %29, %30, %31, %32, %33, %34, %35, %36, %37, %38, %39, %40, %41, %42, %43, %44, %45, %46, %47}, {%56, %57, %58, %59}, tb, p1, 1, 1, 1;\n"
        "add.s64 tb, tb0, 96;\n"
        "wgmma.mma_async.sync.aligned.m64n96k16.f32.bf16.bf16 {%0, %1, %2, %3, %4, %5, %6, %7, %8, %9, %10, %11, %12, %13, %14, %15, %16, %17, %18, %19, %20, %21, %22, %23, %24, %25, %26, %27, %28, %29, %30, %31, %32, %33, %34, %35, %36, %37, %38, %39, %40, %41, %42, %43, %44, %45, %46, %47}, {%60, %61, %62, %63}, tb, p1, 1, 1, 1;\n"
        "add.s64 tb, tb0, 128;\n"
        "wgmma.mma_async.sync.aligned.m64n96k16.f32.bf16.bf16 {%0, %1, %2, %3, %4, %5, %6, %7, %8, %9, %10, %11, %12, %13, %14, %15, %16, %17, %18, %19, %20, %21, %22, %23, %24, %25, %26, %27, %28, %29, %30, %31, %32, %33, %34, %35, %36, %37, %38, %39, %40, %41, %42, %43, %44, %45, %46, %47}, {%64, %65, %66, %67}, tb, p1, 1, 1, 1;\n"
        "}\n"
        : "=f"(d[0]), "=f"(d[1]), "=f"(d[2]), "=f"(d[3]), "=f"(d[4]), "=f"(d[5]), "=f"(d[6]), "=f"(d[7]), "=f"(d[8]), "=f"(d[9]), "=f"(d[10]), "=f"(d[11]), "=f"(d[12]), "=f"(d[13]), "=f"(d[14]), "=f"(d[15]), "=f"(d[16]), "=f"(d[17]), "=f"(d[18]), "=f"(d[19]), "=f"(d[20]), "=f"(d[21]), "=f"(d[22]), "=f"(d[23]), "=f"(d[24]), "=f"(d[25]), "=f"(d[26]), "=f"(d[27]), "=f"(d[28]), "=f"(d[29]), "=f"(d[30]), "=f"(d[31]), "=f"(d[32]), "=f"(d[33]), "=f"(d[34]), "=f"(d[35]), "=f"(d[36]), "=f"(d[37]), "=f"(d[38]), "=f"(d[39]), "=f"(d[40]), "=f"(d[41]), "=f"(d[42]), "=f"(d[43]), "=f"(d[44]), "=f"(d[45]), "=f"(d[46]), "=f"(d[47])
        : "r"(a[AOFF + 0][0]), "r"(a[AOFF + 0][1]), "r"(a[AOFF + 0][2]), "r"(a[AOFF + 0][3]), "r"(a[AOFF + 1][0]), "r"(a[AOFF + 1][1]), "r"(a[AOFF + 1][2]), "r"(a[AOFF + 1][3]), "r"(a[AOFF + 2][0]), "r"(a[AOFF + 2][1]), "r"(a[AOFF + 2][2]), "r"(a[AOFF + 2][3]), "r"(a[AOFF + 3][0]), "r"(a[AOFF + 3][1]), "r"(a[AOFF + 3][2]), "r"(a[AOFF + 3][3]), "r"(a[AOFF + 4][0]), "r"(a[AOFF + 4][1]), "r"(a[AOFF + 4][2]), "r"(a[AOFF + 4][3]), "l"(descB), "n"(BOFF >> 4));
}
};
template <> struct Rng<0, 0, 6> {
template <int BOFF, int AOFF, int NA>
static __device__ __forceinline__ void run(float (&d)[48], const uint32_t (&a)[NA][4], uint64_t descB) {
    asm volatile(
        "{\n"
        ".reg .pred p0, p1;\n"
        ".reg .b64 ta, ta0, tb, tb0;\n"
        "setp.ne.b32 p0, 0, 0;\n"
        "setp.eq.b32 p1, 0, 0;\n"
        "add.s64 tb0, %72, %73;\n"
        "add.s64 tb, tb0, 0;\n"
        "wgmma.mma_async.sync.aligned.m64n96k16.f32.bf16.bf16 {%0, %1, %2, %3, %4, %5, %6, %7, %8, %9, %10, %11, %12, %13, %14, %15, %16, %17, %18, %19, %20, %21, %22, %23, %24, %25, %26, %27, %28, %29, %30, %31, %32, %33, %34, %35, %36, %37, %38, %39, %40, %41, %42, %43, %44, %45, %46, %47}, {%48, %49, %50, %51}, tb, p0, 1, 1, 1;\n"
        "add.s64 tb, tb0, 32;\n"
        "wgmma.mma_async.sync.aligned.m64n96k16.f32.bf16.bf16 {%0, %1, %2, %3, %4, %5, %6, %7, %8, %9, %10, %11, %12, %13, %14, %15, %16, %17, %18, %19, %20, %21, %22, %23, %24, %25, %26, %27, %28, %29, %30, %31, %32, %33, %34, %35, %36, %37, %38, %39, %40, %41, %42, %43, %44, %45, %46, %47}, {%52, %53, %54, %55}, tb, p1, 1, 1, 1;\n"
        "add.s64 tb, tb0, 64;\n"
        "wgmma.mma_async.sync.aligned.m64n96k16.f32.bf16.bf16 {%0, %1, %2, %3, %4, %5, %6, %7, %8, %9, %10, %11, %12, %13, %14, %15, %16, %17, %18, %19, %20, %21, %22, %23, %24, %25, %26, %27, %28, %29, %30, %31, %32, %33, %34, %35, %36, %37, %38, %39, %40, %41, %42, %43, %44, %45, %46, %47}, {%56, %57, %58, %59}, tb, p1, 1, 1, 1;\n"
        "add.s64 tb, tb0, 96;\n"
        "wgmma.mma_async.sync.aligned.m64n96k16.f32.bf16.bf16 {%0, %1, %2, %3, %4, %5, %6, %7, %8, %9, %10, %11, %12, %13, %14, %15, %16, %17, %18, %19, %20, %21, %22, %23, %24, %25, %26, %27, %28, %29, %30, %31, %32, %33, %34, %35, %36, %37, %38, %39, %40, %41, %42, %43, %44, %45, %46, %47}, {%60, %61, %62, %63}, tb, p1, 1, 1, 1;\n"
        "add.s64 tb, tb0, 1536;\n"
        "wgmma.mma_async.sync.aligned.m64n96k16.f32.bf16.bf16 {%0, %1, %2, %3, %4, %5, %6, %7, %8, %9, %10, %11, %12, %13, %14, %15, %16, %17, %18, %19, %20, %21, %22, %23, %24, %25, %26, %27, %28, %29, %30, %31, %32, %33, %34, %35, %36, %37, %38, %39, %40, %41, %42, %43, %44, %45, %46, %47}, {%64, %65, %66, %67}, tb, p1, 1, 1, 1;\n"
        "add.s64 tb, tb0, 1568;\n"
        "wgmma.mma_async.sync.aligned.m64n96k16.f32.bf16.bf16 {%0, %1, %2, %3, %4, %5, %6, %7, %8, %9, %10, %11, %12, %13, %14, %15, %16, %17, %18, %19, %20, %21, %22, %23, %24, %25, %26, %27, %28, %29, %30, %31, %32, %33, %34, %35, %36, %37, %38, %39, %40, %41, %42, %43, %44, %45, %46, %47}, {%68, %69, %70, %71}, tb, p1, 1, 1, 1;\n"
        "}\n"
        : "=f"(d[0]), "=f"(d[1]), "=f"(d[2]), "=f"(d[3]), "=f"(d[4]), "=f"(d[5]), "=f"(d[6]), "=f"(d[7]), "=f"(d[8]), "=f"(d[9]), "=f"(d[10]), "=f"(d[11]), "=f"(d[12]), "=f"(d[13]), "=f"(d[14]), "=f"(d[15]), "=f"(d[16]), "=f"(d[17]), "=f"(d[18]), "=f"(d[19]), "=f"(d[20]), "=f"(d[21]), "=f"(d[22]), "=f"(d[23]), "=f"(d[24]), "=f"(d[25]), "=f"(d[26]), "=f"(d[27]), "=f"(d[28]), "=f"(d[29]), "=f"(d[30]), "=f"(d[31]), "=f"(d[32]), "=f"(d[33]), "=f"(d[34]), "=f"(d[35]), "=f"(d[36]), "=f"(d[37]), "=f"(d[38]), "=f"(d[39]), "=f"(d[40]), "=f"(d[41]), "=f"(d[42]), "=f"(d[43]), "=f"(d[44]), "=f"(d[45]), "=f"(d[46]), "=f"(d[47])
        : "r"(a[AOFF + 0][0]), "r"(a[AOFF + 0][1]), "r"(a[AOFF + 0][2]), "r"(a[AOFF + 0][3]), "r"(a[AOFF + 1][0]), "r"(a[AOFF + 1][1]), "r"(a[AOFF + 1][2]), "r"(a[AOFF + 1][3]), "r"(a[AOFF + 2][0]), "r"(a[AOFF + 2][1]), "r"(a[AOFF + 2][2]), "r"(a[AOFF + 2][3]), "r"(a[AOFF + 3][0]), "r"(a[AOFF + 3][1]), "r"(a[AOFF + 3][2]), "r"(a[AOFF + 3][3]), "r"(a[AOFF + 4][0]), "r"(a[AOFF + 4][1]), "r"(a[AOFF + 4][2]), "r"(a[AOFF + 4][3]), "r"(a[AOFF + 5][0]), "r"(a[AOFF + 5][1]), "r"(a[AOFF + 5][2]), "r"(a[AOFF + 5][3]), "l"(descB), "n"(BOFF >> 4));
}
};
template <> struct Rng<1, 0, 6> {
template <int BOFF, int AOFF, int NA>
static __device__ __forceinline__ void run(float (&d)[48], const uint32_t (&a)[NA][4], uint64_t descB) {
    asm volatile(
        "{\n"
        ".reg .pred p0, p1;\n"
        ".reg .b64 ta, ta0, tb, tb0;\n"
        "setp.ne.b32 p0, 0, 0;\n"
        "setp.eq.b32 p1, 0, 0;\n"
        "add.s64 tb0, %72, %73;\n"
        "add.s64 tb, tb0, 0;\n"
        "wgmma.mma_async.sync.aligned.m64n96k16.f32.bf16.bf16 {%0, %1, %2, %3, %4, %5, %6, %7, %8, %9, %10, %11, %12, %13, %14, %15, %16, %17, %18, %19, %20, %21, %22, %23, %24, %25, %26, %27, %28, %29, %30, %31, %32, %33, %34, %35, %36, %37, %38, %39, %40, %41, %42, %43, %44, %45, %46, %47}, {%48, %49, %50, %51}, tb, p0, 1, 1, 1;\n"
        "add.s64 tb, tb0, 32;\n"
        "wgmma.mma_async.sync.aligned.m64n96k16.f32.bf16.bf16 {%0, %1, %2, %3, %4, %5, %6, %7, %8, %9, %10, %11, %12, %13, %14, %15, %16, %17, %18, %19, %20, %21, %22, %23, %24, %25, %26, %27, %28, %29, %30, %31, %32, %33, %34, %35, %36, %37, %38, %39, %40, %41, %42, %43, %44, %45, %46, %47}, {%52, %53, %54, %55}, tb, p1, 1, 1, 1;\n"
        "add.s64 tb, tb0, 64;\n"
        "wgmma.mma_async.sync.aligned.m64n96k16.f32.bf16.bf16 {%0, %1, %2, %3, %4, %5, %6, %7, %8, %9, %10, %11, %12, %13, %14, %15, %16, %17, %18, %19, %20, %21, %22, %23, %24, %25, %26, %27, %28, %29, %30, %31, %32, %33, %34, %35, %36, %37, %38, %39, %40, %41, %42, %43, %44, %45, %46, %47}, {%56, %57, %58, %59}, tb, p1, 1, 1, 1;\n"
        "add.s64 tb, tb0, 96;\n"
        "wgmma.mma_async.sync.aligned.m64n96k16.f32.bf16.bf16 {%0, %1, %2, %3, %4, %5, %6, %7, %8, %9, %10, %11, %12, %13, %14, %15, %16, %17, %18, %19, %20, %21, %22, %23, %24, %25, %26, %27, %28, %29, %30, %31, %32, %33, %34, %35, %36, %37, %38, %39, %40, %41, %42, %43, %44, %45, %46, %47}, {%60, %61, %62, %63}, tb, p1, 1, 1, 1;\n"
        "add.s64 tb, tb0, 128;\n"
        "wgmma.mma_async.sync.aligned.m64n96k16.f32.bf16.bf16 {%0, %1, %2, %3, %4, %5, %6, %7, %8, %9, %10, %11, %12, %13, %14, %15, %16, %17, %18, %19, %20, %21, %22, %23, %24, %25, %26, %27, %28, %29, %30, %31, %32, %33, %34, %35, %36, %37, %38, %39, %40, %41, %42, %43, %44, %45, %46, %47}, {%64, %65, %66, %67}, tb, p1, 1, 1, 1;\n"
        "add.s64 tb, tb0, 160;\n"
        "wgmma.mma_async.sync.aligned.m64n96k16.f32.bf16.bf16 {%0, %1, %2, %3, %4, %5, %6, %7, %8, %9, %10, %11, %12, %13, %14, %15, %16, %17, %18, %19, %20, %21, %22, %23, %24, %25, %26, %27, %28, %29, %30, %31, %32, %33, %34, %35, %36, %37, %38, %39, %40, %41, %42, %43, %44, %45, %46, %47}, {%68, %69, %70, %71}, tb, p1, 1, 1, 1;\n"
        "}\n"
        : "=f"(d[0]), "=f"(d[1]), "=f"(d[2]), "=f"(d[3]), "=f"(d[4]), "=f"(d[5]), "=f"(d[6]), "=f"(d[7]), "=f"(d[8]), "=f"(d[9]), "=f"(d[10]), "=f"(d[11]), "=f"(d[12]), "=f"(d[13]), "=f"(d[14]), "=f"(d[15]), "=f"(d[16]), "=f"(d[17]), "=f"(d[18]), "=f"(d[19]), "=f"(d[20]), "=f"(d[21]), "=f"(d[22]), "=f"(d[23]), "=f"(d[24]), "=f"(d[25]), "=f"(d[26]), "=f"(d[27]), "=f"(d[28]), "=f"(d[29]), "=f"(d[30]), "=f"(d[31]), "=f"(d[32]), "=f"(d[33]), "=f"(d[34]), "=f"(d[35]), "=f"(d[36]), "=f"(d[37]), "=f"(d[38]), "=f"(d[39]), "=f"(d[40]), "=f"(d[41]), "=f"(d[42]), "=f"(d[43]), "=f"(d[44]), "=f"(d[45]), "=f"(d[46]), "=f"(d[47])
        : "r"(a[AOFF + 0][0]), "r"(a[AOFF + 0][1]), "r"(a[AOFF + 0][2]), "r"(a[AOFF + 0][3]), "r"(a[AOFF + 1][0]), "r"(a[AOFF + 1][1]), "r"(a[AOFF + 1][2]), "r"(a[AOFF + 1][3]), "r"(a[AOFF + 2][0]), "r"(a[AOFF + 2][1]), "r"(a[AOFF + 2][2]), "r"(a[AOFF + 2][3]), "r"(a[AOFF + 3][0]), "r"(a[AOFF + 3][1]), "r"(a[AOFF + 3][2]), "r"(a[AOFF + 3][3]), "r"(a[AOFF + 4][0]), "r"(a[AOFF + 4][1]), "r"(a[AOFF + 4][2]), "r"(a[AOFF + 4][3]), "r"(a[AOFF + 5][0]), "r"(a[AOFF + 5][1]), "r"(a[AOFF + 5][2]), "r"(a[AOFF + 5][3]), "l"(descB), "n"(BOFF >> 4));
}
};
template <> struct Rng<0, 3, 7> {
template <int BOFF, int AOFF, int NA>
static __device__ __forceinline__ void run(float (&d)[48], const uint32_t (&a)[NA][4], uint64_t descB) {
    asm volatile(
        "{\n"
        ".reg .pred p0, p1;\n"
        ".reg .b64 ta, ta0, tb, tb0;\n"
        "setp.ne.b32 p0, 0, 0;\n"
        "setp.eq.b32 p1, 0, 0;\n"
        "add.s64 tb0, %64, %65;\n"
        "add.s64 tb, tb0, 96;\n"
        "wgmma.mma_async.sync.aligned.m64n96k16.f32.bf16.bf16 {%0, %1, %2, %3, %4, %5, %6, %7, %8, %9, %10, %11, %12, %13, %14, %15, %16, %17, %18, %19, %20, %21, %22, %23, %24, %25, %26, %27, %28, %29, %30, %31, %32, %33, %34, %35, %36, %37, %38, %39, %40, %41, %42, %43, %44, %45, %46, %47}, {%48, %49, %50, %51}, tb, p1, 1, 1, 1;\n"
        "add.s64 tb, tb0, 1536;\n"
        "wgmma.mma_async.sync.aligned.m64n96k16.f32.bf16.bf16 {%0, %1, %2, %3, %4, %5, %6, %7, %8, %9, %10, %11, %12, %13, %14, %15, %16, %17, %18, %19, %20, %21, %22, %23, %24, %25, %26, %27, %28, %29, %30, %31, %32, %33, %34, %35, %36, %37, %38, %39, %40, %41, %42, %43, %44, %45, %46, %47}, {%52, %53, %54, %55}, tb, p1, 1, 1, 1;\n"
        "add.s64 tb, tb0, 1568;\n"
        "wgmma.mma_async.sync.aligned.m64n96k16.f32.bf16.bf16 {%0, %1, %2, %3, %4, %5, %6, %7, %8, %9, %10, %11, %12, %13, %14, %15, %16, %17, %18, %19, %20, %21, %22, %23, %24, %25, %26, %27, %28, %29, %30, %31, %32, %33, %34, %35, %36, %37, %38, %39, %40, %41, %42, %43, %44, %45, %46, %47}, {%56, %57, %58, %59}, tb, p1, 1, 1, 1;\n"
        "add.s64 tb, tb0, 1600;\n"
        "wgmma.mma_async.sync.aligned.m64n96k16.f32.bf16.bf16 {%0, %1, %2, %3, %4, %5, %6, %7, %8, %9, %10, %11, %12, %13, %14, %15, %16, %17, %18, %19, %20, %21, %22, %23, %24, %25, %26, %27, %28, %29, %30, %31, %32, %33, %34, %35, %36, %37, %38, %39, %40, %41, %42, %43, %44, %45, %46, %47}, {%60, %61, %62, %63}, tb, p1, 1, 1, 1;\n"
        "}\n"
        : "+f"(d[0]), "+f"(d[1]), "+f"(d[2]), "+f"(d[3]), "+f"(d[4]), "+f"(d[5]), "+f"(d[6]), "+f"(d[7]), "+f"(d[8]), "+f"(d[9]), "+f"(d[10]), "+f"(d[11]), "+f"(d[12]), "+f"(d[13]), "+f"(d[14]), "+f"(d[15]), "+f"(d[16]), "+f"(d[17]), "+f"(d[18]), "+f"(d[19]), "+f"(d[20]), "+f"(d[21]), "+f"(d[22]), "+f"(d[23]), "+f"(d[24]), "+f"(d[25]), "+f"(d[26]), "+f"(d[27]), "+f"(d[28]), "+f"(d[29]), "+f"(d[30]), "+f"(d[31]), "+f"(d[32]), "+f"(d[33]), "+f"(d[34]), "+f"(d[35]), "+f"(d[36]), "+f"(d[37]), "+f"(d[38]), "+f"(d[39]), "+f"(d[40]), "+f"(d[41]), "+f"(d[42]), "+f"(d[43]), "+f"(d[44]), "+f"(d[45]), "+f"(d[46]), "+f"(d[47])
        : "r"(a[AOFF + 0][0]), "r"(a[AOFF + 0][1]), "r"(a[AOFF + 0][2]), "r"(a[AOFF + 0][3]), "r"(a[AOFF + 1][0]), "r"(a[AOFF + 1][1]), "r"(a[AOFF + 1][2]), "r"(a[AOFF + 1][3]), "r"(a[AOFF + 2][0]), "r"(a[AOFF + 2][1]), "r"(a[AOFF + 2][2]), "r"(a[AOFF + 2][3]), "r"(a[AOFF + 3][0]), "r"(a[AOFF + 3][1]), "r"(a[AOFF + 3][2]), "r"(a[AOFF + 3][3]), "l"(descB), "n"(BOFF >> 4));
}
};
template <> struct Rng<1, 3, 7> {
template <int BOFF, int AOFF, int NA>
static __device__ __forceinline__ void run(float (&d)[48], const uint32_t (&a)[NA][4], uint64_t descB) {
    asm volatile(
        "{\n"
        ".reg .pred p0, p1;\n"
        ".reg .b64 ta, ta0, tb, tb0;\n"
        "setp.ne.b32 p0, 0, 0;\n"
        "setp.eq.b32 p1, 0, 0;\n"
        "add.s64 tb0, %64, %65;\n"
        "add.s64 tb, tb0, 96;\n"
        "wgmma.mma_async.sync.aligned.m64n96k16.f32.bf16.bf16 {%0, %1, %2, %3, %4, %5, %6, %7, %8, %9, %10, %11, %12, %13, %14, %15, %16, %17, %18, %19, %20, %21, %22, %23, %24, %25, %26, %27, %28, %29, %30, %31, %32, %33, %34, %35, %36, %37, %38, %39, %40, %41, %42, %43, %44, %45, %46, %47}, {%48, %49, %50, %51}, tb, p1, 1, 1, 1;\n"
        "add.s64 tb, tb0, 128;\n"
        "wgmma.mma_async.sync.aligned.m64n96k16.f32.bf16.bf16 {%0, %1, %2, %3, %4, %5, %6, %7, %8, %9, %10, %11, %12, %13, %14, %15, %16, %17, %18, %19, %20, %21, %22, %23, %24, %25, %26, %27, %28, %29, %30, %31, %32, %33, %34, %35, %36, %37, %38, %39, %40, %41, %42, %43, %44, %45, %46, %47}, {%52, %53, %54, %55}, tb, p1, 1, 1, 1;\n"
        "add.s64 tb, tb0, 160;\n"
        "wgmma.mma_async.sync.aligned.m64n96k16.f32.bf16.bf16 {%0, %1, %2, %3, %4, %5, %6, %7, %8, %9, %10, %11, %12, %13, %14, %15, %16, %17, %18, %19, %20, %21, %22, %23, %24, %25, %26, %27, %28, %29, %30, %31, %32, %33, %34, %35, %36, %37, %38, %39, %40, %41, %42, %43, %44, %45, %46, %47}, {%56, %57, %58, %59}, tb, p1, 1, 1, 1;\n"
        "add.s64 tb, tb0, 192;\n"
        "wgmma.mma_async.sync.aligned.m64n96k16.f32.bf16.bf16 {%0, %1, %2, %3, %4, %5, %6, %7, %8, %9, %10, %11, %12, %13, %14, %15, %16, %17, %18, %19, %20, %21, %22, %23, %24, %25, %26, %27, %28, %29, %30, %31, %32, %33, %34, %35, %36, %37, %38, %39, %40, %41, %42, %43, %44, %45, %46, %47}, {%60, %61, %62, %63}, tb, p1, 1, 1, 1;\n"
        "}\n"
        : "+f"(d[0]), "+f"(d[1]), "+f"(d[2]), "+f"(d[3]), "+f"(d[4]), "+f"(d[5]), "+f"(d[6]), "+f"(d[7]), "+f"(d[8]), "+f"(d[9]), "+f"(d[10]), "+f"(d[11]), "+f"(d[12]), "+f"(d[13]), "+f"(d[14]), "+f"(d[15]), "+f"(d[16]), "+f"(d[17]), "+f"(d[18]), "+f"(d[19]), "+f"(d[20]), "+f"(d[21]), "+f"(d[22]), "+f"(d[23]), "+f"(d[24]), "+f"(d[25]), "+f"(d[26]), "+f"(d[27]), "+f"(d[28]), "+f"(d[29]), "+f"(d[30]), "+f"(d[31]), "+f"(d[32]), "+f"(d[33]), "+f"(d[34]), "+f"(d[35]), "+f"(d[36]), "+f"(d[37]), "+f"(d[38]), "+f"(d[39]), "+f"(d[40]), "+f"(d[41]), "+f"(d[42]), "+f"(d[43]), "+f"(d[44]), "+f"(d[45]), "+f"(d[46]), "+f"(d[47])
        : "r"(a[AOFF + 0][0]), "r"(a[AOFF + 0][1]), "r"(a[AOFF + 0][2]), "r"(a[AOFF + 0][3]), "r"(a[AOFF + 1][0]), "r"(a[AOFF + 1][1]), "r"(a[AOFF + 1][2]), "r"(a[AOFF + 1][3]), "r"(a[AOFF + 2][0]), "r"(a[AOFF + 2][1]), "r"(a[AOFF + 2][2]), "r"(a[AOFF + 2][3]), "r"(a[AOFF + 3][0]), "r"(a[AOFF + 3][1]), "r"(a[AOFF + 3][2]), "r"(a[AOFF + 3][3]), "l"(descB), "n"(BOFF >> 4));
}
};
template <> struct Rng<0, 3, 8> {
template <int BOFF, int AOFF, int NA>
static __device__ __forceinline__ void run(float (&d)[48], const uint32_t (&a)[NA][4], uint64_t descB) {
    asm volatile(
        "{\n"
        ".reg .pred p0, p1;\n"
        ".reg .b64 ta, ta0, tb, tb0;\n"
        "setp.ne.b32 p0, 0, 0;\n"
        "setp.eq.b32 p1, 0, 0;\n"
        "add.s64 tb0, %68, %69;\n"
        "add.s64 tb, tb0, 96;\n"
        "wgmma.mma_async.sync.aligned.m64n96k16.f32.bf16.bf16 {%0, %1, %2, %3, %4, %5, %6, %7, %8, %9, %10, %11, %12, %13, %14, %15, %16, %17, %18, %19, %20, %21, %22, %23, %24, %25, %26, %27, %28, %29, %30, %31, %32, %33, %34, %35, %36, %37, %38, %39, %40, %41, %42, %43, %44, %45, %46, %47}, {%48, %49, %50, %51}, tb, p1, 1, 1, 1;\n"
        "add.s64 tb, tb0, 1536;\n"
        "wgmma.mma_async.sync.aligned.m64n96k16.f32.bf16.bf16 {%0, %1, %2, %3, %4, %5, %6, %7, %8, %9, %10, %11, %12, %13, %14, %15, %16, %17, %18, %19, %20, %21, %22, %23, %24, %25, %26, %27, %28, %29, %30, %31, %32, %33, %34, %35, %36, %37, %38, %39, %40, %41, %42, %43, %44, %45, %46, %47}, {%52, %53, %54, %55}, tb, p1, 1, 1, 1;\n"
        "add.s64 tb, tb0, 1568;\n"
        "wgmma.mma_async.sync.aligned.m64n96k16.f32.bf16.bf16 {%0, %1, %2, %3, %4, %5, %6, %7, %8, %9, %10, %11, %12, %13, %14, %15, %16, %17, %18, %19, %20, %21, %22, %23, %24, %25, %26, %27, %28, %29, %30, %31, %32, %33, %34, %35, %36, %37, %38, %39, %40, %41, %42, %43, %44, %45, %46, %47}, {%56, %57, %58, %59}, tb, p1, 1, 1, 1;\n"
        "add.s64 tb, tb0, 1600;\n"
        "wgmma.mma_async.sync.aligned.m64n96k16.f32.bf16.bf16 {%0, %1, %2, %3, %4, %5, %6, %7, %8, %9, %10, %11, %12, %13, %14, %15, %16, %17, %18, %19, %20, %21, %22, %23, %24, %25, %26, %27, %28, %29, %30, %31, %32, %33, %34, %35, %36, %37, %38, %39, %40, %41, %42, %43, %44, %45, %46, %47}, {%60, %61, %62, %63}, tb, p1, 1, 1, 1;\n"
        "add.s64 tb, tb0, 1632;\n"
        "wgmma.mma_async.sync.aligned.m64n96k16.f32.bf16.bf16 {%0, %1, %2, %3, %4, %5, %6, %7, %8, %9, %10, %11, %12, %13, %14, %15, %16, %17, %18, %19, %20, %21, %22, %23, %24, %25, %26, %27, %28, %29, %30, %31, %32, %33, %34, %35, %36, %37, %38, %39, %40, %41, %42, %43, %44, %45, %46, %47}, {%64, %65, %66, %67}, tb, p1, 1, 1, 1;\n"
        "}\n"
        : "+f"(d[0]), "+f"(d[1]), "+f"(d[2]), "+f"(d[3]), "+f"(d[4]), "+f"(d[5]), "+f"(d[6]), "+f"(d[7]), "+f"(d[8]), "+f"(d[9]), "+f"(d[10]), "+f"(d[11]), "+f"(d[12]), "+f"(d[13]), "+f"(d[14]), "+f"(d[15]), "+f"(d[16]), "+f"(d[17]), "+f"(d[18]), "+f"(d[19]), "+f"(d[20]), "+f"(d[21]), "+f"(d[22]), "+f"(d[23]), "+f"(d[24]), "+f"(d[25]), "+f"(d[26]), "+f"(d[27]), "+f"(d[28]), "+f"(d[29]), "+f"(d[30]), "+f"(d[31]), "+f"(d[32]), "+f"(d[33]), "+f"(d[34]), "+f"(d[35]), "+f"(d[36]), "+f"(d[37]), "+f"(d[38]), "+f"(d[39]), "+f"(d[40]), "+f"(d[41]), "+f"(d[42]), "+f"(d[43]), "+f"(d[44]), "+f"(d[45]), "+f"(d[46]), "+f"(d[47])
        : "r"(a[AOFF + 0][0]), "r"(a[AOFF + 0][1]), "r"(a[AOFF + 0][2]), "r"(a[AOFF + 0][3]), "r"(a[AOFF + 1][0]), "r"(a[AOFF + 1][1]), "r"(a[AOFF + 1][2]), "r"(a[AOFF + 1][3]), "r"(a[AOFF + 2][0]), "r"(a[AOFF + 2][1]), "r"(a[AOFF + 2][2]), "r"(a[AOFF + 2][3]), "r"(a[AOFF + 3][0]), "r"(a[AOFF + 3][1]), "r"(a[AOFF + 3][2]), "r"(a[AOFF + 3][3]), "r"(a[AOFF + 4][0]), "r"(a[AOFF + 4][1]), "r"(a[AOFF + 4][2]), "r"(a[AOFF + 4][3]), "l"(descB), "n"(BOFF >> 4));
}
};
template <> struct Rng<1, 3, 8> {
template <int BOFF, int AOFF, int NA>
static __device__ __forceinline__ void run(float (&d)[48], const uint32_t (&a)[NA][4], uint64_t descB) {
    asm volatile(
        "{\n"
        ".reg .pred p0, p1;\n"
        ".reg .b64 ta, ta0, tb, tb0;\n"
        "setp.ne.b32 p0, 0, 0;\n"
        "setp.eq.b32 p1, 0, 0;\n"
        "add.s64 tb0, %68, %69;\n"
        "add.s64 tb, tb0, 96;\n"
        "wgmma.mma_async.sync.aligned.m64n96k16.f32.bf16.bf16 {%0, %1, %2, %3, %4, %5, %6, %7, %8, %9, %10, %11, %12, %13, %14, %15, %16, %17, %18, %19, %20, %21, %22, %23, %24, %25, %26, %27, %28, %29, %30, %31, %32, %33, %34, %35, %36, %37, %38, %39, %40, %41, %42, %43, %44, %45, %46, %47}, {%48, %49, %50, %51}, tb, p1, 1, 1, 1;\n"
        "add.s64 tb, tb0, 128;\n"
        "wgmma.mma_async.sync.aligned.m64n96k16.f32.bf16.bf16 {%0, %1, %2, %3, %4, %5, %6, %7, %8, %9, %10, %11, %12, %13, %14, %15, %16, %17, %18, %19, %20, %21, %22, %23, %24, %25, %26, %27, %28, %29, %30, %31, %32, %33, %34, %35, %36, %37, %38, %39, %40, %41, %42, %43, %44, %45, %46, %47}, {%52, %53, %54, %55}, tb, p1, 1, 1, 1;\n"
        "add.s64 tb, tb0, 160;\n"
        "wgmma.mma_async.sync.aligned.m64n96k16.f32.bf16.bf16 {%0, %1, %2, %3, %4, %5, %6, %7, %8, %9, %10, %11, %12, %13, %14, %15, %16, %17, %18, %19, %20, %21, %22, %23, %24, %25, %26, %27, %28, %29, %30, %31, %32, %33, %34, %35, %36, %37, %38, %39, %40, %41, %42, %43, %44, %45, %46, %47}, {%56, %57, %58, %59}, tb, p1, 1, 1, 1;\n"
        "add.s64 tb, tb0, 192;\n"
        "wgmma.mma_async.sync.aligned.m64n96k16.f32.bf16.bf16 {%0, %1, %2, %3, %4, %5, %6, %7, %8, %9, %10, %11, %12, %13, %14, %15, %16, %17, %18, %19, %20, %21, %22, %23, %24, %25, %26, %27, %28, %29, %30, %31, %32, %33, %34, %35, %36, %37, %38, %39, %40, %41, %42, %43, %44, %45, %46, %47}, {%60, %61, %62, %63}, tb, p1, 1, 1, 1;\n"
        "add.s64 tb, tb0, 224;\n"
        "wgmma.mma_async.sync.aligned.m64n96k16.f32.bf16.bf16 {%0, %1, %2, %3, %4, %5, %6, %7, %8, %9, %10, %11, %12, %13, %14, %15, %16, %17, %18, %19, %20, %21, %22, %23, %24, %25, %26, %27, %28, %29, %30, %31, %32, %33, %34, %35, %36, %37, %38, %39, %40, %41, %42, %43, %44, %45, %46, %47}, {%64, %65, %66, %67}, tb, p1, 1, 1, 1;\n"
        "}\n"
        : "+f"(d[0]), "+f"(d[1]), "+f"(d[2]), "+f"(d[3]), "+f"(d[4]), "+f"(d[5]), "+f"(d[6]), "+f"(d[7]), "+f"(d[8]), "+f"(d[9]), "+f"(d[10]), "+f"(d[11]), "+f"(d[12]), "+f"(d[13]), "+f"(d[14]), "+f"(d[15]), "+f"(d[16]), "+f"(d[17]), "+f"(d[18]), "+f"(d[19]), "+f"(d[20]), "+f"(d[21]), "+f"(d[22]), "+f"(d[23]), "+f"(d[24]), "+f"(d[25]), "+f"(d[26]), "+f"(d[27]), "+f"(d[28]), "+f"(d[29]), "+f"(d[30]), "+f"(d[31]), "+f"(d[32]), "+f"(d[33]), "+f"(d[34]), "+f"(d[35]), "+f"(d[36]), "+f"(d[37]), "+f"(d[38]), "+f"(d[39]), "+f"(d[40]), "+f"(d[41]), "+f"(d[42]), "+f"(d[43]), "+f"(d[44]), "+f"(d[45]), "+f"(d[46]), "+f"(d[47])
        : "r"(a[AOFF + 0][0]), "r"(a[AOFF + 0][1]), "r"(a[AOFF + 0][2]), "r"(a[AOFF + 0][3]), "r"(a[AOFF + 1][0]), "r"(a[AOFF + 1][1]), "r"(a[AOFF + 1][2]), "r"(a[AOFF + 1][3]), "r"(a[AOFF + 2][0]), "r"(a[AOFF + 2][1]), "r"(a[AOFF + 2][2]), "r"(a[AOFF + 2][3]), "r"(a[AOFF + 3][0]), "r"(a[AOFF + 3][1]), "r"(a[AOFF + 3][2]), "r"(a[AOFF + 3][3]), "r"(a[AOFF + 4][0]), "r"(a[AOFF + 4][1]), "r"(a[AOFF + 4][2]), "r"(a[AOFF + 4][3]), "l"(descB), "n"(BOFF >> 4));
}
};
template <> struct Rng<0, 3, 12> {
template <int BOFF, int AOFF, int NA>
static __device__ __forceinline__ void run(float (&d)[48], const uint32_t (&a)[NA][4], uint64_t descB) {
    asm volatile(
        "{\n"
        ".reg .pred p0, p1;\n"
        ".reg .b64 ta, ta0, tb, tb0;\n"
        "setp.ne.b32 p0, 0, 0;\n"
        "setp.eq.b32 p1, 0, 0;\n"
        "add.s64 tb0, %84, %85;\n"
        "add.s64 tb, tb0, 96;\n"
        "wgmma.mma_async.sync.aligned.m64n96k16.f32.bf16.bf16 {%0, %1, %2, %3, %4, %5, %6, %7, %8, %9, %10, %11, %12, %13, %14, %15, %16, %17, %18, %19, %20, %21, %22, %23, %24, %25, %26, %27, %28, %29, %30, %31, %32, %33, %34, %35, %36, %37, %38, %39, %40, %41, %42, %43, %44, %45, %46, %47}, {%48, %49, %50, %51}, tb, p1, 1, 1, 1;\n"
        "add.s64 tb, tb0, 1536;\n"
        "wgmma.mma_async.sync.aligned.m64n96k16.f32.bf16.bf16 {%0, %1, %2, %3, %4, %5, %6, %7, %8, %9, %10, %11, %12, %13, %14, %15, %16, %17, %18, %19, %20, %21, %22, %23, %24, %25, %26, %27, %28, %29, %30, %31, %32, %33, %34, %35, %36, %37, %38, %39, %40, %41, %42, %43, %44, %45, %46, %47}, {%52, %53, %54, %55}, tb, p1, 1, 1, 1;\n"
        "add.s64 tb, tb0, 1568;\n"
        "wgmma.mma_async.sync.aligned.m64n96k16.f32.bf16.bf16 {%0, %1, %2, %3, %4, %5, %6, %7, %8, %9, %10, %11, %12, %13, %14, %15, %16, %17, %18, %19, %20, %21, %22, %23, %24, %25, %26, %27, %28, %29, %30, %31, %32, %33, %34, %35, %36, %37, %38, %39, %40, %41, %42, %43, %44, %45, %46, %47}, {%56, %57, %58, %59}, tb, p1, 1, 1, 1;\n"
        "add.s64 tb, tb0, 1600;\n"
        "wgmma.mma_async.sync.aligned.m64n96k16.f32.bf16.bf16 {%0, %1, %2, %3, %4, %5, %6, %7, %8, %9, %10, %11, %12, %13, %14, %15, %16, %17, %18, %19, %20, %21, %22, %23, %24, %25, %26, %27, %28, %29, %30, %31, %32, %33, %34, %35, %36, %37, %38, %39, %40, %41, %42, %43, %44, %45, %46, %47}, {%60, %61, %62, %63}, tb, p1, 1, 1, 1;\n"
        "add.s64 tb, tb0, 1632;\n"
        "wgmma.mma_async.sync.aligned.m64n96k16.f32.bf16.bf16 {%0, %1, %2, %3, %4, %5, %6, %7, %8, %9, %10, %11, %12, %13, %14, %15, %16, %17, %18, %19, %20, %21, %22, %23, %24, %25, %26, %27, %28, %29, %30, %31, %32, %33, %34, %35, %36, %37, %38, %39, %40, %41, %42, %43, %44, %45, %46, %47}, {%64, %65, %66, %67}, tb, p1, 1, 1, 1;\n"
        "add.s64 tb, tb0, 3072;\n"
        "wgmma.mma_async.sync.aligned.m64n96k16.f32.bf16.bf16 {%0, %1, %2, %3, %4, %5, %6, %7, %8, %9, %10, %11, %12, %13, %14, %15, %16, %17, %18, %19, %20, %21, %22, %23, %24, %25, %26, %27, %28, %29, %30, %31, %32, %33, %34, %35, %36, %37, %38, %39, %40, %41, %42, %43, %44, %45, %46, %47}, {%68, %69, %70, %71}, tb, p1, 1, 1, 1;\n"
        "add.s64 tb, tb0, 3104;\n"
        "wgmma.mma_async.sync.aligned.m64n96k16.f32.bf16.bf16 {%0, %1, %2, %3, %4, %5, %6, %7, %8, %9, %10, %11, %12, %13, %14, %15, %16, %17, %18, %19, %20, %21, %22, %23, %24, %25, %26, %27, %28, %29, %30, %31, %32, %33, %34, %35, %36, %37, %38, %39, %40, %41, %42, %43, %44, %45, %46, %47}, {%72, %73, %74, %75}, tb, p1, 1, 1, 1;\n"
        "add.s64 tb, tb0, 3136;\n"
        "wgmma.mma_async.sync.aligned.m64n96k16.f32.bf16.bf16 {%0, %1, %2, %3, %4, %5, %6, %7, %8, %9, %10, %11, %12, %13, %14, %15, %16, %17, %18, %19, %20, %21, %22, %23, %24, %25, %26, %27, %28, %29, %30, %31, %32, %33, %34, %35, %36, %37, %38, %39, %40, %41, %42, %43, %44, %45, %46, %47}, {%76, %77, %78, %79}, tb, p1, 1, 1, 1;\n"
        "add.s64 tb, tb0, 3168;\n"
        "wgmma.mma_async.sync.aligned.m64n96k16.f32.bf16.bf16 {%0, %1, %2, %3, %4, %5, %6, %7, %8, %9, %10, %11, %12, %13, %14, %15, %16, %17, %18, %19, %20, %21, %22, %23, %24, %25, %26, %27, %28, %29, %30, %31, %32, %33, %34, %35, %36, %37, %38, %39, %40, %41, %42, %43, %44, %45, %46, %47}, {%80, %81, %82, %83}, tb, p1, 1, 1, 1;\n"
        "}\n"
        : "+f"(d[0]), "+f"(d[1]), "+f"(d[2]), "+f"(d[3]), "+f"(d[4]), "+f"(d[5]), "+f"(d[6]), "+f"(d[7]), "+f"(d[8]), "+f"(d[9]), "+f"(d[10]), "+f"(d[11]), "+f"(d[12]), "+f"(d[13]), "+f"(d[14]), "+f"(d[15]), "+f"(d[16]), "+f"(d[17]), "+f"(d[18]), "+f"(d[19]), "+f"(d[20]), "+f"(d[21]), "+f"(d[22]), "+f"(d[23]), "+f"(d[24]), "+f"(d[25]), "+f"(d[26]), "+f"(d[27]), "+f"(d[28]), "+f"(d[29]), "+f"(d[30]), "+f"(d[31]), "+f"(d[32]), "+f"(d[33]), "+f"(d[34]), "+f"(d[35]), "+f"(d[36]), "+f"(d[37]), "+f"(d[38]), "+f"(d[39]), "+f"(d[40]), "+f"(d[41]), "+f"(d[42]), "+f"(d[43]), "+f"(d[44]), "+f"(d[45]), "+f"(d[46]), "+f"(d[47])
        : "r"(a[AOFF + 0][0]), "r"(a[AOFF + 0][1]), "r"(a[AOFF + 0][2]), "r"(a[AOFF + 0][3]), "r"(a[AOFF + 1][0]), "r"(a[AOFF + 1][1]), "r"(a[AOFF + 1][2]), "r"(a[AOFF + 1][3]), "r"(a[AOFF + 2][0]), "r"(a[AOFF + 2][1]), "r"(a[AOFF + 2][2]), "r"(a[AOFF + 2][3]), "r"(a[AOFF + 3][0]), "r"(a[AOFF + 3][1]), "r"(a[AOFF + 3][2]), "r"(a[AOFF + 3][3]), "r"(a[AOFF + 4][0]), "r"(a[AOFF + 4][1]), "r"(a[AOFF + 4][2]), "r"(a[AOFF + 4][3]), "r"(a[AOFF + 5][0]), "r"(a[AOFF + 5][1]), "r"(a[AOFF + 5][2]), "r"(a[AOFF + 5][3]), "r"(a[AOFF + 6][0]), "r"(a[AOFF + 6][1]), "r"(a[AOFF + 6][2]), "r"(a[AOFF + 6][3]), "r"(a[AOFF + 7][0]), "r"(a[AOFF + 7][1]), "r"(a[AOFF + 7][2]), "r"(a[AOFF + 7][3]), "r"(a[AOFF + 8][0]), "r"(a[AOFF + 8][1]), "r"(a[AOFF + 8][2]), "r"(a[AOFF + 8][3]), "l"(descB), "n"(BOFF >> 4));
}
};
template <> struct Rng<1, 3, 12> {
template <int BOFF, int AOFF, int NA>
static __device__ __forceinline__ void run(float (&d)[48], const uint32_t (&a)[NA][4], uint64_t descB) {
    asm volatile(
        "{\n"
        ".reg .pred p0, p1;\n"
        ".reg .b64 ta, ta0, tb, tb0;\n"
        "setp.ne.b32 p0, 0, 0;\n"
        "setp.eq.b32 p1, 0, 0;\n"
        "add.s64 tb0, %84, %85;\n"
        "add.s64 tb, tb0, 96;\n"
        "wgmma.mma_async.sync.aligned.m64n96k16.f32.bf16.bf16 {%0, %1, %2, %3, %4, %5, %6, %7, %8, %9, %10, %11, %12, %13, %14, %15, %16, %17, %18, %19, %20, %21, %22, %23, %24, %25, %26, %27, %28, %29, %30, %31, %32, %33, %34, %35, %36, %37, %38, %39, %40, %41, %42, %43, %44, %45, %46, %47}, {%48, %49, %50, %51}, tb, p1, 1, 1, 1;\n"
        "add.s64 tb, tb0, 128;\n"
        "wgmma.mma_async.sync.aligned.m64n96k16.f32.bf16.bf16 {%0, %1, %2, %3, %4, %5, %6, %7, %8, %9, %10, %11, %12, %13, %14, %15, %16, %17, %18, %19, %20, %21, %22, %23, %24, %25, %26, %27, %28, %29, %30, %31, %32, %33, %34, %35, %36, %37, %38, %39, %40, %41, %42, %43, %44, %45, %46, %47}, {%52, %53, %54, %55}, tb, p1, 1, 1, 1;\n"
        "add.s64 tb, tb0, 160;\n"
        "wgmma.mma_async.sync.aligned.m64n96k16.f32.bf16.bf16 {%0, %1, %2, %3, %4, %5, %6, %7, %8, %9, %10, %11, %12, %13, %14, %15, %16, %17, %18, %19, %20, %21, %22, %23, %24, %25, %26, %27, %28, %29, %30, %31, %32, %33, %34, %35, %36, %37, %38, %39, %40, %41, %42, %43, %44, %45, %46, %47}, {%56, %57, %58, %59}, tb, p1, 1, 1, 1;\n"
        "add.s64 tb, tb0, 192;\n"
        "wgmma.mma_async.sync.aligned.m64n96k16.f32.bf16.bf16 {%0, %1, %2, %3, %4, %5, %6, %7, %8, %9, %10, %11, %12, %13, %14, %15, %16, %17, %18, %19, %20, %21, %22, %23, %24, %25, %26, %27, %28, %29, %30, %31, %32, %33, %34, %35, %36, %37, %38, %39, %40, %41, %42, %43, %44, %45, %46, %47}, {%60, %61, %62, %63}, tb, p1, 1, 1, 1;\n"
        "add.s64 tb, tb0, 224;\n"
        "wgmma.mma_async.sync.aligned.m64n96k16.f32.bf16.bf16 {%0, %1, %2, %3, %4, %5, %6, %7, %8, %9, %10, %11, %12, %13, %14, %15, %16, %17, %18, %19, %20, %21, %22, %23, %24, %25, %26, %27, %28, %29, %30, %31, %32, %33, %34, %35, %36, %37, %38, %39, %40, %41, %42, %43, %44, %45, %46, %47}, {%64, %65, %66, %67}, tb, p1, 1, 1, 1;\n"
        "add.s64 tb, tb0, 256;\n"
        "wgmma.mma_async.sync.aligned.m64n96k16.f32.bf16.bf16 {%0, %1, %2, %3, %4, %5, %6, %7, %8, %9, %10, %11, %12, %13, %14, %15, %16, %17, %18, %19, %20, %21, %22, %23, %24, %25, %26, %27, %28, %29, %30, %31, %32, %33, %34, %35, %36, %37, %38, %39, %40, %41, %42, %43, %44, %45, %46, %47}, {%68, %69, %70, %71}, tb, p1, 1, 1, 1;\n"
        "add.s64 tb, tb0, 288;\n"
        "wgmma.mma_async.sync.aligned.m64n96k16.f32.bf16.bf16 {%0, %1, %2, %3, %4, %5, %6, %7, %8, %9, %10, %11, %12, %13, %14, %15, %16, %17, %18, %19, %20, %21, %22, %23, %24, %25, %26, %27, %28, %29, %30, %31, %32, %33, %34, %35, %36, %37, %38, %39, %40, %41, %42, %43, %44, %45, %46, %47}, {%72, %73, %74, %75}, tb, p1, 1, 1, 1;\n"
        "add.s64 tb, tb0, 320;\n"
        "wgmma.mma_async.sync.aligned.m64n96k16.f32.bf16.bf16 {%0, %1, %2, %3, %4, %5, %6, %7, %8, %9, %10, %11, %12, %13, %14, %15, %16, %17, %18, %19, %20, %21, %22, %23, %24, %25, %26, %27, %28, %29, %30, %31, %32, %33, %34, %35, %36, %37, %38, %39, %40, %41, %42, %43, %44, %45, %46, %47}, {%76, %77, %78, %79}, tb, p1, 1, 1, 1;\n"
        "add.s64 tb, tb0, 352;\n"
        "wgmma.mma_async.sync.aligned.m64n96k16.f32.bf16.bf16 {%0, %1, %2, %3, %4, %5, %6, %7, %8, %9, %10, %11, %12, %13, %14, %15, %16, %17, %18, %19, %20, %21, %22, %23, %24, %25, %26, %27, %28, %29, %30, %31, %32, %33, %34, %35, %36, %37, %38, %39, %40, %41, %42, %43, %44, %45, %46, %47}, {%80, %81, %82, %83}, tb, p1, 1, 1, 1;\n"
        "}\n"
        : "+f"(d[0]), "+f"(d[1]), "+f"(d[2]), "+f"(d[3]), "+f"(d[4]), "+f"(d[5]), "+f"(d[6]), "+f"(d[7]), "+f"(d[8]), "+f"(d[9]), "+f"(d[10]), "+f"(d[11]), "+f"(d[12]), "+f"(d[13]), "+f"(d[14]), "+f"(d[15]), "+f"(d[16]), "+f"(d[17]), "+f"(d[18]), "+f"(d[19]), "+f"(d[20]), "+f"(d[21]), "+f"(d[22]), "+f"(d[23]), "+f"(d[24]), "+f"(d[25]), "+f"(d[26]), "+f"(d[27]), "+f"(d[28]), "+f"(d[29]), "+f"(d[30]), "+f"(d[31]), "+f"(d[32]), "+f"(d[33]), "+f"(d[34]), "+f"(d[35]), "+f"(d[36]), "+f"(d[37]), "+f"(d[38]), "+f"(d[39]), "+f"(d[40]), "+f"(d[41]), "+f"(d[42]), "+f"(d[43]), "+f"(d[44]), "+f"(d[45]), "+f"(d[46]), "+f"(d[47])
        : "r"(a[AOFF + 0][0]), "r"(a[AOFF + 0][1]), "r"(a[AOFF + 0][2]), "r"(a[AOFF + 0][3]), "r"(a[AOFF + 1][0]), "r"(a[AOFF + 1][1]), "r"(a[AOFF + 1][2]), "r"(a[AOFF + 1][3]), "r"(a[AOFF + 2][0]), "r"(a[AOFF + 2][1]), "r"(a[AOFF + 2][2]), "r"(a[AOFF + 2][3]), "r"(a[AOFF + 3][0]), "r"(a[AOFF + 3][1]), "r"(a[AOFF + 3][2]), "r"(a[AOFF + 3][3]), "r"(a[AOFF + 4][0]), "r"(a[AOFF + 4][1]), "r"(a[AOFF + 4][2]), "r"(a[AOFF + 4][3]), "r"(a[AOFF + 5][0]), "r"(a[AOFF + 5][1]), "r"(a[AOFF + 5][2]), "r"(a[AOFF + 5][3]), "r"(a[AOFF + 6][0]), "r"(a[AOFF + 6][1]), "r"(a[AOFF + 6][2]), "r"(a[AOFF + 6][3]), "r"(a[AOFF + 7][0]), "r"(a[AOFF + 7][1]), "r"(a[AOFF + 7][2]), "r"(a[AOFF + 7][3]), "r"(a[AOFF + 8][0]), "r"(a[AOFF + 8][1]), "r"(a[AOFF + 8][2]), "r"(a[AOFF + 8][3]), "l"(descB), "n"(BOFF >> 4));
}
};
template <> struct Rng<0, 4, 6> {
template <int BOFF, int AOFF, int NA>
static __device__ __forceinline__ void run(float (&d)[48], const uint32_t (&a)[NA][4], uint64_t descB) {
    asm volatile(
        "{\n"
        ".reg .pred p0, p1;\n"
        ".reg .b64 ta, ta0, tb, tb0;\n"
        "setp.ne.b32 p0, 0, 0;\n"
        "setp.eq.b32 p1, 0, 0;\n"
        "add.s64 tb0, %56, %57;\n"
        "add.s64 tb, tb0, 1536;\n"
        "wgmma.mma_async.sync.aligned.m64n96k16.f32.bf16.bf16 {%0, %1, %2, %3, %4, %5, %6, %7, %8, %9, %10, %11, %12, %13, %14, %15, %16, %17, %18, %19, %20, %21, %22, %23, %24, %25, %26, %27, %28, %29, %30, %31, %32, %33, %34, %35, %36, %37, %38, %39, %40, %41, %42, %43, %44, %45, %46, %47}, {%48, %49, %50, %51}, tb, p1, 1, 1, 1;\n"
        "add.s64 tb, tb0, 1568;\n"
        "wgmma.mma_async.sync.aligned.m64n96k16.f32.bf16.bf16 {%0, %1, %2, %3, %4, %5, %6, %7, %8, %9, %10, %11, %12, %13, %14, %15, %16, %17, %18, %19, %20, %21, %22, %23, %24, %25, %26, %27, %28, %29, %30, %31, %32, %33, %34, %35, %36, %37, %38, %39, %40, %41, %42, %43, %44, %45, %46, %47}, {%52, %53, %54, %55}, tb, p1, 1, 1, 1;\n"
        "}\n"
        : "+f"(d[0]), "+f"(d[1]), "+f"(d[2]), "+f"(d[3]), "+f"(d[4]), "+f"(d[5]), "+f"(d[6]), "+f"(d[7]), "+f"(d[8]), "+f"(d[9]), "+f"(d[10]), "+f"(d[11]), "+f"(d[12]), "+f"(d[13]), "+f"(d[14]), "+f"(d[15]), "+f"(d[16]), "+f"(d[17]), "+f"(d[18]), "+f"(d[19]), "+f"(d[20]), "+f"(d[21]), "+f"(d[22]), "+f"(d[23]), "+f"(d[24]), "+f"(d[25]), "+f"(d[26]), "+f"(d[27]), "+f"(d[28]), "+f"(d[29]), "+f"(d[30]), "+f"(d[31]), "+f"(d[32]), "+f"(d[33]), "+f"(d[34]), "+f"(d[35]), "+f"(d[36]), "+f"(d[37]), "+f"(d[38]), "+f"(d[39]), "+f"(d[40]), "+f"(d[41]), "+f"(d[42]), "+f"(d[43]), "+f"(d[44]), "+f"(d[45]), "+f"(d[46]), "+f"(d[47])
        : "r"(a[AOFF + 0][0]), "r"(a[AOFF + 0][1]), "r"(a[AOFF + 0][2]), "r"(a[AOFF + 0][3]), "r"(a[AOFF + 1][0]), "r"(a[AOFF + 1][1]), "r"(a[AOFF + 1][2]), "r"(a[AOFF + 1][3]), "l"(descB), "n"(BOFF >> 4));
}
};
template <> struct Rng<1, 4, 6> {
template <int BOFF, int AOFF, int NA>
static __device__ __forceinline__ void run(float (&d)[48], const uint32_t (&a)[NA][4], uint64_t descB) {
    asm volatile(
        "{\n"
        ".reg .pred p0, p1;\n"
        ".reg .b64 ta, ta0, tb, tb0;\n"
        "setp.ne.b32 p0, 0, 0;\n"
        "setp.eq.b32 p1, 0, 0;\n"
        "add.s64 tb0, %56, %57;\n"
        "add.s64 tb, tb0, 128;\n"
        "wgmma.mma_async.sync.aligned.m64n96k16.f32.bf16.bf16 {%0, %1, %2, %3, %4, %5, %6, %7, %8, %9, %10, %11, %12, %13, %14, %15, %16, %17, %18, %19, %20, %21, %22, %23, %24, %25, %26, %27, %28, %29, %30, %31, %32, %33, %34, %35, %36, %37, %38, %39, %40, %41, %42, %43, %44, %45, %46, %47}, {%48, %49, %50, %51}, tb, p1, 1, 1, 1;\n"
        "add.s64 tb, tb0, 160;\n"
        "wgmma.mma_async.sync.aligned.m64n96k16.f32.bf16.bf16 {%0, %1, %2, %3, %4, %5, %6, %7, %8, %9, %10, %11, %12, %13, %14, %15, %16, %17, %18, %19, %20, %21, %22, %23, %24, %25, %26, %27, %28, %29, %30, %31, %32, %33, %34, %35, %36, %37, %38, %39, %40, %41, %42, %43, %44, %45, %46, %47}, {%52, %53, %54, %55}, tb, p1, 1, 1, 1;\n"
        "}\n"
        : "+f"(d[0]), "+f"(d[1]), "+f"(d[2]), "+f"(d[3]), "+f"(d[4]), "+f"(d[5]), "+f"(d[6]), "+f"(d[7]), "+f"(d[8]), "+f"(d[9]), "+f"(d[10]), "+f"(d[11]), "+f"(d[12]), "+f"(d[13]), "+f"(d[14]), "+f"(d[15]), "+f"(d[16]), "+f"(d[17]), "+f"(d[18]), "+f"(d[19]), "+f"(d[20]), "+f"(d[21]), "+f"(d[22]), "+f"(d[23]), "+f"(d[24]), "+f"(d[25]), "+f"(d[26]), "+f"(d[27]), "+f"(d[28]), "+f"(d[29]), "+f"(d[30]), "+f"(d[31]), "+f"(d[32]), "+f"(d[33]), "+f"(d[34]), "+f"(d[35]), "+f"(d[36]), "+f"(d[37]), "+f"(d[38]), "+f"(d[39]), "+f"(d[40]), "+f"(d[41]), "+f"(d[42]), "+f"(d[43]), "+f"(d[44]), "+f"(d[45]), "+f"(d[46]), "+f"(d[47])
        : "r"(a[AOFF + 0][0]), "r"(a[AOFF + 0][1]), "r"(a[AOFF + 0][2]), "r"(a[AOFF + 0][3]), "r"(a[AOFF + 1][0]), "r"(a[AOFF + 1][1]), "r"(a[AOFF + 1][2]), "r"(a[AOFF + 1][3]), "l"(descB), "n"(BOFF >> 4));
}
};
template <> struct Rng<0, 4, 7> {
template <int BOFF, int AOFF, int NA>
static __device__ __forceinline__ void run(float (&d)[48], const uint32_t (&a)[NA][4], uint64_t descB) {
    asm volatile(
        "{\n"
        ".reg .pred p0, p1;\n"
        ".reg .b64 ta, ta0, tb, tb0;\n"
        "setp.ne.b32 p0, 0, 0;\n"
        "setp.eq.b32 p1, 0, 0;\n"
        "add.s64 tb0, %60, %61;\n"
        "add.s64 tb, tb0, 1536;\n"
        "wgmma.mma_async.sync.aligned.m64n96k16.f32.bf16.bf16 {%0, %1, %2, %3, %4, %5, %6, %7, %8, %9, %10, %11, %12, %13, %14, %15, %16, %17, %18, %19, %20, %21, %22, %23, %24, %25, %26, %27, %28, %29, %30, %31, %32, %33, %34, %35, %36, %37, %38, %39, %40, %41, %42, %43, %44, %45, %46, %47}, {%48, %49, %50, %51}, tb, p1, 1, 1, 1;\n"
        "add.s64 tb, tb0, 1568;\n"
        "wgmma.mma_async.sync.aligned.m64n96k16.f32.bf16.bf16 {%0, %1, %2, %3, %4, %5, %6, %7, %8, %9, %10, %11, %12, %13, %14, %15, %16, %17, %18, %19, %20, %21, %22, %23, %24, %25, %26, %27, %28, %29, %30, %31, %32, %33, %34, %35, %36, %37, %38, %39, %40, %41, %42, %43, %44, %45, %46, %47}, {%52, %53, %54, %55}, tb, p1, 1, 1, 1;\n"
        "add.s64 tb, tb0, 1600;\n"
        "wgmma.mma_async.sync.aligned.m64n96k16.f32.bf16.bf16 {%0, %1, %2, %3, %4, %5, %6, %7, %8, %9, %10, %11, %12, %13, %14, %15, %16, %17, %18, %19, %20, %21, %22, %23, %24, %25, %26, %27, %28, %29, %30, %31, %32, %33, %34, %35, %36, %37, %38, %39, %40, %41, %42, %43, %44, %45, %46, %47}, {%56, %57, %58, %59}, tb, p1, 1, 1, 1;\n"
        "}\n"
        : "+f"(d[0]), "+f"(d[1]), "+f"(d[2]), "+f"(d[3]), "+f"(d[4]), "+f"(d[5]), "+f"(d[6]), "+f"(d[7]), "+f"(d[8]), "+f"(d[9]), "+f"(d[10]), "+f"(d[11]), "+f"(d[12]), "+f"(d[13]), "+f"(d[14]), "+f"(d[15]), "+f"(d[16]), "+f"(d[17]), "+f"(d[18]), "+f"(d[19]), "+f"(d[20]), "+f"(d[21]), "+f"(d[22]), "+f"(d[23]), "+f"(d[24]), "+f"(d[25]), "+f"(d[26]), "+f"(d[27]), "+f"(d[28]), "+f"(d[29]), "+f"(d[30]), "+f"(d[31]), "+f"(d[32]), "+f"(d[33]), "+f"(d[34]), "+f"(d[35]), "+f"(d[36]), "+f"(d[37]), "+f"(d[38]), "+f"(d[39]), "+f"(d[40]), "+f"(d[41]), "+f"(d[42]), "+f"(d[43]), "+f"(d[44]), "+f"(d[45]), "+f"(d[46]), "+f"(d[47])
        : "r"(a[AOFF + 0][0]), "r"(a[AOFF + 0][1]), "r"(a[AOFF + 0][2]), "r"(a[AOFF + 0][3]), "r"(a[AOFF + 1][0]), "r"(a[AOFF + 1][1]), "r"(a[AOFF + 1][2]), "r"(a[AOFF + 1][3]), "r"(a[AOFF + 2][0]), "r"(a[AOFF + 2][1]), "r"(a[AOFF + 2][2]), "r"(a[AOFF + 2][3]), "l"(descB), "n"(BOFF >> 4));
}
};
template <> struct Rng<1, 4, 7> {
template <int BOFF, int AOFF, int NA>
static __device__ __forceinline__ void run(float (&d)[48], const uint32_t (&a)[NA][4], uint64_t descB) {
    asm volatile(
        "{\n"
        ".reg .pred p0, p1;\n"
        ".reg .b64 ta, ta0, tb, tb0;\n"
        "setp.ne.b32 p0, 0, 0;\n"
        "setp.eq.b32 p1, 0, 0;\n"
        "add.s64 tb0, %60, %61;\n"
        "add.s64 tb, tb0, 128;\n"
        "wgmma.mma_async.sync.aligned.m64n96k16.f32.bf16.bf16 {%0, %1, %2, %3, %4, %5, %6, %7, %8, %9, %10, %11, %12, %13, %14, %15, %16, %17, %18, %19, %20, %21, %22, %23, %24, %25, %26, %27, %28, %29, %30, %31, %32, %33, %34, %35, %36, %37, %38, %39, %40, %41, %42, %43, %44, %45, %46, %47}, {%48, %49, %50, %51}, tb, p1, 1, 1, 1;\n"
        "add.s64 tb, tb0, 160;\n"
        "wgmma.mma_async.sync.aligned.m64n96k16.f32.bf16.bf16 {%0, %1, %2, %3, %4, %5, %6, %7, %8, %9, %10, %11, %12, %13, %14, %15, %16, %17, %18, %19, %20, %21, %22, %23, %24, %25, %26, %27, %28, %29, %30, %31, %32, %33, %34, %35, %36, %37, %38, %39, %40, %41, %42, %43, %44, %45, %46, %47}, {%52, %53, %54, %55}, tb, p1, 1, 1, 1;\n"
        "add.s64 tb, tb0, 192;\n"
        "wgmma.mma_async.sync.aligned.m64n96k16.f32.bf16.bf16 {%0, %1, %2, %3, %4, %5, %6, %7, %8, %9, %10, %11, %12, %13, %14, %15, %16, %17, %18, %19, %20, %21, %22, %23, %24, %25, %26, %27, %28, %29, %30, %31, %32, %33, %34, %35, %36, %37, %38, %39, %40, %41, %42, %43, %44, %45, %46, %47}, {%56, %57, %58, %59}, tb, p1, 1, 1, 1;\n"
        "}\n"
        : "+f"(d[0]), "+f"(d[1]), "+f"(d[2]), "+f"(d[3]), "+f"(d[4]), "+f"(d[5]), "+f"(d[6]), "+f"(d[7]), "+f"(d[8]), "+f"(d[9]), "+f"(d[10]), "+f"(d[11]), "+f"(d[12]), "+f"(d[13]), "+f"(d[14]), "+f"(d[15]), "+f"(d[16]), "+f"(d[17]), "+f"(d[18]), "+f"(d[19]), "+f"(d[20]), "+f"(d[21]), "+f"(d[22]), "+f"(d[23]), "+f"(d[24]), "+f"(d[25]), "+f"(d[26]), "+f"(d[27]), "+f"(d[28]), "+f"(d[29]), "+f"(d[30]), "+f"(d[31]), "+f"(d[32]), "+f"(d[33]), "+f"(d[34]), "+f"(d[35]), "+f"(d[36]), "+f"(d[37]), "+f"(d[38]), "+f"(d[39]), "+f"(d[40]), "+f"(d[41]), "+f"(d[42]), "+f"(d[43]), "+f"(d[44]), "+f"(d[45]), "+f"(d[46]), "+f"(d[47])
        : "r"(a[AOFF + 0][0]), "r"(a[AOFF + 0][1]), "r"(a[AOFF + 0][2]), "r"(a[AOFF + 0][3]), "r"(a[AOFF + 1][0]), "r"(a[AOFF + 1][1]), "r"(a[AOFF + 1][2]), "r"(a[AOFF + 1][3]), "r"(a[AOFF + 2][0]), "r"(a[AOFF + 2][1]), "r"(a[AOFF + 2][2]), "r"(a[AOFF + 2][3]), "l"(descB), "n"(BOFF >> 4));
}
};
template <> struct Rng<0, 4, 8> {
template <int BOFF, int AOFF, int NA>
static __device__ __forceinline__ void run(float (&d)[48], const uint32_t (&a)[NA][4], uint64_t descB) {
    asm volatile(
        "{\n"
        ".reg .pred p0, p1;\n"
        ".reg .b64 ta, ta0, tb, tb0;\n"
        "setp.ne.b32 p0, 0, 0;\n"
        "setp.eq.b32 p1, 0, 0;\n"
        "add.s64 tb0, %64, %65;\n"
        "add.s64 tb, tb0, 1536;\n"
        "wgmma.mma_async.sync.aligned.m64n96k16.f32.bf16.bf16 {%0, %1, %2, %3, %4, %5, %6, %7, %8, %9, %10, %11, %12, %13, %14, %15, %16, %17, %18, %19, %20, %21, %22, %23, %24, %25, %26, %27, %28, %29, %30, %31, %32, %33, %34, %35, %36, %37, %38, %39, %40, %41, %42, %43, %44, %45, %46, %47}, {%48, %49, %50, %51}, tb, p1, 1, 1, 1;\n"
        "add.s64 tb, tb0, 1568;\n"
        "wgmma.mma_async.sync.aligned.m64n96k16.f32.bf16.bf16 {%0, %1, %2, %3, %4, %5, %6, %7, %8, %9, %10, %11, %12, %13, %14, %15, %16, %17, %18, %19, %20, %21, %22, %23, %24, %25, %26, %27, %28, %29, %30, %31, %32, %33, %34, %35, %36, %37, %38, %39, %40, %41, %42, %43, %44, %45, %46, %47}, {%52, %53, %54, %55}, tb, p1, 1, 1, 1;\n"
        "add.s64 tb, tb0, 1600;\n"
        "wgmma.mma_async.sync.aligned.m64n96k16.f32.bf16.bf16 {%0, %1, %2, %3, %4, %5, %6, %7, %8, %9, %10, %11, %12, %13, %14, %15, %16, %17, %18, %19, %20, %21, %22, %23, %24, %25, %26, %27, %28, %29, %30, %31, %32, %33, %34, %35, %36, %37, %38, %39, %40, %41, %42, %43, %44, %45, %46, %47}, {%56, %57, %58, %59}, tb, p1, 1, 1, 1;\n"
        "add.s64 tb, tb0, 1632;\n"
        "wgmma.mma_async.sync.aligned.m64n96k16.f32.bf16.bf16 {%0, %1, %2, %3, %4, %5, %6, %7, %8, %9, %10, %11, %12, %13, %14, %15, %16, %17, %18, %19, %20, %21, %22, %23, %24, %25, %26, %27, %28, %29, %30, %31, %32, %33, %34, %35, %36, %37, %38, %39, %40, %41, %42, %43, %44, %45, %46, %47}, {%60, %61, %62, %63}, tb, p1, 1, 1, 1;\n"
        "}\n"
        : "+f"(d[0]), "+f"(d[1]), "+f"(d[2]), "+f"(d[3]), "+f"(d[4]), "+f"(d[5]), "+f"(d[6]), "+f"(d[7]), "+f"(d[8]), "+f"(d[9]), "+f"(d[10]), "+f"(d[11]), "+f"(d[12]), "+f"(d[13]), "+f"(d[14]), "+f"(d[15]), "+f"(d[16]), "+f"(d[17]), "+f"(d[18]), "+f"(d[19]), "+f"(d[20]), "+f"(d[21]), "+f"(d[22]), "+f"(d[23]), "+f"(d[24]), "+f"(d[25]), "+f"(d[26]), "+f"(d[27]), "+f"(d[28]), "+f"(d[29]), "+f"(d[30]), "+f"(d[31]), "+f"(d[32]), "+f"(d[33]), "+f"(d[34]), "+f"(d[35]), "+f"(d[36]), "+f"(d[37]), "+f"(d[38]), "+f"(d[39]), "+f"(d[40]), "+f"(d[41]), "+f"(d[42]), "+f"(d[43]), "+f"(d[44]), "+f"(d[45]), "+f"(d[46]), "+f"(d[47])
        : "r"(a[AOFF + 0][0]), "r"(a[AOFF + 0][1]), "r"(a[AOFF + 0][2]), "r"(a[AOFF + 0][3]), "r"(a[AOFF + 1][0]), "r"(a[AOFF + 1][1]), "r"(a[AOFF + 1][2]), "r"(a[AOFF + 1][3]), "r"(a[AOFF + 2][0]), "r"(a[AOFF + 2][1]), "r"(a[AOFF + 2][2]), "r"(a[AOFF + 2][3]), "r"(a[AOFF + 3][0]), "r"(a[AOFF + 3][1]), "r"(a[AOFF + 3][2]), "r"(a[AOFF + 3][3]), "l"(descB), "n"(BOFF >> 4));
}
};
template <> struct Rng<1, 4, 8> {
template <int BOFF, int AOFF, int NA>
static __device__ __forceinline__ void run(float (&d)[48], const uint32_t (&a)[NA][4], uint64_t descB) {
    asm volatile(
        "{\n"
        ".reg .pred p0, p1;\n"
        ".reg .b64 ta, ta0, tb, tb0;\n"
        "setp.ne.b32 p0, 0, 0;\n"
        "setp.eq.b32 p1, 0, 0;\n"
        "add.s64 tb0, %64, %65;\n"
        "add.s64 tb, tb0, 128;\n"
        "wgmma.mma_async.sync.aligned.m64n96k16.f32.bf16.bf16 {%0, %1, %2, %3, %4, %5, %6, %7, %8, %9, %10, %11, %12, %13, %14, %15, %16, %17, %18, %19, %20, %21, %22, %23, %24, %25, %26, %27, %28, %29, %30, %31, %32, %33, %34, %35, %36, %37, %38, %39, %40, %41, %42, %43, %44, %45, %46, %47}, {%48, %49, %50, %51}, tb, p1, 1, 1, 1;\n"
        "add.s64 tb, tb0, 160;\n"
        "wgmma.mma_async.sync.aligned.m64n96k16.f32.bf16.bf16 {%0, %1, %2, %3, %4, %5, %6, %7, %8, %9, %10, %11, %12, %13, %14, %15, %16, %17, %18, %19, %20, %21, %22, %23, %24, %25, %26, %27, %28, %29, %30, %31, %32, %33, %34, %35, %36, %37, %38, %39, %40, %41, %42, %43, %44, %45, %46, %47}, {%52, %53, %54, %55}, tb, p1, 1, 1, 1;\n"
        "add.s64 tb, tb0, 192;\n"
        "wgmma.mma_async.sync.aligned.m64n96k16.f32.bf16.bf16 {%0, %1, %2, %3, %4, %5, %6, %7, %8, %9, %10, %11, %12, %13, %14, %15, %16, %17, %18, %19, %20, %21, %22, %23, %24, %25, %26, %27, %28, %29, %30, %31, %32, %33, %34, %35, %36, %37, %38, %39, %40, %41, %42, %43, %44, %45, %46, %47}, {%56, %57, %58, %59}, tb, p1, 1, 1, 1;\n"
        "add.s64 tb, tb0, 224;\n"
        "wgmma.mma_async.sync.aligned.m64n96k16.f32.bf16.bf16 {%0, %1, %2, %3, %4, %5, %6, %7, %8, %9, %10, %11, %12, %13, %14, %15, %16, %17, %18, %19, %20, %21, %22, %23, %24, %25, %26, %27, %28, %29, %30, %31, %32, %33, %34, %35, %36, %37, %38, %39, %40, %41, %42, %43, %44, %45, %46, %47}, {%60, %61, %62, %63}, tb, p1, 1, 1, 1;\n"
        "}\n"
        : "+f"(d[0]), "+f"(d[1]), "+f"(d[2]), "+f"(d[3]), "+f"(d[4]), "+f"(d[5]), "+f"(d[6]), "+f"(d[7]), "+f"(d[8]), "+f"(d[9]), "+f"(d[10]), "+f"(d[11]), "+f"(d[12]), "+f"(d[13]), "+f"(d[14]), "+f"(d[15]), "+f"(d[16]), "+f"(d[17]), "+f"(d[18]), "+f"(d[19]), "+f"(d[20]), "+f"(d[21]), "+f"(d[22]), "+f"(d[23]), "+f"(d[24]), "+f"(d[25]), "+f"(d[26]), "+f"(d[27]), "+f"(d[28]), "+f"(d[29]), "+f"(d[30]), "+f"(d[31]), "+f"(d[32]), "+f"(d[33]), "+f"(d[34]), "+f"(d[35]), "+f"(d[36]), "+f"(d[37]), "+f"(d[38]), "+f"(d[39]), "+f"(d[40]), "+f"(d[41]), "+f"(d[42]), "+f"(d[43]), "+f"(d[44]), "+f"(d[45]), "+f"(d[46]), "+f"(d[47])
        : "r"(a[AOFF + 0][0]), "r"(a[AOFF + 0][1]), "r"(a[AOFF + 0][2]), "r"(a[AOFF + 0][3]), "r"(a[AOFF + 1][0]), "r"(a[AOFF + 1][1]), "r"(a[AOFF + 1][2]), "r"(a[AOFF + 1][3]), "r"(a[AOFF + 2][0]), "r"(a[AOFF + 2][1]), "r"(a[AOFF + 2][2]), "r"(a[AOFF + 2][3]), "r"(a[AOFF + 3][0]), "r"(a[AOFF + 3][1]), "r"(a[AOFF + 3][2]), "r"(a[AOFF + 3][3]), "l"(descB), "n"(BOFF >> 4));
}
};
template <> struct Rng<0, 4, 9> {
template <int BOFF, int AOFF, int NA>
static __device__ __forceinline__ void run(float (&d)[48], const uint32_t (&a)[NA][4], uint64_t descB) {
    asm volatile(
        "{\n"
        ".reg .pred p0, p1;\n"
        ".reg .b64 ta, ta0, tb, tb0;\n"
        "setp.ne.b32 p0, 0, 0;\n"
        "setp.eq.b32 p1, 0, 0;\n"
        "add.s64 tb0, %68, %69;\n"
        "add.s64 tb, tb0, 1536;\n"
        "wgmma.mma_async.sync.aligned.m64n96k16.f32.bf16.bf16 {%0, %1, %2, %3, %4, %5, %6, %7, %8, %9, %10, %11, %12, %13, %14, %15, %16, %17, %18, %19, %20, %21, %22, %23, %24, %25, %26, %27, %28, %29, %30, %31, %32, %33, %34, %35, %36, %37, %38, %39, %40, %41, %42, %43, %44, %45, %46, %47}, {%48, %49, %50, %51}, tb, p1, 1, 1, 1;\n"
        "add.s64 tb, tb0, 1568;\n"
        "wgmma.mma_async.sync.aligned.m64n96k16.f32.bf16.bf16 {%0, %1, %2, %3, %4, %5, %6, %7, %8, %9, %10, %11, %12, %13, %14, %15, %16, %17, %18, %19, %20, %21, %22, %23, %24, %25, %26, %27, %28, %29, %30, %31, %32, %33, %34, %35, %36, %37, %38, %39, %40, %41, %42, %43, %44, %45, %46, %47}, {%52, %53, %54, %55}, tb, p1, 1, 1, 1;\n"
        "add.s64 tb, tb0, 1600;\n"
        "wgmma.mma_async.sync.aligned.m64n96k16.f32.bf16.bf16 {%0, %1, %2, %3, %4, %5, %6, %7, %8, %9, %10, %11, %12, %13, %14, %15, %16, %17, %18, %19, %20, %21, %22, %23, %24, %25, %26, %27, %28, %29, %30, %31, %32, %33, %34, %35, %36, %37, %38, %39, %40, %41, %42, %43, %44, %45, %46, %47}, {%56, %57, %58, %59}, tb, p1, 1, 1, 1;\n"
        "add.s64 tb, tb0, 1632;\n"
        "wgmma.mma_async.sync.aligned.m64n96k16.f32.bf16.bf16 {%0, %1, %2, %3, %4, %5, %6, %7, %8, %9, %10, %11, %12, %13, %14, %15, %16, %17, %18, %19, %20, %21, %22, %23, %24, %25, %26, %27, %28, %29, %30, %31, %32, %33, %34, %35, %36, %37, %38, %39, %40, %41, %42, %43, %44, %45, %46, %47}, {%60, %61, %62, %63}, tb, p1, 1, 1, 1;\n"
        "add.s64 tb, tb0, 3072;\n"
        "wgmma.mma_async.sync.aligned.m64n96k16.f32.bf16.bf16 {%0, %1, %2, %3, %4, %5, %6, %7, %8, %9, %10, %11, %12, %13, %14, %15, %16, %17, %18, %19, %20, %21, %22, %23, %24, %25, %26, %27, %28, %29, %30, %31, %32, %33, %34, %35, %36, %37, %38, %39, %40, %41, %42, %43, %44, %45, %46, %47}, {%64, %65, %66, %67}, tb, p1, 1, 1, 1;\n"
        "}\n"
        : "+f"(d[0]), "+f"(d[1]), "+f"(d[2]), "+f"(d[3]), "+f"(d[4]), "+f"(d[5]), "+f"(d[6]), "+f"(d[7]), "+f"(d[8]), "+f"(d[9]), "+f"(d[10]), "+f"(d[11]), "+f"(d[12]), "+f"(d[13]), "+f"(d[14]), "+f"(d[15]), "+f"(d[16]), "+f"(d[17]), "+f"(d[18]), "+f"(d[19]), "+f"(d[20]), "+f"(d[21]), "+f"(d[22]), "+f"(d[23]), "+f"(d[24]), "+f"(d[25]), "+f"(d[26]), "+f"(d[27]), "+f"(d[28]), "+f"(d[29]), "+f"(d[30]), "+f"(d[31]), "+f"(d[32]), "+f"(d[33]), "+f"(d[34]), "+f"(d[35]), "+f"(d[36]), "+f"(d[37]), "+f"(d[38]), "+f"(d[39]), "+f"(d[40]), "+f"(d[41]), "+f"(d[42]), "+f"(d[43]), "+f"(d[44]), "+f"(d[45]), "+f"(d[46]), "+f"(d[47])
        : "r"(a[AOFF + 0][0]), "r"(a[AOFF + 0][1]), "r"(a[AOFF + 0][2]), "r"(a[AOFF + 0][3]), "r"(a[AOFF + 1][0]), "r"(a[AOFF + 1][1]), "r"(a[AOFF + 1][2]), "r"(a[AOFF + 1][3]), "r"(a[AOFF + 2][0]), "r"(a[AOFF + 2][1]), "r"(a[AOFF + 2][2]), "r"(a[AOFF + 2][3]), "r"(a[AOFF + 3][0]), "r"(a[AOFF + 3][1]), "r"(a[AOFF + 3][2]), "r"(a[AOFF + 3][3]), "r"(a[AOFF + 4][0]), "r"(a[AOFF + 4][1]), "r"(a[AOFF + 4][2]), "r"(a[AOFF + 4][3]), "l"(descB), "n"(BOFF >> 4));
}
};
template <> struct Rng<1, 4, 9> {
template <int BOFF, int AOFF, int NA>
static __device__ __forceinline__ void run(float (&d)[48], const uint32_t (&a)[NA][4], uint64_t descB) {
    asm volatile(
        "{\n"
        ".reg .pred p0, p1;\n"
        ".reg .b64 ta, ta0, tb, tb0;\n"
        "setp.ne.b32 p0, 0, 0;\n"
        "setp.eq.b32 p1, 0, 0;\n"
        "add.s64 tb0, %68, %69;\n"
        "add.s64 tb, tb0, 128;\n"
        "wgmma.mma_async.sync.aligned.m64n96k16.f32.bf16.bf16 {%0, %1, %2, %3, %4, %5, %6, %7, %8, %9, %10, %11, %12, %13, %14, %15, %16, %17, %18, %19, %20, %21, %22, %23, %24, %25, %26, %27, %28, %29, %30, %31, %32, %33, %34, %35, %36, %37, %38, %39, %40, %41, %42, %43, %44, %45, %46, %47}, {%48, %49, %50, %51}, tb, p1, 1, 1, 1;\n"
        "add.s64 tb, tb0, 160;\n"
        "wgmma.mma_async.sync.aligned.m64n96k16.f32.bf16.bf16 {%0, %1, %2, %3, %4, %5, %6, %7, %8, %9, %10, %11, %12, %13, %14, %15, %16, %17, %18, %19, %20, %21, %22, %23, %24, %25, %26, %27, %28, %29, %30, %31, %32, %33, %34, %35, %36, %37, %38, %39, %40, %41, %42, %43, %44, %45, %46, %47}, {%52, %53, %54, %55}, tb, p1, 1, 1, 1;\n"
        "add.s64 tb, tb0, 192;\n"
        "wgmma.mma_async.sync.aligned.m64n96k16.f32.bf16.bf16 {%0, %1, %2, %3, %4, %5, %6, %7, %8, %9, %10, %11, %12, %13, %14, %15, %16, %17, %18, %19, %20, %21, %22, %23, %24, %25, %26, %27, %28, %29, %30, %31, %32, %33, %34, %35, %36, %37, %38, %39, %40, %41, %42, %43, %44, %45, %46, %47}, {%56, %57, %58, %59}, tb, p1, 1, 1, 1;\n"
        "add.s64 tb, tb0, 224;\n"
        "wgmma.mma_async.sync.aligned.m64n96k16.f32.bf16.bf16 {%0, %1, %2, %3, %4, %5, %6, %7, %8, %9, %10, %11, %12, %13, %14, %15, %16, %17, %18, %19, %20, %21, %22, %23, %24, %25, %26, %27, %28, %29, %30, %31, %32, %33, %34, %35, %36, %37, %38, %39, %40, %41, %42, %43, %44, %45, %46, %47}, {%60, %61, %62, %63}, tb, p1, 1, 1, 1;\n"
        "add.s64 tb, tb0, 256;\n"
        "wgmma.mma_async.sync.aligned.m64n96k16.f32.bf16.bf16 {%0, %1, %2, %3, %4, %5, %6, %7, %8, %9, %10, %11, %12, %13, %14, %15, %16, %17, %18, %19, %20, %21, %22, %23, %24, %25, %26, %27, %28, %29, %30, %31, %32, %33, %34, %35, %36, %37, %38, %39, %40, %41, %42, %43, %44, %45, %46, %47}, {%64, %65, %66, %67}, tb, p1, 1, 1, 1;\n"
        "}\n"
        : "+f"(d[0]), "+f"(d[1]), "+f"(d[2]), "+f"(d[3]), "+f"(d[4]), "+f"(d[5]), "+f"(d[6]), "+f"(d[7]), "+f"(d[8]), "+f"(d[9]), "+f"(d[10]), "+f"(d[11]), "+f"(d[12]), "+f"(d[13]), "+f"(d[14]), "+f"(d[15]), "+f"(d[16]), "+f"(d[17]), "+f"(d[18]), "+f"(d[19]), "+f"(d[20]), "+f"(d[21]), "+f"(d[22]), "+f"(d[23]), "+f"(d[24]), "+f"(d[25]), "+f"(d[26]), "+f"(d[27]), "+f"(d[28]), "+f"(d[29]), "+f"(d[30]), "+f"(d[31]), "+f"(d[32]), "+f"(d[33]), "+f"(d[34]), "+f"(d[35]), "+f"(d[36]), "+f"(d[37]), "+f"(d[38]), "+f"(d[39]), "+f"(d[40]), "+f"(d[41]), "+f"(d[42]), "+f"(d[43]), "+f"(d[44]), "+f"(d[45]), "+f"(d[46]), "+f"(d[47])
        : "r"(a[AOFF + 0][0]), "r"(a[AOFF + 0][1]), "r"(a[AOFF + 0][2]), "r"(a[AOFF + 0][3]), "r"(a[AOFF + 1][0]), "r"(a[AOFF + 1][1]), "r"(a[AOFF + 1][2]), "r"(a[AOFF + 1][3]), "r"(a[AOFF + 2][0]), "r"(a[AOFF + 2][1]), "r"(a[AOFF + 2][2]), "r"(a[AOFF + 2][3]), "r"(a[AOFF + 3][0]), "r"(a[AOFF + 3][1]), "r"(a[AOFF + 3][2]), "r"(a[AOFF + 3][3]), "r"(a[AOFF + 4][0]), "r"(a[AOFF + 4][1]), "r"(a[AOFF + 4][2]), "r"(a[AOFF + 4][3]), "l"(descB), "n"(BOFF >> 4));
}
};
template <> struct Rng<0, 4, 12> {
template <int BOFF, int AOFF, int NA>
static __device__ __forceinline__ void run(float (&d)[48], const uint32_t (&a)[NA][4], uint64_t descB) {
    asm volatile(
        "{\n"
        ".reg .pred p0, p1;\n"
        ".reg .b64 ta, ta0, tb, tb0;\n"
        "setp.ne.b32 p0, 0, 0;\n"
        "setp.eq.b32 p1, 0, 0;\n"
        "add.s64 tb0, %80, %81;\n"
        "add.s64 tb, tb0, 1536;\n"
        "wgmma.mma_async.sync.aligned.m64n96k16.f32.bf16.bf16 {%0, %1, %2, %3, %4, %5, %6, %7, %8, %9, %10, %11, %12, %13, %14, %15, %16, %17, %18, %19, %20, %21, %22, %23, %24, %25, %26, %27, %28, %29, %30, %31, %32, %33, %34, %35, %36, %37, %38, %39, %40, %41, %42, %43, %44, %45, %46, %47}, {%48, %49, %50, %51}, tb, p1, 1, 1, 1;\n"
        "add.s64 tb, tb0, 1568;\n"
        "wgmma.mma_async.sync.aligned.m64n96k16.f32.bf16.bf16 {%0, %1, %2, %3, %4, %5, %6, %7, %8, %9, %10, %11, %12, %13, %14, %15, %16, %17, %18, %19, %20, %21, %22, %23, %24, %25, %26, %27, %28, %29, %30, %31, %32, %33, %34, %35, %36, %37, %38, %39, %40, %41, %42, %43, %44, %45, %46, %47}, {%52, %53, %54, %55}, tb, p1, 1, 1, 1;\n"
        "add.s64 tb, tb0, 1600;\n"
        "wgmma.mma_async.sync.aligned.m64n96k16.f32.bf16.bf16 {%0, %1, %2, %3, %4, %5, %6, %7, %8, %9, %10, %11, %12, %13, %14, %15, %16, %17, %18, %19, %20, %21, %22, %23, %24, %25, %26, %27, %28, %29, %30, %31, %32, %33, %34, %35, %36, %37, %38, %39, %40, %41, %42, %43, %44, %45, %46, %47}, {%56, %57, %58, %59}, tb, p1, 1, 1, 1;\n"
        "add.s64 tb, tb0, 1632;\n"
        "wgmma.mma_async.sync.aligned.m64n96k16.f32.bf16.bf16 {%0, %1, %2, %3, %4, %5, %6, %7, %8, %9, %10, %11, %12, %13, %14, %15, %16, %17, %18, %19, %20, %21, %22, %23, %24, %25, %26, %27, %28, %29, %30, %31, %32, %33, %34, %35, %36, %37, %38, %39, %40, %41, %42, %43, %44, %45, %46, %47}, {%60, %61, %62, %63}, tb, p1, 1, 1, 1;\n"
        "add.s64 tb, tb0, 3072;\n"
        "wgmma.mma_async.sync.aligned.m64n96k16.f32.bf16.bf16 {%0, %1, %2, %3, %4, %5, %6, %7, %8, %9, %10, %11, %12, %13, %14, %15, %16, %17, %18, %19, %20, %21, %22, %23, %24, %25, %26, %27, %28, %29, %30, %31, %32, %33, %34, %35, %36, %37, %38, %39, %40, %41, %42, %43, %44, %45, %46, %47}, {%64, %65, %66, %67}, tb, p1, 1, 1, 1;\n"
        "add.s64 tb, tb0, 3104;\n"
        "wgmma.mma_async.sync.aligned.m64n96k16.f32.bf16.bf16 {%0, %1, %2, %3, %4, %5, %6, %7, %8, %9, %10, %11, %12, %13, %14, %15, %16, %17, %18, %19, %20, %21, %22, %23, %24, %25, %26, %27, %28, %29, %30, %31, %32, %33, %34, %35, %36, %37, %38, %39, %40, %41, %42, %43, %44, %45, %46, %47}, {%68, %69, %70, %71}, tb, p1, 1, 1, 1;\n"
        "add.s64 tb, tb0, 3136;\n"
        "wgmma.mma_async.sync.aligned.m64n96k16.f32.bf16.bf16 {%0, %1, %2, %3, %4, %5, %6, %7, %8, %9, %10, %11, %12, %13, %14, %15, %16, %17, %18, %19, %20, %21, %22, %23, %24, %25, %26, %27, %28, %29, %30, %31, %32, %33, %34, %35, %36, %37, %38, %39, %40, %41, %42, %43, %44, %45, %46, %47}, {%72, %73, %74, %75}, tb, p1, 1, 1, 1;\n"
        "add.s64 tb, tb0, 3168;\n"
        "wgmma.mma_async.sync.aligned.m64n96k16.f32.bf16.bf16 {%0, %1, %2, %3, %4, %5, %6, %7, %8, %9, %10, %11, %12, %13, %14, %15, %16, %17, %18, %19, %20, %21, %22, %23, %24, %25, %26, %27, %28, %29, %30, %31, %32, %33, %34, %35, %36, %37, %38, %39, %40, %41, %42, %43, %44, %45, %46, %47}, {%76, %77, %78, %79}, tb, p1, 1, 1, 1;\n"
        "}\n"
        : "+f"(d[0]), "+f"(d[1]), "+f"(d[2]), "+f"(d[3]), "+f"(d[4]), "+f"(d[5]), "+f"(d[6]), "+f"(d[7]), "+f"(d[8]), "+f"(d[9]), "+f"(d[10]), "+f"(d[11]), "+f"(d[12]), "+f"(d[13]), "+f"(d[14]), "+f"(d[15]), "+f"(d[16]), "+f"(d[17]), "+f"(d[18]), "+f"(d[19]), "+f"(d[20]), "+f"(d[21]), "+f"(d[22]), "+f"(d[23]), "+f"(d[24]), "+f"(d[25]), "+f"(d[26]), "+f"(d[27]), "+f"(d[28]), "+f"(d[29]), "+f"(d[30]), "+f"(d[31]), "+f"(d[32]), "+f"(d[33]), "+f"(d[34]), "+f"(d[35]), "+f"(d[36]), "+f"(d[37]), "+f"(d[38]), "+f"(d[39]), "+f"(d[40]), "+f"(d[41]), "+f"(d[42]), "+f"(d[43]), "+f"(d[44]), "+f"(d[45]), "+f"(d[46]), "+f"(d[47])
        : "r"(a[AOFF + 0][0]), "r"(a[AOFF + 0][1]), "r"(a[AOFF + 0][2]), "r"(a[AOFF + 0][3]), "r"(a[AOFF + 1][0]), "r"(a[AOFF + 1][1]), "r"(a[AOFF + 1][2]), "r"(a[AOFF + 1][3]), "r"(a[AOFF + 2][0]), "r"(a[AOFF + 2][1]), "r"(a[AOFF + 2][2]), "r"(a[AOFF + 2][3]), "r"(a[AOFF + 3][0]), "r"(a[AOFF + 3][1]), "r"(a[AOFF + 3][2]), "r"(a[AOFF + 3][3]), "r"(a[AOFF + 4][0]), "r"(a[AOFF + 4][1]), "r"(a[AOFF + 4][2]), "r"(a[AOFF + 4][3]), "r"(a[AOFF + 5][0]), "r"(a[AOFF + 5][1]), "r"(a[AOFF + 5][2]), "r"(a[AOFF + 5][3]), "r"(a[AOFF + 6][0]), "r"(a[AOFF + 6][1]), "r"(a[AOFF + 6][2]), "r"(a[AOFF + 6][3]), "r"(a[AOFF + 7][0]), "r"(a[AOFF + 7][1]), "r"(a[AOFF + 7][2]), "r"(a[AOFF + 7][3]), "l"(descB), "n"(BOFF >> 4));
}
};
template <> struct Rng<1, 4, 12> {
template <int BOFF, int AOFF, int NA>
static __device__ __forceinline__ void run(float (&d)[48], const uint32_t (&a)[NA][4], uint64_t descB) {
    asm volatile(
        "{\n"
        ".reg .pred p0, p1;\n"
        ".reg .b64 ta, ta0, tb, tb0;\n"
        "setp.ne.b32 p0, 0, 0;\n"
        "setp.eq.b32 p1, 0, 0;\n"
        "add.s64 tb0, %80, %81;\n"
        "add.s64 tb, tb0, 128;\n"
        "wgmma.mma_async.sync.aligned.m64n96k16.f32.bf16.bf16 {%0, %1, %2, %3, %4, %5, %6, %7, %8, %9, %10, %11, %12, %13, %14, %15, %16, %17, %18, %19, %20, %21, %22, %23, %24, %25, %26, %27, %28, %29, %30, %31, %32, %33, %34, %35, %36, %37, %38, %39, %40, %41, %42, %43, %44, %45, %46, %47}, {%48, %49, %50, %51}, tb, p1, 1, 1, 1;\n"
        "add.s64 tb, tb0, 160;\n"
        "wgmma.mma_async.sync.aligned.m64n96k16.f32.bf16.bf16 {%0, %1, %2, %3, %4, %5, %6, %7, %8, %9, %10, %11, %12, %13, %14, %15, %16, %17, %18, %19, %20, %21, %22, %23, %24, %25, %26, %27, %28, %29, %30, %31, %32, %33, %34, %35, %36, %37, %38, %39, %40, %41, %42, %43, %44, %45, %46, %47}, {%52, %53, %54, %55}, tb, p1, 1, 1, 1;\n"
        "add.s64 tb, tb0, 192;\n"
        "wgmma.mma_async.sync.aligned.m64n96k16.f32.bf16.bf16 {%0, %1, %2, %3, %4, %5, %6, %7, %8, %9, %10, %11, %12, %13, %14, %15, %16, %17, %18, %19, %20, %21, %22, %23, %24, %25, %26, %27, %28, %29, %30, %31, %32, %33, %34, %35, %36, %37, %38, %39, %40, %41, %42, %43, %44, %45, %46, %47}, {%56, %57, %58, %59}, tb, p1, 1, 1, 1;\n"
        "add.s64 tb, tb0, 224;\n"
        "wgmma.mma_async.sync.aligned.m64n96k16.f32.bf16.bf16 {%0, %1, %2, %3, %4, %5, %6, %7, %8, %9, %10, %11, %12, %13, %14, %15, %16, %17, %18, %19, %20, %21, %22, %23, %24, %25, %26, %27, %28, %29, %30, %31, %32, %33, %34, %35, %36, %37, %38, %39, %40, %41, %42, %43, %44, %45, %46, %47}, {%60, %61, %62, %63}, tb, p1, 1, 1, 1;\n"
        "add.s64 tb, tb0, 256;\n"
        "wgmma.mma_async.sync.aligned.m64n96k16.f32.bf16.bf16 {%0, %1, %2, %3, %4, %5, %6, %7, %8, %9, %10, %11, %12, %13, %14, %15, %16, %17, %18, %19, %20, %21, %22, %23, %24, %25, %26, %27, %28, %29, %30, %31, %32, %33, %34, %35, %36, %37, %38, %39, %40, %41, %42, %43, %44, %45, %46, %47}, {%64, %65, %66, %67}, tb, p1, 1, 1, 1;\n"
        "add.s64 tb, tb0, 288;\n"
        "wgmma.mma_async.sync.aligned.m64n96k16.f32.bf16.bf16 {%0, %1, %2, %3, %4, %5, %6, %7, %8, %9, %10, %11, %12, %13, %14, %15, %16, %17, %18, %19, %20, %21, %22, %23, %24, %25, %26, %27, %28, %29, %30, %31, %32, %33, %34, %35, %36, %37, %38, %39, %40, %41, %42, %43, %44, %45, %46, %47}, {%68, %69, %70, %71}, tb, p1, 1, 1, 1;\n"
        "add.s64 tb, tb0, 320;\n"
        "wgmma.mma_async.sync.aligned.m64n96k16.f32.bf16.bf16 {%0, %1, %2, %3, %4, %5, %6, %7, %8, %9, %10, %11, %12, %13, %14, %15, %16, %17, %18, %19, %20, %21, %22, %23, %24, %25, %26, %27, %28, %29, %30, %31, %32, %33, %34, %35, %36, %37, %38, %39, %40, %41, %42, %43, %44, %45, %46, %47}, {%72, %73, %74, %75}, tb, p1, 1, 1, 1;\n"
        "add.s64 tb, tb0, 352;\n"
        "wgmma.mma_async.sync.aligned.m64n96k16.f32.bf16.bf16 {%0, %1, %2, %3, %4, %5, %6, %7, %8, %9, %10, %11, %12, %13, %14, %15, %16, %17, %18, %19, %20, %21, %22, %23, %24, %25, %26, %27, %28, %29, %30, %31, %32, %33, %34, %35, %36, %37, %38, %39, %40, %41, %42, %43, %44, %45, %46, %47}, {%76, %77, %78, %79}, tb, p1, 1, 1, 1;\n"
        "}\n"
        : "+f"(d[0]), "+f"(d[1]), "+f"(d[2]), "+f"(d[3]), "+f"(d[4]), "+f"(d[5]), "+f"(d[6]), "+f"(d[7]), "+f"(d[8]), "+f"(d[9]), "+f"(d[10]), "+f"(d[11]), "+f"(d[12]), "+f"(d[13]), "+f"(d[14]), "+f"(d[15]), "+f"(d[16]), "+f"(d[17]), "+f"(d[18]), "+f"(d[19]), "+f"(d[20]), "+f"(d[21]), "+f"(d[22]), "+f"(d[23]), "+f"(d[24]), "+f"(d[25]), "+f"(d[26]), "+f"(d[27]), "+f"(d[28]), "+f"(d[29]), "+f"(d[30]), "+f"(d[31]), "+f"(d[32]), "+f"(d[33]), "+f"(d[34]), "+f"(d[35]), "+f"(d[36]), "+f"(d[37]), "+f"(d[38]), "+f"(d[39]), "+f"(d[40]), "+f"(d[41]), "+f"(d[42]), "+f"(d[43]), "+f"(d[44]), "+f"(d[45]), "+f"(d[46]), "+f"(d[47])
        : "r"(a[AOFF + 0][0]), "r"(a[AOFF + 0][1]), "r"(a[AOFF + 0][2]), "r"(a[AOFF + 0][3]), "r"(a[AOFF + 1][0]), "r"(a[AOFF + 1][1]), "r"(a[AOFF + 1][2]), "r"(a[AOFF + 1][3]), "r"(a[AOFF + 2][0]), "r"(a[AOFF + 2][1]), "r"(a[AOFF + 2][2]), "r"(a[AOFF + 2][3]), "r"(a[AOFF + 3][0]), "r"(a[AOFF + 3][1]), "r"(a[AOFF + 3][2]), "r"(a[AOFF + 3][3]), "r"(a[AOFF + 4][0]), "r"(a[AOFF + 4][1]), "r"(a[AOFF + 4][2]), "r"(a[AOFF + 4][3]), "r"(a[AOFF + 5][0]), "r"(a[AOFF + 5][1]), "r"(a[AOFF + 5][2]), "r"(a[AOFF + 5][3]), "r"(a[AOFF + 6][0]), "r"(a[AOFF + 6][1]), "r"(a[AOFF + 6][2]), "r"(a[AOFF + 6][3]), "r"(a[AOFF + 7][0]), "r"(a[AOFF + 7][1]), "r"(a[AOFF + 7][2]), "r"(a[AOFF + 7][3]), "l"(descB), "n"(BOFF >> 4));
}
};
template <> struct Rng<0, 5, 8> {
template <int BOFF, int AOFF, int NA>
static __device__ __forceinline__ void run(float (&d)[48], const uint32_t (&a)[NA][4], uint64_t descB) {
    asm volatile(
        "{\n"
        ".reg .pred p0, p1;\n"
        ".reg .b64 ta, ta0, tb, tb0;\n"
        "setp.ne.b32 p0, 0, 0;\n"
        "setp.eq.b32 p1, 0, 0;\n"
        "add.s64 tb0, %60, %61;\n"
        "add.s64 tb, tb0, 1568;\n"
        "wgmma.mma_async.sync.aligned.m64n96k16.f32.bf16.bf16 {%0, %1, %2, %3, %4, %5, %6, %7, %8, %9, %10, %11, %12, %13, %14, %15, %16, %17, %18, %19, %20, %21, %22, %23, %24, %25, %26, %27, %28, %29, %30, %31, %32, %33, %34, %35, %36, %37, %38, %39, %40, %41, %42, %43, %44, %45, %46, %47}, {%48, %49, %50, %51}, tb, p1, 1, 1, 1;\n"
        "add.s64 tb, tb0, 1600;\n"
        "wgmma.mma_async.sync.aligned.m64n96k16.f32.bf16.bf16 {%0, %1, %2, %3, %4, %5, %6, %7, %8, %9, %10, %11, %12, %13, %14, %15, %16, %17, %18, %19, %20, %21, %22, %23, %24, %25, %26, %27, %28, %29, %30, %31, %32, %33, %34, %35, %36, %37, %38, %39, %40, %41, %42, %43, %44, %45, %46, %47}, {%52, %53, %54, %55}, tb, p1, 1, 1, 1;\n"
        "add.s64 tb, tb0, 1632;\n"
        "wgmma.mma_async.sync.aligned.m64n96k16.f32.bf16.bf16 {%0, %1, %2, %3, %4, %5, %6, %7, %8, %9, %10, %11, %12, %13, %14, %15, %16, %17, %18, %19, %20, %21, %22, %23, %24, %25, %26, %27, %28, %29, %30, %31, %32, %33, %34, %35, %36, %37, %38, %39, %40, %41, %42, %43, %44, %45, %46, %47}, {%56, %57, %58, %59}, tb, p1, 1, 1, 1;\n"
        "}\n"
        : "+f"(d[0]), "+f"(d[1]), "+f"(d[2]), "+f"(d[3]), "+f"(d[4]), "+f"(d[5]), "+f"(d[6]), "+f"(d[7]), "+f"(d[8]), "+f"(d[9]), "+f"(d[10]), "+f"(d[11]), "+f"(d[12]), "+f"(d[13]), "+f"(d[14]), "+f"(d[15]), "+f"(d[16]), "+f"(d[17]), "+f"(d[18]), "+f"(d[19]), "+f"(d[20]), "+f"(d[21]), "+f"(d[22]), "+f"(d[23]), "+f"(d[24]), "+f"(d[25]), "+f"(d[26]), "+f"(d[27]), "+f"(d[28]), "+f"(d[29]), "+f"(d[30]), "+f"(d[31]), "+f"(d[32]), "+f"(d[33]), "+f"(d[34]), "+f"(d[35]), "+f"(d[36]), "+f"(d[37]), "+f"(d[38]), "+f"(d[39]), "+f"(d[40]), "+f"(d[41]), "+f"(d[42]), "+f"(d[43]), "+f"(d[44]), "+f"(d[45]), "+f"(d[46]), "+f"(d[47])
        : "r"(a[AOFF + 0][0]), "r"(a[AOFF + 0][1]), "r"(a[AOFF + 0][2]), "r"(a[AOFF + 0][3]), "r"(a[AOFF + 1][0]), "r"(a[AOFF + 1][1]), "r"(a[AOFF + 1][2]), "r"(a[AOFF + 1][3]), "r"(a[AOFF + 2][0]), "r"(a[AOFF + 2][1]), "r"(a[AOFF + 2][2]), "r"(a[AOFF + 2][3]), "l"(descB), "n"(BOFF >> 4));
}
};
template <> struct Rng<1, 5, 8> {
template <int BOFF, int AOFF, int NA>
static __device__ __forceinline__ void run(float (&d)[48], const uint32_t (&a)[NA][4], uint64_t descB) {
    asm volatile(
        "{\n"
        ".reg .pred p0, p1;\n"
        ".reg .b64 ta, ta0, tb, tb0;\n"
        "setp.ne.b32 p0, 0, 0;\n"
        "setp.eq.b32 p1, 0, 0;\n"
        "add.s64 tb0, %60, %61;\n"
        "add.s64 tb, tb0, 160;\n"
        "wgmma.mma_async.sync.aligned.m64n96k16.f32.bf16.bf16 {%0, %1, %2, %3, %4, %5, %6, %7, %8, %9, %10, %11, %12, %13, %14, %15, %16, %17, %18, %19, %20, %21, %22, %23, %24, %25, %26, %27, %28, %29, %30, %31, %32, %33, %34, %35, %36, %37, %38, %39, %40, %41, %42, %43, %44, %45, %46, %47}, {%48, %49, %50, %51}, tb, p1, 1, 1, 1;\n"
        "add.s64 tb, tb0, 192;\n"
        "wgmma.mma_async.sync.aligned.m64n96k16.f32.bf16.bf16 {%0, %1, %2, %3, %4, %5, %6, %7, %8, %9, %10, %11, %12, %13, %14, %15, %16, %17, %18, %19, %20, %21, %22, %23, %24, %25, %26, %27, %28, %29, %30, %31, %32, %33, %34, %35, %36, %37, %38, %39, %40, %41, %42, %43, %44, %45, %46, %47}, {%52, %53, %54, %55}, tb, p1, 1, 1, 1;\n"
        "add.s64 tb, tb0, 224;\n"
        "wgmma.mma_async.sync.aligned.m64n96k16.f32.bf16.bf16 {%0, %1, %2, %3, %4, %5, %6, %7, %8, %9, %10, %11, %12, %13, %14, %15, %16, %17, %18, %19, %20, %21, %22, %23, %24, %25, %26, %27, %28, %29, %30, %31, %32, %33, %34, %35, %36, %37, %38, %39, %40, %41, %42, %43, %44, %45, %46, %47}, {%56, %57, %58, %59}, tb, p1, 1, 1, 1;\n"
        "}\n"
        : "+f"(d[0]), "+f"(d[1]), "+f"(d[2]), "+f"(d[3]), "+f"(d[4]), "+f"(d[5]), "+f"(d[6]), "+f"(d[7]), "+f"(d[8]), "+f"(d[9]), "+f"(d[10]), "+f"(d[11]), "+f"(d[12]), "+f"(d[13]), "+f"(d[14]), "+f"(d[15]), "+f"(d[16]), "+f"(d[17]), "+f"(d[18]), "+f"(d[19]), "+f"(d[20]), "+f"(d[21]), "+f"(d[22]), "+f"(d[23]), "+f"(d[24]), "+f"(d[25]), "+f"(d[26]), "+f"(d[27]), "+f"(d[28]), "+f"(d[29]), "+f"(d[30]), "+f"(d[31]), "+f"(d[32]), "+f"(d[33]), "+f"(d[34]), "+f"(d[35]), "+f"(d[36]), "+f"(d[37]), "+f"(d[38]), "+f"(d[39]), "+f"(d[40]), "+f"(d[41]), "+f"(d[42]), "+f"(d[43]), "+f"(d[44]), "+f"(d[45]), "+f"(d[46]), "+f"(d[47])
        : "r"(a[AOFF + 0][0]), "r"(a[AOFF + 0][1]), "r"(a[AOFF + 0][2]), "r"(a[AOFF + 0][3]), "r"(a[AOFF + 1][0]), "r"(a[AOFF + 1][1]), "r"(a[AOFF + 1][2]), "r"(a[AOFF + 1][3]), "r"(a[AOFF + 2][0]), "r"(a[AOFF + 2][1]), "r"(a[AOFF + 2][2]), "r"(a[AOFF + 2][3]), "l"(descB), "n"(BOFF >> 4));
}
};
template <> struct Rng<0, 5, 9> {
template <int BOFF, int AOFF, int NA>
static __device__ __forceinline__ void run(float (&d)[48], const uint32_t (&a)[NA][4], uint64_t descB) {
    asm volatile(
        "{\n"
        ".reg .pred p0, p1;\n"
        ".reg .b64 ta, ta0, tb, tb0;\n"
        "setp.ne.b32 p0, 0, 0;\n"
        "setp.eq.b32 p1, 0, 0;\n"
        "add.s64 tb0, %64, %65;\n"
        "add.s64 tb, tb0, 1568;\n"
        "wgmma.mma_async.sync.aligned.m64n96k16.f32.bf16.bf16 {%0, %1, %2, %3, %4, %5, %6, %7, %8, %9, %10, %11, %12, %13, %14, %15, %16, %17, %18, %19, %20, %21, %22, %23, %24, %25, %26, %27, %28, %29, %30, %31, %32, %33, %34, %35, %36, %37, %38, %39, %40, %41, %42, %43, %44, %45, %46, %47}, {%48, %49, %50, %51}, tb, p1, 1, 1, 1;\n"
        "add.s64 tb, tb0, 1600;\n"
        "wgmma.mma_async.sync.aligned.m64n96k16.f32.bf16.bf16 {%0, %1, %2, %3, %4, %5, %6, %7, %8, %9, %10, %11, %12, %13, %14, %15, %16, %17, %18, %19, %20, %21, %22, %23, %24, %25, %26, %27, %28, %29, %30, %31, %32, %33, %34, %35, %36, %37, %38, %39, %40, %41, %42, %43, %44, %45, %46, %47}, {%52, %53, %54, %55}, tb, p1, 1, 1, 1;\n"
        "add.s64 tb, tb0, 1632;\n"
        "wgmma.mma_async.sync.aligned.m64n96k16.f32.bf16.bf16 {%0, %1, %2, %3, %4, %5, %6, %7, %8, %9, %10, %11, %12, %13, %14, %15, %16, %17, %18, %19, %20, %21, %22, %23, %24, %25, %26, %27, %28, %29, %30, %31, %32, %33, %34, %35, %36, %37, %38, %39, %40, %41, %42, %43, %44, %45, %46, %47}, {%56, %57, %58, %59}, tb, p1, 1, 1, 1;\n"
        "add.s64 tb, tb0, 3072;\n"
        "wgmma.mma_async.sync.aligned.m64n96k16.f32.bf16.bf16 {%0, %1, %2, %3, %4, %5, %6, %7, %8, %9, %10, %11, %12, %13, %14, %15, %16, %17, %18, %19, %20, %21, %22, %23, %24, %25, %26, %27, %28, %29, %30, %31, %32, %33, %34, %35, %36, %37, %38, %39, %40, %41, %42, %43, %44, %45, %46, %47}, {%60, %61, %62, %63}, tb, p1, 1, 1, 1;\n"
        "}\n"
        : "+f"(d[0]), "+f"(d[1]), "+f"(d[2]), "+f"(d[3]), "+f"(d[4]), "+f"(d[5]), "+f"(d[6]), "+f"(d[7]), "+f"(d[8]), "+f"(d[9]), "+f"(d[10]), "+f"(d[11]), "+f"(d[12]), "+f"(d[13]), "+f"(d[14]), "+f"(d[15]), "+f"(d[16]), "+f"(d[17]), "+f"(d[18]), "+f"(d[19]), "+f"(d[20]), "+f"(d[21]), "+f"(d[22]), "+f"(d[23]), "+f"(d[24]), "+f"(d[25]), "+f"(d[26]), "+f"(d[27]), "+f"(d[28]), "+f"(d[29]), "+f"(d[30]), "+f"(d[31]), "+f"(d[32]), "+f"(d[33]), "+f"(d[34]), "+f"(d[35]), "+f"(d[36]), "+f"(d[37]), "+f"(d[38]), "+f"(d[39]), "+f"(d[40]), "+f"(d[41]), "+f"(d[42]), "+f"(d[43]), "+f"(d[44]), "+f"(d[45]), "+f"(d[46]), "+f"(d[47])
        : "r"(a[AOFF + 0][0]), "r"(a[AOFF + 0][1]), "r"(a[AOFF + 0][2]), "r"(a[AOFF + 0][3]), "r"(a[AOFF + 1][0]), "r"(a[AOFF + 1][1]), "r"(a[AOFF + 1][2]), "r"(a[AOFF + 1][3]), "r"(a[AOFF + 2][0]), "r"(a[AOFF + 2][1]), "r"(a[AOFF + 2][2]), "r"(a[AOFF + 2][3]), "r"(a[AOFF + 3][0]), "r"(a[AOFF + 3][1]), "r"(a[AOFF + 3][2]), "r"(a[AOFF + 3][3]), "l"(descB), "n"(BOFF >> 4));
}
};
template <> struct Rng<1, 5, 9> {
template <int BOFF, int AOFF, int NA>
static __device__ __forceinline__ void run(float (&d)[48], const uint32_t (&a)[NA][4], uint64_t descB) {
    asm volatile(
        "{\n"
        ".reg .pred p0, p1;\n"
        ".reg .b64 ta, ta0, tb, tb0;\n"
        "setp.ne.b32 p0, 0, 0;\n"
        "setp.eq.b32 p1, 0, 0;\n"
        "add.s64 tb0, %64, %65;\n"
        "add.s64 tb, tb0, 160;\n"
        "wgmma.mma_async.sync.aligned.m64n96k16.f32.bf16.bf16 {%0, %1, %2, %3, %4, %5, %6, %7, %8, %9, %10, %11, %12, %13, %14, %15, %16, %17, %18, %19, %20, %21, %22, %23, %24, %25, %26, %27, %28, %29, %30, %31, %32, %33, %34, %35, %36, %37, %38, %39, %40, %41, %42, %43, %44, %45, %46, %47}, {%48, %49, %50, %51}, tb, p1, 1, 1, 1;\n"
        "add.s64 tb, tb0, 192;\n"
        "wgmma.mma_async.sync.aligned.m64n96k16.f32.bf16.bf16 {%0, %1, %2, %3, %4, %5, %6, %7, %8, %9, %10, %11, %12, %13, %14, %15, %16, %17, %18, %19, %20, %21, %22, %23, %24, %25, %26, %27, %28, %29, %30, %31, %32, %33, %34, %35, %36, %37, %38, %39, %40, %41, %42, %43, %44, %45, %46, %47}, {%52, %53, %54, %55}, tb, p1, 1, 1, 1;\n"
        "add.s64 tb, tb0, 224;\n"
        "wgmma.mma_async.sync.aligned.m64n96k16.f32.bf16.bf16 {%0, %1, %2, %3, %4, %5, %6, %7, %8, %9, %10, %11, %12, %13, %14, %15, %16, %17, %18, %19, %20, %21, %22, %23, %24, %25, %26, %27, %28, %29, %30, %31, %32, %33, %34, %35, %36, %37, %38, %39, %40, %41, %42, %43, %44, %45, %46, %47}, {%56, %57, %58, %59}, tb, p1, 1, 1, 1;\n"
        "add.s64 tb, tb0, 256;\n"
        "wgmma.mma_async.sync.aligned.m64n96k16.f32.bf16.bf16 {%0, %1, %2, %3, %4, %5, %6, %7, %8, %9, %10, %11, %12, %13, %14, %15, %16, %17, %18, %19, %20, %21, %22, %23, %24, %25, %26, %27, %28, %29, %30, %31, %32, %33, %34, %35, %36, %37, %38, %39, %40, %41, %42, %43, %44, %45, %46, %47}, {%60, %61, %62, %63}, tb, p1, 1, 1, 1;\n"
        "}\n"
        : "+f"(d[0]), "+f"(d[1]), "+f"(d[2]), "+f"(d[3]), "+f"(d[4]), "+f"(d[5]), "+f"(d[6]), "+f"(d[7]), "+f"(d[8]), "+f"(d[9]), "+f"(d[10]), "+f"(d[11]), "+f"(d[12]), "+f"(d[13]), "+f"(d[14]), "+f"(d[15]), "+f"(d[16]), "+f"(d[17]), "+f"(d[18]), "+f"(d[19]), "+f"(d[20]), "+f"(d[21]), "+f"(d[22]), "+f"(d[23]), "+f"(d[24]), "+f"(d[25]), "+f"(d[26]), "+f"(d[27]), "+f"(d[28]), "+f"(d[29]), "+f"(d[30]), "+f"(d[31]), "+f"(d[32]), "+f"(d[33]), "+f"(d[34]), "+f"(d[35]), "+f"(d[36]), "+f"(d[37]), "+f"(d[38]), "+f"(d[39]), "+f"(d[40]), "+f"(d[41]), "+f"(d[42]), "+f"(d[43]), "+f"(d[44]), "+f"(d[45]), "+f"(d[46]), "+f"(d[47])
        : "r"(a[AOFF + 0][0]), "r"(a[AOFF + 0][1]), "r"(a[AOFF + 0][2]), "r"(a[AOFF + 0][3]), "r"(a[AOFF + 1][0]), "r"(a[AOFF + 1][1]), "r"(a[AOFF + 1][2]), "r"(a[AOFF + 1][3]), "r"(a[AOFF + 2][0]), "r"(a[AOFF + 2][1]), "r"(a[AOFF + 2][2]), "r"(a[AOFF + 2][3]), "r"(a[AOFF + 3][0]), "r"(a[AOFF + 3][1]), "r"(a[AOFF + 3][2]), "r"(a[AOFF + 3][3]), "l"(descB), "n"(BOFF >> 4));
}
};
template <> struct Rng<0, 5, 10> {
template <int BOFF, int AOFF, int NA>
static __device__ __forceinline__ void run(float (&d)[48], const uint32_t (&a)[NA][4], uint64_t descB) {
    asm volatile(
        "{\n"
        ".reg .pred p0, p1;\n"
        ".reg .b64 ta, ta0, tb, tb0;\n"
        "setp.ne.b32 p0, 0, 0;\n"
        "setp.eq.b32 p1, 0, 0;\n"
        "add.s64 tb0, %68, %69;\n"
        "add.s64 tb, tb0, 1568;\n"
        "wgmma.mma_async.sync.aligned.m64n96k16.f32.bf16.bf16 {%0, %1, %2, %3, %4, %5, %6, %7, %8, %9, %10, %11, %12, %13, %14, %15, %16, %17, %18, %19, %20, %21, %22, %23, %24, %25, %26, %27, %28, %29, %30, %31, %32, %33, %34, %35, %36, %37, %38, %39, %40, %41, %42, %43, %44, %45, %46, %47}, {%48, %49, %50, %51}, tb, p1, 1, 1, 1;\n"
        "add.s64 tb, tb0, 1600;\n"
        "wgmma.mma_async.sync.aligned.m64n96k16.f32.bf16.bf16 {%0, %1, %2, %3, %4, %5, %6, %7, %8, %9, %10, %11, %12, %13, %14, %15, %16, %17, %18, %19, %20, %21, %22, %23, %24, %25, %26, %27, %28, %29, %30, %31, %32, %33, %34, %35, %36, %37, %38, %39, %40, %41, %42, %43, %44, %45, %46, %47}, {%52, %53, %54, %55}, tb, p1, 1, 1, 1;\n"
        "add.s64 tb, tb0, 1632;\n"
        "wgmma.mma_async.sync.aligned.m64n96k16.f32.bf16.bf16 {%0, %1, %2, %3, %4, %5, %6, %7, %8, %9, %10, %11, %12, %13, %14, %15, %16, %17, %18, %19, %20, %21, %22, %23, %24, %25, %26, %27, %28, %29, %30, %31, %32, %33, %34, %35, %36, %37, %38, %39, %40, %41, %42, %43, %44, %45, %46, %47}, {%56, %57, %58, %59}, tb, p1, 1, 1, 1;\n"
        "add.s64 tb, tb0, 3072;\n"
        "wgmma.mma_async.sync.aligned.m64n96k16.f32.bf16.bf16 {%0, %1, %2, %3, %4, %5, %6, %7, %8, %9, %10, %11, %12, %13, %14, %15, %16, %17, %18, %19, %20, %21, %22, %23, %24, %25, %26, %27, %28, %29, %30, %31, %32, %33, %34, %35, %36, %37, %38, %39, %40, %41, %42, %43, %44, %45, %46, %47}, {%60, %61, %62, %63}, tb, p1, 1, 1, 1;\n"
        "add.s64 tb, tb0, 3104;\n"
        "wgmma.mma_async.sync.aligned.m64n96k16.f32.bf16.bf16 {%0, %1, %2, %3, %4, %5, %6, %7, %8, %9, %10, %11, %12, %13, %14, %15, %16, %17, %18, %19, %20, %21, %22, %23, %24, %25, %26, %27, %28, %29, %30, %31, %32, %33, %34, %35, %36, %37, %38, %39, %40, %41, %42, %43, %44, %45, %46, %47}, {%64, %65, %66, %67}, tb, p1, 1, 1, 1;\n"
        "}\n"
        : "+f"(d[0]), "+f"(d[1]), "+f"(d[2]), "+f"(d[3]), "+f"(d[4]), "+f"(d[5]), "+f"(d[6]), "+f"(d[7]), "+f"(d[8]), "+f"(d[9]), "+f"(d[10]), "+f"(d[11]), "+f"(d[12]), "+f"(d[13]), "+f"(d[14]), "+f"(d[15]), "+f"(d[16]), "+f"(d[17]), "+f"(d[18]), "+f"(d[19]), "+f"(d[20]), "+f"(d[21]), "+f"(d[22]), "+f"(d[23]), "+f"(d[24]), "+f"(d[25]), "+f"(d[26]), "+f"(d[27]), "+f"(d[28]), "+f"(d[29]), "+f"(d[30]), "+f"(d[31]), "+f"(d[32]), "+f"(d[33]), "+f"(d[34]), "+f"(d[35]), "+f"(d[36]), "+f"(d[37]), "+f"(d[38]), "+f"(d[39]), "+f"(d[40]), "+f"(d[41]), "+f"(d[42]), "+f"(d[43]), "+f"(d[44]), "+f"(d[45]), "+f"(d[46]), "+f"(d[47])
        : "r"(a[AOFF + 0][0]), "r"(a[AOFF + 0][1]), "r"(a[AOFF + 0][2]), "r"(a[AOFF + 0][3]), "r"(a[AOFF + 1][0]), "r"(a[AOFF + 1][1]), "r"(a[AOFF + 1][2]), "r"(a[AOFF + 1][3]), "r"(a[AOFF + 2][0]), "r"(a[AOFF + 2][1]), "r"(a[AOFF + 2][2]), "r"(a[AOFF + 2][3]), "r"(a[AOFF + 3][0]), "r"(a[AOFF + 3][1]), "r"(a[AOFF + 3][2]), "r"(a[AOFF + 3][3]), "r"(a[AOFF + 4][0]), "r"(a[AOFF + 4][1]), "r"(a[AOFF + 4][2]), "r"(a[AOFF + 4][3]), "l"(descB), "n"(BOFF >> 4));
}
};
template <> struct Rng<1, 5, 10> {
template <int BOFF, int AOFF, int NA>
static __device__ __forceinline__ void run(float (&d)[48], const uint32_t (&a)[NA][4], uint64_t descB) {
    asm volatile(
        "{\n"
        ".reg .pred p0, p1;\n"
        ".reg .b64 ta, ta0, tb, tb0;\n"
        "setp.ne.b32 p0, 0, 0;\n"
        "setp.eq.b32 p1, 0, 0;\n"
        "add.s64 tb0, %68, %69;\n"
        "add.s64 tb, tb0, 160;\n"
        "wgmma.mma_async.sync.aligned.m64n96k16.f32.bf16.bf16 {%0, %1, %2, %3, %4, %5, %6, %7, %8, %9, %10, %11, %12, %13, %14, %15, %16, %17, %18, %19, %20, %21, %22, %23, %24, %25, %26, %27, %28, %29, %30, %31, %32, %33, %34, %35, %36, %37, %38, %39, %40, %41, %42, %43, %44, %45, %46, %47}, {%48, %49, %50, %51}, tb, p1, 1, 1, 1;\n"
        "add.s64 tb, tb0, 192;\n"
        "wgmma.mma_async.sync.aligned.m64n96k16.f32.bf16.bf16 {%0, %1, %2, %3, %4, %5, %6, %7, %8, %9, %10, %11, %12, %13, %14, %15, %16, %17, %18, %19, %20, %21, %22, %23, %24, %25, %26, %27, %28, %29, %30, %31, %32, %33, %34, %35, %36, %37, %38, %39, %40, %41, %42, %43, %44, %45, %46, %47}, {%52, %53, %54, %55}, tb, p1, 1, 1, 1;\n"
        "add.s64 tb, tb0, 224;\n"
        "wgmma.mma_async.sync.aligned.m64n96k16.f32.bf16.bf16 {%0, %1, %2, %3, %4, %5, %6, %7, %8, %9, %10, %11, %12, %13, %14, %15, %16, %17, %18, %19, %20, %21, %22, %23, %24, %25, %26, %27, %28, %29, %30, %31, %32, %33, %34, %35, %36, %37, %38, %39, %40, %41, %42, %43, %44, %45, %46, %47}, {%56, %57, %58, %59}, tb, p1, 1, 1, 1;\n"
        "add.s64 tb, tb0, 256;\n"
        "wgmma.mma_async.sync.aligned.m64n96k16.f32.bf16.bf16 {%0, %1, %2, %3, %4, %5, %6, %7, %8, %9, %10, %11, %12, %13, %14, %15, %16, %17, %18, %19, %20, %21, %22, %23, %24, %25, %26, %27, %28, %29, %30, %31, %32, %33, %34, %35, %36, %37, %38, %39, %40, %41, %42, %43, %44, %45, %46, %47}, {%60, %61, %62, %63}, tb, p1, 1, 1, 1;\n"
        "add.s64 tb, tb0, 288;\n"
        "wgmma.mma_async.sync.aligned.m64n96k16.f32.bf16.bf16 {%0, %1, %2, %3, %4, %5, %6, %7, %8, %9, %10, %11, %12, %13, %14, %15, %16, %17, %18, %19, %20, %21, %22, %23, %24, %25, %26, %27, %28, %29, %30, %31, %32, %33, %34, %35, %36, %37, %38, %39, %40, %41, %42, %43, %44, %45, %46, %47}, {%64, %65, %66, %67}, tb, p1, 1, 1, 1;\n"
        "}\n"
        : "+f"(d[0]), "+f"(d[1]), "+f"(d[2]), "+f"(d[3]), "+f"(d[4]), "+f"(d[5]), "+f"(d[6]), "+f"(d[7]), "+f"(d[8]), "+f"(d[9]), "+f"(d[10]), "+f"(d[11]), "+f"(d[12]), "+f"(d[13]), "+f"(d[14]), "+f"(d[15]), "+f"(d[16]), "+f"(d[17]), "+f"(d[18]), "+f"(d[19]), "+f"(d[20]), "+f"(d[21]), "+f"(d[22]), "+f"(d[23]), "+f"(d[24]), "+f"(d[25]), "+f"(d[26]), "+f"(d[27]), "+f"(d[28]), "+f"(d[29]), "+f"(d[30]), "+f"(d[31]), "+f"(d[32]), "+f"(d[33]), "+f"(d[34]), "+f"(d[35]), "+f"(d[36]), "+f"(d[37]), "+f"(d[38]), "+f"(d[39]), "+f"(d[40]), "+f"(d[41]), "+f"(d[42]), "+f"(d[43]), "+f"(d[44]), "+f"(d[45]), "+f"(d[46]), "+f"(d[47])
        : "r"(a[AOFF + 0][0]), "r"(a[AOFF + 0][1]), "r"(a[AOFF + 0][2]), "r"(a[AOFF + 0][3]), "r"(a[AOFF + 1][0]), "r"(a[AOFF + 1][1]), "r"(a[AOFF + 1][2]), "r"(a[AOFF + 1][3]), "r"(a[AOFF + 2][0]), "r"(a[AOFF + 2][1]), "r"(a[AOFF + 2][2]), "r"(a[AOFF + 2][3]), "r"(a[AOFF + 3][0]), "r"(a[AOFF + 3][1]), "r"(a[AOFF + 3][2]), "r"(a[AOFF + 3][3]), "r"(a[AOFF + 4][0]), "r"(a[AOFF + 4][1]), "r"(a[AOFF + 4][2]), "r"(a[AOFF + 4][3]), "l"(descB), "n"(BOFF >> 4));
}
};
template <> struct Rng<0, 5, 12> {
template <int BOFF, int AOFF, int NA>
static __device__ __forceinline__ void run(float (&d)[48], const uint32_t (&a)[NA][4], uint64_t descB) {
    asm volatile(
        "{\n"
        ".reg .pred p0, p1;\n"
        ".reg .b64 ta, ta0, tb, tb0;\n"
        "setp.ne.b32 p0, 0, 0;\n"
        "setp.eq.b32 p1, 0, 0;\n"
        "add.s64 tb0, %76, %77;\n"
        "add.s64 tb, tb0, 1568;\n"
        "wgmma.mma_async.sync.aligned.m64n96k16.f32.bf16.bf16 {%0, %1, %2, %3, %4, %5, %6, %7, %8, %9, %10, %11, %12, %13, %14, %15, %16, %17, %18, %19, %20, %21, %22, %23, %24, %25, %26, %27, %28, %29, %30, %31, %32, %33, %34, %35, %36, %37, %38, %39, %40, %41, %42, %43, %44, %45, %46, %47}, {%48, %49, %50, %51}, tb, p1, 1, 1, 1;\n"
        "add.s64 tb, tb0, 1600;\n"
        "wgmma.mma_async.sync.aligned.m64n96k16.f32.bf16.bf16 {%0, %1, %2, %3, %4, %5, %6, %7, %8, %9, %10, %11, %12, %13, %14, %15, %16, %17, %18, %19, %20, %21, %22, %23, %24, %25, %26, %27, %28, %29, %30, %31, %32, %33, %34, %35, %36, %37, %38, %39, %40, %41, %42, %43, %44, %45, %46, %47}, {%52, %53, %54, %55}, tb, p1, 1, 1, 1;\n"
        "add.s64 tb, tb0, 1632;\n"
        "wgmma.mma_async.sync.aligned.m64n96k16.f32.bf16.bf16 {%0, %1, %2, %3, %4, %5, %6, %7, %8, %9, %10, %11, %12, %13, %14, %15, %16, %17, %18, %19, %20, %21, %22, %23, %24, %25, %26, %27, %28, %29, %30, %31, %32, %33, %34, %35, %36, %37, %38, %39, %40, %41, %42, %43, %44, %45, %46, %47}, {%56, %57, %58, %59}, tb, p1, 1, 1, 1;\n"
        "add.s64 tb, tb0, 3072;\n"
        "wgmma.mma_async.sync.aligned.m64n96k16.f32.bf16.bf16 {%0, %1, %2, %3, %4, %5, %6, %7, %8, %9, %10, %11, %12, %13, %14, %15, %16, %17, %18, %19, %20, %21, %22, %23, %24, %25, %26, %27, %28, %29, %30, %31, %32, %33, %34, %35, %36, %37, %38, %39, %40, %41, %42, %43, %44, %45, %46, %47}, {%60, %61, %62, %63}, tb, p1, 1, 1, 1;\n"
        "add.s64 tb, tb0, 3104;\n"
        "wgmma.mma_async.sync.aligned.m64n96k16.f32.bf16.bf16 {%0, %1, %2, %3, %4, %5, %6, %7, %8, %9, %10, %11, %12, %13, %14, %15, %16, %17, %18, %19, %20, %21, %22, %23, %24, %25, %26, %27, %28, %29, %30, %31, %32, %33, %34, %35, %36, %37, %38, %39, %40, %41, %42, %43, %44, %45, %46, %47}, {%64, %65, %66, %67}, tb, p1, 1, 1, 1;\n"
        "add.s64 tb, tb0, 3136;\n"
        "wgmma.mma_async.sync.aligned.m64n96k16.f32.bf16.bf16 {%0, %1, %2, %3, %4, %5, %6, %7, %8, %9, %10, %11, %12, %13, %14, %15, %16, %17, %18, %19, %20, %21, %22, %23, %24, %25, %26, %27, %28, %29, %30, %31, %32, %33, %34, %35, %36, %37, %38, %39, %40, %41, %42, %43, %44, %45, %46, %47}, {%68, %69, %70, %71}, tb, p1, 1, 1, 1;\n"
        "add.s64 tb, tb0, 3168;\n"
        "wgmma.mma_async.sync.aligned.m64n96k16.f32.bf16.bf16 {%0, %1, %2, %3, %4, %5, %6, %7, %8, %9, %10, %11, %12, %13, %14, %15, %16, %17, %18, %19, %20, %21, %22, %23, %24, %25, %26, %27, %28, %29, %30, %31, %32, %33, %34, %35, %36, %37, %38, %39, %40, %41, %42, %43, %44, %45, %46, %47}, {%72, %73, %74, %75}, tb, p1, 1, 1, 1;\n"
        "}\n"
        : "+f"(d[0]), "+f"(d[1]), "+f"(d[2]), "+f"(d[3]), "+f"(d[4]), "+f"(d[5]), "+f"(d[6]), "+f"(d[7]), "+f"(d[8]), "+f"(d[9]), "+f"(d[10]), "+f"(d[11]), "+f"(d[12]), "+f"(d[13]), "+f"(d[14]), "+f"(d[15]), "+f"(d[16]), "+f"(d[17]), "+f"(d[18]), "+f"(d[19]), "+f"(d[20]), "+f"(d[21]), "+f"(d[22]), "+f"(d[23]), "+f"(d[24]), "+f"(d[25]), "+f"(d[26]), "+f"(d[27]), "+f"(d[28]), "+f"(d[29]), "+f"(d[30]), "+f"(d[31]), "+f"(d[32]), "+f"(d[33]), "+f"(d[34]), "+f"(d[35]), "+f"(d[36]), "+f"(d[37]), "+f"(d[38]), "+f"(d[39]), "+f"(d[40]), "+f"(d[41]), "+f"(d[42]), "+f"(d[43]), "+f"(d[44]), "+f"(d[45]), "+f"(d[46]), "+f"(d[47])
        : "r"(a[AOFF + 0][0]), "r"(a[AOFF + 0][1]), "r"(a[AOFF + 0][2]), "r"(a[AOFF + 0][3]), "r"(a[AOFF + 1][0]), "r"(a[AOFF + 1][1]), "r"(a[AOFF + 1][2]), "r"(a[AOFF + 1][3]), "r"(a[AOFF + 2][0]), "r"(a[AOFF + 2][1]), "r"(a[AOFF + 2][2]), "r"(a[AOFF + 2][3]), "r"(a[AOFF + 3][0]), "r"(a[AOFF + 3][1]), "r"(a[AOFF + 3][2]), "r"(a[AOFF + 3][3]), "r"(a[AOFF + 4][0]), "r"(a[AOFF + 4][1]), "r"(a[AOFF + 4][2]), "r"(a[AOFF + 4][3]), "r"(a[AOFF + 5][0]), "r"(a[AOFF + 5][1]), "r"(a[AOFF + 5][2]), "r"(a[AOFF + 5][3]), "r"(a[AOFF + 6][0]), "r"(a[AOFF + 6][1]), "r"(a[AOFF + 6][2]), "r"(a[AOFF + 6][3]), "l"(descB), "n"(BOFF >> 4));
}
};
template <> struct Rng<1, 5, 12> {
template <int BOFF, int AOFF, int NA>
static __device__ __forceinline__ void run(float (&d)[48], const uint32_t (&a)[NA][4], uint64_t descB) {
    asm volatile(
        "{\n"
        ".reg .pred p0, p1;\n"
        ".reg .b64 ta, ta0, tb, tb0;\n"
        "setp.ne.b32 p0, 0, 0;\n"
        "setp.eq.b32 p1, 0, 0;\n"
        "add.s64 tb0, %76, %77;\n"
        "add.s64 tb, tb0, 160;\n"
        "wgmma.mma_async.sync.aligned.m64n96k16.f32.bf16.bf16 {%0, %1, %2, %3, %4, %5, %6, %7, %8, %9, %10, %11, %12, %13, %14, %15, %16, %17, %18, %19, %20, %21, %22, %23, %24, %25, %26, %27, %28, %29, %30, %31, %32, %33, %34, %35, %36, %37, %38, %39, %40, %41, %42, %43, %44, %45, %46, %47}, {%48, %49, %50, %51}, tb, p1, 1, 1, 1;\n"
        "add.s64 tb, tb0, 192;\n"
        "wgmma.mma_async.sync.aligned.m64n96k16.f32.bf16.bf16 {%0, %1, %2, %3, %4, %5, %6, %7, %8, %9, %10, %11, %12, %13, %14, %15, %16, %17, %18, %19, %20, %21, %22, %23, %24, %25, %26, %27, %28, %29, %30, %31, %32, %33, %34, %35, %36, %37, %38, %39, %40, %41, %42, %43, %44, %45, %46, %47}, {%52, %53, %54, %55}, tb, p1, 1, 1, 1;\n"
        "add.s64 tb, tb0, 224;\n"
        "wgmma.mma_async.sync.aligned.m64n96k16.f32.bf16.bf16 {%0, %1, %2, %3, %4, %5, %6, %7, %8, %9, %10, %11, %12, %13, %14, %15, %16, %17, %18, %19, %20, %21, %22, %23, %24, %25, %26, %27, %28, %29, %30, %31, %32, %33, %34, %35, %36, %37, %38, %39, %40, %41, %42, %43, %44, %45, %46, %47}, {%56, %57, %58, %59}, tb, p1, 1, 1, 1;\n"
        "add.s64 tb, tb0, 256;\n"
        "wgmma.mma_async.sync.aligned.m64n96k16.f32.bf16.bf16 {%0, %1, %2, %3, %4, %5, %6, %7, %8, %9, %10, %11, %12, %13, %14, %15, %16, %17, %18, %19, %20, %21, %22, %23, %24, %25, %26, %27, %28, %29, %30, %31, %32, %33, %34, %35, %36, %37, %38, %39, %40, %41, %42, %43, %44, %45, %46, %47}, {%60, %61, %62, %63}, tb, p1, 1, 1, 1;\n"
        "add.s64 tb, tb0, 288;\n"
        "wgmma.mma_async.sync.aligned.m64n96k16.f32.bf16.bf16 {%0, %1, %2, %3, %4, %5, %6, %7, %8, %9, %10, %11, %12, %13, %14, %15, %16, %17, %18, %19, %20, %21, %22, %23, %24, %25, %26, %27, %28, %29, %30, %31, %32, %33, %34, %35, %36, %37, %38, %39, %40, %41, %42, %43, %44, %45, %46, %47}, {%64, %65, %66, %67}, tb, p1, 1, 1, 1;\n"
        "add.s64 tb, tb0, 320;\n"
        "wgmma.mma_async.sync.aligned.m64n96k16.f32.bf16.bf16 {%0, %1, %2, %3, %4, %5, %6, %7, %8, %9, %10, %11, %12, %13, %14, %15, %16, %17, %18, %19, %20, %21, %22, %23, %24, %25, %26, %27, %28, %29, %30, %31, %32, %33, %34, %35, %36, %37, %38, %39, %40, %41, %42, %43, %44, %45, %46, %47}, {%68, %69, %70, %71}, tb, p1, 1, 1, 1;\n"
        "add.s64 tb, tb0, 352;\n"
        "wgmma.mma_async.sync.aligned.m64n96k16.f32.bf16.bf16 {%0, %1, %2, %3, %4, %5, %6, %7, %8, %9, %10, %11, %12, %13, %14, %15, %16, %17, %18, %19, %20, %21, %22, %23, %24, %25, %26, %27, %28, %29, %30, %31, %32, %33, %34, %35, %36, %37, %38, %39, %40, %41, %42, %43, %44, %45, %46, %47}, {%72, %73, %74, %75}, tb, p1, 1, 1, 1;\n"
        "}\n"
        : "+f"(d[0]), "+f"(d[1]), "+f"(d[2]), "+f"(d[3]), "+f"(d[4]), "+f"(d[5]), "+f"(d[6]), "+f"(d[7]), "+f"(d[8]), "+f"(d[9]), "+f"(d[10]), "+f"(d[11]), "+f"(d[12]), "+f"(d[13]), "+f"(d[14]), "+f"(d[15]), "+f"(d[16]), "+f"(d[17]), "+f"(d[18]), "+f"(d[19]), "+f"(d[20]), "+f"(d[21]), "+f"(d[22]), "+f"(d[23]), "+f"(d[24]), "+f"(d[25]), "+f"(d[26]), "+f"(d[27]), "+f"(d[28]), "+f"(d[29]), "+f"(d[30]), "+f"(d[31]), "+f"(d[32]), "+f"(d[33]), "+f"(d[34]), "+f"(d[35]), "+f"(d[36]), "+f"(d[37]), "+f"(d[38]), "+f"(d[39]), "+f"(d[40]), "+f"(d[41]), "+f"(d[42]), "+f"(d[43]), "+f"(d[44]), "+f"(d[45]), "+f"(d[46]), "+f"(d[47])
        : "r"(a[AOFF + 0][0]), "r"(a[AOFF + 0][1]), "r"(a[AOFF + 0][2]), "r"(a[AOFF + 0][3]), "r"(a[AOFF + 1][0]), "r"(a[AOFF + 1][1]), "r"(a[AOFF + 1][2]), "r"(a[AOFF + 1][3]), "r"(a[AOFF + 2][0]), "r"(a[AOFF + 2][1]), "r"(a[AOFF + 2][2]), "r"(a[AOFF + 2][3]), "r"(a[AOFF + 3][0]), "r"(a[AOFF + 3][1]), "r"(a[AOFF + 3][2]), "r"(a[AOFF + 3][3]), "r"(a[AOFF + 4][0]), "r"(a[AOFF + 4][1]), "r"(a[AOFF + 4][2]), "r"(a[AOFF + 4][3]), "r"(a[AOFF + 5][0]), "r"(a[AOFF + 5][1]), "r"(a[AOFF + 5][2]), "r"(a[AOFF + 5][3]), "r"(a[AOFF + 6][0]), "r"(a[AOFF + 6][1]), "r"(a[AOFF + 6][2]), "r"(a[AOFF + 6][3]), "l"(descB), "n"(BOFF >> 4));
}
};
template <> struct Rng<0, 6, 9> {
template <int BOFF, int AOFF, int NA>
static __device__ __forceinline__ void run(float (&d)[48], const uint32_t (&a)[NA][4], uint64_t descB) {
    asm volatile(
        "{\n"
        ".reg .pred p0, p1;\n"
        ".reg .b64 ta, ta0, tb, tb0;\n"
        "setp.ne.b32 p0, 0, 0;\n"
        "setp.eq.b32 p1, 0, 0;\n"
        "add.s64 tb0, %60, %61;\n"
        "add.s64 tb, tb0, 1600;\n"
        "wgmma.mma_async.sync.aligned.m64n96k16.f32.bf16.bf16 {%0, %1, %2, %3, %4, %5, %6, %7, %8, %9, %10, %11, %12, %13, %14, %15, %16, %17, %18, %19, %20, %21, %22, %23, %24, %25, %26, %27, %28, %29, %30, %31, %32, %33, %34, %35, %36, %37, %38, %39, %40, %41, %42, %43, %44, %45, %46, %47}, {%48, %49, %50, %51}, tb, p1, 1, 1, 1;\n"
        "add.s64 tb, tb0, 1632;\n"
        "wgmma.mma_async.sync.aligned.m64n96k16.f32.bf16.bf16 {%0, %1, %2, %3, %4, %5, %6, %7, %8, %9, %10, %11, %12, %13, %14, %15, %16, %17, %18, %19, %20, %21, %22, %23, %24, %25, %26, %27, %28, %29, %30, %31, %32, %33, %34, %35, %36, %37, %38, %39, %40, %41, %42, %43, %44, %45, %46, %47}, {%52, %53, %54, %55}, tb, p1, 1, 1, 1;\n"
        "add.s64 tb, tb0, 3072;\n"
        "wgmma.mma_async.sync.aligned.m64n96k16.f32.bf16.bf16 {%0, %1, %2, %3, %4, %5, %6, %7, %8, %9, %10, %11, %12, %13, %14, %15, %16, %17, %18, %19, %20, %21, %22, %23, %24, %25, %26, %27, %28, %29, %30, %31, %32, %33, %34, %35, %36, %37, %38, %39, %40, %41, %42, %43, %44, %45, %46, %47}, {%56, %57, %58, %59}, tb, p1, 1, 1, 1;\n"
        "}\n"
        : "+f"(d[0]), "+f"(d[1]), "+f"(d[2]), "+f"(d[3]), "+f"(d[4]), "+f"(d[5]), "+f"(d[6]), "+f"(d[7]), "+f"(d[8]), "+f"(d[9]), "+f"(d[10]), "+f"(d[11]), "+f"(d[12]), "+f"(d[13]), "+f"(d[14]), "+f"(d[15]), "+f"(d[16]), "+f"(d[17]), "+f"(d[18]), "+f"(d[19]), "+f"(d[20]), "+f"(d[21]), "+f"(d[22]), "+f"(d[23]), "+f"(d[24]), "+f"(d[25]), "+f"(d[26]), "+f"(d[27]), "+f"(d[28]), "+f"(d[29]), "+f"(d[30]), "+f"(d[31]), "+f"(d[32]), "+f"(d[33]), "+f"(d[34]), "+f"(d[35]), "+f"(d[36]), "+f"(d[37]), "+f"(d[38]), "+f"(d[39]), "+f"(d[40]), "+f"(d[41]), "+f"(d[42]), "+f"(d[43]), "+f"(d[44]), "+f"(d[45]), "+f"(d[46]), "+f"(d[47])
        : "r"(a[AOFF + 0][0]), "r"(a[AOFF + 0][1]), "r"(a[AOFF + 0][2]), "r"(a[AOFF + 0][3]), "r"(a[AOFF + 1][0]), "r"(a[AOFF + 1][1]), "r"(a[AOFF + 1][2]), "r"(a[AOFF + 1][3]), "r"(a[AOFF + 2][0]), "r"(a[AOFF + 2][1]), "r"(a[AOFF + 2][2]), "r"(a[AOFF + 2][3]), "l"(descB), "n"(BOFF >> 4));
}
};
template <> struct Rng<1, 6, 9> {
template <int BOFF, int AOFF, int NA>
static __device__ __forceinline__ void run(float (&d)[48], const uint32_t (&a)[NA][4], uint64_t descB) {
    asm volatile(
        "{\n"
        ".reg .pred p0, p1;\n"
        ".reg .b64 ta, ta0, tb, tb0;\n"
        "setp.ne.b32 p0, 0, 0;\n"
        "setp.eq.b32 p1, 0, 0;\n"
        "add.s64 tb0, %60, %61;\n"
        "add.s64 tb, tb0, 192;\n"
        "wgmma.mma_async.sync.aligned.m64n96k16.f32.bf16.bf16 {%0, %1, %2, %3, %4, %5, %6, %7, %8, %9, %10, %11, %12, %13, %14, %15, %16, %17, %18, %19, %20, %21, %22, %23, %24, %25, %26, %27, %28, %29, %30, %31, %32, %33, %34, %35, %36, %37, %38, %39, %40, %41, %42, %43, %44, %45, %46, %47}, {%48, %49, %50, %51}, tb, p1, 1, 1, 1;\n"
        "add.s64 tb, tb0, 224;\n"
        "wgmma.mma_async.sync.aligned.m64n96k16.f32.bf16.bf16 {%0, %1, %2, %3, %4, %5, %6, %7, %8, %9, %10, %11, %12, %13, %14, %15, %16, %17, %18, %19, %20, %21, %22, %23, %24, %25, %26, %27, %28, %29, %30, %31, %32, %33, %34, %35, %36, %37, %38, %39, %40, %41, %42, %43, %44, %45, %46, %47}, {%52, %53, %54, %55}, tb, p1, 1, 1, 1;\n"
        "add.s64 tb, tb0, 256;\n"
        "wgmma.mma_async.sync.aligned.m64n96k16.f32.bf16.bf16 {%0, %1, %2, %3, %4, %5, %6, %7, %8, %9, %10, %11, %12, %13, %14, %15, %16, %17, %18, %19, %20, %21, %22, %23, %24, %25, %26, %27, %28, %29, %30, %31, %32, %33, %34, %35, %36, %37, %38, %39, %40, %41, %42, %43, %44, %45, %46, %47}, {%56, %57, %58, %59}, tb, p1, 1, 1, 1;\n"
        "}\n"
        : "+f"(d[0]), "+f"(d[1]), "+f"(d[2]), "+f"(d[3]), "+f"(d[4]), "+f"(d[5]), "+f"(d[6]), "+f"(d[7]), "+f"(d[8]), "+f"(d[9]), "+f"(d[10]), "+f"(d[11]), "+f"(d[12]), "+f"(d[13]), "+f"(d[14]), "+f"(d[15]), "+f"(d[16]), "+f"(d[17]), "+f"(d[18]), "+f"(d[19]), "+f"(d[20]), "+f"(d[21]), "+f"(d[22]), "+f"(d[23]), "+f"(d[24]), "+f"(d[25]), "+f"(d[26]), "+f"(d[27]), "+f"(d[28]), "+f"(d[29]), "+f"(d[30]), "+f"(d[31]), "+f"(d[32]), "+f"(d[33]), "+f"(d[34]), "+f"(d[35]), "+f"(d[36]), "+f"(d[37]), "+f"(d[38]), "+f"(d[39]), "+f"(d[40]), "+f"(d[41]), "+f"(d[42]), "+f"(d[43]), "+f"(d[44]), "+f"(d[45]), "+f"(d[46]), "+f"(d[47])
        : "r"(a[AOFF + 0][0]), "r"(a[AOFF + 0][1]), "r"(a[AOFF + 0][2]), "r"(a[AOFF + 0][3]), "r"(a[AOFF + 1][0]), "r"(a[AOFF + 1][1]), "r"(a[AOFF + 1][2]), "r"(a[AOFF + 1][3]), "r"(a[AOFF + 2][0]), "r"(a[AOFF + 2][1]), "r"(a[AOFF + 2][2]), "r"(a[AOFF + 2][3]), "l"(descB), "n"(BOFF >> 4));
}
};
template <> struct Rng<0, 6, 10> {
template <int BOFF, int AOFF, int NA>
static __device__ __forceinline__ void run(float (&d)[48], const uint32_t (&a)[NA][4], uint64_t descB) {
    asm volatile(
        "{\n"
        ".reg .pred p0, p1;\n"
        ".reg .b64 ta, ta0, tb, tb0;\n"
        "setp.ne.b32 p0, 0, 0;\n"
        "setp.eq.b32 p1, 0, 0;\n"
        "add.s64 tb0, %64, %65;\n"
        "add.s64 tb, tb0, 1600;\n"
        "wgmma.mma_async.sync.aligned.m64n96k16.f32.bf16.bf16 {%0, %1, %2, %3, %4, %5, %6, %7, %8, %9, %10, %11, %12, %13, %14, %15, %16, %17, %18, %19, %20, %21, %22, %23, %24, %25, %26, %27, %28, %29, %30, %31, %32, %33, %34, %35, %36, %37, %38, %39, %40, %41, %42, %43, %44, %45, %46, %47}, {%48, %49, %50, %51}, tb, p1, 1, 1, 1;\n"
        "add.s64 tb, tb0, 1632;\n"
        "wgmma.mma_async.sync.aligned.m64n96k16.f32.bf16.bf16 {%0, %1, %2, %3, %4, %5, %6, %7, %8, %9, %10, %11, %12, %13, %14, %15, %16, %17, %18, %19, %20, %21, %22, %23, %24, %25, %26, %27, %28, %29, %30, %31, %32, %33, %34, %35, %36, %37, %38, %39, %40, %41, %42, %43, %44, %45, %46, %47}, {%52, %53, %54, %55}, tb, p1, 1, 1, 1;\n"
        "add.s64 tb, tb0, 3072;\n"
        "wgmma.mma_async.sync.aligned.m64n96k16.f32.bf16.bf16 {%0, %1, %2, %3, %4, %5, %6, %7, %8, %9, %10, %11, %12, %13, %14, %15, %16, %17, %18, %19, %20, %21, %22, %23, %24, %25, %26, %27, %28, %29, %30, %31, %32, %33, %34, %35, %36, %37, %38, %39, %40, %41, %42, %43, %44, %45, %46, %47}, {%56, %57, %58, %59}, tb, p1, 1, 1, 1;\n"
        "add.s64 tb, tb0, 3104;\n"
        "wgmma.mma_async.sync.aligned.m64n96k16.f32.bf16.bf16 {%0, %1, %2, %3, %4, %5, %6, %7, %8, %9, %10, %11, %12, %13, %14, %15, %16, %17, %18, %19, %20, %21, %22, %23, %24, %25, %26, %27, %28, %29, %30, %31, %32, %33, %34, %35, %36, %37, %38, %39, %40, %41, %42, %43, %44, %45, %46, %47}, {%60, %61, %62, %63}, tb, p1, 1, 1, 1;\n"
        "}\n"
        : "+f"(d[0]), "+f"(d[1]), "+f"(d[2]), "+f"(d[3]), "+f"(d[4]), "+f"(d[5]), "+f"(d[6]), "+f"(d[7]), "+f"(d[8]), "+f"(d[9]), "+f"(d[10]), "+f"(d[11]), "+f"(d[12]), "+f"(d[13]), "+f"(d[14]), "+f"(d[15]), "+f"(d[16]), "+f"(d[17]), "+f"(d[18]), "+f"(d[19]), "+f"(d[20]), "+f"(d[21]), "+f"(d[22]), "+f"(d[23]), "+f"(d[24]), "+f"(d[25]), "+f"(d[26]), "+f"(d[27]), "+f"(d[28]), "+f"(d[29]), "+f"(d[30]), "+f"(d[31]), "+f"(d[32]), "+f"(d[33]), "+f"(d[34]), "+f"(d[35]), "+f"(d[36]), "+f"(d[37]), "+f"(d[38]), "+f"(d[39]), "+f"(d[40]), "+f"(d[41]), "+f"(d[42]), "+f"(d[43]), "+f"(d[44]), "+f"(d[45]), "+f"(d[46]), "+f"(d[47])
        : "r"(a[AOFF + 0][0]), "r"(a[AOFF + 0][1]), "r"(a[AOFF + 0][2]), "r"(a[AOFF + 0][3]), "r"(a[AOFF + 1][0]), "r"(a[AOFF + 1][1]), "r"(a[AOFF + 1][2]), "r"(a[AOFF + 1][3]), "r"(a[AOFF + 2][0]), "r"(a[AOFF + 2][1]), "r"(a[AOFF + 2][2]), "r"(a[AOFF + 2][3]), "r"(a[AOFF + 3][0]), "r"(a[AOFF + 3][1]), "r"(a[AOFF + 3][2]), "r"(a[AOFF + 3][3]), "l"(descB), "n"(BOFF >> 4));
}
};
template <> struct Rng<1, 6, 10> {
template <int BOFF, int AOFF, int NA>
static __device__ __forceinline__ void run(float (&d)[48], const uint32_t (&a)[NA][4], uint64_t descB) {
    asm volatile(
        "{\n"
        ".reg .pred p0, p1;\n"
        ".reg .b64 ta, ta0, tb, tb0;\n"
        "setp.ne.b32 p0, 0, 0;\n"
        "setp.eq.b32 p1, 0, 0;\n"
        "add.s64 tb0, %64, %65;\n"
        "add.s64 tb, tb0, 192;\n"
        "wgmma.mma_async.sync.aligned.m64n96k16.f32.bf16.bf16 {%0, %1, %2, %3, %4, %5, %6, %7, %8, %9, %10, %11, %12, %13, %14, %15, %16, %17, %18, %19, %20, %21, %22, %23, %24, %25, %26, %27, %28, %29, %30, %31, %32, %33, %34, %35, %36, %37, %38, %39, %40, %41, %42, %43, %44, %45, %46, %47}, {%48, %49, %50, %51}, tb, p1, 1, 1, 1;\n"
        "add.s64 tb, tb0, 224;\n"
        "wgmma.mma_async.sync.aligned.m64n96k16.f32.bf16.bf16 {%0, %1, %2, %3, %4, %5, %6, %7, %8, %9, %10, %11, %12, %13, %14, %15, %16, %17, %18, %19, %20, %21, %22, %23, %24, %25, %26, %27, %28, %29, %30, %31, %32, %33, %34, %35, %36, %37, %38, %39, %40, %41, %42, %43, %44, %45, %46, %47}, {%52, %53, %54, %55}, tb, p1, 1, 1, 1;\n"
        "add.s64 tb, tb0, 256;\n"
        "wgmma.mma_async.sync.aligned.m64n96k16.f32.bf16.bf16 {%0, %1, %2, %3, %4, %5, %6, %7, %8, %9, %10, %11, %12, %13, %14, %15, %16, %17, %18, %19, %20, %21, %22, %23, %24, %25, %26, %27, %28, %29, %30, %31, %32, %33, %34, %35, %36, %37, %38, %39, %40, %41, %42, %43, %44, %45, %46, %47}, {%56, %57, %58, %59}, tb, p1, 1, 1, 1;\n"
        "add.s64 tb, tb0, 288;\n"
        "wgmma.mma_async.sync.aligned.m64n96k16.f32.bf16.bf16 {%0, %1, %2, %3, %4, %5, %6, %7, %8, %9, %10, %11, %12, %13, %14, %15, %16, %17, %18, %19, %20, %21, %22, %23, %24, %25, %26, %27, %28, %29, %30, %31, %32, %33, %34, %35, %36, %37, %38, %39, %40, %41, %42, %43, %44, %45, %46, %47}, {%60, %61, %62, %63}, tb, p1, 1, 1, 1;\n"
        "}\n"
        : "+f"(d[0]), "+f"(d[1]), "+f"(d[2]), "+f"(d[3]), "+f"(d[4]), "+f"(d[5]), "+f"(d[6]), "+f"(d[7]), "+f"(d[8]), "+f"(d[9]), "+f"(d[10]), "+f"(d[11]), "+f"(d[12]), "+f"(d[13]), "+f"(d[14]), "+f"(d[15]), "+f"(d[16]), "+f"(d[17]), "+f"(d[18]), "+f"(d[19]), "+f"(d[20]), "+f"(d[21]), "+f"(d[22]), "+f"(d[23]), "+f"(d[24]), "+f"(d[25]), "+f"(d[26]), "+f"(d[27]), "+f"(d[28]), "+f"(d[29]), "+f"(d[30]), "+f"(d[31]), "+f"(d[32]), "+f"(d[33]), "+f"(d[34]), "+f"(d[35]), "+f"(d[36]), "+f"(d[37]), "+f"(d[38]), "+f"(d[39]), "+f"(d[40]), "+f"(d[41]), "+f"(d[42]), "+f"(d[43]), "+f"(d[44]), "+f"(d[45]), "+f"(d[46]), "+f"(d[47])
        : "r"(a[AOFF + 0][0]), "r"(a[AOFF + 0][1]), "r"(a[AOFF + 0][2]), "r"(a[AOFF + 0][3]), "r"(a[AOFF + 1][0]), "r"(a[AOFF + 1][1]), "r"(a[AOFF + 1][2]), "r"(a[AOFF + 1][3]), "r"(a[AOFF + 2][0]), "r"(a[AOFF + 2][1]), "r"(a[AOFF + 2][2]), "r"(a[AOFF + 2][3]), "r"(a[AOFF + 3][0]), "r"(a[AOFF + 3][1]), "r"(a[AOFF + 3][2]), "r"(a[AOFF + 3][3]), "l"(descB), "n"(BOFF >> 4));
}
};
template <> struct Rng<0, 6, 12> {
template <int BOFF, int AOFF, int NA>
static __device__ __forceinline__ void run(float (&d)[48], const uint32_t (&a)[NA][4], uint64_t descB) {
    asm volatile(
        "{\n"
        ".reg .pred p0, p1;\n"
        ".reg .b64 ta, ta0, tb, tb0;\n"
        "setp.ne.b32 p0, 0, 0;\n"
        "setp.eq.b32 p1, 0, 0;\n"
        "add.s64 tb0, %72, %73;\n"
        "add.s64 tb, tb0, 1600;\n"
        "wgmma.mma_async.sync.aligned.m64n96k16.f32.bf16.bf16 {%0, %1, %2, %3, %4, %5, %6, %7, %8, %9, %10, %11, %12, %13, %14, %15, %16, %17, %18, %19, %20, %21, %22, %23, %24, %25, %26, %27, %28, %29, %30, %31, %32, %33, %34, %35, %36, %37, %38, %39, %40, %41, %42, %43, %44, %45, %46, %47}, {%48, %49, %50, %51}, tb, p1, 1, 1, 1;\n"
        "add.s64 tb, tb0, 1632;\n"
        "wgmma.mma_async.sync.aligned.m64n96k16.f32.bf16.bf16 {%0, %1, %2, %3, %4, %5, %6, %7, %8, %9, %10, %11, %12, %13, %14, %15, %16, %17, %18, %19, %20, %21, %22, %23, %24, %25, %26, %27, %28, %29, %30, %31, %32, %33, %34, %35, %36, %37, %38, %39, %40, %41, %42, %43, %44, %45, %46, %47}, {%52, %53, %54, %55}, tb, p1, 1, 1, 1;\n"
        "add.s64 tb, tb0, 3072;\n"
        "wgmma.mma_async.sync.aligned.m64n96k16.f32.bf16.bf16 {%0, %1, %2, %3, %4, %5, %6, %7, %8, %9, %10, %11, %12, %13, %14, %15, %16, %17, %18, %19, %20, %21, %22, %23, %24, %25, %26, %27, %28, %29, %30, %31, %32, %33, %34, %35, %36, %37, %38, %39, %40, %41, %42, %43, %44, %45, %46, %47}, {%56, %57, %58, %59}, tb, p1, 1, 1, 1;\n"
        "add.s64 tb, tb0, 3104;\n"
        "wgmma.mma_async.sync.aligned.m64n96k16.f32.bf16.bf16 {%0, %1, %2, %3, %4, %5, %6, %7, %8, %9, %10, %11, %12, %13, %14, %15, %16, %17, %18, %19, %20, %21, %22, %23, %24, %25, %26, %27, %28, %29, %30, %31, %32, %33, %34, %35, %36, %37, %38, %39, %40, %41, %42, %43, %44, %45, %46, %47}, {%60, %61, %62, %63}, tb, p1, 1, 1, 1;\n"
        "add.s64 tb, tb0, 3136;\n"
        "wgmma.mma_async.sync.aligned.m64n96k16.f32.bf16.bf16 {%0, %1, %2, %3, %4, %5, %6, %7, %8, %9, %10, %11, %12, %13, %14, %15, %16, %17, %18, %19, %20, %21, %22, %23, %24, %25, %26, %27, %28, %29, %30, %31, %32, %33, %34, %35, %36, %37, %38, %39, %40, %41, %42, %43, %44, %45, %46, %47}, {%64, %65, %66, %67}, tb, p1, 1, 1, 1;\n"
        "add.s64 tb, tb0, 3168;\n"
        "wgmma.mma_async.sync.aligned.m64n96k16.f32.bf16.bf16 {%0, %1, %2, %3, %4, %5, %6, %7, %8, %9, %10, %11, %12, %13, %14, %15, %16, %17, %18, %19, %20, %21, %22, %23, %24, %25, %26, %27, %28, %29, %30, %31, %32, %33, %34, %35, %36, %37, %38, %39, %40, %41, %42, %43, %44, %45, %46, %47}, {%68, %69, %70, %71}, tb, p1, 1, 1, 1;\n"
        "}\n"
        : "+f"(d[0]), "+f"(d[1]), "+f"(d[2]), "+f"(d[3]), "+f"(d[4]), "+f"(d[5]), "+f"(d[6]), "+f"(d[7]), "+f"(d[8]), "+f"(d[9]), "+f"(d[10]), "+f"(d[11]), "+f"(d[12]), "+f"(d[13]), "+f"(d[14]), "+f"(d[15]), "+f"(d[16]), "+f"(d[17]), "+f"(d[18]), "+f"(d[19]), "+f"(d[20]), "+f"(d[21]), "+f"(d[22]), "+f"(d[23]), "+f"(d[24]), "+f"(d[25]), "+f"(d[26]), "+f"(d[27]), "+f"(d[28]), "+f"(d[29]), "+f"(d[30]), "+f"(d[31]), "+f"(d[32]), "+f"(d[33]), "+f"(d[34]), "+f"(d[35]), "+f"(d[36]), "+f"(d[37]), "+f"(d[38]), "+f"(d[39]), "+f"(d[40]), "+f"(d[41]), "+f"(d[42]), "+f"(d[43]), "+f"(d[44]), "+f"(d[45]), "+f"(d[46]), "+f"(d[47])
        : "r"(a[AOFF + 0][0]), "r"(a[AOFF + 0][1]), "r"(a[AOFF + 0][2]), "r"(a[AOFF + 0][3]), "r"(a[AOFF + 1][0]), "r"(a[AOFF + 1][1]), "r"(a[AOFF + 1][2]), "r"(a[AOFF + 1][3]), "r"(a[AOFF + 2][0]), "r"(a[AOFF + 2][1]), "r"(a[AOFF + 2][2]), "r"(a[AOFF + 2][3]), "r"(a[AOFF + 3][0]), "r"(a[AOFF + 3][1]), "r"(a[AOFF + 3][2]), "r"(a[AOFF + 3][3]), "r"(a[AOFF + 4][0]), "r"(a[AOFF + 4][1]), "r"(a[AOFF + 4][2]), "r"(a[AOFF + 4][3]), "r"(a[AOFF + 5][0]), "r"(a[AOFF + 5][1]), "r"(a[AOFF + 5][2]), "r"(a[AOFF + 5][3]), "l"(descB), "n"(BOFF >> 4));
}
};
template <> struct Rng<1, 6, 12> {
template <int BOFF, int AOFF, int NA>
static __device__ __forceinline__ void run(float (&d)[48], const uint32_t (&a)[NA][4], uint64_t descB) {
    asm volatile(
        "{\n"
        ".reg .pred p0, p1;\n"
        ".reg .b64 ta, ta0, tb, tb0;\n"
        "setp.ne.b32 p0, 0, 0;\n"
        "setp.eq.b32 p1, 0, 0;\n"
        "add.s64 tb0, %72, %73;\n"
        "add.s64 tb, tb0, 192;\n"
        "wgmma.mma_async.sync.aligned.m64n96k16.f32.bf16.bf16 {%0, %1, %2, %3, %4, %5, %6, %7, %8, %9, %10, %11, %12, %13, %14, %15, %16, %17, %18, %19, %20, %21, %22, %23, %24, %25, %26, %27, %28, %29, %30, %31, %32, %33, %34, %35, %36, %37, %38, %39, %40, %41, %42, %43, %44, %45, %46, %47}, {%48, %49, %50, %51}, tb, p1, 1, 1, 1;\n"
        "add.s64 tb, tb0, 224;\n"
        "wgmma.mma_async.sync.aligned.m64n96k16.f32.bf16.bf16 {%0, %1, %2, %3, %4, %5, %6, %7, %8, %9, %10, %11, %12, %13, %14, %15, %16, %17, %18, %19, %20, %21, %22, %23, %24, %25, %26, %27, %28, %29, %30, %31, %32, %33, %34, %35, %36, %37, %38, %39, %40, %41, %42, %43, %44, %45, %46, %47}, {%52, %53, %54, %55}, tb, p1, 1, 1, 1;\n"
        "add.s64 tb, tb0, 256;\n"
        "wgmma.mma_async.sync.aligned.m64n96k16.f32.bf16.bf16 {%0, %1, %2, %3, %4, %5, %6, %7, %8, %9, %10, %11, %12, %13, %14, %15, %16, %17, %18, %19, %20, %21, %22, %23, %24, %25, %26, %27, %28, %29, %30, %31, %32, %33, %34, %35, %36, %37, %38, %39, %40, %41, %42, %43, %44, %45, %46, %47}, {%56, %57, %58, %59}, tb, p1, 1, 1, 1;\n"
        "add.s64 tb, tb0, 288;\n"
        "wgmma.mma_async.sync.aligned.m64n96k16.f32.bf16.bf16 {%0, %1, %2, %3, %4, %5, %6, %7, %8, %9, %10, %11, %12, %13, %14, %15, %16, %17, %18, %19, %20, %21, %22, %23, %24, %25, %26, %27, %28, %29, %30, %31, %32, %33, %34, %35, %36, %37, %38, %39, %40, %41, %42, %43, %44, %45, %46, %47}, {%60, %61, %62, %63}, tb, p1, 1, 1, 1;\n"
        "add.s64 tb, tb0, 320;\n"
        "wgmma.mma_async.sync.aligned.m64n96k16.f32.bf16.bf16 {%0, %1, %2, %3, %4, %5, %6, %7, %8, %9, %10, %11, %12, %13, %14, %15, %16, %17, %18, %19, %20, %21, %22, %23, %24, %25, %26, %27, %28, %29, %30, %31, %32, %33, %34, %35, %36, %37, %38, %39, %40, %41, %42, %43, %44, %45, %46, %47}, {%64, %65, %66, %67}, tb, p1, 1, 1, 1;\n"
        "add.s64 tb, tb0, 352;\n"
        "wgmma.mma_async.sync.aligned.m64n96k16.f32.bf16.bf16 {%0, %1, %2, %3, %4, %5, %6, %7, %8, %9, %10, %11, %12, %13, %14, %15, %16, %17, %18, %19, %20, %21, %22, %23, %24, %25, %26, %27, %28, %29, %30, %31, %32, %33, %34, %35, %36, %37, %38, %39, %40, %41, %42, %43, %44, %45, %46, %47}, {%68, %69, %70, %71}, tb, p1, 1, 1, 1;\n"
        "}\n"
        : "+f"(d[0]), "+f"(d[1]), "+f"(d[2]), "+f"(d[3]), "+f"(d[4]), "+f"(d[5]), "+f"(d[6]), "+f"(d[7]), "+f"(d[8]), "+f"(d[9]), "+f"(d[10]), "+f"(d[11]), "+f"(d[12]), "+f"(d[13]), "+f"(d[14]), "+f"(d[15]), "+f"(d[16]), "+f"(d[17]), "+f"(d[18]), "+f"(d[19]), "+f"(d[20]), "+f"(d[21]), "+f"(d[22]), "+f"(d[23]), "+f"(d[24]), "+f"(d[25]), "+f"(d[26]), "+f"(d[27]), "+f"(d[28]), "+f"(d[29]), "+f"(d[30]), "+f"(d[31]), "+f"(d[32]), "+f"(d[33]), "+f"(d[34]), "+f"(d[35]), "+f"(d[36]), "+f"(d[37]), "+f"(d[38]), "+f"(d[39]), "+f"(d[40]), "+f"(d[41]), "+f"(d[42]), "+f"(d[43]), "+f"(d[44]), "+f"(d[45]), "+f"(d[46]), "+f"(d[47])
        : "r"(a[AOFF + 0][0]), "r"(a[AOFF + 0][1]), "r"(a[AOFF + 0][2]), "r"(a[AOFF + 0][3]), "r"(a[AOFF + 1][0]), "r"(a[AOFF + 1][1]), "r"(a[AOFF + 1][2]), "r"(a[AOFF + 1][3]), "r"(a[AOFF + 2][0]), "r"(a[AOFF + 2][1]), "r"(a[AOFF + 2][2]), "r"(a[AOFF + 2][3]), "r"(a[AOFF + 3][0]), "r"(a[AOFF + 3][1]), "r"(a[AOFF + 3][2]), "r"(a[AOFF + 3][3]), "r"(a[AOFF + 4][0]), "r"(a[AOFF + 4][1]), "r"(a[AOFF + 4][2]), "r"(a[AOFF + 4][3]), "r"(a[AOFF + 5][0]), "r"(a[AOFF + 5][1]), "r"(a[AOFF + 5][2]), "r"(a[AOFF + 5][3]), "l"(descB), "n"(BOFF >> 4));
}
};
template <> struct Rng<0, 7, 12> {
template <int BOFF, int AOFF, int NA>
static __device__ __forceinline__ void run(float (&d)[48], const uint32_t (&a)[NA][4], uint64_t descB) {
    asm volatile(
        "{\n"
        ".reg .pred p0, p1;\n"
        ".reg .b64 ta, ta0, tb, tb0;\n"
        "setp.ne.b32 p0, 0, 0;\n"
        "setp.eq.b32 p1, 0, 0;\n"
        "add.s64 tb0, %68, %69;\n"
        "add.s64 tb, tb0, 1632;\n"
        "wgmma.mma_async.sync.aligned.m64n96k16.f32.bf16.bf16 {%0, %1, %2, %3, %4, %5, %6, %7, %8, %9, %10, %11, %12, %13, %14, %15, %16, %17, %18, %19, %20, %21, %22, %23, %24, %25, %26, %27, %28, %29, %30, %31, %32, %33, %34, %35, %36, %37, %38, %39, %40, %41, %42, %43, %44, %45, %46, %47}, {%48, %49, %50, %51}, tb, p1, 1, 1, 1;\n"
        "add.s64 tb, tb0, 3072;\n"
        "wgmma.mma_async.sync.aligned.m64n96k16.f32.bf16.bf16 {%0, %1, %2, %3, %4, %5, %6, %7, %8, %9, %10, %11, %12, %13, %14, %15, %16, %17, %18, %19, %20, %21, %22, %23, %24, %25, %26, %27, %28, %29, %30, %31, %32, %33, %34, %35, %36, %37, %38, %39, %40, %41, %42, %43, %44, %45, %46, %47}, {%52, %53, %54, %55}, tb, p1, 1, 1, 1;\n"
        "add.s64 tb, tb0, 3104;\n"
        "wgmma.mma_async.sync.aligned.m64n96k16.f32.bf16.bf16 {%0, %1, %2, %3, %4, %5, %6, %7, %8, %9, %10, %11, %12, %13, %14, %15, %16, %17, %18, %19, %20, %21, %22, %23, %24, %25, %26, %27, %28, %29, %30, %31, %32, %33, %34, %35, %36, %37, %38, %39, %40, %41, %42, %43, %44, %45, %46, %47}, {%56, %57, %58, %59}, tb, p1, 1, 1, 1;\n"
        "add.s64 tb, tb0, 3136;\n"
        "wgmma.mma_async.sync.aligned.m64n96k16.f32.bf16.bf16 {%0, %1, %2, %3, %4, %5, %6, %7, %8, %9, %10, %11, %12, %13, %14, %15, %16, %17, %18, %19, %20, %21, %22, %23, %24, %25, %26, %27, %28, %29, %30, %31, %32, %33, %34, %35, %36, %37, %38, %39, %40, %41, %42, %43, %44, %45, %46, %47}, {%60, %61, %62, %63}, tb, p1, 1, 1, 1;\n"
        "add.s64 tb, tb0, 3168;\n"
        "wgmma.mma_async.sync.aligned.m64n96k16.f32.bf16.bf16 {%0, %1, %2, %3, %4, %5, %6, %7, %8, %9, %10, %11, %12, %13, %14, %15, %16, %17, %18, %19, %20, %21, %22, %23, %24, %25, %26, %27, %28, %29, %30, %31, %32, %33, %34, %35, %36, %37, %38, %39, %40, %41, %42, %43, %44, %45, %46, %47}, {%64, %65, %66, %67}, tb, p1, 1, 1, 1;\n"
        "}\n"
        : "+f"(d[0]), "+f"(d[1]), "+f"(d[2]), "+f"(d[3]), "+f"(d[4]), "+f"(d[5]), "+f"(d[6]), "+f"(d[7]), "+f"(d[8]), "+f"(d[9]), "+f"(d[10]), "+f"(d[11]), "+f"(d[12]), "+f"(d[13]), "+f"(d[14]), "+f"(d[15]), "+f"(d[16]), "+f"(d[17]), "+f"(d[18]), "+f"(d[19]), "+f"(d[20]), "+f"(d[21]), "+f"(d[22]), "+f"(d[23]), "+f"(d[24]), "+f"(d[25]), "+f"(d[26]), "+f"(d[27]), "+f"(d[28]), "+f"(d[29]), "+f"(d[30]), "+f"(d[31]), "+f"(d[32]), "+f"(d[33]), "+f"(d[34]), "+f"(d[35]), "+f"(d[36]), "+f"(d[37]), "+f"(d[38]), "+f"(d[39]), "+f"(d[40]), "+f"(d[41]), "+f"(d[42]), "+f"(d[43]), "+f"(d[44]), "+f"(d[45]), "+f"(d[46]), "+f"(d[47])
        : "r"(a[AOFF + 0][0]), "r"(a[AOFF + 0][1]), "r"(a[AOFF + 0][2]), "r"(a[AOFF + 0][3]), "r"(a[AOFF + 1][0]), "r"(a[AOFF + 1][1]), "r"(a[AOFF + 1][2]), "r"(a[AOFF + 1][3]), "r"(a[AOFF + 2][0]), "r"(a[AOFF + 2][1]), "r"(a[AOFF + 2][2]), "r"(a[AOFF + 2][3]), "r"(a[AOFF + 3][0]), "r"(a[AOFF + 3][1]), "r"(a[AOFF + 3][2]), "r"(a[AOFF + 3][3]), "r"(a[AOFF + 4][0]), "r"(a[AOFF + 4][1]), "r"(a[AOFF + 4][2]), "r"(a[AOFF + 4][3]), "l"(descB), "n"(BOFF >> 4));
}
};
template <> struct Rng<1, 7, 12> {
template <int BOFF, int AOFF, int NA>
static __device__ __forceinline__ void run(float (&d)[48], const uint32_t (&a)[NA][4], uint64_t descB) {
    asm volatile(
        "{\n"
        ".reg .pred p0, p1;\n"
        ".reg .b64 ta, ta0, tb, tb0;\n"
        "setp.ne.b32 p0, 0, 0;\n"
        "setp.eq.b32 p1, 0, 0;\n"
        "add.s64 tb0, %68, %69;\n"
        "add.s64 tb, tb0, 224;\n"
        "wgmma.mma_async.sync.aligned.m64n96k16.f32.bf16.bf16 {%0, %1, %2, %3, %4, %5, %6, %7, %8, %9, %10, %11, %12, %13, %14, %15, %16, %17, %18, %19, %20, %21, %22, %23, %24, %25, %26, %27, %28, %29, %30, %31, %32, %33, %34, %35, %36, %37, %38, %39, %40, %41, %42, %43, %44, %45, %46, %47}, {%48, %49, %50, %51}, tb, p1, 1, 1, 1;\n"
        "add.s64 tb, tb0, 256;\n"
        "wgmma.mma_async.sync.aligned.m64n96k16.f32.bf16.bf16 {%0, %1, %2, %3, %4, %5, %6, %7, %8, %9, %10, %11, %12, %13, %14, %15, %16, %17, %18, %19, %20, %21, %22, %23, %24, %25, %26, %27, %28, %29, %30, %31, %32, %33, %34, %35, %36, %37, %38, %39, %40, %41, %42, %43, %44, %45, %46, %47}, {%52, %53, %54, %55}, tb, p1, 1, 1, 1;\n"
        "add.s64 tb, tb0, 288;\n"
        "wgmma.mma_async.sync.aligned.m64n96k16.f32.bf16.bf16 {%0, %1, %2, %3, %4, %5, %6, %7, %8, %9, %10, %11, %12, %13, %14, %15, %16, %17, %18, %19, %20, %21, %22, %23, %24, %25, %26, %27, %28, %29, %30, %31, %32, %33, %34, %35, %36, %37, %38, %39, %40, %41, %42, %43, %44, %45, %46, %47}, {%56, %57, %58, %59}, tb, p1, 1, 1, 1;\n"
        "add.s64 tb, tb0, 320;\n"
        "wgmma.mma_async.sync.aligned.m64n96k16.f32.bf16.bf16 {%0, %1, %2, %3, %4, %5, %6, %7, %8, %9, %10, %11, %12, %13, %14, %15, %16, %17, %18, %19, %20, %21, %22, %23, %24, %25, %26, %27, %28, %29, %30, %31, %32, %33, %34, %35, %36, %37, %38, %39, %40, %41, %42, %43, %44, %45, %46, %47}, {%60, %61, %62, %63}, tb, p1, 1, 1, 1;\n"
        "add.s64 tb, tb0, 352;\n"
        "wgmma.mma_async.sync.aligned.m64n96k16.f32.bf16.bf16 {%0, %1, %2, %3, %4, %5, %6, %7, %8, %9, %10, %11, %12, %13, %14, %15, %16, %17, %18, %19, %20, %21, %22, %23, %24, %25, %26, %27, %28, %29, %30, %31, %32, %33, %34, %35, %36, %37, %38, %39, %40, %41, %42, %43, %44, %45, %46, %47}, {%64, %65, %66, %67}, tb, p1, 1, 1, 1;\n"
        "}\n"
        : "+f"(d[0]), "+f"(d[1]), "+f"(d[2]), "+f"(d[3]), "+f"(d[4]), "+f"(d[5]), "+f"(d[6]), "+f"(d[7]), "+f"(d[8]), "+f"(d[9]), "+f"(d[10]), "+f"(d[11]), "+f"(d[12]), "+f"(d[13]), "+f"(d[14]), "+f"(d[15]), "+f"(d[16]), "+f"(d[17]), "+f"(d[18]), "+f"(d[19]), "+f"(d[20]), "+f"(d[21]), "+f"(d[22]), "+f"(d[23]), "+f"(d[24]), "+f"(d[25]), "+f"(d[26]), "+f"(d[27]), "+f"(d[28]), "+f"(d[29]), "+f"(d[30]), "+f"(d[31]), "+f"(d[32]), "+f"(d[33]), "+f"(d[34]), "+f"(d[35]), "+f"(d[36]), "+f"(d[37]), "+f"(d[38]), "+f"(d[39]), "+f"(d[40]), "+f"(d[41]), "+f"(d[42]), "+f"(d[43]), "+f"(d[44]), "+f"(d[45]), "+f"(d[46]), "+f"(d[47])
        : "r"(a[AOFF + 0][0]), "r"(a[AOFF + 0][1]), "r"(a[AOFF + 0][2]), "r"(a[AOFF + 0][3]), "r"(a[AOFF + 1][0]), "r"(a[AOFF + 1][1]), "r"(a[AOFF + 1][2]), "r"(a[AOFF + 1][3]), "r"(a[AOFF + 2][0]), "r"(a[AOFF + 2][1]), "r"(a[AOFF + 2][2]), "r"(a[AOFF + 2][3]), "r"(a[AOFF + 3][0]), "r"(a[AOFF + 3][1]), "r"(a[AOFF + 3][2]), "r"(a[AOFF + 3][3]), "r"(a[AOFF + 4][0]), "r"(a[AOFF + 4][1]), "r"(a[AOFF + 4][2]), "r"(a[AOFF + 4][3]), "l"(descB), "n"(BOFF >> 4));
}
};
template <> struct Rng<0, 8, 12> {
template <int BOFF, int AOFF, int NA>
static __device__ __forceinline__ void run(float (&d)[48], const uint32_t (&a)[NA][4], uint64_t descB) {
    asm volatile(
        "{\n"
        ".reg .pred p0, p1;\n"
        ".reg .b64 ta, ta0, tb, tb0;\n"
        "setp.ne.b32 p0, 0, 0;\n"
        "setp.eq.b32 p1, 0, 0;\n"
        "add.s64 tb0, %64, %65;\n"
        "add.s64 tb, tb0, 3072;\n"
        "wgmma.mma_async.sync.aligned.m64n96k16.f32.bf16.bf16 {%0, %1, %2, %3, %4, %5, %6, %7, %8, %9, %10, %11, %12, %13, %14, %15, %16, %17, %18, %19, %20, %21, %22, %23, %24, %25, %26, %27, %28, %29, %30, %31, %32, %33, %34, %35, %36, %37, %38, %39, %40, %41, %42, %43, %44, %45, %46, %47}, {%48, %49, %50, %51}, tb, p1, 1, 1, 1;\n"
        "add.s64 tb, tb0, 3104;\n"
        "wgmma.mma_async.sync.aligned.m64n96k16.f32.bf16.bf16 {%0, %1, %2, %3, %4, %5, %6, %7, %8, %9, %10, %11, %12, %13, %14, %15, %16, %17, %18, %19, %20, %21, %22, %23, %24, %25, %26, %27, %28, %29, %30, %31, %32, %33, %34, %35, %36, %37, %38, %39, %40, %41, %42, %43, %44, %45, %46, %47}, {%52, %53, %54, %55}, tb, p1, 1, 1, 1;\n"
        "add.s64 tb, tb0, 3136;\n"
        "wgmma.mma_async.sync.aligned.m64n96k16.f32.bf16.bf16 {%0, %1, %2, %3, %4, %5, %6, %7, %8, %9, %10, %11, %12, %13, %14, %15, %16, %17, %18, %19, %20, %21, %22, %23, %24, %25, %26, %27, %28, %29, %30, %31, %32, %33, %34, %35, %36, %37, %38, %39, %40, %41, %42, %43, %44, %45, %46, %47}, {%56, %57, %58, %59}, tb, p1, 1, 1, 1;\n"
        "add.s64 tb, tb0, 3168;\n"
        "wgmma.mma_async.sync.aligned.m64n96k16.f32.bf16.bf16 {%0, %1, %2, %3, %4, %5, %6, %7, %8, %9, %10, %11, %12, %13, %14, %15, %16, %17, %18, %19, %20, %21, %22, %23, %24, %25, %26, %27, %28, %29, %30, %31, %32, %33, %34, %35, %36, %37, %38, %39, %40, %41, %42, %43, %44, %45, %46, %47}, {%60, %61, %62, %63}, tb, p1, 1, 1, 1;\n"
        "}\n"
        : "+f"(d[0]), "+f"(d[1]), "+f"(d[2]), "+f"(d[3]), "+f"(d[4]), "+f"(d[5]), "+f"(d[6]), "+f"(d[7]), "+f"(d[8]), "+f"(d[9]), "+f"(d[10]), "+f"(d[11]), "+f"(d[12]), "+f"(d[13]), "+f"(d[14]), "+f"(d[15]), "+f"(d[16]), "+f"(d[17]), "+f"(d[18]), "+f"(d[19]), "+f"(d[20]), "+f"(d[21]), "+f"(d[22]), "+f"(d[23]), "+f"(d[24]), "+f"(d[25]), "+f"(d[26]), "+f"(d[27]), "+f"(d[28]), "+f"(d[29]), "+f"(d[30]), "+f"(d[31]), "+f"(d[32]), "+f"(d[33]), "+f"(d[34]), "+f"(d[35]), "+f"(d[36]), "+f"(d[37]), "+f"(d[38]), "+f"(d[39]), "+f"(d[40]), "+f"(d[41]), "+f"(d[42]), "+f"(d[43]), "+f"(d[44]), "+f"(d[45]), "+f"(d[46]), "+f"(d[47])
        : "r"(a[AOFF + 0][0]), "r"(a[AOFF + 0][1]), "r"(a[AOFF + 0][2]), "r"(a[AOFF + 0][3]), "r"(a[AOFF + 1][0]), "r"(a[AOFF + 1][1]), "r"(a[AOFF + 1][2]), "r"(a[AOFF + 1][3]), "r"(a[AOFF + 2][0]), "r"(a[AOFF + 2][1]), "r"(a[AOFF + 2][2]), "r"(a[AOFF + 2][3]), "r"(a[AOFF + 3][0]), "r"(a[AOFF + 3][1]), "r"(a[AOFF + 3][2]), "r"(a[AOFF + 3][3]), "l"(descB), "n"(BOFF >> 4));
}
};
template <> struct Rng<1, 8, 12> {
template <int BOFF, int AOFF, int NA>
static __device__ __forceinline__ void run(float (&d)[48], const uint32_t (&a)[NA][4], uint64_t descB) {
    asm volatile(
        "{\n"
        ".reg .pred p0, p1;\n"
        ".reg .b64 ta, ta0, tb, tb0;\n"
        "setp.ne.b32 p0, 0, 0;\n"
        "setp.eq.b32 p1, 0, 0;\n"
        "add.s64 tb0, %64, %65;\n"
        "add.s64 tb, tb0, 256;\n"
        "wgmma.mma_async.sync.aligned.m64n96k16.f32.bf16.bf16 {%0, %1, %2, %3, %4, %5, %6, %7, %8, %9, %10, %11, %12, %13, %14, %15, %16, %17, %18, %19, %20, %21, %22, %23, %24, %25, %26, %27, %28, %29, %30, %31, %32, %33, %34, %35, %36, %37, %38, %39, %40, %41, %42, %43, %44, %45, %46, %47}, {%48, %49, %50, %51}, tb, p1, 1, 1, 1;\n"
        "add.s64 tb, tb0, 288;\n"
        "wgmma.mma_async.sync.aligned.m64n96k16.f32.bf16.bf16 {%0, %1, %2, %3, %4, %5, %6, %7, %8, %9, %10, %11, %12, %13, %14, %15, %16, %17, %18, %19, %20, %21, %22, %23, %24, %25, %26, %27, %28, %29, %30, %31, %32, %33, %34, %35, %36, %37, %38, %39, %40, %41, %42, %43, %44, %45, %46, %47}, {%52, %53, %54, %55}, tb, p1, 1, 1, 1;\n"
        "add.s64 tb, tb0, 320;\n"
        "wgmma.mma_async.sync.aligned.m64n96k16.f32.bf16.bf16 {%0, %1, %2, %3, %4, %5, %6, %7, %8, %9, %10, %11, %12, %13, %14, %15, %16, %17, %18, %19, %20, %21, %22, %23, %24, %25, %26, %27, %28, %29, %30, %31, %32, %33, %34, %35, %36, %37, %38, %39, %40, %41, %42, %43, %44, %45, %46, %47}, {%56, %57, %58, %59}, tb, p1, 1, 1, 1;\n"
        "add.s64 tb, tb0, 352;\n"
        "wgmma.mma_async.sync.aligned.m64n96k16.f32.bf16.bf16 {%0, %1, %2, %3, %4, %5, %6, %7, %8, %9, %10, %11, %12, %13, %14, %15, %16, %17, %18, %19, %20, %21, %22, %23, %24, %25, %26, %27, %28, %29, %30, %31, %32, %33, %34, %35, %36, %37, %38, %39, %40, %41, %42, %43, %44, %45, %46, %47}, {%60, %61, %62, %63}, tb, p1, 1, 1, 1;\n"
        "}\n"
        : "+f"(d[0]), "+f"(d[1]), "+f"(d[2]), "+f"(d[3]), "+f"(d[4]), "+f"(d[5]), "+f"(d[6]), "+f"(d[7]), "+f"(d[8]), "+f"(d[9]), "+f"(d[10]), "+f"(d[11]), "+f"(d[12]), "+f"(d[13]), "+f"(d[14]), "+f"(d[15]), "+f"(d[16]), "+f"(d[17]), "+f"(d[18]), "+f"(d[19]), "+f"(d[20]), "+f"(d[21]), "+f"(d[22]), "+f"(d[23]), "+f"(d[24]), "+f"(d[25]), "+f"(d[26]), "+f"(d[27]), "+f"(d[28]), "+f"(d[29]), "+f"(d[30]), "+f"(d[31]), "+f"(d[32]), "+f"(d[33]), "+f"(d[34]), "+f"(d[35]), "+f"(d[36]), "+f"(d[37]), "+f"(d[38]), "+f"(d[39]), "+f"(d[40]), "+f"(d[41]), "+f"(d[42]), "+f"(d[43]), "+f"(d[44]), "+f"(d[45]), "+f"(d[46]), "+f"(d[47])
        : "r"(a[AOFF + 0][0]), "r"(a[AOFF + 0][1]), "r"(a[AOFF + 0][2]), "r"(a[AOFF + 0][3]), "r"(a[AOFF + 1][0]), "r"(a[AOFF + 1][1]), "r"(a[AOFF + 1][2]), "r"(a[AOFF + 1][3]), "r"(a[AOFF + 2][0]), "r"(a[AOFF + 2][1]), "r"(a[AOFF + 2][2]), "r"(a[AOFF + 2][3]), "r"(a[AOFF + 3][0]), "r"(a[AOFF + 3][1]), "r"(a[AOFF + 3][2]), "r"(a[AOFF + 3][3]), "l"(descB), "n"(BOFF >> 4));
}
};
template <> struct Rng<0, 9, 12> {
template <int BOFF, int AOFF, int NA>
static __device__ __forceinline__ void run(float (&d)[48], const uint32_t (&a)[NA][4], uint64_t descB) {
    asm volatile(
        "{\n"
        ".reg .pred p0, p1;\n"
        ".reg .b64 ta, ta0, tb, tb0;\n"
        "setp.ne.b32 p0, 0, 0;\n"
        "setp.eq.b32 p1, 0, 0;\n"
        "add.s64 tb0, %60, %61;\n"
        "add.s64 tb, tb0, 3104;\n"
        "wgmma.mma_async.sync.aligned.m64n96k16.f32.bf16.bf16 {%0, %1, %2, %3, %4, %5, %6, %7, %8, %9, %10, %11, %12, %13, %14, %15, %16, %17, %18, %19, %20, %21, %22, %23, %24, %25, %26, %27, %28, %29, %30, %31, %32, %33, %34, %35, %36, %37, %38, %39, %40, %41, %42, %43, %44, %45, %46, %47}, {%48, %49, %50, %51}, tb, p1, 1, 1, 1;\n"
        "add.s64 tb, tb0, 3136;\n"
        "wgmma.mma_async.sync.aligned.m64n96k16.f32.bf16.bf16 {%0, %1, %2, %3, %4, %5, %6, %7, %8, %9, %10, %11, %12, %13, %14, %15, %16, %17, %18, %19, %20, %21, %22, %23, %24, %25, %26, %27, %28, %29, %30, %31, %32, %33, %34, %35, %36, %37, %38, %39, %40, %41, %42, %43, %44, %45, %46, %47}, {%52, %53, %54, %55}, tb, p1, 1, 1, 1;\n"
        "add.s64 tb, tb0, 3168;\n"
        "wgmma.mma_async.sync.aligned.m64n96k16.f32.bf16.bf16 {%0, %1, %2, %3, %4, %5, %6, %7, %8, %9, %10, %11, %12, %13, %14, %15, %16, %17, %18, %19, %20, %21, %22, %23, %24, %25, %26, %27, %28, %29, %30, %31, %32, %33, %34, %35, %36, %37, %38, %39, %40, %41, %42, %43, %44, %45, %46, %47}, {%56, %57, %58, %59}, tb, p1, 1, 1, 1;\n"
        "}\n"
        : "+f"(d[0]), "+f"(d[1]), "+f"(d[2]), "+f"(d[3]), "+f"(d[4]), "+f"(d[5]), "+f"(d[6]), "+f"(d[7]), "+f"(d[8]), "+f"(d[9]), "+f"(d[10]), "+f"(d[11]), "+f"(d[12]), "+f"(d[13]), "+f"(d[14]), "+f"(d[15]), "+f"(d[16]), "+f"(d[17]), "+f"(d[18]), "+f"(d[19]), "+f"(d[20]), "+f"(d[21]), "+f"(d[22]), "+f"(d[23]), "+f"(d[24]), "+f"(d[25]), "+f"(d[26]), "+f"(d[27]), "+f"(d[28]), "+f"(d[29]), "+f"(d[30]), "+f"(d[31]), "+f"(d[32]), "+f"(d[33]), "+f"(d[34]), "+f"(d[35]), "+f"(d[36]), "+f"(d[37]), "+f"(d[38]), "+f"(d[39]), "+f"(d[40]), "+f"(d[41]), "+f"(d[42]), "+f"(d[43]), "+f"(d[44]), "+f"(d[45]), "+f"(d[46]), "+f"(d[47])
        : "r"(a[AOFF + 0][0]), "r"(a[AOFF + 0][1]), "r"(a[AOFF + 0][2]), "r"(a[AOFF + 0][3]), "r"(a[AOFF + 1][0]), "r"(a[AOFF + 1][1]), "r"(a[AOFF + 1][2]), "r"(a[AOFF + 1][3]), "r"(a[AOFF + 2][0]), "r"(a[AOFF + 2][1]), "r"(a[AOFF + 2][2]), "r"(a[AOFF + 2][3]), "l"(descB), "n"(BOFF >> 4));
}
};
template <> struct Rng<1, 9, 12> {
template <int BOFF, int AOFF, int NA>
static __device__ __forceinline__ void run(float (&d)[48], const uint32_t (&a)[NA][4], uint64_t descB) {
    asm volatile(
        "{\n"
        ".reg .pred p0, p1;\n"
        ".reg .b64 ta, ta0, tb, tb0;\n"
        "setp.ne.b32 p0, 0, 0;\n"
        "setp.eq.b32 p1, 0, 0;\n"
        "add.s64 tb0, %60, %61;\n"
        "add.s64 tb, tb0, 288;\n"
        "wgmma.mma_async.sync.aligned.m64n96k16.f32.bf16.bf16 {%0, %1, %2, %3, %4, %5, %6, %7, %8, %9, %10, %11, %12, %13, %14, %15, %16, %17, %18, %19, %20, %21, %22, %23, %24, %25, %26, %27, %28, %29, %30, %31, %32, %33, %34, %35, %36, %37, %38, %39, %40, %41, %42, %43, %44, %45, %46, %47}, {%48, %49, %50, %51}, tb, p1, 1, 1, 1;\n"
        "add.s64 tb, tb0, 320;\n"
        "wgmma.mma_async.sync.aligned.m64n96k16.f32.bf16.bf16 {%0, %1, %2, %3, %4, %5, %6, %7, %8, %9, %10, %11, %12, %13, %14, %15, %16, %17, %18, %19, %20, %21, %22, %23, %24, %25, %26, %27, %28, %29, %30, %31, %32, %33, %34, %35, %36, %37, %38, %39, %40, %41, %42, %43, %44, %45, %46, %47}, {%52, %53, %54, %55}, tb, p1, 1, 1, 1;\n"
        "add.s64 tb, tb0, 352;\n"
        "wgmma.mma_async.sync.aligned.m64n96k16.f32.bf16.bf16 {%0, %1, %2, %3, %4, %5, %6, %7, %8, %9, %10, %11, %12, %13, %14, %15, %16, %17, %18, %19, %20, %21, %22, %23, %24, %25, %26, %27, %28, %29, %30, %31, %32, %33, %34, %35, %36, %37, %38, %39, %40, %41, %42, %43, %44, %45, %46, %47}, {%56, %57, %58, %59}, tb, p1, 1, 1, 1;\n"
        "}\n"
        : "+f"(d[0]), "+f"(d[1]), "+f"(d[2]), "+f"(d[3]), "+f"(d[4]), "+f"(d[5]), "+f"(d[6]), "+f"(d[7]), "+f"(d[8]), "+f"(d[9]), "+f"(d[10]), "+f"(d[11]), "+f"(d[12]), "+f"(d[13]), "+f"(d[14]), "+f"(d[15]), "+f"(d[16]), "+f"(d[17]), "+f"(d[18]), "+f"(d[19]), "+f"(d[20]), "+f"(d[21]), "+f"(d[22]), "+f"(d[23]), "+f"(d[24]), "+f"(d[25]), "+f"(d[26]), "+f"(d[27]), "+f"(d[28]), "+f"(d[29]), "+f"(d[30]), "+f"(d[31]), "+f"(d[32]), "+f"(d[33]), "+f"(d[34]), "+f"(d[35]), "+f"(d[36]), "+f"(d[37]), "+f"(d[38]), "+f"(d[39]), "+f"(d[40]), "+f"(d[41]), "+f"(d[42]), "+f"(d[43]), "+f"(d[44]), "+f"(d[45]), "+f"(d[46]), "+f"(d[47])
        : "r"(a[AOFF + 0][0]), "r"(a[AOFF + 0][1]), "r"(a[AOFF + 0][2]), "r"(a[AOFF + 0][3]), "r"(a[AOFF + 1][0]), "r"(a[AOFF + 1][1]), "r"(a[AOFF + 1][2]), "r"(a[AOFF + 1][3]), "r"(a[AOFF + 2][0]), "r"(a[AOFF + 2][1]), "r"(a[AOFF + 2][2]), "r"(a[AOFF + 2][3]), "l"(descB), "n"(BOFF >> 4));
}
};
template <> struct Rng<0, 10, 12> {
template <int BOFF, int AOFF, int NA>
static __device__ __forceinline__ void run(float (&d)[48], const uint32_t (&a)[NA][4], uint64_t descB) {
    asm volatile(
        "{\n"
        ".reg .pred p0, p1;\n"
        ".reg .b64 ta, ta0, tb, tb0;\n"
        "setp.ne.b32 p0, 0, 0;\n"
        "setp.eq.b32 p1, 0, 0;\n"
        "add.s64 tb0, %56, %57;\n"
        "add.s64 tb, tb0, 3136;\n"
        "wgmma.mma_async.sync.aligned.m64n96k16.f32.bf16.bf16 {%0, %1, %2, %3, %4, %5, %6, %7, %8, %9, %10, %11, %12, %13, %14, %15, %16, %17, %18, %19, %20, %21, %22, %23, %24, %25, %26, %27, %28, %29, %30, %31, %32, %33, %34, %35, %36, %37, %38, %39, %40, %41, %42, %43, %44, %45, %46, %47}, {%48, %49, %50, %51}, tb, p1, 1, 1, 1;\n"
        "add.s64 tb, tb0, 3168;\n"
        "wgmma.mma_async.sync.aligned.m64n96k16.f32.bf16.bf16 {%0, %1, %2, %3, %4, %5, %6, %7, %8, %9, %10, %11, %12, %13, %14, %15, %16, %17, %18, %19, %20, %21, %22, %23, %24, %25, %26, %27, %28, %29, %30, %31, %32, %33, %34, %35, %36, %37, %38, %39, %40, %41, %42, %43, %44, %45, %46, %47}, {%52, %53, %54, %55}, tb, p1, 1, 1, 1;\n"
        "}\n"
        : "+f"(d[0]), "+f"(d[1]), "+f"(d[2]), "+f"(d[3]), "+f"(d[4]), "+f"(d[5]), "+f"(d[6]), "+f"(d[7]), "+f"(d[8]), "+f"(d[9]), "+f"(d[10]), "+f"(d[11]), "+f"(d[12]), "+f"(d[13]), "+f"(d[14]), "+f"(d[15]), "+f"(d[16]), "+f"(d[17]), "+f"(d[18]), "+f"(d[19]), "+f"(d[20]), "+f"(d[21]), "+f"(d[22]), "+f"(d[23]), "+f"(d[24]), "+f"(d[25]), "+f"(d[26]), "+f"(d[27]), "+f"(d[28]), "+f"(d[29]), "+f"(d[30]), "+f"(d[31]), "+f"(d[32]), "+f"(d[33]), "+f"(d[34]), "+f"(d[35]), "+f"(d[36]), "+f"(d[37]), "+f"(d[38]), "+f"(d[39]), "+f"(d[40]), "+f"(d[41]), "+f"(d[42]), "+f"(d[43]), "+f"(d[44]), "+f"(d[45]), "+f"(d[46]), "+f"(d[47])
        : "r"(a[AOFF + 0][0]), "r"(a[AOFF + 0][1]), "r"(a[AOFF + 0][2]), "r"(a[AOFF + 0][3]), "r"(a[AOFF + 1][0]), "r"(a[AOFF + 1][1]), "r"(a[AOFF + 1][2]), "r"(a[AOFF + 1][3]), "l"(descB), "n"(BOFF >> 4));
}
};
template <> struct Rng<1, 10, 12> {
template <int BOFF, int AOFF, int NA>
static __device__ __forceinline__ void run(float (&d)[48], const uint32_t (&a)[NA][4], uint64_t descB) {
    asm volatile(
        "{\n"
        ".reg .pred p0, p1;\n"
        ".reg .b64 ta, ta0, tb, tb0;\n"
        "setp.ne.b32 p0, 0, 0;\n"
        "setp.eq.b32 p1, 0, 0;\n"
        "add.s64 tb0, %56, %57;\n"
        "add.s64 tb, tb0, 320;\n"
        "wgmma.mma_async.sync.aligned.m64n96k16.f32.bf16.bf16 {%0, %1, %2, %3, %4, %5, %6, %7, %8, %9, %10, %11, %12, %13, %14, %15, %16, %17, %18, %19, %20, %21, %22, %23, %24, %25, %26, %27, %28, %29, %30, %31, %32, %33, %34, %35, %36, %37, %38, %39, %40, %41, %42, %43, %44, %45, %46, %47}, {%48, %49, %50, %51}, tb, p1, 1, 1, 1;\n"
        "add.s64 tb, tb0, 352;\n"
        "wgmma.mma_async.sync.aligned.m64n96k16.f32.bf16.bf16 {%0, %1, %2, %3, %4, %5, %6, %7, %8, %9, %10, %11, %12, %13, %14, %15, %16, %17, %18, %19, %20, %21, %22, %23, %24, %25, %26, %27, %28, %29, %30, %31, %32, %33, %34, %35, %36, %37, %38, %39, %40, %41, %42, %43, %44, %45, %46, %47}, {%52, %53, %54, %55}, tb, p1, 1, 1, 1;\n"
        "}\n"
        : "+f"(d[0]), "+f"(d[1]), "+f"(d[2]), "+f"(d[3]), "+f"(d[4]), "+f"(d[5]), "+f"(d[6]), "+f"(d[7]), "+f"(d[8]), "+f"(d[9]), "+f"(d[10]), "+f"(d[11]), "+f"(d[12]), "+f"(d[13]), "+f"(d[14]), "+f"(d[15]), "+f"(d[16]), "+f"(d[17]), "+f"(d[18]), "+f"(d[19]), "+f"(d[20]), "+f"(d[21]), "+f"(d[22]), "+f"(d[23]), "+f"(d[24]), "+f"(d[25]), "+f"(d[26]), "+f"(d[27]), "+f"(d[28]), "+f"(d[29]), "+f"(d[30]), "+f"(d[31]), "+f"(d[32]), "+f"(d[33]), "+f"(d[34]), "+f"(d[35]), "+f"(d[36]), "+f"(d[37]), "+f"(d[38]), "+f"(d[39]), "+f"(d[40]), "+f"(d[41]), "+f"(d[42]), "+f"(d[43]), "+f"(d[44]), "+f"(d[45]), "+f"(d[46]), "+f"(d[47])
        : "r"(a[AOFF + 0][0]), "r"(a[AOFF + 0][1]), "r"(a[AOFF + 0][2]), "r"(a[AOFF + 0][3]), "r"(a[AOFF + 1][0]), "r"(a[AOFF + 1][1]), "r"(a[AOFF + 1][2]), "r"(a[AOFF + 1][3]), "l"(descB), "n"(BOFF >> 4));
}
};
template <int V, int BOFF, int S0, int S1>
__device__ __forceinline__ void mma_rng(float (&d)[48], const uint32_t (&a)[12][4], uint64_t descB) {
    if constexpr (S0 < S1) Rng<V, S0, S1>::template run<BOFF, S0, 12>(d, a, descB);
}

template <int AOFF, int BOFF>
__device__ __forceinline__ void mma_qk0(float (&d)[28], uint64_t descA, uint64_t descB) {
    asm volatile(
        "{\n"
        ".reg .pred p0, p1;\n"
        ".reg .b64 ta, ta0, tb, tb0;\n"
        "setp.ne.b32 p0, 0, 0;\n"
        "setp.eq.b32 p1, 0, 0;\n"
        "add.s64 tb0, %30, %31;\n"
        "add.s64 ta0, %28, %29;\n"
        "add.s64 tb, tb0, 4;\n"
        "add.s64 ta, ta0, 0;\n"
        "wgmma.mma_async.sync.aligned.m64n56k16.f32.bf16.bf16 {%0, %1, %2, %3, %4, %5, %6, %7, %8, %9, %10, %11, %12, %13, %14, %15, %16, %17, %18, %19, %20, %21, %22, %23, %24, %25, %26, %27}, ta, tb, p0, 1, 1, 0, 0;\n"
        "add.s64 tb, tb0, 1572;\n"
        "add.s64 ta, ta0, 1568;\n"
        "wgmma.mma_async.sync.aligned.m64n56k16.f32.bf16.bf16 {%0, %1, %2, %3, %4, %5, %6, %7, %8, %9, %10, %11, %12, %13, %14, %15, %16, %17, %18, %19, %20, %21, %22, %23, %24, %25, %26, %27}, ta, tb, p1, 1, 1, 0, 0;\n"
        "add.s64 tb, tb0, 3140;\n"
        "add.s64 ta, ta0, 3136;\n"
        "wgmma.mma_async.sync.aligned.m64n56k16.f32.bf16.bf16 {%0, %1, %2, %3, %4, %5, %6, %7, %8, %9, %10, %11, %12, %13, %14, %15, %16, %17, %18, %19, %20, %21, %22, %23, %24, %25, %26, %27}, ta, tb, p1, 1, 1, 0, 0;\n"
        "}\n"
        : "=f"(d[0]), "=f"(d[1]), "=f"(d[2]), "=f"(d[3]), "=f"(d[4]), "=f"(d[5]), "=f"(d[6]), "=f"(d[7]), "=f"(d[8]), "=f"(d[9]), "=f"(d[10]), "=f"(d[11]), "=f"(d[12]), "=f"(d[13]), "=f"(d[14]), "=f"(d[15]), "=f"(d[16]), "=f"(d[17]), "=f"(d[18]), "=f"(d[19]), "=f"(d[20]), "=f"(d[21]), "=f"(d[22]), "=f"(d[23]), "=f"(d[24]), "=f"(d[25]), "=f"(d[26]), "=f"(d[27])
        : "l"(descA), "n"(AOFF >> 4), "l"(descB), "n"(BOFF >> 4));
}

template <int AOFF, int BOFF>
__device__ __forceinline__ void mma_qk1(float (&d)[28], uint64_t descA, uint64_t descB) {
    asm volatile(
        "{\n"
        ".reg .pred p0, p1;\n"
        ".reg .b64 ta, ta0, tb, tb0;\n"
        "setp.ne.b32 p0, 0, 0;\n"
        "setp.eq.b32 p1, 0, 0;\n"
        "add.s64 tb0, %30, %31;\n"
        "add.s64 ta0, %28, %29;\n"
        "add.s64 tb, tb0, 6;\n"
        "add.s64 ta, ta0, 2;\n"
        "wgmma.mma_async.sync.aligned.m64n56k16.f32.bf16.bf16 {%0, %1, %2, %3, %4, %5, %6, %7, %8, %9, %10, %11, %12, %13, %14, %15, %16, %17, %18, %19, %20, %21, %22, %23, %24, %25, %26, %27}, ta, tb, p0, 1, 1, 0, 0;\n"
        "add.s64 tb, tb0, 1574;\n"
        "add.s64 ta, ta0, 1570;\n"
        "wgmma.mma_async.sync.aligned.m64n56k16.f32.bf16.bf16 {%0, %1, %2, %3, %4, %5, %6, %7, %8, %9, %10, %11, %12, %13, %14, %15, %16, %17, %18, %19, %20, %21, %22, %23, %24, %25, %26, %27}, ta, tb, p1, 1, 1, 0, 0;\n"
        "add.s64 tb, tb0, 3142;\n"
        "add.s64 ta, ta0, 3138;\n"
        "wgmma.mma_async.sync.aligned.m64n56k16.f32.bf16.bf16 {%0, %1, %2, %3, %4, %5, %6, %7, %8, %9, %10, %11, %12, %13, %14, %15, %16, %17, %18, %19, %20, %21, %22, %23, %24, %25, %26, %27}, ta, tb, p1, 1, 1, 0, 0;\n"
        "}\n"
        : "=f"(d[0]), "=f"(d[1]), "=f"(d[2]), "=f"(d[3]), "=f"(d[4]), "=f"(d[5]), "=f"(d[6]), "=f"(d[7]), "=f"(d[8]), "=f"(d[9]), "=f"(d[10]), "=f"(d[11]), "=f"(d[12]), "=f"(d[13]), "=f"(d[14]), "=f"(d[15]), "=f"(d[16]), "=f"(d[17]), "=f"(d[18]), "=f"(d[19]), "=f"(d[20]), "=f"(d[21]), "=f"(d[22]), "=f"(d[23]), "=f"(d[24]), "=f"(d[25]), "=f"(d[26]), "=f"(d[27])
        : "l"(descA), "n"(AOFF >> 4), "l"(descB), "n"(BOFF >> 4));
}

template <int BOFF, int AOFF, int NA>
__device__ __forceinline__ void mma_pv(float (&d)[28], const uint32_t (&a)[NA][4], uint64_t descB) {
    asm volatile(
        "{\n"
        ".reg .pred p0, p1;\n"
        ".reg .b64 ta, ta0, tb, tb0;\n"
        "setp.ne.b32 p0, 0, 0;\n"
        "setp.eq.b32 p1, 0, 0;\n"
        "add.s64 tb0, %44, %45;\n"
        "add.s64 tb, tb0, 0;\n"
        "wgmma.mma_async.sync.aligned.m64n56k16.f32.bf16.bf16 {%0, %1, %2, %3, %4, %5, %6, %7, %8, %9, %10, %11, %12, %13, %14, %15, %16, %17, %18, %19, %20, %21, %22, %23, %24, %25, %26, %27}, {%28, %29, %30, %31}, tb, p0, 1, 1, 1;\n"
        "add.s64 tb, tb0, 16;\n"
        "wgmma.mma_async.sync.aligned.m64n56k16.f32.bf16.bf16 {%0, %1, %2, %3, %4, %5, %6, %7, %8, %9, %10, %11, %12, %13, %14, %15, %16, %17, %18, %19, %20, %21, %22, %23, %24, %25, %26, %27}, {%32, %33, %34, %35}, tb, p1, 1, 1, 1;\n"
        "add.s64 tb, tb0, 32;\n"
        "wgmma.mma_async.sync.aligned.m64n56k16.f32.bf16.bf16 {%0, %1, %2, %3, %4, %5, %6, %7, %8, %9, %10, %11, %12, %13, %14, %15, %16, %17, %18, %19, %20, %21, %22, %23, %24, %25, %26, %27}, {%36, %37, %38, %39}, tb, p1, 1, 1, 1;\n"
        "add.s64 tb, tb0, 48;\n"
        "wgmma.mma_async.sync.aligned.m64n56k16.f32.bf16.bf16 {%0, %1, %2, %3, %4, %5, %6, %7, %8, %9, %10, %11, %12, %13, %14, %15, %16, %17, %18, %19, %20, %21, %22, %23, %24, %25, %26, %27}, {%40, %41, %42, %43}, tb, p1, 1, 1, 1;\n"
        "}\n"
        : "=f"(d[0]), "=f"(d[1]), "=f"(d[2]), "=f"(d[3]), "=f"(d[4]), "=f"(d[5]), "=f"(d[6]), "=f"(d[7]), "=f"(d[8]), "=f"(d[9]), "=f"(d[10]), "=f"(d[11]), "=f"(d[12]), "=f"(d[13]), "=f"(d[14]), "=f"(d[15]), "=f"(d[16]), "=f"(d[17]), "=f"(d[18]), "=f"(d[19]), "=f"(d[20]), "=f"(d[21]), "=f"(d[22]), "=f"(d[23]), "=f"(d[24]), "=f"(d[25]), "=f"(d[26]), "=f"(d[27])
        : "r"(a[AOFF + 0][0]), "r"(a[AOFF + 0][1]), "r"(a[AOFF + 0][2]), "r"(a[AOFF + 0][3]), "r"(a[AOFF + 1][0]), "r"(a[AOFF + 1][1]), "r"(a[AOFF + 1][2]), "r"(a[AOFF + 1][3]), "r"(a[AOFF + 2][0]), "r"(a[AOFF + 2][1]), "r"(a[AOFF + 2][2]), "r"(a[AOFF + 2][3]), "r"(a[AOFF + 3][0]), "r"(a[AOFF + 3][1]), "r"(a[AOFF + 3][2]), "r"(a[AOFF + 3][3]), "l"(descB), "n"(BOFF >> 4));
}

template <int AOFF, int BOFF>
__device__ __forceinline__ void mma_proj(float (&d)[96], uint64_t descA, uint64_t descB) {
    asm volatile(
        "{\n"
        ".reg .pred p0, p1;\n"
        ".reg .b64 ta, ta0, tb, tb0;\n"
        "setp.ne.b32 p0, 0, 0;\n"
        "setp.eq.b32 p1, 0, 0;\n"
        "add.s64 tb0, %98, %99;\n"
        "add.s64 ta0, %96, %97;\n"
        "add.s64 tb, tb0, 0;\n"
        "add.s64 ta, ta0, 0;\n"
        "wgmma.mma_async.sync.aligned.m64n192k16.f32.bf16.bf16 {%0, %1, %2, %3, %4, %5, %6, %7, %8, %9, %10, %11, %12, %13, %14, %15, %16, %17, %18, %19, %20, %21, %22, %23, %24, %25, %26, %27, %28, %29, %30, %31, %32, %33, %34, %35, %36, %37, %38, %39, %40, %41, %42, %43, %44, %45, %46, %47, %48, %49, %50, %51, %52, %53, %54, %55, %56, %57, %58, %59, %60, %61, %62, %63, %64, %65, %66, %67, %68, %69, %70, %71, %72, %73, %74, %75, %76, %77, %78, %79, %80, %81, %82, %83, %84, %85, %86, %87, %88, %89, %90, %91, %92, %93, %94, %95}, ta, tb, p0, 1, 1, 0, 1;\n"
        "add.s64 tb, tb0, 64;\n"
        "add.s64 ta, ta0, 2;\n"
        "wgmma.mma_async.sync.aligned.m64n192k16.f32.bf16.bf16 {%0, %1, %2, %3, %4, %5, %6, %7, %8, %9, %10, %11, %12, %13, %14, %15, %16, %17, %18, %19, %20, %21, %22, %23, %24, %25, %26, %27, %28, %29, %30, %31, %32, %33, %34, %35, %36, %37, %38, %39, %40, %41, %42, %43, %44, %45, %46, %47, %48, %49, %50, %51, %52, %53, %54, %55, %56, %57, %58, %59, %60, %61, %62, %63, %64, %65, %66, %67, %68, %69, %70, %71, %72, %73, %74, %75, %76, %77, %78, %79, %80, %81, %82, %83, %84, %85, %86, %87, %88, %89, %90, %91, %92, %93, %94, %95}, ta, tb, p1, 1, 1, 0, 1;\n"
        "add.s64 tb, tb0, 128;\n"
        "add.s64 ta, ta0, 4;\n"
        "wgmma.mma_async.sync.aligned.m64n192k16.f32.bf16.bf16 {%0, %1, %2, %3, %4, %5, %6, %7, %8, %9, %10, %11, %12, %13, %14, %15, %16, %17, %18, %19, %20, %21, %22, %23, %24, %25, %26, %27, %28, %29, %30, %31, %32, %33, %34, %35, %36, %37, %38, %39, %40, %41, %42, %43, %44, %45, %46, %47, %48, %49, %50, %51, %52, %53, %54, %55, %56, %57, %58, %59, %60, %61, %62, %63, %64, %65, %66, %67, %68, %69, %70, %71, %72, %73, %74, %75, %76, %77, %78, %79, %80, %81, %82, %83, %84, %85, %86, %87, %88, %89, %90, %91, %92, %93, %94, %95}, ta, tb, p1, 1, 1, 0, 1;\n"
        "add.s64 tb, tb0, 192;\n"
        "add.s64 ta, ta0, 6;\n"
        "wgmma.mma_async.sync.aligned.m64n192k16.f32.bf16.bf16 {%0, %1, %2, %3, %4, %5, %6, %7, %8, %9, %10, %11, %12, %13, %14, %15, %16, %17, %18, %19, %20, %21, %22, %23, %24, %25, %26, %27, %28, %29, %30, %31, %32, %33, %34, %35, %36, %37, %38, %39, %40, %41, %42, %43, %44, %45, %46, %47, %48, %49, %50, %51, %52, %53, %54, %55, %56, %57, %58, %59, %60, %61, %62, %63, %64, %65, %66, %67, %68, %69, %70, %71, %72, %73, %74, %75, %76, %77, %78, %79, %80, %81, %82, %83, %84, %85, %86, %87, %88, %89, %90, %91, %92, %93, %94, %95}, ta, tb, p1, 1, 1, 0, 1;\n"
        "add.s64 tb, tb0, 256;\n"
        "add.s64 ta, ta0, 512;\n"
        "wgmma.mma_async.sync.aligned.m64n192k16.f32.bf16.bf16 {%0, %1, %2, %3, %4, %5, %6, %7, %8, %9, %10, %11, %12, %13, %14, %15, %16, %17, %18, %19, %20, %21, %22, %23, %24, %25, %26, %27, %28, %29, %30, %31, %32, %33, %34, %35, %36, %37, %38, %39, %40, %41, %42, %43, %44, %45, %46, %47, %48, %49, %50, %51, %52, %53, %54, %55, %56, %57, %58, %59, %60, %61, %62, %63, %64, %65, %66, %67, %68, %69, %70, %71, %72, %73, %74, %75, %76, %77, %78, %79, %80, %81, %82, %83, %84, %85, %86, %87, %88, %89, %90, %91, %92, %93, %94, %95}, ta, tb, p1, 1, 1, 0, 1;\n"
        "add.s64 tb, tb0, 320;\n"
        "add.s64 ta, ta0, 514;\n"
        "wgmma.mma_async.sync.aligned.m64n192k16.f32.bf16.bf16 {%0, %1, %2, %3, %4, %5, %6, %7, %8, %9, %10, %11, %12, %13, %14, %15, %16, %17, %18, %19, %20, %21, %22, %23, %24, %25, %26, %27, %28, %29, %30, %31, %32, %33, %34, %35, %36, %37, %38, %39, %40, %41, %42, %43, %44, %45, %46, %47, %48, %49, %50, %51, %52, %53, %54, %55, %56, %57, %58, %59, %60, %61, %62, %63, %64, %65, %66, %67, %68, %69, %70, %71, %72, %73, %74, %75, %76, %77, %78, %79, %80, %81, %82, %83, %84, %85, %86, %87, %88, %89, %90, %91, %92, %93, %94, %95}, ta, tb, p1, 1, 1, 0, 1;\n"
        "add.s64 tb, tb0, 384;\n"
        "add.s64 ta, ta0, 516;\n"
        "wgmma.mma_async.sync.aligned.m64n192k16.f32.bf16.bf16 {%0, %1, %2, %3, %4, %5, %6, %7, %8, %9, %10, %11, %12, %13, %14, %15, %16, %17, %18, %19, %20, %21, %22, %23, %24, %25, %26, %27, %28, %29, %30, %31, %32, %33, %34, %35, %36, %37, %38, %39, %40, %41, %42, %43, %44, %45, %46, %47, %48, %49, %50, %51, %52, %53, %54, %55, %56, %57, %58, %59, %60, %61, %62, %63, %64, %65, %66, %67, %68, %69, %70, %71, %72, %73, %74, %75, %76, %77, %78, %79, %80, %81, %82, %83, %84, %85, %86, %87, %88, %89, %90, %91, %92, %93, %94, %95}, ta, tb, p1, 1, 1, 0, 1;\n"
        "add.s64 tb, tb0, 448;\n"
        "add.s64 ta, ta0, 518;\n"
        "wgmma.mma_async.sync.aligned.m64n192k16.f32.bf16.bf16 {%0, %1, %2, %3, %4, %5, %6, %7, %8, %9, %10, %11, %12, %13, %14, %15, %16, %17, %18, %19, %20, %21, %22, %23, %24, %25, %26, %27, %28, %29, %30, %31, %32, %33, %34, %35, %36, %37, %38, %39, %40, %41, %42, %43, %44, %45, %46, %47, %48, %49, %50, %51, %52, %53, %54, %55, %56, %57, %58, %59, %60, %61, %62, %63, %64, %65, %66, %67, %68, %69, %70, %71, %72, %73, %74, %75, %76, %77, %78, %79, %80, %81, %82, %83, %84, %85, %86, %87, %88, %89, %90, %91, %92, %93, %94, %95}, ta, tb, p1, 1, 1, 0, 1;\n"
        "add.s64 tb, tb0, 512;\n"
        "add.s64 ta, ta0, 1024;\n"
        "wgmma.mma_async.sync.aligned.m64n192k16.f32.bf16.bf16 {%0, %1, %2, %3, %4, %5, %6, %7, %8, %9, %10, %11, %12, %13, %14, %15, %16, %17, %18, %19, %20, %21, %22, %23, %24, %25, %26, %27, %28, %29, %30, %31, %32, %33, %34, %35, %36, %37, %38, %39, %40, %41, %42, %43, %44, %45, %46, %47, %48, %49, %50, %51, %52, %53, %54, %55, %56, %57, %58, %59, %60, %61, %62, %63, %64, %65, %66, %67, %68, %69, %70, %71, %72, %73, %74, %75, %76, %77, %78, %79, %80, %81, %82, %83, %84, %85, %86, %87, %88, %89, %90, %91, %92, %93, %94, %95}, ta, tb, p1, 1, 1, 0, 1;\n"
        "add.s64 tb, tb0, 576;\n"
        "add.s64 ta, ta0, 1026;\n"
        "wgmma.mma_async.sync.aligned.m64n192k16.f32.bf16.bf16 {%0, %1, %2, %3, %4, %5, %6, %7, %8, %9, %10, %11, %12, %13, %14, %15, %16, %17, %18, %19, %20, %21, %22, %23, %24, %25, %26, %27, %28, %29, %30, %31, %32, %33, %34, %35, %36, %37, %38, %39, %40, %41, %42, %43, %44, %45, %46, %47, %48, %49, %50, %51, %52, %53, %54, %55, %56, %57, %58, %59, %60, %61, %62, %63, %64, %65, %66, %67, %68, %69, %70, %71, %72, %73, %74, %75, %76, %77, %78, %79, %80, %81, %82, %83, %84, %85, %86, %87, %88, %89, %90, %91, %92, %93, %94, %95}, ta, tb, p1, 1, 1, 0, 1;\n"
        "add.s64 tb, tb0, 640;\n"
        "add.s64 ta, ta0, 1028;\n"
        "wgmma.mma_async.sync.aligned.m64n192k16.f32.bf16.bf16 {%0, %1, %2, %3, %4, %5, %6, %7, %8, %9, %10, %11, %12, %13, %14, %15, %16, %17, %18, %19, %20, %21, %22, %23, %24, %25, %26, %27, %28, %29, %30, %31, %32, %33, %34, %35, %36, %37, %38, %39, %40, %41, %42, %43, %44, %45, %46, %47, %48, %49, %50, %51, %52, %53, %54, %55, %56, %57, %58, %59, %60, %61, %62, %63, %64, %65, %66, %67, %68, %69, %70, %71, %72, %73, %74, %75, %76, %77, %78, %79, %80, %81, %82, %83, %84, %85, %86, %87, %88, %89, %90, %91, %92, %93, %94, %95}, ta, tb, p1, 1, 1, 0, 1;\n"
        "add.s64 tb, tb0, 704;\n"
        "add.s64 ta, ta0, 1030;\n"
        "wgmma.mma_async.sync.aligned.m64n192k16.f32.bf16.bf16 {%0, %1, %2, %3, %4, %5, %6, %7, %8, %9, %10, %11, %12, %13, %14, %15, %16, %17, %18, %19, %20, %21, %22, %23, %24, %25, %26, %27, %28, %29, %30, %31, %32, %33, %34, %35, %36, %37, %38, %39, %40, %41, %42, %43, %44, %45, %46, %47, %48, %49, %50, %51, %52, %53, %54, %55, %56, %57, %58, %59, %60, %61, %62, %63, %64, %65, %66, %67, %68, %69, %70, %71, %72, %73, %74, %75, %76, %77, %78, %79, %80, %81, %82, %83, %84, %85, %86, %87, %88, %89, %90, %91, %92, %93, %94, %95}, ta, tb, p1, 1, 1, 0, 1;\n"
        "}\n"
        : "+f"(d[0]), "+f"(d[1]), "+f"(d[2]), "+f"(d[3]), "+f"(d[4]), "+f"(d[5]), "+f"(d[6]), "+f"(d[7]), "+f"(d[8]), "+f"(d[9]), "+f"(d[10]), "+f"(d[11]), "+f"(d[12]), "+f"(d[13]), "+f"(d[14]), "+f"(d[15]), "+f"(d[16]), "+f"(d[17]), "+f"(d[18]), "+f"(d[19]), "+f"(d[20]), "+f"(d[21]), "+f"(d[22]), "+f"(d[23]), "+f"(d[24]), "+f"(d[25]), "+f"(d[26]), "+f"(d[27]), "+f"(d[28]), "+f"(d[29]), "+f"(d[30]), "+f"(d[31]), "+f"(d[32]), "+f"(d[33]), "+f"(d[34]), "+f"(d[35]), "+f"(d[36]), "+f"(d[37]), "+f"(d[38]), "+f"(d[39]), "+f"(d[40]), "+f"(d[41]), "+f"(d[42]), "+f"(d[43]), "+f"(d[44]), "+f"(d[45]), "+f"(d[46]), "+f"(d[47]), "+f"(d[48]), "+f"(d[49]), "+f"(d[50]), "+f"(d[51]), "+f"(d[52]), "+f"(d[53]), "+f"(d[54]), "+f"(d[55]), "+f"(d[56]), "+f"(d[57]), "+f"(d[58]), "+f"(d[59]), "+f"(d[60]), "+f"(d[61]), "+f"(d[62]), "+f"(d[63]), "+f"(d[64]), "+f"(d[65]), "+f"(d[66]), "+f"(d[67]), "+f"(d[68]), "+f"(d[69]), "+f"(d[70]), "+f"(d[71]), "+f"(d[72]), "+f"(d[73]), "+f"(d[74]), "+f"(d[75]), "+f"(d[76]), "+f"(d[77]), "+f"(d[78]), "+f"(d[79]), "+f"(d[80]), "+f"(d[81]), "+f"(d[82]), "+f"(d[83]), "+f"(d[84]), "+f"(d[85]), "+f"(d[86]), "+f"(d[87]), "+f"(d[88]), "+f"(d[89]), "+f"(d[90]), "+f"(d[91]), "+f"(d[92]), "+f"(d[93]), "+f"(d[94]), "+f"(d[95])
        : "l"(descA), "n"(AOFF >> 4), "l"(descB), "n"(BOFF >> 4));
}

struct Params {
    const __nv_bfloat16* x;
    const __nv_bfloat16* wqkv;
    const __nv_bfloat16* wo;
    const __nv_bfloat16* logit_scale;
    const __nv_bfloat16* cpb_w1;
    const __nv_bfloat16* cpb_w2;
    const __nv_bfloat16* rel_coords;
    const int*           rel_idx;
    const __nv_bfloat16* mask;
    __nv_bfloat16*       out;
    unsigned long long   z1;
};

struct Q {
    static constexpr int npair = NPAIR, nh = NH, hw = NH ? HW : 0;
    static constexpr uint32_t need = ROW_DONE;
    static constexpr int nq = (NWINDOWS - hw) / NPAIR, nr = (NWINDOWS - hw) % NPAIR;
    static constexpr int nr2 = 2 * nr, nt0 = (nq * TOK + 63) / 64, nt1 = ((nq + 1) * TOK + 63) / 64;
    static constexpr int hq = NH ? HW / (NH ? NH : 1) : 0, hr = NPAIR + (NH ? HW % (NH ? NH : 1) : 0), hr2 = 2 * hr;
    static constexpr int ht0 = (hq * TOK + 63) / 64, ht1 = ((hq + 1) * TOK + 63) / 64;
    static constexpr int t1 = TILES - NTAIL;
};
#define PQ(f) Q::f
#define GRID 132

struct Maps {
    CUtensorMap x77, x47, x37, x44, x43, x34, x33;
    CUtensorMap w64, w32, w;
    CUtensorMap s47, s37, s43, s33;
    CUtensorMap o, ob;
};

__device__ __forceinline__ uint32_t row_token(uint32_t r) {
    return r < 28 ? r + 3 * (r >> 2) : r - 24 + 4 * (((r - 28) * 11) >> 5);
}
__device__ __forceinline__ int unrot(int r) { return r ? r - 1 : NWS - 1; }
__device__ __forceinline__ void finish(uint32_t total) {
    __threadfence();
    if (atomicAdd(&g_done, 1u) == total - 1) {
        for (int i = 0; i <= NWS; i++) g_cnt[i] = 0;
        g_done = 0;
    }
}

__global__ void __launch_bounds__(NTHREADS, 1)
swin_window_attn_kernel(const Params P, const __grid_constant__ Maps M) {
    const CUtensorMap &xmap = M.x77, &omap = M.o, &omapb = M.ob, &wmap = M.w;
    extern __shared__ __align__(1024) uint8_t smem[];
    constexpr uint32_t sbase = 1024;
    if (smem_u32(smem) != sbase) return;
    const int tid = threadIdx.x;
    const int wg = __shfl_sync(0xffffffffu, tid >> 7, 0);
    const int warp = __shfl_sync(0xffffffffu, (tid >> 5) & 3, 0);
    const int lane = tid & 31;
    const int g = lane >> 2, c = lane & 3;

    TR(26, wg);
    TP(wg);
    if (tid == 0) TC(0);
    const bool attn = (int)blockIdx.x < 2 * (PQ(npair) + PQ(nh));
    const int pair = blockIdx.x >> 1, half = blockIdx.x & 1;
    const int nwin = pair < PQ(npair) ? PQ(nq) + (pair < PQ(nr) ? 1 : 0) : PQ(hq) + (pair < PQ(hr) ? 1 : 0);
    const int w0 = pair < PQ(npair) ? PQ(hw) + pair : pair - PQ(npair), wstep = pair < PQ(npair) ? PQ(npair) : PQ(nh);
    const int wr0 = w0 >= NWS, wq0 = w0 - wr0 * NWS;
    const int ntiles = (nwin * TOK + 63) >> 6;
    const uint32_t bars = sbase + SM_BAR;
    auto load_x = [&](uint32_t dst, uint32_t bar, uint32_t bar2, int wh, int ww) {
        const int x0 = 7 * ww + 3, y0 = 7 * wh + 3, x1 = ww == NWS - 1 ? 0 : x0 + 4;
        if (wh < NWS - 1) {
#pragma unroll
            for (int ch = 0; ch < 3; ch++) tma_3d_x(dst + ch * QK_CHUNK, &M.x47, bar, ch * 64, x0, y0);
#pragma unroll
            for (int ch = 0; ch < 3; ch++) tma_3d_x(dst + ch * QK_CHUNK + 28 * 128, &M.x37, bar2, ch * 64, x1, y0);
        } else {
#pragma unroll
            for (int ch = 0; ch < 3; ch++) {
                tma_3d_x(dst + ch * QK_CHUNK, &M.x44, bar, ch * 64, x0, y0);
                tma_3d_x(dst + ch * QK_CHUNK + 16 * 128, &M.x43, bar, ch * 64, x0, 0);
            }
#pragma unroll
            for (int ch = 0; ch < 3; ch++) {
                tma_3d_x(dst + ch * QK_CHUNK + 28 * 128, &M.x34, bar2, ch * 64, x1, y0);
                tma_3d_x(dst + ch * QK_CHUNK + 40 * 128, &M.x33, bar2, ch * 64, x1, 0);
            }
        }
    };
    if (EPF && (wg == 1 || wg == 2)) {
        const int i = tid - 128, q = w0 + half * wstep, r = q >= NWS;
        const int px = (i * 171) >> 9, py = (px * 37) >> 8;
        int y = 7 * unrot(r) + 3 + py, x = 7 * unrot(q - r * NWS) + 3 + px - 7 * py;
        if (y >= IMG) y -= IMG;
        if (x >= IMG) x -= IMG;
        const char* p = reinterpret_cast<const char*>(P.x) + (size_t)(y * IMG + x) * 384 + (i - 3 * px) * 128;
        if (EPW && i >= 147) p = reinterpret_cast<const char*>(P.wqkv) + min((int)blockIdx.x * 14 + i - 147, 1727) * 128;
        if (i < 147 ? attn : EPW && i < 161) {
            if (EPF == 1) asm volatile("prefetch.global.L2 [%0];\n" :: "l"(p) : "memory");
            if (EPF == 2) { uint32_t d; asm volatile("ld.global.nc.L2::128B.b32 %0, [%1];\n" : "=r"(d) : "l"(p) : "memory"); }
            if (EPF == 3) for (int j = 0; j < 4; j++) asm volatile("prefetch.global.L2 [%0];\n" :: "l"(p + 32 * j) : "memory");
        }
    }
    uint32_t ls = 0;
    if (wg == 0) {
        TP(28);
        if (attn && warp < (WSEQ ? 1 : 3) && elect_one()) {
#pragma unroll
            for (int i = 0; i < (WSEQ ? 3 : 1); i++) mbar_init(bars + B_WRAW + 16 - 8 * (warp + i), 1);
            fence_async_smem();
            if (HDEL && pair >= PQ(npair)) {
                const uint32_t c0 = clock();
                while (clock() - c0 < HDEL) __nanosleep(100);
            }
            TP(29);
#pragma unroll 1
            for (int i = warp; i < warp + (WSEQ ? 3 : 1); i++) {
                const uint32_t bar = bars + B_WRAW + 16 - 8 * i, dst = sbase + i * 24576;
                mbar_arrive_expect_tx(bar, 24576);
                tma_3d(dst, &M.w64, bar, half * 128, 64 * i, 0);
                tma_3d(dst + 16384, &M.w32, bar, 64 + half * 32, 64 * i, 0);
            }
            TP(30);
        }
        __syncwarp();
        if (WFIRST && warp == 0) asm volatile("bar.arrive 3, 96;\n" ::: "memory");
        if (PPAR && warp == 0) nb_arrive<416>(11);
        if (attn) asm volatile("ld.global.nc.u16 %0, [%1];\n" : "=r"(ls) : "l"(P.logit_scale + 2 * half + (GORD == 2 ? c >> 1 : c & 1)));
    } else if (wg == 3) {
        if (warp == 3) {
            if (elect_one()) {
#pragma unroll
                for (int i = 0; i < 6; i++)
                    asm volatile("prefetch.tensormap [%0];\n" :: "l"(reinterpret_cast<uint64_t>(&M.x44 + (i < 4 ? i : i - 6))) : "memory");
            }
            if (attn)
#pragma unroll
                for (int i = 0; i < 4; i++) sts128(sbase + SM_V + i * V_STRIDE + (lane < 16 ? lane * 16 : V_STRIDE - 64 + (lane & 3) * 16), 0, 0, 0, 0);
            sts32(sbase + SM_FLAG + lane * 4, 0);
            fence_async_smem();
            asm volatile("bar.arrive 0, 256;\nbar.arrive 11, %0;\n" :: "n"(PPAR ? 416 : 384) : "memory");
        } else if (warp != 1) {
            if (tid == 384) {
                for (int b = 0; b < 4; b++) mbar_init(bars + B_XFULL + b * 8, 2);
                asm volatile("mbarrier.expect_tx.relaxed.cta.shared::cta.b64 [%0], %1;\n" :: "r"(bars + B_XFULL + 8), "r"(3 * 21 * 128) : "memory");
                fence_async_smem();
            }
            __syncwarp();
            asm volatile("bar.arrive 0, 256;\nbar.arrive 11, %0;\n" :: "n"(PPAR ? 416 : 384) : "memory");
            nb_sync<WFIRST ? 96 : 64>(3);
            if (attn && elect_one()) {
                const int j = warp >> 1, q = w0 + j * wstep, r = q >= NWS;
                mbar_arrive_expect_tx(bars + B_XFULL, j ? 3 * 28 * 128 : 3 * XCH);
                load_x(sbase + SM_QK + j * XCH, bars + B_XFULL, bars + B_XFULL + j * 8, unrot(r), unrot(q - r * NWS));
                TP(26 + j);
            }
            __syncwarp();
        } else {
            if (lane == 0) {
                for (int b = 0; b < 4; b++) {
                    mbar_init(bars + B_QKRAW + b * 8, 4);
                    mbar_init(bars + B_VRAW + b * 8, 4);
                    mbar_init(bars + B_VFREE + b * 8, 2);
                    mbar_init(bars + B_QKFREE + b * 8, (NB & 1) ? 1 : 4);
                    mbar_init(bars + B_ODONE + b * 8, 4);
                }
                mbar_init(bars + B_WFULL, 1);
                mbar_init(bars + B_MFULL, 1);
                mbar_init(bars + B_MCONS, 4);
                sts32(bars + B_PROG, 0);
                if (SDEF == 4) sts32(bars + B_PROG + 8, 0);
                for (int b = 0; b < 4; b++) mbar_init(bars + B_STORED + b * 8, 1);
                for (int b = 0; b < 6; b++) {
                    mbar_init(sbase + SM_PBAR + b * 8, 1);
                    mbar_init(sbase + SM_PBAR + 48 + b * 8, PSTORE ? 1 : 4);
                    mbar_init(sbase + SM_PBAR + 104 + b * 8, 4);
                }
                mbar_init(sbase + SM_PBAR + 96, 13);
                fence_async_smem();
            }
            __syncwarp();
            TP(19);
            asm volatile("bar.arrive 0, 256;\nbar.arrive 11, %0;\n" :: "n"(PPAR ? 416 : 384) : "memory");
        }
        asm volatile("bar.sync 2, 128;\n" ::: "memory");
        if (warp == 3 && lane < 8)
            asm volatile("prefetch.tensormap [%0];\n" :: "l"(reinterpret_cast<uint64_t>(&M.x77 + (lane ? lane + 8 : 0))) : "memory");
        TP(13);
    }
    uint32_t ridx[26];
    uint32_t rc, w2[16];
    uint4 w1[4];
    if (attn && (wg == 1 || wg == 2)) {
        rc = reinterpret_cast<const uint32_t*>(P.rel_coords)[min(tid - 128, 168)];
#pragma unroll
        for (int i = 0; i < 4; i++) w1[i] = reinterpret_cast<const uint4*>(P.cpb_w1)[i];
#pragma unroll
        for (int u = 0; u < 16; u++) w2[u] = reinterpret_cast<const uint32_t*>(P.cpb_w2)[2 * u + half];
        ls = reinterpret_cast<const uint32_t*>(P.logit_scale)[half];
        asm volatile("" ::: "memory");
        uint32_t col[7];
#pragma unroll
        for (int j = 0; j < 7; j++) {
            const uint32_t n = j ? 8 * ((j + 5) >> 1) + ((j + 1) & 1) : 0;
            col[j] = prmt(0, row_token(n) | row_token(n + 2) << 8 | row_token(n + 4) << 16 | row_token(n + 6) << 24, 4 + c);
        }
#pragma unroll
        for (int rh = 0; rh < 2; rh++) {
            const uint32_t* ri = reinterpret_cast<const uint32_t*>(P.rel_idx) + row_token(min(warp * 16 + g + 8 * rh, TOK - 1)) * TOK;
            asm volatile("" : "+l"(ri));
#pragma unroll
            for (int j = 0; j < 12; j++) ridx[13 * rh + j] = j < 6 ? (ri + col[0])[14 * (j >> 1) + (j & 1)] : ri[col[j - 5]];
            ridx[13 * rh + 12] = ri[48];
        }
    }
    if (wg == 1) TP(31);
    if (wg == 0) asm volatile("bar.sync 0, 256;\n" ::: "memory");
    else if (wg < 3) nb_sync<PPAR ? 416 : 384>(11);
    TP(4 + wg);

    const uint32_t nfinish = GRID + 4 * (PQ(npair) + PQ(nh));
#define PROJ_SCHEDULE                                                                                   \
    int bid = blockIdx.x;                                                                               \
    asm volatile("" : "+r"(bid));                      \
    const bool at = bid < 2 * PQ(npair);                                                                  \
    const int tile0 = at ? PQ(t1) + 2 * PQ(npair) - 1 - bid : bid - 2 * PQ(npair);                                              \
    const int tstep = at ? 2 * PQ(npair) : GRID - 2 * PQ(npair);                                  \
    const int tend = at ? TILES : PQ(t1);
    if (wg == 3) {
        asm volatile("setmaxnreg.dec.sync.aligned.u32 %0;\n" :: "n"(REG_H));
        if (attn && warp == 1 && !(XP & 1)) {
            uint32_t fph = 0, cph = 0, mis = 0, busy = 0;
            auto load = [&](int k, uint32_t dst) {
                const int wi = w0 + k * wstep, wr = wi / NWS;
                const uint32_t off = (uint32_t)(unrot(wr) * NWS + unrot(wi - wr * NWS)) * 4802u;
                mis = mis << 4 | (off & 15);
                if (busy) {
                    mbar_wait(bars + B_MCONS, cph);
                    cph ^= 1;
                    fence_async_smem();
                    busy = 0;
                }
                if (elect_one()) {
                    uint32_t bytes = 4816;
                    if (wi == 0) {
                        bytes = 4800;
                        asm volatile("st.shared.u16 [%0], %1;\n" :: "r"(sbase + SM_MASK + 4800),
                                     "h"(reinterpret_cast<const uint16_t*>(P.mask)[NWINDOWS * TOK * TOK - 1]) : "memory");
                    }
                    asm volatile("mbarrier.expect_tx.relaxed.cta.shared::cta.b64 [%0], %1;\n" :: "r"(bars + B_MFULL), "r"(bytes) : "memory");
                    if (dst == sbase + SM_MASK) mbar_arrive(bars + B_MFULL);
                    asm volatile("cp.async.bulk.shared::cluster.global.mbarrier::complete_tx::bytes.L2::cache_hint [%0], [%1], %2, [%3], %4;\n"
                                 :: "r"(dst), "l"(reinterpret_cast<const char*>(P.mask) + (off & ~15u)),
                                    "r"(bytes), "r"(bars + B_MFULL), "l"(EVICT_FIRST) : "memory");
                }
            };
            auto landed = [&]() {
                mbar_wait_s<HS & 1>(bars + B_MFULL, fph);
                fph ^= 1;
            };
            auto flag = [&](int k, uint32_t f) {
                asm volatile("st.volatile.shared.u8 [%0], %1;\n" :: "r"(sbase + SM_FLAG + k), "r"(f) : "memory");
                TR(18, k);
                if (k < 2) TP(14 + k);
            };
            auto buffer = [&](int k) { return sbase + (k == 0 || k > 3 ? SM_MASK : SM_V + 2 * V_STRIDE + 256 + (k >> 1) * 4816); };
#pragma unroll 1
            for (int k = 2 + half; k >= 0; k = (k >> 1) - (k == 0)) load(k, buffer(k));
            uint32_t todo = 0;
            int sp = 0;
#pragma unroll 1
            for (int k = 0, kn; sp < nwin; k = kn) {
                if (k < nwin) {
#pragma unroll 1
                    for (uint32_t n = 0; n < (1u << 22); n++) {
                        int done;
                        asm volatile("ld.volatile.shared.b32 %0, [%1];\n" : "=r"(done) : "r"(bars + B_PROG) : "memory");
                        if (done >= (k + 2 < nwin ? k - MLEAD : k - 3)) break;
                        __nanosleep(PSLEEP);
                    }
                    const uint32_t buf = buffer(k);
                    if (buf == sbase + SM_MASK) landed();
                    TR(17, k);
                    uint32_t any;
                    asm volatile("ld.shared.u16 %0, [%1];\n" : "=r"(any)
                                 : "r"(buf + (mis & 15) + ((lane & 8) ? 4800 - 14 : 0) + (lane & 7) * 2) : "memory");
                    mis >>= 4;
#pragma unroll
                    for (int i = 0; i < 10; i++) {
                        uint32_t v[4];
                        asm volatile("ld.shared.v4.b32 {%0, %1, %2, %3}, [%4];\n" : "=r"(v[0]), "=r"(v[1]), "=r"(v[2]), "=r"(v[3])
                                     : "r"(buf + lane * 16 + (i < 9 ? 16 + i * 512 : 4800 - 512)) : "memory");
                        any |= (v[0] | v[1]) | (v[2] | v[3]);
                    }
                    const uint32_t masked = __any_sync(0xffffffffu, any & 0x7FFF7FFFu);
                    if (k >= 2) asm volatile("st.relaxed.gpu.global.u32 [%0], %1;\n" :: "l"(g_flag + pair * 128 + k), "r"(1 + masked) : "memory");
                    if (masked && k) todo |= 1u << (k - sp);
                    else {
                        if (k == 0) __threadfence_block();
                        flag(k, 1 + masked);
                        busy |= masked;
                    }
                }
                if ((k >> 1) == 1 && lane == 0) mbar_arrive(bars + B_VFREE + 8);
                if (k > 2 && k <= nwin) {
                    uint32_t f;
#pragma unroll 1
                    for (uint32_t n = 0; n < (1u << 22); n++) {
                        asm volatile("ld.relaxed.gpu.global.u32 %0, [%1];\n" : "=r"(f) : "l"(g_flag + pair * 128 + k - 1) : "memory");
                        if (__all_sync(0xffffffffu, f)) break;
                        __nanosleep(PSLEEP);
                    }
                    g_flag[pair * 128 + k - 1] = 0;
                    if (f != 1) todo |= 1u << (k - 1 - sp);
                    else flag(k - 1, 1);
                }
#pragma unroll 1
                for (; sp < k; sp++, todo >>= 1)
                    if (todo & 1) {
                        load(sp, sbase + SM_MASK);
                        landed();
                        __threadfence_block();
                        flag(sp, 2);
                        busy = 1;
                    }
                kn = k >= 2 ? k + 2 : k + 1 + (k & half);
                if (kn < nwin && kn > 3) load(kn, sbase + SM_MASK);
                if (MP2 && kn + 2 * MP2 < nwin && kn > 1) {
                    const int wi = w0 + (kn + 2 * MP2) * wstep, wr = wi / NWS;
                    const uint32_t off = (uint32_t)(unrot(wr) * NWS + unrot(wi - wr * NWS)) * 4802u;
                    if (elect_one())
                        asm volatile("cp.async.bulk.prefetch.L2.global [%0], 4816;\n" :: "l"(reinterpret_cast<const char*>(P.mask) + (off & ~15u)) : "memory");
                }
            }
        }
        if (!elect_one()) return;
        if (warp == 0) {
          if (attn) {
            const int kmax = (64 * ntiles + 63) / TOK;
            int wr = wr0, wq = wq0, npf = 0;
            int pr2 = (w0 + PF_DIST * wstep) / NWS, pq2 = w0 + PF_DIST * wstep - pr2 * NWS;
#pragma unroll 1
            for (int k = -4; k + 4 <= kmax; k++) {
                const int row0 = (k + 4) * TOK;
                const uint32_t dst = sbase + SM_QK + (k & 3) * XCH, bar = bars + B_XFULL + ((row0 >> 6) & 3) * 8;
                const bool alone = (row0 & 63) >= 64 - TOK && (row0 & 63) < TOK;
                const int wh = unrot(wr), ww = unrot(wq), ph2 = unrot(pr2), pw2 = unrot(pq2);
                const bool done = k < -2;
                if (k == WVK) {
                    TP(24);
                    mbar_arrive_expect_tx(bars + B_WFULL, 6 * W_ATOM);
                    tma_3d(sbase + SM_WV, &wmap, bars + B_WFULL, 0, 0, V64 ? 12 + half * 3 : 24 + half * 6);
                }
                const uint32_t bar2 = (row0 & 63) >= 64 - 28 ? bars + B_XFULL + (((row0 >> 6) + 1) & 3) * 8 : bar;
                if (alone && !done) mbar_arrive(bar);
                if (!done && !(k + 4 >= nwin && k >= 0)) {
                    if (bar2 != bar) asm volatile("mbarrier.expect_tx.relaxed.cta.shared::cta.b64 [%0], %1;\n" :: "r"(bar2), "r"(3 * 21 * 128) : "memory");
                    mbar_arrive_expect_tx(bar, bar2 != bar ? 3 * 28 * 128 : 3 * XCH);
                }
                if (SDEF == 4 && k >= 0 && k + 4 < nwin) {
                    const int t1 = (TOK * (k + 1) - 1) >> 6;
                    mbar_wait(bars + B_QKRAW + (t1 & 3) * 8, (t1 >> 2) & 1);
                    asm volatile("st.volatile.shared.v2.b32 [%0], {%1, %2};\n" :: "r"(bars + B_PROG + 8), "r"(k), "r"(clock32()) : "memory");
                }
                if (k >= 0 && k + 4 < nwin && wh < NWS - 1) {
                    const int x0 = 7 * ww + 3, y0 = 7 * wh + 3, x1 = ww == NWS - 1 ? 0 : x0 + 4;
                    asm volatile("bar.sync %0, 160;\n"
                                 "cp.async.bulk.tensor.3d.shared::cluster.global.mbarrier::complete_tx::bytes [%1], [%7, {%14, %11, %13}], [%9];\n"
                                 "cp.async.bulk.tensor.3d.shared::cluster.global.mbarrier::complete_tx::bytes [%2], [%7, {%15, %11, %13}], [%9];\n"
                                 "cp.async.bulk.tensor.3d.shared::cluster.global.mbarrier::complete_tx::bytes [%3], [%7, {%16, %11, %13}], [%9];\n"
                                 "cp.async.bulk.tensor.3d.shared::cluster.global.mbarrier::complete_tx::bytes [%4], [%8, {%14, %12, %13}], [%10];\n"
                                 "cp.async.bulk.tensor.3d.shared::cluster.global.mbarrier::complete_tx::bytes [%5], [%8, {%15, %12, %13}], [%10];\n"
                                 "cp.async.bulk.tensor.3d.shared::cluster.global.mbarrier::complete_tx::bytes [%6], [%8, {%16, %12, %13}], [%10];\n"
                                 :: "r"(NB_QKFREE + (k & 1) + (EXD ? __umulhi(__umulhi((x0 | y0 | x1) + dst, bar2), bar) : 0)), "r"(dst), "r"(dst + QK_CHUNK), "r"(dst + 2 * QK_CHUNK), "r"(dst + 28 * 128),
                                    "r"(dst + QK_CHUNK + 28 * 128), "r"(dst + 2 * QK_CHUNK + 28 * 128),
                                    "l"(reinterpret_cast<uint64_t>(&M.x47)), "l"(reinterpret_cast<uint64_t>(&M.x37)), "r"(bar), "r"(bar2),
                                    "r"(x0), "r"(x1), "r"(y0), "r"(0), "r"(64), "r"(128) : "memory");
                } else {
                if (NB & 1) {
                    if (k >= 0) nb_sync<160>(NB_QKFREE + (k & 1));
                } else mbar_wait(bars + B_QKFREE + (k & 3) * 8, (k >> 2) & 1);
                if (!EXH && alone && !done) mbar_arrive(bar);
                if (k + 4 >= nwin && k >= 0) {
                    mbar_arrive(bar);
                    continue;
                }
                TR(20, k + 4);
                if (k < 0) TP(44 + k);
                if (!done) load_x(dst, bar, bar2, wh, ww);
                }
                TR(25, k + 4);
                asm volatile("st.volatile.shared.b32 [%0], %1;\n" :: "r"(bars + B_PROG), "r"(max(k + 1, 0)) : "memory");
                if (NOPF || (PFM >= 7 && k > 0)) {
                } else if (PFM == 6) {
                    npf++;
                    const int t1 = (TOK * (k + 2) - 1) >> 6;
                    if (half == 0 && (k < 0 || npf > 2 || !mbar_test(bars + B_QKRAW + (t1 & 3) * 8, (t1 >> 2) & 1))) {
#pragma unroll 1
                        for (; npf > 0; npf--) {
                            if (pr2 < NWS)
                                asm volatile("cp.async.bulk.prefetch.tensor.3d.L2.global.tile [%0, {%1, %2, %3}];\n"
                                             :: "l"(reinterpret_cast<uint64_t>(&xmap)), "r"(0), "r"(7 * unrot(pq2) + 3), "r"(7 * unrot(pr2) + 3) : "memory");
                            pq2 += wstep; if (pq2 >= NWS) { pq2 -= NWS; pr2++; }
                        }
                    }
                } else if (PFM == 2) {
                    if (pr2 < NWS && half == 0) {
                        const char* xp = reinterpret_cast<const char*>(P.x) + (size_t)((7 * ph2 + 3) * IMG + 7 * pw2 + 3) * 384;
#pragma unroll 1
                        for (int r = 0; r < (ph2 == NWS - 1 ? 3 : 7); r++)
                            asm volatile("cp.async.bulk.prefetch.L2.global [%0], 2688;\n" :: "l"(xp + r * (IMG * 384)) : "memory");
                    }
                } else if (PFM == 1 ? ((k ^ half) & 1) : PFM == 4 ? half == 1 : PFM == 5 ? 1 : half == 0) {
                    if (pr2 < NWS) {
#pragma unroll
                        for (int ch = 0; ch < (PF1 ? 1 : 3); ch++)
                            if (CH & 8)
                            asm volatile("cp.async.bulk.prefetch.tensor.3d.L2.global.tile.L2::cache_hint [%0, {%1, %2, %3}], %4;\n"
                                         :: "l"(reinterpret_cast<uint64_t>(&xmap)), "r"(ch * 64), "r"(7 * pw2 + 3), "r"(7 * ph2 + 3), "l"(EVICT_FIRST)
                                         : "memory");
                            else
                            asm volatile("cp.async.bulk.prefetch.tensor.3d.L2.global.tile [%0, {%1, %2, %3}];\n"
                                         :: "l"(reinterpret_cast<uint64_t>(&xmap)), "r"(ch * 64), "r"(7 * pw2 + 3), "r"(7 * ph2 + 3)
                                         : "memory");
                    }
                }
                wq += wstep; if (wq >= NWS) { wq -= NWS; wr++; }
                if (PFM != 6) { pq2 += wstep; if (pq2 >= NWS) { pq2 -= NWS; pr2++; } }
            }
            mbar_wait(bars + B_VRAW + ((ntiles - 1) & 3) * 8, ((ntiles - 1) >> 2) & 1);
          }
            PROJ_SCHEDULE
            int st = 0, ready = -1;
            uint32_t ph = 1;
#pragma unroll 1
            for (int t = tile0; t < tend; t += tstep) {
                const int p0 = (t < TILES_A) ? SEG_B + 64 * t : 64 * (t - TILES_A);
                const int w1 = (t < TILES_A) ? 0 : min((p0 + 63 + 4 * IMG) / (7 * IMG), NWS - 1);
                if (bid < 2 * (PQ(npair) + PQ(nh)) && t == tile0 + tstep) {
                    mbar_wait(sbase + SM_PBAR + 96, 0);
                    fence_async_smem();
                }
                if (ready < w1) {
                    ready = max(ready, w1 - 2);
#pragma unroll 1
                    while (ready < w1) {
                        ready++;
#pragma unroll 1
                        for (uint32_t n = 0; n < (1u << 22); n++) {
                            uint32_t a;
                            asm volatile("ld.acquire.gpu.global.u32 %0, [%1];\n" : "=r"(a) : "l"(g_cnt + ready) : "memory");
                            if (a >= PQ(need)) break;
                            __nanosleep(64);
                        }
                    }
                    asm volatile("fence.proxy.async.global;\n" ::: "memory");
                }
                TRH(9, (t - tile0) / tstep);
                mbar_wait_s<(HS & 4) != 0>(sbase + SM_PBAR + 48 + st * 8, ph);
                TRH(5, (t - tile0) / tstep);
                if (PEXP & 2) mbar_arrive(sbase + SM_PBAR + st * 8); else {
                mbar_arrive_expect_tx(sbase + SM_PBAR + st * 8, STAGE_BYTES);
#pragma unroll
                for (int ch = 0; ch < 3; ch++)
                    tma_2d(sbase + SM_STAGE + st * STAGE_BYTES + ch * 8192, &omap, sbase + SM_PBAR + st * 8, ch * 64, (PEXP & 4) ? p0 & 8191 : p0);
                }
                if (++st == 6) { st = 0; ph ^= 1; }
            }
            finish(nfinish);
        } else if (!attn) {
        } else if (warp == 1) {
          {
            if (PQ(t1) < TILES) {
#pragma unroll 1
                for (uint32_t n = 0; n < (1u << 22); n++) {
                    uint32_t a;
                    asm volatile("ld.acquire.gpu.global.u32 %0, [%1];\n" : "=r"(a) : "l"(g_cnt + NWS) : "memory");
                    if (a) break;
                    __nanosleep(64);
                }
                asm volatile("fence.proxy.async.global;\n" ::: "memory");
                if (blockIdx.x % 6 == 0)
                    asm volatile("cp.async.bulk.prefetch.L2.global [%0], 4096;\n" :: "l"(g_wo + blockIdx.x / 6 % 18 * 4096) : "memory");
                if (NB & 4) mbar_wait(bars + B_QKRAW, 0);
                else mbar_wait(bars + B_QKRAW + ((ntiles - 1) & 3) * 8, ((ntiles - 1) >> 2) & 1);
                mbar_arrive_expect_tx(bars + B_WRAW, 73728);
#pragma unroll
                for (int i = 0; i < 4; i++) {
                    const uint32_t o = ((i + pair) & 3) * 18432;
                    asm volatile("cp.async.bulk.shared::cluster.global.mbarrier::complete_tx::bytes [%0], [%1], 18432, [%2];\n"
                                 :: "r"(sbase + SM_WO + o), "l"(g_wo + o), "r"(bars + B_WRAW) : "memory");
                }
            }
            finish(nfinish);
          }
        } else if (warp == 2) {
            int wh = wr0, ww = wq0, nb = wr0 + 1, k = 0;
#pragma unroll 1
            for (int j = 0; k < nwin; j++) {
                mbar_wait_s<HS & 1>(bars + B_STORED + (j & 1) * 8, (j >> 1) & 1);
                mbar_arrive(bars + B_PUBD + (j & 1) * 8);
                if (PUBM != 1) asm volatile("fence.release.gpu;\n" ::: "memory");
#pragma unroll 1
                for (; wh < nb && k < nwin; k++) {
                    asm volatile("red.relaxed.gpu.global.add.u32 [%0], 1;\n" :: "l"(g_cnt + wh) : "memory");
                    ww += wstep; if (ww >= NWS) { ww -= NWS; wh++; }
                }
                nb = wh >= PBE ? wh + 1 : (wh | 1) + 1;
            }
            TC(7);
            finish(nfinish);
        } else {
            for (int t = 0; t < 2; t++) mbar_arrive_n(bars + B_VFREE + t * 8, M01 == 2 ? 2 - t : 2);
            int wr = wr0, wq = wq0, nb = wr0 + 1, j = 0, npf = 0, tprev = 0;
            int pr2 = (w0 + (PF_DIST + 5) * wstep) / NWS, pq2 = w0 + (PF_DIST + 5) * wstep - pr2 * NWS;
#pragma unroll 1
            for (int k = 0; k < nwin; k++) {
                const uint32_t src = sbase + SM_V + (k & 3) * V_STRIDE;
                const int wh = unrot(wr), ww = unrot(wq);
                const int x0 = 7 * ww + 3, y0 = 7 * wh + 3;
                if (NB & 2) nb_sync<160>(NB_ODONE + (k & 3));
                else mbar_wait_s<(HS & 2) != 0>(bars + B_ODONE + (k & 3) * 8, (k >> 2) & 1);
                if (SDEF) {
                    const int t1 = (TOK * (k + 2) - 1) >> 6, t2 = (TOK * (k + 3) - 1) >> 6;
                    int need = 0;
                    if (SDEF == 4) {
                        int tag, tq;
                        asm volatile("ld.volatile.shared.v2.b32 {%0, %1}, [%2];\n" : "=r"(tag), "=r"(tq) : "r"(bars + B_PROG + 8) : "memory");
                        const int now = clock32();
                        if (tag == k + 1 && now - tq > STH && now - tprev > STH + STP) need = k + 2;
                        tprev = now;
                    } else
                    if (SDEF == 3 || mbar_test(bars + B_QKRAW + (t1 & 3) * 8, (t1 >> 2) & 1)) need = k + 2;
                    if (SDEF == 2 && mbar_test(bars + B_QKRAW + (t2 & 3) * 8, (t2 >> 2) & 1)) need = k + 3;
                    need = min(need, nwin - 4);
#pragma unroll 1
                    for (int n = 0; n < 4096; n++) {
                        int done;
                        asm volatile("ld.volatile.shared.b32 %0, [%1];\n" : "=r"(done) : "r"(bars + B_PROG) : "memory");
                        if (done >= need) break;
                        __nanosleep(SDN);
                    }
                }
                fence_async_smem();
                TR(22, k);
                const int x1 = ww == NWS - 1 ? 0 : x0 + 4;
                if (!(XP & 2)) tma_store_4d(&M.s47, src, 0, half, x0, y0);
                if (!(XP & 2)) tma_store_4d(&M.s37, src + 28 * O_PITCH, 0, half, x1, y0);
                if (wh == NWS - 1) {
                    tma_store_4d(&M.s43, src + 16 * O_PITCH, 0, half, x0, 0);
                    tma_store_4d(&M.s33, src + 40 * O_PITCH, 0, half, x1, 0);
                }
                asm volatile("cp.async.bulk.commit_group;\n" ::: "memory");
                if (PFM >= 7) {
                    npf++;
                    const int t2 = (TOK * (k + 3) - 1) >> 6;
                    if (half == 0 && (PFM == 8 || npf > 2 || !mbar_test(bars + B_QKRAW + (t2 & 3) * 8, (t2 >> 2) & 1))) {
#pragma unroll 1
                        for (; npf > 0; npf--) {
                            if (pr2 < NWS && k + PF_DIST + 6 - npf < nwin)
                                asm volatile("cp.async.bulk.prefetch.tensor.3d.L2.global.tile [%0, {%1, %2, %3}];\n"
                                             :: "l"(reinterpret_cast<uint64_t>(&xmap)), "r"(0), "r"(7 * unrot(pq2) + 3), "r"(7 * unrot(pr2) + 3) : "memory");
                            pq2 += wstep; if (pq2 >= NWS) { pq2 -= NWS; pr2++; }
                        }
                    }
                }
                asm volatile("cp.async.bulk.wait_group.read 0;\n" ::: "memory");
                {
                    const int row0 = (k + 4) * TOK;
                    mbar_arrive_n(bars + B_VFREE + ((row0 >> 6) & 3) * 8, ((row0 & 63) >= 64 - TOK && (row0 & 63) < TOK) ? 2 : 1);
                }
                TR(23, k);
                if (k == nwin - 1) mbar_arrive(sbase + SM_PBAR + 96);
                wq += wstep; if (wq >= NWS) { wq -= NWS; wr++; }
                if (wr >= nb || k == nwin - 1) {
                    nb = wr >= PBE ? wr + 1 : (wr | 1) + 1;
                    asm volatile("cp.async.bulk.wait_group 0;\n" ::: "memory");
                    if (WFEN) asm volatile("fence.proxy.async.global;\n" ::: "memory");
                    mbar_wait(bars + B_PUBD + (j & 1) * 8, ((j >> 1) + 1) & 1);
                    mbar_arrive(bars + B_STORED + (j & 1) * 8);
                    j++;
                }
            }
        }
        if (PSTORE && warp == 1) {
            PROJ_SCHEDULE
            int st = 0, prev = -1;
            uint32_t ph = 0;
#pragma unroll 1
            for (int t = tile0; t < tend; t += tstep) {
                const int p0 = (t < TILES_A) ? SEG_B + 64 * t : 64 * (t - TILES_A);
                mbar_wait_s<(HS & 4) != 0>(sbase + SM_PBAR + 104 + st * 8, ph);
                fence_async_smem();
#pragma unroll
                for (int ch = 0; ch < ((PEXP & 1) ? 0 : 3); ch++)
                    if (CH & 1)
                    asm volatile("cp.async.bulk.tensor.2d.global.shared::cta.tile.bulk_group.L2::cache_hint [%0, {%2, %3}], [%1], %4;\n"
                                 :: "l"(reinterpret_cast<uint64_t>(t < TILES_A ? &omap : &omapb)),
                                    "r"(sbase + SM_STAGE + st * STAGE_BYTES + ch * 8192), "r"(ch * 64), "r"(p0), "l"(EVICT_FIRST) : "memory");
                    else
                    asm volatile("cp.async.bulk.tensor.2d.global.shared::cta.tile.bulk_group [%0, {%2, %3}], [%1];\n"
                                 :: "l"(reinterpret_cast<uint64_t>(t < TILES_A ? &omap : &omapb)),
                                    "r"(sbase + SM_STAGE + st * STAGE_BYTES + ch * 8192), "r"(ch * 64), "r"((PEXP & 8) ? (p0 & 8191) + 16384 : p0) : "memory");
                asm volatile("cp.async.bulk.commit_group;\n" ::: "memory");
                TRH(6, (t - tile0) / tstep);
                if (prev >= 0) {
                    asm volatile("cp.async.bulk.wait_group.read 1;\n" ::: "memory");
                    mbar_arrive(sbase + SM_PBAR + 48 + prev * 8);
                    TRH(21, (t - tile0) / tstep - 1);
                }
                prev = st;
                if (++st == 6) { st = 0; ph ^= 1; }
            }
            if (ENDR) asm volatile("cp.async.bulk.wait_group.read 0;\n" ::: "memory");
            else asm volatile("cp.async.bulk.wait_group 0;\n" ::: "memory");
            TR(30, 0);
            TC(1);
        }
        return;
    }
    auto permute = [&](int i0, int i1) {
            uint32_t src[3][4], dst[3];
#pragma unroll
            for (int it = 0; it < 3; it++) {
                const int o = warp * 12 + it * 4 + (lane >> 3), r = (o / 6) * 8 + (lane & 7), u = o % 6;
#pragma unroll
                for (int h = 0; h < (GORD == 2 ? 0 : 2); h++) {
                    const int v = u + 6 * h + 4 * half;
                    const bool wide = v >> 3 == half;
                    src[it][h] = wide ? r * 128 + (((v ^ r) & 7) << 4) : 16384 + r * 64 + (((v ^ (r >> 1)) & 3) << 4);
                    src[it][2 + h] = src[it][h] + (wide ? 8192 : 4096);
                }
                dst[it] = sbase + u * 4096 + r * 32 + ((lane >> 2) & 1) * 16;
            }
            TP(16);
#pragma unroll 1
            for (int i = i0; i < i1; i++) {
                uint4 w[3][4];
                mbar_wait(bars + B_WRAW + 16 - 8 * i, 0);
                TP(20 + i);
#pragma unroll
                for (int it = 0; it < 3; it++)
#pragma unroll
                    for (int m = 0; m < 4; m++) w[it][m] = *reinterpret_cast<const uint4*>(smem + src[it][m] + i * 24576);
                wg_bar(PPAR ? 12 + wg : 7);
#pragma unroll
                for (int it = 0; it < 3; it++) {
                    const uint32_t d = dst[it] + i * 24576;
                    sts128(d, w[it][0].x, w[it][1].x, w[it][2].x, w[it][3].x);
                    sts128(d ^ 16, w[it][0].y, w[it][1].y, w[it][2].y, w[it][3].y);
                    sts128(d + 2048, w[it][0].z, w[it][1].z, w[it][2].z, w[it][3].z);
                    sts128((d ^ 16) + 2048, w[it][0].w, w[it][1].w, w[it][2].w, w[it][3].w);
                }
            }
        };
    if (PPAR && attn) {
        permute(wg, wg + 1);
        if (wg) nb_arrive<384>(15);
    }
    if (!attn) {
        asm volatile("setmaxnreg.inc.sync.aligned.u32 160;\n");
    } else if (wg == 0) {
        if (!PPAR) permute(0, 3);
        asm volatile("setmaxnreg.inc.sync.aligned.u32 %0;\n" :: "n"(REG_G));
        float qs = 1.f;
        if (GORD == 2 || c < 2) qs = round_bf16(expf(round_bf16(fminf(fmaxf(bf16lo(ls), -100.f), 4.6052f)))) * LOG2E;
        uint32_t xa[12][4];
        float accA[48], accB[48], accV[48];
        uint32_t rho = warp * 16 + (lane & 15), rq = warp * 16 + g;
        uint32_t hi = lane >> 4, lane0 = lane == 0, c2 = 2 * c;
        asm volatile("" : "+r"(hi), "+r"(lane0), "+r"(c2));
        auto row_addr = [&](uint32_t (&ax)[4], uint32_t r) {
            ax[0] = sbase + SM_QK + r * 128 + (((r & 7) ^ hi) << 4);
#pragma unroll
            for (int i = 1; i < 4; i++) ax[i] = ax[0] ^ (32 * i);
        };
#define XADDR(ax, s) ((ax)[((s) & 3) ^ (((s) >> 1) & 2)] + ((s) >> 2) * QK_CHUNK)
        uint64_t descW = make_desc(sbase, 2048, 256, 3);
        const uint32_t zero = (uint32_t)P.z1;
        const uint32_t vbase = sbase + SM_V + (lane >> 4) * GRP;
        const uint32_t ones = 0x3F803F80u, ones2 = ones;
        TP(10);
        {
            uint32_t ax[4];
            row_addr(ax, rho);
            mbar_wait(bars + B_XFULL, 0);
#pragma unroll
            for (int s = 0; s < 12; s++) ldsm_x4(xa[s], XADDR(ax, s));
        }
        TP(8);
        if (PPAR) nb_sync<384>(15); else wg_bar(7);
        fence_async_smem();
        TP(9);
        wgmma_fence();
        mma_qkv_a<SM_WA, 0>(accA, xa, descW);
        mma_qkv_b<SM_WA, KLO>(accA, xa, descW);
        wgmma_commit();
        mma_qkv_a<SM_WB, 0>(accB, xa, descW);
        wgmma_commit();
        TP(11);
        mbar_wait(bars + B_WFULL, 0);
        TP(12);
        if (tid == 0) TC(3);
        const int nt = (int)blockIdx.x < 2 * PQ(npair) ? ((int)blockIdx.x < PQ(nr2) ? PQ(nt1) : PQ(nt0)) : ((int)blockIdx.x < PQ(hr2) ? PQ(ht1) : PQ(ht0));
        for (int t = 0; t < nt; t++) {
            descW += P.z1;
            float ss[4];
            uint32_t pk[2][24];
            wgmma_wait<1>();
            reg_fence(accA);
            TR(0, t);
            TA(1, 0);
            if (t < 12 && (t < 4 || (t & 1))) TP(t < 4 ? 32 + t : 34 + (t >> 1));
#pragma unroll
            for (int i = 0; i < 4; i++) ss[i] = accA[i] * accA[i];
#pragma unroll
            for (int i = 4; i < 48; i++) ss[i & 3] = fmaf(accA[i], accA[i], ss[i & 3]);
            mma_qkv_b<SM_WB, KLO>(accB, xa, descW);
            wgmma_commit();
            TA(1, 1);
            sched_fence(zero, __float_as_uint(ss[0]), __float_as_uint(ss[1]), __float_as_uint(ss[2]), __float_as_uint(ss[3]));
#pragma unroll
            for (int j = 0; j < 12; j++) {
                pk[0][j] = pack_bf16(accA[4 * j], accA[4 * j + 1]);
                pk[1][j] = pack_bf16(accA[4 * j + 2], accA[4 * j + 3]);
                asm volatile("" : "+r"(pk[0][j]), "+r"(pk[1][j]));
            }
            wgmma_fence();
            if (V64) mma_w_a<0, 0>(accV, xa, descW + D_WV64); else mma_v_a<D_WV, 0>(accV, xa, descW);
            wgmma_commit();
            TA(1, 2);
            uint32_t av = vbase + rho * 16 + ((rho * 1338) >> 16) * (V_STRIDE - GRP);
            uint32_t aq[2];
            aq[0] = sbase + SM_QK + rq * 128 + (((rq & 7) ^ c2) << 4);
            aq[1] = aq[0] + 1024;
            if (rq >= 4 * TOK - 8) aq[1] = (aq[1] - QK_CHUNK) ^ 64;
            rho += 64;
            if (rho >= 4 * TOK) rho -= 4 * TOK;
            rq += 64;
            if (rq >= 4 * TOK) rq -= 4 * TOK;
            uint32_t an[4];
            row_addr(an, rho);
            const uint32_t bt = bars + (t & 3) * 8, pt = (t >> 2) & 1, bn = bars + ((t + 1) & 3) * 8, pn = ((t + 1) >> 2) & 1;
            uint32_t xok;
            wgmma_wait<1>();
            reg_fence(accB);
            TA(1, 3);
#pragma unroll
            for (int i = 0; i < 48; i++) ss[i & 3] = fmaf(accB[i], accB[i], ss[i & 3]);
            ss[0] += ss[1]; ss[2] += ss[3];
            if (V64) mma_w_b<0, KLO>(accV, xa, descW + D_WV64); else mma_v_b<D_WV, KLO>(accV, xa, descW);
            wgmma_commit();
            TA(1, 4);
            sched_fence(zero, __float_as_uint(ss[0]), __float_as_uint(ss[2]), av, aq[0], aq[1], an[0], an[1], an[2], an[3], rho, rq);
            const float f0 = rsqrt_ftz(ss[0] + 1e-12f) * qs, f1 = rsqrt_ftz(ss[2] + 1e-12f) * qs;
            const uint32_t f2[2] = {pack_bf16(f0, f0), pack_bf16(f1, f1)};
#pragma unroll
            for (int j = 0; j < 12; j++) {
                pk[0][12 + j] = (FM & 1) ? pack_bf16(accB[4 * j] * f0, accB[4 * j + 1] * f0) : pack_bf16(accB[4 * j], accB[4 * j + 1]);
                pk[1][12 + j] = (FM & 1) ? pack_bf16(accB[4 * j + 2] * f1, accB[4 * j + 3] * f1) : pack_bf16(accB[4 * j + 2], accB[4 * j + 3]);
            }
            auto qk_store = [&](int u0, int u1) {
#pragma unroll
                for (int u = u0; u < u1; u++)
#pragma unroll
                    for (int r = 0; r < 2; r++)
                        if ((FM & 1) && u >= 3)
                        sts128((aq[r] ^ ((u & 1) * 16 + (u & 2) * 32)) + (u >> 1) * QK_CHUNK, pk[r][4 * u], pk[r][4 * u + 1], pk[r][4 * u + 2], pk[r][4 * u + 3]);
                        else
                        sts128((aq[r] ^ ((u & 1) * 16 + (u & 2) * 32)) + (u >> 1) * QK_CHUNK,
                               hmul2_bf16(pk[r][4 * u], f2[r]), hmul2_bf16(pk[r][4 * u + 1], f2[r]),
                               hmul2_bf16(pk[r][4 * u + 2], f2[r]), hmul2_bf16(pk[r][4 * u + 3], f2[r]));
            };
            qk_store(0, XPOS - 1);
            xok = mbar_test(bn + B_XFULL, pn);
            qk_store(XPOS - 1, QSPLIT);
            if (EARLYQ) {
                __syncwarp();
                mbar_arrive_if(bt + B_QKRAW, lane0);
            }
            TR(1, t);
            TA(1, 5);
            mbar_wait_unless(xok, bn + B_XFULL, pn);
            TR(2, t);
            wgmma_wait<1>();
            TA(1, 6);
#pragma unroll
            for (int s = 0; s < KLO; s++) ldsm_x4(xa[s], XADDR(an, s));
            qk_store(QSPLIT, 6 - QPOST);
            if (QPOST) {
                wgmma_fence();
                mma_qkv_a<SM_WA, 0>(accA, xa, descW);
                wgmma_commit();
                qk_store(6 - QPOST, 6);
            }
            if (!EARLYQ) {
                __syncwarp();
                mbar_arrive_if(bt + B_QKRAW, lane0);
            }
            TR(3, t);
            TA(1, 7);
            if (!QPOST) {
                wgmma_fence();
                mma_qkv_a<SM_WA, 0>(accA, xa, descW);
                wgmma_commit();
            }
            TA(1, 8);
            wgmma_wait<1>();
            reg_fence(accV);
            TA(1, 9);
#pragma unroll
            for (int s = KLO; s < 12; s++) ldsm_x4(xa[s], XADDR(an, s));
            const uint32_t vok = mbar_test(bt + B_VFREE, pt);
            uint32_t vp[24];
#pragma unroll
            for (int j = 0; j < 24; j++) vp[j] = pack_bf16(accV[2 * j], accV[2 * j + 1]);
            reg_fence(vp);
            wgmma_fence();
            mma_qkv_b<SM_WA, KLO>(accA, xa, descW);
            wgmma_commit();
            TA(1, 10);
            mbar_wait_unless(vok, bt + B_VFREE, pt);
#pragma unroll
            for (int p = 0; p < 6; p++)
                stsm_x4(av + (p < 3 ? 2 * p : 2 * p + 1) * GRP, vp[4 * p], vp[4 * p + 1], vp[4 * p + 2], vp[4 * p + 3]);
            stsm_x2(av + 6 * GRP, ones, ones2);
            __syncwarp();
            mbar_arrive_if(bt + B_VRAW, lane0);
            TR(4, t);
            if (MERGEW != 1) wgmma_fence();
            mma_qkv_a<SM_WB, 0>(accB, xa, descW);
            wgmma_commit();
            TA(1, 11);
        }
        TAEND(1);
        wgmma_wait<0>();
        reg_fence(accA);
        reg_fence(accB);
        asm volatile("setmaxnreg.dec.sync.aligned.u32 160;\n");
    } else {
        if (REG_A > 128) asm volatile("setmaxnreg.inc.sync.aligned.u32 %0;\n" :: "n"(REG_A));
        {
            const float c0 = bf16lo(rc), c1 = bf16hi(rc);
            float a0 = 0.f, a1 = 0.f;
#pragma unroll
            for (int u = 0; u < 16; u += 2) {
                const uint32_t p = reinterpret_cast<const uint32_t*>(w1)[u >> 1], q = reinterpret_cast<const uint32_t*>(w1)[8 + (u >> 1)];
                uint32_t h;
                asm("cvt.rn.relu.bf16x2.f32 %0, %1, %2;\n" : "=r"(h) : "f"(c0 * bf16hi(p) + c1 * bf16hi(q)), "f"(c0 * bf16lo(p) + c1 * bf16lo(q)));
                a0 += bf16lo(h) * bf16lo(w2[u]);
                a1 += bf16lo(h) * bf16hi(w2[u]);
                a0 += bf16hi(h) * bf16lo(w2[u + 1]);
                a1 += bf16hi(h) * bf16hi(w2[u + 1]);
            }
            const float s0 = round_bf16(__fdividef(1.f, 1.f + expf(-round_bf16(a0))));
            const float s1 = round_bf16(__fdividef(1.f, 1.f + expf(-round_bf16(a1))));
            if (tid - 128 < 169) sts32(sbase + SM_TAB + (tid - 128) * 4, pack_bf16(exp2f(fmaf(s0, 16.f * LOG2E, -12.f)), exp2f(fmaf(s1, 16.f * LOG2E, -12.f))));
        }
        asm volatile("bar.sync 1, 256;\n" ::: "memory");
        uint32_t eb[26];
        {
            const uint32_t* tab = reinterpret_cast<const uint32_t*>(smem + SM_TAB);
#pragma unroll
            for (int i = 0; i < 13; i++) {
                const uint32_t lo = tab[min(ridx[i < 12 ? 13 * (i & 1) + (i & ~1) : 12], 168u)];
                const uint32_t hi = tab[min(ridx[i < 12 ? 13 * (i & 1) + (i | 1) : 25], 168u)];
                eb[i]      = prmt(lo, hi, 0x5410);
                eb[13 + i] = prmt(lo, hi, 0x7632);
            }
            if (c != 0) eb[12] = eb[25] = 0;
            if (EBZ) {
                const uint32_t k0 = warp * 16 + g < TOK ? ~0u : 0u, k1 = warp < 3 ? ~0u : 0u;
#pragma unroll
                for (int i = 0; i < 26; i++) eb[i] &= i % 13 == 12 ? (k0 & 0xFFFFu) | (k1 & 0xFFFF0000u) : ((i % 13) & 1) ? k1 : k0;
            }
        }
        uint32_t slow = (bf16lo(ls) <= LS_FAST ? 0 : 1) | (bf16hi(ls) <= LS_FAST ? 0 : 2);
        reg_fence(eb);
        if (SLOWH == 2) sts32(bars + B_PROG + 4, slow);
        wg_bar(3 + wg);
        if ((tid & 127) == 0) mbar_arrive(bars + B_VFREE + 16);
        const uint32_t ov0 = warp * 16 + g < TOK, ov1 = warp < 3;
        const uint64_t descK0 = make_desc(sbase + SM_QK, 16, 1024, 1);
        const uint64_t descV0 = make_desc(sbase + SM_V, 128, GRP, 0);
        slow = __shfl_sync(0xffffffffu, slow, 0);
        const uint32_t barw = bars + (wg - 1) * 8;
        const uint64_t descKw = descK0 + (uint64_t)((wg - 1) * (XCH >> 4)), descVw = descV0 + (uint64_t)((wg - 1) * (V_STRIDE >> 4));
        const uint32_t oa = sbase + SM_V + (wg - 1) * V_STRIDE + (warp * 16 + g) * O_PITCH + c * 48;
        uint32_t qok = 0;
        const uint32_t zero = (uint32_t)P.z1;
        auto window = [&](auto IT_, int k) {
            constexpr int IT = decltype(IT_)::value;
            const uint32_t bar = barw + 16 * IT;
            const int tl = (k * TOK + TOK - 1) >> 6, tn = ((k + 2) * TOK + TOK - 1) >> 6;
            const uint32_t bt = bars + (tl & 3) * 8, pt = (tl >> 2) & 1;
            TR(8, k);
            if (k < 2) TP(44 + k);
            float sc0[28], sc1[28];
            TR(10, k);
            TA(2, 0);
            if (NB & 4) nb_sync<256>(NB_QKRAW + 2 * IT - 1 + wg);
            else mbar_wait_unless(qok, bt + B_QKRAW, pt);
            fence_async_smem();
            TR(11, k);
            TA(2, 1);
            if (k == 0) TP(17);
            wgmma_fence();
            mma_qk0<2 * IT * XCH, 2 * IT * XCH>(sc0, descKw, descKw);
            mma_qk1<2 * IT * XCH, 2 * IT * XCH>(sc1, descKw, descKw);
            wgmma_commit();
            TA(2, 2);
            const uint32_t vok = mbar_test(bt + B_VRAW, pt);
            uint32_t mflag = 1;
            if (!(XP & 1)) asm volatile("ld.volatile.shared.u8 %0, [%1];\n" : "=r"(mflag) : "r"(sbase + SM_FLAG + k) : "memory");
            wgmma_wait<0>();
            reg_fence(sc0);
            reg_fence(sc1);
            if (NB & 1) nb_arrive<160>(NB_QKFREE - 1 + wg);
            else if (lane == 0) mbar_arrive(bar + B_QKFREE);
            TR(12, k);
            TA(2, 3);
            if (k == 0) TP(18);
            if (mflag != 1) {
              asm volatile(
                "{\n.reg .pred p;\n.reg .u32 n;\nmov.u32 n, 0;\n"
                "WAIT_%=:\n"
                "ld.volatile.shared.u8 %0, [%1];\n"
                "setp.ne.u32 p, %0, 0;\n"
                "@p bra DONE_%=;\n"
                "add.u32 n, n, 1;\n"
                "setp.lt.u32 p, n, 16777216;\n"
                "@p bra WAIT_%=;\n"
                "trap;\n"
                "DONE_%=:\n}\n" : "=r"(mflag) : "r"(sbase + SM_FLAG + k) : "memory");
              if (mflag == 2) {
                uint32_t mk[13];
                __threadfence_block();
                uint32_t u = threadIdx.x, bid = blockIdx.x;
                asm volatile("" : "+r"(u), "+r"(bid));
                const uint32_t r0 = ((u >> 1) & 48) + ((u >> 2) & 7);
                const int pr = bid >> 1, wi = pr < PQ(npair) ? PQ(hw) + pr + k * PQ(npair) : pr - PQ(npair) + k * PQ(nh), wr = wi / NWS;
                const uint32_t mp = sbase + SM_MASK + (((unrot(wr) * NWS + unrot(wi - wr * NWS)) * 2) & 15);
                const uint32_t mr[2] = {mp + row_token(min(r0, TOK - 1u)) * (2 * TOK), mp + row_token(min(r0 + 8, TOK - 1u)) * (2 * TOK)};
                const uint32_t c0 = 2 * row_token(2 * (u & 3));
#pragma unroll
                for (int i = 0; i < 13; i++) {
                    const uint32_t a0 = i < 6 ? mr[i & 1] + c0 + 28 * (i >> 1) : i < 12 ? mr[i & 1] + 2 * row_token(2 * (u & 3) + 8 * (i >> 1)) : mr[0] + 2 * TOK - 2;
                    const uint32_t a1 = i < 6 ? a0 + 2 : i < 12 ? mr[i & 1] + 2 * row_token(2 * (u & 3) + 8 * (i >> 1) + 1) : mr[1] + 2 * TOK - 2;
                    uint32_t lo, hi;
                    asm volatile("ld.shared.u16 %0, [%1];\n" : "=r"(lo) : "r"(a0) : "memory");
                    asm volatile("ld.shared.u16 %0, [%1];\n" : "=r"(hi) : "r"(a1) : "memory");
                    mk[i] = prmt(lo, hi, 0x5410);
                }
                reg_fence(mk);
                __syncwarp();
                if (lane == 0) mbar_arrive(bars + B_MCONS);
                uint32_t m0 = mk[0], m1 = mk[1];
#pragma unroll
                for (int i = 2; i < 12; i += 2) { m0 = hmax2_bf16(m0, mk[i]); m1 = hmax2_bf16(m1, mk[i + 1]); }
                m0 = hmax2_bf16(hmax2_bf16(prmt(m0, m1, 0x5410), prmt(m0, m1, 0x7632)), mk[12]);
                m0 = hmax2_bf16(m0, __shfl_xor_sync(0xffffffffu, m0, 1));
                m0 = hmax2_bf16(m0, __shfl_xor_sync(0xffffffffu, m0, 2));
                const float m[2] = {bf16lo(m0), bf16hi(m0)};
#pragma unroll
                for (int i = 0; i < 13; i++) {
                    const float lo = bf16lo(mk[i]) - m[i & 1], hi = bf16hi(mk[i]) - m[i < 12 ? i & 1 : 1];
                    const int j = i < 12 ? 2 * i + 1 : 26;
                    sc0[2 * i] = fmaf(lo, LOG2E, sc0[2 * i]); sc0[j] = fmaf(hi, LOG2E, sc0[j]);
                    sc1[2 * i] = fmaf(lo, LOG2E, sc1[2 * i]); sc1[j] = fmaf(hi, LOG2E, sc1[j]);
                }
              }
            }
            if (slow) {
                auto shift = [&](float (&S)[28], int h) {
                    float m[2];
#pragma unroll
                    for (int i = 12; i >= 0; i--) {
                        uint32_t e = eb[13 * h + i];
                        asm volatile("" : "+r"(e));
                        const float a = S[2 * i] + lg2_ftz(bf16lo(e)), b = S[i < 12 ? 2 * i + 1 : 26] + lg2_ftz(bf16hi(e));
                        if (i == 12) { m[0] = a; m[1] = b; }
                        else m[i & 1] = fmaxf(m[i & 1], fmaxf(a, b));
                    }
#pragma unroll
                    for (int r = 0; r < 2; r++) {
                        m[r] = fmaxf(m[r], __shfl_xor_sync(0xffffffffu, m[r], 1));
                        m[r] = fmaxf(m[r], __shfl_xor_sync(0xffffffffu, m[r], 2));
                    }
#pragma unroll
                    for (int i = 0; i < 27; i++) S[i] -= m[(i >> 1) & 1];
                };
                uint32_t sl = slow;
                if (SLOWH == 2) asm volatile("ld.volatile.shared.u32 %0, [%1];\n" : "=r"(sl) : "r"(bars + B_PROG + 4) : "memory");
                if (!SLOWH || (sl & 1)) shift(sc0, 0);
                if (!SLOWH || (sl & 2)) shift(sc1, 1);
            }
            auto exps = [&](const float (&S)[28], uint32_t (&e)[13]) {
#pragma unroll
                for (int i = 0; i < 12; i++) e[i] = pack_bf16(ex2_ftz(S[2 * i]), ex2_ftz(S[2 * i + 1]));
                e[12] = hmin2_bf16(pack_bf16(ex2_ftz(S[24]), ex2_ftz(S[26])), 0x7F7F7F7Fu);
            };
            auto probs = [&](const uint32_t (&e)[13], int h, uint32_t (&pa)[4][4]) {
#pragma unroll
                for (int i = 0; i < 12; i++) pa[i >> 2][i & 3] = hmul2_bf16(e[i], eb[13 * h + i]);
                const uint32_t l = hmul2_bf16(e[12], eb[13 * h + 12]);
                pa[3][0] = l & 0xFFFFu;
                pa[3][1] = l >> 16;
                pa[3][2] = 0u; pa[3][3] = 0u;
                reg_fence(pa);
            };
            uint32_t pa0[4][4], pa1[4][4], e[13];
            float o0[28], o1[28];
            TR(13, k);
            TA(2, 10);
            if (k == 0) TP(23);
            exps(sc0, e);
            probs(e, 0, pa0);
            TA(2, 4);
            mbar_wait_unless(vok, bt + B_VRAW, pt);
            fence_async_smem();
            TR(14, k);
            TA(2, 5);
            wgmma_fence();
            mma_pv<2 * IT * V_STRIDE, 0>(o0, pa0, descVw);
            wgmma_commit();
            exps(sc1, e);
            reg_fence(e);
            TA(2, 6);
            wgmma_wait<0>();
            reg_fence(o0);
            TA(2, 7);
            sched_fence_rw(zero, e);
            probs(e, 1, pa1);
            wgmma_fence();
            mma_pv<2 * IT * V_STRIDE + 6 * GRP, 0>(o1, pa1, descVw);
            wgmma_commit();
            uint32_t w[24];
            {
                const float il0 = rcp_ftz(o0[24]), il1 = rcp_ftz(o0[26]);
                const uint32_t l0 = pack_bf16(il0, il0), l1 = pack_bf16(il1, il1);
#pragma unroll
                for (int j = 0; j < 12; j++) w[j] = (FM & 2) ? pack_bf16(o0[2 * j] * ((j & 1) ? il1 : il0), o0[2 * j + 1] * ((j & 1) ? il1 : il0)) : hmul2_bf16(pack_bf16(o0[2 * j], o0[2 * j + 1]), (j & 1) ? l1 : l0);
            }
            TA(2, 8);
            wgmma_wait<0>();
            reg_fence(o1);
            TA(2, 9);
            TR(15, k);
            if (k == 0) TP(25);
            wg_bar(3 + wg);
            if (!(NB & 4)) qok = mbar_test(bars + (tn & 3) * 8 + B_QKRAW, (tn >> 2) & 1);
            {
                const float il2 = rcp_ftz(o1[0]), il3 = rcp_ftz(o1[2]);
                const uint32_t l2 = pack_bf16(il2, il2), l3 = pack_bf16(il3, il3);
#pragma unroll
                for (int j = 0; j < 12; j++) w[12 + j] = (FM & 4) ? pack_bf16(o1[2 * j + 4] * ((j & 1) ? il3 : il2), o1[2 * j + 5] * ((j & 1) ? il3 : il2)) : hmul2_bf16(pack_bf16(o1[2 * j + 4], o1[2 * j + 5]), (j & 1) ? l3 : l2);
#pragma unroll
                for (int p = 0; p < 6; p++) {
                    const int j = 8 * (p >> 1) + (p & 1);
                    sts128_if((p & 1) ? ov1 : ov0, oa + 2 * IT * V_STRIDE + (p & 1) * 8 * O_PITCH + (p >> 1) * 16, w[j], w[j + 2], w[j + 4], w[j + 6]);
                }
            }
            if (NB & 2) nb_arrive<160>(NB_ODONE + 2 * IT - 1 + wg);
            else {
                __syncwarp();
                if (lane == 0) mbar_arrive(bar + B_ODONE);
            }
            TR(16, k);
            TA(2, 11);
            if (k < 2) TP(46 + k);
        };
        for (int k = wg - 1;; k += 4) {
            window(std::integral_constant<int, 0>(), k);
            if (k + 2 >= nwin) break;
            window(std::integral_constant<int, 1>(), k + 2);
            if (k + 4 >= nwin) break;
        }
        TAEND(2);
        (void)zero;
        asm volatile("setmaxnreg.inc.sync.aligned.u32 160;\n");
    }

    TR(27, wg);
    if ((tid & 127) == 0) TC(4 + wg);
    if (attn) {
        __syncwarp();
        if (lane == 0) mbar_arrive(sbase + SM_PBAR + 96);
    }
    if (!attn) {
#pragma unroll
        for (int row = tid >> 2; row < 192; row += 96) {
            uint4 w[6];
            const int pr = row % 96, srow = row - pr + (pr % 24) / 12 * 48 + (pr % 12) / 2 * 8 + pr / 24 * 2 + (pr & 1);
#pragma unroll
            for (int a = 0; a < 6; a++) w[a] = *reinterpret_cast<const uint4*>(P.wo + srow * 192 + 32 * a + 8 * c);
            float s = 0.f;
#pragma unroll
            for (int a = 0; a < 6; a++)
                s += ((bf16lo(w[a].x) + bf16hi(w[a].x)) + (bf16lo(w[a].y) + bf16hi(w[a].y))) +
                     ((bf16lo(w[a].z) + bf16hi(w[a].z)) + (bf16lo(w[a].w) + bf16hi(w[a].w)));
            s += __shfl_xor_sync(0xffffffffu, s, 1);
            s += __shfl_xor_sync(0xffffffffu, s, 2);
            s *= (1.f / 192.f);
            const uint32_t d = sbase + SM_WO + row * 64 + ((c ^ ((row >> 1) & 3)) << 4);
#pragma unroll
            for (int a = 0; a < 6; a++)
                sts128(d + a * 12288, pack_bf16(bf16lo(w[a].x) - s, bf16hi(w[a].x) - s), pack_bf16(bf16lo(w[a].y) - s, bf16hi(w[a].y) - s),
                       pack_bf16(bf16lo(w[a].z) - s, bf16hi(w[a].z) - s), pack_bf16(bf16lo(w[a].w) - s, bf16hi(w[a].w) - s));
        }
        fence_async_smem();
        asm volatile("bar.sync 6, 384;\n" ::: "memory");
        if (tid == 0 && (int)blockIdx.x == 2 * (PQ(npair) + PQ(nh))) {
            asm volatile("cp.async.bulk.global.shared::cta.bulk_group [%0], [%1], 73728;\n" :: "l"(g_wo), "r"(sbase + SM_WO) : "memory");
            asm volatile("cp.async.bulk.commit_group;\n" ::: "memory");
            asm volatile("cp.async.bulk.wait_group 0;\n" ::: "memory");
            asm volatile("fence.proxy.async.global;\n" ::: "memory");
            asm volatile("red.release.gpu.global.add.u32 [%0], 1;\n" :: "l"(g_cnt + NWS) : "memory");
        }
        __syncwarp();
    } else if (PQ(t1) < TILES) {
        mbar_wait(sbase + SM_BAR + B_WRAW, 1);
    }
    TR(27, 4 + wg);
    if (tid == 0) TC(2);
    {
        PROJ_SCHEDULE
        uint64_t descW = make_desc(sbase + SM_WO, 12288, 512, 2);
        const uint64_t descA = make_desc(sbase + SM_STAGE + wg * STAGE_BYTES, 16, 1024, 1);
        const uint32_t bar = sbase + SM_PBAR + wg * 8;
        const uint32_t yrel = sbase + SM_STAGE + wg * STAGE_BYTES + (warp * 16 + (lane & 15)) * 128 + (((lane & 7) ^ (lane >> 4)) << 4);
        float acc[96];
#pragma unroll
        for (int i = 0; i < 96; i++) acc[i] = 0.f;
        uint32_t it = 0;
        for (int tile = tile0 + wg * tstep; tile < tend; tile += 3 * tstep, it++) {
            descW += P.z1;
            mbar_wait_s<(HS & 8) != 0>(bar + (it & 1) * 24, (it >> 1) & 1);
            TR(28, it * 3 + wg);
            if (it > 0 || wg > 0) asm volatile("bar.sync %0, 256;\n" :: "r"(8 + wg) : "memory");
            wgmma_fence();
            mma_proj<0, 0>(acc, descA + (uint64_t)((it & 1) * (3 * STAGE_BYTES >> 4)), descW);
            wgmma_commit();
            if (tile + tstep < tend) asm volatile("bar.arrive %0, 256;\n" :: "r"(wg == 2 ? 8 : 9 + wg) : "memory");
            wgmma_wait<0>();
            reg_fence(acc);
            float a[4];
#pragma unroll
            for (int i = 0; i < 4; i++) a[i] = acc[i] * acc[i];
#pragma unroll
            for (int j = 1; j < 24; j++)
#pragma unroll
                for (int i = 0; i < 4; i++) a[i] = fmaf(acc[4 * j + i], acc[4 * j + i], a[i]);
            float s0 = a[0] + a[1], s1 = a[2] + a[3];
            s0 += __shfl_xor_sync(0xffffffffu, s0, 1);
            s1 += __shfl_xor_sync(0xffffffffu, s1, 1);
            s0 += __shfl_xor_sync(0xffffffffu, s0, 2);
            s1 += __shfl_xor_sync(0xffffffffu, s1, 2);
            const float rs0 = rsqrt_ftz(fmaf(s0, 1.f / 192.f, 1e-5f));
            const float rs1 = rsqrt_ftz(fmaf(s1, 1.f / 192.f, 1e-5f));
            const uint32_t ya = yrel + (it & 1) * 3 * STAGE_BYTES;
#pragma unroll
            for (int p = 0; p < 12; p++)
                stsm_x4((ya ^ (32 * (p & 3))) + (p >> 2) * 8192,
                        pack_bf16(acc[8 * p] * rs0, acc[8 * p + 1] * rs0), pack_bf16(acc[8 * p + 2] * rs1, acc[8 * p + 3] * rs1),
                        pack_bf16(acc[8 * p + 4] * rs0, acc[8 * p + 5] * rs0), pack_bf16(acc[8 * p + 6] * rs1, acc[8 * p + 7] * rs1));
            __syncwarp();
            if (lane == 0) mbar_arrive(bar + 104 + (it & 1) * 24);
            TR(29, it * 3 + wg);
        }
    }
}

}

typedef CUresult (*PFN_encodeTiled)(CUtensorMap*, CUtensorMapDataType, cuuint32_t, void*, const cuuint64_t*,
                                    const cuuint64_t*, const cuuint32_t*, const cuuint32_t*, CUtensorMapInterleave,
                                    CUtensorMapSwizzle, CUtensorMapL2promotion, CUtensorMapFloatOOBfill);

extern "C" void kernel_launch(void* const* d_in, const int* in_sizes, int n_in, void* d_out, int out_size) {
    swin::Params P;
    P.x           = (const __nv_bfloat16*)d_in[0];
    P.wqkv        = (const __nv_bfloat16*)d_in[1];
    P.wo          = (const __nv_bfloat16*)d_in[2];
    P.logit_scale = (const __nv_bfloat16*)d_in[3];
    P.cpb_w1      = (const __nv_bfloat16*)d_in[4];
    P.cpb_w2      = (const __nv_bfloat16*)d_in[5];
    P.rel_coords  = (const __nv_bfloat16*)d_in[6];
    P.rel_idx     = (const int*)d_in[7];
    P.mask        = (const __nv_bfloat16*)d_in[8];
    P.out         = (__nv_bfloat16*)d_out;
    P.z1 = 0;
    static PFN_encodeTiled encode = nullptr;
    if (!encode) {
        cudaFuncSetAttribute(swin::swin_window_attn_kernel, cudaFuncAttributeMaxDynamicSharedMemorySize, swin::SM_TOTAL);
        cudaDriverEntryPointQueryResult qr;
        cudaGetDriverEntryPoint("cuTensorMapEncodeTiled", (void**)&encode, cudaEnableDefault, &qr);
    }
    swin::Maps M;
    const cuuint32_t estr[4] = {1, 1, 1, 1};
    auto make = [&](CUtensorMap* m, const void* base, int rank, const cuuint64_t* gdim, const cuuint64_t* gstr,
                    const cuuint32_t* box, CUtensorMapSwizzle swz = CU_TENSOR_MAP_SWIZZLE_128B) {
        CUresult r = encode(m, CU_TENSOR_MAP_DATA_TYPE_BFLOAT16, rank, const_cast<void*>(base), gdim, gstr, box, estr,
               CU_TENSOR_MAP_INTERLEAVE_NONE, swz, CU_TENSOR_MAP_L2_PROMOTION_L2_128B,
               CU_TENSOR_MAP_FLOAT_OOB_FILL_NONE);
        (void)r;
    };
    {
        const cuuint64_t gdim[3] = {192, swin::IMG, swin::IMG}, gstr[2] = {384, swin::IMG * 384};
        const cuuint32_t box[7][3] = {{64, 7, 7}, {64, 4, 7}, {64, 3, 7}, {64, 4, 4}, {64, 4, 3}, {64, 3, 4}, {64, 3, 3}};
        for (int i = 0; i < 7; i++) make(&M.x77 + i, P.x, 3, gdim, gstr, box[i]);
        const cuuint32_t boxp[3] = {192, 7, 7};
        if (PF1) make(&M.x77, P.x, 3, gdim, gstr, boxp, CU_TENSOR_MAP_SWIZZLE_NONE);
    }
    {
        const cuuint64_t gdim[2] = {192, (cuuint64_t)swin::NPIX}, gstr[1] = {384};
        const cuuint32_t box64[2] = {64, 64};
        make(&M.o, d_out, 2, gdim, gstr, box64);
        const cuuint64_t gdimb[2] = {192, (cuuint64_t)swin::SEG_B};
        make(&M.ob, d_out, 2, gdimb, gstr, box64);
    }
    {
        const cuuint64_t gdim[3] = {V64 ? 32 : 16, 192, V64 ? 18 : 36}, gstr[2] = {1152, V64 ? 64 : 32};
        const cuuint32_t box[3] = {V64 ? 32 : 16, 192, V64 ? 3 : 6};
        make(&M.w, P.wqkv, 3, gdim, gstr, box, V64 ? CU_TENSOR_MAP_SWIZZLE_64B : CU_TENSOR_MAP_SWIZZLE_32B);
        const cuuint64_t gdim3[3] = {192, 192, 3}, gstr3[2] = {1152, 384};
        const cuuint32_t box64[3] = {64, 64, 2}, box32[3] = {32, 64, 2};
        make(&M.w64, P.wqkv, 3, gdim3, gstr3, box64);
        make(&M.w32, P.wqkv, 3, gdim3, gstr3, box32, CU_TENSOR_MAP_SWIZZLE_64B);
    }
    {
        const cuuint64_t gdim[4] = {96, 2, swin::IMG, swin::IMG}, gstr[3] = {192, 384, swin::IMG * 384};
        const cuuint32_t box[4][4] = {{96, 1, 4, 7}, {96, 1, 3, 7}, {96, 1, 4, 3}, {96, 1, 3, 3}};
        for (int i = 0; i < 4; i++) make(&M.s47 + i, d_out, 4, gdim, gstr, box[i], CU_TENSOR_MAP_SWIZZLE_NONE);
    }
    swin::swin_window_attn_kernel<<<132, swin::NTHREADS, swin::SM_TOTAL>>>(P, M);
}
```

```cpp
#include <cuda_runtime.h>
#include <cuda.h>
#include <cuda_bf16.h>
#include <stdint.h>
#include <type_traits>

namespace swin {
#define STR_(x) #x
#define STR(x) STR_(x)
#define HINT ""

#define NPAIR 53
#define PF_DIST 3
#define QSPLIT 4
#define CLUSTER 0
#define NOPF 0
#define NTAIL 345
#define PSTORE 1
#define PORDER 1
#define GORD 0
#define GF1 1
#define MERGEW 0
#define MWAIT 0
#define PSLEEP 200
#define CH 5
#define NB 1
#define SCM 0
#define MPF 2
#define MLEAD 4
#define PFM 0
#define PFK 4
#define XP 0
#define KLO 6
#define VPOS 1
#define XSPLIT 1
#define SEQ 1
#define PREL 0
#define PEXP 0
#define PFD 0
#define PFW 1
#define WVK -4
#define WSEQ 1
#define PF1 1
#define WFIRST 1
#define MPRE 1
#define SLOWH 2
#define LS_FAST 4.f
#define ENDR 1
#define EBZ 1
#define HSQ 0
#define AFENCE 0
#define FM 0
#define QPOST 0
#define EARLYQ 0
#define KL 4
#define VB1 4
#define VA0 1
#define K1 3
#define Q1 2
#define RWF 3
#define PUBM 2
#define NH 12
#define HW 29
#define HDEL 0
#define CONSTQ 1
#define V64 1
#define M01 2
#define PPAR 1
#define EPF 0
#define EPW 1
#define HS 0
#define MP2 1
#define SDEF 1
#define EXH 2
#define EXD 1
#define STH 200
#define STP 100
#define LDE 0
#define MD 0
#define COOP 0
#define PVL 0
#define VT 0
#define SDV 0
#define SDN 32
#define XPOS 4
#define PBE 70
#define WFEN 1
#define REG_G 224
#define REG_A 128
#define REG_H 32
constexpr int IMG      = 511;
constexpr int NWS      = 73;
constexpr int NWINDOWS = NWS * NWS;
constexpr int TOK      = 49;
constexpr int NPIX     = IMG * IMG;
constexpr int NTHREADS = 512;

constexpr int W_ATOM = 6144;
constexpr int SM_WA = 0, SM_WB = 6 * 2048, SM_WV = 12 * W_ATOM, D_WV = SM_WV + ((W_ATOM - 2048) << 16);
constexpr int GRP   = TOK * 16;
constexpr int XCH   = TOK * 128;
constexpr int SM_V  = 18 * W_ATOM, V_STRIDE = 10240, O_PITCH = 192;
constexpr int SM_QK = SM_V + 4 * V_STRIDE, QK_CHUNK = 4 * XCH;
constexpr int SM_MASK = SM_QK + 3 * QK_CHUNK;
constexpr int SM_TAB  = SM_V + 3 * V_STRIDE + 256;
constexpr int SM_BAR  = SM_MASK + 4816;
constexpr int B_XFULL = 0, B_WRAW = 32, B_QKRAW = 64, B_QKFREE = 96, B_VFREE = 128, B_ODONE = 160,
              B_PROG = 192, B_VRAW = 224, B_MFULL = 256, B_MCONS = 272, B_WFULL = 280, B_STORED = 288, B_PUBD = 304;
constexpr int SM_FLAG = SM_BAR + 320;
constexpr int SM_A_END = SM_FLAG + 128;
static_assert(SM_QK % 1024 == 0 && 13 * GRP <= V_STRIDE && V_STRIDE % 128 == 0, "layout");
constexpr int SM_WO    = 0;
constexpr int SM_STAGE = 73728;
constexpr int STAGE_BYTES = 24576;
constexpr int SM_PBAR  = SM_A_END;
#define TA(role, idx)
#define TAEND(role)
constexpr int SM_TOTAL = SM_PBAR + 152;
#define TP(idx)
static_assert(SM_STAGE + 6 * STAGE_BYTES <= SM_BAR, "smem");
static_assert(SM_TOTAL <= 232448, "smem");
static_assert(SM_STAGE + 6 * STAGE_BYTES + 3072 <= SM_MASK && NTAIL >= 2 * NPAIR * (COOP + 1) && NTAIL <= 12 * NPAIR, "shared tiles");
static_assert(SM_BAR % 8 == 0 && NWINDOWS / NPAIR < 127, "barrier alignment, flags");

constexpr int SEG_B   = (IMG - 4) * IMG;
constexpr int TILES_A = (NPIX - SEG_B + 63) / 64;
constexpr int TILES   = TILES_A + (SEG_B + 63) / 64;
constexpr uint32_t ROW_DONE = NWS * 2;

__device__ uint32_t g_cnt[NWS + 7];
__device__ __align__(128) uint8_t g_wo[73728];
__device__ uint32_t g_flag[66 * 128];
__device__ uint32_t g_done;

#define TR(ev, idx)
#define TC(slot)
#define TS(i)
#define TRH(ev, idx)
constexpr float LOG2E = 1.4426950408889634f;
__device__ __forceinline__ int clock32() { int c; asm volatile("mov.u32 %0, %%clock;" : "=r"(c) :: "memory"); return c; }

__device__ __forceinline__ uint32_t smem_u32(const void* p) {
    return (uint32_t)__cvta_generic_to_shared(p);
}
__device__ __forceinline__ uint64_t make_desc(uint32_t saddr, uint32_t lbo, uint32_t sbo, uint32_t swz = 0) {
    return (uint64_t)((saddr & 0x3FFFF) >> 4) | ((uint64_t)(lbo >> 4) << 16) | ((uint64_t)(sbo >> 4) << 32) |
           ((uint64_t)swz << 62);
}
__host__ __device__ constexpr uint64_t make_desc_c(uint32_t saddr, uint32_t lbo, uint32_t sbo, uint32_t swz) {
    return (uint64_t)(saddr >> 4) | ((uint64_t)(lbo >> 4) << 16) | ((uint64_t)(sbo >> 4) << 32) | ((uint64_t)swz << 62);
}
constexpr uint64_t D_WV64 = make_desc_c(SM_WV, 12288, 512, 2) - make_desc_c(0, 2048, 256, 3);
__device__ __forceinline__ void wgmma_fence()  { asm volatile("wgmma.fence.sync.aligned;\n" ::: "memory"); }
__device__ __forceinline__ void wgmma_commit() { asm volatile("wgmma.commit_group.sync.aligned;\n" ::: "memory"); }
template <int N> __device__ __forceinline__ void wgmma_wait() {
    asm volatile("wgmma.wait_group.sync.aligned %0;\n" :: "n"(N) : "memory");
}
__device__ __forceinline__ void fence_async_smem() { asm volatile("fence.proxy.async.shared::cta;\n" ::: "memory"); }
template <int N> __device__ __forceinline__ void nb_sync(int id) { asm volatile("bar.sync %0, %1;\n" :: "r"(id), "n"(N) : "memory"); }
template <int N> __device__ __forceinline__ void nb_arrive(int id) { asm volatile("bar.arrive %0, %1;\n" :: "r"(id), "n"(N) : "memory"); }
constexpr int NB_ODONE = 0, NB_QKFREE = 6, NB_QKRAW = 12;
__device__ __forceinline__ void wg_bar(int id) { asm volatile("bar.sync %0, 128;\n" :: "r"(id) : "memory"); }

template <int N> __device__ __forceinline__ void reg_fence(float (&v)[N]) {
#pragma unroll
    for (int i = 0; i < N; i++) asm volatile("" : "+f"(v[i]) :: "memory");
}
template <int N> __device__ __forceinline__ void reg_fence(uint32_t (&v)[N]) {
#pragma unroll
    for (int i = 0; i < N; i++) asm volatile("" : "+r"(v[i]) :: "memory");
}
template <int N, int M> __device__ __forceinline__ void reg_fence(uint32_t (&v)[N][M]) {
#pragma unroll
    for (int i = 0; i < N; i++) reg_fence(v[i]);
}

__device__ __forceinline__ uint32_t pack_bf16(float lo, float hi) {
    uint32_t r;
    asm("cvt.rn.bf16x2.f32 %0, %1, %2;\n" : "=r"(r) : "f"(hi), "f"(lo));
    return r;
}
__device__ __forceinline__ float bf16lo(uint32_t v) { return __uint_as_float(v << 16); }
__device__ __forceinline__ float bf16hi(uint32_t v) { return __uint_as_float(v & 0xFFFF0000u); }
__device__ __forceinline__ uint32_t hadd2_bf16(uint32_t a, uint32_t b) {
    uint32_t r;
    asm("add.rn.bf16x2 %0, %1, %2;\n" : "=r"(r) : "r"(a), "r"(b));
    return r;
}
__device__ __forceinline__ uint32_t hmul2_bf16(uint32_t a, uint32_t b) {
    uint32_t r;
    asm("mul.rn.bf16x2 %0, %1, %2;\n" : "=r"(r) : "r"(a), "r"(b));
    return r;
}
__device__ __forceinline__ uint32_t hsub2_bf16(uint32_t a, uint32_t b) {
    uint32_t r;
    asm("sub.rn.bf16x2 %0, %1, %2;\n" : "=r"(r) : "r"(a), "r"(b));
    return r;
}
__device__ __forceinline__ uint32_t hfma2_bf16(uint32_t a, uint32_t b, uint32_t c) {
    uint32_t r;
    asm("fma.rn.bf16x2 %0, %1, %2, %3;\n" : "=r"(r) : "r"(a), "r"(b), "r"(c));
    return r;
}
__device__ __forceinline__ uint32_t hmax2_bf16(uint32_t a, uint32_t b) {
    uint32_t r;
    asm("max.bf16x2 %0, %1, %2;\n" : "=r"(r) : "r"(a), "r"(b));
    return r;
}
__device__ __forceinline__ uint32_t hmin2_bf16(uint32_t a, uint32_t b) {
    uint32_t r;
    asm("min.bf16x2 %0, %1, %2;\n" : "=r"(r) : "r"(a), "r"(b));
    return r;
}
__device__ __forceinline__ uint32_t ex2_bf16x2(uint32_t a) {
    uint32_t r;
    asm("ex2.approx.ftz.bf16x2 %0, %1;\n" : "=r"(r) : "r"(a));
    return r;
}
__device__ __forceinline__ uint32_t ex2_bf16lo(uint32_t a) {
    uint32_t r;
    asm("{\n.reg .b16 l, h;\nmov.b32 {l, h}, %1;\nex2.approx.ftz.bf16 l, l;\ncvt.u32.u16 %0, l;\n}\n" : "=r"(r) : "r"(a));
    return r;
}
__device__ __forceinline__ uint32_t mbar_test(uint32_t bar, uint32_t parity) {
    uint32_t ok;
    asm volatile("{\n.reg .pred p;\nmbarrier.test_wait.parity.shared::cta.b64 p, [%1], %2;\nselp.u32 %0, 1, 0, p;\n}\n"
                 : "=r"(ok) : "r"(bar), "r"(parity) : "memory");
    return ok;
}
__device__ __forceinline__ uint32_t prmt(uint32_t a, uint32_t b, uint32_t sel) {
    uint32_t r;
    asm("prmt.b32 %0, %1, %2, %3;\n" : "=r"(r) : "r"(a), "r"(b), "r"(sel));
    return r;
}
__device__ __forceinline__ float round_bf16(float x) { return __bfloat162float(__float2bfloat16_rn(x)); }

__device__ __forceinline__ void mbar_init(uint32_t bar, uint32_t count) {
    asm volatile("mbarrier.init.shared::cta.b64 [%0], %1;\n" :: "r"(bar), "r"(count) : "memory");
}
__device__ __forceinline__ void mbar_wait(uint32_t bar, uint32_t parity) {
    asm volatile(
        "{\n"
        ".reg .pred p;\n"
        ".reg .u32 n;\n"
        "mov.u32 n, 0;\n"
        "WAIT_%=:\n"
        "mbarrier.try_wait.parity.shared::cta.b64 p, [%0], %1" HINT ";\n"
        "@p bra DONE_%=;\n"
        "add.u32 n, n, 1;\n"
        "setp.lt.u32 p, n, 4194304;\n"
        "@p bra WAIT_%=;\n"
        "trap;\n"
        "DONE_%=:\n"
        "}\n" :: "r"(bar), "r"(parity) : "memory");
}
template <bool S> __device__ __forceinline__ void mbar_wait_s(uint32_t bar, uint32_t parity) {
    if (!S) mbar_wait(bar, parity);
    else asm volatile(
        "{\n"
        ".reg .pred p;\n"
        ".reg .u32 n;\n"
        "mov.u32 n, 0;\n"
        "WAIT_%=:\n"
        "mbarrier.try_wait.parity.shared::cta.b64 p, [%0], %1, 4000;\n"
        "@p bra DONE_%=;\n"
        "add.u32 n, n, 1;\n"
        "setp.lt.u32 p, n, 262144;\n"
        "@p bra WAIT_%=;\n"
        "trap;\n"
        "DONE_%=:\n"
        "}\n" :: "r"(bar), "r"(parity) : "memory");
}
__device__ __forceinline__ void mbar_wait4(uint32_t b0, uint32_t p0, uint32_t b1, uint32_t p1, uint32_t b2, uint32_t p2,
                                           uint32_t b3, uint32_t p3) {
    asm volatile(
        "{\n"
        ".reg .pred p, q, r, s;\n"
        ".reg .u32 n;\n"
        "mov.u32 n, 0;\n"
        "WAIT_%=:\n"
        "mbarrier.try_wait.parity.shared::cta.b64 p, [%0], %1" HINT ";\n"
        "mbarrier.try_wait.parity.shared::cta.b64 q, [%2], %3" HINT ";\n"
        "mbarrier.try_wait.parity.shared::cta.b64 r, [%4], %5" HINT ";\n"
        "mbarrier.try_wait.parity.shared::cta.b64 s, [%6], %7" HINT ";\n"
        "and.pred p, p, q;\n"
        "and.pred r, r, s;\n"
        "and.pred p, p, r;\n"
        "@p bra DONE_%=;\n"
        "add.u32 n, n, 1;\n"
        "setp.lt.u32 p, n, 4194304;\n"
        "@p bra WAIT_%=;\n"
        "trap;\n"
        "DONE_%=:\n"
        "}\n" :: "r"(b0), "r"(p0), "r"(b1), "r"(p1), "r"(b2), "r"(p2), "r"(b3), "r"(p3) : "memory");
}
__device__ __forceinline__ void mbar_wait2(uint32_t b0, uint32_t p0, uint32_t b1, uint32_t p1) {
    asm volatile(
        "{\n"
        ".reg .pred p, q;\n"
        ".reg .u32 n;\n"
        "mov.u32 n, 0;\n"
        "WAIT_%=:\n"
        "mbarrier.try_wait.parity.shared::cta.b64 p, [%0], %1" HINT ";\n"
        "mbarrier.try_wait.parity.shared::cta.b64 q, [%2], %3" HINT ";\n"
        "and.pred p, p, q;\n"
        "@p bra DONE_%=;\n"
        "add.u32 n, n, 1;\n"
        "setp.lt.u32 p, n, 4194304;\n"
        "@p bra WAIT_%=;\n"
        "trap;\n"
        "DONE_%=:\n"
        "}\n" :: "r"(b0), "r"(p0), "r"(b1), "r"(p1) : "memory");
}
#define HINTA ""
__device__ __forceinline__ void mbar_wait_unless(uint32_t ok, uint32_t bar, uint32_t parity) {
    asm volatile(
        "{\n"
        ".reg .pred p;\n"
        ".reg .u32 n;\n"
        "setp.ne.u32 p, %2, 0;\n"
        "vote.sync.all.pred p, p, 0xffffffff;\n"
        "@p bra DONE_%=;\n"
        "mov.u32 n, 0;\n"
        "WAIT_%=:\n"
        "mbarrier.try_wait.parity.shared::cta.b64 p, [%0], %1" HINTA ";\n"
        "@p bra DONE_%=;\n"
        "add.u32 n, n, 1;\n"
        "setp.lt.u32 p, n, 4194304;\n"
        "@p bra WAIT_%=;\n"
        "trap;\n"
        "DONE_%=:\n"
        "}\n" :: "r"(bar), "r"(parity), "r"(ok) : "memory");
}
__device__ __forceinline__ void mbar_wait2_unless(uint32_t ok, uint32_t b0, uint32_t p0, uint32_t b1, uint32_t p1) {
    asm volatile(
        "{\n"
        ".reg .pred p, q;\n"
        ".reg .u32 n;\n"
        "setp.ne.u32 p, %4, 0;\n"
        "vote.sync.all.pred p, p, 0xffffffff;\n"
        "@p bra DONE_%=;\n"
        "mov.u32 n, 0;\n"
        "WAIT_%=:\n"
        "mbarrier.try_wait.parity.shared::cta.b64 p, [%0], %1" HINT ";\n"
        "mbarrier.try_wait.parity.shared::cta.b64 q, [%2], %3" HINT ";\n"
        "and.pred p, p, q;\n"
        "@p bra DONE_%=;\n"
        "add.u32 n, n, 1;\n"
        "setp.lt.u32 p, n, 4194304;\n"
        "@p bra WAIT_%=;\n"
        "trap;\n"
        "DONE_%=:\n"
        "}\n" :: "r"(b0), "r"(p0), "r"(b1), "r"(p1), "r"(ok) : "memory");
}
__device__ __forceinline__ void mbar_wait4_unless(uint32_t ok, uint32_t b0, uint32_t p0, uint32_t b1, uint32_t p1, uint32_t b2,
                                                  uint32_t p2, uint32_t b3, uint32_t p3) {
    asm volatile(
        "{\n"
        ".reg .pred p, q, r, s;\n"
        ".reg .u32 n;\n"
        "setp.ne.u32 p, %8, 0;\n"
        "vote.sync.all.pred p, p, 0xffffffff;\n"
        "@p bra DONE_%=;\n"
        "mov.u32 n, 0;\n"
        "WAIT_%=:\n"
        "mbarrier.try_wait.parity.shared::cta.b64 p, [%0], %1" HINT ";\n"
        "mbarrier.try_wait.parity.shared::cta.b64 q, [%2], %3" HINT ";\n"
        "mbarrier.try_wait.parity.shared::cta.b64 r, [%4], %5" HINT ";\n"
        "mbarrier.try_wait.parity.shared::cta.b64 s, [%6], %7" HINT ";\n"
        "and.pred p, p, q;\n"
        "and.pred r, r, s;\n"
        "and.pred p, p, r;\n"
        "@p bra DONE_%=;\n"
        "add.u32 n, n, 1;\n"
        "setp.lt.u32 p, n, 4194304;\n"
        "@p bra WAIT_%=;\n"
        "trap;\n"
        "DONE_%=:\n"
        "}\n" :: "r"(b0), "r"(p0), "r"(b1), "r"(p1), "r"(b2), "r"(p2), "r"(b3), "r"(p3), "r"(ok) : "memory");
}
__device__ __forceinline__ void sched_fence(uint32_t zero, uint32_t a, uint32_t b, uint32_t c, uint32_t d, uint32_t e = 0,
                                            uint32_t f = 0, uint32_t g = 0, uint32_t h = 0, uint32_t i = 0, uint32_t j = 0,
                                            uint32_t k = 0) {
    asm volatile("{\n.reg .pred p;\n.reg .u32 n;\nsetp.eq.u32 p, %0, 0;\n@p bra.uni DONE_%=;\nmov.u32 n, %0;\nSPIN_%=:\n"
                 "nanosleep.u32 %1;\nnanosleep.u32 %2;\nnanosleep.u32 %3;\nnanosleep.u32 %4;\nnanosleep.u32 %5;\n"
                 "nanosleep.u32 %6;\nnanosleep.u32 %7;\nnanosleep.u32 %8;\nnanosleep.u32 %9;\nnanosleep.u32 %10;\n"
                 "nanosleep.u32 %11;\nsub.u32 n, n, 1;\nsetp.ne.u32 p, n, 0;\n@p bra.uni SPIN_%=;\nDONE_%=:\n}\n"
                 :: "r"(zero), "r"(a), "r"(b), "r"(c), "r"(d), "r"(e), "r"(f), "r"(g), "r"(h), "r"(i), "r"(j), "r"(k) : "memory");
}
__device__ __forceinline__ void sched_fence2(uint32_t zero, float& x, float& y, uint32_t a, uint32_t b, uint32_t c, uint32_t d = 0,
                                             uint32_t e = 0, uint32_t f = 0) {
    asm volatile("{\n.reg .pred p;\n.reg .u32 n;\nsetp.eq.u32 p, %2, 0;\n@p bra.uni DONE_%=;\nmov.u32 n, %2;\nSPIN_%=:\n"
                 "add.f32 %0, %0, %1;\nadd.f32 %1, %1, %0;\nnanosleep.u32 %3;\nnanosleep.u32 %4;\nnanosleep.u32 %5;\n"
                 "nanosleep.u32 %6;\nnanosleep.u32 %7;\nnanosleep.u32 %8;\n"
                 "sub.u32 n, n, 1;\nsetp.ne.u32 p, n, 0;\n@p bra.uni SPIN_%=;\nDONE_%=:\n}\n"
                 : "+f"(x), "+f"(y) : "r"(zero), "r"(a), "r"(b), "r"(c), "r"(d), "r"(e), "r"(f) : "memory");
}
template <int N> __device__ __forceinline__ void use_regs(const uint32_t* v) {
    if constexpr (N >= 4) {
        asm volatile("nanosleep.u32 %0;\nnanosleep.u32 %1;\nnanosleep.u32 %2;\nnanosleep.u32 %3;\n" :: "r"(v[0]), "r"(v[1]), "r"(v[2]), "r"(v[3]) : "memory");
        use_regs<N - 4>(v + 4);
    } else if constexpr (N > 0) {
        asm volatile("nanosleep.u32 %0;\n" :: "r"(v[0]) : "memory");
        use_regs<N - 1>(v + 1);
    }
}
template <int N> __device__ __forceinline__ void sched_fence_n(uint32_t zero, const uint32_t (&v)[N]) {
    if (__builtin_expect(zero != 0, 0)) {
#pragma unroll 1
        for (uint32_t n = zero; n; n--) use_regs<N>(v);
    }
}
__device__ __forceinline__ void sched_fence_rw(uint32_t zero, uint32_t (&v)[13]) {
    asm volatile("{\n.reg .pred p;\n.reg .u32 n;\nsetp.eq.u32 p, %13, 0;\n@p bra.uni DONE_%=;\nmov.u32 n, %13;\nSPIN_%=:\n"
                 "add.u32 %0, %0, %1;\nadd.u32 %1, %1, %2;\nadd.u32 %2, %2, %3;\nadd.u32 %3, %3, %4;\nadd.u32 %4, %4, %5;\n"
                 "add.u32 %5, %5, %6;\nadd.u32 %6, %6, %7;\nadd.u32 %7, %7, %8;\nadd.u32 %8, %8, %9;\nadd.u32 %9, %9, %10;\n"
                 "add.u32 %10, %10, %11;\nadd.u32 %11, %11, %12;\nadd.u32 %12, %12, %0;\n"
                 "sub.u32 n, n, 1;\nsetp.ne.u32 p, n, 0;\n@p bra.uni SPIN_%=;\nDONE_%=:\n}\n"
                 : "+r"(v[0]), "+r"(v[1]), "+r"(v[2]), "+r"(v[3]), "+r"(v[4]), "+r"(v[5]), "+r"(v[6]), "+r"(v[7]), "+r"(v[8]),
                   "+r"(v[9]), "+r"(v[10]), "+r"(v[11]), "+r"(v[12]) : "r"(zero) : "memory");
}
__device__ __forceinline__ void mbar_arrive(uint32_t bar) {
    asm volatile("mbarrier.arrive.shared::cta.b64 _, [%0];\n" :: "r"(bar) : "memory");
}
__device__ __forceinline__ void mbar_arrive_n(uint32_t bar, uint32_t n) {
    asm volatile("mbarrier.arrive.shared::cta.b64 _, [%0], %1;\n" :: "r"(bar), "r"(n) : "memory");
}
__device__ __forceinline__ void mbar_arrive_expect_tx(uint32_t bar, uint32_t bytes) {
    asm volatile("mbarrier.arrive.expect_tx.shared::cta.b64 _, [%0], %1;\n" :: "r"(bar), "r"(bytes) : "memory");
}
__device__ __forceinline__ void stg128_if(bool p, void* addr, uint32_t x, uint32_t y, uint32_t z, uint32_t w) {
    asm volatile("{\n.reg .pred q;\nsetp.ne.b32 q, %5, 0;\n@q st.global.L1::no_allocate.v4.b32 [%0], {%1, %2, %3, %4};\n}\n"
                 :: "l"(addr), "r"(x), "r"(y), "r"(z), "r"(w), "r"((uint32_t)p) : "memory");
}
__device__ __forceinline__ void stsm_x4(uint32_t addr, uint32_t r0, uint32_t r1, uint32_t r2, uint32_t r3) {
    asm volatile("stmatrix.sync.aligned.m8n8.x4.shared.b16 [%0], {%1, %2, %3, %4};\n"
                 :: "r"(addr), "r"(r0), "r"(r1), "r"(r2), "r"(r3) : "memory");
}
__device__ __forceinline__ void stsm_x2(uint32_t addr, uint32_t r0, uint32_t r1) {
    asm volatile("stmatrix.sync.aligned.m8n8.x2.shared.b16 [%0], {%1, %2};\n" :: "r"(addr), "r"(r0), "r"(r1) : "memory");
}
__device__ __forceinline__ void sts128(uint32_t addr, uint32_t r0, uint32_t r1, uint32_t r2, uint32_t r3) {
    asm volatile("st.shared.v4.b32 [%0], {%1, %2, %3, %4};\n" :: "r"(addr), "r"(r0), "r"(r1), "r"(r2), "r"(r3) : "memory");
}
__device__ __forceinline__ void sts128_if(uint32_t p, uint32_t addr, uint32_t r0, uint32_t r1, uint32_t r2, uint32_t r3) {
    asm volatile("{\n.reg .pred q;\nsetp.ne.b32 q, %5, 0;\n@q st.shared.v4.b32 [%0], {%1, %2, %3, %4};\n}\n"
                 :: "r"(addr), "r"(r0), "r"(r1), "r"(r2), "r"(r3), "r"(p) : "memory");
}
__device__ __forceinline__ void sts32(uint32_t addr, uint32_t v) {
    asm volatile("st.shared.b32 [%0], %1;\n" :: "r"(addr), "r"(v) : "memory");
}
__device__ __forceinline__ uint32_t lds32(uint32_t addr) {
    uint32_t v;
    asm volatile("ld.shared.b32 %0, [%1];\n" : "=r"(v) : "r"(addr) : "memory");
    return v;
}
__device__ __forceinline__ void ldg_nc_v4(uint32_t (&r)[4], const void* p) {
    asm volatile("ld.global.nc.L1::no_allocate.v4.u32 {%0, %1, %2, %3}, [%4];\n"
                 : "=r"(r[0]), "=r"(r[1]), "=r"(r[2]), "=r"(r[3]) : "l"(p));
}
__device__ __forceinline__ uint32_t ldg_u32(const void* p) {
    uint32_t v;
    asm volatile("ld.global.nc.L1::evict_first.u32 %0, [%1];\n" : "=r"(v) : "l"(p));
    return v;
}
__device__ __forceinline__ void ldg_u64(const void* p, uint32_t& a, uint32_t& b) {
    asm volatile("ld.global.nc.L1::evict_first.v2.u32 {%0, %1}, [%2];\n" : "=r"(a), "=r"(b) : "l"(p));
}
__device__ __forceinline__ void prefetch_l2(const void* p) {
    asm volatile("prefetch.global.L2 [%0];\n" :: "l"(p));
}
__device__ __forceinline__ void cp_async16(uint32_t dst, const void* src) {
    asm volatile("cp.async.cg.shared.global [%0], [%1], 16;\n" :: "r"(dst), "l"(src) : "memory");
}
__device__ __forceinline__ float ex2_ftz(float x) {
    float y;
    asm("ex2.approx.ftz.f32 %0, %1;\n" : "=f"(y) : "f"(x));
    return y;
}
__device__ __forceinline__ float lg2_ftz(float x) {
    float y;
    asm("lg2.approx.ftz.f32 %0, %1;\n" : "=f"(y) : "f"(x));
    return y;
}
__device__ __forceinline__ float rcp_ftz(float x) {
    float y;
    asm("rcp.approx.ftz.f32 %0, %1;\n" : "=f"(y) : "f"(x));
    return y;
}
__device__ __forceinline__ float rsqrt_ftz(float x) {
    float y;
    asm("rsqrt.approx.ftz.f32 %0, %1;\n" : "=f"(y) : "f"(x));
    return y;
}

__device__ __forceinline__ bool elect_one() {
    uint32_t p;
    asm volatile("{\n.reg .pred q;\nelect.sync _|q, 0xffffffff;\nselp.u32 %0, 1, 0, q;\n}\n" : "=r"(p));
    return p != 0;
}
__device__ __forceinline__ void ldsm_x4(uint32_t (&r)[4], uint32_t addr) {
    asm volatile("ldmatrix.sync.aligned.m8n8.x4.shared.b16 {%0, %1, %2, %3}, [%4];\n"
                 : "=r"(r[0]), "=r"(r[1]), "=r"(r[2]), "=r"(r[3]) : "r"(addr) : "memory");
}
__device__ __forceinline__ void ldsm_x2(uint32_t& r0, uint32_t& r1, uint32_t addr) {
    asm volatile("ldmatrix.sync.aligned.m8n8.x2.shared.b16 {%0, %1}, [%2];\n" : "=r"(r0), "=r"(r1) : "r"(addr) : "memory");
}
__device__ __forceinline__ void tma_2d(uint32_t dst, const CUtensorMap* map, uint32_t bar, int c0, int c1) {
    asm volatile("cp.async.bulk.tensor.2d.shared::cluster.global.mbarrier::complete_tx::bytes [%0], [%1, {%3, %4}], [%2];\n"
                 :: "r"(dst), "l"(reinterpret_cast<uint64_t>(map)), "r"(bar), "r"(c0), "r"(c1) : "memory");
}
__device__ __forceinline__ void tma_3d(uint32_t dst, const CUtensorMap* map, uint32_t bar, int c0, int c1, int c2) {
    asm volatile("cp.async.bulk.tensor.3d.shared::cluster.global.mbarrier::complete_tx::bytes [%0], [%1, {%3, %4, %5}], [%2];\n"
                 :: "r"(dst), "l"(reinterpret_cast<uint64_t>(map)), "r"(bar), "r"(c0), "r"(c1), "r"(c2) : "memory");
}
constexpr uint64_t EVICT_FIRST = 0x12F0000000000000ull;
__device__ __forceinline__ void tma_3d_x(uint32_t dst, const CUtensorMap* map, uint32_t bar, int c0, int c1, int c2) {
    if (CH & 50)
        asm volatile("cp.async.bulk.tensor.3d.shared::cluster.global.mbarrier::complete_tx::bytes.L2::cache_hint [%0], [%1, {%3, %4, %5}], [%2], %6;\n"
                     :: "r"(dst), "l"(reinterpret_cast<uint64_t>(map)), "r"(bar), "r"(c0), "r"(c1), "r"(c2),
                        "l"((CH & 2) || (blockIdx.x & 1) == ((CH >> 5) & 1) ? EVICT_FIRST : 0x1000000000000000ull) : "memory");
    else tma_3d(dst, map, bar, c0, c1, c2);
}
__device__ __forceinline__ void tma_store_4d(const CUtensorMap* map, uint32_t src, int c0, int c1, int c2, int c3) {
    asm volatile("cp.async.bulk.tensor.4d.global.shared::cta.tile.bulk_group [%0, {%2, %3, %4, %5}], [%1];\n"
                 :: "l"(reinterpret_cast<uint64_t>(map)), "r"(src), "r"(c0), "r"(c1), "r"(c2), "r"(c3) : "memory");
}
__device__ __forceinline__ void mbar_arrive_if(uint32_t bar, uint32_t cnt) {
    asm volatile("{\n.reg .pred q;\nsetp.ne.b32 q, %1, 0;\n@q mbarrier.arrive.shared::cta.b64 _, [%0], %1;\n}\n"
                 :: "r"(bar), "r"(cnt) : "memory");
}

template <int BOFF, int AOFF, int NA>
__device__ __forceinline__ void mma_qkv_a(float (&d)[48], const uint32_t (&a)[NA][4], uint64_t descB) {
    asm volatile(
        "{\n"
        ".reg .pred p0, p1;\n"
        ".reg .b64 ta, ta0, tb, tb0;\n"
        "setp.ne.b32 p0, 0, 0;\n"
        "setp.eq.b32 p1, 0, 0;\n"
        "add.s64 tb0, %72, %73;\n"
        "add.s64 tb, tb0, 0;\n"
        "wgmma.mma_async.sync.aligned.m64n96k16.f32.bf16.bf16 {%0, %1, %2, %3, %4, %5, %6, %7, %8, %9, %10, %11, %12, %13, %14, %15, %16, %17, %18, %19, %20, %21, %22, %23, %24, %25, %26, %27, %28, %29, %30, %31, %32, %33, %34, %35, %36, %37, %38, %39, %40, %41, %42, %43, %44, %45, %46, %47}, {%48, %49, %50, %51}, tb, p0, 1, 1, 1;\n"
        "add.s64 tb, tb0, 32;\n"
        "wgmma.mma_async.sync.aligned.m64n96k16.f32.bf16.bf16 {%0, %1, %2, %3, %4, %5, %6, %7, %8, %9, %10, %11, %12, %13, %14, %15, %16, %17, %18, %19, %20, %21, %22, %23, %24, %25, %26, %27, %28, %29, %30, %31, %32, %33, %34, %35, %36, %37, %38, %39, %40, %41, %42, %43, %44, %45, %46, %47}, {%52, %53, %54, %55}, tb, p1, 1, 1, 1;\n"
        "add.s64 tb, tb0, 64;\n"
        "wgmma.mma_async.sync.aligned.m64n96k16.f32.bf16.bf16 {%0, %1, %2, %3, %4, %5, %6, %7, %8, %9, %10, %11, %12, %13, %14, %15, %16, %17, %18, %19, %20, %21, %22, %23, %24, %25, %26, %27, %28, %29, %30, %31, %32, %33, %34, %35, %36, %37, %38, %39, %40, %41, %42, %43, %44, %45, %46, %47}, {%56, %57, %58, %59}, tb, p1, 1, 1, 1;\n"
        "add.s64 tb, tb0, 96;\n"
        "wgmma.mma_async.sync.aligned.m64n96k16.f32.bf16.bf16 {%0, %1, %2, %3, %4, %5, %6, %7, %8, %9, %10, %11, %12, %13, %14, %15, %16, %17, %18, %19, %20, %21, %22, %23, %24, %25, %26, %27, %28, %29, %30, %31, %32, %33, %34, %35, %36, %37, %38, %39, %40, %41, %42, %43, %44, %45, %46, %47}, {%60, %61, %62, %63}, tb, p1, 1, 1, 1;\n"
        "add.s64 tb, tb0, 1536;\n"
        "wgmma.mma_async.sync.aligned.m64n96k16.f32.bf16.bf16 {%0, %1, %2, %3, %4, %5, %6, %7, %8, %9, %10, %11, %12, %13, %14, %15, %16, %17, %18, %19, %20, %21, %22, %23, %24, %25, %26, %27, %28, %29, %30, %31, %32, %33, %34, %35, %36, %37, %38, %39, %40, %41, %42, %43, %44, %45, %46, %47}, {%64, %65, %66, %67}, tb, p1, 1, 1, 1;\n"
        "add.s64 tb, tb0, 1568;\n"
        "wgmma.mma_async.sync.aligned.m64n96k16.f32.bf16.bf16 {%0, %1, %2, %3, %4, %5, %6, %7, %8, %9, %10, %11, %12, %13, %14, %15, %16, %17, %18, %19, %20, %21, %22, %23, %24, %25, %26, %27, %28, %29, %30, %31, %32, %33, %34, %35, %36, %37, %38, %39, %40, %41, %42, %43, %44, %45, %46, %47}, {%68, %69, %70, %71}, tb, p1, 1, 1, 1;\n"
        "}\n"
        : "=f"(d[0]), "=f"(d[1]), "=f"(d[2]), "=f"(d[3]), "=f"(d[4]), "=f"(d[5]), "=f"(d[6]), "=f"(d[7]), "=f"(d[8]), "=f"(d[9]), "=f"(d[10]), "=f"(d[11]), "=f"(d[12]), "=f"(d[13]), "=f"(d[14]), "=f"(d[15]), "=f"(d[16]), "=f"(d[17]), "=f"(d[18]), "=f"(d[19]), "=f"(d[20]), "=f"(d[21]), "=f"(d[22]), "=f"(d[23]), "=f"(d[24]), "=f"(d[25]), "=f"(d[26]), "=f"(d[27]), "=f"(d[28]), "=f"(d[29]), "=f"(d[30]), "=f"(d[31]), "=f"(d[32]), "=f"(d[33]), "=f"(d[34]), "=f"(d[35]), "=f"(d[36]), "=f"(d[37]), "=f"(d[38]), "=f"(d[39]), "=f"(d[40]), "=f"(d[41]), "=f"(d[42]), "=f"(d[43]), "=f"(d[44]), "=f"(d[45]), "=f"(d[46]), "=f"(d[47])
        : "r"(a[AOFF + 0][0]), "r"(a[AOFF + 0][1]), "r"(a[AOFF + 0][2]), "r"(a[AOFF + 0][3]), "r"(a[AOFF + 1][0]), "r"(a[AOFF + 1][1]), "r"(a[AOFF + 1][2]), "r"(a[AOFF + 1][3]), "r"(a[AOFF + 2][0]), "r"(a[AOFF + 2][1]), "r"(a[AOFF + 2][2]), "r"(a[AOFF + 2][3]), "r"(a[AOFF + 3][0]), "r"(a[AOFF + 3][1]), "r"(a[AOFF + 3][2]), "r"(a[AOFF + 3][3]), "r"(a[AOFF + 4][0]), "r"(a[AOFF + 4][1]), "r"(a[AOFF + 4][2]), "r"(a[AOFF + 4][3]), "r"(a[AOFF + 5][0]), "r"(a[AOFF + 5][1]), "r"(a[AOFF + 5][2]), "r"(a[AOFF + 5][3]), "l"(descB), "n"(BOFF >> 4));
}

template <int BOFF, int AOFF, int NA>
__device__ __forceinline__ void mma_qkv_b(float (&d)[48], const uint32_t (&a)[NA][4], uint64_t descB) {
    asm volatile(
        "{\n"
        ".reg .pred p0, p1;\n"
        ".reg .b64 ta, ta0, tb, tb0;\n"
        "setp.ne.b32 p0, 0, 0;\n"
        "setp.eq.b32 p1, 0, 0;\n"
        "add.s64 tb0, %72, %73;\n"
        "add.s64 tb, tb0, 1600;\n"
        "wgmma.mma_async.sync.aligned.m64n96k16.f32.bf16.bf16 {%0, %1, %2, %3, %4, %5, %6, %7, %8, %9, %10, %11, %12, %13, %14, %15, %16, %17, %18, %19, %20, %21, %22, %23, %24, %25, %26, %27, %28, %29, %30, %31, %32, %33, %34, %35, %36, %37, %38, %39, %40, %41, %42, %43, %44, %45, %46, %47}, {%48, %49, %50, %51}, tb, p1, 1, 1, 1;\n"
        "add.s64 tb, tb0, 1632;\n"
        "wgmma.mma_async.sync.aligned.m64n96k16.f32.bf16.bf16 {%0, %1, %2, %3, %4, %5, %6, %7, %8, %9, %10, %11, %12, %13, %14, %15, %16, %17, %18, %19, %20, %21, %22, %23, %24, %25, %26, %27, %28, %29, %30, %31, %32, %33, %34, %35, %36, %37, %38, %39, %40, %41, %42, %43, %44, %45, %46, %47}, {%52, %53, %54, %55}, tb, p1, 1, 1, 1;\n"
        "add.s64 tb, tb0, 3072;\n"
        "wgmma.mma_async.sync.aligned.m64n96k16.f32.bf16.bf16 {%0, %1, %2, %3, %4, %5, %6, %7, %8, %9, %10, %11, %12, %13, %14, %15, %16, %17, %18, %19, %20, %21, %22, %23, %24, %25, %26, %27, %28, %29, %30, %31, %32, %33, %34, %35, %36, %37, %38, %39, %40, %41, %42, %43, %44, %45, %46, %47}, {%56, %57, %58, %59}, tb, p1, 1, 1, 1;\n"
        "add.s64 tb, tb0, 3104;\n"
        "wgmma.mma_async.sync.aligned.m64n96k16.f32.bf16.bf16 {%0, %1, %2, %3, %4, %5, %6, %7, %8, %9, %10, %11, %12, %13, %14, %15, %16, %17, %18, %19, %20, %21, %22, %23, %24, %25, %26, %27, %28, %29, %30, %31, %32, %33, %34, %35, %36, %37, %38, %39, %40, %41, %42, %43, %44, %45, %46, %47}, {%60, %61, %62, %63}, tb, p1, 1, 1, 1;\n"
        "add.s64 tb, tb0, 3136;\n"
        "wgmma.mma_async.sync.aligned.m64n96k16.f32.bf16.bf16 {%0, %1, %2, %3, %4, %5, %6, %7, %8, %9, %10, %11, %12, %13, %14, %15, %16, %17, %18, %19, %20, %21, %22, %23, %24, %25, %26, %27, %28, %29, %30, %31, %32, %33, %34, %35, %36, %37, %38, %39, %40, %41, %42, %43, %44, %45, %46, %47}, {%64, %65, %66, %67}, tb, p1, 1, 1, 1;\n"
        "add.s64 tb, tb0, 3168;\n"
        "wgmma.mma_async.sync.aligned.m64n96k16.f32.bf16.bf16 {%0, %1, %2, %3, %4, %5, %6, %7, %8, %9, %10, %11, %12, %13, %14, %15, %16, %17, %18, %19, %20, %21, %22, %23, %24, %25, %26, %27, %28, %29, %30, %31, %32, %33, %34, %35, %36, %37, %38, %39, %40, %41, %42, %43, %44, %45, %46, %47}, {%68, %69, %70, %71}, tb, p1, 1, 1, 1;\n"
        "}\n"
        : "+f"(d[0]), "+f"(d[1]), "+f"(d[2]), "+f"(d[3]), "+f"(d[4]), "+f"(d[5]), "+f"(d[6]), "+f"(d[7]), "+f"(d[8]), "+f"(d[9]), "+f"(d[10]), "+f"(d[11]), "+f"(d[12]), "+f"(d[13]), "+f"(d[14]), "+f"(d[15]), "+f"(d[16]), "+f"(d[17]), "+f"(d[18]), "+f"(d[19]), "+f"(d[20]), "+f"(d[21]), "+f"(d[22]), "+f"(d[23]), "+f"(d[24]), "+f"(d[25]), "+f"(d[26]), "+f"(d[27]), "+f"(d[28]), "+f"(d[29]), "+f"(d[30]), "+f"(d[31]), "+f"(d[32]), "+f"(d[33]), "+f"(d[34]), "+f"(d[35]), "+f"(d[36]), "+f"(d[37]), "+f"(d[38]), "+f"(d[39]), "+f"(d[40]), "+f"(d[41]), "+f"(d[42]), "+f"(d[43]), "+f"(d[44]), "+f"(d[45]), "+f"(d[46]), "+f"(d[47])
        : "r"(a[AOFF + 0][0]), "r"(a[AOFF + 0][1]), "r"(a[AOFF + 0][2]), "r"(a[AOFF + 0][3]), "r"(a[AOFF + 1][0]), "r"(a[AOFF + 1][1]), "r"(a[AOFF + 1][2]), "r"(a[AOFF + 1][3]), "r"(a[AOFF + 2][0]), "r"(a[AOFF + 2][1]), "r"(a[AOFF + 2][2]), "r"(a[AOFF + 2][3]), "r"(a[AOFF + 3][0]), "r"(a[AOFF + 3][1]), "r"(a[AOFF + 3][2]), "r"(a[AOFF + 3][3]), "r"(a[AOFF + 4][0]), "r"(a[AOFF + 4][1]), "r"(a[AOFF + 4][2]), "r"(a[AOFF + 4][3]), "r"(a[AOFF + 5][0]), "r"(a[AOFF + 5][1]), "r"(a[AOFF + 5][2]), "r"(a[AOFF + 5][3]), "l"(descB), "n"(BOFF >> 4));
}

template <int BOFF, int AOFF, int NA>
__device__ __forceinline__ void mma_v_a(float (&d)[48], const uint32_t (&a)[NA][4], uint64_t descB) {
    asm volatile(
        "{\n"
        ".reg .pred p0, p1;\n"
        ".reg .b64 ta, ta0, tb, tb0;\n"
        "setp.ne.b32 p0, 0, 0;\n"
        "setp.eq.b32 p1, 0, 0;\n"
        "add.s64 tb0, %72, %73;\n"
        "add.s64 tb, tb0, 0;\n"
        "wgmma.mma_async.sync.aligned.m64n96k16.f32.bf16.bf16 {%0, %1, %2, %3, %4, %5, %6, %7, %8, %9, %10, %11, %12, %13, %14, %15, %16, %17, %18, %19, %20, %21, %22, %23, %24, %25, %26, %27, %28, %29, %30, %31, %32, %33, %34, %35, %36, %37, %38, %39, %40, %41, %42, %43, %44, %45, %46, %47}, {%48, %49, %50, %51}, tb, p0, 1, 1, 1;\n"
        "add.s64 tb, tb0, 32;\n"
        "wgmma.mma_async.sync.aligned.m64n96k16.f32.bf16.bf16 {%0, %1, %2, %3, %4, %5, %6, %7, %8, %9, %10, %11, %12, %13, %14, %15, %16, %17, %18, %19, %20, %21, %22, %23, %24, %25, %26, %27, %28, %29, %30, %31, %32, %33, %34, %35, %36, %37, %38, %39, %40, %41, %42, %43, %44, %45, %46, %47}, {%52, %53, %54, %55}, tb, p1, 1, 1, 1;\n"
        "add.s64 tb, tb0, 64;\n"
        "wgmma.mma_async.sync.aligned.m64n96k16.f32.bf16.bf16 {%0, %1, %2, %3, %4, %5, %6, %7, %8, %9, %10, %11, %12, %13, %14, %15, %16, %17, %18, %19, %20, %21, %22, %23, %24, %25, %26, %27, %28, %29, %30, %31, %32, %33, %34, %35, %36, %37, %38, %39, %40, %41, %42, %43, %44, %45, %46, %47}, {%56, %57, %58, %59}, tb, p1, 1, 1, 1;\n"
        "add.s64 tb, tb0, 96;\n"
        "wgmma.mma_async.sync.aligned.m64n96k16.f32.bf16.bf16 {%0, %1, %2, %3, %4, %5, %6, %7, %8, %9, %10, %11, %12, %13, %14, %15, %16, %17, %18, %19, %20, %21, %22, %23, %24, %25, %26, %27, %28, %29, %30, %31, %32, %33, %34, %35, %36, %37, %38, %39, %40, %41, %42, %43, %44, %45, %46, %47}, {%60, %61, %62, %63}, tb, p1, 1, 1, 1;\n"
        "add.s64 tb, tb0, 128;\n"
        "wgmma.mma_async.sync.aligned.m64n96k16.f32.bf16.bf16 {%0, %1, %2, %3, %4, %5, %6, %7, %8, %9, %10, %11, %12, %13, %14, %15, %16, %17, %18, %19, %20, %21, %22, %23, %24, %25, %26, %27, %28, %29, %30, %31, %32, %33, %34, %35, %36, %37, %38, %39, %40, %41, %42, %43, %44, %45, %46, %47}, {%64, %65, %66, %67}, tb, p1, 1, 1, 1;\n"
        "add.s64 tb, tb0, 160;\n"
        "wgmma.mma_async.sync.aligned.m64n96k16.f32.bf16.bf16 {%0, %1, %2, %3, %4, %5, %6, %7, %8, %9, %10, %11, %12, %13, %14, %15, %16, %17, %18, %19, %20, %21, %22, %23, %24, %25, %26, %27, %28, %29, %30, %31, %32, %33, %34, %35, %36, %37, %38, %39, %40, %41, %42, %43, %44, %45, %46, %47}, {%68, %69, %70, %71}, tb, p1, 1, 1, 1;\n"
        "}\n"
        : "=f"(d[0]), "=f"(d[1]), "=f"(d[2]), "=f"(d[3]), "=f"(d[4]), "=f"(d[5]), "=f"(d[6]), "=f"(d[7]), "=f"(d[8]), "=f"(d[9]), "=f"(d[10]), "=f"(d[11]), "=f"(d[12]), "=f"(d[13]), "=f"(d[14]), "=f"(d[15]), "=f"(d[16]), "=f"(d[17]), "=f"(d[18]), "=f"(d[19]), "=f"(d[20]), "=f"(d[21]), "=f"(d[22]), "=f"(d[23]), "=f"(d[24]), "=f"(d[25]), "=f"(d[26]), "=f"(d[27]), "=f"(d[28]), "=f"(d[29]), "=f"(d[30]), "=f"(d[31]), "=f"(d[32]), "=f"(d[33]), "=f"(d[34]), "=f"(d[35]), "=f"(d[36]), "=f"(d[37]), "=f"(d[38]), "=f"(d[39]), "=f"(d[40]), "=f"(d[41]), "=f"(d[42]), "=f"(d[43]), "=f"(d[44]), "=f"(d[45]), "=f"(d[46]), "=f"(d[47])
        : "r"(a[AOFF + 0][0]), "r"(a[AOFF + 0][1]), "r"(a[AOFF + 0][2]), "r"(a[AOFF + 0][3]), "r"(a[AOFF + 1][0]), "r"(a[AOFF + 1][1]), "r"(a[AOFF + 1][2]), "r"(a[AOFF + 1][3]), "r"(a[AOFF + 2][0]), "r"(a[AOFF + 2][1]), "r"(a[AOFF + 2][2]), "r"(a[AOFF + 2][3]), "r"(a[AOFF + 3][0]), "r"(a[AOFF + 3][1]), "r"(a[AOFF + 3][2]), "r"(a[AOFF + 3][3]), "r"(a[AOFF + 4][0]), "r"(a[AOFF + 4][1]), "r"(a[AOFF + 4][2]), "r"(a[AOFF + 4][3]), "r"(a[AOFF + 5][0]), "r"(a[AOFF + 5][1]), "r"(a[AOFF + 5][2]), "r"(a[AOFF + 5][3]), "l"(descB), "n"(BOFF >> 4));
}

template <int BOFF, int AOFF, int NA>
__device__ __forceinline__ void mma_v_b(float (&d)[48], const uint32_t (&a)[NA][4], uint64_t descB) {
    asm volatile(
        "{\n"
        ".reg .pred p0, p1;\n"
        ".reg .b64 ta, ta0, tb, tb0;\n"
        "setp.ne.b32 p0, 0, 0;\n"
        "setp.eq.b32 p1, 0, 0;\n"
        "add.s64 tb0, %72, %73;\n"
        "add.s64 tb, tb0, 192;\n"
        "wgmma.mma_async.sync.aligned.m64n96k16.f32.bf16.bf16 {%0, %1, %2, %3, %4, %5, %6, %7, %8, %9, %10, %11, %12, %13, %14, %15, %16, %17, %18, %19, %20, %21, %22, %23, %24, %25, %26, %27, %28, %29, %30, %31, %32, %33, %34, %35, %36, %37, %38, %39, %40, %41, %42, %43, %44, %45, %46, %47}, {%48, %49, %50, %51}, tb, p1, 1, 1, 1;\n"
        "add.s64 tb, tb0, 224;\n"
        "wgmma.mma_async.sync.aligned.m64n96k16.f32.bf16.bf16 {%0, %1, %2, %3, %4, %5, %6, %7, %8, %9, %10, %11, %12, %13, %14, %15, %16, %17, %18, %19, %20, %21, %22, %23, %24, %25, %26, %27, %28, %29, %30, %31, %32, %33, %34, %35, %36, %37, %38, %39, %40, %41, %42, %43, %44, %45, %46, %47}, {%52, %53, %54, %55}, tb, p1, 1, 1, 1;\n"
        "add.s64 tb, tb0, 256;\n"
        "wgmma.mma_async.sync.aligned.m64n96k16.f32.bf16.bf16 {%0, %1, %2, %3, %4, %5, %6, %7, %8, %9, %10, %11, %12, %13, %14, %15, %16, %17, %18, %19, %20, %21, %22, %23, %24, %25, %26, %27, %28, %29, %30, %31, %32, %33, %34, %35, %36, %37, %38, %39, %40, %41, %42, %43, %44, %45, %46, %47}, {%56, %57, %58, %59}, tb, p1, 1, 1, 1;\n"
        "add.s64 tb, tb0, 288;\n"
        "wgmma.mma_async.sync.aligned.m64n96k16.f32.bf16.bf16 {%0, %1, %2, %3, %4, %5, %6, %7, %8, %9, %10, %11, %12, %13, %14, %15, %16, %17, %18, %19, %20, %21, %22, %23, %24, %25, %26, %27, %28, %29, %30, %31, %32, %33, %34, %35, %36, %37, %38, %39, %40, %41, %42, %43, %44, %45, %46, %47}, {%60, %61, %62, %63}, tb, p1, 1, 1, 1;\n"
        "add.s64 tb, tb0, 320;\n"
        "wgmma.mma_async.sync.aligned.m64n96k16.f32.bf16.bf16 {%0, %1, %2, %3, %4, %5, %6, %7, %8, %9, %10, %11, %12, %13, %14, %15, %16, %17, %18, %19, %20, %21, %22, %23, %24, %25, %26, %27, %28, %29, %30, %31, %32, %33, %34, %35, %36, %37, %38, %39, %40, %41, %42, %43, %44, %45, %46, %47}, {%64, %65, %66, %67}, tb, p1, 1, 1, 1;\n"
        "add.s64 tb, tb0, 352;\n"
        "wgmma.mma_async.sync.aligned.m64n96k16.f32.bf16.bf16 {%0, %1, %2, %3, %4, %5, %6, %7, %8, %9, %10, %11, %12, %13, %14, %15, %16, %17, %18, %19, %20, %21, %22, %23, %24, %25, %26, %27, %28, %29, %30, %31, %32, %33, %34, %35, %36, %37, %38, %39, %40, %41, %42, %43, %44, %45, %46, %47}, {%68, %69, %70, %71}, tb, p1, 1, 1, 1;\n"
        "}\n"
        : "+f"(d[0]), "+f"(d[1]), "+f"(d[2]), "+f"(d[3]), "+f"(d[4]), "+f"(d[5]), "+f"(d[6]), "+f"(d[7]), "+f"(d[8]), "+f"(d[9]), "+f"(d[10]), "+f"(d[11]), "+f"(d[12]), "+f"(d[13]), "+f"(d[14]), "+f"(d[15]), "+f"(d[16]), "+f"(d[17]), "+f"(d[18]), "+f"(d[19]), "+f"(d[20]), "+f"(d[21]), "+f"(d[22]), "+f"(d[23]), "+f"(d[24]), "+f"(d[25]), "+f"(d[26]), "+f"(d[27]), "+f"(d[28]), "+f"(d[29]), "+f"(d[30]), "+f"(d[31]), "+f"(d[32]), "+f"(d[33]), "+f"(d[34]), "+f"(d[35]), "+f"(d[36]), "+f"(d[37]), "+f"(d[38]), "+f"(d[39]), "+f"(d[40]), "+f"(d[41]), "+f"(d[42]), "+f"(d[43]), "+f"(d[44]), "+f"(d[45]), "+f"(d[46]), "+f"(d[47])
        : "r"(a[AOFF + 0][0]), "r"(a[AOFF + 0][1]), "r"(a[AOFF + 0][2]), "r"(a[AOFF + 0][3]), "r"(a[AOFF + 1][0]), "r"(a[AOFF + 1][1]), "r"(a[AOFF + 1][2]), "r"(a[AOFF + 1][3]), "r"(a[AOFF + 2][0]), "r"(a[AOFF + 2][1]), "r"(a[AOFF + 2][2]), "r"(a[AOFF + 2][3]), "r"(a[AOFF + 3][0]), "r"(a[AOFF + 3][1]), "r"(a[AOFF + 3][2]), "r"(a[AOFF + 3][3]), "r"(a[AOFF + 4][0]), "r"(a[AOFF + 4][1]), "r"(a[AOFF + 4][2]), "r"(a[AOFF + 4][3]), "r"(a[AOFF + 5][0]), "r"(a[AOFF + 5][1]), "r"(a[AOFF + 5][2]), "r"(a[AOFF + 5][3]), "l"(descB), "n"(BOFF >> 4));
}

template <int BOFF, int AOFF, int NA>
__device__ __forceinline__ void mma_w_a(float (&d)[48], const uint32_t (&a)[NA][4], uint64_t descB) {
    asm volatile(
        "{\n"
        ".reg .pred p0, p1;\n"
        ".reg .b64 ta, ta0, tb, tb0;\n"
        "setp.ne.b32 p0, 0, 0;\n"
        "setp.eq.b32 p1, 0, 0;\n"
        "add.s64 tb0, %72, %73;\n"
        "add.s64 tb, tb0, 0;\n"
        "wgmma.mma_async.sync.aligned.m64n96k16.f32.bf16.bf16 {%0, %1, %2, %3, %4, %5, %6, %7, %8, %9, %10, %11, %12, %13, %14, %15, %16, %17, %18, %19, %20, %21, %22, %23, %24, %25, %26, %27, %28, %29, %30, %31, %32, %33, %34, %35, %36, %37, %38, %39, %40, %41, %42, %43, %44, %45, %46, %47}, {%48, %49, %50, %51}, tb, p0, 1, 1, 1;\n"
        "add.s64 tb, tb0, 64;\n"
        "wgmma.mma_async.sync.aligned.m64n96k16.f32.bf16.bf16 {%0, %1, %2, %3, %4, %5, %6, %7, %8, %9, %10, %11, %12, %13, %14, %15, %16, %17, %18, %19, %20, %21, %22, %23, %24, %25, %26, %27, %28, %29, %30, %31, %32, %33, %34, %35, %36, %37, %38, %39, %40, %41, %42, %43, %44, %45, %46, %47}, {%52, %53, %54, %55}, tb, p1, 1, 1, 1;\n"
        "add.s64 tb, tb0, 128;\n"
        "wgmma.mma_async.sync.aligned.m64n96k16.f32.bf16.bf16 {%0, %1, %2, %3, %4, %5, %6, %7, %8, %9, %10, %11, %12, %13, %14, %15, %16, %17, %18, %19, %20, %21, %22, %23, %24, %25, %26, %27, %28, %29, %30, %31, %32, %33, %34, %35, %36, %37, %38, %39, %40, %41, %42, %43, %44, %45, %46, %47}, {%56, %57, %58, %59}, tb, p1, 1, 1, 1;\n"
        "add.s64 tb, tb0, 192;\n"
        "wgmma.mma_async.sync.aligned.m64n96k16.f32.bf16.bf16 {%0, %1, %2, %3, %4, %5, %6, %7, %8, %9, %10, %11, %12, %13, %14, %15, %16, %17, %18, %19, %20, %21, %22, %23, %24, %25, %26, %27, %28, %29, %30, %31, %32, %33, %34, %35, %36, %37, %38, %39, %40, %41, %42, %43, %44, %45, %46, %47}, {%60, %61, %62, %63}, tb, p1, 1, 1, 1;\n"
        "add.s64 tb, tb0, 256;\n"
        "wgmma.mma_async.sync.aligned.m64n96k16.f32.bf16.bf16 {%0, %1, %2, %3, %4, %5, %6, %7, %8, %9, %10, %11, %12, %13, %14, %15, %16, %17, %18, %19, %20, %21, %22, %23, %24, %25, %26, %27, %28, %29, %30, %31, %32, %33, %34, %35, %36, %37, %38, %39, %40, %41, %42, %43, %44, %45, %46, %47}, {%64, %65, %66, %67}, tb, p1, 1, 1, 1;\n"
        "add.s64 tb, tb0, 320;\n"
        "wgmma.mma_async.sync.aligned.m64n96k16.f32.bf16.bf16 {%0, %1, %2, %3, %4, %5, %6, %7, %8, %9, %10, %11, %12, %13, %14, %15, %16, %17, %18, %19, %20, %21, %22, %23, %24, %25, %26, %27, %28, %29, %30, %31, %32, %33, %34, %35, %36, %37, %38, %39, %40, %41, %42, %43, %44, %45, %46, %47}, {%68, %69, %70, %71}, tb, p1, 1, 1, 1;\n"
        "}\n"
        : "=f"(d[0]), "=f"(d[1]), "=f"(d[2]), "=f"(d[3]), "=f"(d[4]), "=f"(d[5]), "=f"(d[6]), "=f"(d[7]), "=f"(d[8]), "=f"(d[9]), "=f"(d[10]), "=f"(d[11]), "=f"(d[12]), "=f"(d[13]), "=f"(d[14]), "=f"(d[15]), "=f"(d[16]), "=f"(d[17]), "=f"(d[18]), "=f"(d[19]), "=f"(d[20]), "=f"(d[21]), "=f"(d[22]), "=f"(d[23]), "=f"(d[24]), "=f"(d[25]), "=f"(d[26]), "=f"(d[27]), "=f"(d[28]), "=f"(d[29]), "=f"(d[30]), "=f"(d[31]), "=f"(d[32]), "=f"(d[33]), "=f"(d[34]), "=f"(d[35]), "=f"(d[36]), "=f"(d[37]), "=f"(d[38]), "=f"(d[39]), "=f"(d[40]), "=f"(d[41]), "=f"(d[42]), "=f"(d[43]), "=f"(d[44]), "=f"(d[45]), "=f"(d[46]), "=f"(d[47])
        : "r"(a[AOFF + 0][0]), "r"(a[AOFF + 0][1]), "r"(a[AOFF + 0][2]), "r"(a[AOFF + 0][3]), "r"(a[AOFF + 1][0]), "r"(a[AOFF + 1][1]), "r"(a[AOFF + 1][2]), "r"(a[AOFF + 1][3]), "r"(a[AOFF + 2][0]), "r"(a[AOFF + 2][1]), "r"(a[AOFF + 2][2]), "r"(a[AOFF + 2][3]), "r"(a[AOFF + 3][0]), "r"(a[AOFF + 3][1]), "r"(a[AOFF + 3][2]), "r"(a[AOFF + 3][3]), "r"(a[AOFF + 4][0]), "r"(a[AOFF + 4][1]), "r"(a[AOFF + 4][2]), "r"(a[AOFF + 4][3]), "r"(a[AOFF + 5][0]), "r"(a[AOFF + 5][1]), "r"(a[AOFF + 5][2]), "r"(a[AOFF + 5][3]), "l"(descB), "n"(BOFF >> 4));
}

template <int BOFF, int AOFF, int NA>
__device__ __forceinline__ void mma_w_b(float (&d)[48], const uint32_t (&a)[NA][4], uint64_t descB) {
    asm volatile(
        "{\n"
        ".reg .pred p0, p1;\n"
        ".reg .b64 ta, ta0, tb, tb0;\n"
        "setp.ne.b32 p0, 0, 0;\n"
        "setp.eq.b32 p1, 0, 0;\n"
        "add.s64 tb0, %72, %73;\n"
        "add.s64 tb, tb0, 384;\n"
        "wgmma.mma_async.sync.aligned.m64n96k16.f32.bf16.bf16 {%0, %1, %2, %3, %4, %5, %6, %7, %8, %9, %10, %11, %12, %13, %14, %15, %16, %17, %18, %19, %20, %21, %22, %23, %24, %25, %26, %27, %28, %29, %30, %31, %32, %33, %34, %35, %36, %37, %38, %39, %40, %41, %42, %43, %44, %45, %46, %47}, {%48, %49, %50, %51}, tb, p1, 1, 1, 1;\n"
        "add.s64 tb, tb0, 448;\n"
        "wgmma.mma_async.sync.aligned.m64n96k16.f32.bf16.bf16 {%0, %1, %2, %3, %4, %5, %6, %7, %8, %9, %10, %11, %12, %13, %14, %15, %16, %17, %18, %19, %20, %21, %22, %23, %24, %25, %26, %27, %28, %29, %30, %31, %32, %33, %34, %35, %36, %37, %38, %39, %40, %41, %42, %43, %44, %45, %46, %47}, {%52, %53, %54, %55}, tb, p1, 1, 1, 1;\n"
        "add.s64 tb, tb0, 512;\n"
        "wgmma.mma_async.sync.aligned.m64n96k16.f32.bf16.bf16 {%0, %1, %2, %3, %4, %5, %6, %7, %8, %9, %10, %11, %12, %13, %14, %15, %16, %17, %18, %19, %20, %21, %22, %23, %24, %25, %26, %27, %28, %29, %30, %31, %32, %33, %34, %35, %36, %37, %38, %39, %40, %41, %42, %43, %44, %45, %46, %47}, {%56, %57, %58, %59}, tb, p1, 1, 1, 1;\n"
        "add.s64 tb, tb0, 576;\n"
        "wgmma.mma_async.sync.aligned.m64n96k16.f32.bf16.bf16 {%0, %1, %2, %3, %4, %5, %6, %7, %8, %9, %10, %11, %12, %13, %14, %15, %16, %17, %18, %19, %20, %21, %22, %23, %24, %25, %26, %27, %28, %29, %30, %31, %32, %33, %34, %35, %36, %37, %38, %39, %40, %41, %42, %43, %44, %45, %46, %47}, {%60, %61, %62, %63}, tb, p1, 1, 1, 1;\n"
        "add.s64 tb, tb0, 640;\n"
        "wgmma.mma_async.sync.aligned.m64n96k16.f32.bf16.bf16 {%0, %1, %2, %3, %4, %5, %6, %7, %8, %9, %10, %11, %12, %13, %14, %15, %16, %17, %18, %19, %20, %21, %22, %23, %24, %25, %26, %27, %28, %29, %30, %31, %32, %33, %34, %35, %36, %37, %38, %39, %40, %41, %42, %43, %44, %45, %46, %47}, {%64, %65, %66, %67}, tb, p1, 1, 1, 1;\n"
        "add.s64 tb, tb0, 704;\n"
        "wgmma.mma_async.sync.aligned.m64n96k16.f32.bf16.bf16 {%0, %1, %2, %3, %4, %5, %6, %7, %8, %9, %10, %11, %12, %13, %14, %15, %16, %17, %18, %19, %20, %21, %22, %23, %24, %25, %26, %27, %28, %29, %30, %31, %32, %33, %34, %35, %36, %37, %38, %39, %40, %41, %42, %43, %44, %45, %46, %47}, {%68, %69, %70, %71}, tb, p1, 1, 1, 1;\n"
        "}\n"
        : "+f"(d[0]), "+f"(d[1]), "+f"(d[2]), "+f"(d[3]), "+f"(d[4]), "+f"(d[5]), "+f"(d[6]), "+f"(d[7]), "+f"(d[8]), "+f"(d[9]), "+f"(d[10]), "+f"(d[11]), "+f"(d[12]), "+f"(d[13]), "+f"(d[14]), "+f"(d[15]), "+f"(d[16]), "+f"(d[17]), "+f"(d[18]), "+f"(d[19]), "+f"(d[20]), "+f"(d[21]), "+f"(d[22]), "+f"(d[23]), "+f"(d[24]), "+f"(d[25]), "+f"(d[26]), "+f"(d[27]), "+f"(d[28]), "+f"(d[29]), "+f"(d[30]), "+f"(d[31]), "+f"(d[32]), "+f"(d[33]), "+f"(d[34]), "+f"(d[35]), "+f"(d[36]), "+f"(d[37]), "+f"(d[38]), "+f"(d[39]), "+f"(d[40]), "+f"(d[41]), "+f"(d[42]), "+f"(d[43]), "+f"(d[44]), "+f"(d[45]), "+f"(d[46]), "+f"(d[47])
        : "r"(a[AOFF + 0][0]), "r"(a[AOFF + 0][1]), "r"(a[AOFF + 0][2]), "r"(a[AOFF + 0][3]), "r"(a[AOFF + 1][0]), "r"(a[AOFF + 1][1]), "r"(a[AOFF + 1][2]), "r"(a[AOFF + 1][3]), "r"(a[AOFF + 2][0]), "r"(a[AOFF + 2][1]), "r"(a[AOFF + 2][2]), "r"(a[AOFF + 2][3]), "r"(a[AOFF + 3][0]), "r"(a[AOFF + 3][1]), "r"(a[AOFF + 3][2]), "r"(a[AOFF + 3][3]), "r"(a[AOFF + 4][0]), "r"(a[AOFF + 4][1]), "r"(a[AOFF + 4][2]), "r"(a[AOFF + 4][3]), "r"(a[AOFF + 5][0]), "r"(a[AOFF + 5][1]), "r"(a[AOFF + 5][2]), "r"(a[AOFF + 5][3]), "l"(descB), "n"(BOFF >> 4));
}
template <int V, int S0, int S1> struct Rng;
template <> struct Rng<0, 0, 3> {
template <int BOFF, int AOFF, int NA>
static __device__ __forceinline__ void run(float (&d)[48], const uint32_t (&a)[NA][4], uint64_t descB) {
    asm volatile(
        "{\n"
        ".reg .pred p0, p1;\n"
        ".reg .b64 ta, ta0, tb, tb0;\n"
        "setp.ne.b32 p0, 0, 0;\n"
        "setp.eq.b32 p1, 0, 0;\n"
        "add.s64 tb0, %60, %61;\n"
        "add.s64 tb, tb0, 0;\n"
        "wgmma.mma_async.sync.aligned.m64n96k16.f32.bf16.bf16 {%0, %1, %2, %3, %4, %5, %6, %7, %8, %9, %10, %11, %12, %13, %14, %15, %16, %17, %18, %19, %20, %21, %22, %23, %24, %25, %26, %27, %28, %29, %30, %31, %32, %33, %34, %35, %36, %37, %38, %39, %40, %41, %42, %43, %44, %45, %46, %47}, {%48, %49, %50, %51}, tb, p0, 1, 1, 1;\n"
        "add.s64 tb, tb0, 32;\n"
        "wgmma.mma_async.sync.aligned.m64n96k16.f32.bf16.bf16 {%0, %1, %2, %3, %4, %5, %6, %7, %8, %9, %10, %11, %12, %13, %14, %15, %16, %17, %18, %19, %20, %21, %22, %23, %24, %25, %26, %27, %28, %29, %30, %31, %32, %33, %34, %35, %36, %37, %38, %39, %40, %41, %42, %43, %44, %45, %46, %47}, {%52, %53, %54, %55}, tb, p1, 1, 1, 1;\n"
        "add.s64 tb, tb0, 64;\n"
        "wgmma.mma_async.sync.aligned.m64n96k16.f32.bf16.bf16 {%0, %1, %2, %3, %4, %5, %6, %7, %8, %9, %10, %11, %12, %13, %14, %15, %16, %17, %18, %19, %20, %21, %22, %23, %24, %25, %26, %27, %28, %29, %30, %31, %32, %33, %34, %35, %36, %37, %38, %39, %40, %41, %42, %43, %44, %45, %46, %47}, {%56, %57, %58, %59}, tb, p1, 1, 1, 1;\n"
        "}\n"
        : "=f"(d[0]), "=f"(d[1]), "=f"(d[2]), "=f"(d[3]), "=f"(d[4]), "=f"(d[5]), "=f"(d[6]), "=f"(d[7]), "=f"(d[8]), "=f"(d[9]), "=f"(d[10]), "=f"(d[11]), "=f"(d[12]), "=f"(d[13]), "=f"(d[14]), "=f"(d[15]), "=f"(d[16]), "=f"(d[17]), "=f"(d[18]), "=f"(d[19]), "=f"(d[20]), "=f"(d[21]), "=f"(d[22]), "=f"(d[23]), "=f"(d[24]), "=f"(d[25]), "=f"(d[26]), "=f"(d[27]), "=f"(d[28]), "=f"(d[29]), "=f"(d[30]), "=f"(d[31]), "=f"(d[32]), "=f"(d[33]), "=f"(d[34]), "=f"(d[35]), "=f"(d[36]), "=f"(d[37]), "=f"(d[38]), "=f"(d[39]), "=f"(d[40]), "=f"(d[41]), "=f"(d[42]), "=f"(d[43]), "=f"(d[44]), "=f"(d[45]), "=f"(d[46]), "=f"(d[47])
        : "r"(a[AOFF + 0][0]), "r"(a[AOFF + 0][1]), "r"(a[AOFF + 0][2]), "r"(a[AOFF + 0][3]), "r"(a[AOFF + 1][0]), "r"(a[AOFF + 1][1]), "r"(a[AOFF + 1][2]), "r"(a[AOFF + 1][3]), "r"(a[AOFF + 2][0]), "r"(a[AOFF + 2][1]), "r"(a[AOFF + 2][2]), "r"(a[AOFF + 2][3]), "l"(descB), "n"(BOFF >> 4));
}
};
template <> struct Rng<1, 0, 3> {
template <int BOFF, int AOFF, int NA>
static __device__ __forceinline__ void run(float (&d)[48], const uint32_t (&a)[NA][4], uint64_t descB) {
    asm volatile(
        "{\n"
        ".reg .pred p0, p1;\n"
        ".reg .b64 ta, ta0, tb, tb0;\n"
        "setp.ne.b32 p0, 0, 0;\n"
        "setp.eq.b32 p1, 0, 0;\n"
        "add.s64 tb0, %60, %61;\n"
        "add.s64 tb, tb0, 0;\n"
        "wgmma.mma_async.sync.aligned.m64n96k16.f32.bf16.bf16 {%0, %1, %2, %3, %4, %5, %6, %7, %8, %9, %10, %11, %12, %13, %14, %15, %16, %17, %18, %19, %20, %21, %22, %23, %24, %25, %26, %27, %28, %29, %30, %31, %32, %33, %34, %35, %36, %37, %38, %39, %40, %41, %42, %43, %44, %45, %46, %47}, {%48, %49, %50, %51}, tb, p0, 1, 1, 1;\n"
        "add.s64 tb, tb0, 32;\n"
        "wgmma.mma_async.sync.aligned.m64n96k16.f32.bf16.bf16 {%0, %1, %2, %3, %4, %5, %6, %7, %8, %9, %10, %11, %12, %13, %14, %15, %16, %17, %18, %19, %20, %21, %22, %23, %24, %25, %26, %27, %28, %29, %30, %31, %32, %33, %34, %35, %36, %37, %38, %39, %40, %41, %42, %43, %44, %45, %46, %47}, {%52, %53, %54, %55}, tb, p1, 1, 1, 1;\n"
        "add.s64 tb, tb0, 64;\n"
        "wgmma.mma_async.sync.aligned.m64n96k16.f32.bf16.bf16 {%0, %1, %2, %3, %4, %5, %6, %7, %8, %9, %10, %11, %12, %13, %14, %15, %16, %17, %18, %19, %20, %21, %22, %23, %24, %25, %26, %27, %28, %29, %30, %31, %32, %33, %34, %35, %36, %37, %38, %39, %40, %41, %42, %43, %44, %45, %46, %47}, {%56, %57, %58, %59}, tb, p1, 1, 1, 1;\n"
        "}\n"
        : "=f"(d[0]), "=f"(d[1]), "=f"(d[2]), "=f"(d[3]), "=f"(d[4]), "=f"(d[5]), "=f"(d[6]), "=f"(d[7]), "=f"(d[8]), "=f"(d[9]), "=f"(d[10]), "=f"(d[11]), "=f"(d[12]), "=f"(d[13]), "=f"(d[14]), "=f"(d[15]), "=f"(d[16]), "=f"(d[17]), "=f"(d[18]), "=f"(d[19]), "=f"(d[20]), "=f"(d[21]), "=f"(d[22]), "=f"(d[23]), "=f"(d[24]), "=f"(d[25]), "=f"(d[26]), "=f"(d[27]), "=f"(d[28]), "=f"(d[29]), "=f"(d[30]), "=f"(d[31]), "=f"(d[32]), "=f"(d[33]), "=f"(d[34]), "=f"(d[35]), "=f"(d[36]), "=f"(d[37]), "=f"(d[38]), "=f"(d[39]), "=f"(d[40]), "=f"(d[41]), "=f"(d[42]), "=f"(d[43]), "=f"(d[44]), "=f"(d[45]), "=f"(d[46]), "=f"(d[47])
        : "r"(a[AOFF + 0][0]), "r"(a[AOFF + 0][1]), "r"(a[AOFF + 0][2]), "r"(a[AOFF + 0][3]), "r"(a[AOFF + 1][0]), "r"(a[AOFF + 1][1]), "r"(a[AOFF + 1][2]), "r"(a[AOFF + 1][3]), "r"(a[AOFF + 2][0]), "r"(a[AOFF + 2][1]), "r"(a[AOFF + 2][2]), "r"(a[AOFF + 2][3]), "l"(descB), "n"(BOFF >> 4));
}
};
template <> struct Rng<0, 0, 4> {
template <int BOFF, int AOFF, int NA>
static __device__ __forceinline__ void run(float (&d)[48], const uint32_t (&a)[NA][4], uint64_t descB) {
    asm volatile(
        "{\n"
        ".reg .pred p0, p1;\n"
        ".reg .b64 ta, ta0, tb, tb0;\n"
        "setp.ne.b32 p0, 0, 0;\n"
        "setp.eq.b32 p1, 0, 0;\n"
        "add.s64 tb0, %64, %65;\n"
        "add.s64 tb, tb0, 0;\n"
        "wgmma.mma_async.sync.aligned.m64n96k16.f32.bf16.bf16 {%0, %1, %2, %3, %4, %5, %6, %7, %8, %9, %10, %11, %12, %13, %14, %15, %16, %17, %18, %19, %20, %21, %22, %23, %24, %25, %26, %27, %28, %29, %30, %31, %32, %33, %34, %35, %36, %37, %38, %39, %40, %41, %42, %43, %44, %45, %46, %47}, {%48, %49, %50, %51}, tb, p0, 1, 1, 1;\n"
        "add.s64 tb, tb0, 32;\n"
        "wgmma.mma_async.sync.aligned.m64n96k16.f32.bf16.bf16 {%0, %1, %2, %3, %4, %5, %6, %7, %8, %9, %10, %11, %12, %13, %14, %15, %16, %17, %18, %19, %20, %21, %22, %23, %24, %25, %26, %27, %28, %29, %30, %31, %32, %33, %34, %35, %36, %37, %38, %39, %40, %41, %42, %43, %44, %45, %46, %47}, {%52, %53, %54, %55}, tb, p1, 1, 1, 1;\n"
        "add.s64 tb, tb0, 64;\n"
        "wgmma.mma_async.sync.aligned.m64n96k16.f32.bf16.bf16 {%0, %1, %2, %3, %4, %5, %6, %7, %8, %9, %10, %11, %12, %13, %14, %15, %16, %17, %18, %19, %20, %21, %22, %23, %24, %25, %26, %27, %28, %29, %30, %31, %32, %33, %34, %35, %36, %37, %38, %39, %40, %41, %42, %43, %44, %45, %46, %47}, {%56, %57, %58, %59}, tb, p1, 1, 1, 1;\n"
        "add.s64 tb, tb0, 96;\n"
        "wgmma.mma_async.sync.aligned.m64n96k16.f32.bf16.bf16 {%0, %1, %2, %3, %4, %5, %6, %7, %8, %9, %10, %11, %12, %13, %14, %15, %16, %17, %18, %19, %20, %21, %22, %23, %24, %25, %26, %27, %28, %29, %30, %31, %32, %33, %34, %35, %36, %37, %38, %39, %40, %41, %42, %43, %44, %45, %46, %47}, {%60, %61, %62, %63}, tb, p1, 1, 1, 1;\n"
        "}\n"
        : "=f"(d[0]), "=f"(d[1]), "=f"(d[2]), "=f"(d[3]), "=f"(d[4]), "=f"(d[5]), "=f"(d[6]), "=f"(d[7]), "=f"(d[8]), "=f"(d[9]), "=f"(d[10]), "=f"(d[11]), "=f"(d[12]), "=f"(d[13]), "=f"(d[14]), "=f"(d[15]), "=f"(d[16]), "=f"(d[17]), "=f"(d[18]), "=f"(d[19]), "=f"(d[20]), "=f"(d[21]), "=f"(d[22]), "=f"(d[23]), "=f"(d[24]), "=f"(d[25]), "=f"(d[26]), "=f"(d[27]), "=f"(d[28]), "=f"(d[29]), "=f"(d[30]), "=f"(d[31]), "=f"(d[32]), "=f"(d[33]), "=f"(d[34]), "=f"(d[35]), "=f"(d[36]), "=f"(d[37]), "=f"(d[38]), "=f"(d[39]), "=f"(d[40]), "=f"(d[41]), "=f"(d[42]), "=f"(d[43]), "=f"(d[44]), "=f"(d[45]), "=f"(d[46]), "=f"(d[47])
        : "r"(a[AOFF + 0][0]), "r"(a[AOFF + 0][1]), "r"(a[AOFF + 0][2]), "r"(a[AOFF + 0][3]), "r"(a[AOFF + 1][0]), "r"(a[AOFF + 1][1]), "r"(a[AOFF + 1][2]), "r"(a[AOFF + 1][3]), "r"(a[AOFF + 2][0]), "r"(a[AOFF + 2][1]), "r"(a[AOFF + 2][2]), "r"(a[AOFF + 2][3]), "r"(a[AOFF + 3][0]), "r"(a[AOFF + 3][1]), "r"(a[AOFF + 3][2]), "r"(a[AOFF + 3][3]), "l"(descB), "n"(BOFF >> 4));
}
};
template <> struct Rng<1, 0, 4> {
template <int BOFF, int AOFF, int NA>
static __device__ __forceinline__ void run(float (&d)[48], const uint32_t (&a)[NA][4], uint64_t descB) {
    asm volatile(
        "{\n"
        ".reg .pred p0, p1;\n"
        ".reg .b64 ta, ta0, tb, tb0;\n"
        "setp.ne.b32 p0, 0, 0;\n"
        "setp.eq.b32 p1, 0, 0;\n"
        "add.s64 tb0, %64, %65;\n"
        "add.s64 tb, tb0, 0;\n"
        "wgmma.mma_async.sync.aligned.m64n96k16.f32.bf16.bf16 {%0, %1, %2, %3, %4, %5, %6, %7, %8, %9, %10, %11, %12, %13, %14, %15, %16, %17, %18, %19, %20, %21, %22, %23, %24, %25, %26, %27, %28, %29, %30, %31, %32, %33, %34, %35, %36, %37, %38, %39, %40, %41, %42, %43, %44, %45, %46, %47}, {%48, %49, %50, %51}, tb, p0, 1, 1, 1;\n"
        "add.s64 tb, tb0, 32;\n"
        "wgmma.mma_async.sync.aligned.m64n96k16.f32.bf16.bf16 {%0, %1, %2, %3, %4, %5, %6, %7, %8, %9, %10, %11, %12, %13, %14, %15, %16, %17, %18, %19, %20, %21, %22, %23, %24, %25, %26, %27, %28, %29, %30, %31, %32, %33, %34, %35, %36, %37, %38, %39, %40, %41, %42, %43, %44, %45, %46, %47}, {%52, %53, %54, %55}, tb, p1, 1, 1, 1;\n"
        "add.s64 tb, tb0, 64;\n"
        "wgmma.mma_async.sync.aligned.m64n96k16.f32.bf16.bf16 {%0, %1, %2, %3, %4, %5, %6, %7, %8, %9, %10, %11, %12, %13, %14, %15, %16, %17, %18, %19, %20, %21, %22, %23, %24, %25, %26, %27, %28, %29, %30, %31, %32, %33, %34, %35, %36, %37, %38, %39, %40, %41, %42, %43, %44, %45, %46, %47}, {%56, %57, %58, %59}, tb, p1, 1, 1, 1;\n"
        "add.s64 tb, tb0, 96;\n"
        "wgmma.mma_async.sync.aligned.m64n96k16.f32.bf16.bf16 {%0, %1, %2, %3, %4, %5, %6, %7, %8, %9, %10, %11, %12, %13, %14, %15, %16, %17, %18, %19, %20, %21, %22, %23, %24, %25, %26, %27, %28, %29, %30, %31, %32, %33, %34, %35, %36, %37, %38, %39, %40, %41, %42, %43, %44, %45, %46, %47}, {%60, %61, %62, %63}, tb, p1, 1, 1, 1;\n"
        "}\n"
        : "=f"(d[0]), "=f"(d[1]), "=f"(d[2]), "=f"(d[3]), "=f"(d[4]), "=f"(d[5]), "=f"(d[6]), "=f"(d[7]), "=f"(d[8]), "=f"(d[9]), "=f"(d[10]), "=f"(d[11]), "=f"(d[12]), "=f"(d[13]), "=f"(d[14]), "=f"(d[15]), "=f"(d[16]), "=f"(d[17]), "=f"(d[18]), "=f"(d[19]), "=f"(d[20]), "=f"(d[21]), "=f"(d[22]), "=f"(d[23]), "=f"(d[24]), "=f"(d[25]), "=f"(d[26]), "=f"(d[27]), "=f"(d[28]), "=f"(d[29]), "=f"(d[30]), "=f"(d[31]), "=f"(d[32]), "=f"(d[33]), "=f"(d[34]), "=f"(d[35]), "=f"(d[36]), "=f"(d[37]), "=f"(d[38]), "=f"(d[39]), "=f"(d[40]), "=f"(d[41]), "=f"(d[42]), "=f"(d[43]), "=f"(d[44]), "=f"(d[45]), "=f"(d[46]), "=f"(d[47])
        : "r"(a[AOFF + 0][0]), "r"(a[AOFF + 0][1]), "r"(a[AOFF + 0][2]), "r"(a[AOFF + 0][3]), "r"(a[AOFF + 1][0]), "r"(a[AOFF + 1][1]), "r"(a[AOFF + 1][2]), "r"(a[AOFF + 1][3]), "r"(a[AOFF + 2][0]), "r"(a[AOFF + 2][1]), "r"(a[AOFF + 2][2]), "r"(a[AOFF + 2][3]), "r"(a[AOFF + 3][0]), "r"(a[AOFF + 3][1]), "r"(a[AOFF + 3][2]), "r"(a[AOFF + 3][3]), "l"(descB), "n"(BOFF >> 4));
}
};
template <> struct Rng<0, 0, 5> {
template <int BOFF, int AOFF, int NA>
static __device__ __forceinline__ void run(float (&d)[48], const uint32_t (&a)[NA][4], uint64_t descB) {
    asm volatile(
        "{\n"
        ".reg .pred p0, p1;\n"
        ".reg .b64 ta, ta0, tb, tb0;\n"
        "setp.ne.b32 p0, 0, 0;\n"
        "setp.eq.b32 p1, 0, 0;\n"
        "add.s64 tb0, %68, %69;\n"
        "add.s64 tb, tb0, 0;\n"
        "wgmma.mma_async.sync.aligned.m64n96k16.f32.bf16.bf16 {%0, %1, %2, %3, %4, %5, %6, %7, %8, %9, %10, %11, %12, %13, %14, %15, %16, %17, %18, %19, %20, %21, %22, %23, %24, %25, %26, %27, %28, %29, %30, %31, %32, %33, %34, %35, %36, %37, %38, %39, %40, %41, %42, %43, %44, %45, %46, %47}, {%48, %49, %50, %51}, tb, p0, 1, 1, 1;\n"
        "add.s64 tb, tb0, 32;\n"
        "wgmma.mma_async.sync.aligned.m64n96k16.f32.bf16.bf16 {%0, %1, %2, %3, %4, %5, %6, %7, %8, %9, %10, %11, %12, %13, %14, %15, %16, %17, %18, %19, %20, %21, %22, %23, %24, %25, %26, %27, %28, %29, %30, %31, %32, %33, %34, %35, %36, %37, %38, %39, %40, %41, %42, %43, %44, %45, %46, %47}, {%52, %53, %54, %55}, tb, p1, 1, 1, 1;\n"
        "add.s64 tb, tb0, 64;\n"
        "wgmma.mma_async.sync.aligned.m64n96k16.f32.bf16.bf16 {%0, %1, %2, %3, %4, %5, %6, %7, %8, %9, %10, %11, %12, %13, %14, %15, %16, %17, %18, %19, %20, %21, %22, %23, %24, %25, %26, %27, %28, %29, %30, %31, %32, %33, %34, %35, %36, %37, %38, %39, %40, %41, %42, %43, %44, %45, %46, %47}, {%56, %57, %58, %59}, tb, p1, 1, 1, 1;\n"
        "add.s64 tb, tb0, 96;\n"
        "wgmma.mma_async.sync.aligned.m64n96k16.f32.bf16.bf16 {%0, %1, %2, %3, %4, %5, %6, %7, %8, %9, %10, %11, %12, %13, %14, %15, %16, %17, %18, %19, %20, %21, %22, %23, %24, %25, %26, %27, %28, %29, %30, %31, %32, %33, %34, %35, %36, %37, %38, %39, %40, %41, %42, %43, %44, %45, %46, %47}, {%60, %61, %62, %63}, tb, p1, 1, 1, 1;\n"
        "add.s64 tb, tb0, 1536;\n"
        "wgmma.mma_async.sync.aligned.m64n96k16.f32.bf16.bf16 {%0, %1, %2, %3, %4, %5, %6, %7, %8, %9, %10, %11, %12, %13, %14, %15, %16, %17, %18, %19, %20, %21, %22, %23, %24, %25, %26, %27, %28, %29, %30, %31, %32, %33, %34, %35, %36, %37, %38, %39, %40, %41, %42, %43, %44, %45, %46, %47}, {%64, %65, %66, %67}, tb, p1, 1, 1, 1;\n"
        "}\n"
        : "=f"(d[0]), "=f"(d[1]), "=f"(d[2]), "=f"(d[3]), "=f"(d[4]), "=f"(d[5]), "=f"(d[6]), "=f"(d[7]), "=f"(d[8]), "=f"(d[9]), "=f"(d[10]), "=f"(d[11]), "=f"(d[12]), "=f"(d[13]), "=f"(d[14]), "=f"(d[15]), "=f"(d[16]), "=f"(d[17]), "=f"(d[18]), "=f"(d[19]), "=f"(d[20]), "=f"(d[21]), "=f"(d[22]), "=f"(d[23]), "=f"(d[24]), "=f"(d[25]), "=f"(d[26]), "=f"(d[27]), "=f"(d[28]), "=f"(d[29]), "=f"(d[30]), "=f"(d[31]), "=f"(d[32]), "=f"(d[33]), "=f"(d[34]), "=f"(d[35]), "=f"(d[36]), "=f"(d[37]), "=f"(d[38]), "=f"(d[39]), "=f"(d[40]), "=f"(d[41]), "=f"(d[42]), "=f"(d[43]), "=f"(d[44]), "=f"(d[45]), "=f"(d[46]), "=f"(d[47])
        : "r"(a[AOFF + 0][0]), "r"(a[AOFF + 0][1]), "r"(a[AOFF + 0][2]), "r"(a[AOFF + 0][3]), "r"(a[AOFF + 1][0]), "r"(a[AOFF + 1][1]), "r"(a[AOFF + 1][2]), "r"(a[AOFF + 1][3]), "r"(a[AOFF + 2][0]), "r"(a[AOFF + 2][1]), "r"(a[AOFF + 2][2]), "r"(a[AOFF + 2][3]), "r"(a[AOFF + 3][0]), "r"(a[AOFF + 3][1]), "r"(a[AOFF + 3][2]), "r"(a[AOFF + 3][3]), "r"(a[AOFF + 4][0]), "r"(a[AOFF + 4][1]), "r"(a[AOFF + 4][2]), "r"(a[AOFF + 4][3]), "l"(descB), "n"(BOFF >> 4));
}
};
template <> struct Rng<1, 0, 5> {
template <int BOFF, int AOFF, int NA>
static __device__ __forceinline__ void run(float (&d)[48], const uint32_t (&a)[NA][4], uint64_t descB) {
    asm volatile(
        "{\n"
        ".reg .pred p0, p1;\n"
        ".reg .b64 ta, ta0, tb, tb0;\n"
        "setp.ne.b32 p0, 0, 0;\n"
        "setp.eq.b32 p1, 0, 0;\n"
        "add.s64 tb0, %68, %69;\n"
        "add.s64 tb, tb0, 0;\n"
        "wgmma.mma_async.sync.aligned.m64n96k16.f32.bf16.bf16 {%0, %1, %2, %3, %4, %5, %6, %7, %8, %9, %10, %11, %12, %13, %14, %15, %16, %17, %18, %19, %20, %21, %22, %23, %24, %25, %26, %27, %28, %29, %30, %31, %32, %33, %34, %35, %36, %37, %38, %39, %40, %41, %42, %43, %44, %45, %46, %47}, {%48, %49, %50, %51}, tb, p0, 1, 1, 1;\n"
        "add.s64 tb, tb0, 32;\n"
        "wgmma.mma_async.sync.aligned.m64n96k16.f32.bf16.bf16 {%0, %1, %2, %3, %4, %5, %6, %7, %8, %9, %10, %11, %12, %13, %14, %15, %16, %17, %18, %19, %20, %21, %22, %23, %24, %25, %26, %27, %28, %29, %30, %31, %32, %33, %34, %35, %36, %37, %38, %39, %40, %41, %42, %43, %44, %45, %46, %47}, {%52, %53, %54, %55}, tb, p1, 1, 1, 1;\n"
        "add.s64 tb, tb0, 64;\n"
        "wgmma.mma_async.sync.aligned.m64n96k16.f32.bf16.bf16 {%0, %1, %2, %3, %4, %5, %6, %7, %8, %9, %10, %11, %12, %13, %14, %15, %16, %17, %18, %19, %20, %21, %22, %23, %24, %25, %26, %27, %28, %29, %30, %31, %32, %33, %34, %35, %36, %37, %38, %39, %40, %41, %42, %43, %44, %45, %46, %47}, {%56, %57, %58, %59}, tb, p1, 1, 1, 1;\n"
        "add.s64 tb, tb0, 96;\n"
        "wgmma.mma_async.sync.aligned.m64n96k16.f32.bf16.bf16 {%0, %1, %2, %3, %4, %5, %6, %7, %8, %9, %10, %11, %12, %13, %14, %15, %16, %17, %18, %19, %20, %21, %22, %23, %24, %25, %26, %27, %28, %29, %30, %31, %32, %33, %34, %35, %36, %37, %38, %39, %40, %41, %42, %43, %44, %45, %46, %47}, {%60, %61, %62, %63}, tb, p1, 1, 1, 1;\n"
        "add.s64 tb, tb0, 128;\n"
        "wgmma.mma_async.sync.aligned.m64n96k16.f32.bf16.bf16 {%0, %1, %2, %3, %4, %5, %6, %7, %8, %9, %10, %11, %12, %13, %14, %15, %16, %17, %18, %19, %20, %21, %22, %23, %24, %25, %26, %27, %28, %29, %30, %31, %32, %33, %34, %35, %36, %37, %38, %39, %40, %41, %42, %43, %44, %45, %46, %47}, {%64, %65, %66, %67}, tb, p1, 1, 1, 1;\n"
        "}\n"
        : "=f"(d[0]), "=f"(d[1]), "=f"(d[2]), "=f"(d[3]), "=f"(d[4]), "=f"(d[5]), "=f"(d[6]), "=f"(d[7]), "=f"(d[8]), "=f"(d[9]), "=f"(d[10]), "=f"(d[11]), "=f"(d[12]), "=f"(d[13]), "=f"(d[14]), "=f"(d[15]), "=f"(d[16]), "=f"(d[17]), "=f"(d[18]), "=f"(d[19]), "=f"(d[20]), "=f"(d[21]), "=f"(d[22]), "=f"(d[23]), "=f"(d[24]), "=f"(d[25]), "=f"(d[26]), "=f"(d[27]), "=f"(d[28]), "=f"(d[29]), "=f"(d[30]), "=f"(d[31]), "=f"(d[32]), "=f"(d[33]), "=f"(d[34]), "=f"(d[35]), "=f"(d[36]), "=f"(d[37]), "=f"(d[38]), "=f"(d[39]), "=f"(d[40]), "=f"(d[41]), "=f"(d[42]), "=f"(d[43]), "=f"(d[44]), "=f"(d[45]), "=f"(d[46]), "=f"(d[47])
        : "r"(a[AOFF + 0][0]), "r"(a[AOFF + 0][1]), "r"(a[AOFF + 0][2]), "r"(a[AOFF + 0][3]), "r"(a[AOFF + 1][0]), "r"(a[AOFF + 1][1]), "r"(a[AOFF + 1][2]), "r"(a[AOFF + 1][3]), "r"(a[AOFF + 2][0]), "r"(a[AOFF + 2][1]), "r"(a[AOFF + 2][2]), "r"(a[AOFF + 2][3]), "r"(a[AOFF + 3][0]), "r"(a[AOFF + 3][1]), "r"(a[AOFF + 3][2]), "r"(a[AOFF + 3][3]), "r"(a[AOFF + 4][0]), "r"(a[AOFF + 4][1]), "r"(a[AOFF + 4][2]), "r"(a[AOFF + 4][3]), "l"(descB), "n"(BOFF >> 4));
}
};
template <> struct Rng<0, 0, 6> {
template <int BOFF, int AOFF, int NA>
static __device__ __forceinline__ void run(float (&d)[48], const uint32_t (&a)[NA][4], uint64_t descB) {
    asm volatile(
        "{\n"
        ".reg .pred p0, p1;\n"
        ".reg .b64 ta, ta0, tb, tb0;\n"
        "setp.ne.b32 p0, 0, 0;\n"
        "setp.eq.b32 p1, 0, 0;\n"
        "add.s64 tb0, %72, %73;\n"
        "add.s64 tb, tb0, 0;\n"
        "wgmma.mma_async.sync.aligned.m64n96k16.f32.bf16.bf16 {%0, %1, %2, %3, %4, %5, %6, %7, %8, %9, %10, %11, %12, %13, %14, %15, %16, %17, %18, %19, %20, %21, %22, %23, %24, %25, %26, %27, %28, %29, %30, %31, %32, %33, %34, %35, %36, %37, %38, %39, %40, %41, %42, %43, %44, %45, %46, %47}, {%48, %49, %50, %51}, tb, p0, 1, 1, 1;\n"
        "add.s64 tb, tb0, 32;\n"
        "wgmma.mma_async.sync.aligned.m64n96k16.f32.bf16.bf16 {%0, %1, %2, %3, %4, %5, %6, %7, %8, %9, %10, %11, %12, %13, %14, %15, %16, %17, %18, %19, %20, %21, %22, %23, %24, %25, %26, %27, %28, %29, %30, %31, %32, %33, %34, %35, %36, %37, %38, %39, %40, %41, %42, %43, %44, %45, %46, %47}, {%52, %53, %54, %55}, tb, p1, 1, 1, 1;\n"
        "add.s64 tb, tb0, 64;\n"
        "wgmma.mma_async.sync.aligned.m64n96k16.f32.bf16.bf16 {%0, %1, %2, %3, %4, %5, %6, %7, %8, %9, %10, %11, %12, %13, %14, %15, %16, %17, %18, %19, %20, %21, %22, %23, %24, %25, %26, %27, %28, %29, %30, %31, %32, %33, %34, %35, %36, %37, %38, %39, %40, %41, %42, %43, %44, %45, %46, %47}, {%56, %57, %58, %59}, tb, p1, 1, 1, 1;\n"
        "add.s64 tb, tb0, 96;\n"
        "wgmma.mma_async.sync.aligned.m64n96k16.f32.bf16.bf16 {%0, %1, %2, %3, %4, %5, %6, %7, %8, %9, %10, %11, %12, %13, %14, %15, %16, %17, %18, %19, %20, %21, %22, %23, %24, %25, %26, %27, %28, %29, %30, %31, %32, %33, %34, %35, %36, %37, %38, %39, %40, %41, %42, %43, %44, %45, %46, %47}, {%60, %61, %62, %63}, tb, p1, 1, 1, 1;\n"
        "add.s64 tb, tb0, 1536;\n"
        "wgmma.mma_async.sync.aligned.m64n96k16.f32.bf16.bf16 {%0, %1, %2, %3, %4, %5, %6, %7, %8, %9, %10, %11, %12, %13, %14, %15, %16, %17, %18, %19, %20, %21, %22, %23, %24, %25, %26, %27, %28, %29, %30, %31, %32, %33, %34, %35, %36, %37, %38, %39, %40, %41, %42, %43, %44, %45, %46, %47}, {%64, %65, %66, %67}, tb, p1, 1, 1, 1;\n"
        "add.s64 tb, tb0, 1568;\n"
        "wgmma.mma_async.sync.aligned.m64n96k16.f32.bf16.bf16 {%0, %1, %2, %3, %4, %5, %6, %7, %8, %9, %10, %11, %12, %13, %14, %15, %16, %17, %18, %19, %20, %21, %22, %23, %24, %25, %26, %27, %28, %29, %30, %31, %32, %33, %34, %35, %36, %37, %38, %39, %40, %41, %42, %43, %44, %45, %46, %47}, {%68, %69, %70, %71}, tb, p1, 1, 1, 1;\n"
        "}\n"
        : "=f"(d[0]), "=f"(d[1]), "=f"(d[2]), "=f"(d[3]), "=f"(d[4]), "=f"(d[5]), "=f"(d[6]), "=f"(d[7]), "=f"(d[8]), "=f"(d[9]), "=f"(d[10]), "=f"(d[11]), "=f"(d[12]), "=f"(d[13]), "=f"(d[14]), "=f"(d[15]), "=f"(d[16]), "=f"(d[17]), "=f"(d[18]), "=f"(d[19]), "=f"(d[20]), "=f"(d[21]), "=f"(d[22]), "=f"(d[23]), "=f"(d[24]), "=f"(d[25]), "=f"(d[26]), "=f"(d[27]), "=f"(d[28]), "=f"(d[29]), "=f"(d[30]), "=f"(d[31]), "=f"(d[32]), "=f"(d[33]), "=f"(d[34]), "=f"(d[35]), "=f"(d[36]), "=f"(d[37]), "=f"(d[38]), "=f"(d[39]), "=f"(d[40]), "=f"(d[41]), "=f"(d[42]), "=f"(d[43]), "=f"(d[44]), "=f"(d[45]), "=f"(d[46]), "=f"(d[47])
        : "r"(a[AOFF + 0][0]), "r"(a[AOFF + 0][1]), "r"(a[AOFF + 0][2]), "r"(a[AOFF + 0][3]), "r"(a[AOFF + 1][0]), "r"(a[AOFF + 1][1]), "r"(a[AOFF + 1][2]), "r"(a[AOFF + 1][3]), "r"(a[AOFF + 2][0]), "r"(a[AOFF + 2][1]), "r"(a[AOFF + 2][2]), "r"(a[AOFF + 2][3]), "r"(a[AOFF + 3][0]), "r"(a[AOFF + 3][1]), "r"(a[AOFF + 3][2]), "r"(a[AOFF + 3][3]), "r"(a[AOFF + 4][0]), "r"(a[AOFF + 4][1]), "r"(a[AOFF + 4][2]), "r"(a[AOFF + 4][3]), "r"(a[AOFF + 5][0]), "r"(a[AOFF + 5][1]), "r"(a[AOFF + 5][2]), "r"(a[AOFF + 5][3]), "l"(descB), "n"(BOFF >> 4));
}
};
template <> struct Rng<1, 0, 6> {
template <int BOFF, int AOFF, int NA>
static __device__ __forceinline__ void run(float (&d)[48], const uint32_t (&a)[NA][4], uint64_t descB) {
    asm volatile(
        "{\n"
        ".reg .pred p0, p1;\n"
        ".reg .b64 ta, ta0, tb, tb0;\n"
        "setp.ne.b32 p0, 0, 0;\n"
        "setp.eq.b32 p1, 0, 0;\n"
        "add.s64 tb0, %72, %73;\n"
        "add.s64 tb, tb0, 0;\n"
        "wgmma.mma_async.sync.aligned.m64n96k16.f32.bf16.bf16 {%0, %1, %2, %3, %4, %5, %6, %7, %8, %9, %10, %11, %12, %13, %14, %15, %16, %17, %18, %19, %20, %21, %22, %23, %24, %25, %26, %27, %28, %29, %30, %31, %32, %33, %34, %35, %36, %37, %38, %39, %40, %41, %42, %43, %44, %45, %46, %47}, {%48, %49, %50, %51}, tb, p0, 1, 1, 1;\n"
        "add.s64 tb, tb0, 32;\n"
        "wgmma.mma_async.sync.aligned.m64n96k16.f32.bf16.bf16 {%0, %1, %2, %3, %4, %5, %6, %7, %8, %9, %10, %11, %12, %13, %14, %15, %16, %17, %18, %19, %20, %21, %22, %23, %24, %25, %26, %27, %28, %29, %30, %31, %32, %33, %34, %35, %36, %37, %38, %39, %40, %41, %42, %43, %44, %45, %46, %47}, {%52, %53, %54, %55}, tb, p1, 1, 1, 1;\n"
        "add.s64 tb, tb0, 64;\n"
        "wgmma.mma_async.sync.aligned.m64n96k16.f32.bf16.bf16 {%0, %1, %2, %3, %4, %5, %6, %7, %8, %9, %10, %11, %12, %13, %14, %15, %16, %17, %18, %19, %20, %21, %22, %23, %24, %25, %26, %27, %28, %29, %30, %31, %32, %33, %34, %35, %36, %37, %38, %39, %40, %41, %42, %43, %44, %45, %46, %47}, {%56, %57, %58, %59}, tb, p1, 1, 1, 1;\n"
        "add.s64 tb, tb0, 96;\n"
        "wgmma.mma_async.sync.aligned.m64n96k16.f32.bf16.bf16 {%0, %1, %2, %3, %4, %5, %6, %7, %8, %9, %10, %11, %12, %13, %14, %15, %16, %17, %18, %19, %20, %21, %22, %23, %24, %25, %26, %27, %28, %29, %30, %31, %32, %33, %34, %35, %36, %37, %38, %39, %40, %41, %42, %43, %44, %45, %46, %47}, {%60, %61, %62, %63}, tb, p1, 1, 1, 1;\n"
        "add.s64 tb, tb0, 128;\n"
        "wgmma.mma_async.sync.aligned.m64n96k16.f32.bf16.bf16 {%0, %1, %2, %3, %4, %5, %6, %7, %8, %9, %10, %11, %12, %13, %14, %15, %16, %17, %18, %19, %20, %21, %22, %23, %24, %25, %26, %27, %28, %29, %30, %31, %32, %33, %34, %35, %36, %37, %38, %39, %40, %41, %42, %43, %44, %45, %46, %47}, {%64, %65, %66, %67}, tb, p1, 1, 1, 1;\n"
        "add.s64 tb, tb0, 160;\n"
        "wgmma.mma_async.sync.aligned.m64n96k16.f32.bf16.bf16 {%0, %1, %2, %3, %4, %5, %6, %7, %8, %9, %10, %11, %12, %13, %14, %15, %16, %17, %18, %19, %20, %21, %22, %23, %24, %25, %26, %27, %28, %29, %30, %31, %32, %33, %34, %35, %36, %37, %38, %39, %40, %41, %42, %43, %44, %45, %46, %47}, {%68, %69, %70, %71}, tb, p1, 1, 1, 1;\n"
        "}\n"
        : "=f"(d[0]), "=f"(d[1]), "=f"(d[2]), "=f"(d[3]), "=f"(d[4]), "=f"(d[5]), "=f"(d[6]), "=f"(d[7]), "=f"(d[8]), "=f"(d[9]), "=f"(d[10]), "=f"(d[11]), "=f"(d[12]), "=f"(d[13]), "=f"(d[14]), "=f"(d[15]), "=f"(d[16]), "=f"(d[17]), "=f"(d[18]), "=f"(d[19]), "=f"(d[20]), "=f"(d[21]), "=f"(d[22]), "=f"(d[23]), "=f"(d[24]), "=f"(d[25]), "=f"(d[26]), "=f"(d[27]), "=f"(d[28]), "=f"(d[29]), "=f"(d[30]), "=f"(d[31]), "=f"(d[32]), "=f"(d[33]), "=f"(d[34]), "=f"(d[35]), "=f"(d[36]), "=f"(d[37]), "=f"(d[38]), "=f"(d[39]), "=f"(d[40]), "=f"(d[41]), "=f"(d[42]), "=f"(d[43]), "=f"(d[44]), "=f"(d[45]), "=f"(d[46]), "=f"(d[47])
        : "r"(a[AOFF + 0][0]), "r"(a[AOFF + 0][1]), "r"(a[AOFF + 0][2]), "r"(a[AOFF + 0][3]), "r"(a[AOFF + 1][0]), "r"(a[AOFF + 1][1]), "r"(a[AOFF + 1][2]), "r"(a[AOFF + 1][3]), "r"(a[AOFF + 2][0]), "r"(a[AOFF + 2][1]), "r"(a[AOFF + 2][2]), "r"(a[AOFF + 2][3]), "r"(a[AOFF + 3][0]), "r"(a[AOFF + 3][1]), "r"(a[AOFF + 3][2]), "r"(a[AOFF + 3][3]), "r"(a[AOFF + 4][0]), "r"(a[AOFF + 4][1]), "r"(a[AOFF + 4][2]), "r"(a[AOFF + 4][3]), "r"(a[AOFF + 5][0]), "r"(a[AOFF + 5][1]), "r"(a[AOFF + 5][2]), "r"(a[AOFF + 5][3]), "l"(descB), "n"(BOFF >> 4));
}
};
template <> struct Rng<0, 3, 7> {
template <int BOFF, int AOFF, int NA>
static __device__ __forceinline__ void run(float (&d)[48], const uint32_t (&a)[NA][4], uint64_t descB) {
    asm volatile(
        "{\n"
        ".reg .pred p0, p1;\n"
        ".reg .b64 ta, ta0, tb, tb0;\n"
        "setp.ne.b32 p0, 0, 0;\n"
        "setp.eq.b32 p1, 0, 0;\n"
        "add.s64 tb0, %64, %65;\n"
        "add.s64 tb, tb0, 96;\n"
        "wgmma.mma_async.sync.aligned.m64n96k16.f32.bf16.bf16 {%0, %1, %2, %3, %4, %5, %6, %7, %8, %9, %10, %11, %12, %13, %14, %15, %16, %17, %18, %19, %20, %21, %22, %23, %24, %25, %26, %27, %28, %29, %30, %31, %32, %33, %34, %35, %36, %37, %38, %39, %40, %41, %42, %43, %44, %45, %46, %47}, {%48, %49, %50, %51}, tb, p1, 1, 1, 1;\n"
        "add.s64 tb, tb0, 1536;\n"
        "wgmma.mma_async.sync.aligned.m64n96k16.f32.bf16.bf16 {%0, %1, %2, %3, %4, %5, %6, %7, %8, %9, %10, %11, %12, %13, %14, %15, %16, %17, %18, %19, %20, %21, %22, %23, %24, %25, %26, %27, %28, %29, %30, %31, %32, %33, %34, %35, %36, %37, %38, %39, %40, %41, %42, %43, %44, %45, %46, %47}, {%52, %53, %54, %55}, tb, p1, 1, 1, 1;\n"
        "add.s64 tb, tb0, 1568;\n"
        "wgmma.mma_async.sync.aligned.m64n96k16.f32.bf16.bf16 {%0, %1, %2, %3, %4, %5, %6, %7, %8, %9, %10, %11, %12, %13, %14, %15, %16, %17, %18, %19, %20, %21, %22, %23, %24, %25, %26, %27, %28, %29, %30, %31, %32, %33, %34, %35, %36, %37, %38, %39, %40, %41, %42, %43, %44, %45, %46, %47}, {%56, %57, %58, %59}, tb, p1, 1, 1, 1;\n"
        "add.s64 tb, tb0, 1600;\n"
        "wgmma.mma_async.sync.aligned.m64n96k16.f32.bf16.bf16 {%0, %1, %2, %3, %4, %5, %6, %7, %8, %9, %10, %11, %12, %13, %14, %15, %16, %17, %18, %19, %20, %21, %22, %23, %24, %25, %26, %27, %28, %29, %30, %31, %32, %33, %34, %35, %36, %37, %38, %39, %40, %41, %42, %43, %44, %45, %46, %47}, {%60, %61, %62, %63}, tb, p1, 1, 1, 1;\n"
        "}\n"
        : "+f"(d[0]), "+f"(d[1]), "+f"(d[2]), "+f"(d[3]), "+f"(d[4]), "+f"(d[5]), "+f"(d[6]), "+f"(d[7]), "+f"(d[8]), "+f"(d[9]), "+f"(d[10]), "+f"(d[11]), "+f"(d[12]), "+f"(d[13]), "+f"(d[14]), "+f"(d[15]), "+f"(d[16]), "+f"(d[17]), "+f"(d[18]), "+f"(d[19]), "+f"(d[20]), "+f"(d[21]), "+f"(d[22]), "+f"(d[23]), "+f"(d[24]), "+f"(d[25]), "+f"(d[26]), "+f"(d[27]), "+f"(d[28]), "+f"(d[29]), "+f"(d[30]), "+f"(d[31]), "+f"(d[32]), "+f"(d[33]), "+f"(d[34]), "+f"(d[35]), "+f"(d[36]), "+f"(d[37]), "+f"(d[38]), "+f"(d[39]), "+f"(d[40]), "+f"(d[41]), "+f"(d[42]), "+f"(d[43]), "+f"(d[44]), "+f"(d[45]), "+f"(d[46]), "+f"(d[47])
        : "r"(a[AOFF + 0][0]), "r"(a[AOFF + 0][1]), "r"(a[AOFF + 0][2]), "r"(a[AOFF + 0][3]), "r"(a[AOFF + 1][0]), "r"(a[AOFF + 1][1]), "r"(a[AOFF + 1][2]), "r"(a[AOFF + 1][3]), "r"(a[AOFF + 2][0]), "r"(a[AOFF + 2][1]), "r"(a[AOFF + 2][2]), "r"(a[AOFF + 2][3]), "r"(a[AOFF + 3][0]), "r"(a[AOFF + 3][1]), "r"(a[AOFF + 3][2]), "r"(a[AOFF + 3][3]), "l"(descB), "n"(BOFF >> 4));
}
};
template <> struct Rng<1, 3, 7> {
template <int BOFF, int AOFF, int NA>
static __device__ __forceinline__ void run(float (&d)[48], const uint32_t (&a)[NA][4], uint64_t descB) {
    asm volatile(
        "{\n"
        ".reg .pred p0, p1;\n"
        ".reg .b64 ta, ta0, tb, tb0;\n"
        "setp.ne.b32 p0, 0, 0;\n"
        "setp.eq.b32 p1, 0, 0;\n"
        "add.s64 tb0, %64, %65;\n"
        "add.s64 tb, tb0, 96;\n"
        "wgmma.mma_async.sync.aligned.m64n96k16.f32.bf16.bf16 {%0, %1, %2, %3, %4, %5, %6, %7, %8, %9, %10, %11, %12, %13, %14, %15, %16, %17, %18, %19, %20, %21, %22, %23, %24, %25, %26, %27, %28, %29, %30, %31, %32, %33, %34, %35, %36, %37, %38, %39, %40, %41, %42, %43, %44, %45, %46, %47}, {%48, %49, %50, %51}, tb, p1, 1, 1, 1;\n"
        "add.s64 tb, tb0, 128;\n"
        "wgmma.mma_async.sync.aligned.m64n96k16.f32.bf16.bf16 {%0, %1, %2, %3, %4, %5, %6, %7, %8, %9, %10, %11, %12, %13, %14, %15, %16, %17, %18, %19, %20, %21, %22, %23, %24, %25, %26, %27, %28, %29, %30, %31, %32, %33, %34, %35, %36, %37, %38, %39, %40, %41, %42, %43, %44, %45, %46, %47}, {%52, %53, %54, %55}, tb, p1, 1, 1, 1;\n"
        "add.s64 tb, tb0, 160;\n"
        "wgmma.mma_async.sync.aligned.m64n96k16.f32.bf16.bf16 {%0, %1, %2, %3, %4, %5, %6, %7, %8, %9, %10, %11, %12, %13, %14, %15, %16, %17, %18, %19, %20, %21, %22, %23, %24, %25, %26, %27, %28, %29, %30, %31, %32, %33, %34, %35, %36, %37, %38, %39, %40, %41, %42, %43, %44, %45, %46, %47}, {%56, %57, %58, %59}, tb, p1, 1, 1, 1;\n"
        "add.s64 tb, tb0, 192;\n"
        "wgmma.mma_async.sync.aligned.m64n96k16.f32.bf16.bf16 {%0, %1, %2, %3, %4, %5, %6, %7, %8, %9, %10, %11, %12, %13, %14, %15, %16, %17, %18, %19, %20, %21, %22, %23, %24, %25, %26, %27, %28, %29, %30, %31, %32, %33, %34, %35, %36, %37, %38, %39, %40, %41, %42, %43, %44, %45, %46, %47}, {%60, %61, %62, %63}, tb, p1, 1, 1, 1;\n"
        "}\n"
        : "+f"(d[0]), "+f"(d[1]), "+f"(d[2]), "+f"(d[3]), "+f"(d[4]), "+f"(d[5]), "+f"(d[6]), "+f"(d[7]), "+f"(d[8]), "+f"(d[9]), "+f"(d[10]), "+f"(d[11]), "+f"(d[12]), "+f"(d[13]), "+f"(d[14]), "+f"(d[15]), "+f"(d[16]), "+f"(d[17]), "+f"(d[18]), "+f"(d[19]), "+f"(d[20]), "+f"(d[21]), "+f"(d[22]), "+f"(d[23]), "+f"(d[24]), "+f"(d[25]), "+f"(d[26]), "+f"(d[27]), "+f"(d[28]), "+f"(d[29]), "+f"(d[30]), "+f"(d[31]), "+f"(d[32]), "+f"(d[33]), "+f"(d[34]), "+f"(d[35]), "+f"(d[36]), "+f"(d[37]), "+f"(d[38]), "+f"(d[39]), "+f"(d[40]), "+f"(d[41]), "+f"(d[42]), "+f"(d[43]), "+f"(d[44]), "+f"(d[45]), "+f"(d[46]), "+f"(d[47])
        : "r"(a[AOFF + 0][0]), "r"(a[AOFF + 0][1]), "r"(a[AOFF + 0][2]), "r"(a[AOFF + 0][3]), "r"(a[AOFF + 1][0]), "r"(a[AOFF + 1][1]), "r"(a[AOFF + 1][2]), "r"(a[AOFF + 1][3]), "r"(a[AOFF + 2][0]), "r"(a[AOFF + 2][1]), "r"(a[AOFF + 2][2]), "r"(a[AOFF + 2][3]), "r"(a[AOFF + 3][0]), "r"(a[AOFF + 3][1]), "r"(a[AOFF + 3][2]), "r"(a[AOFF + 3][3]), "l"(descB), "n"(BOFF >> 4));
}
};
template <> struct Rng<0, 3, 8> {
template <int BOFF, int AOFF, int NA>
static __device__ __forceinline__ void run(float (&d)[48], const uint32_t (&a)[NA][4], uint64_t descB) {
    asm volatile(
        "{\n"
        ".reg .pred p0, p1;\n"
        ".reg .b64 ta, ta0, tb, tb0;\n"
        "setp.ne.b32 p0, 0, 0;\n"
        "setp.eq.b32 p1, 0, 0;\n"
        "add.s64 tb0, %68, %69;\n"
        "add.s64 tb, tb0, 96;\n"
        "wgmma.mma_async.sync.aligned.m64n96k16.f32.bf16.bf16 {%0, %1, %2, %3, %4, %5, %6, %7, %8, %9, %10, %11, %12, %13, %14, %15, %16, %17, %18, %19, %20, %21, %22, %23, %24, %25, %26, %27, %28, %29, %30, %31, %32, %33, %34, %35, %36, %37, %38, %39, %40, %41, %42, %43, %44, %45, %46, %47}, {%48, %49, %50, %51}, tb, p1, 1, 1, 1;\n"
        "add.s64 tb, tb0, 1536;\n"
        "wgmma.mma_async.sync.aligned.m64n96k16.f32.bf16.bf16 {%0, %1, %2, %3, %4, %5, %6, %7, %8, %9, %10, %11, %12, %13, %14, %15, %16, %17, %18, %19, %20, %21, %22, %23, %24, %25, %26, %27, %28, %29, %30, %31, %32, %33, %34, %35, %36, %37, %38, %39, %40, %41, %42, %43, %44, %45, %46, %47}, {%52, %53, %54, %55}, tb, p1, 1, 1, 1;\n"
        "add.s64 tb, tb0, 1568;\n"
        "wgmma.mma_async.sync.aligned.m64n96k16.f32.bf16.bf16 {%0, %1, %2, %3, %4, %5, %6, %7, %8, %9, %10, %11, %12, %13, %14, %15, %16, %17, %18, %19, %20, %21, %22, %23, %24, %25, %26, %27, %28, %29, %30, %31, %32, %33, %34, %35, %36, %37, %38, %39, %40, %41, %42, %43, %44, %45, %46, %47}, {%56, %57, %58, %59}, tb, p1, 1, 1, 1;\n"
        "add.s64 tb, tb0, 1600;\n"
        "wgmma.mma_async.sync.aligned.m64n96k16.f32.bf16.bf16 {%0, %1, %2, %3, %4, %5, %6, %7, %8, %9, %10, %11, %12, %13, %14, %15, %16, %17, %18, %19, %20, %21, %22, %23, %24, %25, %26, %27, %28, %29, %30, %31, %32, %33, %34, %35, %36, %37, %38, %39, %40, %41, %42, %43, %44, %45, %46, %47}, {%60, %61, %62, %63}, tb, p1, 1, 1, 1;\n"
        "add.s64 tb, tb0, 1632;\n"
        "wgmma.mma_async.sync.aligned.m64n96k16.f32.bf16.bf16 {%0, %1, %2, %3, %4, %5, %6, %7, %8, %9, %10, %11, %12, %13, %14, %15, %16, %17, %18, %19, %20, %21, %22, %23, %24, %25, %26, %27, %28, %29, %30, %31, %32, %33, %34, %35, %36, %37, %38, %39, %40, %41, %42, %43, %44, %45, %46, %47}, {%64, %65, %66, %67}, tb, p1, 1, 1, 1;\n"
        "}\n"
        : "+f"(d[0]), "+f"(d[1]), "+f"(d[2]), "+f"(d[3]), "+f"(d[4]), "+f"(d[5]), "+f"(d[6]), "+f"(d[7]), "+f"(d[8]), "+f"(d[9]), "+f"(d[10]), "+f"(d[11]), "+f"(d[12]), "+f"(d[13]), "+f"(d[14]), "+f"(d[15]), "+f"(d[16]), "+f"(d[17]), "+f"(d[18]), "+f"(d[19]), "+f"(d[20]), "+f"(d[21]), "+f"(d[22]), "+f"(d[23]), "+f"(d[24]), "+f"(d[25]), "+f"(d[26]), "+f"(d[27]), "+f"(d[28]), "+f"(d[29]), "+f"(d[30]), "+f"(d[31]), "+f"(d[32]), "+f"(d[33]), "+f"(d[34]), "+f"(d[35]), "+f"(d[36]), "+f"(d[37]), "+f"(d[38]), "+f"(d[39]), "+f"(d[40]), "+f"(d[41]), "+f"(d[42]), "+f"(d[43]), "+f"(d[44]), "+f"(d[45]), "+f"(d[46]), "+f"(d[47])
        : "r"(a[AOFF + 0][0]), "r"(a[AOFF + 0][1]), "r"(a[AOFF + 0][2]), "r"(a[AOFF + 0][3]), "r"(a[AOFF + 1][0]), "r"(a[AOFF + 1][1]), "r"(a[AOFF + 1][2]), "r"(a[AOFF + 1][3]), "r"(a[AOFF + 2][0]), "r"(a[AOFF + 2][1]), "r"(a[AOFF + 2][2]), "r"(a[AOFF + 2][3]), "r"(a[AOFF + 3][0]), "r"(a[AOFF + 3][1]), "r"(a[AOFF + 3][2]), "r"(a[AOFF + 3][3]), "r"(a[AOFF + 4][0]), "r"(a[AOFF + 4][1]), "r"(a[AOFF + 4][2]), "r"(a[AOFF + 4][3]), "l"(descB), "n"(BOFF >> 4));
}
};
template <> struct Rng<1, 3, 8> {
template <int BOFF, int AOFF, int NA>
static __device__ __forceinline__ void run(float (&d)[48], const uint32_t (&a)[NA][4], uint64_t descB) {
    asm volatile(
        "{\n"
        ".reg .pred p0, p1;\n"
        ".reg .b64 ta, ta0, tb, tb0;\n"
        "setp.ne.b32 p0, 0, 0;\n"
        "setp.eq.b32 p1, 0, 0;\n"
        "add.s64 tb0, %68, %69;\n"
        "add.s64 tb, tb0, 96;\n"
        "wgmma.mma_async.sync.aligned.m64n96k16.f32.bf16.bf16 {%0, %1, %2, %3, %4, %5, %6, %7, %8, %9, %10, %11, %12, %13, %14, %15, %16, %17, %18, %19, %20, %21, %22, %23, %24, %25, %26, %27, %28, %29, %30, %31, %32, %33, %34, %35, %36, %37, %38, %39, %40, %41, %42, %43, %44, %45, %46, %47}, {%48, %49, %50, %51}, tb, p1, 1, 1, 1;\n"
        "add.s64 tb, tb0, 128;\n"
        "wgmma.mma_async.sync.aligned.m64n96k16.f32.bf16.bf16 {%0, %1, %2, %3, %4, %5, %6, %7, %8, %9, %10, %11, %12, %13, %14, %15, %16, %17, %18, %19, %20, %21, %22, %23, %24, %25, %26, %27, %28, %29, %30, %31, %32, %33, %34, %35, %36, %37, %38, %39, %40, %41, %42, %43, %44, %45, %46, %47}, {%52, %53, %54, %55}, tb, p1, 1, 1, 1;\n"
        "add.s64 tb, tb0, 160;\n"
        "wgmma.mma_async.sync.aligned.m64n96k16.f32.bf16.bf16 {%0, %1, %2, %3, %4, %5, %6, %7, %8, %9, %10, %11, %12, %13, %14, %15, %16, %17, %18, %19, %20, %21, %22, %23, %24, %25, %26, %27, %28, %29, %30, %31, %32, %33, %34, %35, %36, %37, %38, %39, %40, %41, %42, %43, %44, %45, %46, %47}, {%56, %57, %58, %59}, tb, p1, 1, 1, 1;\n"
        "add.s64 tb, tb0, 192;\n"
        "wgmma.mma_async.sync.aligned.m64n96k16.f32.bf16.bf16 {%0, %1, %2, %3, %4, %5, %6, %7, %8, %9, %10, %11, %12, %13, %14, %15, %16, %17, %18, %19, %20, %21, %22, %23, %24, %25, %26, %27, %28, %29, %30, %31, %32, %33, %34, %35, %36, %37, %38, %39, %40, %41, %42, %43, %44, %45, %46, %47}, {%60, %61, %62, %63}, tb, p1, 1, 1, 1;\n"
        "add.s64 tb, tb0, 224;\n"
        "wgmma.mma_async.sync.aligned.m64n96k16.f32.bf16.bf16 {%0, %1, %2, %3, %4, %5, %6, %7, %8, %9, %10, %11, %12, %13, %14, %15, %16, %17, %18, %19, %20, %21, %22, %23, %24, %25, %26, %27, %28, %29, %30, %31, %32, %33, %34, %35, %36, %37, %38, %39, %40, %41, %42, %43, %44, %45, %46, %47}, {%64, %65, %66, %67}, tb, p1, 1, 1, 1;\n"
        "}\n"
        : "+f"(d[0]), "+f"(d[1]), "+f"(d[2]), "+f"(d[3]), "+f"(d[4]), "+f"(d[5]), "+f"(d[6]), "+f"(d[7]), "+f"(d[8]), "+f"(d[9]), "+f"(d[10]), "+f"(d[11]), "+f"(d[12]), "+f"(d[13]), "+f"(d[14]), "+f"(d[15]), "+f"(d[16]), "+f"(d[17]), "+f"(d[18]), "+f"(d[19]), "+f"(d[20]), "+f"(d[21]), "+f"(d[22]), "+f"(d[23]), "+f"(d[24]), "+f"(d[25]), "+f"(d[26]), "+f"(d[27]), "+f"(d[28]), "+f"(d[29]), "+f"(d[30]), "+f"(d[31]), "+f"(d[32]), "+f"(d[33]), "+f"(d[34]), "+f"(d[35]), "+f"(d[36]), "+f"(d[37]), "+f"(d[38]), "+f"(d[39]), "+f"(d[40]), "+f"(d[41]), "+f"(d[42]), "+f"(d[43]), "+f"(d[44]), "+f"(d[45]), "+f"(d[46]), "+f"(d[47])
        : "r"(a[AOFF + 0][0]), "r"(a[AOFF + 0][1]), "r"(a[AOFF + 0][2]), "r"(a[AOFF + 0][3]), "r"(a[AOFF + 1][0]), "r"(a[AOFF + 1][1]), "r"(a[AOFF + 1][2]), "r"(a[AOFF + 1][3]), "r"(a[AOFF + 2][0]), "r"(a[AOFF + 2][1]), "r"(a[AOFF + 2][2]), "r"(a[AOFF + 2][3]), "r"(a[AOFF + 3][0]), "r"(a[AOFF + 3][1]), "r"(a[AOFF + 3][2]), "r"(a[AOFF + 3][3]), "r"(a[AOFF + 4][0]), "r"(a[AOFF + 4][1]), "r"(a[AOFF + 4][2]), "r"(a[AOFF + 4][3]), "l"(descB), "n"(BOFF >> 4));
}
};
template <> struct Rng<0, 3, 12> {
template <int BOFF, int AOFF, int NA>
static __device__ __forceinline__ void run(float (&d)[48], const uint32_t (&a)[NA][4], uint64_t descB) {
    asm volatile(
        "{\n"
        ".reg .pred p0, p1;\n"
        ".reg .b64 ta, ta0, tb, tb0;\n"
        "setp.ne.b32 p0, 0, 0;\n"
        "setp.eq.b32 p1, 0, 0;\n"
        "add.s64 tb0, %84, %85;\n"
        "add.s64 tb, tb0, 96;\n"
        "wgmma.mma_async.sync.aligned.m64n96k16.f32.bf16.bf16 {%0, %1, %2, %3, %4, %5, %6, %7, %8, %9, %10, %11, %12, %13, %14, %15, %16, %17, %18, %19, %20, %21, %22, %23, %24, %25, %26, %27, %28, %29, %30, %31, %32, %33, %34, %35, %36, %37, %38, %39, %40, %41, %42, %43, %44, %45, %46, %47}, {%48, %49, %50, %51}, tb, p1, 1, 1, 1;\n"
        "add.s64 tb, tb0, 1536;\n"
        "wgmma.mma_async.sync.aligned.m64n96k16.f32.bf16.bf16 {%0, %1, %2, %3, %4, %5, %6, %7, %8, %9, %10, %11, %12, %13, %14, %15, %16, %17, %18, %19, %20, %21, %22, %23, %24, %25, %26, %27, %28, %29, %30, %31, %32, %33, %34, %35, %36, %37, %38, %39, %40, %41, %42, %43, %44, %45, %46, %47}, {%52, %53, %54, %55}, tb, p1, 1, 1, 1;\n"
        "add.s64 tb, tb0, 1568;\n"
        "wgmma.mma_async.sync.aligned.m64n96k16.f32.bf16.bf16 {%0, %1, %2, %3, %4, %5, %6, %7, %8, %9, %10, %11, %12, %13, %14, %15, %16, %17, %18, %19, %20, %21, %22, %23, %24, %25, %26, %27, %28, %29, %30, %31, %32, %33, %34, %35, %36, %37, %38, %39, %40, %41, %42, %43, %44, %45, %46, %47}, {%56, %57, %58, %59}, tb, p1, 1, 1, 1;\n"
        "add.s64 tb, tb0, 1600;\n"
        "wgmma.mma_async.sync.aligned.m64n96k16.f32.bf16.bf16 {%0, %1, %2, %3, %4, %5, %6, %7, %8, %9, %10, %11, %12, %13, %14, %15, %16, %17, %18, %19, %20, %21, %22, %23, %24, %25, %26, %27, %28, %29, %30, %31, %32, %33, %34, %35, %36, %37, %38, %39, %40, %41, %42, %43, %44, %45, %46, %47}, {%60, %61, %62, %63}, tb, p1, 1, 1, 1;\n"
        "add.s64 tb, tb0, 1632;\n"
        "wgmma.mma_async.sync.aligned.m64n96k16.f32.bf16.bf16 {%0, %1, %2, %3, %4, %5, %6, %7, %8, %9, %10, %11, %12, %13, %14, %15, %16, %17, %18, %19, %20, %21, %22, %23, %24, %25, %26, %27, %28, %29, %30, %31, %32, %33, %34, %35, %36, %37, %38, %39, %40, %41, %42, %43, %44, %45, %46, %47}, {%64, %65, %66, %67}, tb, p1, 1, 1, 1;\n"
        "add.s64 tb, tb0, 3072;\n"
        "wgmma.mma_async.sync.aligned.m64n96k16.f32.bf16.bf16 {%0, %1, %2, %3, %4, %5, %6, %7, %8, %9, %10, %11, %12, %13, %14, %15, %16, %17, %18, %19, %20, %21, %22, %23, %24, %25, %26, %27, %28, %29, %30, %31, %32, %33, %34, %35, %36, %37, %38, %39, %40, %41, %42, %43, %44, %45, %46, %47}, {%68, %69, %70, %71}, tb, p1, 1, 1, 1;\n"
        "add.s64 tb, tb0, 3104;\n"
        "wgmma.mma_async.sync.aligned.m64n96k16.f32.bf16.bf16 {%0, %1, %2, %3, %4, %5, %6, %7, %8, %9, %10, %11, %12, %13, %14, %15, %16, %17, %18, %19, %20, %21, %22, %23, %24, %25, %26, %27, %28, %29, %30, %31, %32, %33, %34, %35, %36, %37, %38, %39, %40, %41, %42, %43, %44, %45, %46, %47}, {%72, %73, %74, %75}, tb, p1, 1, 1, 1;\n"
        "add.s64 tb, tb0, 3136;\n"
        "wgmma.mma_async.sync.aligned.m64n96k16.f32.bf16.bf16 {%0, %1, %2, %3, %4, %5, %6, %7, %8, %9, %10, %11, %12, %13, %14, %15, %16, %17, %18, %19, %20, %21, %22, %23, %24, %25, %26, %27, %28, %29, %30, %31, %32, %33, %34, %35, %36, %37, %38, %39, %40, %41, %42, %43, %44, %45, %46, %47}, {%76, %77, %78, %79}, tb, p1, 1, 1, 1;\n"
        "add.s64 tb, tb0, 3168;\n"
        "wgmma.mma_async.sync.aligned.m64n96k16.f32.bf16.bf16 {%0, %1, %2, %3, %4, %5, %6, %7, %8, %9, %10, %11, %12, %13, %14, %15, %16, %17, %18, %19, %20, %21, %22, %23, %24, %25, %26, %27, %28, %29, %30, %31, %32, %33, %34, %35, %36, %37, %38, %39, %40, %41, %42, %43, %44, %45, %46, %47}, {%80, %81, %82, %83}, tb, p1, 1, 1, 1;\n"
        "}\n"
        : "+f"(d[0]), "+f"(d[1]), "+f"(d[2]), "+f"(d[3]), "+f"(d[4]), "+f"(d[5]), "+f"(d[6]), "+f"(d[7]), "+f"(d[8]), "+f"(d[9]), "+f"(d[10]), "+f"(d[11]), "+f"(d[12]), "+f"(d[13]), "+f"(d[14]), "+f"(d[15]), "+f"(d[16]), "+f"(d[17]), "+f"(d[18]), "+f"(d[19]), "+f"(d[20]), "+f"(d[21]), "+f"(d[22]), "+f"(d[23]), "+f"(d[24]), "+f"(d[25]), "+f"(d[26]), "+f"(d[27]), "+f"(d[28]), "+f"(d[29]), "+f"(d[30]), "+f"(d[31]), "+f"(d[32]), "+f"(d[33]), "+f"(d[34]), "+f"(d[35]), "+f"(d[36]), "+f"(d[37]), "+f"(d[38]), "+f"(d[39]), "+f"(d[40]), "+f"(d[41]), "+f"(d[42]), "+f"(d[43]), "+f"(d[44]), "+f"(d[45]), "+f"(d[46]), "+f"(d[47])
        : "r"(a[AOFF + 0][0]), "r"(a[AOFF + 0][1]), "r"(a[AOFF + 0][2]), "r"(a[AOFF + 0][3]), "r"(a[AOFF + 1][0]), "r"(a[AOFF + 1][1]), "r"(a[AOFF + 1][2]), "r"(a[AOFF + 1][3]), "r"(a[AOFF + 2][0]), "r"(a[AOFF + 2][1]), "r"(a[AOFF + 2][2]), "r"(a[AOFF + 2][3]), "r"(a[AOFF + 3][0]), "r"(a[AOFF + 3][1]), "r"(a[AOFF + 3][2]), "r"(a[AOFF + 3][3]), "r"(a[AOFF + 4][0]), "r"(a[AOFF + 4][1]), "r"(a[AOFF + 4][2]), "r"(a[AOFF + 4][3]), "r"(a[AOFF + 5][0]), "r"(a[AOFF + 5][1]), "r"(a[AOFF + 5][2]), "r"(a[AOFF + 5][3]), "r"(a[AOFF + 6][0]), "r"(a[AOFF + 6][1]), "r"(a[AOFF + 6][2]), "r"(a[AOFF + 6][3]), "r"(a[AOFF + 7][0]), "r"(a[AOFF + 7][1]), "r"(a[AOFF + 7][2]), "r"(a[AOFF + 7][3]), "r"(a[AOFF + 8][0]), "r"(a[AOFF + 8][1]), "r"(a[AOFF + 8][2]), "r"(a[AOFF + 8][3]), "l"(descB), "n"(BOFF >> 4));
}
};
template <> struct Rng<1, 3, 12> {
template <int BOFF, int AOFF, int NA>
static __device__ __forceinline__ void run(float (&d)[48], const uint32_t (&a)[NA][4], uint64_t descB) {
    asm volatile(
        "{\n"
        ".reg .pred p0, p1;\n"
        ".reg .b64 ta, ta0, tb, tb0;\n"
        "setp.ne.b32 p0, 0, 0;\n"
        "setp.eq.b32 p1, 0, 0;\n"
        "add.s64 tb0, %84, %85;\n"
        "add.s64 tb, tb0, 96;\n"
        "wgmma.mma_async.sync.aligned.m64n96k16.f32.bf16.bf16 {%0, %1, %2, %3, %4, %5, %6, %7, %8, %9, %10, %11, %12, %13, %14, %15, %16, %17, %18, %19, %20, %21, %22, %23, %24, %25, %26, %27, %28, %29, %30, %31, %32, %33, %34, %35, %36, %37, %38, %39, %40, %41, %42, %43, %44, %45, %46, %47}, {%48, %49, %50, %51}, tb, p1, 1, 1, 1;\n"
        "add.s64 tb, tb0, 128;\n"
        "wgmma.mma_async.sync.aligned.m64n96k16.f32.bf16.bf16 {%0, %1, %2, %3, %4, %5, %6, %7, %8, %9, %10, %11, %12, %13, %14, %15, %16, %17, %18, %19, %20, %21, %22, %23, %24, %25, %26, %27, %28, %29, %30, %31, %32, %33, %34, %35, %36, %37, %38, %39, %40, %41, %42, %43, %44, %45, %46, %47}, {%52, %53, %54, %55}, tb, p1, 1, 1, 1;\n"
        "add.s64 tb, tb0, 160;\n"
        "wgmma.mma_async.sync.aligned.m64n96k16.f32.bf16.bf16 {%0, %1, %2, %3, %4, %5, %6, %7, %8, %9, %10, %11, %12, %13, %14, %15, %16, %17, %18, %19, %20, %21, %22, %23, %24, %25, %26, %27, %28, %29, %30, %31, %32, %33, %34, %35, %36, %37, %38, %39, %40, %41, %42, %43, %44, %45, %46, %47}, {%56, %57, %58, %59}, tb, p1, 1, 1, 1;\n"
        "add.s64 tb, tb0, 192;\n"
        "wgmma.mma_async.sync.aligned.m64n96k16.f32.bf16.bf16 {%0, %1, %2, %3, %4, %5, %6, %7, %8, %9, %10, %11, %12, %13, %14, %15, %16, %17, %18, %19, %20, %21, %22, %23, %24, %25, %26, %27, %28, %29, %30, %31, %32, %33, %34, %35, %36, %37, %38, %39, %40, %41, %42, %43, %44, %45, %46, %47}, {%60, %61, %62, %63}, tb, p1, 1, 1, 1;\n"
        "add.s64 tb, tb0, 224;\n"
        "wgmma.mma_async.sync.aligned.m64n96k16.f32.bf16.bf16 {%0, %1, %2, %3, %4, %5, %6, %7, %8, %9, %10, %11, %12, %13, %14, %15, %16, %17, %18, %19, %20, %21, %22, %23, %24, %25, %26, %27, %28, %29, %30, %31, %32, %33, %34, %35, %36, %37, %38, %39, %40, %41, %42, %43, %44, %45, %46, %47}, {%64, %65, %66, %67}, tb, p1, 1, 1, 1;\n"
        "add.s64 tb, tb0, 256;\n"
        "wgmma.mma_async.sync.aligned.m64n96k16.f32.bf16.bf16 {%0, %1, %2, %3, %4, %5, %6, %7, %8, %9, %10, %11, %12, %13, %14, %15, %16, %17, %18, %19, %20, %21, %22, %23, %24, %25, %26, %27, %28, %29, %30, %31, %32, %33, %34, %35, %36, %37, %38, %39, %40, %41, %42, %43, %44, %45, %46, %47}, {%68, %69, %70, %71}, tb, p1, 1, 1, 1;\n"
        "add.s64 tb, tb0, 288;\n"
        "wgmma.mma_async.sync.aligned.m64n96k16.f32.bf16.bf16 {%0, %1, %2, %3, %4, %5, %6, %7, %8, %9, %10, %11, %12, %13, %14, %15, %16, %17, %18, %19, %20, %21, %22, %23, %24, %25, %26, %27, %28, %29, %30, %31, %32, %33, %34, %35, %36, %37, %38, %39, %40, %41, %42, %43, %44, %45, %46, %47}, {%72, %73, %74, %75}, tb, p1, 1, 1, 1;\n"
        "add.s64 tb, tb0, 320;\n"
        "wgmma.mma_async.sync.aligned.m64n96k16.f32.bf16.bf16 {%0, %1, %2, %3, %4, %5, %6, %7, %8, %9, %10, %11, %12, %13, %14, %15, %16, %17, %18, %19, %20, %21, %22, %23, %24, %25, %26, %27, %28, %29, %30, %31, %32, %33, %34, %35, %36, %37, %38, %39, %40, %41, %42, %43, %44, %45, %46, %47}, {%76, %77, %78, %79}, tb, p1, 1, 1, 1;\n"
        "add.s64 tb, tb0, 352;\n"
        "wgmma.mma_async.sync.aligned.m64n96k16.f32.bf16.bf16 {%0, %1, %2, %3, %4, %5, %6, %7, %8, %9, %10, %11, %12, %13, %14, %15, %16, %17, %18, %19, %20, %21, %22, %23, %24, %25, %26, %27, %28, %29, %30, %31, %32, %33, %34, %35, %36, %37, %38, %39, %40, %41, %42, %43, %44, %45, %46, %47}, {%80, %81, %82, %83}, tb, p1, 1, 1, 1;\n"
        "}\n"
        : "+f"(d[0]), "+f"(d[1]), "+f"(d[2]), "+f"(d[3]), "+f"(d[4]), "+f"(d[5]), "+f"(d[6]), "+f"(d[7]), "+f"(d[8]), "+f"(d[9]), "+f"(d[10]), "+f"(d[11]), "+f"(d[12]), "+f"(d[13]), "+f"(d[14]), "+f"(d[15]), "+f"(d[16]), "+f"(d[17]), "+f"(d[18]), "+f"(d[19]), "+f"(d[20]), "+f"(d[21]), "+f"(d[22]), "+f"(d[23]), "+f"(d[24]), "+f"(d[25]), "+f"(d[26]), "+f"(d[27]), "+f"(d[28]), "+f"(d[29]), "+f"(d[30]), "+f"(d[31]), "+f"(d[32]), "+f"(d[33]), "+f"(d[34]), "+f"(d[35]), "+f"(d[36]), "+f"(d[37]), "+f"(d[38]), "+f"(d[39]), "+f"(d[40]), "+f"(d[41]), "+f"(d[42]), "+f"(d[43]), "+f"(d[44]), "+f"(d[45]), "+f"(d[46]), "+f"(d[47])
        : "r"(a[AOFF + 0][0]), "r"(a[AOFF + 0][1]), "r"(a[AOFF + 0][2]), "r"(a[AOFF + 0][3]), "r"(a[AOFF + 1][0]), "r"(a[AOFF + 1][1]), "r"(a[AOFF + 1][2]), "r"(a[AOFF + 1][3]), "r"(a[AOFF + 2][0]), "r"(a[AOFF + 2][1]), "r"(a[AOFF + 2][2]), "r"(a[AOFF + 2][3]), "r"(a[AOFF + 3][0]), "r"(a[AOFF + 3][1]), "r"(a[AOFF + 3][2]), "r"(a[AOFF + 3][3]), "r"(a[AOFF + 4][0]), "r"(a[AOFF + 4][1]), "r"(a[AOFF + 4][2]), "r"(a[AOFF + 4][3]), "r"(a[AOFF + 5][0]), "r"(a[AOFF + 5][1]), "r"(a[AOFF + 5][2]), "r"(a[AOFF + 5][3]), "r"(a[AOFF + 6][0]), "r"(a[AOFF + 6][1]), "r"(a[AOFF + 6][2]), "r"(a[AOFF + 6][3]), "r"(a[AOFF + 7][0]), "r"(a[AOFF + 7][1]), "r"(a[AOFF + 7][2]), "r"(a[AOFF + 7][3]), "r"(a[AOFF + 8][0]), "r"(a[AOFF + 8][1]), "r"(a[AOFF + 8][2]), "r"(a[AOFF + 8][3]), "l"(descB), "n"(BOFF >> 4));
}
};
template <> struct Rng<0, 4, 6> {
template <int BOFF, int AOFF, int NA>
static __device__ __forceinline__ void run(float (&d)[48], const uint32_t (&a)[NA][4], uint64_t descB) {
    asm volatile(
        "{\n"
        ".reg .pred p0, p1;\n"
        ".reg .b64 ta, ta0, tb, tb0;\n"
        "setp.ne.b32 p0, 0, 0;\n"
        "setp.eq.b32 p1, 0, 0;\n"
        "add.s64 tb0, %56, %57;\n"
        "add.s64 tb, tb0, 1536;\n"
        "wgmma.mma_async.sync.aligned.m64n96k16.f32.bf16.bf16 {%0, %1, %2, %3, %4, %5, %6, %7, %8, %9, %10, %11, %12, %13, %14, %15, %16, %17, %18, %19, %20, %21, %22, %23, %24, %25, %26, %27, %28, %29, %30, %31, %32, %33, %34, %35, %36, %37, %38, %39, %40, %41, %42, %43, %44, %45, %46, %47}, {%48, %49, %50, %51}, tb, p1, 1, 1, 1;\n"
        "add.s64 tb, tb0, 1568;\n"
        "wgmma.mma_async.sync.aligned.m64n96k16.f32.bf16.bf16 {%0, %1, %2, %3, %4, %5, %6, %7, %8, %9, %10, %11, %12, %13, %14, %15, %16, %17, %18, %19, %20, %21, %22, %23, %24, %25, %26, %27, %28, %29, %30, %31, %32, %33, %34, %35, %36, %37, %38, %39, %40, %41, %42, %43, %44, %45, %46, %47}, {%52, %53, %54, %55}, tb, p1, 1, 1, 1;\n"
        "}\n"
        : "+f"(d[0]), "+f"(d[1]), "+f"(d[2]), "+f"(d[3]), "+f"(d[4]), "+f"(d[5]), "+f"(d[6]), "+f"(d[7]), "+f"(d[8]), "+f"(d[9]), "+f"(d[10]), "+f"(d[11]), "+f"(d[12]), "+f"(d[13]), "+f"(d[14]), "+f"(d[15]), "+f"(d[16]), "+f"(d[17]), "+f"(d[18]), "+f"(d[19]), "+f"(d[20]), "+f"(d[21]), "+f"(d[22]), "+f"(d[23]), "+f"(d[24]), "+f"(d[25]), "+f"(d[26]), "+f"(d[27]), "+f"(d[28]), "+f"(d[29]), "+f"(d[30]), "+f"(d[31]), "+f"(d[32]), "+f"(d[33]), "+f"(d[34]), "+f"(d[35]), "+f"(d[36]), "+f"(d[37]), "+f"(d[38]), "+f"(d[39]), "+f"(d[40]), "+f"(d[41]), "+f"(d[42]), "+f"(d[43]), "+f"(d[44]), "+f"(d[45]), "+f"(d[46]), "+f"(d[47])
        : "r"(a[AOFF + 0][0]), "r"(a[AOFF + 0][1]), "r"(a[AOFF + 0][2]), "r"(a[AOFF + 0][3]), "r"(a[AOFF + 1][0]), "r"(a[AOFF + 1][1]), "r"(a[AOFF + 1][2]), "r"(a[AOFF + 1][3]), "l"(descB), "n"(BOFF >> 4));
}
};
template <> struct Rng<1, 4, 6> {
template <int BOFF, int AOFF, int NA>
static __device__ __forceinline__ void run(float (&d)[48], const uint32_t (&a)[NA][4], uint64_t descB) {
    asm volatile(
        "{\n"
        ".reg .pred p0, p1;\n"
        ".reg .b64 ta, ta0, tb, tb0;\n"
        "setp.ne.b32 p0, 0, 0;\n"
        "setp.eq.b32 p1, 0, 0;\n"
        "add.s64 tb0, %56, %57;\n"
        "add.s64 tb, tb0, 128;\n"
        "wgmma.mma_async.sync.aligned.m64n96k16.f32.bf16.bf16 {%0, %1, %2, %3, %4, %5, %6, %7, %8, %9, %10, %11, %12, %13, %14, %15, %16, %17, %18, %19, %20, %21, %22, %23, %24, %25, %26, %27, %28, %29, %30, %31, %32, %33, %34, %35, %36, %37, %38, %39, %40, %41, %42, %43, %44, %45, %46, %47}, {%48, %49, %50, %51}, tb, p1, 1, 1, 1;\n"
        "add.s64 tb, tb0, 160;\n"
        "wgmma.mma_async.sync.aligned.m64n96k16.f32.bf16.bf16 {%0, %1, %2, %3, %4, %5, %6, %7, %8, %9, %10, %11, %12, %13, %14, %15, %16, %17, %18, %19, %20, %21, %22, %23, %24, %25, %26, %27, %28, %29, %30, %31, %32, %33, %34, %35, %36, %37, %38, %39, %40, %41, %42, %43, %44, %45, %46, %47}, {%52, %53, %54, %55}, tb, p1, 1, 1, 1;\n"
        "}\n"
        : "+f"(d[0]), "+f"(d[1]), "+f"(d[2]), "+f"(d[3]), "+f"(d[4]), "+f"(d[5]), "+f"(d[6]), "+f"(d[7]), "+f"(d[8]), "+f"(d[9]), "+f"(d[10]), "+f"(d[11]), "+f"(d[12]), "+f"(d[13]), "+f"(d[14]), "+f"(d[15]), "+f"(d[16]), "+f"(d[17]), "+f"(d[18]), "+f"(d[19]), "+f"(d[20]), "+f"(d[21]), "+f"(d[22]), "+f"(d[23]), "+f"(d[24]), "+f"(d[25]), "+f"(d[26]), "+f"(d[27]), "+f"(d[28]), "+f"(d[29]), "+f"(d[30]), "+f"(d[31]), "+f"(d[32]), "+f"(d[33]), "+f"(d[34]), "+f"(d[35]), "+f"(d[36]), "+f"(d[37]), "+f"(d[38]), "+f"(d[39]), "+f"(d[40]), "+f"(d[41]), "+f"(d[42]), "+f"(d[43]), "+f"(d[44]), "+f"(d[45]), "+f"(d[46]), "+f"(d[47])
        : "r"(a[AOFF + 0][0]), "r"(a[AOFF + 0][1]), "r"(a[AOFF + 0][2]), "r"(a[AOFF + 0][3]), "r"(a[AOFF + 1][0]), "r"(a[AOFF + 1][1]), "r"(a[AOFF + 1][2]), "r"(a[AOFF + 1][3]), "l"(descB), "n"(BOFF >> 4));
}
};
template <> struct Rng<0, 4, 7> {
template <int BOFF, int AOFF, int NA>
static __device__ __forceinline__ void run(float (&d)[48], const uint32_t (&a)[NA][4], uint64_t descB) {
    asm volatile(
        "{\n"
        ".reg .pred p0, p1;\n"
        ".reg .b64 ta, ta0, tb, tb0;\n"
        "setp.ne.b32 p0, 0, 0;\n"
        "setp.eq.b32 p1, 0, 0;\n"
        "add.s64 tb0, %60, %61;\n"
        "add.s64 tb, tb0, 1536;\n"
        "wgmma.mma_async.sync.aligned.m64n96k16.f32.bf16.bf16 {%0, %1, %2, %3, %4, %5, %6, %7, %8, %9, %10, %11, %12, %13, %14, %15, %16, %17, %18, %19, %20, %21, %22, %23, %24, %25, %26, %27, %28, %29, %30, %31, %32, %33, %34, %35, %36, %37, %38, %39, %40, %41, %42, %43, %44, %45, %46, %47}, {%48, %49, %50, %51}, tb, p1, 1, 1, 1;\n"
        "add.s64 tb, tb0, 1568;\n"
        "wgmma.mma_async.sync.aligned.m64n96k16.f32.bf16.bf16 {%0, %1, %2, %3, %4, %5, %6, %7, %8, %9, %10, %11, %12, %13, %14, %15, %16, %17, %18, %19, %20, %21, %22, %23, %24, %25, %26, %27, %28, %29, %30, %31, %32, %33, %34, %35, %36, %37, %38, %39, %40, %41, %42, %43, %44, %45, %46, %47}, {%52, %53, %54, %55}, tb, p1, 1, 1, 1;\n"
        "add.s64 tb, tb0, 1600;\n"
        "wgmma.mma_async.sync.aligned.m64n96k16.f32.bf16.bf16 {%0, %1, %2, %3, %4, %5, %6, %7, %8, %9, %10, %11, %12, %13, %14, %15, %16, %17, %18, %19, %20, %21, %22, %23, %24, %25, %26, %27, %28, %29, %30, %31, %32, %33, %34, %35, %36, %37, %38, %39, %40, %41, %42, %43, %44, %45, %46, %47}, {%56, %57, %58, %59}, tb, p1, 1, 1, 1;\n"
        "}\n"
        : "+f"(d[0]), "+f"(d[1]), "+f"(d[2]), "+f"(d[3]), "+f"(d[4]), "+f"(d[5]), "+f"(d[6]), "+f"(d[7]), "+f"(d[8]), "+f"(d[9]), "+f"(d[10]), "+f"(d[11]), "+f"(d[12]), "+f"(d[13]), "+f"(d[14]), "+f"(d[15]), "+f"(d[16]), "+f"(d[17]), "+f"(d[18]), "+f"(d[19]), "+f"(d[20]), "+f"(d[21]), "+f"(d[22]), "+f"(d[23]), "+f"(d[24]), "+f"(d[25]), "+f"(d[26]), "+f"(d[27]), "+f"(d[28]), "+f"(d[29]), "+f"(d[30]), "+f"(d[31]), "+f"(d[32]), "+f"(d[33]), "+f"(d[34]), "+f"(d[35]), "+f"(d[36]), "+f"(d[37]), "+f"(d[38]), "+f"(d[39]), "+f"(d[40]), "+f"(d[41]), "+f"(d[42]), "+f"(d[43]), "+f"(d[44]), "+f"(d[45]), "+f"(d[46]), "+f"(d[47])
        : "r"(a[AOFF + 0][0]), "r"(a[AOFF + 0][1]), "r"(a[AOFF + 0][2]), "r"(a[AOFF + 0][3]), "r"(a[AOFF + 1][0]), "r"(a[AOFF + 1][1]), "r"(a[AOFF + 1][2]), "r"(a[AOFF + 1][3]), "r"(a[AOFF + 2][0]), "r"(a[AOFF + 2][1]), "r"(a[AOFF + 2][2]), "r"(a[AOFF + 2][3]), "l"(descB), "n"(BOFF >> 4));
}
};
template <> struct Rng<1, 4, 7> {
template <int BOFF, int AOFF, int NA>
static __device__ __forceinline__ void run(float (&d)[48], const uint32_t (&a)[NA][4], uint64_t descB) {
    asm volatile(
        "{\n"
        ".reg .pred p0, p1;\n"
        ".reg .b64 ta, ta0, tb, tb0;\n"
        "setp.ne.b32 p0, 0, 0;\n"
        "setp.eq.b32 p1, 0, 0;\n"
        "add.s64 tb0, %60, %61;\n"
        "add.s64 tb, tb0, 128;\n"
        "wgmma.mma_async.sync.aligned.m64n96k16.f32.bf16.bf16 {%0, %1, %2, %3, %4, %5, %6, %7, %8, %9, %10, %11, %12, %13, %14, %15, %16, %17, %18, %19, %20, %21, %22, %23, %24, %25, %26, %27, %28, %29, %30, %31, %32, %33, %34, %35, %36, %37, %38, %39, %40, %41, %42, %43, %44, %45, %46, %47}, {%48, %49, %50, %51}, tb, p1, 1, 1, 1;\n"
        "add.s64 tb, tb0, 160;\n"
        "wgmma.mma_async.sync.aligned.m64n96k16.f32.bf16.bf16 {%0, %1, %2, %3, %4, %5, %6, %7, %8, %9, %10, %11, %12, %13, %14, %15, %16, %17, %18, %19, %20, %21, %22, %23, %24, %25, %26, %27, %28, %29, %30, %31, %32, %33, %34, %35, %36, %37, %38, %39, %40, %41, %42, %43, %44, %45, %46, %47}, {%52, %53, %54, %55}, tb, p1, 1, 1, 1;\n"
        "add.s64 tb, tb0, 192;\n"
        "wgmma.mma_async.sync.aligned.m64n96k16.f32.bf16.bf16 {%0, %1, %2, %3, %4, %5, %6, %7, %8, %9, %10, %11, %12, %13, %14, %15, %16, %17, %18, %19, %20, %21, %22, %23, %24, %25, %26, %27, %28, %29, %30, %31, %32, %33, %34, %35, %36, %37, %38, %39, %40, %41, %42, %43, %44, %45, %46, %47}, {%56, %57, %58, %59}, tb, p1, 1, 1, 1;\n"
        "}\n"
        : "+f"(d[0]), "+f"(d[1]), "+f"(d[2]), "+f"(d[3]), "+f"(d[4]), "+f"(d[5]), "+f"(d[6]), "+f"(d[7]), "+f"(d[8]), "+f"(d[9]), "+f"(d[10]), "+f"(d[11]), "+f"(d[12]), "+f"(d[13]), "+f"(d[14]), "+f"(d[15]), "+f"(d[16]), "+f"(d[17]), "+f"(d[18]), "+f"(d[19]), "+f"(d[20]), "+f"(d[21]), "+f"(d[22]), "+f"(d[23]), "+f"(d[24]), "+f"(d[25]), "+f"(d[26]), "+f"(d[27]), "+f"(d[28]), "+f"(d[29]), "+f"(d[30]), "+f"(d[31]), "+f"(d[32]), "+f"(d[33]), "+f"(d[34]), "+f"(d[35]), "+f"(d[36]), "+f"(d[37]), "+f"(d[38]), "+f"(d[39]), "+f"(d[40]), "+f"(d[41]), "+f"(d[42]), "+f"(d[43]), "+f"(d[44]), "+f"(d[45]), "+f"(d[46]), "+f"(d[47])
        : "r"(a[AOFF + 0][0]), "r"(a[AOFF + 0][1]), "r"(a[AOFF + 0][2]), "r"(a[AOFF + 0][3]), "r"(a[AOFF + 1][0]), "r"(a[AOFF + 1][1]), "r"(a[AOFF + 1][2]), "r"(a[AOFF + 1][3]), "r"(a[AOFF + 2][0]), "r"(a[AOFF + 2][1]), "r"(a[AOFF + 2][2]), "r"(a[AOFF + 2][3]), "l"(descB), "n"(BOFF >> 4));
}
};
template <> struct Rng<0, 4, 8> {
template <int BOFF, int AOFF, int NA>
static __device__ __forceinline__ void run(float (&d)[48], const uint32_t (&a)[NA][4], uint64_t descB) {
    asm volatile(
        "{\n"
        ".reg .pred p0, p1;\n"
        ".reg .b64 ta, ta0, tb, tb0;\n"
        "setp.ne.b32 p0, 0, 0;\n"
        "setp.eq.b32 p1, 0, 0;\n"
        "add.s64 tb0, %64, %65;\n"
        "add.s64 tb, tb0, 1536;\n"
        "wgmma.mma_async.sync.aligned.m64n96k16.f32.bf16.bf16 {%0, %1, %2, %3, %4, %5, %6, %7, %8, %9, %10, %11, %12, %13, %14, %15, %16, %17, %18, %19, %20, %21, %22, %23, %24, %25, %26, %27, %28, %29, %30, %31, %32, %33, %34, %35, %36, %37, %38, %39, %40, %41, %42, %43, %44, %45, %46, %47}, {%48, %49, %50, %51}, tb, p1, 1, 1, 1;\n"
        "add.s64 tb, tb0, 1568;\n"
        "wgmma.mma_async.sync.aligned.m64n96k16.f32.bf16.bf16 {%0, %1, %2, %3, %4, %5, %6, %7, %8, %9, %10, %11, %12, %13, %14, %15, %16, %17, %18, %19, %20, %21, %22, %23, %24, %25, %26, %27, %28, %29, %30, %31, %32, %33, %34, %35, %36, %37, %38, %39, %40, %41, %42, %43, %44, %45, %46, %47}, {%52, %53, %54, %55}, tb, p1, 1, 1, 1;\n"
        "add.s64 tb, tb0, 1600;\n"
        "wgmma.mma_async.sync.aligned.m64n96k16.f32.bf16.bf16 {%0, %1, %2, %3, %4, %5, %6, %7, %8, %9, %10, %11, %12, %13, %14, %15, %16, %17, %18, %19, %20, %21, %22, %23, %24, %25, %26, %27, %28, %29, %30, %31, %32, %33, %34, %35, %36, %37, %38, %39, %40, %41, %42, %43, %44, %45, %46, %47}, {%56, %57, %58, %59}, tb, p1, 1, 1, 1;\n"
        "add.s64 tb, tb0, 1632;\n"
        "wgmma.mma_async.sync.aligned.m64n96k16.f32.bf16.bf16 {%0, %1, %2, %3, %4, %5, %6, %7, %8, %9, %10, %11, %12, %13, %14, %15, %16, %17, %18, %19, %20, %21, %22, %23, %24, %25, %26, %27, %28, %29, %30, %31, %32, %33, %34, %35, %36, %37, %38, %39, %40, %41, %42, %43, %44, %45, %46, %47}, {%60, %61, %62, %63}, tb, p1, 1, 1, 1;\n"
        "}\n"
        : "+f"(d[0]), "+f"(d[1]), "+f"(d[2]), "+f"(d[3]), "+f"(d[4]), "+f"(d[5]), "+f"(d[6]), "+f"(d[7]), "+f"(d[8]), "+f"(d[9]), "+f"(d[10]), "+f"(d[11]), "+f"(d[12]), "+f"(d[13]), "+f"(d[14]), "+f"(d[15]), "+f"(d[16]), "+f"(d[17]), "+f"(d[18]), "+f"(d[19]), "+f"(d[20]), "+f"(d[21]), "+f"(d[22]), "+f"(d[23]), "+f"(d[24]), "+f"(d[25]), "+f"(d[26]), "+f"(d[27]), "+f"(d[28]), "+f"(d[29]), "+f"(d[30]), "+f"(d[31]), "+f"(d[32]), "+f"(d[33]), "+f"(d[34]), "+f"(d[35]), "+f"(d[36]), "+f"(d[37]), "+f"(d[38]), "+f"(d[39]), "+f"(d[40]), "+f"(d[41]), "+f"(d[42]), "+f"(d[43]), "+f"(d[44]), "+f"(d[45]), "+f"(d[46]), "+f"(d[47])
        : "r"(a[AOFF + 0][0]), "r"(a[AOFF + 0][1]), "r"(a[AOFF + 0][2]), "r"(a[AOFF + 0][3]), "r"(a[AOFF + 1][0]), "r"(a[AOFF + 1][1]), "r"(a[AOFF + 1][2]), "r"(a[AOFF + 1][3]), "r"(a[AOFF + 2][0]), "r"(a[AOFF + 2][1]), "r"(a[AOFF + 2][2]), "r"(a[AOFF + 2][3]), "r"(a[AOFF + 3][0]), "r"(a[AOFF + 3][1]), "r"(a[AOFF + 3][2]), "r"(a[AOFF + 3][3]), "l"(descB), "n"(BOFF >> 4));
}
};
template <> struct Rng<1, 4, 8> {
template <int BOFF, int AOFF, int NA>
static __device__ __forceinline__ void run(float (&d)[48], const uint32_t (&a)[NA][4], uint64_t descB) {
    asm volatile(
        "{\n"
        ".reg .pred p0, p1;\n"
        ".reg .b64 ta, ta0, tb, tb0;\n"
        "setp.ne.b32 p0, 0, 0;\n"
        "setp.eq.b32 p1, 0, 0;\n"
        "add.s64 tb0, %64, %65;\n"
        "add.s64 tb, tb0, 128;\n"
        "wgmma.mma_async.sync.aligned.m64n96k16.f32.bf16.bf16 {%0, %1, %2, %3, %4, %5, %6, %7, %8, %9, %10, %11, %12, %13, %14, %15, %16, %17, %18, %19, %20, %21, %22, %23, %24, %25, %26, %27, %28, %29, %30, %31, %32, %33, %34, %35, %36, %37, %38, %39, %40, %41, %42, %43, %44, %45, %46, %47}, {%48, %49, %50, %51}, tb, p1, 1, 1, 1;\n"
        "add.s64 tb, tb0, 160;\n"
        "wgmma.mma_async.sync.aligned.m64n96k16.f32.bf16.bf16 {%0, %1, %2, %3, %4, %5, %6, %7, %8, %9, %10, %11, %12, %13, %14, %15, %16, %17, %18, %19, %20, %21, %22, %23, %24, %25, %26, %27, %28, %29, %30, %31, %32, %33, %34, %35, %36, %37, %38, %39, %40, %41, %42, %43, %44, %45, %46, %47}, {%52, %53, %54, %55}, tb, p1, 1, 1, 1;\n"
        "add.s64 tb, tb0, 192;\n"
        "wgmma.mma_async.sync.aligned.m64n96k16.f32.bf16.bf16 {%0, %1, %2, %3, %4, %5, %6, %7, %8, %9, %10, %11, %12, %13, %14, %15, %16, %17, %18, %19, %20, %21, %22, %23, %24, %25, %26, %27, %28, %29, %30, %31, %32, %33, %34, %35, %36, %37, %38, %39, %40, %41, %42, %43, %44, %45, %46, %47}, {%56, %57, %58, %59}, tb, p1, 1, 1, 1;\n"
        "add.s64 tb, tb0, 224;\n"
        "wgmma.mma_async.sync.aligned.m64n96k16.f32.bf16.bf16 {%0, %1, %2, %3, %4, %5, %6, %7, %8, %9, %10, %11, %12, %13, %14, %15, %16, %17, %18, %19, %20, %21, %22, %23, %24, %25, %26, %27, %28, %29, %30, %31, %32, %33, %34, %35, %36, %37, %38, %39, %40, %41, %42, %43, %44, %45, %46, %47}, {%60, %61, %62, %63}, tb, p1, 1, 1, 1;\n"
        "}\n"
        : "+f"(d[0]), "+f"(d[1]), "+f"(d[2]), "+f"(d[3]), "+f"(d[4]), "+f"(d[5]), "+f"(d[6]), "+f"(d[7]), "+f"(d[8]), "+f"(d[9]), "+f"(d[10]), "+f"(d[11]), "+f"(d[12]), "+f"(d[13]), "+f"(d[14]), "+f"(d[15]), "+f"(d[16]), "+f"(d[17]), "+f"(d[18]), "+f"(d[19]), "+f"(d[20]), "+f"(d[21]), "+f"(d[22]), "+f"(d[23]), "+f"(d[24]), "+f"(d[25]), "+f"(d[26]), "+f"(d[27]), "+f"(d[28]), "+f"(d[29]), "+f"(d[30]), "+f"(d[31]), "+f"(d[32]), "+f"(d[33]), "+f"(d[34]), "+f"(d[35]), "+f"(d[36]), "+f"(d[37]), "+f"(d[38]), "+f"(d[39]), "+f"(d[40]), "+f"(d[41]), "+f"(d[42]), "+f"(d[43]), "+f"(d[44]), "+f"(d[45]), "+f"(d[46]), "+f"(d[47])
        : "r"(a[AOFF + 0][0]), "r"(a[AOFF + 0][1]), "r"(a[AOFF + 0][2]), "r"(a[AOFF + 0][3]), "r"(a[AOFF + 1][0]), "r"(a[AOFF + 1][1]), "r"(a[AOFF + 1][2]), "r"(a[AOFF + 1][3]), "r"(a[AOFF + 2][0]), "r"(a[AOFF + 2][1]), "r"(a[AOFF + 2][2]), "r"(a[AOFF + 2][3]), "r"(a[AOFF + 3][0]), "r"(a[AOFF + 3][1]), "r"(a[AOFF + 3][2]), "r"(a[AOFF + 3][3]), "l"(descB), "n"(BOFF >> 4));
}
};
template <> struct Rng<0, 4, 9> {
template <int BOFF, int AOFF, int NA>
static __device__ __forceinline__ void run(float (&d)[48], const uint32_t (&a)[NA][4], uint64_t descB) {
    asm volatile(
        "{\n"
        ".reg .pred p0, p1;\n"
        ".reg .b64 ta, ta0, tb, tb0;\n"
        "setp.ne.b32 p0, 0, 0;\n"
        "setp.eq.b32 p1, 0, 0;\n"
        "add.s64 tb0, %68, %69;\n"
        "add.s64 tb, tb0, 1536;\n"
        "wgmma.mma_async.sync.aligned.m64n96k16.f32.bf16.bf16 {%0, %1, %2, %3, %4, %5, %6, %7, %8, %9, %10, %11, %12, %13, %14, %15, %16, %17, %18, %19, %20, %21, %22, %23, %24, %25, %26, %27, %28, %29, %30, %31, %32, %33, %34, %35, %36, %37, %38, %39, %40, %41, %42, %43, %44, %45, %46, %47}, {%48, %49, %50, %51}, tb, p1, 1, 1, 1;\n"
        "add.s64 tb, tb0, 1568;\n"
        "wgmma.mma_async.sync.aligned.m64n96k16.f32.bf16.bf16 {%0, %1, %2, %3, %4, %5, %6, %7, %8, %9, %10, %11, %12, %13, %14, %15, %16, %17, %18, %19, %20, %21, %22, %23, %24, %25, %26, %27, %28, %29, %30, %31, %32, %33, %34, %35, %36, %37, %38, %39, %40, %41, %42, %43, %44, %45, %46, %47}, {%52, %53, %54, %55}, tb, p1, 1, 1, 1;\n"
        "add.s64 tb, tb0, 1600;\n"
        "wgmma.mma_async.sync.aligned.m64n96k16.f32.bf16.bf16 {%0, %1, %2, %3, %4, %5, %6, %7, %8, %9, %10, %11, %12, %13, %14, %15, %16, %17, %18, %19, %20, %21, %22, %23, %24, %25, %26, %27, %28, %29, %30, %31, %32, %33, %34, %35, %36, %37, %38, %39, %40, %41, %42, %43, %44, %45, %46, %47}, {%56, %57, %58, %59}, tb, p1, 1, 1, 1;\n"
        "add.s64 tb, tb0, 1632;\n"
        "wgmma.mma_async.sync.aligned.m64n96k16.f32.bf16.bf16 {%0, %1, %2, %3, %4, %5, %6, %7, %8, %9, %10, %11, %12, %13, %14, %15, %16, %17, %18, %19, %20, %21, %22, %23, %24, %25, %26, %27, %28, %29, %30, %31, %32, %33, %34, %35, %36, %37, %38, %39, %40, %41, %42, %43, %44, %45, %46, %47}, {%60, %61, %62, %63}, tb, p1, 1, 1, 1;\n"
        "add.s64 tb, tb0, 3072;\n"
        "wgmma.mma_async.sync.aligned.m64n96k16.f32.bf16.bf16 {%0, %1, %2, %3, %4, %5, %6, %7, %8, %9, %10, %11, %12, %13, %14, %15, %16, %17, %18, %19, %20, %21, %22, %23, %24, %25, %26, %27, %28, %29, %30, %31, %32, %33, %34, %35, %36, %37, %38, %39, %40, %41, %42, %43, %44, %45, %46, %47}, {%64, %65, %66, %67}, tb, p1, 1, 1, 1;\n"
        "}\n"
        : "+f"(d[0]), "+f"(d[1]), "+f"(d[2]), "+f"(d[3]), "+f"(d[4]), "+f"(d[5]), "+f"(d[6]), "+f"(d[7]), "+f"(d[8]), "+f"(d[9]), "+f"(d[10]), "+f"(d[11]), "+f"(d[12]), "+f"(d[13]), "+f"(d[14]), "+f"(d[15]), "+f"(d[16]), "+f"(d[17]), "+f"(d[18]), "+f"(d[19]), "+f"(d[20]), "+f"(d[21]), "+f"(d[22]), "+f"(d[23]), "+f"(d[24]), "+f"(d[25]), "+f"(d[26]), "+f"(d[27]), "+f"(d[28]), "+f"(d[29]), "+f"(d[30]), "+f"(d[31]), "+f"(d[32]), "+f"(d[33]), "+f"(d[34]), "+f"(d[35]), "+f"(d[36]), "+f"(d[37]), "+f"(d[38]), "+f"(d[39]), "+f"(d[40]), "+f"(d[41]), "+f"(d[42]), "+f"(d[43]), "+f"(d[44]), "+f"(d[45]), "+f"(d[46]), "+f"(d[47])
        : "r"(a[AOFF + 0][0]), "r"(a[AOFF + 0][1]), "r"(a[AOFF + 0][2]), "r"(a[AOFF + 0][3]), "r"(a[AOFF + 1][0]), "r"(a[AOFF + 1][1]), "r"(a[AOFF + 1][2]), "r"(a[AOFF + 1][3]), "r"(a[AOFF + 2][0]), "r"(a[AOFF + 2][1]), "r"(a[AOFF + 2][2]), "r"(a[AOFF + 2][3]), "r"(a[AOFF + 3][0]), "r"(a[AOFF + 3][1]), "r"(a[AOFF + 3][2]), "r"(a[AOFF + 3][3]), "r"(a[AOFF + 4][0]), "r"(a[AOFF + 4][1]), "r"(a[AOFF + 4][2]), "r"(a[AOFF + 4][3]), "l"(descB), "n"(BOFF >> 4));
}
};
template <> struct Rng<1, 4, 9> {
template <int BOFF, int AOFF, int NA>
static __device__ __forceinline__ void run(float (&d)[48], const uint32_t (&a)[NA][4], uint64_t descB) {
    asm volatile(
        "{\n"
        ".reg .pred p0, p1;\n"
        ".reg .b64 ta, ta0, tb, tb0;\n"
        "setp.ne.b32 p0, 0, 0;\n"
        "setp.eq.b32 p1, 0, 0;\n"
        "add.s64 tb0, %68, %69;\n"
        "add.s64 tb, tb0, 128;\n"
        "wgmma.mma_async.sync.aligned.m64n96k16.f32.bf16.bf16 {%0, %1, %2, %3, %4, %5, %6, %7, %8, %9, %10, %11, %12, %13, %14, %15, %16, %17, %18, %19, %20, %21, %22, %23, %24, %25, %26, %27, %28, %29, %30, %31, %32, %33, %34, %35, %36, %37, %38, %39, %40, %41, %42, %43, %44, %45, %46, %47}, {%48, %49, %50, %51}, tb, p1, 1, 1, 1;\n"
        "add.s64 tb, tb0, 160;\n"
        "wgmma.mma_async.sync.aligned.m64n96k16.f32.bf16.bf16 {%0, %1, %2, %3, %4, %5, %6, %7, %8, %9, %10, %11, %12, %13, %14, %15, %16, %17, %18, %19, %20, %21, %22, %23, %24, %25, %26, %27, %28, %29, %30, %31, %32, %33, %34, %35, %36, %37, %38, %39, %40, %41, %42, %43, %44, %45, %46, %47}, {%52, %53, %54, %55}, tb, p1, 1, 1, 1;\n"
        "add.s64 tb, tb0, 192;\n"
        "wgmma.mma_async.sync.aligned.m64n96k16.f32.bf16.bf16 {%0, %1, %2, %3, %4, %5, %6, %7, %8, %9, %10, %11, %12, %13, %14, %15, %16, %17, %18, %19, %20, %21, %22, %23, %24, %25, %26, %27, %28, %29, %30, %31, %32, %33, %34, %35, %36, %37, %38, %39, %40, %41, %42, %43, %44, %45, %46, %47}, {%56, %57, %58, %59}, tb, p1, 1, 1, 1;\n"
        "add.s64 tb, tb0, 224;\n"
        "wgmma.mma_async.sync.aligned.m64n96k16.f32.bf16.bf16 {%0, %1, %2, %3, %4, %5, %6, %7, %8, %9, %10, %11, %12, %13, %14, %15, %16, %17, %18, %19, %20, %21, %22, %23, %24, %25, %26, %27, %28, %29, %30, %31, %32, %33, %34, %35, %36, %37, %38, %39, %40, %41, %42, %43, %44, %45, %46, %47}, {%60, %61, %62, %63}, tb, p1, 1, 1, 1;\n"
        "add.s64 tb, tb0, 256;\n"
        "wgmma.mma_async.sync.aligned.m64n96k16.f32.bf16.bf16 {%0, %1, %2, %3, %4, %5, %6, %7, %8, %9, %10, %11, %12, %13, %14, %15, %16, %17, %18, %19, %20, %21, %22, %23, %24, %25, %26, %27, %28, %29, %30, %31, %32, %33, %34, %35, %36, %37, %38, %39, %40, %41, %42, %43, %44, %45, %46, %47}, {%64, %65, %66, %67}, tb, p1, 1, 1, 1;\n"
        "}\n"
        : "+f"(d[0]), "+f"(d[1]), "+f"(d[2]), "+f"(d[3]), "+f"(d[4]), "+f"(d[5]), "+f"(d[6]), "+f"(d[7]), "+f"(d[8]), "+f"(d[9]), "+f"(d[10]), "+f"(d[11]), "+f"(d[12]), "+f"(d[13]), "+f"(d[14]), "+f"(d[15]), "+f"(d[16]), "+f"(d[17]), "+f"(d[18]), "+f"(d[19]), "+f"(d[20]), "+f"(d[21]), "+f"(d[22]), "+f"(d[23]), "+f"(d[24]), "+f"(d[25]), "+f"(d[26]), "+f"(d[27]), "+f"(d[28]), "+f"(d[29]), "+f"(d[30]), "+f"(d[31]), "+f"(d[32]), "+f"(d[33]), "+f"(d[34]), "+f"(d[35]), "+f"(d[36]), "+f"(d[37]), "+f"(d[38]), "+f"(d[39]), "+f"(d[40]), "+f"(d[41]), "+f"(d[42]), "+f"(d[43]), "+f"(d[44]), "+f"(d[45]), "+f"(d[46]), "+f"(d[47])
        : "r"(a[AOFF + 0][0]), "r"(a[AOFF + 0][1]), "r"(a[AOFF + 0][2]), "r"(a[AOFF + 0][3]), "r"(a[AOFF + 1][0]), "r"(a[AOFF + 1][1]), "r"(a[AOFF + 1][2]), "r"(a[AOFF + 1][3]), "r"(a[AOFF + 2][0]), "r"(a[AOFF + 2][1]), "r"(a[AOFF + 2][2]), "r"(a[AOFF + 2][3]), "r"(a[AOFF + 3][0]), "r"(a[AOFF + 3][1]), "r"(a[AOFF + 3][2]), "r"(a[AOFF + 3][3]), "r"(a[AOFF + 4][0]), "r"(a[AOFF + 4][1]), "r"(a[AOFF + 4][2]), "r"(a[AOFF + 4][3]), "l"(descB), "n"(BOFF >> 4));
}
};
template <> struct Rng<0, 4, 12> {
template <int BOFF, int AOFF, int NA>
static __device__ __forceinline__ void run(float (&d)[48], const uint32_t (&a)[NA][4], uint64_t descB) {
    asm volatile(
        "{\n"
        ".reg .pred p0, p1;\n"
        ".reg .b64 ta, ta0, tb, tb0;\n"
        "setp.ne.b32 p0, 0, 0;\n"
        "setp.eq.b32 p1, 0, 0;\n"
        "add.s64 tb0, %80, %81;\n"
        "add.s64 tb, tb0, 1536;\n"
        "wgmma.mma_async.sync.aligned.m64n96k16.f32.bf16.bf16 {%0, %1, %2, %3, %4, %5, %6, %7, %8, %9, %10, %11, %12, %13, %14, %15, %16, %17, %18, %19, %20, %21, %22, %23, %24, %25, %26, %27, %28, %29, %30, %31, %32, %33, %34, %35, %36, %37, %38, %39, %40, %41, %42, %43, %44, %45, %46, %47}, {%48, %49, %50, %51}, tb, p1, 1, 1, 1;\n"
        "add.s64 tb, tb0, 1568;\n"
        "wgmma.mma_async.sync.aligned.m64n96k16.f32.bf16.bf16 {%0, %1, %2, %3, %4, %5, %6, %7, %8, %9, %10, %11, %12, %13, %14, %15, %16, %17, %18, %19, %20, %21, %22, %23, %24, %25, %26, %27, %28, %29, %30, %31, %32, %33, %34, %35, %36, %37, %38, %39, %40, %41, %42, %43, %44, %45, %46, %47}, {%52, %53, %54, %55}, tb, p1, 1, 1, 1;\n"
        "add.s64 tb, tb0, 1600;\n"
        "wgmma.mma_async.sync.aligned.m64n96k16.f32.bf16.bf16 {%0, %1, %2, %3, %4, %5, %6, %7, %8, %9, %10, %11, %12, %13, %14, %15, %16, %17, %18, %19, %20, %21, %22, %23, %24, %25, %26, %27, %28, %29, %30, %31, %32, %33, %34, %35, %36, %37, %38, %39, %40, %41, %42, %43, %44, %45, %46, %47}, {%56, %57, %58, %59}, tb, p1, 1, 1, 1;\n"
        "add.s64 tb, tb0, 1632;\n"
        "wgmma.mma_async.sync.aligned.m64n96k16.f32.bf16.bf16 {%0, %1, %2, %3, %4, %5, %6, %7, %8, %9, %10, %11, %12, %13, %14, %15, %16, %17, %18, %19, %20, %21, %22, %23, %24, %25, %26, %27, %28, %29, %30, %31, %32, %33, %34, %35, %36, %37, %38, %39, %40, %41, %42, %43, %44, %45, %46, %47}, {%60, %61, %62, %63}, tb, p1, 1, 1, 1;\n"
        "add.s64 tb, tb0, 3072;\n"
        "wgmma.mma_async.sync.aligned.m64n96k16.f32.bf16.bf16 {%0, %1, %2, %3, %4, %5, %6, %7, %8, %9, %10, %11, %12, %13, %14, %15, %16, %17, %18, %19, %20, %21, %22, %23, %24, %25, %26, %27, %28, %29, %30, %31, %32, %33, %34, %35, %36, %37, %38, %39, %40, %41, %42, %43, %44, %45, %46, %47}, {%64, %65, %66, %67}, tb, p1, 1, 1, 1;\n"
        "add.s64 tb, tb0, 3104;\n"
        "wgmma.mma_async.sync.aligned.m64n96k16.f32.bf16.bf16 {%0, %1, %2, %3, %4, %5, %6, %7, %8, %9, %10, %11, %12, %13, %14, %15, %16, %17, %18, %19, %20, %21, %22, %23, %24, %25, %26, %27, %28, %29, %30, %31, %32, %33, %34, %35, %36, %37, %38, %39, %40, %41, %42, %43, %44, %45, %46, %47}, {%68, %69, %70, %71}, tb, p1, 1, 1, 1;\n"
        "add.s64 tb, tb0, 3136;\n"
        "wgmma.mma_async.sync.aligned.m64n96k16.f32.bf16.bf16 {%0, %1, %2, %3, %4, %5, %6, %7, %8, %9, %10, %11, %12, %13, %14, %15, %16, %17, %18, %19, %20, %21, %22, %23, %24, %25, %26, %27, %28, %29, %30, %31, %32, %33, %34, %35, %36, %37, %38, %39, %40, %41, %42, %43, %44, %45, %46, %47}, {%72, %73, %74, %75}, tb, p1, 1, 1, 1;\n"
        "add.s64 tb, tb0, 3168;\n"
        "wgmma.mma_async.sync.aligned.m64n96k16.f32.bf16.bf16 {%0, %1, %2, %3, %4, %5, %6, %7, %8, %9, %10, %11, %12, %13, %14, %15, %16, %17, %18, %19, %20, %21, %22, %23, %24, %25, %26, %27, %28, %29, %30, %31, %32, %33, %34, %35, %36, %37, %38, %39, %40, %41, %42, %43, %44, %45, %46, %47}, {%76, %77, %78, %79}, tb, p1, 1, 1, 1;\n"
        "}\n"
        : "+f"(d[0]), "+f"(d[1]), "+f"(d[2]), "+f"(d[3]), "+f"(d[4]), "+f"(d[5]), "+f"(d[6]), "+f"(d[7]), "+f"(d[8]), "+f"(d[9]), "+f"(d[10]), "+f"(d[11]), "+f"(d[12]), "+f"(d[13]), "+f"(d[14]), "+f"(d[15]), "+f"(d[16]), "+f"(d[17]), "+f"(d[18]), "+f"(d[19]), "+f"(d[20]), "+f"(d[21]), "+f"(d[22]), "+f"(d[23]), "+f"(d[24]), "+f"(d[25]), "+f"(d[26]), "+f"(d[27]), "+f"(d[28]), "+f"(d[29]), "+f"(d[30]), "+f"(d[31]), "+f"(d[32]), "+f"(d[33]), "+f"(d[34]), "+f"(d[35]), "+f"(d[36]), "+f"(d[37]), "+f"(d[38]), "+f"(d[39]), "+f"(d[40]), "+f"(d[41]), "+f"(d[42]), "+f"(d[43]), "+f"(d[44]), "+f"(d[45]), "+f"(d[46]), "+f"(d[47])
        : "r"(a[AOFF + 0][0]), "r"(a[AOFF + 0][1]), "r"(a[AOFF + 0][2]), "r"(a[AOFF + 0][3]), "r"(a[AOFF + 1][0]), "r"(a[AOFF + 1][1]), "r"(a[AOFF + 1][2]), "r"(a[AOFF + 1][3]), "r"(a[AOFF + 2][0]), "r"(a[AOFF + 2][1]), "r"(a[AOFF + 2][2]), "r"(a[AOFF + 2][3]), "r"(a[AOFF + 3][0]), "r"(a[AOFF + 3][1]), "r"(a[AOFF + 3][2]), "r"(a[AOFF + 3][3]), "r"(a[AOFF + 4][0]), "r"(a[AOFF + 4][1]), "r"(a[AOFF + 4][2]), "r"(a[AOFF + 4][3]), "r"(a[AOFF + 5][0]), "r"(a[AOFF + 5][1]), "r"(a[AOFF + 5][2]), "r"(a[AOFF + 5][3]), "r"(a[AOFF + 6][0]), "r"(a[AOFF + 6][1]), "r"(a[AOFF + 6][2]), "r"(a[AOFF + 6][3]), "r"(a[AOFF + 7][0]), "r"(a[AOFF + 7][1]), "r"(a[AOFF + 7][2]), "r"(a[AOFF + 7][3]), "l"(descB), "n"(BOFF >> 4));
}
};
template <> struct Rng<1, 4, 12> {
template <int BOFF, int AOFF, int NA>
static __device__ __forceinline__ void run(float (&d)[48], const uint32_t (&a)[NA][4], uint64_t descB) {
    asm volatile(
        "{\n"
        ".reg .pred p0, p1;\n"
        ".reg .b64 ta, ta0, tb, tb0;\n"
        "setp.ne.b32 p0, 0, 0;\n"
        "setp.eq.b32 p1, 0, 0;\n"
        "add.s64 tb0, %80, %81;\n"
        "add.s64 tb, tb0, 128;\n"
        "wgmma.mma_async.sync.aligned.m64n96k16.f32.bf16.bf16 {%0, %1, %2, %3, %4, %5, %6, %7, %8, %9, %10, %11, %12, %13, %14, %15, %16, %17, %18, %19, %20, %21, %22, %23, %24, %25, %26, %27, %28, %29, %30, %31, %32, %33, %34, %35, %36, %37, %38, %39, %40, %41, %42, %43, %44, %45, %46, %47}, {%48, %49, %50, %51}, tb, p1, 1, 1, 1;\n"
        "add.s64 tb, tb0, 160;\n"
        "wgmma.mma_async.sync.aligned.m64n96k16.f32.bf16.bf16 {%0, %1, %2, %3, %4, %5, %6, %7, %8, %9, %10, %11, %12, %13, %14, %15, %16, %17, %18, %19, %20, %21, %22, %23, %24, %25, %26, %27, %28, %29, %30, %31, %32, %33, %34, %35, %36, %37, %38, %39, %40, %41, %42, %43, %44, %45, %46, %47}, {%52, %53, %54, %55}, tb, p1, 1, 1, 1;\n"
        "add.s64 tb, tb0, 192;\n"
        "wgmma.mma_async.sync.aligned.m64n96k16.f32.bf16.bf16 {%0, %1, %2, %3, %4, %5, %6, %7, %8, %9, %10, %11, %12, %13, %14, %15, %16, %17, %18, %19, %20, %21, %22, %23, %24, %25, %26, %27, %28, %29, %30, %31, %32, %33, %34, %35, %36, %37, %38, %39, %40, %41, %42, %43, %44, %45, %46, %47}, {%56, %57, %58, %59}, tb, p1, 1, 1, 1;\n"
        "add.s64 tb, tb0, 224;\n"
        "wgmma.mma_async.sync.aligned.m64n96k16.f32.bf16.bf16 {%0, %1, %2, %3, %4, %5, %6, %7, %8, %9, %10, %11, %12, %13, %14, %15, %16, %17, %18, %19, %20, %21, %22, %23, %24, %25, %26, %27, %28, %29, %30, %31, %32, %33, %34, %35, %36, %37, %38, %39, %40, %41, %42, %43, %44, %45, %46, %47}, {%60, %61, %62, %63}, tb, p1, 1, 1, 1;\n"
        "add.s64 tb, tb0, 256;\n"
        "wgmma.mma_async.sync.aligned.m64n96k16.f32.bf16.bf16 {%0, %1, %2, %3, %4, %5, %6, %7, %8, %9, %10, %11, %12, %13, %14, %15, %16, %17, %18, %19, %20, %21, %22, %23, %24, %25, %26, %27, %28, %29, %30, %31, %32, %33, %34, %35, %36, %37, %38, %39, %40, %41, %42, %43, %44, %45, %46, %47}, {%64, %65, %66, %67}, tb, p1, 1, 1, 1;\n"
        "add.s64 tb, tb0, 288;\n"
        "wgmma.mma_async.sync.aligned.m64n96k16.f32.bf16.bf16 {%0, %1, %2, %3, %4, %5, %6, %7, %8, %9, %10, %11, %12, %13, %14, %15, %16, %17, %18, %19, %20, %21, %22, %23, %24, %25, %26, %27, %28, %29, %30, %31, %32, %33, %34, %35, %36, %37, %38, %39, %40, %41, %42, %43, %44, %45, %46, %47}, {%68, %69, %70, %71}, tb, p1, 1, 1, 1;\n"
        "add.s64 tb, tb0, 320;\n"
        "wgmma.mma_async.sync.aligned.m64n96k16.f32.bf16.bf16 {%0, %1, %2, %3, %4, %5, %6, %7, %8, %9, %10, %11, %12, %13, %14, %15, %16, %17, %18, %19, %20, %21, %22, %23, %24, %25, %26, %27, %28, %29, %30, %31, %32, %33, %34, %35, %36, %37, %38, %39, %40, %41, %42, %43, %44, %45, %46, %47}, {%72, %73, %74, %75}, tb, p1, 1, 1, 1;\n"
        "add.s64 tb, tb0, 352;\n"
        "wgmma.mma_async.sync.aligned.m64n96k16.f32.bf16.bf16 {%0, %1, %2, %3, %4, %5, %6, %7, %8, %9, %10, %11, %12, %13, %14, %15, %16, %17, %18, %19, %20, %21, %22, %23, %24, %25, %26, %27, %28, %29, %30, %31, %32, %33, %34, %35, %36, %37, %38, %39, %40, %41, %42, %43, %44, %45, %46, %47}, {%76, %77, %78, %79}, tb, p1, 1, 1, 1;\n"
        "}\n"
        : "+f"(d[0]), "+f"(d[1]), "+f"(d[2]), "+f"(d[3]), "+f"(d[4]), "+f"(d[5]), "+f"(d[6]), "+f"(d[7]), "+f"(d[8]), "+f"(d[9]), "+f"(d[10]), "+f"(d[11]), "+f"(d[12]), "+f"(d[13]), "+f"(d[14]), "+f"(d[15]), "+f"(d[16]), "+f"(d[17]), "+f"(d[18]), "+f"(d[19]), "+f"(d[20]), "+f"(d[21]), "+f"(d[22]), "+f"(d[23]), "+f"(d[24]), "+f"(d[25]), "+f"(d[26]), "+f"(d[27]), "+f"(d[28]), "+f"(d[29]), "+f"(d[30]), "+f"(d[31]), "+f"(d[32]), "+f"(d[33]), "+f"(d[34]), "+f"(d[35]), "+f"(d[36]), "+f"(d[37]), "+f"(d[38]), "+f"(d[39]), "+f"(d[40]), "+f"(d[41]), "+f"(d[42]), "+f"(d[43]), "+f"(d[44]), "+f"(d[45]), "+f"(d[46]), "+f"(d[47])
        : "r"(a[AOFF + 0][0]), "r"(a[AOFF + 0][1]), "r"(a[AOFF + 0][2]), "r"(a[AOFF + 0][3]), "r"(a[AOFF + 1][0]), "r"(a[AOFF + 1][1]), "r"(a[AOFF + 1][2]), "r"(a[AOFF + 1][3]), "r"(a[AOFF + 2][0]), "r"(a[AOFF + 2][1]), "r"(a[AOFF + 2][2]), "r"(a[AOFF + 2][3]), "r"(a[AOFF + 3][0]), "r"(a[AOFF + 3][1]), "r"(a[AOFF + 3][2]), "r"(a[AOFF + 3][3]), "r"(a[AOFF + 4][0]), "r"(a[AOFF + 4][1]), "r"(a[AOFF + 4][2]), "r"(a[AOFF + 4][3]), "r"(a[AOFF + 5][0]), "r"(a[AOFF + 5][1]), "r"(a[AOFF + 5][2]), "r"(a[AOFF + 5][3]), "r"(a[AOFF + 6][0]), "r"(a[AOFF + 6][1]), "r"(a[AOFF + 6][2]), "r"(a[AOFF + 6][3]), "r"(a[AOFF + 7][0]), "r"(a[AOFF + 7][1]), "r"(a[AOFF + 7][2]), "r"(a[AOFF + 7][3]), "l"(descB), "n"(BOFF >> 4));
}
};
template <> struct Rng<0, 5, 8> {
template <int BOFF, int AOFF, int NA>
static __device__ __forceinline__ void run(float (&d)[48], const uint32_t (&a)[NA][4], uint64_t descB) {
    asm volatile(
        "{\n"
        ".reg .pred p0, p1;\n"
        ".reg .b64 ta, ta0, tb, tb0;\n"
        "setp.ne.b32 p0, 0, 0;\n"
        "setp.eq.b32 p1, 0, 0;\n"
        "add.s64 tb0, %60, %61;\n"
        "add.s64 tb, tb0, 1568;\n"
        "wgmma.mma_async.sync.aligned.m64n96k16.f32.bf16.bf16 {%0, %1, %2, %3, %4, %5, %6, %7, %8, %9, %10, %11, %12, %13, %14, %15, %16, %17, %18, %19, %20, %21, %22, %23, %24, %25, %26, %27, %28, %29, %30, %31, %32, %33, %34, %35, %36, %37, %38, %39, %40, %41, %42, %43, %44, %45, %46, %47}, {%48, %49, %50, %51}, tb, p1, 1, 1, 1;\n"
        "add.s64 tb, tb0, 1600;\n"
        "wgmma.mma_async.sync.aligned.m64n96k16.f32.bf16.bf16 {%0, %1, %2, %3, %4, %5, %6, %7, %8, %9, %10, %11, %12, %13, %14, %15, %16, %17, %18, %19, %20, %21, %22, %23, %24, %25, %26, %27, %28, %29, %30, %31, %32, %33, %34, %35, %36, %37, %38, %39, %40, %41, %42, %43, %44, %45, %46, %47}, {%52, %53, %54, %55}, tb, p1, 1, 1, 1;\n"
        "add.s64 tb, tb0, 1632;\n"
        "wgmma.mma_async.sync.aligned.m64n96k16.f32.bf16.bf16 {%0, %1, %2, %3, %4, %5, %6, %7, %8, %9, %10, %11, %12, %13, %14, %15, %16, %17, %18, %19, %20, %21, %22, %23, %24, %25, %26, %27, %28, %29, %30, %31, %32, %33, %34, %35, %36, %37, %38, %39, %40, %41, %42, %43, %44, %45, %46, %47}, {%56, %57, %58, %59}, tb, p1, 1, 1, 1;\n"
        "}\n"
        : "+f"(d[0]), "+f"(d[1]), "+f"(d[2]), "+f"(d[3]), "+f"(d[4]), "+f"(d[5]), "+f"(d[6]), "+f"(d[7]), "+f"(d[8]), "+f"(d[9]), "+f"(d[10]), "+f"(d[11]), "+f"(d[12]), "+f"(d[13]), "+f"(d[14]), "+f"(d[15]), "+f"(d[16]), "+f"(d[17]), "+f"(d[18]), "+f"(d[19]), "+f"(d[20]), "+f"(d[21]), "+f"(d[22]), "+f"(d[23]), "+f"(d[24]), "+f"(d[25]), "+f"(d[26]), "+f"(d[27]), "+f"(d[28]), "+f"(d[29]), "+f"(d[30]), "+f"(d[31]), "+f"(d[32]), "+f"(d[33]), "+f"(d[34]), "+f"(d[35]), "+f"(d[36]), "+f"(d[37]), "+f"(d[38]), "+f"(d[39]), "+f"(d[40]), "+f"(d[41]), "+f"(d[42]), "+f"(d[43]), "+f"(d[44]), "+f"(d[45]), "+f"(d[46]), "+f"(d[47])
        : "r"(a[AOFF + 0][0]), "r"(a[AOFF + 0][1]), "r"(a[AOFF + 0][2]), "r"(a[AOFF + 0][3]), "r"(a[AOFF + 1][0]), "r"(a[AOFF + 1][1]), "r"(a[AOFF + 1][2]), "r"(a[AOFF + 1][3]), "r"(a[AOFF + 2][0]), "r"(a[AOFF + 2][1]), "r"(a[AOFF + 2][2]), "r"(a[AOFF + 2][3]), "l"(descB), "n"(BOFF >> 4));
}
};
template <> struct Rng<1, 5, 8> {
template <int BOFF, int AOFF, int NA>
static __device__ __forceinline__ void run(float (&d)[48], const uint32_t (&a)[NA][4], uint64_t descB) {
    asm volatile(
        "{\n"
        ".reg .pred p0, p1;\n"
        ".reg .b64 ta, ta0, tb, tb0;\n"
        "setp.ne.b32 p0, 0, 0;\n"
        "setp.eq.b32 p1, 0, 0;\n"
        "add.s64 tb0, %60, %61;\n"
        "add.s64 tb, tb0, 160;\n"
        "wgmma.mma_async.sync.aligned.m64n96k16.f32.bf16.bf16 {%0, %1, %2, %3, %4, %5, %6, %7, %8, %9, %10, %11, %12, %13, %14, %15, %16, %17, %18, %19, %20, %21, %22, %23, %24, %25, %26, %27, %28, %29, %30, %31, %32, %33, %34, %35, %36, %37, %38, %39, %40, %41, %42, %43, %44, %45, %46, %47}, {%48, %49, %50, %51}, tb, p1, 1, 1, 1;\n"
        "add.s64 tb, tb0, 192;\n"
        "wgmma.mma_async.sync.aligned.m64n96k16.f32.bf16.bf16 {%0, %1, %2, %3, %4, %5, %6, %7, %8, %9, %10, %11, %12, %13, %14, %15, %16, %17, %18, %19, %20, %21, %22, %23, %24, %25, %26, %27, %28, %29, %30, %31, %32, %33, %34, %35, %36, %37, %38, %39, %40, %41, %42, %43, %44, %45, %46, %47}, {%52, %53, %54, %55}, tb, p1, 1, 1, 1;\n"
        "add.s64 tb, tb0, 224;\n"
        "wgmma.mma_async.sync.aligned.m64n96k16.f32.bf16.bf16 {%0, %1, %2, %3, %4, %5, %6, %7, %8, %9, %10, %11, %12, %13, %14, %15, %16, %17, %18, %19, %20, %21, %22, %23, %24, %25, %26, %27, %28, %29, %30, %31, %32, %33, %34, %35, %36, %37, %38, %39, %40, %41, %42, %43, %44, %45, %46, %47}, {%56, %57, %58, %59}, tb, p1, 1, 1, 1;\n"
        "}\n"
        : "+f"(d[0]), "+f"(d[1]), "+f"(d[2]), "+f"(d[3]), "+f"(d[4]), "+f"(d[5]), "+f"(d[6]), "+f"(d[7]), "+f"(d[8]), "+f"(d[9]), "+f"(d[10]), "+f"(d[11]), "+f"(d[12]), "+f"(d[13]), "+f"(d[14]), "+f"(d[15]), "+f"(d[16]), "+f"(d[17]), "+f"(d[18]), "+f"(d[19]), "+f"(d[20]), "+f"(d[21]), "+f"(d[22]), "+f"(d[23]), "+f"(d[24]), "+f"(d[25]), "+f"(d[26]), "+f"(d[27]), "+f"(d[28]), "+f"(d[29]), "+f"(d[30]), "+f"(d[31]), "+f"(d[32]), "+f"(d[33]), "+f"(d[34]), "+f"(d[35]), "+f"(d[36]), "+f"(d[37]), "+f"(d[38]), "+f"(d[39]), "+f"(d[40]), "+f"(d[41]), "+f"(d[42]), "+f"(d[43]), "+f"(d[44]), "+f"(d[45]), "+f"(d[46]), "+f"(d[47])
        : "r"(a[AOFF + 0][0]), "r"(a[AOFF + 0][1]), "r"(a[AOFF + 0][2]), "r"(a[AOFF + 0][3]), "r"(a[AOFF + 1][0]), "r"(a[AOFF + 1][1]), "r"(a[AOFF + 1][2]), "r"(a[AOFF + 1][3]), "r"(a[AOFF + 2][0]), "r"(a[AOFF + 2][1]), "r"(a[AOFF + 2][2]), "r"(a[AOFF + 2][3]), "l"(descB), "n"(BOFF >> 4));
}
};
template <> struct Rng<0, 5, 9> {
template <int BOFF, int AOFF, int NA>
static __device__ __forceinline__ void run(float (&d)[48], const uint32_t (&a)[NA][4], uint64_t descB) {
    asm volatile(
        "{\n"
        ".reg .pred p0, p1;\n"
        ".reg .b64 ta, ta0, tb, tb0;\n"
        "setp.ne.b32 p0, 0, 0;\n"
        "setp.eq.b32 p1, 0, 0;\n"
        "add.s64 tb0, %64, %65;\n"
        "add.s64 tb, tb0, 1568;\n"
        "wgmma.mma_async.sync.aligned.m64n96k16.f32.bf16.bf16 {%0, %1, %2, %3, %4, %5, %6, %7, %8, %9, %10, %11, %12, %13, %14, %15, %16, %17, %18, %19, %20, %21, %22, %23, %24, %25, %26, %27, %28, %29, %30, %31, %32, %33, %34, %35, %36, %37, %38, %39, %40, %41, %42, %43, %44, %45, %46, %47}, {%48, %49, %50, %51}, tb, p1, 1, 1, 1;\n"
        "add.s64 tb, tb0, 1600;\n"
        "wgmma.mma_async.sync.aligned.m64n96k16.f32.bf16.bf16 {%0, %1, %2, %3, %4, %5, %6, %7, %8, %9, %10, %11, %12, %13, %14, %15, %16, %17, %18, %19, %20, %21, %22, %23, %24, %25, %26, %27, %28, %29, %30, %31, %32, %33, %34, %35, %36, %37, %38, %39, %40, %41, %42, %43, %44, %45, %46, %47}, {%52, %53, %54, %55}, tb, p1, 1, 1, 1;\n"
        "add.s64 tb, tb0, 1632;\n"
        "wgmma.mma_async.sync.aligned.m64n96k16.f32.bf16.bf16 {%0, %1, %2, %3, %4, %5, %6, %7, %8, %9, %10, %11, %12, %13, %14, %15, %16, %17, %18, %19, %20, %21, %22, %23, %24, %25, %26, %27, %28, %29, %30, %31, %32, %33, %34, %35, %36, %37, %38, %39, %40, %41, %42, %43, %44, %45, %46, %47}, {%56, %57, %58, %59}, tb, p1, 1, 1, 1;\n"
        "add.s64 tb, tb0, 3072;\n"
        "wgmma.mma_async.sync.aligned.m64n96k16.f32.bf16.bf16 {%0, %1, %2, %3, %4, %5, %6, %7, %8, %9, %10, %11, %12, %13, %14, %15, %16, %17, %18, %19, %20, %21, %22, %23, %24, %25, %26, %27, %28, %29, %30, %31, %32, %33, %34, %35, %36, %37, %38, %39, %40, %41, %42, %43, %44, %45, %46, %47}, {%60, %61, %62, %63}, tb, p1, 1, 1, 1;\n"
        "}\n"
        : "+f"(d[0]), "+f"(d[1]), "+f"(d[2]), "+f"(d[3]), "+f"(d[4]), "+f"(d[5]), "+f"(d[6]), "+f"(d[7]), "+f"(d[8]), "+f"(d[9]), "+f"(d[10]), "+f"(d[11]), "+f"(d[12]), "+f"(d[13]), "+f"(d[14]), "+f"(d[15]), "+f"(d[16]), "+f"(d[17]), "+f"(d[18]), "+f"(d[19]), "+f"(d[20]), "+f"(d[21]), "+f"(d[22]), "+f"(d[23]), "+f"(d[24]), "+f"(d[25]), "+f"(d[26]), "+f"(d[27]), "+f"(d[28]), "+f"(d[29]), "+f"(d[30]), "+f"(d[31]), "+f"(d[32]), "+f"(d[33]), "+f"(d[34]), "+f"(d[35]), "+f"(d[36]), "+f"(d[37]), "+f"(d[38]), "+f"(d[39]), "+f"(d[40]), "+f"(d[41]), "+f"(d[42]), "+f"(d[43]), "+f"(d[44]), "+f"(d[45]), "+f"(d[46]), "+f"(d[47])
        : "r"(a[AOFF + 0][0]), "r"(a[AOFF + 0][1]), "r"(a[AOFF + 0][2]), "r"(a[AOFF + 0][3]), "r"(a[AOFF + 1][0]), "r"(a[AOFF + 1][1]), "r"(a[AOFF + 1][2]), "r"(a[AOFF + 1][3]), "r"(a[AOFF + 2][0]), "r"(a[AOFF + 2][1]), "r"(a[AOFF + 2][2]), "r"(a[AOFF + 2][3]), "r"(a[AOFF + 3][0]), "r"(a[AOFF + 3][1]), "r"(a[AOFF + 3][2]), "r"(a[AOFF + 3][3]), "l"(descB), "n"(BOFF >> 4));
}
};
template <> struct Rng<1, 5, 9> {
template <int BOFF, int AOFF, int NA>
static __device__ __forceinline__ void run(float (&d)[48], const uint32_t (&a)[NA][4], uint64_t descB) {
    asm volatile(
        "{\n"
        ".reg .pred p0, p1;\n"
        ".reg .b64 ta, ta0, tb, tb0;\n"
        "setp.ne.b32 p0, 0, 0;\n"
        "setp.eq.b32 p1, 0, 0;\n"
        "add.s64 tb0, %64, %65;\n"
        "add.s64 tb, tb0, 160;\n"
        "wgmma.mma_async.sync.aligned.m64n96k16.f32.bf16.bf16 {%0, %1, %2, %3, %4, %5, %6, %7, %8, %9, %10, %11, %12, %13, %14, %15, %16, %17, %18, %19, %20, %21, %22, %23, %24, %25, %26, %27, %28, %29, %30, %31, %32, %33, %34, %35, %36, %37, %38, %39, %40, %41, %42, %43, %44, %45, %46, %47}, {%48, %49, %50, %51}, tb, p1, 1, 1, 1;\n"
        "add.s64 tb, tb0, 192;\n"
        "wgmma.mma_async.sync.aligned.m64n96k16.f32.bf16.bf16 {%0, %1, %2, %3, %4, %5, %6, %7, %8, %9, %10, %11, %12, %13, %14, %15, %16, %17, %18, %19, %20, %21, %22, %23, %24, %25, %26, %27, %28, %29, %30, %31, %32, %33, %34, %35, %36, %37, %38, %39, %40, %41, %42, %43, %44, %45, %46, %47}, {%52, %53, %54, %55}, tb, p1, 1, 1, 1;\n"
        "add.s64 tb, tb0, 224;\n"
        "wgmma.mma_async.sync.aligned.m64n96k16.f32.bf16.bf16 {%0, %1, %2, %3, %4, %5, %6, %7, %8, %9, %10, %11, %12, %13, %14, %15, %16, %17, %18, %19, %20, %21, %22, %23, %24, %25, %26, %27, %28, %29, %30, %31, %32, %33, %34, %35, %36, %37, %38, %39, %40, %41, %42, %43, %44, %45, %46, %47}, {%56, %57, %58, %59}, tb, p1, 1, 1, 1;\n"
        "add.s64 tb, tb0, 256;\n"
        "wgmma.mma_async.sync.aligned.m64n96k16.f32.bf16.bf16 {%0, %1, %2, %3, %4, %5, %6, %7, %8, %9, %10, %11, %12, %13, %14, %15, %16, %17, %18, %19, %20, %21, %22, %23, %24, %25, %26, %27, %28, %29, %30, %31, %32, %33, %34, %35, %36, %37, %38, %39, %40, %41, %42, %43, %44, %45, %46, %47}, {%60, %61, %62, %63}, tb, p1, 1, 1, 1;\n"
        "}\n"
        : "+f"(d[0]), "+f"(d[1]), "+f"(d[2]), "+f"(d[3]), "+f"(d[4]), "+f"(d[5]), "+f"(d[6]), "+f"(d[7]), "+f"(d[8]), "+f"(d[9]), "+f"(d[10]), "+f"(d[11]), "+f"(d[12]), "+f"(d[13]), "+f"(d[14]), "+f"(d[15]), "+f"(d[16]), "+f"(d[17]), "+f"(d[18]), "+f"(d[19]), "+f"(d[20]), "+f"(d[21]), "+f"(d[22]), "+f"(d[23]), "+f"(d[24]), "+f"(d[25]), "+f"(d[26]), "+f"(d[27]), "+f"(d[28]), "+f"(d[29]), "+f"(d[30]), "+f"(d[31]), "+f"(d[32]), "+f"(d[33]), "+f"(d[34]), "+f"(d[35]), "+f"(d[36]), "+f"(d[37]), "+f"(d[38]), "+f"(d[39]), "+f"(d[40]), "+f"(d[41]), "+f"(d[42]), "+f"(d[43]), "+f"(d[44]), "+f"(d[45]), "+f"(d[46]), "+f"(d[47])
        : "r"(a[AOFF + 0][0]), "r"(a[AOFF + 0][1]), "r"(a[AOFF + 0][2]), "r"(a[AOFF + 0][3]), "r"(a[AOFF + 1][0]), "r"(a[AOFF + 1][1]), "r"(a[AOFF + 1][2]), "r"(a[AOFF + 1][3]), "r"(a[AOFF + 2][0]), "r"(a[AOFF + 2][1]), "r"(a[AOFF + 2][2]), "r"(a[AOFF + 2][3]), "r"(a[AOFF + 3][0]), "r"(a[AOFF + 3][1]), "r"(a[AOFF + 3][2]), "r"(a[AOFF + 3][3]), "l"(descB), "n"(BOFF >> 4));
}
};
template <> struct Rng<0, 5, 10> {
template <int BOFF, int AOFF, int NA>
static __device__ __forceinline__ void run(float (&d)[48], const uint32_t (&a)[NA][4], uint64_t descB) {
    asm volatile(
        "{\n"
        ".reg .pred p0, p1;\n"
        ".reg .b64 ta, ta0, tb, tb0;\n"
        "setp.ne.b32 p0, 0, 0;\n"
        "setp.eq.b32 p1, 0, 0;\n"
        "add.s64 tb0, %68, %69;\n"
        "add.s64 tb, tb0, 1568;\n"
        "wgmma.mma_async.sync.aligned.m64n96k16.f32.bf16.bf16 {%0, %1, %2, %3, %4, %5, %6, %7, %8, %9, %10, %11, %12, %13, %14, %15, %16, %17, %18, %19, %20, %21, %22, %23, %24, %25, %26, %27, %28, %29, %30, %31, %32, %33, %34, %35, %36, %37, %38, %39, %40, %41, %42, %43, %44, %45, %46, %47}, {%48, %49, %50, %51}, tb, p1, 1, 1, 1;\n"
        "add.s64 tb, tb0, 1600;\n"
        "wgmma.mma_async.sync.aligned.m64n96k16.f32.bf16.bf16 {%0, %1, %2, %3, %4, %5, %6, %7, %8, %9, %10, %11, %12, %13, %14, %15, %16, %17, %18, %19, %20, %21, %22, %23, %24, %25, %26, %27, %28, %29, %30, %31, %32, %33, %34, %35, %36, %37, %38, %39, %40, %41, %42, %43, %44, %45, %46, %47}, {%52, %53, %54, %55}, tb, p1, 1, 1, 1;\n"
        "add.s64 tb, tb0, 1632;\n"
        "wgmma.mma_async.sync.aligned.m64n96k16.f32.bf16.bf16 {%0, %1, %2, %3, %4, %5, %6, %7, %8, %9, %10, %11, %12, %13, %14, %15, %16, %17, %18, %19, %20, %21, %22, %23, %24, %25, %26, %27, %28, %29, %30, %31, %32, %33, %34, %35, %36, %37, %38, %39, %40, %41, %42, %43, %44, %45, %46, %47}, {%56, %57, %58, %59}, tb, p1, 1, 1, 1;\n"
        "add.s64 tb, tb0, 3072;\n"
        "wgmma.mma_async.sync.aligned.m64n96k16.f32.bf16.bf16 {%0, %1, %2, %3, %4, %5, %6, %7, %8, %9, %10, %11, %12, %13, %14, %15, %16, %17, %18, %19, %20, %21, %22, %23, %24, %25, %26, %27, %28, %29, %30, %31, %32, %33, %34, %35, %36, %37, %38, %39, %40, %41, %42, %43, %44, %45, %46, %47}, {%60, %61, %62, %63}, tb, p1, 1, 1, 1;\n"
        "add.s64 tb, tb0, 3104;\n"
        "wgmma.mma_async.sync.aligned.m64n96k16.f32.bf16.bf16 {%0, %1, %2, %3, %4, %5, %6, %7, %8, %9, %10, %11, %12, %13, %14, %15, %16, %17, %18, %19, %20, %21, %22, %23, %24, %25, %26, %27, %28, %29, %30, %31, %32, %33, %34, %35, %36, %37, %38, %39, %40, %41, %42, %43, %44, %45, %46, %47}, {%64, %65, %66, %67}, tb, p1, 1, 1, 1;\n"
        "}\n"
        : "+f"(d[0]), "+f"(d[1]), "+f"(d[2]), "+f"(d[3]), "+f"(d[4]), "+f"(d[5]), "+f"(d[6]), "+f"(d[7]), "+f"(d[8]), "+f"(d[9]), "+f"(d[10]), "+f"(d[11]), "+f"(d[12]), "+f"(d[13]), "+f"(d[14]), "+f"(d[15]), "+f"(d[16]), "+f"(d[17]), "+f"(d[18]), "+f"(d[19]), "+f"(d[20]), "+f"(d[21]), "+f"(d[22]), "+f"(d[23]), "+f"(d[24]), "+f"(d[25]), "+f"(d[26]), "+f"(d[27]), "+f"(d[28]), "+f"(d[29]), "+f"(d[30]), "+f"(d[31]), "+f"(d[32]), "+f"(d[33]), "+f"(d[34]), "+f"(d[35]), "+f"(d[36]), "+f"(d[37]), "+f"(d[38]), "+f"(d[39]), "+f"(d[40]), "+f"(d[41]), "+f"(d[42]), "+f"(d[43]), "+f"(d[44]), "+f"(d[45]), "+f"(d[46]), "+f"(d[47])
        : "r"(a[AOFF + 0][0]), "r"(a[AOFF + 0][1]), "r"(a[AOFF + 0][2]), "r"(a[AOFF + 0][3]), "r"(a[AOFF + 1][0]), "r"(a[AOFF + 1][1]), "r"(a[AOFF + 1][2]), "r"(a[AOFF + 1][3]), "r"(a[AOFF + 2][0]), "r"(a[AOFF + 2][1]), "r"(a[AOFF + 2][2]), "r"(a[AOFF + 2][3]), "r"(a[AOFF + 3][0]), "r"(a[AOFF + 3][1]), "r"(a[AOFF + 3][2]), "r"(a[AOFF + 3][3]), "r"(a[AOFF + 4][0]), "r"(a[AOFF + 4][1]), "r"(a[AOFF + 4][2]), "r"(a[AOFF + 4][3]), "l"(descB), "n"(BOFF >> 4));
}
};
template <> struct Rng<1, 5, 10> {
template <int BOFF, int AOFF, int NA>
static __device__ __forceinline__ void run(float (&d)[48], const uint32_t (&a)[NA][4], uint64_t descB) {
    asm volatile(
        "{\n"
        ".reg .pred p0, p1;\n"
        ".reg .b64 ta, ta0, tb, tb0;\n"
        "setp.ne.b32 p0, 0, 0;\n"
        "setp.eq.b32 p1, 0, 0;\n"
        "add.s64 tb0, %68, %69;\n"
        "add.s64 tb, tb0, 160;\n"
        "wgmma.mma_async.sync.aligned.m64n96k16.f32.bf16.bf16 {%0, %1, %2, %3, %4, %5, %6, %7, %8, %9, %10, %11, %12, %13, %14, %15, %16, %17, %18, %19, %20, %21, %22, %23, %24, %25, %26, %27, %28, %29, %30, %31, %32, %33, %34, %35, %36, %37, %38, %39, %40, %41, %42, %43, %44, %45, %46, %47}, {%48, %49, %50, %51}, tb, p1, 1, 1, 1;\n"
        "add.s64 tb, tb0, 192;\n"
        "wgmma.mma_async.sync.aligned.m64n96k16.f32.bf16.bf16 {%0, %1, %2, %3, %4, %5, %6, %7, %8, %9, %10, %11, %12, %13, %14, %15, %16, %17, %18, %19, %20, %21, %22, %23, %24, %25, %26, %27, %28, %29, %30, %31, %32, %33, %34, %35, %36, %37, %38, %39, %40, %41, %42, %43, %44, %45, %46, %47}, {%52, %53, %54, %55}, tb, p1, 1, 1, 1;\n"
        "add.s64 tb, tb0, 224;\n"
        "wgmma.mma_async.sync.aligned.m64n96k16.f32.bf16.bf16 {%0, %1, %2, %3, %4, %5, %6, %7, %8, %9, %10, %11, %12, %13, %14, %15, %16, %17, %18, %19, %20, %21, %22, %23, %24, %25, %26, %27, %28, %29, %30, %31, %32, %33, %34, %35, %36, %37, %38, %39, %40, %41, %42, %43, %44, %45, %46, %47}, {%56, %57, %58, %59}, tb, p1, 1, 1, 1;\n"
        "add.s64 tb, tb0, 256;\n"
        "wgmma.mma_async.sync.aligned.m64n96k16.f32.bf16.bf16 {%0, %1, %2, %3, %4, %5, %6, %7, %8, %9, %10, %11, %12, %13, %14, %15, %16, %17, %18, %19, %20, %21, %22, %23, %24, %25, %26, %27, %28, %29, %30, %31, %32, %33, %34, %35, %36, %37, %38, %39, %40, %41, %42, %43, %44, %45, %46, %47}, {%60, %61, %62, %63}, tb, p1, 1, 1, 1;\n"
        "add.s64 tb, tb0, 288;\n"
        "wgmma.mma_async.sync.aligned.m64n96k16.f32.bf16.bf16 {%0, %1, %2, %3, %4, %5, %6, %7, %8, %9, %10, %11, %12, %13, %14, %15, %16, %17, %18, %19, %20, %21, %22, %23, %24, %25, %26, %27, %28, %29, %30, %31, %32, %33, %34, %35, %36, %37, %38, %39, %40, %41, %42, %43, %44, %45, %46, %47}, {%64, %65, %66, %67}, tb, p1, 1, 1, 1;\n"
        "}\n"
        : "+f"(d[0]), "+f"(d[1]), "+f"(d[2]), "+f"(d[3]), "+f"(d[4]), "+f"(d[5]), "+f"(d[6]), "+f"(d[7]), "+f"(d[8]), "+f"(d[9]), "+f"(d[10]), "+f"(d[11]), "+f"(d[12]), "+f"(d[13]), "+f"(d[14]), "+f"(d[15]), "+f"(d[16]), "+f"(d[17]), "+f"(d[18]), "+f"(d[19]), "+f"(d[20]), "+f"(d[21]), "+f"(d[22]), "+f"(d[23]), "+f"(d[24]), "+f"(d[25]), "+f"(d[26]), "+f"(d[27]), "+f"(d[28]), "+f"(d[29]), "+f"(d[30]), "+f"(d[31]), "+f"(d[32]), "+f"(d[33]), "+f"(d[34]), "+f"(d[35]), "+f"(d[36]), "+f"(d[37]), "+f"(d[38]), "+f"(d[39]), "+f"(d[40]), "+f"(d[41]), "+f"(d[42]), "+f"(d[43]), "+f"(d[44]), "+f"(d[45]), "+f"(d[46]), "+f"(d[47])
        : "r"(a[AOFF + 0][0]), "r"(a[AOFF + 0][1]), "r"(a[AOFF + 0][2]), "r"(a[AOFF + 0][3]), "r"(a[AOFF + 1][0]), "r"(a[AOFF + 1][1]), "r"(a[AOFF + 1][2]), "r"(a[AOFF + 1][3]), "r"(a[AOFF + 2][0]), "r"(a[AOFF + 2][1]), "r"(a[AOFF + 2][2]), "r"(a[AOFF + 2][3]), "r"(a[AOFF + 3][0]), "r"(a[AOFF + 3][1]), "r"(a[AOFF + 3][2]), "r"(a[AOFF + 3][3]), "r"(a[AOFF + 4][0]), "r"(a[AOFF + 4][1]), "r"(a[AOFF + 4][2]), "r"(a[AOFF + 4][3]), "l"(descB), "n"(BOFF >> 4));
}
};
template <> struct Rng<0, 5, 12> {
template <int BOFF, int AOFF, int NA>
static __device__ __forceinline__ void run(float (&d)[48], const uint32_t (&a)[NA][4], uint64_t descB) {
    asm volatile(
        "{\n"
        ".reg .pred p0, p1;\n"
        ".reg .b64 ta, ta0, tb, tb0;\n"
        "setp.ne.b32 p0, 0, 0;\n"
        "setp.eq.b32 p1, 0, 0;\n"
        "add.s64 tb0, %76, %77;\n"
        "add.s64 tb, tb0, 1568;\n"
        "wgmma.mma_async.sync.aligned.m64n96k16.f32.bf16.bf16 {%0, %1, %2, %3, %4, %5, %6, %7, %8, %9, %10, %11, %12, %13, %14, %15, %16, %17, %18, %19, %20, %21, %22, %23, %24, %25, %26, %27, %28, %29, %30, %31, %32, %33, %34, %35, %36, %37, %38, %39, %40, %41, %42, %43, %44, %45, %46, %47}, {%48, %49, %50, %51}, tb, p1, 1, 1, 1;\n"
        "add.s64 tb, tb0, 1600;\n"
        "wgmma.mma_async.sync.aligned.m64n96k16.f32.bf16.bf16 {%0, %1, %2, %3, %4, %5, %6, %7, %8, %9, %10, %11, %12, %13, %14, %15, %16, %17, %18, %19, %20, %21, %22, %23, %24, %25, %26, %27, %28, %29, %30, %31, %32, %33, %34, %35, %36, %37, %38, %39, %40, %41, %42, %43, %44, %45, %46, %47}, {%52, %53, %54, %55}, tb, p1, 1, 1, 1;\n"
        "add.s64 tb, tb0, 1632;\n"
        "wgmma.mma_async.sync.aligned.m64n96k16.f32.bf16.bf16 {%0, %1, %2, %3, %4, %5, %6, %7, %8, %9, %10, %11, %12, %13, %14, %15, %16, %17, %18, %19, %20, %21, %22, %23, %24, %25, %26, %27, %28, %29, %30, %31, %32, %33, %34, %35, %36, %37, %38, %39, %40, %41, %42, %43, %44, %45, %46, %47}, {%56, %57, %58, %59}, tb, p1, 1, 1, 1;\n"
        "add.s64 tb, tb0, 3072;\n"
        "wgmma.mma_async.sync.aligned.m64n96k16.f32.bf16.bf16 {%0, %1, %2, %3, %4, %5, %6, %7, %8, %9, %10, %11, %12, %13, %14, %15, %16, %17, %18, %19, %20, %21, %22, %23, %24, %25, %26, %27, %28, %29, %30, %31, %32, %33, %34, %35, %36, %37, %38, %39, %40, %41, %42, %43, %44, %45, %46, %47}, {%60, %61, %62, %63}, tb, p1, 1, 1, 1;\n"
        "add.s64 tb, tb0, 3104;\n"
        "wgmma.mma_async.sync.aligned.m64n96k16.f32.bf16.bf16 {%0, %1, %2, %3, %4, %5, %6, %7, %8, %9, %10, %11, %12, %13, %14, %15, %16, %17, %18, %19, %20, %21, %22, %23, %24, %25, %26, %27, %28, %29, %30, %31, %32, %33, %34, %35, %36, %37, %38, %39, %40, %41, %42, %43, %44, %45, %46, %47}, {%64, %65, %66, %67}, tb, p1, 1, 1, 1;\n"
        "add.s64 tb, tb0, 3136;\n"
        "wgmma.mma_async.sync.aligned.m64n96k16.f32.bf16.bf16 {%0, %1, %2, %3, %4, %5, %6, %7, %8, %9, %10, %11, %12, %13, %14, %15, %16, %17, %18, %19, %20, %21, %22, %23, %24, %25, %26, %27, %28, %29, %30, %31, %32, %33, %34, %35, %36, %37, %38, %39, %40, %41, %42, %43, %44, %45, %46, %47}, {%68, %69, %70, %71}, tb, p1, 1, 1, 1;\n"
        "add.s64 tb, tb0, 3168;\n"
        "wgmma.mma_async.sync.aligned.m64n96k16.f32.bf16.bf16 {%0, %1, %2, %3, %4, %5, %6, %7, %8, %9, %10, %11, %12, %13, %14, %15, %16, %17, %18, %19, %20, %21, %22, %23, %24, %25, %26, %27, %28, %29, %30, %31, %32, %33, %34, %35, %36, %37, %38, %39, %40, %41, %42, %43, %44, %45, %46, %47}, {%72, %73, %74, %75}, tb, p1, 1, 1, 1;\n"
        "}\n"
        : "+f"(d[0]), "+f"(d[1]), "+f"(d[2]), "+f"(d[3]), "+f"(d[4]), "+f"(d[5]), "+f"(d[6]), "+f"(d[7]), "+f"(d[8]), "+f"(d[9]), "+f"(d[10]), "+f"(d[11]), "+f"(d[12]), "+f"(d[13]), "+f"(d[14]), "+f"(d[15]), "+f"(d[16]), "+f"(d[17]), "+f"(d[18]), "+f"(d[19]), "+f"(d[20]), "+f"(d[21]), "+f"(d[22]), "+f"(d[23]), "+f"(d[24]), "+f"(d[25]), "+f"(d[26]), "+f"(d[27]), "+f"(d[28]), "+f"(d[29]), "+f"(d[30]), "+f"(d[31]), "+f"(d[32]), "+f"(d[33]), "+f"(d[34]), "+f"(d[35]), "+f"(d[36]), "+f"(d[37]), "+f"(d[38]), "+f"(d[39]), "+f"(d[40]), "+f"(d[41]), "+f"(d[42]), "+f"(d[43]), "+f"(d[44]), "+f"(d[45]), "+f"(d[46]), "+f"(d[47])
        : "r"(a[AOFF + 0][0]), "r"(a[AOFF + 0][1]), "r"(a[AOFF + 0][2]), "r"(a[AOFF + 0][3]), "r"(a[AOFF + 1][0]), "r"(a[AOFF + 1][1]), "r"(a[AOFF + 1][2]), "r"(a[AOFF + 1][3]), "r"(a[AOFF + 2][0]), "r"(a[AOFF + 2][1]), "r"(a[AOFF + 2][2]), "r"(a[AOFF + 2][3]), "r"(a[AOFF + 3][0]), "r"(a[AOFF + 3][1]), "r"(a[AOFF + 3][2]), "r"(a[AOFF + 3][3]), "r"(a[AOFF + 4][0]), "r"(a[AOFF + 4][1]), "r"(a[AOFF + 4][2]), "r"(a[AOFF + 4][3]), "r"(a[AOFF + 5][0]), "r"(a[AOFF + 5][1]), "r"(a[AOFF + 5][2]), "r"(a[AOFF + 5][3]), "r"(a[AOFF + 6][0]), "r"(a[AOFF + 6][1]), "r"(a[AOFF + 6][2]), "r"(a[AOFF + 6][3]), "l"(descB), "n"(BOFF >> 4));
}
};
template <> struct Rng<1, 5, 12> {
template <int BOFF, int AOFF, int NA>
static __device__ __forceinline__ void run(float (&d)[48], const uint32_t (&a)[NA][4], uint64_t descB) {
    asm volatile(
        "{\n"
        ".reg .pred p0, p1;\n"
        ".reg .b64 ta, ta0, tb, tb0;\n"
        "setp.ne.b32 p0, 0, 0;\n"
        "setp.eq.b32 p1, 0, 0;\n"
        "add.s64 tb0, %76, %77;\n"
        "add.s64 tb, tb0, 160;\n"
        "wgmma.mma_async.sync.aligned.m64n96k16.f32.bf16.bf16 {%0, %1, %2, %3, %4, %5, %6, %7, %8, %9, %10, %11, %12, %13, %14, %15, %16, %17, %18, %19, %20, %21, %22, %23, %24, %25, %26, %27, %28, %29, %30, %31, %32, %33, %34, %35, %36, %37, %38, %39, %40, %41, %42, %43, %44, %45, %46, %47}, {%48, %49, %50, %51}, tb, p1, 1, 1, 1;\n"
        "add.s64 tb, tb0, 192;\n"
        "wgmma.mma_async.sync.aligned.m64n96k16.f32.bf16.bf16 {%0, %1, %2, %3, %4, %5, %6, %7, %8, %9, %10, %11, %12, %13, %14, %15, %16, %17, %18, %19, %20, %21, %22, %23, %24, %25, %26, %27, %28, %29, %30, %31, %32, %33, %34, %35, %36, %37, %38, %39, %40, %41, %42, %43, %44, %45, %46, %47}, {%52, %53, %54, %55}, tb, p1, 1, 1, 1;\n"
        "add.s64 tb, tb0, 224;\n"
        "wgmma.mma_async.sync.aligned.m64n96k16.f32.bf16.bf16 {%0, %1, %2, %3, %4, %5, %6, %7, %8, %9, %10, %11, %12, %13, %14, %15, %16, %17, %18, %19, %20, %21, %22, %23, %24, %25, %26, %27, %28, %29, %30, %31, %32, %33, %34, %35, %36, %37, %38, %39, %40, %41, %42, %43, %44, %45, %46, %47}, {%56, %57, %58, %59}, tb, p1, 1, 1, 1;\n"
        "add.s64 tb, tb0, 256;\n"
        "wgmma.mma_async.sync.aligned.m64n96k16.f32.bf16.bf16 {%0, %1, %2, %3, %4, %5, %6, %7, %8, %9, %10, %11, %12, %13, %14, %15, %16, %17, %18, %19, %20, %21, %22, %23, %24, %25, %26, %27, %28, %29, %30, %31, %32, %33, %34, %35, %36, %37, %38, %39, %40, %41, %42, %43, %44, %45, %46, %47}, {%60, %61, %62, %63}, tb, p1, 1, 1, 1;\n"
        "add.s64 tb, tb0, 288;\n"
        "wgmma.mma_async.sync.aligned.m64n96k16.f32.bf16.bf16 {%0, %1, %2, %3, %4, %5, %6, %7, %8, %9, %10, %11, %12, %13, %14, %15, %16, %17, %18, %19, %20, %21, %22, %23, %24, %25, %26, %27, %28, %29, %30, %31, %32, %33, %34, %35, %36, %37, %38, %39, %40, %41, %42, %43, %44, %45, %46, %47}, {%64, %65, %66, %67}, tb, p1, 1, 1, 1;\n"
        "add.s64 tb, tb0, 320;\n"
        "wgmma.mma_async.sync.aligned.m64n96k16.f32.bf16.bf16 {%0, %1, %2, %3, %4, %5, %6, %7, %8, %9, %10, %11, %12, %13, %14, %15, %16, %17, %18, %19, %20, %21, %22, %23, %24, %25, %26, %27, %28, %29, %30, %31, %32, %33, %34, %35, %36, %37, %38, %39, %40, %41, %42, %43, %44, %45, %46, %47}, {%68, %69, %70, %71}, tb, p1, 1, 1, 1;\n"
        "add.s64 tb, tb0, 352;\n"
        "wgmma.mma_async.sync.aligned.m64n96k16.f32.bf16.bf16 {%0, %1, %2, %3, %4, %5, %6, %7, %8, %9, %10, %11, %12, %13, %14, %15, %16, %17, %18, %19, %20, %21, %22, %23, %24, %25, %26, %27, %28, %29, %30, %31, %32, %33, %34, %35, %36, %37, %38, %39, %40, %41, %42, %43, %44, %45, %46, %47}, {%72, %73, %74, %75}, tb, p1, 1, 1, 1;\n"
        "}\n"
        : "+f"(d[0]), "+f"(d[1]), "+f"(d[2]), "+f"(d[3]), "+f"(d[4]), "+f"(d[5]), "+f"(d[6]), "+f"(d[7]), "+f"(d[8]), "+f"(d[9]), "+f"(d[10]), "+f"(d[11]), "+f"(d[12]), "+f"(d[13]), "+f"(d[14]), "+f"(d[15]), "+f"(d[16]), "+f"(d[17]), "+f"(d[18]), "+f"(d[19]), "+f"(d[20]), "+f"(d[21]), "+f"(d[22]), "+f"(d[23]), "+f"(d[24]), "+f"(d[25]), "+f"(d[26]), "+f"(d[27]), "+f"(d[28]), "+f"(d[29]), "+f"(d[30]), "+f"(d[31]), "+f"(d[32]), "+f"(d[33]), "+f"(d[34]), "+f"(d[35]), "+f"(d[36]), "+f"(d[37]), "+f"(d[38]), "+f"(d[39]), "+f"(d[40]), "+f"(d[41]), "+f"(d[42]), "+f"(d[43]), "+f"(d[44]), "+f"(d[45]), "+f"(d[46]), "+f"(d[47])
        : "r"(a[AOFF + 0][0]), "r"(a[AOFF + 0][1]), "r"(a[AOFF + 0][2]), "r"(a[AOFF + 0][3]), "r"(a[AOFF + 1][0]), "r"(a[AOFF + 1][1]), "r"(a[AOFF + 1][2]), "r"(a[AOFF + 1][3]), "r"(a[AOFF + 2][0]), "r"(a[AOFF + 2][1]), "r"(a[AOFF + 2][2]), "r"(a[AOFF + 2][3]), "r"(a[AOFF + 3][0]), "r"(a[AOFF + 3][1]), "r"(a[AOFF + 3][2]), "r"(a[AOFF + 3][3]), "r"(a[AOFF + 4][0]), "r"(a[AOFF + 4][1]), "r"(a[AOFF + 4][2]), "r"(a[AOFF + 4][3]), "r"(a[AOFF + 5][0]), "r"(a[AOFF + 5][1]), "r"(a[AOFF + 5][2]), "r"(a[AOFF + 5][3]), "r"(a[AOFF + 6][0]), "r"(a[AOFF + 6][1]), "r"(a[AOFF + 6][2]), "r"(a[AOFF + 6][3]), "l"(descB), "n"(BOFF >> 4));
}
};
template <> struct Rng<0, 6, 9> {
template <int BOFF, int AOFF, int NA>
static __device__ __forceinline__ void run(float (&d)[48], const uint32_t (&a)[NA][4], uint64_t descB) {
    asm volatile(
        "{\n"
        ".reg .pred p0, p1;\n"
        ".reg .b64 ta, ta0, tb, tb0;\n"
        "setp.ne.b32 p0, 0, 0;\n"
        "setp.eq.b32 p1, 0, 0;\n"
        "add.s64 tb0, %60, %61;\n"
        "add.s64 tb, tb0, 1600;\n"
        "wgmma.mma_async.sync.aligned.m64n96k16.f32.bf16.bf16 {%0, %1, %2, %3, %4, %5, %6, %7, %8, %9, %10, %11, %12, %13, %14, %15, %16, %17, %18, %19, %20, %21, %22, %23, %24, %25, %26, %27, %28, %29, %30, %31, %32, %33, %34, %35, %36, %37, %38, %39, %40, %41, %42, %43, %44, %45, %46, %47}, {%48, %49, %50, %51}, tb, p1, 1, 1, 1;\n"
        "add.s64 tb, tb0, 1632;\n"
        "wgmma.mma_async.sync.aligned.m64n96k16.f32.bf16.bf16 {%0, %1, %2, %3, %4, %5, %6, %7, %8, %9, %10, %11, %12, %13, %14, %15, %16, %17, %18, %19, %20, %21, %22, %23, %24, %25, %26, %27, %28, %29, %30, %31, %32, %33, %34, %35, %36, %37, %38, %39, %40, %41, %42, %43, %44, %45, %46, %47}, {%52, %53, %54, %55}, tb, p1, 1, 1, 1;\n"
        "add.s64 tb, tb0, 3072;\n"
        "wgmma.mma_async.sync.aligned.m64n96k16.f32.bf16.bf16 {%0, %1, %2, %3, %4, %5, %6, %7, %8, %9, %10, %11, %12, %13, %14, %15, %16, %17, %18, %19, %20, %21, %22, %23, %24, %25, %26, %27, %28, %29, %30, %31, %32, %33, %34, %35, %36, %37, %38, %39, %40, %41, %42, %43, %44, %45, %46, %47}, {%56, %57, %58, %59}, tb, p1, 1, 1, 1;\n"
        "}\n"
        : "+f"(d[0]), "+f"(d[1]), "+f"(d[2]), "+f"(d[3]), "+f"(d[4]), "+f"(d[5]), "+f"(d[6]), "+f"(d[7]), "+f"(d[8]), "+f"(d[9]), "+f"(d[10]), "+f"(d[11]), "+f"(d[12]), "+f"(d[13]), "+f"(d[14]), "+f"(d[15]), "+f"(d[16]), "+f"(d[17]), "+f"(d[18]), "+f"(d[19]), "+f"(d[20]), "+f"(d[21]), "+f"(d[22]), "+f"(d[23]), "+f"(d[24]), "+f"(d[25]), "+f"(d[26]), "+f"(d[27]), "+f"(d[28]), "+f"(d[29]), "+f"(d[30]), "+f"(d[31]), "+f"(d[32]), "+f"(d[33]), "+f"(d[34]), "+f"(d[35]), "+f"(d[36]), "+f"(d[37]), "+f"(d[38]), "+f"(d[39]), "+f"(d[40]), "+f"(d[41]), "+f"(d[42]), "+f"(d[43]), "+f"(d[44]), "+f"(d[45]), "+f"(d[46]), "+f"(d[47])
        : "r"(a[AOFF + 0][0]), "r"(a[AOFF + 0][1]), "r"(a[AOFF + 0][2]), "r"(a[AOFF + 0][3]), "r"(a[AOFF + 1][0]), "r"(a[AOFF + 1][1]), "r"(a[AOFF + 1][2]), "r"(a[AOFF + 1][3]), "r"(a[AOFF + 2][0]), "r"(a[AOFF + 2][1]), "r"(a[AOFF + 2][2]), "r"(a[AOFF + 2][3]), "l"(descB), "n"(BOFF >> 4));
}
};
template <> struct Rng<1, 6, 9> {
template <int BOFF, int AOFF, int NA>
static __device__ __forceinline__ void run(float (&d)[48], const uint32_t (&a)[NA][4], uint64_t descB) {
    asm volatile(
        "{\n"
        ".reg .pred p0, p1;\n"
        ".reg .b64 ta, ta0, tb, tb0;\n"
        "setp.ne.b32 p0, 0, 0;\n"
        "setp.eq.b32 p1, 0, 0;\n"
        "add.s64 tb0, %60, %61;\n"
        "add.s64 tb, tb0, 192;\n"
        "wgmma.mma_async.sync.aligned.m64n96k16.f32.bf16.bf16 {%0, %1, %2, %3, %4, %5, %6, %7, %8, %9, %10, %11, %12, %13, %14, %15, %16, %17, %18, %19, %20, %21, %22, %23, %24, %25, %26, %27, %28, %29, %30, %31, %32, %33, %34, %35, %36, %37, %38, %39, %40, %41, %42, %43, %44, %45, %46, %47}, {%48, %49, %50, %51}, tb, p1, 1, 1, 1;\n"
        "add.s64 tb, tb0, 224;\n"
        "wgmma.mma_async.sync.aligned.m64n96k16.f32.bf16.bf16 {%0, %1, %2, %3, %4, %5, %6, %7, %8, %9, %10, %11, %12, %13, %14, %15, %16, %17, %18, %19, %20, %21, %22, %23, %24, %25, %26, %27, %28, %29, %30, %31, %32, %33, %34, %35, %36, %37, %38, %39, %40, %41, %42, %43, %44, %45, %46, %47}, {%52, %53, %54, %55}, tb, p1, 1, 1, 1;\n"
        "add.s64 tb, tb0, 256;\n"
        "wgmma.mma_async.sync.aligned.m64n96k16.f32.bf16.bf16 {%0, %1, %2, %3, %4, %5, %6, %7, %8, %9, %10, %11, %12, %13, %14, %15, %16, %17, %18, %19, %20, %21, %22, %23, %24, %25, %26, %27, %28, %29, %30, %31, %32, %33, %34, %35, %36, %37, %38, %39, %40, %41, %42, %43, %44, %45, %46, %47}, {%56, %57, %58, %59}, tb, p1, 1, 1, 1;\n"
        "}\n"
        : "+f"(d[0]), "+f"(d[1]), "+f"(d[2]), "+f"(d[3]), "+f"(d[4]), "+f"(d[5]), "+f"(d[6]), "+f"(d[7]), "+f"(d[8]), "+f"(d[9]), "+f"(d[10]), "+f"(d[11]), "+f"(d[12]), "+f"(d[13]), "+f"(d[14]), "+f"(d[15]), "+f"(d[16]), "+f"(d[17]), "+f"(d[18]), "+f"(d[19]), "+f"(d[20]), "+f"(d[21]), "+f"(d[22]), "+f"(d[23]), "+f"(d[24]), "+f"(d[25]), "+f"(d[26]), "+f"(d[27]), "+f"(d[28]), "+f"(d[29]), "+f"(d[30]), "+f"(d[31]), "+f"(d[32]), "+f"(d[33]), "+f"(d[34]), "+f"(d[35]), "+f"(d[36]), "+f"(d[37]), "+f"(d[38]), "+f"(d[39]), "+f"(d[40]), "+f"(d[41]), "+f"(d[42]), "+f"(d[43]), "+f"(d[44]), "+f"(d[45]), "+f"(d[46]), "+f"(d[47])
        : "r"(a[AOFF + 0][0]), "r"(a[AOFF + 0][1]), "r"(a[AOFF + 0][2]), "r"(a[AOFF + 0][3]), "r"(a[AOFF + 1][0]), "r"(a[AOFF + 1][1]), "r"(a[AOFF + 1][2]), "r"(a[AOFF + 1][3]), "r"(a[AOFF + 2][0]), "r"(a[AOFF + 2][1]), "r"(a[AOFF + 2][2]), "r"(a[AOFF + 2][3]), "l"(descB), "n"(BOFF >> 4));
}
};
template <> struct Rng<0, 6, 10> {
template <int BOFF, int AOFF, int NA>
static __device__ __forceinline__ void run(float (&d)[48], const uint32_t (&a)[NA][4], uint64_t descB) {
    asm volatile(
        "{\n"
        ".reg .pred p0, p1;\n"
        ".reg .b64 ta, ta0, tb, tb0;\n"
        "setp.ne.b32 p0, 0, 0;\n"
        "setp.eq.b32 p1, 0, 0;\n"
        "add.s64 tb0, %64, %65;\n"
        "add.s64 tb, tb0, 1600;\n"
        "wgmma.mma_async.sync.aligned.m64n96k16.f32.bf16.bf16 {%0, %1, %2, %3, %4, %5, %6, %7, %8, %9, %10, %11, %12, %13, %14, %15, %16, %17, %18, %19, %20, %21, %22, %23, %24, %25, %26, %27, %28, %29, %30, %31, %32, %33, %34, %35, %36, %37, %38, %39, %40, %41, %42, %43, %44, %45, %46, %47}, {%48, %49, %50, %51}, tb, p1, 1, 1, 1;\n"
        "add.s64 tb, tb0, 1632;\n"
        "wgmma.mma_async.sync.aligned.m64n96k16.f32.bf16.bf16 {%0, %1, %2, %3, %4, %5, %6, %7, %8, %9, %10, %11, %12, %13, %14, %15, %16, %17, %18, %19, %20, %21, %22, %23, %24, %25, %26, %27, %28, %29, %30, %31, %32, %33, %34, %35, %36, %37, %38, %39, %40, %41, %42, %43, %44, %45, %46, %47}, {%52, %53, %54, %55}, tb, p1, 1, 1, 1;\n"
        "add.s64 tb, tb0, 3072;\n"
        "wgmma.mma_async.sync.aligned.m64n96k16.f32.bf16.bf16 {%0, %1, %2, %3, %4, %5, %6, %7, %8, %9, %10, %11, %12, %13, %14, %15, %16, %17, %18, %19, %20, %21, %22, %23, %24, %25, %26, %27, %28, %29, %30, %31, %32, %33, %34, %35, %36, %37, %38, %39, %40, %41, %42, %43, %44, %45, %46, %47}, {%56, %57, %58, %59}, tb, p1, 1, 1, 1;\n"
        "add.s64 tb, tb0, 3104;\n"
        "wgmma.mma_async.sync.aligned.m64n96k16.f32.bf16.bf16 {%0, %1, %2, %3, %4, %5, %6, %7, %8, %9, %10, %11, %12, %13, %14, %15, %16, %17, %18, %19, %20, %21, %22, %23, %24, %25, %26, %27, %28, %29, %30, %31, %32, %33, %34, %35, %36, %37, %38, %39, %40, %41, %42, %43, %44, %45, %46, %47}, {%60, %61, %62, %63}, tb, p1, 1, 1, 1;\n"
        "}\n"
        : "+f"(d[0]), "+f"(d[1]), "+f"(d[2]), "+f"(d[3]), "+f"(d[4]), "+f"(d[5]), "+f"(d[6]), "+f"(d[7]), "+f"(d[8]), "+f"(d[9]), "+f"(d[10]), "+f"(d[11]), "+f"(d[12]), "+f"(d[13]), "+f"(d[14]), "+f"(d[15]), "+f"(d[16]), "+f"(d[17]), "+f"(d[18]), "+f"(d[19]), "+f"(d[20]), "+f"(d[21]), "+f"(d[22]), "+f"(d[23]), "+f"(d[24]), "+f"(d[25]), "+f"(d[26]), "+f"(d[27]), "+f"(d[28]), "+f"(d[29]), "+f"(d[30]), "+f"(d[31]), "+f"(d[32]), "+f"(d[33]), "+f"(d[34]), "+f"(d[35]), "+f"(d[36]), "+f"(d[37]), "+f"(d[38]), "+f"(d[39]), "+f"(d[40]), "+f"(d[41]), "+f"(d[42]), "+f"(d[43]), "+f"(d[44]), "+f"(d[45]), "+f"(d[46]), "+f"(d[47])
        : "r"(a[AOFF + 0][0]), "r"(a[AOFF + 0][1]), "r"(a[AOFF + 0][2]), "r"(a[AOFF + 0][3]), "r"(a[AOFF + 1][0]), "r"(a[AOFF + 1][1]), "r"(a[AOFF + 1][2]), "r"(a[AOFF + 1][3]), "r"(a[AOFF + 2][0]), "r"(a[AOFF + 2][1]), "r"(a[AOFF + 2][2]), "r"(a[AOFF + 2][3]), "r"(a[AOFF + 3][0]), "r"(a[AOFF + 3][1]), "r"(a[AOFF + 3][2]), "r"(a[AOFF + 3][3]), "l"(descB), "n"(BOFF >> 4));
}
};
template <> struct Rng<1, 6, 10> {
template <int BOFF, int AOFF, int NA>
static __device__ __forceinline__ void run(float (&d)[48], const uint32_t (&a)[NA][4], uint64_t descB) {
    asm volatile(
        "{\n"
        ".reg .pred p0, p1;\n"
        ".reg .b64 ta, ta0, tb, tb0;\n"
        "setp.ne.b32 p0, 0, 0;\n"
        "setp.eq.b32 p1, 0, 0;\n"
        "add.s64 tb0, %64, %65;\n"
        "add.s64 tb, tb0, 192;\n"
        "wgmma.mma_async.sync.aligned.m64n96k16.f32.bf16.bf16 {%0, %1, %2, %3, %4, %5, %6, %7, %8, %9, %10, %11, %12, %13, %14, %15, %16, %17, %18, %19, %20, %21, %22, %23, %24, %25, %26, %27, %28, %29, %30, %31, %32, %33, %34, %35, %36, %37, %38, %39, %40, %41, %42, %43, %44, %45, %46, %47}, {%48, %49, %50, %51}, tb, p1, 1, 1, 1;\n"
        "add.s64 tb, tb0, 224;\n"
        "wgmma.mma_async.sync.aligned.m64n96k16.f32.bf16.bf16 {%0, %1, %2, %3, %4, %5, %6, %7, %8, %9, %10, %11, %12, %13, %14, %15, %16, %17, %18, %19, %20, %21, %22, %23, %24, %25, %26, %27, %28, %29, %30, %31, %32, %33, %34, %35, %36, %37, %38, %39, %40, %41, %42, %43, %44, %45, %46, %47}, {%52, %53, %54, %55}, tb, p1, 1, 1, 1;\n"
        "add.s64 tb, tb0, 256;\n"
        "wgmma.mma_async.sync.aligned.m64n96k16.f32.bf16.bf16 {%0, %1, %2, %3, %4, %5, %6, %7, %8, %9, %10, %11, %12, %13, %14, %15, %16, %17, %18, %19, %20, %21, %22, %23, %24, %25, %26, %27, %28, %29, %30, %31, %32, %33, %34, %35, %36, %37, %38, %39, %40, %41, %42, %43, %44, %45, %46, %47}, {%56, %57, %58, %59}, tb, p1, 1, 1, 1;\n"
        "add.s64 tb, tb0, 288;\n"
        "wgmma.mma_async.sync.aligned.m64n96k16.f32.bf16.bf16 {%0, %1, %2, %3, %4, %5, %6, %7, %8, %9, %10, %11, %12, %13, %14, %15, %16, %17, %18, %19, %20, %21, %22, %23, %24, %25, %26, %27, %28, %29, %30, %31, %32, %33, %34, %35, %36, %37, %38, %39, %40, %41, %42, %43, %44, %45, %46, %47}, {%60, %61, %62, %63}, tb, p1, 1, 1, 1;\n"
        "}\n"
        : "+f"(d[0]), "+f"(d[1]), "+f"(d[2]), "+f"(d[3]), "+f"(d[4]), "+f"(d[5]), "+f"(d[6]), "+f"(d[7]), "+f"(d[8]), "+f"(d[9]), "+f"(d[10]), "+f"(d[11]), "+f"(d[12]), "+f"(d[13]), "+f"(d[14]), "+f"(d[15]), "+f"(d[16]), "+f"(d[17]), "+f"(d[18]), "+f"(d[19]), "+f"(d[20]), "+f"(d[21]), "+f"(d[22]), "+f"(d[23]), "+f"(d[24]), "+f"(d[25]), "+f"(d[26]), "+f"(d[27]), "+f"(d[28]), "+f"(d[29]), "+f"(d[30]), "+f"(d[31]), "+f"(d[32]), "+f"(d[33]), "+f"(d[34]), "+f"(d[35]), "+f"(d[36]), "+f"(d[37]), "+f"(d[38]), "+f"(d[39]), "+f"(d[40]), "+f"(d[41]), "+f"(d[42]), "+f"(d[43]), "+f"(d[44]), "+f"(d[45]), "+f"(d[46]), "+f"(d[47])
        : "r"(a[AOFF + 0][0]), "r"(a[AOFF + 0][1]), "r"(a[AOFF + 0][2]), "r"(a[AOFF + 0][3]), "r"(a[AOFF + 1][0]), "r"(a[AOFF + 1][1]), "r"(a[AOFF + 1][2]), "r"(a[AOFF + 1][3]), "r"(a[AOFF + 2][0]), "r"(a[AOFF + 2][1]), "r"(a[AOFF + 2][2]), "r"(a[AOFF + 2][3]), "r"(a[AOFF + 3][0]), "r"(a[AOFF + 3][1]), "r"(a[AOFF + 3][2]), "r"(a[AOFF + 3][3]), "l"(descB), "n"(BOFF >> 4));
}
};
template <> struct Rng<0, 6, 12> {
template <int BOFF, int AOFF, int NA>
static __device__ __forceinline__ void run(float (&d)[48], const uint32_t (&a)[NA][4], uint64_t descB) {
    asm volatile(
        "{\n"
        ".reg .pred p0, p1;\n"
        ".reg .b64 ta, ta0, tb, tb0;\n"
        "setp.ne.b32 p0, 0, 0;\n"
        "setp.eq.b32 p1, 0, 0;\n"
        "add.s64 tb0, %72, %73;\n"
        "add.s64 tb, tb0, 1600;\n"
        "wgmma.mma_async.sync.aligned.m64n96k16.f32.bf16.bf16 {%0, %1, %2, %3, %4, %5, %6, %7, %8, %9, %10, %11, %12, %13, %14, %15, %16, %17, %18, %19, %20, %21, %22, %23, %24, %25, %26, %27, %28, %29, %30, %31, %32, %33, %34, %35, %36, %37, %38, %39, %40, %41, %42, %43, %44, %45, %46, %47}, {%48, %49, %50, %51}, tb, p1, 1, 1, 1;\n"
        "add.s64 tb, tb0, 1632;\n"
        "wgmma.mma_async.sync.aligned.m64n96k16.f32.bf16.bf16 {%0, %1, %2, %3, %4, %5, %6, %7, %8, %9, %10, %11, %12, %13, %14, %15, %16, %17, %18, %19, %20, %21, %22, %23, %24, %25, %26, %27, %28, %29, %30, %31, %32, %33, %34, %35, %36, %37, %38, %39, %40, %41, %42, %43, %44, %45, %46, %47}, {%52, %53, %54, %55}, tb, p1, 1, 1, 1;\n"
        "add.s64 tb, tb0, 3072;\n"
        "wgmma.mma_async.sync.aligned.m64n96k16.f32.bf16.bf16 {%0, %1, %2, %3, %4, %5, %6, %7, %8, %9, %10, %11, %12, %13, %14, %15, %16, %17, %18, %19, %20, %21, %22, %23, %24, %25, %26, %27, %28, %29, %30, %31, %32, %33, %34, %35, %36, %37, %38, %39, %40, %41, %42, %43, %44, %45, %46, %47}, {%56, %57, %58, %59}, tb, p1, 1, 1, 1;\n"
        "add.s64 tb, tb0, 3104;\n"
        "wgmma.mma_async.sync.aligned.m64n96k16.f32.bf16.bf16 {%0, %1, %2, %3, %4, %5, %6, %7, %8, %9, %10, %11, %12, %13, %14, %15, %16, %17, %18, %19, %20, %21, %22, %23, %24, %25, %26, %27, %28, %29, %30, %31, %32, %33, %34, %35, %36, %37, %38, %39, %40, %41, %42, %43, %44, %45, %46, %47}, {%60, %61, %62, %63}, tb, p1, 1, 1, 1;\n"
        "add.s64 tb, tb0, 3136;\n"
        "wgmma.mma_async.sync.aligned.m64n96k16.f32.bf16.bf16 {%0, %1, %2, %3, %4, %5, %6, %7, %8, %9, %10, %11, %12, %13, %14, %15, %16, %17, %18, %19, %20, %21, %22, %23, %24, %25, %26, %27, %28, %29, %30, %31, %32, %33, %34, %35, %36, %37, %38, %39, %40, %41, %42, %43, %44, %45, %46, %47}, {%64, %65, %66, %67}, tb, p1, 1, 1, 1;\n"
        "add.s64 tb, tb0, 3168;\n"
        "wgmma.mma_async.sync.aligned.m64n96k16.f32.bf16.bf16 {%0, %1, %2, %3, %4, %5, %6, %7, %8, %9, %10, %11, %12, %13, %14, %15, %16, %17, %18, %19, %20, %21, %22, %23, %24, %25, %26, %27, %28, %29, %30, %31, %32, %33, %34, %35, %36, %37, %38, %39, %40, %41, %42, %43, %44, %45, %46, %47}, {%68, %69, %70, %71}, tb, p1, 1, 1, 1;\n"
        "}\n"
        : "+f"(d[0]), "+f"(d[1]), "+f"(d[2]), "+f"(d[3]), "+f"(d[4]), "+f"(d[5]), "+f"(d[6]), "+f"(d[7]), "+f"(d[8]), "+f"(d[9]), "+f"(d[10]), "+f"(d[11]), "+f"(d[12]), "+f"(d[13]), "+f"(d[14]), "+f"(d[15]), "+f"(d[16]), "+f"(d[17]), "+f"(d[18]), "+f"(d[19]), "+f"(d[20]), "+f"(d[21]), "+f"(d[22]), "+f"(d[23]), "+f"(d[24]), "+f"(d[25]), "+f"(d[26]), "+f"(d[27]), "+f"(d[28]), "+f"(d[29]), "+f"(d[30]), "+f"(d[31]), "+f"(d[32]), "+f"(d[33]), "+f"(d[34]), "+f"(d[35]), "+f"(d[36]), "+f"(d[37]), "+f"(d[38]), "+f"(d[39]), "+f"(d[40]), "+f"(d[41]), "+f"(d[42]), "+f"(d[43]), "+f"(d[44]), "+f"(d[45]), "+f"(d[46]), "+f"(d[47])
        : "r"(a[AOFF + 0][0]), "r"(a[AOFF + 0][1]), "r"(a[AOFF + 0][2]), "r"(a[AOFF + 0][3]), "r"(a[AOFF + 1][0]), "r"(a[AOFF + 1][1]), "r"(a[AOFF + 1][2]), "r"(a[AOFF + 1][3]), "r"(a[AOFF + 2][0]), "r"(a[AOFF + 2][1]), "r"(a[AOFF + 2][2]), "r"(a[AOFF + 2][3]), "r"(a[AOFF + 3][0]), "r"(a[AOFF + 3][1]), "r"(a[AOFF + 3][2]), "r"(a[AOFF + 3][3]), "r"(a[AOFF + 4][0]), "r"(a[AOFF + 4][1]), "r"(a[AOFF + 4][2]), "r"(a[AOFF + 4][3]), "r"(a[AOFF + 5][0]), "r"(a[AOFF + 5][1]), "r"(a[AOFF + 5][2]), "r"(a[AOFF + 5][3]), "l"(descB), "n"(BOFF >> 4));
}
};
template <> struct Rng<1, 6, 12> {
template <int BOFF, int AOFF, int NA>
static __device__ __forceinline__ void run(float (&d)[48], const uint32_t (&a)[NA][4], uint64_t descB) {
    asm volatile(
        "{\n"
        ".reg .pred p0, p1;\n"
        ".reg .b64 ta, ta0, tb, tb0;\n"
        "setp.ne.b32 p0, 0, 0;\n"
        "setp.eq.b32 p1, 0, 0;\n"
        "add.s64 tb0, %72, %73;\n"
        "add.s64 tb, tb0, 192;\n"
        "wgmma.mma_async.sync.aligned.m64n96k16.f32.bf16.bf16 {%0, %1, %2, %3, %4, %5, %6, %7, %8, %9, %10, %11, %12, %13, %14, %15, %16, %17, %18, %19, %20, %21, %22, %23, %24, %25, %26, %27, %28, %29, %30, %31, %32, %33, %34, %35, %36, %37, %38, %39, %40, %41, %42, %43, %44, %45, %46, %47}, {%48, %49, %50, %51}, tb, p1, 1, 1, 1;\n"
        "add.s64 tb, tb0, 224;\n"
        "wgmma.mma_async.sync.aligned.m64n96k16.f32.bf16.bf16 {%0, %1, %2, %3, %4, %5, %6, %7, %8, %9, %10, %11, %12, %13, %14, %15, %16, %17, %18, %19, %20, %21, %22, %23, %24, %25, %26, %27, %28, %29, %30, %31, %32, %33, %34, %35, %36, %37, %38, %39, %40, %41, %42, %43, %44, %45, %46, %47}, {%52, %53, %54, %55}, tb, p1, 1, 1, 1;\n"
        "add.s64 tb, tb0, 256;\n"
        "wgmma.mma_async.sync.aligned.m64n96k16.f32.bf16.bf16 {%0, %1, %2, %3, %4, %5, %6, %7, %8, %9, %10, %11, %12, %13, %14, %15, %16, %17, %18, %19, %20, %21, %22, %23, %24, %25, %26, %27, %28, %29, %30, %31, %32, %33, %34, %35, %36, %37, %38, %39, %40, %41, %42, %43, %44, %45, %46, %47}, {%56, %57, %58, %59}, tb, p1, 1, 1, 1;\n"
        "add.s64 tb, tb0, 288;\n"
        "wgmma.mma_async.sync.aligned.m64n96k16.f32.bf16.bf16 {%0, %1, %2, %3, %4, %5, %6, %7, %8, %9, %10, %11, %12, %13, %14, %15, %16, %17, %18, %19, %20, %21, %22, %23, %24, %25, %26, %27, %28, %29, %30, %31, %32, %33, %34, %35, %36, %37, %38, %39, %40, %41, %42, %43, %44, %45, %46, %47}, {%60, %61, %62, %63}, tb, p1, 1, 1, 1;\n"
        "add.s64 tb, tb0, 320;\n"
        "wgmma.mma_async.sync.aligned.m64n96k16.f32.bf16.bf16 {%0, %1, %2, %3, %4, %5, %6, %7, %8, %9, %10, %11, %12, %13, %14, %15, %16, %17, %18, %19, %20, %21, %22, %23, %24, %25, %26, %27, %28, %29, %30, %31, %32, %33, %34, %35, %36, %37, %38, %39, %40, %41, %42, %43, %44, %45, %46, %47}, {%64, %65, %66, %67}, tb, p1, 1, 1, 1;\n"
        "add.s64 tb, tb0, 352;\n"
        "wgmma.mma_async.sync.aligned.m64n96k16.f32.bf16.bf16 {%0, %1, %2, %3, %4, %5, %6, %7, %8, %9, %10, %11, %12, %13, %14, %15, %16, %17, %18, %19, %20, %21, %22, %23, %24, %25, %26, %27, %28, %29, %30, %31, %32, %33, %34, %35, %36, %37, %38, %39, %40, %41, %42, %43, %44, %45, %46, %47}, {%68, %69, %70, %71}, tb, p1, 1, 1, 1;\n"
        "}\n"
        : "+f"(d[0]), "+f"(d[1]), "+f"(d[2]), "+f"(d[3]), "+f"(d[4]), "+f"(d[5]), "+f"(d[6]), "+f"(d[7]), "+f"(d[8]), "+f"(d[9]), "+f"(d[10]), "+f"(d[11]), "+f"(d[12]), "+f"(d[13]), "+f"(d[14]), "+f"(d[15]), "+f"(d[16]), "+f"(d[17]), "+f"(d[18]), "+f"(d[19]), "+f"(d[20]), "+f"(d[21]), "+f"(d[22]), "+f"(d[23]), "+f"(d[24]), "+f"(d[25]), "+f"(d[26]), "+f"(d[27]), "+f"(d[28]), "+f"(d[29]), "+f"(d[30]), "+f"(d[31]), "+f"(d[32]), "+f"(d[33]), "+f"(d[34]), "+f"(d[35]), "+f"(d[36]), "+f"(d[37]), "+f"(d[38]), "+f"(d[39]), "+f"(d[40]), "+f"(d[41]), "+f"(d[42]), "+f"(d[43]), "+f"(d[44]), "+f"(d[45]), "+f"(d[46]), "+f"(d[47])
        : "r"(a[AOFF + 0][0]), "r"(a[AOFF + 0][1]), "r"(a[AOFF + 0][2]), "r"(a[AOFF + 0][3]), "r"(a[AOFF + 1][0]), "r"(a[AOFF + 1][1]), "r"(a[AOFF + 1][2]), "r"(a[AOFF + 1][3]), "r"(a[AOFF + 2][0]), "r"(a[AOFF + 2][1]), "r"(a[AOFF + 2][2]), "r"(a[AOFF + 2][3]), "r"(a[AOFF + 3][0]), "r"(a[AOFF + 3][1]), "r"(a[AOFF + 3][2]), "r"(a[AOFF + 3][3]), "r"(a[AOFF + 4][0]), "r"(a[AOFF + 4][1]), "r"(a[AOFF + 4][2]), "r"(a[AOFF + 4][3]), "r"(a[AOFF + 5][0]), "r"(a[AOFF + 5][1]), "r"(a[AOFF + 5][2]), "r"(a[AOFF + 5][3]), "l"(descB), "n"(BOFF >> 4));
}
};
template <> struct Rng<0, 7, 12> {
template <int BOFF, int AOFF, int NA>
static __device__ __forceinline__ void run(float (&d)[48], const uint32_t (&a)[NA][4], uint64_t descB) {
    asm volatile(
        "{\n"
        ".reg .pred p0, p1;\n"
        ".reg .b64 ta, ta0, tb, tb0;\n"
        "setp.ne.b32 p0, 0, 0;\n"
        "setp.eq.b32 p1, 0, 0;\n"
        "add.s64 tb0, %68, %69;\n"
        "add.s64 tb, tb0, 1632;\n"
        "wgmma.mma_async.sync.aligned.m64n96k16.f32.bf16.bf16 {%0, %1, %2, %3, %4, %5, %6, %7, %8, %9, %10, %11, %12, %13, %14, %15, %16, %17, %18, %19, %20, %21, %22, %23, %24, %25, %26, %27, %28, %29, %30, %31, %32, %33, %34, %35, %36, %37, %38, %39, %40, %41, %42, %43, %44, %45, %46, %47}, {%48, %49, %50, %51}, tb, p1, 1, 1, 1;\n"
        "add.s64 tb, tb0, 3072;\n"
        "wgmma.mma_async.sync.aligned.m64n96k16.f32.bf16.bf16 {%0, %1, %2, %3, %4, %5, %6, %7, %8, %9, %10, %11, %12, %13, %14, %15, %16, %17, %18, %19, %20, %21, %22, %23, %24, %25, %26, %27, %28, %29, %30, %31, %32, %33, %34, %35, %36, %37, %38, %39, %40, %41, %42, %43, %44, %45, %46, %47}, {%52, %53, %54, %55}, tb, p1, 1, 1, 1;\n"
        "add.s64 tb, tb0, 3104;\n"
        "wgmma.mma_async.sync.aligned.m64n96k16.f32.bf16.bf16 {%0, %1, %2, %3, %4, %5, %6, %7, %8, %9, %10, %11, %12, %13, %14, %15, %16, %17, %18, %19, %20, %21, %22, %23, %24, %25, %26, %27, %28, %29, %30, %31, %32, %33, %34, %35, %36, %37, %38, %39, %40, %41, %42, %43, %44, %45, %46, %47}, {%56, %57, %58, %59}, tb, p1, 1, 1, 1;\n"
        "add.s64 tb, tb0, 3136;\n"
        "wgmma.mma_async.sync.aligned.m64n96k16.f32.bf16.bf16 {%0, %1, %2, %3, %4, %5, %6, %7, %8, %9, %10, %11, %12, %13, %14, %15, %16, %17, %18, %19, %20, %21, %22, %23, %24, %25, %26, %27, %28, %29, %30, %31, %32, %33, %34, %35, %36, %37, %38, %39, %40, %41, %42, %43, %44, %45, %46, %47}, {%60, %61, %62, %63}, tb, p1, 1, 1, 1;\n"
        "add.s64 tb, tb0, 3168;\n"
        "wgmma.mma_async.sync.aligned.m64n96k16.f32.bf16.bf16 {%0, %1, %2, %3, %4, %5, %6, %7, %8, %9, %10, %11, %12, %13, %14, %15, %16, %17, %18, %19, %20, %21, %22, %23, %24, %25, %26, %27, %28, %29, %30, %31, %32, %33, %34, %35, %36, %37, %38, %39, %40, %41, %42, %43, %44, %45, %46, %47}, {%64, %65, %66, %67}, tb, p1, 1, 1, 1;\n"
        "}\n"
        : "+f"(d[0]), "+f"(d[1]), "+f"(d[2]), "+f"(d[3]), "+f"(d[4]), "+f"(d[5]), "+f"(d[6]), "+f"(d[7]), "+f"(d[8]), "+f"(d[9]), "+f"(d[10]), "+f"(d[11]), "+f"(d[12]), "+f"(d[13]), "+f"(d[14]), "+f"(d[15]), "+f"(d[16]), "+f"(d[17]), "+f"(d[18]), "+f"(d[19]), "+f"(d[20]), "+f"(d[21]), "+f"(d[22]), "+f"(d[23]), "+f"(d[24]), "+f"(d[25]), "+f"(d[26]), "+f"(d[27]), "+f"(d[28]), "+f"(d[29]), "+f"(d[30]), "+f"(d[31]), "+f"(d[32]), "+f"(d[33]), "+f"(d[34]), "+f"(d[35]), "+f"(d[36]), "+f"(d[37]), "+f"(d[38]), "+f"(d[39]), "+f"(d[40]), "+f"(d[41]), "+f"(d[42]), "+f"(d[43]), "+f"(d[44]), "+f"(d[45]), "+f"(d[46]), "+f"(d[47])
        : "r"(a[AOFF + 0][0]), "r"(a[AOFF + 0][1]), "r"(a[AOFF + 0][2]), "r"(a[AOFF + 0][3]), "r"(a[AOFF + 1][0]), "r"(a[AOFF + 1][1]), "r"(a[AOFF + 1][2]), "r"(a[AOFF + 1][3]), "r"(a[AOFF + 2][0]), "r"(a[AOFF + 2][1]), "r"(a[AOFF + 2][2]), "r"(a[AOFF + 2][3]), "r"(a[AOFF + 3][0]), "r"(a[AOFF + 3][1]), "r"(a[AOFF + 3][2]), "r"(a[AOFF + 3][3]), "r"(a[AOFF + 4][0]), "r"(a[AOFF + 4][1]), "r"(a[AOFF + 4][2]), "r"(a[AOFF + 4][3]), "l"(descB), "n"(BOFF >> 4));
}
};
template <> struct Rng<1, 7, 12> {
template <int BOFF, int AOFF, int NA>
static __device__ __forceinline__ void run(float (&d)[48], const uint32_t (&a)[NA][4], uint64_t descB) {
    asm volatile(
        "{\n"
        ".reg .pred p0, p1;\n"
        ".reg .b64 ta, ta0, tb, tb0;\n"
        "setp.ne.b32 p0, 0, 0;\n"
        "setp.eq.b32 p1, 0, 0;\n"
        "add.s64 tb0, %68, %69;\n"
        "add.s64 tb, tb0, 224;\n"
        "wgmma.mma_async.sync.aligned.m64n96k16.f32.bf16.bf16 {%0, %1, %2, %3, %4, %5, %6, %7, %8, %9, %10, %11, %12, %13, %14, %15, %16, %17, %18, %19, %20, %21, %22, %23, %24, %25, %26, %27, %28, %29, %30, %31, %32, %33, %34, %35, %36, %37, %38, %39, %40, %41, %42, %43, %44, %45, %46, %47}, {%48, %49, %50, %51}, tb, p1, 1, 1, 1;\n"
        "add.s64 tb, tb0, 256;\n"
        "wgmma.mma_async.sync.aligned.m64n96k16.f32.bf16.bf16 {%0, %1, %2, %3, %4, %5, %6, %7, %8, %9, %10, %11, %12, %13, %14, %15, %16, %17, %18, %19, %20, %21, %22, %23, %24, %25, %26, %27, %28, %29, %30, %31, %32, %33, %34, %35, %36, %37, %38, %39, %40, %41, %42, %43, %44, %45, %46, %47}, {%52, %53, %54, %55}, tb, p1, 1, 1, 1;\n"
        "add.s64 tb, tb0, 288;\n"
        "wgmma.mma_async.sync.aligned.m64n96k16.f32.bf16.bf16 {%0, %1, %2, %3, %4, %5, %6, %7, %8, %9, %10, %11, %12, %13, %14, %15, %16, %17, %18, %19, %20, %21, %22, %23, %24, %25, %26, %27, %28, %29, %30, %31, %32, %33, %34, %35, %36, %37, %38, %39, %40, %41, %42, %43, %44, %45, %46, %47}, {%56, %57, %58, %59}, tb, p1, 1, 1, 1;\n"
        "add.s64 tb, tb0, 320;\n"
        "wgmma.mma_async.sync.aligned.m64n96k16.f32.bf16.bf16 {%0, %1, %2, %3, %4, %5, %6, %7, %8, %9, %10, %11, %12, %13, %14, %15, %16, %17, %18, %19, %20, %21, %22, %23, %24, %25, %26, %27, %28, %29, %30, %31, %32, %33, %34, %35, %36, %37, %38, %39, %40, %41, %42, %43, %44, %45, %46, %47}, {%60, %61, %62, %63}, tb, p1, 1, 1, 1;\n"
        "add.s64 tb, tb0, 352;\n"
        "wgmma.mma_async.sync.aligned.m64n96k16.f32.bf16.bf16 {%0, %1, %2, %3, %4, %5, %6, %7, %8, %9, %10, %11, %12, %13, %14, %15, %16, %17, %18, %19, %20, %21, %22, %23, %24, %25, %26, %27, %28, %29, %30, %31, %32, %33, %34, %35, %36, %37, %38, %39, %40, %41, %42, %43, %44, %45, %46, %47}, {%64, %65, %66, %67}, tb, p1, 1, 1, 1;\n"
        "}\n"
        : "+f"(d[0]), "+f"(d[1]), "+f"(d[2]), "+f"(d[3]), "+f"(d[4]), "+f"(d[5]), "+f"(d[6]), "+f"(d[7]), "+f"(d[8]), "+f"(d[9]), "+f"(d[10]), "+f"(d[11]), "+f"(d[12]), "+f"(d[13]), "+f"(d[14]), "+f"(d[15]), "+f"(d[16]), "+f"(d[17]), "+f"(d[18]), "+f"(d[19]), "+f"(d[20]), "+f"(d[21]), "+f"(d[22]), "+f"(d[23]), "+f"(d[24]), "+f"(d[25]), "+f"(d[26]), "+f"(d[27]), "+f"(d[28]), "+f"(d[29]), "+f"(d[30]), "+f"(d[31]), "+f"(d[32]), "+f"(d[33]), "+f"(d[34]), "+f"(d[35]), "+f"(d[36]), "+f"(d[37]), "+f"(d[38]), "+f"(d[39]), "+f"(d[40]), "+f"(d[41]), "+f"(d[42]), "+f"(d[43]), "+f"(d[44]), "+f"(d[45]), "+f"(d[46]), "+f"(d[47])
        : "r"(a[AOFF + 0][0]), "r"(a[AOFF + 0][1]), "r"(a[AOFF + 0][2]), "r"(a[AOFF + 0][3]), "r"(a[AOFF + 1][0]), "r"(a[AOFF + 1][1]), "r"(a[AOFF + 1][2]), "r"(a[AOFF + 1][3]), "r"(a[AOFF + 2][0]), "r"(a[AOFF + 2][1]), "r"(a[AOFF + 2][2]), "r"(a[AOFF + 2][3]), "r"(a[AOFF + 3][0]), "r"(a[AOFF + 3][1]), "r"(a[AOFF + 3][2]), "r"(a[AOFF + 3][3]), "r"(a[AOFF + 4][0]), "r"(a[AOFF + 4][1]), "r"(a[AOFF + 4][2]), "r"(a[AOFF + 4][3]), "l"(descB), "n"(BOFF >> 4));
}
};
template <> struct Rng<0, 8, 12> {
template <int BOFF, int AOFF, int NA>
static __device__ __forceinline__ void run(float (&d)[48], const uint32_t (&a)[NA][4], uint64_t descB) {
    asm volatile(
        "{\n"
        ".reg .pred p0, p1;\n"
        ".reg .b64 ta, ta0, tb, tb0;\n"
        "setp.ne.b32 p0, 0, 0;\n"
        "setp.eq.b32 p1, 0, 0;\n"
        "add.s64 tb0, %64, %65;\n"
        "add.s64 tb, tb0, 3072;\n"
        "wgmma.mma_async.sync.aligned.m64n96k16.f32.bf16.bf16 {%0, %1, %2, %3, %4, %5, %6, %7, %8, %9, %10, %11, %12, %13, %14, %15, %16, %17, %18, %19, %20, %21, %22, %23, %24, %25, %26, %27, %28, %29, %30, %31, %32, %33, %34, %35, %36, %37, %38, %39, %40, %41, %42, %43, %44, %45, %46, %47}, {%48, %49, %50, %51}, tb, p1, 1, 1, 1;\n"
        "add.s64 tb, tb0, 3104;\n"
        "wgmma.mma_async.sync.aligned.m64n96k16.f32.bf16.bf16 {%0, %1, %2, %3, %4, %5, %6, %7, %8, %9, %10, %11, %12, %13, %14, %15, %16, %17, %18, %19, %20, %21, %22, %23, %24, %25, %26, %27, %28, %29, %30, %31, %32, %33, %34, %35, %36, %37, %38, %39, %40, %41, %42, %43, %44, %45, %46, %47}, {%52, %53, %54, %55}, tb, p1, 1, 1, 1;\n"
        "add.s64 tb, tb0, 3136;\n"
        "wgmma.mma_async.sync.aligned.m64n96k16.f32.bf16.bf16 {%0, %1, %2, %3, %4, %5, %6, %7, %8, %9, %10, %11, %12, %13, %14, %15, %16, %17, %18, %19, %20, %21, %22, %23, %24, %25, %26, %27, %28, %29, %30, %31, %32, %33, %34, %35, %36, %37, %38, %39, %40, %41, %42, %43, %44, %45, %46, %47}, {%56, %57, %58, %59}, tb, p1, 1, 1, 1;\n"
        "add.s64 tb, tb0, 3168;\n"
        "wgmma.mma_async.sync.aligned.m64n96k16.f32.bf16.bf16 {%0, %1, %2, %3, %4, %5, %6, %7, %8, %9, %10, %11, %12, %13, %14, %15, %16, %17, %18, %19, %20, %21, %22, %23, %24, %25, %26, %27, %28, %29, %30, %31, %32, %33, %34, %35, %36, %37, %38, %39, %40, %41, %42, %43, %44, %45, %46, %47}, {%60, %61, %62, %63}, tb, p1, 1, 1, 1;\n"
        "}\n"
        : "+f"(d[0]), "+f"(d[1]), "+f"(d[2]), "+f"(d[3]), "+f"(d[4]), "+f"(d[5]), "+f"(d[6]), "+f"(d[7]), "+f"(d[8]), "+f"(d[9]), "+f"(d[10]), "+f"(d[11]), "+f"(d[12]), "+f"(d[13]), "+f"(d[14]), "+f"(d[15]), "+f"(d[16]), "+f"(d[17]), "+f"(d[18]), "+f"(d[19]), "+f"(d[20]), "+f"(d[21]), "+f"(d[22]), "+f"(d[23]), "+f"(d[24]), "+f"(d[25]), "+f"(d[26]), "+f"(d[27]), "+f"(d[28]), "+f"(d[29]), "+f"(d[30]), "+f"(d[31]), "+f"(d[32]), "+f"(d[33]), "+f"(d[34]), "+f"(d[35]), "+f"(d[36]), "+f"(d[37]), "+f"(d[38]), "+f"(d[39]), "+f"(d[40]), "+f"(d[41]), "+f"(d[42]), "+f"(d[43]), "+f"(d[44]), "+f"(d[45]), "+f"(d[46]), "+f"(d[47])
        : "r"(a[AOFF + 0][0]), "r"(a[AOFF + 0][1]), "r"(a[AOFF + 0][2]), "r"(a[AOFF + 0][3]), "r"(a[AOFF + 1][0]), "r"(a[AOFF + 1][1]), "r"(a[AOFF + 1][2]), "r"(a[AOFF + 1][3]), "r"(a[AOFF + 2][0]), "r"(a[AOFF + 2][1]), "r"(a[AOFF + 2][2]), "r"(a[AOFF + 2][3]), "r"(a[AOFF + 3][0]), "r"(a[AOFF + 3][1]), "r"(a[AOFF + 3][2]), "r"(a[AOFF + 3][3]), "l"(descB), "n"(BOFF >> 4));
}
};
template <> struct Rng<1, 8, 12> {
template <int BOFF, int AOFF, int NA>
static __device__ __forceinline__ void run(float (&d)[48], const uint32_t (&a)[NA][4], uint64_t descB) {
    asm volatile(
        "{\n"
        ".reg .pred p0, p1;\n"
        ".reg .b64 ta, ta0, tb, tb0;\n"
        "setp.ne.b32 p0, 0, 0;\n"
        "setp.eq.b32 p1, 0, 0;\n"
        "add.s64 tb0, %64, %65;\n"
        "add.s64 tb, tb0, 256;\n"
        "wgmma.mma_async.sync.aligned.m64n96k16.f32.bf16.bf16 {%0, %1, %2, %3, %4, %5, %6, %7, %8, %9, %10, %11, %12, %13, %14, %15, %16, %17, %18, %19, %20, %21, %22, %23, %24, %25, %26, %27, %28, %29, %30, %31, %32, %33, %34, %35, %36, %37, %38, %39, %40, %41, %42, %43, %44, %45, %46, %47}, {%48, %49, %50, %51}, tb, p1, 1, 1, 1;\n"
        "add.s64 tb, tb0, 288;\n"
        "wgmma.mma_async.sync.aligned.m64n96k16.f32.bf16.bf16 {%0, %1, %2, %3, %4, %5, %6, %7, %8, %9, %10, %11, %12, %13, %14, %15, %16, %17, %18, %19, %20, %21, %22, %23, %24, %25, %26, %27, %28, %29, %30, %31, %32, %33, %34, %35, %36, %37, %38, %39, %40, %41, %42, %43, %44, %45, %46, %47}, {%52, %53, %54, %55}, tb, p1, 1, 1, 1;\n"
        "add.s64 tb, tb0, 320;\n"
        "wgmma.mma_async.sync.aligned.m64n96k16.f32.bf16.bf16 {%0, %1, %2, %3, %4, %5, %6, %7, %8, %9, %10, %11, %12, %13, %14, %15, %16, %17, %18, %19, %20, %21, %22, %23, %24, %25, %26, %27, %28, %29, %30, %31, %32, %33, %34, %35, %36, %37, %38, %39, %40, %41, %42, %43, %44, %45, %46, %47}, {%56, %57, %58, %59}, tb, p1, 1, 1, 1;\n"
        "add.s64 tb, tb0, 352;\n"
        "wgmma.mma_async.sync.aligned.m64n96k16.f32.bf16.bf16 {%0, %1, %2, %3, %4, %5, %6, %7, %8, %9, %10, %11, %12, %13, %14, %15, %16, %17, %18, %19, %20, %21, %22, %23, %24, %25, %26, %27, %28, %29, %30, %31, %32, %33, %34, %35, %36, %37, %38, %39, %40, %41, %42, %43, %44, %45, %46, %47}, {%60, %61, %62, %63}, tb, p1, 1, 1, 1;\n"
        "}\n"
        : "+f"(d[0]), "+f"(d[1]), "+f"(d[2]), "+f"(d[3]), "+f"(d[4]), "+f"(d[5]), "+f"(d[6]), "+f"(d[7]), "+f"(d[8]), "+f"(d[9]), "+f"(d[10]), "+f"(d[11]), "+f"(d[12]), "+f"(d[13]), "+f"(d[14]), "+f"(d[15]), "+f"(d[16]), "+f"(d[17]), "+f"(d[18]), "+f"(d[19]), "+f"(d[20]), "+f"(d[21]), "+f"(d[22]), "+f"(d[23]), "+f"(d[24]), "+f"(d[25]), "+f"(d[26]), "+f"(d[27]), "+f"(d[28]), "+f"(d[29]), "+f"(d[30]), "+f"(d[31]), "+f"(d[32]), "+f"(d[33]), "+f"(d[34]), "+f"(d[35]), "+f"(d[36]), "+f"(d[37]), "+f"(d[38]), "+f"(d[39]), "+f"(d[40]), "+f"(d[41]), "+f"(d[42]), "+f"(d[43]), "+f"(d[44]), "+f"(d[45]), "+f"(d[46]), "+f"(d[47])
        : "r"(a[AOFF + 0][0]), "r"(a[AOFF + 0][1]), "r"(a[AOFF + 0][2]), "r"(a[AOFF + 0][3]), "r"(a[AOFF + 1][0]), "r"(a[AOFF + 1][1]), "r"(a[AOFF + 1][2]), "r"(a[AOFF + 1][3]), "r"(a[AOFF + 2][0]), "r"(a[AOFF + 2][1]), "r"(a[AOFF + 2][2]), "r"(a[AOFF + 2][3]), "r"(a[AOFF + 3][0]), "r"(a[AOFF + 3][1]), "r"(a[AOFF + 3][2]), "r"(a[AOFF + 3][3]), "l"(descB), "n"(BOFF >> 4));
}
};
template <> struct Rng<0, 9, 12> {
template <int BOFF, int AOFF, int NA>
static __device__ __forceinline__ void run(float (&d)[48], const uint32_t (&a)[NA][4], uint64_t descB) {
    asm volatile(
        "{\n"
        ".reg .pred p0, p1;\n"
        ".reg .b64 ta, ta0, tb, tb0;\n"
        "setp.ne.b32 p0, 0, 0;\n"
        "setp.eq.b32 p1, 0, 0;\n"
        "add.s64 tb0, %60, %61;\n"
        "add.s64 tb, tb0, 3104;\n"
        "wgmma.mma_async.sync.aligned.m64n96k16.f32.bf16.bf16 {%0, %1, %2, %3, %4, %5, %6, %7, %8, %9, %10, %11, %12, %13, %14, %15, %16, %17, %18, %19, %20, %21, %22, %23, %24, %25, %26, %27, %28, %29, %30, %31, %32, %33, %34, %35, %36, %37, %38, %39, %40, %41, %42, %43, %44, %45, %46, %47}, {%48, %49, %50, %51}, tb, p1, 1, 1, 1;\n"
        "add.s64 tb, tb0, 3136;\n"
        "wgmma.mma_async.sync.aligned.m64n96k16.f32.bf16.bf16 {%0, %1, %2, %3, %4, %5, %6, %7, %8, %9, %10, %11, %12, %13, %14, %15, %16, %17, %18, %19, %20, %21, %22, %23, %24, %25, %26, %27, %28, %29, %30, %31, %32, %33, %34, %35, %36, %37, %38, %39, %40, %41, %42, %43, %44, %45, %46, %47}, {%52, %53, %54, %55}, tb, p1, 1, 1, 1;\n"
        "add.s64 tb, tb0, 3168;\n"
        "wgmma.mma_async.sync.aligned.m64n96k16.f32.bf16.bf16 {%0, %1, %2, %3, %4, %5, %6, %7, %8, %9, %10, %11, %12, %13, %14, %15, %16, %17, %18, %19, %20, %21, %22, %23, %24, %25, %26, %27, %28, %29, %30, %31, %32, %33, %34, %35, %36, %37, %38, %39, %40, %41, %42, %43, %44, %45, %46, %47}, {%56, %57, %58, %59}, tb, p1, 1, 1, 1;\n"
        "}\n"
        : "+f"(d[0]), "+f"(d[1]), "+f"(d[2]), "+f"(d[3]), "+f"(d[4]), "+f"(d[5]), "+f"(d[6]), "+f"(d[7]), "+f"(d[8]), "+f"(d[9]), "+f"(d[10]), "+f"(d[11]), "+f"(d[12]), "+f"(d[13]), "+f"(d[14]), "+f"(d[15]), "+f"(d[16]), "+f"(d[17]), "+f"(d[18]), "+f"(d[19]), "+f"(d[20]), "+f"(d[21]), "+f"(d[22]), "+f"(d[23]), "+f"(d[24]), "+f"(d[25]), "+f"(d[26]), "+f"(d[27]), "+f"(d[28]), "+f"(d[29]), "+f"(d[30]), "+f"(d[31]), "+f"(d[32]), "+f"(d[33]), "+f"(d[34]), "+f"(d[35]), "+f"(d[36]), "+f"(d[37]), "+f"(d[38]), "+f"(d[39]), "+f"(d[40]), "+f"(d[41]), "+f"(d[42]), "+f"(d[43]), "+f"(d[44]), "+f"(d[45]), "+f"(d[46]), "+f"(d[47])
        : "r"(a[AOFF + 0][0]), "r"(a[AOFF + 0][1]), "r"(a[AOFF + 0][2]), "r"(a[AOFF + 0][3]), "r"(a[AOFF + 1][0]), "r"(a[AOFF + 1][1]), "r"(a[AOFF + 1][2]), "r"(a[AOFF + 1][3]), "r"(a[AOFF + 2][0]), "r"(a[AOFF + 2][1]), "r"(a[AOFF + 2][2]), "r"(a[AOFF + 2][3]), "l"(descB), "n"(BOFF >> 4));
}
};
template <> struct Rng<1, 9, 12> {
template <int BOFF, int AOFF, int NA>
static __device__ __forceinline__ void run(float (&d)[48], const uint32_t (&a)[NA][4], uint64_t descB) {
    asm volatile(
        "{\n"
        ".reg .pred p0, p1;\n"
        ".reg .b64 ta, ta0, tb, tb0;\n"
        "setp.ne.b32 p0, 0, 0;\n"
        "setp.eq.b32 p1, 0, 0;\n"
        "add.s64 tb0, %60, %61;\n"
        "add.s64 tb, tb0, 288;\n"
        "wgmma.mma_async.sync.aligned.m64n96k16.f32.bf16.bf16 {%0, %1, %2, %3, %4, %5, %6, %7, %8, %9, %10, %11, %12, %13, %14, %15, %16, %17, %18, %19, %20, %21, %22, %23, %24, %25, %26, %27, %28, %29, %30, %31, %32, %33, %34, %35, %36, %37, %38, %39, %40, %41, %42, %43, %44, %45, %46, %47}, {%48, %49, %50, %51}, tb, p1, 1, 1, 1;\n"
        "add.s64 tb, tb0, 320;\n"
        "wgmma.mma_async.sync.aligned.m64n96k16.f32.bf16.bf16 {%0, %1, %2, %3, %4, %5, %6, %7, %8, %9, %10, %11, %12, %13, %14, %15, %16, %17, %18, %19, %20, %21, %22, %23, %24, %25, %26, %27, %28, %29, %30, %31, %32, %33, %34, %35, %36, %37, %38, %39, %40, %41, %42, %43, %44, %45, %46, %47}, {%52, %53, %54, %55}, tb, p1, 1, 1, 1;\n"
        "add.s64 tb, tb0, 352;\n"
        "wgmma.mma_async.sync.aligned.m64n96k16.f32.bf16.bf16 {%0, %1, %2, %3, %4, %5, %6, %7, %8, %9, %10, %11, %12, %13, %14, %15, %16, %17, %18, %19, %20, %21, %22, %23, %24, %25, %26, %27, %28, %29, %30, %31, %32, %33, %34, %35, %36, %37, %38, %39, %40, %41, %42, %43, %44, %45, %46, %47}, {%56, %57, %58, %59}, tb, p1, 1, 1, 1;\n"
        "}\n"
        : "+f"(d[0]), "+f"(d[1]), "+f"(d[2]), "+f"(d[3]), "+f"(d[4]), "+f"(d[5]), "+f"(d[6]), "+f"(d[7]), "+f"(d[8]), "+f"(d[9]), "+f"(d[10]), "+f"(d[11]), "+f"(d[12]), "+f"(d[13]), "+f"(d[14]), "+f"(d[15]), "+f"(d[16]), "+f"(d[17]), "+f"(d[18]), "+f"(d[19]), "+f"(d[20]), "+f"(d[21]), "+f"(d[22]), "+f"(d[23]), "+f"(d[24]), "+f"(d[25]), "+f"(d[26]), "+f"(d[27]), "+f"(d[28]), "+f"(d[29]), "+f"(d[30]), "+f"(d[31]), "+f"(d[32]), "+f"(d[33]), "+f"(d[34]), "+f"(d[35]), "+f"(d[36]), "+f"(d[37]), "+f"(d[38]), "+f"(d[39]), "+f"(d[40]), "+f"(d[41]), "+f"(d[42]), "+f"(d[43]), "+f"(d[44]), "+f"(d[45]), "+f"(d[46]), "+f"(d[47])
        : "r"(a[AOFF + 0][0]), "r"(a[AOFF + 0][1]), "r"(a[AOFF + 0][2]), "r"(a[AOFF + 0][3]), "r"(a[AOFF + 1][0]), "r"(a[AOFF + 1][1]), "r"(a[AOFF + 1][2]), "r"(a[AOFF + 1][3]), "r"(a[AOFF + 2][0]), "r"(a[AOFF + 2][1]), "r"(a[AOFF + 2][2]), "r"(a[AOFF + 2][3]), "l"(descB), "n"(BOFF >> 4));
}
};
template <> struct Rng<0, 10, 12> {
template <int BOFF, int AOFF, int NA>
static __device__ __forceinline__ void run(float (&d)[48], const uint32_t (&a)[NA][4], uint64_t descB) {
    asm volatile(
        "{\n"
        ".reg .pred p0, p1;\n"
        ".reg .b64 ta, ta0, tb, tb0;\n"
        "setp.ne.b32 p0, 0, 0;\n"
        "setp.eq.b32 p1, 0, 0;\n"
        "add.s64 tb0, %56, %57;\n"
        "add.s64 tb, tb0, 3136;\n"
        "wgmma.mma_async.sync.aligned.m64n96k16.f32.bf16.bf16 {%0, %1, %2, %3, %4, %5, %6, %7, %8, %9, %10, %11, %12, %13, %14, %15, %16, %17, %18, %19, %20, %21, %22, %23, %24, %25, %26, %27, %28, %29, %30, %31, %32, %33, %34, %35, %36, %37, %38, %39, %40, %41, %42, %43, %44, %45, %46, %47}, {%48, %49, %50, %51}, tb, p1, 1, 1, 1;\n"
        "add.s64 tb, tb0, 3168;\n"
        "wgmma.mma_async.sync.aligned.m64n96k16.f32.bf16.bf16 {%0, %1, %2, %3, %4, %5, %6, %7, %8, %9, %10, %11, %12, %13, %14, %15, %16, %17, %18, %19, %20, %21, %22, %23, %24, %25, %26, %27, %28, %29, %30, %31, %32, %33, %34, %35, %36, %37, %38, %39, %40, %41, %42, %43, %44, %45, %46, %47}, {%52, %53, %54, %55}, tb, p1, 1, 1, 1;\n"
        "}\n"
        : "+f"(d[0]), "+f"(d[1]), "+f"(d[2]), "+f"(d[3]), "+f"(d[4]), "+f"(d[5]), "+f"(d[6]), "+f"(d[7]), "+f"(d[8]), "+f"(d[9]), "+f"(d[10]), "+f"(d[11]), "+f"(d[12]), "+f"(d[13]), "+f"(d[14]), "+f"(d[15]), "+f"(d[16]), "+f"(d[17]), "+f"(d[18]), "+f"(d[19]), "+f"(d[20]), "+f"(d[21]), "+f"(d[22]), "+f"(d[23]), "+f"(d[24]), "+f"(d[25]), "+f"(d[26]), "+f"(d[27]), "+f"(d[28]), "+f"(d[29]), "+f"(d[30]), "+f"(d[31]), "+f"(d[32]), "+f"(d[33]), "+f"(d[34]), "+f"(d[35]), "+f"(d[36]), "+f"(d[37]), "+f"(d[38]), "+f"(d[39]), "+f"(d[40]), "+f"(d[41]), "+f"(d[42]), "+f"(d[43]), "+f"(d[44]), "+f"(d[45]), "+f"(d[46]), "+f"(d[47])
        : "r"(a[AOFF + 0][0]), "r"(a[AOFF + 0][1]), "r"(a[AOFF + 0][2]), "r"(a[AOFF + 0][3]), "r"(a[AOFF + 1][0]), "r"(a[AOFF + 1][1]), "r"(a[AOFF + 1][2]), "r"(a[AOFF + 1][3]), "l"(descB), "n"(BOFF >> 4));
}
};
template <> struct Rng<1, 10, 12> {
template <int BOFF, int AOFF, int NA>
static __device__ __forceinline__ void run(float (&d)[48], const uint32_t (&a)[NA][4], uint64_t descB) {
    asm volatile(
        "{\n"
        ".reg .pred p0, p1;\n"
        ".reg .b64 ta, ta0, tb, tb0;\n"
        "setp.ne.b32 p0, 0, 0;\n"
        "setp.eq.b32 p1, 0, 0;\n"
        "add.s64 tb0, %56, %57;\n"
        "add.s64 tb, tb0, 320;\n"
        "wgmma.mma_async.sync.aligned.m64n96k16.f32.bf16.bf16 {%0, %1, %2, %3, %4, %5, %6, %7, %8, %9, %10, %11, %12, %13, %14, %15, %16, %17, %18, %19, %20, %21, %22, %23, %24, %25, %26, %27, %28, %29, %30, %31, %32, %33, %34, %35, %36, %37, %38, %39, %40, %41, %42, %43, %44, %45, %46, %47}, {%48, %49, %50, %51}, tb, p1, 1, 1, 1;\n"
        "add.s64 tb, tb0, 352;\n"
        "wgmma.mma_async.sync.aligned.m64n96k16.f32.bf16.bf16 {%0, %1, %2, %3, %4, %5, %6, %7, %8, %9, %10, %11, %12, %13, %14, %15, %16, %17, %18, %19, %20, %21, %22, %23, %24, %25, %26, %27, %28, %29, %30, %31, %32, %33, %34, %35, %36, %37, %38, %39, %40, %41, %42, %43, %44, %45, %46, %47}, {%52, %53, %54, %55}, tb, p1, 1, 1, 1;\n"
        "}\n"
        : "+f"(d[0]), "+f"(d[1]), "+f"(d[2]), "+f"(d[3]), "+f"(d[4]), "+f"(d[5]), "+f"(d[6]), "+f"(d[7]), "+f"(d[8]), "+f"(d[9]), "+f"(d[10]), "+f"(d[11]), "+f"(d[12]), "+f"(d[13]), "+f"(d[14]), "+f"(d[15]), "+f"(d[16]), "+f"(d[17]), "+f"(d[18]), "+f"(d[19]), "+f"(d[20]), "+f"(d[21]), "+f"(d[22]), "+f"(d[23]), "+f"(d[24]), "+f"(d[25]), "+f"(d[26]), "+f"(d[27]), "+f"(d[28]), "+f"(d[29]), "+f"(d[30]), "+f"(d[31]), "+f"(d[32]), "+f"(d[33]), "+f"(d[34]), "+f"(d[35]), "+f"(d[36]), "+f"(d[37]), "+f"(d[38]), "+f"(d[39]), "+f"(d[40]), "+f"(d[41]), "+f"(d[42]), "+f"(d[43]), "+f"(d[44]), "+f"(d[45]), "+f"(d[46]), "+f"(d[47])
        : "r"(a[AOFF + 0][0]), "r"(a[AOFF + 0][1]), "r"(a[AOFF + 0][2]), "r"(a[AOFF + 0][3]), "r"(a[AOFF + 1][0]), "r"(a[AOFF + 1][1]), "r"(a[AOFF + 1][2]), "r"(a[AOFF + 1][3]), "l"(descB), "n"(BOFF >> 4));
}
};
template <int V, int BOFF, int S0, int S1>
__device__ __forceinline__ void mma_rng(float (&d)[48], const uint32_t (&a)[12][4], uint64_t descB) {
    if constexpr (S0 < S1) Rng<V, S0, S1>::template run<BOFF, S0, 12>(d, a, descB);
}

template <int AOFF, int BOFF>
__device__ __forceinline__ void mma_qk0(float (&d)[28], uint64_t descA, uint64_t descB) {
    asm volatile(
        "{\n"
        ".reg .pred p0, p1;\n"
        ".reg .b64 ta, ta0, tb, tb0;\n"
        "setp.ne.b32 p0, 0, 0;\n"
        "setp.eq.b32 p1, 0, 0;\n"
        "add.s64 tb0, %30, %31;\n"
        "add.s64 ta0, %28, %29;\n"
        "add.s64 tb, tb0, 4;\n"
        "add.s64 ta, ta0, 0;\n"
        "wgmma.mma_async.sync.aligned.m64n56k16.f32.bf16.bf16 {%0, %1, %2, %3, %4, %5, %6, %7, %8, %9, %10, %11, %12, %13, %14, %15, %16, %17, %18, %19, %20, %21, %22, %23, %24, %25, %26, %27}, ta, tb, p0, 1, 1, 0, 0;\n"
        "add.s64 tb, tb0, 1572;\n"
        "add.s64 ta, ta0, 1568;\n"
        "wgmma.mma_async.sync.aligned.m64n56k16.f32.bf16.bf16 {%0, %1, %2, %3, %4, %5, %6, %7, %8, %9, %10, %11, %12, %13, %14, %15, %16, %17, %18, %19, %20, %21, %22, %23, %24, %25, %26, %27}, ta, tb, p1, 1, 1, 0, 0;\n"
        "add.s64 tb, tb0, 3140;\n"
        "add.s64 ta, ta0, 3136;\n"
        "wgmma.mma_async.sync.aligned.m64n56k16.f32.bf16.bf16 {%0, %1, %2, %3, %4, %5, %6, %7, %8, %9, %10, %11, %12, %13, %14, %15, %16, %17, %18, %19, %20, %21, %22, %23, %24, %25, %26, %27}, ta, tb, p1, 1, 1, 0, 0;\n"
        "}\n"
        : "=f"(d[0]), "=f"(d[1]), "=f"(d[2]), "=f"(d[3]), "=f"(d[4]), "=f"(d[5]), "=f"(d[6]), "=f"(d[7]), "=f"(d[8]), "=f"(d[9]), "=f"(d[10]), "=f"(d[11]), "=f"(d[12]), "=f"(d[13]), "=f"(d[14]), "=f"(d[15]), "=f"(d[16]), "=f"(d[17]), "=f"(d[18]), "=f"(d[19]), "=f"(d[20]), "=f"(d[21]), "=f"(d[22]), "=f"(d[23]), "=f"(d[24]), "=f"(d[25]), "=f"(d[26]), "=f"(d[27])
        : "l"(descA), "n"(AOFF >> 4), "l"(descB), "n"(BOFF >> 4));
}

template <int AOFF, int BOFF>
__device__ __forceinline__ void mma_qk1(float (&d)[28], uint64_t descA, uint64_t descB) {
    asm volatile(
        "{\n"
        ".reg .pred p0, p1;\n"
        ".reg .b64 ta, ta0, tb, tb0;\n"
        "setp.ne.b32 p0, 0, 0;\n"
        "setp.eq.b32 p1, 0, 0;\n"
        "add.s64 tb0, %30, %31;\n"
        "add.s64 ta0, %28, %29;\n"
        "add.s64 tb, tb0, 6;\n"
        "add.s64 ta, ta0, 2;\n"
        "wgmma.mma_async.sync.aligned.m64n56k16.f32.bf16.bf16 {%0, %1, %2, %3, %4, %5, %6, %7, %8, %9, %10, %11, %12, %13, %14, %15, %16, %17, %18, %19, %20, %21, %22, %23, %24, %25, %26, %27}, ta, tb, p0, 1, 1, 0, 0;\n"
        "add.s64 tb, tb0, 1574;\n"
        "add.s64 ta, ta0, 1570;\n"
        "wgmma.mma_async.sync.aligned.m64n56k16.f32.bf16.bf16 {%0, %1, %2, %3, %4, %5, %6, %7, %8, %9, %10, %11, %12, %13, %14, %15, %16, %17, %18, %19, %20, %21, %22, %23, %24, %25, %26, %27}, ta, tb, p1, 1, 1, 0, 0;\n"
        "add.s64 tb, tb0, 3142;\n"
        "add.s64 ta, ta0, 3138;\n"
        "wgmma.mma_async.sync.aligned.m64n56k16.f32.bf16.bf16 {%0, %1, %2, %3, %4, %5, %6, %7, %8, %9, %10, %11, %12, %13, %14, %15, %16, %17, %18, %19, %20, %21, %22, %23, %24, %25, %26, %27}, ta, tb, p1, 1, 1, 0, 0;\n"
        "}\n"
        : "=f"(d[0]), "=f"(d[1]), "=f"(d[2]), "=f"(d[3]), "=f"(d[4]), "=f"(d[5]), "=f"(d[6]), "=f"(d[7]), "=f"(d[8]), "=f"(d[9]), "=f"(d[10]), "=f"(d[11]), "=f"(d[12]), "=f"(d[13]), "=f"(d[14]), "=f"(d[15]), "=f"(d[16]), "=f"(d[17]), "=f"(d[18]), "=f"(d[19]), "=f"(d[20]), "=f"(d[21]), "=f"(d[22]), "=f"(d[23]), "=f"(d[24]), "=f"(d[25]), "=f"(d[26]), "=f"(d[27])
        : "l"(descA), "n"(AOFF >> 4), "l"(descB), "n"(BOFF >> 4));
}

template <int BOFF, int AOFF, int NA>
__device__ __forceinline__ void mma_pv(float (&d)[28], const uint32_t (&a)[NA][4], uint64_t descB) {
    asm volatile(
        "{\n"
        ".reg .pred p0, p1;\n"
        ".reg .b64 ta, ta0, tb, tb0;\n"
        "setp.ne.b32 p0, 0, 0;\n"
        "setp.eq.b32 p1, 0, 0;\n"
        "add.s64 tb0, %44, %45;\n"
        "add.s64 tb, tb0, 0;\n"
        "wgmma.mma_async.sync.aligned.m64n56k16.f32.bf16.bf16 {%0, %1, %2, %3, %4, %5, %6, %7, %8, %9, %10, %11, %12, %13, %14, %15, %16, %17, %18, %19, %20, %21, %22, %23, %24, %25, %26, %27}, {%28, %29, %30, %31}, tb, p0, 1, 1, 1;\n"
        "add.s64 tb, tb0, 16;\n"
        "wgmma.mma_async.sync.aligned.m64n56k16.f32.bf16.bf16 {%0, %1, %2, %3, %4, %5, %6, %7, %8, %9, %10, %11, %12, %13, %14, %15, %16, %17, %18, %19, %20, %21, %22, %23, %24, %25, %26, %27}, {%32, %33, %34, %35}, tb, p1, 1, 1, 1;\n"
        "add.s64 tb, tb0, 32;\n"
        "wgmma.mma_async.sync.aligned.m64n56k16.f32.bf16.bf16 {%0, %1, %2, %3, %4, %5, %6, %7, %8, %9, %10, %11, %12, %13, %14, %15, %16, %17, %18, %19, %20, %21, %22, %23, %24, %25, %26, %27}, {%36, %37, %38, %39}, tb, p1, 1, 1, 1;\n"
        "add.s64 tb, tb0, 48;\n"
        "wgmma.mma_async.sync.aligned.m64n56k16.f32.bf16.bf16 {%0, %1, %2, %3, %4, %5, %6, %7, %8, %9, %10, %11, %12, %13, %14, %15, %16, %17, %18, %19, %20, %21, %22, %23, %24, %25, %26, %27}, {%40, %41, %42, %43}, tb, p1, 1, 1, 1;\n"
        "}\n"
        : "=f"(d[0]), "=f"(d[1]), "=f"(d[2]), "=f"(d[3]), "=f"(d[4]), "=f"(d[5]), "=f"(d[6]), "=f"(d[7]), "=f"(d[8]), "=f"(d[9]), "=f"(d[10]), "=f"(d[11]), "=f"(d[12]), "=f"(d[13]), "=f"(d[14]), "=f"(d[15]), "=f"(d[16]), "=f"(d[17]), "=f"(d[18]), "=f"(d[19]), "=f"(d[20]), "=f"(d[21]), "=f"(d[22]), "=f"(d[23]), "=f"(d[24]), "=f"(d[25]), "=f"(d[26]), "=f"(d[27])
        : "r"(a[AOFF + 0][0]), "r"(a[AOFF + 0][1]), "r"(a[AOFF + 0][2]), "r"(a[AOFF + 0][3]), "r"(a[AOFF + 1][0]), "r"(a[AOFF + 1][1]), "r"(a[AOFF + 1][2]), "r"(a[AOFF + 1][3]), "r"(a[AOFF + 2][0]), "r"(a[AOFF + 2][1]), "r"(a[AOFF + 2][2]), "r"(a[AOFF + 2][3]), "r"(a[AOFF + 3][0]), "r"(a[AOFF + 3][1]), "r"(a[AOFF + 3][2]), "r"(a[AOFF + 3][3]), "l"(descB), "n"(BOFF >> 4));
}

template <int AOFF, int BOFF>
__device__ __forceinline__ void mma_proj(float (&d)[96], uint64_t descA, uint64_t descB) {
    asm volatile(
        "{\n"
        ".reg .pred p0, p1;\n"
        ".reg .b64 ta, ta0, tb, tb0;\n"
        "setp.ne.b32 p0, 0, 0;\n"
        "setp.eq.b32 p1, 0, 0;\n"
        "add.s64 tb0, %98, %99;\n"
        "add.s64 ta0, %96, %97;\n"
        "add.s64 tb, tb0, 0;\n"
        "add.s64 ta, ta0, 0;\n"
        "wgmma.mma_async.sync.aligned.m64n192k16.f32.bf16.bf16 {%0, %1, %2, %3, %4, %5, %6, %7, %8, %9, %10, %11, %12, %13, %14, %15, %16, %17, %18, %19, %20, %21, %22, %23, %24, %25, %26, %27, %28, %29, %30, %31, %32, %33, %34, %35, %36, %37, %38, %39, %40, %41, %42, %43, %44, %45, %46, %47, %48, %49, %50, %51, %52, %53, %54, %55, %56, %57, %58, %59, %60, %61, %62, %63, %64, %65, %66, %67, %68, %69, %70, %71, %72, %73, %74, %75, %76, %77, %78, %79, %80, %81, %82, %83, %84, %85, %86, %87, %88, %89, %90, %91, %92, %93, %94, %95}, ta, tb, p0, 1, 1, 0, 1;\n"
        "add.s64 tb, tb0, 64;\n"
        "add.s64 ta, ta0, 2;\n"
        "wgmma.mma_async.sync.aligned.m64n192k16.f32.bf16.bf16 {%0, %1, %2, %3, %4, %5, %6, %7, %8, %9, %10, %11, %12, %13, %14, %15, %16, %17, %18, %19, %20, %21, %22, %23, %24, %25, %26, %27, %28, %29, %30, %31, %32, %33, %34, %35, %36, %37, %38, %39, %40, %41, %42, %43, %44, %45, %46, %47, %48, %49, %50, %51, %52, %53, %54, %55, %56, %57, %58, %59, %60, %61, %62, %63, %64, %65, %66, %67, %68, %69, %70, %71, %72, %73, %74, %75, %76, %77, %78, %79, %80, %81, %82, %83, %84, %85, %86, %87, %88, %89, %90, %91, %92, %93, %94, %95}, ta, tb, p1, 1, 1, 0, 1;\n"
        "add.s64 tb, tb0, 128;\n"
        "add.s64 ta, ta0, 4;\n"
        "wgmma.mma_async.sync.aligned.m64n192k16.f32.bf16.bf16 {%0, %1, %2, %3, %4, %5, %6, %7, %8, %9, %10, %11, %12, %13, %14, %15, %16, %17, %18, %19, %20, %21, %22, %23, %24, %25, %26, %27, %28, %29, %30, %31, %32, %33, %34, %35, %36, %37, %38, %39, %40, %41, %42, %43, %44, %45, %46, %47, %48, %49, %50, %51, %52, %53, %54, %55, %56, %57, %58, %59, %60, %61, %62, %63, %64, %65, %66, %67, %68, %69, %70, %71, %72, %73, %74, %75, %76, %77, %78, %79, %80, %81, %82, %83, %84, %85, %86, %87, %88, %89, %90, %91, %92, %93, %94, %95}, ta, tb, p1, 1, 1, 0, 1;\n"
        "add.s64 tb, tb0, 192;\n"
        "add.s64 ta, ta0, 6;\n"
        "wgmma.mma_async.sync.aligned.m64n192k16.f32.bf16.bf16 {%0, %1, %2, %3, %4, %5, %6, %7, %8, %9, %10, %11, %12, %13, %14, %15, %16, %17, %18, %19, %20, %21, %22, %23, %24, %25, %26, %27, %28, %29, %30, %31, %32, %33, %34, %35, %36, %37, %38, %39, %40, %41, %42, %43, %44, %45, %46, %47, %48, %49, %50, %51, %52, %53, %54, %55, %56, %57, %58, %59, %60, %61, %62, %63, %64, %65, %66, %67, %68, %69, %70, %71, %72, %73, %74, %75, %76, %77, %78, %79, %80, %81, %82, %83, %84, %85, %86, %87, %88, %89, %90, %91, %92, %93, %94, %95}, ta, tb, p1, 1, 1, 0, 1;\n"
        "add.s64 tb, tb0, 256;\n"
        "add.s64 ta, ta0, 512;\n"
        "wgmma.mma_async.sync.aligned.m64n192k16.f32.bf16.bf16 {%0, %1, %2, %3, %4, %5, %6, %7, %8, %9, %10, %11, %12, %13, %14, %15, %16, %17, %18, %19, %20, %21, %22, %23, %24, %25, %26, %27, %28, %29, %30, %31, %32, %33, %34, %35, %36, %37, %38, %39, %40, %41, %42, %43, %44, %45, %46, %47, %48, %49, %50, %51, %52, %53, %54, %55, %56, %57, %58, %59, %60, %61, %62, %63, %64, %65, %66, %67, %68, %69, %70, %71, %72, %73, %74, %75, %76, %77, %78, %79, %80, %81, %82, %83, %84, %85, %86, %87, %88, %89, %90, %91, %92, %93, %94, %95}, ta, tb, p1, 1, 1, 0, 1;\n"
        "add.s64 tb, tb0, 320;\n"
        "add.s64 ta, ta0, 514;\n"
        "wgmma.mma_async.sync.aligned.m64n192k16.f32.bf16.bf16 {%0, %1, %2, %3, %4, %5, %6, %7, %8, %9, %10, %11, %12, %13, %14, %15, %16, %17, %18, %19, %20, %21, %22, %23, %24, %25, %26, %27, %28, %29, %30, %31, %32, %33, %34, %35, %36, %37, %38, %39, %40, %41, %42, %43, %44, %45, %46, %47, %48, %49, %50, %51, %52, %53, %54, %55, %56, %57, %58, %59, %60, %61, %62, %63, %64, %65, %66, %67, %68, %69, %70, %71, %72, %73, %74, %75, %76, %77, %78, %79, %80, %81, %82, %83, %84, %85, %86, %87, %88, %89, %90, %91, %92, %93, %94, %95}, ta, tb, p1, 1, 1, 0, 1;\n"
        "add.s64 tb, tb0, 384;\n"
        "add.s64 ta, ta0, 516;\n"
        "wgmma.mma_async.sync.aligned.m64n192k16.f32.bf16.bf16 {%0, %1, %2, %3, %4, %5, %6, %7, %8, %9, %10, %11, %12, %13, %14, %15, %16, %17, %18, %19, %20, %21, %22, %23, %24, %25, %26, %27, %28, %29, %30, %31, %32, %33, %34, %35, %36, %37, %38, %39, %40, %41, %42, %43, %44, %45, %46, %47, %48, %49, %50, %51, %52, %53, %54, %55, %56, %57, %58, %59, %60, %61, %62, %63, %64, %65, %66, %67, %68, %69, %70, %71, %72, %73, %74, %75, %76, %77, %78, %79, %80, %81, %82, %83, %84, %85, %86, %87, %88, %89, %90, %91, %92, %93, %94, %95}, ta, tb, p1, 1, 1, 0, 1;\n"
        "add.s64 tb, tb0, 448;\n"
        "add.s64 ta, ta0, 518;\n"
        "wgmma.mma_async.sync.aligned.m64n192k16.f32.bf16.bf16 {%0, %1, %2, %3, %4, %5, %6, %7, %8, %9, %10, %11, %12, %13, %14, %15, %16, %17, %18, %19, %20, %21, %22, %23, %24, %25, %26, %27, %28, %29, %30, %31, %32, %33, %34, %35, %36, %37, %38, %39, %40, %41, %42, %43, %44, %45, %46, %47, %48, %49, %50, %51, %52, %53, %54, %55, %56, %57, %58, %59, %60, %61, %62, %63, %64, %65, %66, %67, %68, %69, %70, %71, %72, %73, %74, %75, %76, %77, %78, %79, %80, %81, %82, %83, %84, %85, %86, %87, %88, %89, %90, %91, %92, %93, %94, %95}, ta, tb, p1, 1, 1, 0, 1;\n"
        "add.s64 tb, tb0, 512;\n"
        "add.s64 ta, ta0, 1024;\n"
        "wgmma.mma_async.sync.aligned.m64n192k16.f32.bf16.bf16 {%0, %1, %2, %3, %4, %5, %6, %7, %8, %9, %10, %11, %12, %13, %14, %15, %16, %17, %18, %19, %20, %21, %22, %23, %24, %25, %26, %27, %28, %29, %30, %31, %32, %33, %34, %35, %36, %37, %38, %39, %40, %41, %42, %43, %44, %45, %46, %47, %48, %49, %50, %51, %52, %53, %54, %55, %56, %57, %58, %59, %60, %61, %62, %63, %64, %65, %66, %67, %68, %69, %70, %71, %72, %73, %74, %75, %76, %77, %78, %79, %80, %81, %82, %83, %84, %85, %86, %87, %88, %89, %90, %91, %92, %93, %94, %95}, ta, tb, p1, 1, 1, 0, 1;\n"
        "add.s64 tb, tb0, 576;\n"
        "add.s64 ta, ta0, 1026;\n"
        "wgmma.mma_async.sync.aligned.m64n192k16.f32.bf16.bf16 {%0, %1, %2, %3, %4, %5, %6, %7, %8, %9, %10, %11, %12, %13, %14, %15, %16, %17, %18, %19, %20, %21, %22, %23, %24, %25, %26, %27, %28, %29, %30, %31, %32, %33, %34, %35, %36, %37, %38, %39, %40, %41, %42, %43, %44, %45, %46, %47, %48, %49, %50, %51, %52, %53, %54, %55, %56, %57, %58, %59, %60, %61, %62, %63, %64, %65, %66, %67, %68, %69, %70, %71, %72, %73, %74, %75, %76, %77, %78, %79, %80, %81, %82, %83, %84, %85, %86, %87, %88, %89, %90, %91, %92, %93, %94, %95}, ta, tb, p1, 1, 1, 0, 1;\n"
        "add.s64 tb, tb0, 640;\n"
        "add.s64 ta, ta0, 1028;\n"
        "wgmma.mma_async.sync.aligned.m64n192k16.f32.bf16.bf16 {%0, %1, %2, %3, %4, %5, %6, %7, %8, %9, %10, %11, %12, %13, %14, %15, %16, %17, %18, %19, %20, %21, %22, %23, %24, %25, %26, %27, %28, %29, %30, %31, %32, %33, %34, %35, %36, %37, %38, %39, %40, %41, %42, %43, %44, %45, %46, %47, %48, %49, %50, %51, %52, %53, %54, %55, %56, %57, %58, %59, %60, %61, %62, %63, %64, %65, %66, %67, %68, %69, %70, %71, %72, %73, %74, %75, %76, %77, %78, %79, %80, %81, %82, %83, %84, %85, %86, %87, %88, %89, %90, %91, %92, %93, %94, %95}, ta, tb, p1, 1, 1, 0, 1;\n"
        "add.s64 tb, tb0, 704;\n"
        "add.s64 ta, ta0, 1030;\n"
        "wgmma.mma_async.sync.aligned.m64n192k16.f32.bf16.bf16 {%0, %1, %2, %3, %4, %5, %6, %7, %8, %9, %10, %11, %12, %13, %14, %15, %16, %17, %18, %19, %20, %21, %22, %23, %24, %25, %26, %27, %28, %29, %30, %31, %32, %33, %34, %35, %36, %37, %38, %39, %40, %41, %42, %43, %44, %45, %46, %47, %48, %49, %50, %51, %52, %53, %54, %55, %56, %57, %58, %59, %60, %61, %62, %63, %64, %65, %66, %67, %68, %69, %70, %71, %72, %73, %74, %75, %76, %77, %78, %79, %80, %81, %82, %83, %84, %85, %86, %87, %88, %89, %90, %91, %92, %93, %94, %95}, ta, tb, p1, 1, 1, 0, 1;\n"
        "}\n"
        : "+f"(d[0]), "+f"(d[1]), "+f"(d[2]), "+f"(d[3]), "+f"(d[4]), "+f"(d[5]), "+f"(d[6]), "+f"(d[7]), "+f"(d[8]), "+f"(d[9]), "+f"(d[10]), "+f"(d[11]), "+f"(d[12]), "+f"(d[13]), "+f"(d[14]), "+f"(d[15]), "+f"(d[16]), "+f"(d[17]), "+f"(d[18]), "+f"(d[19]), "+f"(d[20]), "+f"(d[21]), "+f"(d[22]), "+f"(d[23]), "+f"(d[24]), "+f"(d[25]), "+f"(d[26]), "+f"(d[27]), "+f"(d[28]), "+f"(d[29]), "+f"(d[30]), "+f"(d[31]), "+f"(d[32]), "+f"(d[33]), "+f"(d[34]), "+f"(d[35]), "+f"(d[36]), "+f"(d[37]), "+f"(d[38]), "+f"(d[39]), "+f"(d[40]), "+f"(d[41]), "+f"(d[42]), "+f"(d[43]), "+f"(d[44]), "+f"(d[45]), "+f"(d[46]), "+f"(d[47]), "+f"(d[48]), "+f"(d[49]), "+f"(d[50]), "+f"(d[51]), "+f"(d[52]), "+f"(d[53]), "+f"(d[54]), "+f"(d[55]), "+f"(d[56]), "+f"(d[57]), "+f"(d[58]), "+f"(d[59]), "+f"(d[60]), "+f"(d[61]), "+f"(d[62]), "+f"(d[63]), "+f"(d[64]), "+f"(d[65]), "+f"(d[66]), "+f"(d[67]), "+f"(d[68]), "+f"(d[69]), "+f"(d[70]), "+f"(d[71]), "+f"(d[72]), "+f"(d[73]), "+f"(d[74]), "+f"(d[75]), "+f"(d[76]), "+f"(d[77]), "+f"(d[78]), "+f"(d[79]), "+f"(d[80]), "+f"(d[81]), "+f"(d[82]), "+f"(d[83]), "+f"(d[84]), "+f"(d[85]), "+f"(d[86]), "+f"(d[87]), "+f"(d[88]), "+f"(d[89]), "+f"(d[90]), "+f"(d[91]), "+f"(d[92]), "+f"(d[93]), "+f"(d[94]), "+f"(d[95])
        : "l"(descA), "n"(AOFF >> 4), "l"(descB), "n"(BOFF >> 4));
}

template <int AOFF, int BOFF>
__device__ __forceinline__ void mma_proj64(float (&d)[32], uint64_t descA, uint64_t descB) {
    asm volatile(
        "{\n"
        ".reg .pred p0, p1;\n"
        ".reg .b64 ta, ta0, tb, tb0;\n"
        "setp.ne.b32 p0, 0, 0;\n"
        "setp.eq.b32 p1, 0, 0;\n"
        "add.s64 tb0, %34, %35;\n"
        "add.s64 ta0, %32, %33;\n"
        "add.s64 tb, tb0, 0;\n"
        "add.s64 ta, ta0, 0;\n"
        "wgmma.mma_async.sync.aligned.m64n64k16.f32.bf16.bf16 {%0, %1, %2, %3, %4, %5, %6, %7, %8, %9, %10, %11, %12, %13, %14, %15, %16, %17, %18, %19, %20, %21, %22, %23, %24, %25, %26, %27, %28, %29, %30, %31}, ta, tb, p0, 1, 1, 0, 1;\n"
        "add.s64 tb, tb0, 64;\n"
        "add.s64 ta, ta0, 2;\n"
        "wgmma.mma_async.sync.aligned.m64n64k16.f32.bf16.bf16 {%0, %1, %2, %3, %4, %5, %6, %7, %8, %9, %10, %11, %12, %13, %14, %15, %16, %17, %18, %19, %20, %21, %22, %23, %24, %25, %26, %27, %28, %29, %30, %31}, ta, tb, p1, 1, 1, 0, 1;\n"
        "add.s64 tb, tb0, 128;\n"
        "add.s64 ta, ta0, 4;\n"
        "wgmma.mma_async.sync.aligned.m64n64k16.f32.bf16.bf16 {%0, %1, %2, %3, %4, %5, %6, %7, %8, %9, %10, %11, %12, %13, %14, %15, %16, %17, %18, %19, %20, %21, %22, %23, %24, %25, %26, %27, %28, %29, %30, %31}, ta, tb, p1, 1, 1, 0, 1;\n"
        "add.s64 tb, tb0, 192;\n"
        "add.s64 ta, ta0, 6;\n"
        "wgmma.mma_async.sync.aligned.m64n64k16.f32.bf16.bf16 {%0, %1, %2, %3, %4, %5, %6, %7, %8, %9, %10, %11, %12, %13, %14, %15, %16, %17, %18, %19, %20, %21, %22, %23, %24, %25, %26, %27, %28, %29, %30, %31}, ta, tb, p1, 1, 1, 0, 1;\n"
        "add.s64 tb, tb0, 256;\n"
        "add.s64 ta, ta0, 512;\n"
        "wgmma.mma_async.sync.aligned.m64n64k16.f32.bf16.bf16 {%0, %1, %2, %3, %4, %5, %6, %7, %8, %9, %10, %11, %12, %13, %14, %15, %16, %17, %18, %19, %20, %21, %22, %23, %24, %25, %26, %27, %28, %29, %30, %31}, ta, tb, p1, 1, 1, 0, 1;\n"
        "add.s64 tb, tb0, 320;\n"
        "add.s64 ta, ta0, 514;\n"
        "wgmma.mma_async.sync.aligned.m64n64k16.f32.bf16.bf16 {%0, %1, %2, %3, %4, %5, %6, %7, %8, %9, %10, %11, %12, %13, %14, %15, %16, %17, %18, %19, %20, %21, %22, %23, %24, %25, %26, %27, %28, %29, %30, %31}, ta, tb, p1, 1, 1, 0, 1;\n"
        "add.s64 tb, tb0, 384;\n"
        "add.s64 ta, ta0, 516;\n"
        "wgmma.mma_async.sync.aligned.m64n64k16.f32.bf16.bf16 {%0, %1, %2, %3, %4, %5, %6, %7, %8, %9, %10, %11, %12, %13, %14, %15, %16, %17, %18, %19, %20, %21, %22, %23, %24, %25, %26, %27, %28, %29, %30, %31}, ta, tb, p1, 1, 1, 0, 1;\n"
        "add.s64 tb, tb0, 448;\n"
        "add.s64 ta, ta0, 518;\n"
        "wgmma.mma_async.sync.aligned.m64n64k16.f32.bf16.bf16 {%0, %1, %2, %3, %4, %5, %6, %7, %8, %9, %10, %11, %12, %13, %14, %15, %16, %17, %18, %19, %20, %21, %22, %23, %24, %25, %26, %27, %28, %29, %30, %31}, ta, tb, p1, 1, 1, 0, 1;\n"
        "add.s64 tb, tb0, 512;\n"
        "add.s64 ta, ta0, 1024;\n"
        "wgmma.mma_async.sync.aligned.m64n64k16.f32.bf16.bf16 {%0, %1, %2, %3, %4, %5, %6, %7, %8, %9, %10, %11, %12, %13, %14, %15, %16, %17, %18, %19, %20, %21, %22, %23, %24, %25, %26, %27, %28, %29, %30, %31}, ta, tb, p1, 1, 1, 0, 1;\n"
        "add.s64 tb, tb0, 576;\n"
        "add.s64 ta, ta0, 1026;\n"
        "wgmma.mma_async.sync.aligned.m64n64k16.f32.bf16.bf16 {%0, %1, %2, %3, %4, %5, %6, %7, %8, %9, %10, %11, %12, %13, %14, %15, %16, %17, %18, %19, %20, %21, %22, %23, %24, %25, %26, %27, %28, %29, %30, %31}, ta, tb, p1, 1, 1, 0, 1;\n"
        "add.s64 tb, tb0, 640;\n"
        "add.s64 ta, ta0, 1028;\n"
        "wgmma.mma_async.sync.aligned.m64n64k16.f32.bf16.bf16 {%0, %1, %2, %3, %4, %5, %6, %7, %8, %9, %10, %11, %12, %13, %14, %15, %16, %17, %18, %19, %20, %21, %22, %23, %24, %25, %26, %27, %28, %29, %30, %31}, ta, tb, p1, 1, 1, 0, 1;\n"
        "add.s64 tb, tb0, 704;\n"
        "add.s64 ta, ta0, 1030;\n"
        "wgmma.mma_async.sync.aligned.m64n64k16.f32.bf16.bf16 {%0, %1, %2, %3, %4, %5, %6, %7, %8, %9, %10, %11, %12, %13, %14, %15, %16, %17, %18, %19, %20, %21, %22, %23, %24, %25, %26, %27, %28, %29, %30, %31}, ta, tb, p1, 1, 1, 0, 1;\n"
        "}\n"
        : "=f"(d[0]), "=f"(d[1]), "=f"(d[2]), "=f"(d[3]), "=f"(d[4]), "=f"(d[5]), "=f"(d[6]), "=f"(d[7]), "=f"(d[8]), "=f"(d[9]), "=f"(d[10]), "=f"(d[11]), "=f"(d[12]), "=f"(d[13]), "=f"(d[14]), "=f"(d[15]), "=f"(d[16]), "=f"(d[17]), "=f"(d[18]), "=f"(d[19]), "=f"(d[20]), "=f"(d[21]), "=f"(d[22]), "=f"(d[23]), "=f"(d[24]), "=f"(d[25]), "=f"(d[26]), "=f"(d[27]), "=f"(d[28]), "=f"(d[29]), "=f"(d[30]), "=f"(d[31])
        : "l"(descA), "n"(AOFF >> 4), "l"(descB), "n"(BOFF >> 4));
}

struct Params {
    const __nv_bfloat16* x;
    const __nv_bfloat16* wqkv;
    const __nv_bfloat16* wo;
    const __nv_bfloat16* logit_scale;
    const __nv_bfloat16* cpb_w1;
    const __nv_bfloat16* cpb_w2;
    const __nv_bfloat16* rel_coords;
    const int*           rel_idx;
    const __nv_bfloat16* mask;
    __nv_bfloat16*       out;
    unsigned long long   z1;
};

struct Q {
    static constexpr int npair = NPAIR, nh = NH, hw = NH ? HW : 0;
    static constexpr uint32_t need = ROW_DONE;
    static constexpr int nq = (NWINDOWS - hw) / NPAIR, nr = (NWINDOWS - hw) % NPAIR;
    static constexpr int nr2 = 2 * nr, nt0 = (nq * TOK + 63) / 64, nt1 = ((nq + 1) * TOK + 63) / 64;
    static constexpr int hq = NH ? HW / (NH ? NH : 1) : 0, hr = NPAIR + (NH ? HW % (NH ? NH : 1) : 0), hr2 = 2 * hr;
    static constexpr int ht0 = (hq * TOK + 63) / 64, ht1 = ((hq + 1) * TOK + 63) / 64;
    static constexpr int t1 = TILES - NTAIL;
};
#define PQ(f) Q::f
#define GRID 132

struct Maps {
    CUtensorMap x77, x47, x37, x44, x43, x34, x33;
    CUtensorMap w64, w32, w;
    CUtensorMap s47, s37, s43, s33;
    CUtensorMap o, ob;
};

__device__ __forceinline__ uint32_t row_token(uint32_t r) {
    return r < 28 ? r + 3 * (r >> 2) : r - 24 + 4 * (((r - 28) * 11) >> 5);
}
__device__ __forceinline__ int unrot(int r) { return r ? r - 1 : NWS - 1; }
__device__ __forceinline__ void finish(uint32_t total) {
    __threadfence();
    if (atomicAdd(&g_done, 1u) == total - 1) {
        for (int i = 0; i <= NWS; i++) g_cnt[i] = 0;
        g_done = 0;
    }
}

__global__ void __launch_bounds__(NTHREADS, 1)
swin_window_attn_kernel(const Params P, const __grid_constant__ Maps M) {
    const CUtensorMap &xmap = M.x77, &omap = M.o, &omapb = M.ob, &wmap = M.w;
    extern __shared__ __align__(1024) uint8_t smem[];
    constexpr uint32_t sbase = 1024;
    if (smem_u32(smem) != sbase) return;
    const int tid = threadIdx.x;
    const int wg = __shfl_sync(0xffffffffu, tid >> 7, 0);
    const int warp = __shfl_sync(0xffffffffu, (tid >> 5) & 3, 0);
    const int lane = tid & 31;
    const int g = lane >> 2, c = lane & 3;

    TR(26, wg);
    TP(wg);
    if (tid == 0) TC(0);
    const bool attn = (int)blockIdx.x < 2 * (PQ(npair) + PQ(nh));
    const int pair = blockIdx.x >> 1, half = blockIdx.x & 1;
    const int nwin = pair < PQ(npair) ? PQ(nq) + (pair < PQ(nr) ? 1 : 0) : PQ(hq) + (pair < PQ(hr) ? 1 : 0);
    const int w0 = pair < PQ(npair) ? PQ(hw) + pair : pair - PQ(npair), wstep = pair < PQ(npair) ? PQ(npair) : PQ(nh);
    const int wr0 = w0 >= NWS, wq0 = w0 - wr0 * NWS;
    const int ntiles = (nwin * TOK + 63) >> 6;
    const uint32_t bars = sbase + SM_BAR;
    auto load_x = [&](uint32_t dst, uint32_t bar, uint32_t bar2, int wh, int ww) {
        const int x0 = 7 * ww + 3, y0 = 7 * wh + 3, x1 = ww == NWS - 1 ? 0 : x0 + 4;
        if (wh < NWS - 1) {
#pragma unroll
            for (int ch = 0; ch < 3; ch++) tma_3d_x(dst + ch * QK_CHUNK, &M.x47, bar, ch * 64, x0, y0);
#pragma unroll
            for (int ch = 0; ch < 3; ch++) tma_3d_x(dst + ch * QK_CHUNK + 28 * 128, &M.x37, bar2, ch * 64, x1, y0);
        } else {
#pragma unroll
            for (int ch = 0; ch < 3; ch++) {
                tma_3d_x(dst + ch * QK_CHUNK, &M.x44, bar, ch * 64, x0, y0);
                tma_3d_x(dst + ch * QK_CHUNK + 16 * 128, &M.x43, bar, ch * 64, x0, 0);
            }
#pragma unroll
            for (int ch = 0; ch < 3; ch++) {
                tma_3d_x(dst + ch * QK_CHUNK + 28 * 128, &M.x34, bar2, ch * 64, x1, y0);
                tma_3d_x(dst + ch * QK_CHUNK + 40 * 128, &M.x33, bar2, ch * 64, x1, 0);
            }
        }
    };
    if (EPF && (wg == 1 || wg == 2)) {
        const int i = tid - 128, q = w0 + half * wstep, r = q >= NWS;
        const int px = (i * 171) >> 9, py = (px * 37) >> 8;
        int y = 7 * unrot(r) + 3 + py, x = 7 * unrot(q - r * NWS) + 3 + px - 7 * py;
        if (y >= IMG) y -= IMG;
        if (x >= IMG) x -= IMG;
        const char* p = reinterpret_cast<const char*>(P.x) + (size_t)(y * IMG + x) * 384 + (i - 3 * px) * 128;
        if (EPW && i >= 147) p = reinterpret_cast<const char*>(P.wqkv) + min((int)blockIdx.x * 14 + i - 147, 1727) * 128;
        if (i < 147 ? attn : EPW && i < 161) {
            if (EPF == 1) asm volatile("prefetch.global.L2 [%0];\n" :: "l"(p) : "memory");
            if (EPF == 2) { uint32_t d; asm volatile("ld.global.nc.L2::128B.b32 %0, [%1];\n" : "=r"(d) : "l"(p) : "memory"); }
            if (EPF == 3) for (int j = 0; j < 4; j++) asm volatile("prefetch.global.L2 [%0];\n" :: "l"(p + 32 * j) : "memory");
        }
    }
    uint32_t ls = 0;
    if (wg == 0) {
        TP(28);
        if (attn && warp < (WSEQ ? 1 : 3) && elect_one()) {
#pragma unroll
            for (int i = 0; i < (WSEQ ? 3 : 1); i++) mbar_init(bars + B_WRAW + 16 - 8 * (warp + i), 1);
            fence_async_smem();
            if (HDEL && pair >= PQ(npair)) {
                const uint32_t c0 = clock();
                while (clock() - c0 < HDEL) __nanosleep(100);
            }
            TP(29);
#pragma unroll 1
            for (int i = warp; i < warp + (WSEQ ? 3 : 1); i++) {
                const uint32_t bar = bars + B_WRAW + 16 - 8 * i, dst = sbase + i * 24576;
                mbar_arrive_expect_tx(bar, 24576);
                tma_3d(dst, &M.w64, bar, half * 128, 64 * i, 0);
                tma_3d(dst + 16384, &M.w32, bar, 64 + half * 32, 64 * i, 0);
            }
            TP(30);
        }
        __syncwarp();
        if (WFIRST && warp == 0) asm volatile("bar.arrive 3, 96;\n" ::: "memory");
        if (PPAR && warp == 0) nb_arrive<416>(11);
        if (attn) asm volatile("ld.global.nc.u16 %0, [%1];\n" : "=r"(ls) : "l"(P.logit_scale + 2 * half + (GORD == 2 ? c >> 1 : c & 1)));
    } else if (wg == 3) {
        if (warp == 3) {
            if (elect_one()) {
#pragma unroll
                for (int i = 0; i < 6; i++)
                    asm volatile("prefetch.tensormap [%0];\n" :: "l"(reinterpret_cast<uint64_t>(&M.x44 + (i < 4 ? i : i - 6))) : "memory");
            }
            if (attn)
#pragma unroll
                for (int i = 0; i < 4; i++) sts128(sbase + SM_V + i * V_STRIDE + (lane < 16 ? lane * 16 : V_STRIDE - 64 + (lane & 3) * 16), 0, 0, 0, 0);
            sts32(sbase + SM_FLAG + lane * 4, 0);
            fence_async_smem();
            asm volatile("bar.arrive 0, 256;\nbar.arrive 11, %0;\n" :: "n"(PPAR ? 416 : 384) : "memory");
        } else if (warp != 1) {
            if (tid == 384) {
                for (int b = 0; b < 4; b++) mbar_init(bars + B_XFULL + b * 8, 2);
                asm volatile("mbarrier.expect_tx.relaxed.cta.shared::cta.b64 [%0], %1;\n" :: "r"(bars + B_XFULL + 8), "r"(3 * 21 * 128) : "memory");
                fence_async_smem();
            }
            __syncwarp();
            asm volatile("bar.arrive 0, 256;\nbar.arrive 11, %0;\n" :: "n"(PPAR ? 416 : 384) : "memory");
            nb_sync<WFIRST ? 96 : 64>(3);
            if (attn && elect_one()) {
                const int j = warp >> 1, q = w0 + j * wstep, r = q >= NWS;
                mbar_arrive_expect_tx(bars + B_XFULL, j ? 3 * 28 * 128 : 3 * XCH);
                load_x(sbase + SM_QK + j * XCH, bars + B_XFULL, bars + B_XFULL + j * 8, unrot(r), unrot(q - r * NWS));
                TP(26 + j);
            }
            __syncwarp();
        } else {
            if (lane == 0) {
                for (int b = 0; b < 4; b++) {
                    mbar_init(bars + B_QKRAW + b * 8, 4);
                    mbar_init(bars + B_VRAW + b * 8, 4);
                    mbar_init(bars + B_VFREE + b * 8, 2);
                    mbar_init(bars + B_QKFREE + b * 8, (NB & 1) ? 1 : 4);
                    mbar_init(bars + B_ODONE + b * 8, 4);
                }
                mbar_init(bars + B_WFULL, 1);
                mbar_init(bars + B_MFULL, 1);
                mbar_init(bars + B_MCONS, 4);
                sts32(bars + B_PROG, 0);
                if (SDEF == 4) sts32(bars + B_PROG + 8, 0);
                for (int b = 0; b < 4; b++) mbar_init(bars + B_STORED + b * 8, 1);
                for (int b = 0; b < 6; b++) {
                    mbar_init(sbase + SM_PBAR + b * 8, 1);
                    mbar_init(sbase + SM_PBAR + 48 + b * 8, PSTORE ? 1 : 4);
                    mbar_init(sbase + SM_PBAR + 104 + b * 8, 4);
                }
                mbar_init(sbase + SM_PBAR + 96, 13);
                fence_async_smem();
            }
            __syncwarp();
            TP(19);
            asm volatile("bar.arrive 0, 256;\nbar.arrive 11, %0;\n" :: "n"(PPAR ? 416 : 384) : "memory");
        }
        asm volatile("bar.sync 2, 128;\n" ::: "memory");
        if (warp == 3 && lane < 8)
            asm volatile("prefetch.tensormap [%0];\n" :: "l"(reinterpret_cast<uint64_t>(&M.x77 + (lane ? lane + 8 : 0))) : "memory");
        TP(13);
    }
    uint32_t ridx[26];
    uint32_t rc, w2[16];
    uint4 w1[4];
    if (attn && (wg == 1 || wg == 2)) {
        rc = reinterpret_cast<const uint32_t*>(P.rel_coords)[min(tid - 128, 168)];
#pragma unroll
        for (int i = 0; i < 4; i++) w1[i] = reinterpret_cast<const uint4*>(P.cpb_w1)[i];
#pragma unroll
        for (int u = 0; u < 16; u++) w2[u] = reinterpret_cast<const uint32_t*>(P.cpb_w2)[2 * u + half];
        ls = reinterpret_cast<const uint32_t*>(P.logit_scale)[half];
        asm volatile("" ::: "memory");
        uint32_t col[7];
#pragma unroll
        for (int j = 0; j < 7; j++) {
            const uint32_t n = j ? 8 * ((j + 5) >> 1) + ((j + 1) & 1) : 0;
            col[j] = prmt(0, row_token(n) | row_token(n + 2) << 8 | row_token(n + 4) << 16 | row_token(n + 6) << 24, 4 + c);
        }
#pragma unroll
        for (int rh = 0; rh < 2; rh++) {
            const uint32_t* ri = reinterpret_cast<const uint32_t*>(P.rel_idx) + row_token(min(warp * 16 + g + 8 * rh, TOK - 1)) * TOK;
            asm volatile("" : "+l"(ri));
#pragma unroll
            for (int j = 0; j < 12; j++) ridx[13 * rh + j] = j < 6 ? (ri + col[0])[14 * (j >> 1) + (j & 1)] : ri[col[j - 5]];
            ridx[13 * rh + 12] = ri[48];
        }
    }
    if (wg == 1) TP(31);
    if (wg == 0) asm volatile("bar.sync 0, 256;\n" ::: "memory");
    else if (wg < 3) nb_sync<PPAR ? 416 : 384>(11);
    TP(4 + wg);

    const uint32_t nfinish = GRID + 4 * (PQ(npair) + PQ(nh));
#define PROJ_SCHEDULE                                                                                   \
    int bid = blockIdx.x;                                                                               \
    asm volatile("" : "+r"(bid));                      \
    const bool at = bid < 2 * PQ(npair);                                                                  \
    const int tile0 = at ? PQ(t1) + 2 * PQ(npair) - 1 - bid : bid - 2 * PQ(npair);                                              \
    const int tstep = at ? 2 * PQ(npair) : GRID - 2 * PQ(npair);                                  \
    const int tend = at ? TILES : PQ(t1);                                                                \
    const int nl = (TILES - 1 - tile0) / (2 * PQ(npair));        \
    const int tend1 = COOP && at ? tile0 + (nl + 1 - COOP) * tstep : tend;
    if (wg == 3) {
        asm volatile("setmaxnreg.dec.sync.aligned.u32 %0;\n" :: "n"(REG_H));
        if (attn && warp == 1 && !(XP & 1)) {
            uint32_t fph = 0, cph = 0, mis = 0, busy = 0;
            auto load = [&](int k, uint32_t dst) {
                const int wi = w0 + k * wstep, wr = wi / NWS;
                const uint32_t off = (uint32_t)(unrot(wr) * NWS + unrot(wi - wr * NWS)) * 4802u;
                mis = mis << 4 | (off & 15);
                if (busy) {
                    mbar_wait(bars + B_MCONS, cph);
                    cph ^= 1;
                    fence_async_smem();
                    busy = 0;
                }
                if (elect_one()) {
                    uint32_t bytes = 4816;
                    if (wi == 0) {
                        bytes = 4800;
                        asm volatile("st.shared.u16 [%0], %1;\n" :: "r"(sbase + SM_MASK + 4800),
                                     "h"(reinterpret_cast<const uint16_t*>(P.mask)[NWINDOWS * TOK * TOK - 1]) : "memory");
                    }
                    asm volatile("mbarrier.expect_tx.relaxed.cta.shared::cta.b64 [%0], %1;\n" :: "r"(bars + B_MFULL), "r"(bytes) : "memory");
                    if (dst == sbase + SM_MASK) mbar_arrive(bars + B_MFULL);
                    asm volatile("cp.async.bulk.shared::cluster.global.mbarrier::complete_tx::bytes.L2::cache_hint [%0], [%1], %2, [%3], %4;\n"
                                 :: "r"(dst), "l"(reinterpret_cast<const char*>(P.mask) + (off & ~15u)),
                                    "r"(bytes), "r"(bars + B_MFULL), "l"(EVICT_FIRST) : "memory");
                }
            };
            auto landed = [&]() {
                mbar_wait_s<HS & 1>(bars + B_MFULL, fph);
                fph ^= 1;
            };
            auto flag = [&](int k, uint32_t f) {
                asm volatile("st.volatile.shared.u8 [%0], %1;\n" :: "r"(sbase + SM_FLAG + k), "r"(f) : "memory");
                TR(18, k);
                if (k < 2) TP(14 + k);
            };
            auto pace = [&](int need) {
                int done = 0;
#pragma unroll 1
                for (uint32_t n = 0; n < (1u << 22); n++) {
                    asm volatile("ld.volatile.shared.b32 %0, [%1];\n" : "=r"(done) : "r"(bars + B_PROG) : "memory");
                    if (done >= need) break;
                    __nanosleep(PSLEEP);
                }
                return done;
            };
            auto buffer = [&](int k) { return sbase + (k == 0 || k > 3 ? SM_MASK : SM_V + 2 * V_STRIDE + 256 + (k >> 1) * 4816); };
#pragma unroll 1
            for (int k = 2 + half; k >= 0; k = (k >> 1) - (k == 0)) load(k, buffer(k));
            uint32_t todo = 0;
            int sp = 0;
#pragma unroll 1
            for (int k = 0, kn; sp < nwin; k = kn) {
                int done = 0;
                if (k < nwin) {
                    done = pace(MD ? k - MLEAD - MD : k + 2 < nwin ? k - MLEAD : k - 3);
                    if (MD) done = __shfl_sync(0xffffffffu, done, 0);
                    const uint32_t buf = buffer(k);
                    if (buf == sbase + SM_MASK) landed();
                    TR(17, k);
                    uint32_t any;
                    asm volatile("ld.shared.u16 %0, [%1];\n" : "=r"(any)
                                 : "r"(buf + (mis & 15) + ((lane & 8) ? 4800 - 14 : 0) + (lane & 7) * 2) : "memory");
                    mis >>= 4;
#pragma unroll
                    for (int i = 0; i < 10; i++) {
                        uint32_t v[4];
                        asm volatile("ld.shared.v4.b32 {%0, %1, %2, %3}, [%4];\n" : "=r"(v[0]), "=r"(v[1]), "=r"(v[2]), "=r"(v[3])
                                     : "r"(buf + lane * 16 + (i < 9 ? 16 + i * 512 : 4800 - 512)) : "memory");
                        any |= (v[0] | v[1]) | (v[2] | v[3]);
                    }
                    const uint32_t masked = __any_sync(0xffffffffu, any & 0x7FFF7FFFu);
                    if (k >= 2) asm volatile("st.relaxed.gpu.global.u32 [%0], %1;\n" :: "l"(g_flag + pair * 128 + k), "r"(1 + masked) : "memory");
                    if (masked && k) todo |= 1u << (k - sp);
                    else {
                        if (k == 0) __threadfence_block();
                        flag(k, 1 + masked);
                        busy |= masked;
                    }
                }
                if ((k >> 1) == 1 && lane == 0) mbar_arrive(bars + B_VFREE + 8);
                const int lim = MD && k < nwin ? min(k, done + MLEAD) : k;
#pragma unroll
                for (int pass = MD ? 1 : 0; pass >= 0; pass--) {
                if (pass == 0 && k > 2 && k <= nwin) {
                    uint32_t f;
#pragma unroll 1
                    for (uint32_t n = 0; n < (1u << 22); n++) {
                        asm volatile("ld.relaxed.gpu.global.u32 %0, [%1];\n" : "=r"(f) : "l"(g_flag + pair * 128 + k - 1) : "memory");
                        if (__all_sync(0xffffffffu, f)) break;
                        __nanosleep(PSLEEP);
                    }
                    g_flag[pair * 128 + k - 1] = 0;
                    if (f != 1) todo |= 1u << (k - 1 - sp);
                    else flag(k - 1, 1);
                }
#pragma unroll 1
                for (; sp < lim && sp < k - pass; sp++, todo >>= 1)
                    if (todo & 1) {
                        load(sp, sbase + SM_MASK);
                        landed();
                        __threadfence_block();
                        flag(sp, 2);
                        busy = 1;
                    }
                }
                kn = k >= 2 ? k + 2 : k + 1 + (k & half);
                if (kn < nwin && kn > 3) load(kn, sbase + SM_MASK);
                if (MP2 && kn + 2 * MP2 < nwin && kn > 1) {
                    const int wi = w0 + (kn + 2 * MP2) * wstep, wr = wi / NWS;
                    const uint32_t off = (uint32_t)(unrot(wr) * NWS + unrot(wi - wr * NWS)) * 4802u;
                    if (elect_one())
                        asm volatile("cp.async.bulk.prefetch.L2.global [%0], 4816;\n" :: "l"(reinterpret_cast<const char*>(P.mask) + (off & ~15u)) : "memory");
                }
            }
            if (MD) pace(nwin - 4);
        }
        if (!elect_one()) return;
        if (warp == 0) {
          if (attn) {
            const int kmax = (64 * ntiles + 63) / TOK;
            int wr = wr0, wq = wq0, npf = 0;
            int pr2 = (w0 + PF_DIST * wstep) / NWS, pq2 = w0 + PF_DIST * wstep - pr2 * NWS;
#pragma unroll 1
            for (int k = -4; k + 4 <= kmax; k++) {
                const int row0 = (k + 4) * TOK;
                const uint32_t dst = sbase + SM_QK + (k & 3) * XCH, bar = bars + B_XFULL + ((row0 >> 6) & 3) * 8;
                const bool alone = (row0 & 63) >= 64 - TOK && (row0 & 63) < TOK;
                const int wh = unrot(wr), ww = unrot(wq), ph2 = unrot(pr2), pw2 = unrot(pq2);
                const bool done = k < -2;
                if (k == WVK) {
                    TP(24);
                    mbar_arrive_expect_tx(bars + B_WFULL, 6 * W_ATOM);
                    tma_3d(sbase + SM_WV, &wmap, bars + B_WFULL, 0, 0, V64 ? 12 + half * 3 : 24 + half * 6);
                }
                const uint32_t bar2 = (row0 & 63) >= 64 - 28 ? bars + B_XFULL + (((row0 >> 6) + 1) & 3) * 8 : bar;
                if (alone && !done) mbar_arrive(bar);
                if (!done && !(k + 4 >= nwin && k >= 0)) {
                    if (bar2 != bar) asm volatile("mbarrier.expect_tx.relaxed.cta.shared::cta.b64 [%0], %1;\n" :: "r"(bar2), "r"(3 * 21 * 128) : "memory");
                    mbar_arrive_expect_tx(bar, bar2 != bar ? 3 * 28 * 128 : 3 * XCH);
                }
                if (SDEF == 4 && k >= 0 && k + 4 < nwin) {
                    const int t1 = (TOK * (k + 1) - 1) >> 6;
                    mbar_wait(bars + B_QKRAW + (t1 & 3) * 8, (t1 >> 2) & 1);
                    asm volatile("st.volatile.shared.v2.b32 [%0], {%1, %2};\n" :: "r"(bars + B_PROG + 8), "r"(k), "r"(clock32()) : "memory");
                }
                if (k >= 0 && k + 4 < nwin && wh < NWS - 1) {
                    const int x0 = 7 * ww + 3, y0 = 7 * wh + 3, x1 = ww == NWS - 1 ? 0 : x0 + 4;
                    asm volatile("bar.sync %0, 160;\n"
                                 "cp.async.bulk.tensor.3d.shared::cluster.global.mbarrier::complete_tx::bytes [%1], [%7, {%14, %11, %13}], [%9];\n"
                                 "cp.async.bulk.tensor.3d.shared::cluster.global.mbarrier::complete_tx::bytes [%2], [%7, {%15, %11, %13}], [%9];\n"
                                 "cp.async.bulk.tensor.3d.shared::cluster.global.mbarrier::complete_tx::bytes [%3], [%7, {%16, %11, %13}], [%9];\n"
                                 "cp.async.bulk.tensor.3d.shared::cluster.global.mbarrier::complete_tx::bytes [%4], [%8, {%14, %12, %13}], [%10];\n"
                                 "cp.async.bulk.tensor.3d.shared::cluster.global.mbarrier::complete_tx::bytes [%5], [%8, {%15, %12, %13}], [%10];\n"
                                 "cp.async.bulk.tensor.3d.shared::cluster.global.mbarrier::complete_tx::bytes [%6], [%8, {%16, %12, %13}], [%10];\n"
                                 :: "r"(NB_QKFREE + (k & 1) + (EXD ? __umulhi(__umulhi((x0 | y0 | x1) + dst, bar2), bar) : 0)), "r"(dst), "r"(dst + QK_CHUNK), "r"(dst + 2 * QK_CHUNK), "r"(dst + 28 * 128),
                                    "r"(dst + QK_CHUNK + 28 * 128), "r"(dst + 2 * QK_CHUNK + 28 * 128),
                                    "l"(reinterpret_cast<uint64_t>(&M.x47)), "l"(reinterpret_cast<uint64_t>(&M.x37)), "r"(bar), "r"(bar2),
                                    "r"(x0), "r"(x1), "r"(y0), "r"(0), "r"(64), "r"(128) : "memory");
                } else {
                if (NB & 1) {
                    if (k >= 0) nb_sync<160>(NB_QKFREE + (k & 1));
                } else mbar_wait(bars + B_QKFREE + (k & 3) * 8, (k >> 2) & 1);
                if (!EXH && alone && !done) mbar_arrive(bar);
                if (k + 4 >= nwin && k >= 0) {
                    mbar_arrive(bar);
                    continue;
                }
                TR(20, k + 4);
                if (k < 0) TP(44 + k);
                if (!done) load_x(dst, bar, bar2, wh, ww);
                }
                TR(25, k + 4);
                asm volatile("st.volatile.shared.b32 [%0], %1;\n" :: "r"(bars + B_PROG), "r"(max(k + 1, 0)) : "memory");
                if (NOPF || (PFM >= 7 && k > 0)) {
                } else if (PFM == 6) {
                    npf++;
                    const int t1 = (TOK * (k + 2) - 1) >> 6;
                    if (half == 0 && (k < 0 || npf > 2 || !mbar_test(bars + B_QKRAW + (t1 & 3) * 8, (t1 >> 2) & 1))) {
#pragma unroll 1
                        for (; npf > 0; npf--) {
                            if (pr2 < NWS)
                                asm volatile("cp.async.bulk.prefetch.tensor.3d.L2.global.tile [%0, {%1, %2, %3}];\n"
                                             :: "l"(reinterpret_cast<uint64_t>(&xmap)), "r"(0), "r"(7 * unrot(pq2) + 3), "r"(7 * unrot(pr2) + 3) : "memory");
                            pq2 += wstep; if (pq2 >= NWS) { pq2 -= NWS; pr2++; }
                        }
                    }
                } else if (PFM == 2) {
                    if (pr2 < NWS && half == 0) {
                        const char* xp = reinterpret_cast<const char*>(P.x) + (size_t)((7 * ph2 + 3) * IMG + 7 * pw2 + 3) * 384;
#pragma unroll 1
                        for (int r = 0; r < (ph2 == NWS - 1 ? 3 : 7); r++)
                            asm volatile("cp.async.bulk.prefetch.L2.global [%0], 2688;\n" :: "l"(xp + r * (IMG * 384)) : "memory");
                    }
                } else if (PFM == 1 ? ((k ^ half) & 1) : PFM == 4 ? half == 1 : PFM == 5 ? 1 : half == 0) {
                    if (pr2 < NWS) {
#pragma unroll
                        for (int ch = 0; ch < (PF1 ? 1 : 3); ch++)
                            if (CH & 8)
                            asm volatile("cp.async.bulk.prefetch.tensor.3d.L2.global.tile.L2::cache_hint [%0, {%1, %2, %3}], %4;\n"
                                         :: "l"(reinterpret_cast<uint64_t>(&xmap)), "r"(ch * 64), "r"(7 * pw2 + 3), "r"(7 * ph2 + 3), "l"(EVICT_FIRST)
                                         : "memory");
                            else
                            asm volatile("cp.async.bulk.prefetch.tensor.3d.L2.global.tile [%0, {%1, %2, %3}];\n"
                                         :: "l"(reinterpret_cast<uint64_t>(&xmap)), "r"(ch * 64), "r"(7 * pw2 + 3), "r"(7 * ph2 + 3)
                                         : "memory");
                        if (PFW && pw2 == NWS - 1)
                            asm volatile("cp.async.bulk.prefetch.tensor.3d.L2.global.tile [%0, {%1, %2, %3}];\n"
                                         :: "l"(reinterpret_cast<uint64_t>(&xmap)), "r"(0), "r"(-4), "r"(7 * ph2 + 3) : "memory");
                    }
                }
                wq += wstep; if (wq >= NWS) { wq -= NWS; wr++; }
                if (PFM != 6) { pq2 += wstep; if (pq2 >= NWS) { pq2 -= NWS; pr2++; } }
            }
            mbar_wait(bars + B_VRAW + ((ntiles - 1) & 3) * 8, ((ntiles - 1) >> 2) & 1);
          }
            PROJ_SCHEDULE
            int st = 0, ready = -1;
            uint32_t ph = 1;
#pragma unroll 1
            for (int t = tile0; t < tend; t += tstep) {
                const int p0 = (t < TILES_A) ? SEG_B + 64 * t : 64 * (t - TILES_A);
                const int w1 = (t < TILES_A) ? 0 : min((p0 + 63 + 4 * IMG) / (7 * IMG), NWS - 1);
                if (bid < 2 * (PQ(npair) + PQ(nh)) && t == tile0 + tstep) {
                    mbar_wait(sbase + SM_PBAR + 96, 0);
                    fence_async_smem();
                }
                if (ready < w1) {
                    ready = max(ready, w1 - 2);
#pragma unroll 1
                    while (ready < w1) {
                        ready++;
#pragma unroll 1
                        for (uint32_t n = 0; n < (1u << 22); n++) {
                            uint32_t a;
                            asm volatile("ld.acquire.gpu.global.u32 %0, [%1];\n" : "=r"(a) : "l"(g_cnt + ready) : "memory");
                            if (a >= PQ(need)) break;
                            __nanosleep(64);
                        }
                    }
                    asm volatile("fence.proxy.async.global;\n" ::: "memory");
                }
                TRH(9, (t - tile0) / tstep);
                mbar_wait_s<(HS & 4) != 0>(sbase + SM_PBAR + 48 + st * 8, ph);
                TRH(5, (t - tile0) / tstep);
                if (PEXP & 2) mbar_arrive(sbase + SM_PBAR + st * 8); else {
                mbar_arrive_expect_tx(sbase + SM_PBAR + st * 8, STAGE_BYTES);
#pragma unroll
                for (int ch = 0; ch < 3; ch++)
                    tma_2d(sbase + SM_STAGE + st * STAGE_BYTES + ch * 8192, &omap, sbase + SM_PBAR + st * 8, ch * 64, (PEXP & 4) ? p0 & 8191 : p0);
                }
                if (++st == 6) { st = 0; ph ^= 1; }
            }
            finish(nfinish);
        } else if (!attn) {
        } else if (warp == 1) {
          {
            if (PQ(t1) < TILES) {
#pragma unroll 1
                for (uint32_t n = 0; n < (1u << 22); n++) {
                    uint32_t a;
                    asm volatile("ld.acquire.gpu.global.u32 %0, [%1];\n" : "=r"(a) : "l"(g_cnt + NWS) : "memory");
                    if (a) break;
                    __nanosleep(64);
                }
                asm volatile("fence.proxy.async.global;\n" ::: "memory");
                if (blockIdx.x % 6 == 0)
                    asm volatile("cp.async.bulk.prefetch.L2.global [%0], 4096;\n" :: "l"(g_wo + blockIdx.x / 6 % 18 * 4096) : "memory");
                if (NB & 4) mbar_wait(bars + B_QKRAW, 0);
                else mbar_wait(bars + B_QKRAW + ((ntiles - 1) & 3) * 8, ((ntiles - 1) >> 2) & 1);
                mbar_arrive_expect_tx(bars + B_WRAW, 73728);
#pragma unroll
                for (int i = 0; i < 4; i++) {
                    const uint32_t o = ((i + pair) & 3) * 18432;
                    asm volatile("cp.async.bulk.shared::cluster.global.mbarrier::complete_tx::bytes [%0], [%1], 18432, [%2];\n"
                                 :: "r"(sbase + SM_WO + o), "l"(g_wo + o), "r"(bars + B_WRAW) : "memory");
                }
            }
            finish(nfinish);
          }
        } else if (warp == 2) {
            int wh = wr0, ww = wq0, nb = wr0 + 1, k = 0;
#pragma unroll 1
            for (int j = 0; k < nwin; j++) {
                mbar_wait_s<HS & 1>(bars + B_STORED + (j & 1) * 8, (j >> 1) & 1);
                mbar_arrive(bars + B_PUBD + (j & 1) * 8);
                if (PUBM != 1) asm volatile("fence.release.gpu;\n" ::: "memory");
#pragma unroll 1
                for (; wh < nb && k < nwin; k++) {
                    asm volatile("red.relaxed.gpu.global.add.u32 [%0], 1;\n" :: "l"(g_cnt + wh) : "memory");
                    ww += wstep; if (ww >= NWS) { ww -= NWS; wh++; }
                }
                nb = wh >= PBE ? wh + 1 : (wh | 1) + 1;
            }
            TC(7);
            finish(nfinish);
        } else {
            for (int t = 0; t < 2; t++) mbar_arrive_n(bars + B_VFREE + t * 8, M01 == 2 ? 2 - t : 2);
            int wr = wr0, wq = wq0, nb = wr0 + 1, j = 0, npf = 0, tprev = 0;
            int pr2 = (w0 + (PF_DIST + 5) * wstep) / NWS, pq2 = w0 + (PF_DIST + 5) * wstep - pr2 * NWS;
#pragma unroll 1
            for (int k = 0; k < nwin; k++) {
                const uint32_t src = sbase + SM_V + (k & 3) * V_STRIDE;
                const int wh = unrot(wr), ww = unrot(wq);
                const int x0 = 7 * ww + 3, y0 = 7 * wh + 3;
                if (NB & 2) nb_sync<160>(NB_ODONE + (k & 3));
                else mbar_wait_s<(HS & 2) != 0>(bars + B_ODONE + (k & 3) * 8, (k >> 2) & 1);
                if (SDEF) {
                    const int t1 = (TOK * (k + 2) - 1) >> 6, t2 = (TOK * (k + 3) - 1) >> 6;
                    int need = 0;
                    if (SDEF == 4) {
                        int tag, tq;
                        asm volatile("ld.volatile.shared.v2.b32 {%0, %1}, [%2];\n" : "=r"(tag), "=r"(tq) : "r"(bars + B_PROG + 8) : "memory");
                        const int now = clock32();
                        if (tag == k + 1 && now - tq > STH && now - tprev > STH + STP) need = k + 2;
                        tprev = now;
                    } else
                    if (SDEF == 3 || mbar_test(bars + B_QKRAW + (t1 & 3) * 8, (t1 >> 2) & 1)) need = k + 2;
                    if (SDEF == 2 && mbar_test(bars + B_QKRAW + (t2 & 3) * 8, (t2 >> 2) & 1)) need = k + 3;
                    need = min(need, nwin - 4);
#pragma unroll 1
                    for (int n = 0; n < (SDV == 2 ? 0 : 4096); n++) {
                        int done;
                        asm volatile("ld.volatile.shared.b32 %0, [%1];\n" : "=r"(done) : "r"(bars + B_PROG) : "memory");
                        if (done >= need) break;
                        __nanosleep(SDN);
                    }
                    if (SDV && need == k + 2) mbar_wait(bars + B_VRAW + (t1 & 3) * 8, (t1 >> 2) & 1);
                }
                fence_async_smem();
                TR(22, k);
                const int x1 = ww == NWS - 1 ? 0 : x0 + 4;
                if (!(XP & 2)) tma_store_4d(&M.s47, src, 0, half, x0, y0);
                if (!(XP & 2)) tma_store_4d(&M.s37, src + 28 * O_PITCH, 0, half, x1, y0);
                if (wh == NWS - 1) {
                    tma_store_4d(&M.s43, src + 16 * O_PITCH, 0, half, x0, 0);
                    tma_store_4d(&M.s33, src + 40 * O_PITCH, 0, half, x1, 0);
                }
                asm volatile("cp.async.bulk.commit_group;\n" ::: "memory");
                if (PFM >= 7) {
                    npf++;
                    const int t2 = (TOK * (k + 3) - 1) >> 6;
                    if (half == 0 && (PFM == 8 || npf > 2 || !mbar_test(bars + B_QKRAW + (t2 & 3) * 8, (t2 >> 2) & 1))) {
#pragma unroll 1
                        for (; npf > 0; npf--) {
                            if (pr2 < NWS && k + PF_DIST + 6 - npf < nwin)
                                asm volatile("cp.async.bulk.prefetch.tensor.3d.L2.global.tile [%0, {%1, %2, %3}];\n"
                                             :: "l"(reinterpret_cast<uint64_t>(&xmap)), "r"(0), "r"(7 * unrot(pq2) + 3), "r"(7 * unrot(pr2) + 3) : "memory");
                            pq2 += wstep; if (pq2 >= NWS) { pq2 -= NWS; pr2++; }
                        }
                    }
                }
                asm volatile("cp.async.bulk.wait_group.read 0;\n" ::: "memory");
                {
                    const int row0 = (k + 4) * TOK;
                    mbar_arrive_n(bars + B_VFREE + ((row0 >> 6) & 3) * 8, ((row0 & 63) >= 64 - TOK && (row0 & 63) < TOK) ? 2 : 1);
                }
                TR(23, k);
                if (k == nwin - 1) mbar_arrive(sbase + SM_PBAR + 96);
                wq += wstep; if (wq >= NWS) { wq -= NWS; wr++; }
                if (wr >= nb || k == nwin - 1) {
                    nb = wr >= PBE ? wr + 1 : (wr | 1) + 1;
                    asm volatile("cp.async.bulk.wait_group 0;\n" ::: "memory");
                    if (WFEN) asm volatile("fence.proxy.async.global;\n" ::: "memory");
                    mbar_wait(bars + B_PUBD + (j & 1) * 8, ((j >> 1) + 1) & 1);
                    mbar_arrive(bars + B_STORED + (j & 1) * 8);
                    j++;
                }
            }
        }
        if (PSTORE && warp == 1) {
            PROJ_SCHEDULE
            int st = 0, prev = -1;
            uint32_t ph = 0;
#pragma unroll 1
            for (int t = tile0; t < tend1; t += tstep) {
                const int p0 = (t < TILES_A) ? SEG_B + 64 * t : 64 * (t - TILES_A);
                mbar_wait_s<(HS & 4) != 0>(sbase + SM_PBAR + 104 + st * 8, ph);
                fence_async_smem();
#pragma unroll
                for (int ch = 0; ch < ((PEXP & 1) ? 0 : 3); ch++)
                    if (CH & 1)
                    asm volatile("cp.async.bulk.tensor.2d.global.shared::cta.tile.bulk_group.L2::cache_hint [%0, {%2, %3}], [%1], %4;\n"
                                 :: "l"(reinterpret_cast<uint64_t>(t < TILES_A ? &omap : &omapb)),
                                    "r"(sbase + SM_STAGE + st * STAGE_BYTES + ch * 8192), "r"(ch * 64), "r"(p0), "l"(EVICT_FIRST) : "memory");
                    else
                    asm volatile("cp.async.bulk.tensor.2d.global.shared::cta.tile.bulk_group [%0, {%2, %3}], [%1];\n"
                                 :: "l"(reinterpret_cast<uint64_t>(t < TILES_A ? &omap : &omapb)),
                                    "r"(sbase + SM_STAGE + st * STAGE_BYTES + ch * 8192), "r"(ch * 64), "r"((PEXP & 8) ? (p0 & 8191) + 16384 : p0) : "memory");
                asm volatile("cp.async.bulk.commit_group;\n" ::: "memory");
                TRH(6, (t - tile0) / tstep);
                if (prev >= 0) {
                    asm volatile("cp.async.bulk.wait_group.read 1;\n" ::: "memory");
                    mbar_arrive(sbase + SM_PBAR + 48 + prev * 8);
                    TRH(21, (t - tile0) / tstep - 1);
                }
                prev = st;
                if (++st == 6) { st = 0; ph ^= 1; }
            }
            if (ENDR) asm volatile("cp.async.bulk.wait_group.read 0;\n" ::: "memory");
            else asm volatile("cp.async.bulk.wait_group 0;\n" ::: "memory");
            TR(30, 0);
            if (!(COOP && at)) TC(1);
        }
        return;
    }
    auto permute = [&](int i0, int i1) {
            uint32_t src[3][4], dst[3];
#pragma unroll
            for (int it = 0; it < 3; it++) {
                const int o = warp * 12 + it * 4 + (lane >> 3), r = (o / 6) * 8 + (lane & 7), u = o % 6;
#pragma unroll
                for (int h = 0; h < (GORD == 2 ? 0 : 2); h++) {
                    const int v = u + 6 * h + 4 * half;
                    const bool wide = v >> 3 == half;
                    src[it][h] = wide ? r * 128 + (((v ^ r) & 7) << 4) : 16384 + r * 64 + (((v ^ (r >> 1)) & 3) << 4);
                    src[it][2 + h] = src[it][h] + (wide ? 8192 : 4096);
                }
                dst[it] = sbase + u * 4096 + r * 32 + ((lane >> 2) & 1) * 16;
            }
            TP(16);
#pragma unroll 1
            for (int i = i0; i < i1; i++) {
                uint4 w[3][4];
                mbar_wait(bars + B_WRAW + 16 - 8 * i, 0);
                TP(20 + i);
#pragma unroll
                for (int it = 0; it < 3; it++)
#pragma unroll
                    for (int m = 0; m < 4; m++) w[it][m] = *reinterpret_cast<const uint4*>(smem + src[it][m] + i * 24576);
                wg_bar(PPAR ? 12 + wg : 7);
#pragma unroll
                for (int it = 0; it < 3; it++) {
                    const uint32_t d = dst[it] + i * 24576;
                    sts128(d, w[it][0].x, w[it][1].x, w[it][2].x, w[it][3].x);
                    sts128(d ^ 16, w[it][0].y, w[it][1].y, w[it][2].y, w[it][3].y);
                    sts128(d + 2048, w[it][0].z, w[it][1].z, w[it][2].z, w[it][3].z);
                    sts128((d ^ 16) + 2048, w[it][0].w, w[it][1].w, w[it][2].w, w[it][3].w);
                }
            }
        };
    if (PPAR && attn) {
        permute(wg, wg + 1);
        if (wg) nb_arrive<384>(15);
    }
    if (!attn) {
        asm volatile("setmaxnreg.inc.sync.aligned.u32 160;\n");
    } else if (wg == 0) {
        if (!PPAR) permute(0, 3);
        asm volatile("setmaxnreg.inc.sync.aligned.u32 %0;\n" :: "n"(REG_G));
        float qs = 1.f;
        if (GORD == 2 || c < 2) qs = round_bf16(expf(round_bf16(fminf(fmaxf(bf16lo(ls), -100.f), 4.6052f)))) * LOG2E;
        uint32_t xa[12][4];
        float accA[48], accB[48], accV[48];
        uint32_t rho = warp * 16 + (lane & 15), rq = warp * 16 + g;
        uint32_t hi = lane >> 4, lane0 = lane == 0, c2 = 2 * c;
        asm volatile("" : "+r"(hi), "+r"(lane0), "+r"(c2));
        auto row_addr = [&](uint32_t (&ax)[4], uint32_t r) {
            ax[0] = sbase + SM_QK + r * 128 + (((r & 7) ^ hi) << 4);
#pragma unroll
            for (int i = 1; i < 4; i++) ax[i] = ax[0] ^ (32 * i);
        };
#define XADDR(ax, s) ((ax)[((s) & 3) ^ (((s) >> 1) & 2)] + ((s) >> 2) * QK_CHUNK)
        uint64_t descW = make_desc(sbase, 2048, 256, 3);
        const uint32_t zero = (uint32_t)P.z1;
        const uint32_t vbase = sbase + SM_V + (lane >> 4) * GRP;
        const uint32_t ones = 0x3F803F80u, ones2 = ones;
        TP(10);
        {
            uint32_t ax[4];
            row_addr(ax, rho);
            mbar_wait(bars + B_XFULL, 0);
#pragma unroll
            for (int s = 0; s < 12; s++) ldsm_x4(xa[s], XADDR(ax, s));
        }
        TP(8);
        if (PPAR) nb_sync<384>(15); else wg_bar(7);
        fence_async_smem();
        TP(9);
        wgmma_fence();
        mma_qkv_a<SM_WA, 0>(accA, xa, descW);
        mma_qkv_b<SM_WA, KLO>(accA, xa, descW);
        wgmma_commit();
        mma_qkv_a<SM_WB, 0>(accB, xa, descW);
        wgmma_commit();
        TP(11);
        mbar_wait(bars + B_WFULL, 0);
        TP(12);
        if (tid == 0) TC(3);
        const int nt = (int)blockIdx.x < 2 * PQ(npair) ? ((int)blockIdx.x < PQ(nr2) ? PQ(nt1) : PQ(nt0)) : ((int)blockIdx.x < PQ(hr2) ? PQ(ht1) : PQ(ht0));
        for (int t = 0; t < nt; t++) {
            descW += P.z1;
            float ss[4];
            uint32_t pk[2][24];
            wgmma_wait<1>();
            reg_fence(accA);
            TR(0, t);
            TA(1, 0);
            if (t < 12 && (t < 4 || (t & 1))) TP(t < 4 ? 32 + t : 34 + (t >> 1));
#pragma unroll
            for (int i = 0; i < 4; i++) ss[i] = accA[i] * accA[i];
#pragma unroll
            for (int i = 4; i < 48; i++) ss[i & 3] = fmaf(accA[i], accA[i], ss[i & 3]);
            mma_qkv_b<SM_WB, KLO>(accB, xa, descW);
            wgmma_commit();
            TA(1, 1);
            sched_fence(zero, __float_as_uint(ss[0]), __float_as_uint(ss[1]), __float_as_uint(ss[2]), __float_as_uint(ss[3]));
#pragma unroll
            for (int j = 0; j < 12; j++) {
                pk[0][j] = pack_bf16(accA[4 * j], accA[4 * j + 1]);
                pk[1][j] = pack_bf16(accA[4 * j + 2], accA[4 * j + 3]);
                asm volatile("" : "+r"(pk[0][j]), "+r"(pk[1][j]));
            }
            wgmma_fence();
            if (V64) mma_w_a<0, 0>(accV, xa, descW + D_WV64); else mma_v_a<D_WV, 0>(accV, xa, descW);
            wgmma_commit();
            TA(1, 2);
            uint32_t av = vbase + rho * 16 + ((rho * 1338) >> 16) * (V_STRIDE - GRP);
            uint32_t aq[2];
            aq[0] = sbase + SM_QK + rq * 128 + (((rq & 7) ^ c2) << 4);
            aq[1] = aq[0] + 1024;
            if (rq >= 4 * TOK - 8) aq[1] = (aq[1] - QK_CHUNK) ^ 64;
            rho += 64;
            if (rho >= 4 * TOK) rho -= 4 * TOK;
            rq += 64;
            if (rq >= 4 * TOK) rq -= 4 * TOK;
            uint32_t an[4];
            row_addr(an, rho);
            const uint32_t bt = bars + (t & 3) * 8, pt = (t >> 2) & 1, bn = bars + ((t + 1) & 3) * 8, pn = ((t + 1) >> 2) & 1;
            uint32_t xok;
            wgmma_wait<1>();
            reg_fence(accB);
            TA(1, 3);
#pragma unroll
            for (int i = 0; i < 48; i++) ss[i & 3] = fmaf(accB[i], accB[i], ss[i & 3]);
            ss[0] += ss[1]; ss[2] += ss[3];
            if (V64) mma_w_b<0, KLO>(accV, xa, descW + D_WV64); else mma_v_b<D_WV, KLO>(accV, xa, descW);
            wgmma_commit();
            TA(1, 4);
            sched_fence(zero, __float_as_uint(ss[0]), __float_as_uint(ss[2]), av, aq[0], aq[1], an[0], an[1], an[2], an[3], rho, rq);
            const float f0 = rsqrt_ftz(ss[0] + 1e-12f) * qs, f1 = rsqrt_ftz(ss[2] + 1e-12f) * qs;
            const uint32_t f2[2] = {pack_bf16(f0, f0), pack_bf16(f1, f1)};
#pragma unroll
            for (int j = 0; j < 12; j++) {
                pk[0][12 + j] = (FM & 1) ? pack_bf16(accB[4 * j] * f0, accB[4 * j + 1] * f0) : pack_bf16(accB[4 * j], accB[4 * j + 1]);
                pk[1][12 + j] = (FM & 1) ? pack_bf16(accB[4 * j + 2] * f1, accB[4 * j + 3] * f1) : pack_bf16(accB[4 * j + 2], accB[4 * j + 3]);
            }
            auto qk_store = [&](int u0, int u1) {
#pragma unroll
                for (int u = u0; u < u1; u++)
#pragma unroll
                    for (int r = 0; r < 2; r++)
                        if ((FM & 1) && u >= 3)
                        sts128((aq[r] ^ ((u & 1) * 16 + (u & 2) * 32)) + (u >> 1) * QK_CHUNK, pk[r][4 * u], pk[r][4 * u + 1], pk[r][4 * u + 2], pk[r][4 * u + 3]);
                        else
                        sts128((aq[r] ^ ((u & 1) * 16 + (u & 2) * 32)) + (u >> 1) * QK_CHUNK,
                               hmul2_bf16(pk[r][4 * u], f2[r]), hmul2_bf16(pk[r][4 * u + 1], f2[r]),
                               hmul2_bf16(pk[r][4 * u + 2], f2[r]), hmul2_bf16(pk[r][4 * u + 3], f2[r]));
            };
            qk_store(0, XPOS - 1);
            xok = mbar_test(bn + B_XFULL, pn);
            qk_store(XPOS - 1, QSPLIT);
            if (EARLYQ) {
                __syncwarp();
                mbar_arrive_if(bt + B_QKRAW, lane0);
            }
            TR(1, t);
            TA(1, 5);
            mbar_wait_unless(xok, bn + B_XFULL, pn);
            TR(2, t);
            wgmma_wait<1>();
            TA(1, 6);
#pragma unroll
            for (int s = 0; s < (LDE == 2 ? 12 : KLO); s++) ldsm_x4(xa[s], XADDR(an, s));
            qk_store(QSPLIT, 6 - QPOST);
            if (QPOST) {
                wgmma_fence();
                mma_qkv_a<SM_WA, 0>(accA, xa, descW);
                wgmma_commit();
                qk_store(6 - QPOST, 6);
            }
            if (!EARLYQ) {
                __syncwarp();
                mbar_arrive_if(bt + B_QKRAW, lane0);
            }
            TR(3, t);
            TA(1, 7);
            if (!QPOST) {
                wgmma_fence();
                mma_qkv_a<SM_WA, 0>(accA, xa, descW);
                wgmma_commit();
            }
            TA(1, 8);
            wgmma_wait<1>();
            reg_fence(accV);
            TA(1, 9);
#pragma unroll
            for (int s = KLO; s < 12; s++) ldsm_x4(xa[s], XADDR(an, s));
            const uint32_t vok = mbar_test(bt + B_VFREE, pt);
            uint32_t vp[24];
#pragma unroll
            for (int j = 0; j < 24; j++) vp[j] = pack_bf16(accV[2 * j], accV[2 * j + 1]);
            reg_fence(vp);
            wgmma_fence();
            mma_qkv_b<SM_WA, KLO>(accA, xa, descW);
            wgmma_commit();
            TA(1, 10);
            mbar_wait_unless(vok, bt + B_VFREE, pt);
#pragma unroll
            for (int p = 0; p < 6; p++)
                stsm_x4(av + (p < 3 ? 2 * p : 2 * p + 1) * GRP, vp[4 * p], vp[4 * p + 1], vp[4 * p + 2], vp[4 * p + 3]);
            stsm_x2(av + 6 * GRP, ones, ones2);
            __syncwarp();
            mbar_arrive_if(bt + B_VRAW, lane0);
            TR(4, t);
            if (MERGEW != 1) wgmma_fence();
            mma_qkv_a<SM_WB, 0>(accB, xa, descW);
            wgmma_commit();
            TA(1, 11);
        }
        TAEND(1);
        wgmma_wait<0>();
        reg_fence(accA);
        reg_fence(accB);
        asm volatile("setmaxnreg.dec.sync.aligned.u32 160;\n");
    } else {
        if (REG_A > 128) asm volatile("setmaxnreg.inc.sync.aligned.u32 %0;\n" :: "n"(REG_A));
        {
            const float c0 = bf16lo(rc), c1 = bf16hi(rc);
            float a0 = 0.f, a1 = 0.f;
#pragma unroll
            for (int u = 0; u < 16; u += 2) {
                const uint32_t p = reinterpret_cast<const uint32_t*>(w1)[u >> 1], q = reinterpret_cast<const uint32_t*>(w1)[8 + (u >> 1)];
                uint32_t h;
                asm("cvt.rn.relu.bf16x2.f32 %0, %1, %2;\n" : "=r"(h) : "f"(c0 * bf16hi(p) + c1 * bf16hi(q)), "f"(c0 * bf16lo(p) + c1 * bf16lo(q)));
                a0 += bf16lo(h) * bf16lo(w2[u]);
                a1 += bf16lo(h) * bf16hi(w2[u]);
                a0 += bf16hi(h) * bf16lo(w2[u + 1]);
                a1 += bf16hi(h) * bf16hi(w2[u + 1]);
            }
            const float s0 = round_bf16(__fdividef(1.f, 1.f + expf(-round_bf16(a0))));
            const float s1 = round_bf16(__fdividef(1.f, 1.f + expf(-round_bf16(a1))));
            if (tid - 128 < 169) sts32(sbase + SM_TAB + (tid - 128) * 4, pack_bf16(exp2f(fmaf(s0, 16.f * LOG2E, -12.f)), exp2f(fmaf(s1, 16.f * LOG2E, -12.f))));
        }
        asm volatile("bar.sync 1, 256;\n" ::: "memory");
        uint32_t eb[26];
        {
            const uint32_t* tab = reinterpret_cast<const uint32_t*>(smem + SM_TAB);
#pragma unroll
            for (int i = 0; i < 13; i++) {
                const uint32_t lo = tab[min(ridx[i < 12 ? 13 * (i & 1) + (i & ~1) : 12], 168u)];
                const uint32_t hi = tab[min(ridx[i < 12 ? 13 * (i & 1) + (i | 1) : 25], 168u)];
                eb[i]      = prmt(lo, hi, 0x5410);
                eb[13 + i] = prmt(lo, hi, 0x7632);
            }
            if (c != 0) eb[12] = eb[25] = 0;
            if (EBZ) {
                const uint32_t k0 = warp * 16 + g < TOK ? ~0u : 0u, k1 = warp < 3 ? ~0u : 0u;
#pragma unroll
                for (int i = 0; i < 26; i++) eb[i] &= i % 13 == 12 ? (k0 & 0xFFFFu) | (k1 & 0xFFFF0000u) : ((i % 13) & 1) ? k1 : k0;
            }
        }
        uint32_t slow = (bf16lo(ls) <= LS_FAST ? 0 : 1) | (bf16hi(ls) <= LS_FAST ? 0 : 2);
        reg_fence(eb);
        if (SLOWH == 2) sts32(bars + B_PROG + 4, slow);
        wg_bar(3 + wg);
        if ((tid & 127) == 0) mbar_arrive(bars + B_VFREE + 16);
        const uint32_t ov0 = warp * 16 + g < TOK, ov1 = warp < 3;
        const uint64_t descK0 = make_desc(sbase + SM_QK, 16, 1024, 1);
        const uint64_t descV0 = make_desc(sbase + SM_V, 128, GRP, 0);
        slow = __shfl_sync(0xffffffffu, slow, 0);
        const uint32_t barw = bars + (wg - 1) * 8;
        const uint64_t descKw = descK0 + (uint64_t)((wg - 1) * (XCH >> 4)), descVw = descV0 + (uint64_t)((wg - 1) * (V_STRIDE >> 4));
        const uint32_t oa = sbase + SM_V + (wg - 1) * V_STRIDE + (warp * 16 + g) * O_PITCH + c * 48;
        uint32_t qok = 0;
        const uint32_t zero = (uint32_t)P.z1;
        auto window = [&](auto IT_, int k) {
            constexpr int IT = decltype(IT_)::value;
            const uint32_t bar = barw + 16 * IT;
            const int tl = (k * TOK + TOK - 1) >> 6, tn = ((k + 2) * TOK + TOK - 1) >> 6;
            const uint32_t bt = bars + (tl & 3) * 8, pt = (tl >> 2) & 1;
            TR(8, k);
            if (k < 2) TP(44 + k);
            float sc0[28], sc1[28];
            TR(10, k);
            TA(2, 0);
            if (NB & 4) nb_sync<256>(NB_QKRAW + 2 * IT - 1 + wg);
            else mbar_wait_unless(qok, bt + B_QKRAW, pt);
            fence_async_smem();
            TR(11, k);
            TA(2, 1);
            if (k == 0) TP(17);
            wgmma_fence();
            mma_qk0<2 * IT * XCH, 2 * IT * XCH>(sc0, descKw, descKw);
            mma_qk1<2 * IT * XCH, 2 * IT * XCH>(sc1, descKw, descKw);
            wgmma_commit();
            TA(2, 2);
            uint32_t vok = PVL || VT ? 0 : mbar_test(bt + B_VRAW, pt);
            uint32_t mflag = 1;
            if (!(XP & 1)) asm volatile("ld.volatile.shared.u8 %0, [%1];\n" : "=r"(mflag) : "r"(sbase + SM_FLAG + k) : "memory");
            wgmma_wait<0>();
            reg_fence(sc0);
            reg_fence(sc1);
            if (NB & 1) nb_arrive<160>(NB_QKFREE - 1 + wg);
            else if (lane == 0) mbar_arrive(bar + B_QKFREE);
            TR(12, k);
            TA(2, 3);
            if (k == 0) TP(18);
            if (mflag != 1) {
              asm volatile(
                "{\n.reg .pred p;\n.reg .u32 n;\nmov.u32 n, 0;\n"
                "WAIT_%=:\n"
                "ld.volatile.shared.u8 %0, [%1];\n"
                "setp.ne.u32 p, %0, 0;\n"
                "@p bra DONE_%=;\n"
                "add.u32 n, n, 1;\n"
                "setp.lt.u32 p, n, 16777216;\n"
                "@p bra WAIT_%=;\n"
                "trap;\n"
                "DONE_%=:\n}\n" : "=r"(mflag) : "r"(sbase + SM_FLAG + k) : "memory");
              if (mflag == 2) {
                uint32_t mk[13];
                __threadfence_block();
                uint32_t u = threadIdx.x, bid = blockIdx.x;
                asm volatile("" : "+r"(u), "+r"(bid));
                const uint32_t r0 = ((u >> 1) & 48) + ((u >> 2) & 7);
                const int pr = bid >> 1, wi = pr < PQ(npair) ? PQ(hw) + pr + k * PQ(npair) : pr - PQ(npair) + k * PQ(nh), wr = wi / NWS;
                const uint32_t mp = sbase + SM_MASK + (((unrot(wr) * NWS + unrot(wi - wr * NWS)) * 2) & 15);
                const uint32_t mr[2] = {mp + row_token(min(r0, TOK - 1u)) * (2 * TOK), mp + row_token(min(r0 + 8, TOK - 1u)) * (2 * TOK)};
                const uint32_t c0 = 2 * row_token(2 * (u & 3));
#pragma unroll
                for (int i = 0; i < 13; i++) {
                    const uint32_t a0 = i < 6 ? mr[i & 1] + c0 + 28 * (i >> 1) : i < 12 ? mr[i & 1] + 2 * row_token(2 * (u & 3) + 8 * (i >> 1)) : mr[0] + 2 * TOK - 2;
                    const uint32_t a1 = i < 6 ? a0 + 2 : i < 12 ? mr[i & 1] + 2 * row_token(2 * (u & 3) + 8 * (i >> 1) + 1) : mr[1] + 2 * TOK - 2;
                    uint32_t lo, hi;
                    asm volatile("ld.shared.u16 %0, [%1];\n" : "=r"(lo) : "r"(a0) : "memory");
                    asm volatile("ld.shared.u16 %0, [%1];\n" : "=r"(hi) : "r"(a1) : "memory");
                    mk[i] = prmt(lo, hi, 0x5410);
                }
                reg_fence(mk);
                __syncwarp();
                if (lane == 0) mbar_arrive(bars + B_MCONS);
                uint32_t m0 = mk[0], m1 = mk[1];
#pragma unroll
                for (int i = 2; i < 12; i += 2) { m0 = hmax2_bf16(m0, mk[i]); m1 = hmax2_bf16(m1, mk[i + 1]); }
                m0 = hmax2_bf16(hmax2_bf16(prmt(m0, m1, 0x5410), prmt(m0, m1, 0x7632)), mk[12]);
                m0 = hmax2_bf16(m0, __shfl_xor_sync(0xffffffffu, m0, 1));
                m0 = hmax2_bf16(m0, __shfl_xor_sync(0xffffffffu, m0, 2));
                const float m[2] = {bf16lo(m0), bf16hi(m0)};
#pragma unroll
                for (int i = 0; i < 13; i++) {
                    const float lo = bf16lo(mk[i]) - m[i & 1], hi = bf16hi(mk[i]) - m[i < 12 ? i & 1 : 1];
                    const int j = i < 12 ? 2 * i + 1 : 26;
                    sc0[2 * i] = fmaf(lo, LOG2E, sc0[2 * i]); sc0[j] = fmaf(hi, LOG2E, sc0[j]);
                    sc1[2 * i] = fmaf(lo, LOG2E, sc1[2 * i]); sc1[j] = fmaf(hi, LOG2E, sc1[j]);
                }
              }
            }
            if (slow) {
                auto shift = [&](float (&S)[28], int h) {
                    float m[2];
#pragma unroll
                    for (int i = 12; i >= 0; i--) {
                        uint32_t e = eb[13 * h + i];
                        asm volatile("" : "+r"(e));
                        const float a = S[2 * i] + lg2_ftz(bf16lo(e)), b = S[i < 12 ? 2 * i + 1 : 26] + lg2_ftz(bf16hi(e));
                        if (i == 12) { m[0] = a; m[1] = b; }
                        else m[i & 1] = fmaxf(m[i & 1], fmaxf(a, b));
                    }
#pragma unroll
                    for (int r = 0; r < 2; r++) {
                        m[r] = fmaxf(m[r], __shfl_xor_sync(0xffffffffu, m[r], 1));
                        m[r] = fmaxf(m[r], __shfl_xor_sync(0xffffffffu, m[r], 2));
                    }
#pragma unroll
                    for (int i = 0; i < 27; i++) S[i] -= m[(i >> 1) & 1];
                };
                uint32_t sl = slow;
                if (SLOWH == 2) asm volatile("ld.volatile.shared.u32 %0, [%1];\n" : "=r"(sl) : "r"(bars + B_PROG + 4) : "memory");
                if (!SLOWH || (sl & 1)) shift(sc0, 0);
                if (!SLOWH || (sl & 2)) shift(sc1, 1);
            }
            auto exps = [&](const float (&S)[28], uint32_t (&e)[13]) {
#pragma unroll
                for (int i = 0; i < 12; i++) e[i] = pack_bf16(ex2_ftz(S[2 * i]), ex2_ftz(S[2 * i + 1]));
                e[12] = hmin2_bf16(pack_bf16(ex2_ftz(S[24]), ex2_ftz(S[26])), 0x7F7F7F7Fu);
            };
            auto probs = [&](const uint32_t (&e)[13], int h, uint32_t (&pa)[4][4]) {
#pragma unroll
                for (int i = 0; i < 12; i++) pa[i >> 2][i & 3] = hmul2_bf16(e[i], eb[13 * h + i]);
                const uint32_t l = hmul2_bf16(e[12], eb[13 * h + 12]);
                pa[3][0] = l & 0xFFFFu;
                pa[3][1] = l >> 16;
                pa[3][2] = 0u; pa[3][3] = 0u;
                reg_fence(pa);
            };
            uint32_t pa0[4][4], pa1[4][4], e[13];
            float o0[28], o1[28];
            TR(13, k);
            TA(2, 10);
            if (k == 0) TP(23);
            exps(sc0, e);
            if (VT) { reg_fence(e); vok = mbar_test(bt + B_VRAW, pt); }
            probs(e, 0, pa0);
            TA(2, 4);
            mbar_wait_unless(vok, bt + B_VRAW, pt);
            fence_async_smem();
            TR(14, k);
            TA(2, 5);
            wgmma_fence();
            mma_pv<2 * IT * V_STRIDE, 0>(o0, pa0, descVw);
            wgmma_commit();
            exps(sc1, e);
            reg_fence(e);
            TA(2, 6);
            wgmma_wait<0>();
            reg_fence(o0);
            TA(2, 7);
            sched_fence_rw(zero, e);
            if (!PVL || PVL == 3) {
                probs(e, 1, pa1);
                wgmma_fence();
            }
            mma_pv<2 * IT * V_STRIDE + 6 * GRP, 0>(o1, pa1, descVw);
            wgmma_commit();
            uint32_t w[24];
            {
                const float il0 = rcp_ftz(o0[24]), il1 = rcp_ftz(o0[26]);
                const uint32_t l0 = pack_bf16(il0, il0), l1 = pack_bf16(il1, il1);
#pragma unroll
                for (int j = 0; j < 12; j++) w[j] = (FM & 2) ? pack_bf16(o0[2 * j] * ((j & 1) ? il1 : il0), o0[2 * j + 1] * ((j & 1) ? il1 : il0)) : hmul2_bf16(pack_bf16(o0[2 * j], o0[2 * j + 1]), (j & 1) ? l1 : l0);
            }
            TA(2, 8);
            wgmma_wait<0>();
            reg_fence(o1);
            TA(2, 9);
            TR(15, k);
            if (k == 0) TP(25);
            wg_bar(3 + wg);
            if (!(NB & 4)) qok = mbar_test(bars + (tn & 3) * 8 + B_QKRAW, (tn >> 2) & 1);
            {
                const float il2 = rcp_ftz(o1[0]), il3 = rcp_ftz(o1[2]);
                const uint32_t l2 = pack_bf16(il2, il2), l3 = pack_bf16(il3, il3);
#pragma unroll
                for (int j = 0; j < 12; j++) w[12 + j] = (FM & 4) ? pack_bf16(o1[2 * j + 4] * ((j & 1) ? il3 : il2), o1[2 * j + 5] * ((j & 1) ? il3 : il2)) : hmul2_bf16(pack_bf16(o1[2 * j + 4], o1[2 * j + 5]), (j & 1) ? l3 : l2);
#pragma unroll
                for (int p = 0; p < 6; p++) {
                    const int j = 8 * (p >> 1) + (p & 1);
                    sts128_if((p & 1) ? ov1 : ov0, oa + 2 * IT * V_STRIDE + (p & 1) * 8 * O_PITCH + (p >> 1) * 16, w[j], w[j + 2], w[j + 4], w[j + 6]);
                }
            }
            if (NB & 2) nb_arrive<160>(NB_ODONE + 2 * IT - 1 + wg);
            else {
                __syncwarp();
                if (lane == 0) mbar_arrive(bar + B_ODONE);
            }
            TR(16, k);
            TA(2, 11);
            if (k < 2) TP(46 + k);
        };
        for (int k = wg - 1;; k += 4) {
            window(std::integral_constant<int, 0>(), k);
            if (k + 2 >= nwin) break;
            window(std::integral_constant<int, 1>(), k + 2);
            if (k + 4 >= nwin) break;
        }
        TAEND(2);
        (void)zero;
        asm volatile("setmaxnreg.inc.sync.aligned.u32 160;\n");
    }

    TR(27, wg);
    if ((tid & 127) == 0) TC(4 + wg);
    if (attn) {
        __syncwarp();
        if (lane == 0) mbar_arrive(sbase + SM_PBAR + 96);
    }
    if (!attn) {
#pragma unroll
        for (int row = tid >> 2; row < 192; row += 96) {
            uint4 w[6];
            const int pr = row % 96, srow = row - pr + (pr % 24) / 12 * 48 + (pr % 12) / 2 * 8 + pr / 24 * 2 + (pr & 1);
#pragma unroll
            for (int a = 0; a < 6; a++) w[a] = *reinterpret_cast<const uint4*>(P.wo + srow * 192 + 32 * a + 8 * c);
            float s = 0.f;
#pragma unroll
            for (int a = 0; a < 6; a++)
                s += ((bf16lo(w[a].x) + bf16hi(w[a].x)) + (bf16lo(w[a].y) + bf16hi(w[a].y))) +
                     ((bf16lo(w[a].z) + bf16hi(w[a].z)) + (bf16lo(w[a].w) + bf16hi(w[a].w)));
            s += __shfl_xor_sync(0xffffffffu, s, 1);
            s += __shfl_xor_sync(0xffffffffu, s, 2);
            s *= (1.f / 192.f);
            const uint32_t d = sbase + SM_WO + row * 64 + ((c ^ ((row >> 1) & 3)) << 4);
#pragma unroll
            for (int a = 0; a < 6; a++)
                sts128(d + a * 12288, pack_bf16(bf16lo(w[a].x) - s, bf16hi(w[a].x) - s), pack_bf16(bf16lo(w[a].y) - s, bf16hi(w[a].y) - s),
                       pack_bf16(bf16lo(w[a].z) - s, bf16hi(w[a].z) - s), pack_bf16(bf16lo(w[a].w) - s, bf16hi(w[a].w) - s));
        }
        fence_async_smem();
        asm volatile("bar.sync 6, 384;\n" ::: "memory");
        if (tid == 0 && (int)blockIdx.x == 2 * (PQ(npair) + PQ(nh))) {
            asm volatile("cp.async.bulk.global.shared::cta.bulk_group [%0], [%1], 73728;\n" :: "l"(g_wo), "r"(sbase + SM_WO) : "memory");
            asm volatile("cp.async.bulk.commit_group;\n" ::: "memory");
            asm volatile("cp.async.bulk.wait_group 0;\n" ::: "memory");
            asm volatile("fence.proxy.async.global;\n" ::: "memory");
            asm volatile("red.release.gpu.global.add.u32 [%0], 1;\n" :: "l"(g_cnt + NWS) : "memory");
        }
        __syncwarp();
    } else if (PQ(t1) < TILES) {
        mbar_wait(sbase + SM_BAR + B_WRAW, 1);
    }
    TR(27, 4 + wg);
    if (tid == 0) TC(2);
    {
        PROJ_SCHEDULE
        uint64_t descW = make_desc(sbase + SM_WO, 12288, 512, 2);
        const uint64_t descA = make_desc(sbase + SM_STAGE + wg * STAGE_BYTES, 16, 1024, 1);
        const uint32_t bar = sbase + SM_PBAR + wg * 8;
        const uint32_t yrel = sbase + SM_STAGE + wg * STAGE_BYTES + (warp * 16 + (lane & 15)) * 128 + (((lane & 7) ^ (lane >> 4)) << 4);
        float acc[96];
#pragma unroll
        for (int i = 0; i < 96; i++) acc[i] = 0.f;
        uint32_t it = 0;
        for (int tile = tile0 + wg * tstep; tile < tend1; tile += 3 * tstep, it++) {
            descW += P.z1;
            mbar_wait_s<(HS & 8) != 0>(bar + (it & 1) * 24, (it >> 1) & 1);
            TR(28, it * 3 + wg);
            if (it > 0 || wg > 0) asm volatile("bar.sync %0, 256;\n" :: "r"(8 + wg) : "memory");
            wgmma_fence();
            mma_proj<0, 0>(acc, descA + (uint64_t)((it & 1) * (3 * STAGE_BYTES >> 4)), descW);
            wgmma_commit();
            if (tile + tstep < tend1) asm volatile("bar.arrive %0, 256;\n" :: "r"(wg == 2 ? 8 : 9 + wg) : "memory");
            wgmma_wait<0>();
            reg_fence(acc);
            float a[4];
#pragma unroll
            for (int i = 0; i < 4; i++) a[i] = acc[i] * acc[i];
#pragma unroll
            for (int j = 1; j < 24; j++)
#pragma unroll
                for (int i = 0; i < 4; i++) a[i] = fmaf(acc[4 * j + i], acc[4 * j + i], a[i]);
            float s0 = a[0] + a[1], s1 = a[2] + a[3];
            s0 += __shfl_xor_sync(0xffffffffu, s0, 1);
            s1 += __shfl_xor_sync(0xffffffffu, s1, 1);
            s0 += __shfl_xor_sync(0xffffffffu, s0, 2);
            s1 += __shfl_xor_sync(0xffffffffu, s1, 2);
            const float rs0 = rsqrt_ftz(fmaf(s0, 1.f / 192.f, 1e-5f));
            const float rs1 = rsqrt_ftz(fmaf(s1, 1.f / 192.f, 1e-5f));
            const uint32_t ya = yrel + (it & 1) * 3 * STAGE_BYTES;
#pragma unroll
            for (int p = 0; p < 12; p++)
                stsm_x4((ya ^ (32 * (p & 3))) + (p >> 2) * 8192,
                        pack_bf16(acc[8 * p] * rs0, acc[8 * p + 1] * rs0), pack_bf16(acc[8 * p + 2] * rs1, acc[8 * p + 3] * rs1),
                        pack_bf16(acc[8 * p + 4] * rs0, acc[8 * p + 5] * rs0), pack_bf16(acc[8 * p + 6] * rs1, acc[8 * p + 7] * rs1));
            __syncwarp();
            if (lane == 0) mbar_arrive(bar + 104 + (it & 1) * 24);
            TR(29, it * 3 + wg);
        }
#pragma unroll 1
        for (int j = nl + 1 - COOP; COOP && at && j <= nl; j++) {
            float d[32];
            const uint32_t stage = sbase + SM_STAGE + j * STAGE_BYTES;
            mbar_wait(sbase + SM_PBAR + j * 8, 0);
            wgmma_fence();
            mma_proj64<0, 0>(d, make_desc(stage, 16, 1024, 1), descW + (uint64_t)(wg * (2 * 12288 >> 4)));
            wgmma_commit();
            wgmma_wait<0>();
            reg_fence(d);
            float a[4];
#pragma unroll
            for (int i = 0; i < 4; i++) a[i] = d[i] * d[i];
#pragma unroll
            for (int j = 1; j < 8; j++)
#pragma unroll
                for (int i = 0; i < 4; i++) a[i] = fmaf(d[4 * j + i], d[4 * j + i], a[i]);
            const uint32_t sa = sbase + SM_MASK - (j & 1) * 3072 + (warp * 16 + g) * 48;
            sts32(sa + wg * 16 + c * 4, __float_as_uint(a[0] + a[1]));
            sts32(sa + wg * 16 + c * 4 + 8 * 48, __float_as_uint(a[2] + a[3]));
            nb_sync<384>(15);
            float rs[2];
#pragma unroll
            for (int r = 0; r < 2; r++) {
                float v[12];
#pragma unroll
                for (int i = 0; i < 3; i++)
                    asm volatile("ld.shared.v4.f32 {%0, %1, %2, %3}, [%4];\n" : "=f"(v[4 * i]), "=f"(v[4 * i + 1]), "=f"(v[4 * i + 2]), "=f"(v[4 * i + 3])
                                 : "r"(sa + r * 8 * 48 + i * 16) : "memory");
                const float s = ((v[0] + v[1]) + (v[2] + v[3])) + ((v[4] + v[5]) + (v[6] + v[7])) + ((v[8] + v[9]) + (v[10] + v[11]));
                rs[r] = rsqrt_ftz(fmaf(s, 1.f / 192.f, 1e-5f));
            }
            const uint32_t ya = stage + wg * 8192 + (warp * 16 + (lane & 15)) * 128 + (((lane & 7) ^ (lane >> 4)) << 4);
#pragma unroll
            for (int p = 0; p < 4; p++)
                stsm_x4(ya ^ (32 * p),
                        pack_bf16(d[8 * p] * rs[0], d[8 * p + 1] * rs[0]), pack_bf16(d[8 * p + 2] * rs[1], d[8 * p + 3] * rs[1]),
                        pack_bf16(d[8 * p + 4] * rs[0], d[8 * p + 5] * rs[0]), pack_bf16(d[8 * p + 6] * rs[1], d[8 * p + 7] * rs[1]));
            fence_async_smem();
            wg_bar(12 + wg);
            if (warp == 0 && elect_one()) {
                asm volatile("cp.async.bulk.tensor.2d.global.shared::cta.tile.bulk_group.L2::cache_hint [%0, {%2, %3}], [%1], %4;\n"
                             :: "l"(reinterpret_cast<uint64_t>(&omapb)), "r"(stage + wg * 8192), "r"(wg * 64), "r"(64 * (tile0 + j * tstep - TILES_A)),
                                "l"(EVICT_FIRST) : "memory");
                asm volatile("cp.async.bulk.commit_group;\n" ::: "memory");
                if (j == nl) {
                    if (ENDR) asm volatile("cp.async.bulk.wait_group.read 0;\n" ::: "memory");
                    else asm volatile("cp.async.bulk.wait_group 0;\n" ::: "memory");
                }
                if (wg == 0) TC(1);
            }
        }
    }
}

}

typedef CUresult (*PFN_encodeTiled)(CUtensorMap*, CUtensorMapDataType, cuuint32_t, void*, const cuuint64_t*,
                                    const cuuint64_t*, const cuuint32_t*, const cuuint32_t*, CUtensorMapInterleave,
                                    CUtensorMapSwizzle, CUtensorMapL2promotion, CUtensorMapFloatOOBfill);

extern "C" void kernel_launch(void* const* d_in, const int* in_sizes, int n_in, void* d_out, int out_size) {
    swin::Params P;
    P.x           = (const __nv_bfloat16*)d_in[0];
    P.wqkv        = (const __nv_bfloat16*)d_in[1];
    P.wo          = (const __nv_bfloat16*)d_in[2];
    P.logit_scale = (const __nv_bfloat16*)d_in[3];
    P.cpb_w1      = (const __nv_bfloat16*)d_in[4];
    P.cpb_w2      = (const __nv_bfloat16*)d_in[5];
    P.rel_coords  = (const __nv_bfloat16*)d_in[6];
    P.rel_idx     = (const int*)d_in[7];
    P.mask        = (const __nv_bfloat16*)d_in[8];
    P.out         = (__nv_bfloat16*)d_out;
    P.z1 = 0;
    static PFN_encodeTiled encode = nullptr;
    if (!encode) {
        cudaFuncSetAttribute(swin::swin_window_attn_kernel, cudaFuncAttributeMaxDynamicSharedMemorySize, swin::SM_TOTAL);
        cudaDriverEntryPointQueryResult qr;
        cudaGetDriverEntryPoint("cuTensorMapEncodeTiled", (void**)&encode, cudaEnableDefault, &qr);
    }
    swin::Maps M;
    const cuuint32_t estr[4] = {1, 1, 1, 1};
    auto make = [&](CUtensorMap* m, const void* base, int rank, const cuuint64_t* gdim, const cuuint64_t* gstr,
                    const cuuint32_t* box, CUtensorMapSwizzle swz = CU_TENSOR_MAP_SWIZZLE_128B) {
        CUresult r = encode(m, CU_TENSOR_MAP_DATA_TYPE_BFLOAT16, rank, const_cast<void*>(base), gdim, gstr, box, estr,
               CU_TENSOR_MAP_INTERLEAVE_NONE, swz, CU_TENSOR_MAP_L2_PROMOTION_L2_128B,
               CU_TENSOR_MAP_FLOAT_OOB_FILL_NONE);
        (void)r;
    };
    {
        const cuuint64_t gdim[3] = {192, swin::IMG, swin::IMG}, gstr[2] = {384, swin::IMG * 384};
        const cuuint32_t box[7][3] = {{64, 7, 7}, {64, 4, 7}, {64, 3, 7}, {64, 4, 4}, {64, 4, 3}, {64, 3, 4}, {64, 3, 3}};
        for (int i = 0; i < 7; i++) make(&M.x77 + i, P.x, 3, gdim, gstr, box[i]);
        const cuuint32_t boxp[3] = {192, 7, 7};
        if (PF1) make(&M.x77, P.x, 3, gdim, gstr, boxp, CU_TENSOR_MAP_SWIZZLE_NONE);
    }
    {
        const cuuint64_t gdim[2] = {192, (cuuint64_t)swin::NPIX}, gstr[1] = {384};
        const cuuint32_t box64[2] = {64, 64};
        make(&M.o, d_out, 2, gdim, gstr, box64);
        const cuuint64_t gdimb[2] = {192, (cuuint64_t)swin::SEG_B};
        make(&M.ob, d_out, 2, gdimb, gstr, box64);
    }
    {
        const cuuint64_t gdim[3] = {V64 ? 32 : 16, 192, V64 ? 18 : 36}, gstr[2] = {1152, V64 ? 64 : 32};
        const cuuint32_t box[3] = {V64 ? 32 : 16, 192, V64 ? 3 : 6};
        make(&M.w, P.wqkv, 3, gdim, gstr, box, V64 ? CU_TENSOR_MAP_SWIZZLE_64B : CU_TENSOR_MAP_SWIZZLE_32B);
        const cuuint64_t gdim3[3] = {192, 192, 3}, gstr3[2] = {1152, 384};
        const cuuint32_t box64[3] = {64, 64, 2}, box32[3] = {32, 64, 2};
        make(&M.w64, P.wqkv, 3, gdim3, gstr3, box64);
        make(&M.w32, P.wqkv, 3, gdim3, gstr3, box32, CU_TENSOR_MAP_SWIZZLE_64B);
    }
    {
        const cuuint64_t gdim[4] = {96, 2, swin::IMG, swin::IMG}, gstr[3] = {192, 384, swin::IMG * 384};
        const cuuint32_t box[4][4] = {{96, 1, 4, 7}, {96, 1, 3, 7}, {96, 1, 4, 3}, {96, 1, 3, 3}};
        for (int i = 0; i < 4; i++) make(&M.s47 + i, d_out, 4, gdim, gstr, box[i], CU_TENSOR_MAP_SWIZZLE_NONE);
    }
    swin::swin_window_attn_kernel<<<132, swin::NTHREADS, swin::SM_TOTAL>>>(P, M);
}
```

```cpp
#include <cuda_runtime.h>
#include <cuda.h>
#include <cuda_bf16.h>
#include <stdint.h>
#include <type_traits>

namespace swin {
#define STR_(x) #x
#define STR(x) STR_(x)
#define HINT ""

#define NPAIR 53
#define PF_DIST 3
#define QSPLIT 4
#define CLUSTER 0
#define NOPF 0
#define NTAIL 303
#define PSTORE 1
#define PORDER 1
#define GORD 0
#define GF1 1
#define MERGEW 0
#define MWAIT 0
#define PSLEEP 200
#define CH 5
#define NB 1
#define SCM 0
#define MPF 2
#define MLEAD 4
#define PFM 0
#define PFK 4
#define XP 0
#define KLO 6
#define VPOS 1
#define XSPLIT 1
#define SEQ 1
#define PREL 0
#define PEXP 0
#define PFD 0
#define PFW 1
#define WVK -4
#define WSEQ 1
#define PF1 1
#define WFIRST 1
#define MPRE 1
#define SLOWH 2
#define LS_FAST 4.f
#define ENDR 1
#define EBZ 1
#define HSQ 0
#define AFENCE 0
#define FM 0
#define QPOST 0
#define EARLYQ 0
#define KL 4
#define VB1 4
#define VA0 1
#define K1 3
#define Q1 2
#define RWF 3
#define PUBM 2
#define NH 12
#define HW 29
#define HDEL 0
#define CONSTQ 1
#define V64 1
#define M01 2
#define PPAR 1
#define EPF 0
#define EPW 1
#define HS 0
#define MP2 1
#define SDEF 1
#define EXH 2
#define EXD 1
#define STH 200
#define STP 100
#define LDE 0
#define MD 0
#define COOP 0
#define PVL 0
#define VT 0
#define SDV 0
#define WROT 0
#define WVW 0
#define PSL2 64
#define SELFP 0
#define CHK 1
#define CHKS 100
#define LOOKA 1
#define VLATE 0
#define LOOKE 1
#define SDN 32
#define XPOS 4
#define PBE 70
#define WFEN 1
#define REG_G 224
#define REG_A 128
#define REG_H 32
constexpr int IMG      = 511;
constexpr int NWS      = 73;
constexpr int NWINDOWS = NWS * NWS;
constexpr int TOK      = 49;
constexpr int NPIX     = IMG * IMG;
constexpr int NTHREADS = 512;

constexpr int W_ATOM = 6144;
constexpr int SM_WA = 0, SM_WB = 6 * 2048, SM_WV = 12 * W_ATOM, D_WV = SM_WV + ((W_ATOM - 2048) << 16);
constexpr int GRP   = TOK * 16;
constexpr int XCH   = TOK * 128;
constexpr int SM_V  = 18 * W_ATOM, V_STRIDE = 10240, O_PITCH = 192;
constexpr int SM_QK = SM_V + 4 * V_STRIDE, QK_CHUNK = 4 * XCH;
constexpr int SM_MASK = SM_QK + 3 * QK_CHUNK;
constexpr int SM_TAB  = SM_V + 3 * V_STRIDE + 256;
constexpr int SM_BAR  = SM_MASK + 4816;
constexpr int B_XFULL = 0, B_WRAW = 32, B_QKRAW = 64, B_QKFREE = 96, B_VFREE = 128, B_ODONE = 160,
              B_PROG = 192, B_VRAW = 224, B_MFULL = 256, B_MCONS = 272, B_WFULL = 280, B_STORED = 288, B_PUBD = 304;
constexpr int SM_FLAG = SM_BAR + 320;
constexpr int SM_A_END = SM_FLAG + 128;
static_assert(SM_QK % 1024 == 0 && 13 * GRP <= V_STRIDE && V_STRIDE % 128 == 0, "layout");
constexpr int SM_WO    = 0;
constexpr int SM_STAGE = 73728;
constexpr int STAGE_BYTES = 24576;
constexpr int SM_PBAR  = SM_A_END;
#define TA(role, idx)
#define TAEND(role)
constexpr int SM_TOTAL = SM_PBAR + 152;
#define TP(idx)
static_assert(SM_STAGE + 6 * STAGE_BYTES <= SM_BAR, "smem");
static_assert(SM_TOTAL <= 232448, "smem");
static_assert(SM_STAGE + 6 * STAGE_BYTES + 3072 <= SM_MASK && NTAIL >= 2 * NPAIR * (COOP + 1) && NTAIL <= 12 * NPAIR, "shared tiles");
static_assert(SM_BAR % 8 == 0 && NWINDOWS / NPAIR < 123, "barrier alignment, flags");

constexpr int SEG_B   = (IMG - 4) * IMG;
constexpr int TILES_A = (NPIX - SEG_B + 63) / 64;
constexpr int TILES   = TILES_A + (SEG_B + 63) / 64;
constexpr uint32_t ROW_DONE = NWS * 2;

__device__ uint32_t g_cnt[NWS + 7];
__device__ __align__(128) uint8_t g_wo[73728];
__device__ uint32_t g_flag[66 * 128];
__device__ uint32_t g_done;

#define TR(ev, idx)
#define TC(slot)
#define TS(i)
#define TRH(ev, idx)
constexpr float LOG2E = 1.4426950408889634f;
__device__ __forceinline__ int clock32() { int c; asm volatile("mov.u32 %0, %%clock;" : "=r"(c) :: "memory"); return c; }

__device__ __forceinline__ uint32_t smem_u32(const void* p) {
    return (uint32_t)__cvta_generic_to_shared(p);
}
__device__ __forceinline__ uint64_t make_desc(uint32_t saddr, uint32_t lbo, uint32_t sbo, uint32_t swz = 0) {
    return (uint64_t)((saddr & 0x3FFFF) >> 4) | ((uint64_t)(lbo >> 4) << 16) | ((uint64_t)(sbo >> 4) << 32) |
           ((uint64_t)swz << 62);
}
__host__ __device__ constexpr uint64_t make_desc_c(uint32_t saddr, uint32_t lbo, uint32_t sbo, uint32_t swz) {
    return (uint64_t)(saddr >> 4) | ((uint64_t)(lbo >> 4) << 16) | ((uint64_t)(sbo >> 4) << 32) | ((uint64_t)swz << 62);
}
constexpr uint64_t D_WV64 = make_desc_c(SM_WV, 12288, 512, 2) - make_desc_c(0, 2048, 256, 3);
__device__ __forceinline__ void wgmma_fence()  { asm volatile("wgmma.fence.sync.aligned;\n" ::: "memory"); }
__device__ __forceinline__ void wgmma_commit() { asm volatile("wgmma.commit_group.sync.aligned;\n" ::: "memory"); }
template <int N> __device__ __forceinline__ void wgmma_wait() {
    asm volatile("wgmma.wait_group.sync.aligned %0;\n" :: "n"(N) : "memory");
}
__device__ __forceinline__ void fence_async_smem() { asm volatile("fence.proxy.async.shared::cta;\n" ::: "memory"); }
template <int N> __device__ __forceinline__ void nb_sync(int id) { asm volatile("bar.sync %0, %1;\n" :: "r"(id), "n"(N) : "memory"); }
template <int N> __device__ __forceinline__ void nb_arrive(int id) { asm volatile("bar.arrive %0, %1;\n" :: "r"(id), "n"(N) : "memory"); }
constexpr int NB_ODONE = 0, NB_QKFREE = 6, NB_QKRAW = 12;
__device__ __forceinline__ void wg_bar(int id) { asm volatile("bar.sync %0, 128;\n" :: "r"(id) : "memory"); }

template <int N> __device__ __forceinline__ void reg_fence(float (&v)[N]) {
#pragma unroll
    for (int i = 0; i < N; i++) asm volatile("" : "+f"(v[i]) :: "memory");
}
template <int N> __device__ __forceinline__ void reg_fence(uint32_t (&v)[N]) {
#pragma unroll
    for (int i = 0; i < N; i++) asm volatile("" : "+r"(v[i]) :: "memory");
}
template <int N, int M> __device__ __forceinline__ void reg_fence(uint32_t (&v)[N][M]) {
#pragma unroll
    for (int i = 0; i < N; i++) reg_fence(v[i]);
}

__device__ __forceinline__ uint32_t pack_bf16(float lo, float hi) {
    uint32_t r;
    asm("cvt.rn.bf16x2.f32 %0, %1, %2;\n" : "=r"(r) : "f"(hi), "f"(lo));
    return r;
}
__device__ __forceinline__ float bf16lo(uint32_t v) { return __uint_as_float(v << 16); }
__device__ __forceinline__ float bf16hi(uint32_t v) { return __uint_as_float(v & 0xFFFF0000u); }
__device__ __forceinline__ uint32_t hadd2_bf16(uint32_t a, uint32_t b) {
    uint32_t r;
    asm("add.rn.bf16x2 %0, %1, %2;\n" : "=r"(r) : "r"(a), "r"(b));
    return r;
}
__device__ __forceinline__ uint32_t hmul2_bf16(uint32_t a, uint32_t b) {
    uint32_t r;
    asm("mul.rn.bf16x2 %0, %1, %2;\n" : "=r"(r) : "r"(a), "r"(b));
    return r;
}
__device__ __forceinline__ uint32_t hsub2_bf16(uint32_t a, uint32_t b) {
    uint32_t r;
    asm("sub.rn.bf16x2 %0, %1, %2;\n" : "=r"(r) : "r"(a), "r"(b));
    return r;
}
__device__ __forceinline__ uint32_t hfma2_bf16(uint32_t a, uint32_t b, uint32_t c) {
    uint32_t r;
    asm("fma.rn.bf16x2 %0, %1, %2, %3;\n" : "=r"(r) : "r"(a), "r"(b), "r"(c));
    return r;
}
__device__ __forceinline__ uint32_t hmax2_bf16(uint32_t a, uint32_t b) {
    uint32_t r;
    asm("max.bf16x2 %0, %1, %2;\n" : "=r"(r) : "r"(a), "r"(b));
    return r;
}
__device__ __forceinline__ uint32_t hmin2_bf16(uint32_t a, uint32_t b) {
    uint32_t r;
    asm("min.bf16x2 %0, %1, %2;\n" : "=r"(r) : "r"(a), "r"(b));
    return r;
}
__device__ __forceinline__ uint32_t ex2_bf16x2(uint32_t a) {
    uint32_t r;
    asm("ex2.approx.ftz.bf16x2 %0, %1;\n" : "=r"(r) : "r"(a));
    return r;
}
__device__ __forceinline__ uint32_t ex2_bf16lo(uint32_t a) {
    uint32_t r;
    asm("{\n.reg .b16 l, h;\nmov.b32 {l, h}, %1;\nex2.approx.ftz.bf16 l, l;\ncvt.u32.u16 %0, l;\n}\n" : "=r"(r) : "r"(a));
    return r;
}
__device__ __forceinline__ uint32_t mbar_test(uint32_t bar, uint32_t parity) {
    uint32_t ok;
    asm volatile("{\n.reg .pred p;\nmbarrier.test_wait.parity.shared::cta.b64 p, [%1], %2;\nselp.u32 %0, 1, 0, p;\n}\n"
                 : "=r"(ok) : "r"(bar), "r"(parity) : "memory");
    return ok;
}
__device__ __forceinline__ uint32_t prmt(uint32_t a, uint32_t b, uint32_t sel) {
    uint32_t r;
    asm("prmt.b32 %0, %1, %2, %3;\n" : "=r"(r) : "r"(a), "r"(b), "r"(sel));
    return r;
}
__device__ __forceinline__ float round_bf16(float x) { return __bfloat162float(__float2bfloat16_rn(x)); }

__device__ __forceinline__ void mbar_init(uint32_t bar, uint32_t count) {
    asm volatile("mbarrier.init.shared::cta.b64 [%0], %1;\n" :: "r"(bar), "r"(count) : "memory");
}
__device__ __forceinline__ void mbar_wait(uint32_t bar, uint32_t parity) {
    asm volatile(
        "{\n"
        ".reg .pred p;\n"
        ".reg .u32 n;\n"
        "mov.u32 n, 0;\n"
        "WAIT_%=:\n"
        "mbarrier.try_wait.parity.shared::cta.b64 p, [%0], %1" HINT ";\n"
        "@p bra DONE_%=;\n"
        "add.u32 n, n, 1;\n"
        "setp.lt.u32 p, n, 4194304;\n"
        "@p bra WAIT_%=;\n"
        "trap;\n"
        "DONE_%=:\n"
        "}\n" :: "r"(bar), "r"(parity) : "memory");
}
template <bool S> __device__ __forceinline__ void mbar_wait_s(uint32_t bar, uint32_t parity) {
    if (!S) mbar_wait(bar, parity);
    else asm volatile(
        "{\n"
        ".reg .pred p;\n"
        ".reg .u32 n;\n"
        "mov.u32 n, 0;\n"
        "WAIT_%=:\n"
        "mbarrier.try_wait.parity.shared::cta.b64 p, [%0], %1, 4000;\n"
        "@p bra DONE_%=;\n"
        "add.u32 n, n, 1;\n"
        "setp.lt.u32 p, n, 262144;\n"
        "@p bra WAIT_%=;\n"
        "trap;\n"
        "DONE_%=:\n"
        "}\n" :: "r"(bar), "r"(parity) : "memory");
}
__device__ __forceinline__ void mbar_wait4(uint32_t b0, uint32_t p0, uint32_t b1, uint32_t p1, uint32_t b2, uint32_t p2,
                                           uint32_t b3, uint32_t p3) {
    asm volatile(
        "{\n"
        ".reg .pred p, q, r, s;\n"
        ".reg .u32 n;\n"
        "mov.u32 n, 0;\n"
        "WAIT_%=:\n"
        "mbarrier.try_wait.parity.shared::cta.b64 p, [%0], %1" HINT ";\n"
        "mbarrier.try_wait.parity.shared::cta.b64 q, [%2], %3" HINT ";\n"
        "mbarrier.try_wait.parity.shared::cta.b64 r, [%4], %5" HINT ";\n"
        "mbarrier.try_wait.parity.shared::cta.b64 s, [%6], %7" HINT ";\n"
        "and.pred p, p, q;\n"
        "and.pred r, r, s;\n"
        "and.pred p, p, r;\n"
        "@p bra DONE_%=;\n"
        "add.u32 n, n, 1;\n"
        "setp.lt.u32 p, n, 4194304;\n"
        "@p bra WAIT_%=;\n"
        "trap;\n"
        "DONE_%=:\n"
        "}\n" :: "r"(b0), "r"(p0), "r"(b1), "r"(p1), "r"(b2), "r"(p2), "r"(b3), "r"(p3) : "memory");
}
__device__ __forceinline__ void mbar_wait2(uint32_t b0, uint32_t p0, uint32_t b1, uint32_t p1) {
    asm volatile(
        "{\n"
        ".reg .pred p, q;\n"
        ".reg .u32 n;\n"
        "mov.u32 n, 0;\n"
        "WAIT_%=:\n"
        "mbarrier.try_wait.parity.shared::cta.b64 p, [%0], %1" HINT ";\n"
        "mbarrier.try_wait.parity.shared::cta.b64 q, [%2], %3" HINT ";\n"
        "and.pred p, p, q;\n"
        "@p bra DONE_%=;\n"
        "add.u32 n, n, 1;\n"
        "setp.lt.u32 p, n, 4194304;\n"
        "@p bra WAIT_%=;\n"
        "trap;\n"
        "DONE_%=:\n"
        "}\n" :: "r"(b0), "r"(p0), "r"(b1), "r"(p1) : "memory");
}
#define HINTA ""
__device__ __forceinline__ void mbar_wait_unless(uint32_t ok, uint32_t bar, uint32_t parity) {
    asm volatile(
        "{\n"
        ".reg .pred p;\n"
        ".reg .u32 n;\n"
        "setp.ne.u32 p, %2, 0;\n"
        "vote.sync.all.pred p, p, 0xffffffff;\n"
        "@p bra DONE_%=;\n"
        "mov.u32 n, 0;\n"
        "WAIT_%=:\n"
        "mbarrier.try_wait.parity.shared::cta.b64 p, [%0], %1" HINTA ";\n"
        "@p bra DONE_%=;\n"
        "add.u32 n, n, 1;\n"
        "setp.lt.u32 p, n, 4194304;\n"
        "@p bra WAIT_%=;\n"
        "trap;\n"
        "DONE_%=:\n"
        "}\n" :: "r"(bar), "r"(parity), "r"(ok) : "memory");
}
__device__ __forceinline__ void mbar_wait2_unless(uint32_t ok, uint32_t b0, uint32_t p0, uint32_t b1, uint32_t p1) {
    asm volatile(
        "{\n"
        ".reg .pred p, q;\n"
        ".reg .u32 n;\n"
        "setp.ne.u32 p, %4, 0;\n"
        "vote.sync.all.pred p, p, 0xffffffff;\n"
        "@p bra DONE_%=;\n"
        "mov.u32 n, 0;\n"
        "WAIT_%=:\n"
        "mbarrier.try_wait.parity.shared::cta.b64 p, [%0], %1" HINT ";\n"
        "mbarrier.try_wait.parity.shared::cta.b64 q, [%2], %3" HINT ";\n"
        "and.pred p, p, q;\n"
        "@p bra DONE_%=;\n"
        "add.u32 n, n, 1;\n"
        "setp.lt.u32 p, n, 4194304;\n"
        "@p bra WAIT_%=;\n"
        "trap;\n"
        "DONE_%=:\n"
        "}\n" :: "r"(b0), "r"(p0), "r"(b1), "r"(p1), "r"(ok) : "memory");
}
__device__ __forceinline__ void mbar_wait4_unless(uint32_t ok, uint32_t b0, uint32_t p0, uint32_t b1, uint32_t p1, uint32_t b2,
                                                  uint32_t p2, uint32_t b3, uint32_t p3) {
    asm volatile(
        "{\n"
        ".reg .pred p, q, r, s;\n"
        ".reg .u32 n;\n"
        "setp.ne.u32 p, %8, 0;\n"
        "vote.sync.all.pred p, p, 0xffffffff;\n"
        "@p bra DONE_%=;\n"
        "mov.u32 n, 0;\n"
        "WAIT_%=:\n"
        "mbarrier.try_wait.parity.shared::cta.b64 p, [%0], %1" HINT ";\n"
        "mbarrier.try_wait.parity.shared::cta.b64 q, [%2], %3" HINT ";\n"
        "mbarrier.try_wait.parity.shared::cta.b64 r, [%4], %5" HINT ";\n"
        "mbarrier.try_wait.parity.shared::cta.b64 s, [%6], %7" HINT ";\n"
        "and.pred p, p, q;\n"
        "and.pred r, r, s;\n"
        "and.pred p, p, r;\n"
        "@p bra DONE_%=;\n"
        "add.u32 n, n, 1;\n"
        "setp.lt.u32 p, n, 4194304;\n"
        "@p bra WAIT_%=;\n"
        "trap;\n"
        "DONE_%=:\n"
        "}\n" :: "r"(b0), "r"(p0), "r"(b1), "r"(p1), "r"(b2), "r"(p2), "r"(b3), "r"(p3), "r"(ok) : "memory");
}
__device__ __forceinline__ void sched_fence(uint32_t zero, uint32_t a, uint32_t b, uint32_t c, uint32_t d, uint32_t e = 0,
                                            uint32_t f = 0, uint32_t g = 0, uint32_t h = 0, uint32_t i = 0, uint32_t j = 0,
                                            uint32_t k = 0) {
    asm volatile("{\n.reg .pred p;\n.reg .u32 n;\nsetp.eq.u32 p, %0, 0;\n@p bra.uni DONE_%=;\nmov.u32 n, %0;\nSPIN_%=:\n"
                 "nanosleep.u32 %1;\nnanosleep.u32 %2;\nnanosleep.u32 %3;\nnanosleep.u32 %4;\nnanosleep.u32 %5;\n"
                 "nanosleep.u32 %6;\nnanosleep.u32 %7;\nnanosleep.u32 %8;\nnanosleep.u32 %9;\nnanosleep.u32 %10;\n"
                 "nanosleep.u32 %11;\nsub.u32 n, n, 1;\nsetp.ne.u32 p, n, 0;\n@p bra.uni SPIN_%=;\nDONE_%=:\n}\n"
                 :: "r"(zero), "r"(a), "r"(b), "r"(c), "r"(d), "r"(e), "r"(f), "r"(g), "r"(h), "r"(i), "r"(j), "r"(k) : "memory");
}
__device__ __forceinline__ void sched_fence2(uint32_t zero, float& x, float& y, uint32_t a, uint32_t b, uint32_t c, uint32_t d = 0,
                                             uint32_t e = 0, uint32_t f = 0) {
    asm volatile("{\n.reg .pred p;\n.reg .u32 n;\nsetp.eq.u32 p, %2, 0;\n@p bra.uni DONE_%=;\nmov.u32 n, %2;\nSPIN_%=:\n"
                 "add.f32 %0, %0, %1;\nadd.f32 %1, %1, %0;\nnanosleep.u32 %3;\nnanosleep.u32 %4;\nnanosleep.u32 %5;\n"
                 "nanosleep.u32 %6;\nnanosleep.u32 %7;\nnanosleep.u32 %8;\n"
                 "sub.u32 n, n, 1;\nsetp.ne.u32 p, n, 0;\n@p bra.uni SPIN_%=;\nDONE_%=:\n}\n"
                 : "+f"(x), "+f"(y) : "r"(zero), "r"(a), "r"(b), "r"(c), "r"(d), "r"(e), "r"(f) : "memory");
}
template <int N> __device__ __forceinline__ void use_regs(const uint32_t* v) {
    if constexpr (N >= 4) {
        asm volatile("nanosleep.u32 %0;\nnanosleep.u32 %1;\nnanosleep.u32 %2;\nnanosleep.u32 %3;\n" :: "r"(v[0]), "r"(v[1]), "r"(v[2]), "r"(v[3]) : "memory");
        use_regs<N - 4>(v + 4);
    } else if constexpr (N > 0) {
        asm volatile("nanosleep.u32 %0;\n" :: "r"(v[0]) : "memory");
        use_regs<N - 1>(v + 1);
    }
}
template <int N> __device__ __forceinline__ void sched_fence_n(uint32_t zero, const uint32_t (&v)[N]) {
    if (__builtin_expect(zero != 0, 0)) {
#pragma unroll 1
        for (uint32_t n = zero; n; n--) use_regs<N>(v);
    }
}
__device__ __forceinline__ void sched_fence_rw(uint32_t zero, uint32_t (&v)[13]) {
    asm volatile("{\n.reg .pred p;\n.reg .u32 n;\nsetp.eq.u32 p, %13, 0;\n@p bra.uni DONE_%=;\nmov.u32 n, %13;\nSPIN_%=:\n"
                 "add.u32 %0, %0, %1;\nadd.u32 %1, %1, %2;\nadd.u32 %2, %2, %3;\nadd.u32 %3, %3, %4;\nadd.u32 %4, %4, %5;\n"
                 "add.u32 %5, %5, %6;\nadd.u32 %6, %6, %7;\nadd.u32 %7, %7, %8;\nadd.u32 %8, %8, %9;\nadd.u32 %9, %9, %10;\n"
                 "add.u32 %10, %10, %11;\nadd.u32 %11, %11, %12;\nadd.u32 %12, %12, %0;\n"
                 "sub.u32 n, n, 1;\nsetp.ne.u32 p, n, 0;\n@p bra.uni SPIN_%=;\nDONE_%=:\n}\n"
                 : "+r"(v[0]), "+r"(v[1]), "+r"(v[2]), "+r"(v[3]), "+r"(v[4]), "+r"(v[5]), "+r"(v[6]), "+r"(v[7]), "+r"(v[8]),
                   "+r"(v[9]), "+r"(v[10]), "+r"(v[11]), "+r"(v[12]) : "r"(zero) : "memory");
}
__device__ __forceinline__ void mbar_arrive(uint32_t bar) {
    asm volatile("mbarrier.arrive.shared::cta.b64 _, [%0];\n" :: "r"(bar) : "memory");
}
__device__ __forceinline__ void mbar_arrive_n(uint32_t bar, uint32_t n) {
    asm volatile("mbarrier.arrive.shared::cta.b64 _, [%0], %1;\n" :: "r"(bar), "r"(n) : "memory");
}
__device__ __forceinline__ void mbar_arrive_expect_tx(uint32_t bar, uint32_t bytes) {
    asm volatile("mbarrier.arrive.expect_tx.shared::cta.b64 _, [%0], %1;\n" :: "r"(bar), "r"(bytes) : "memory");
}
__device__ __forceinline__ void stg128_if(bool p, void* addr, uint32_t x, uint32_t y, uint32_t z, uint32_t w) {
    asm volatile("{\n.reg .pred q;\nsetp.ne.b32 q, %5, 0;\n@q st.global.L1::no_allocate.v4.b32 [%0], {%1, %2, %3, %4};\n}\n"
                 :: "l"(addr), "r"(x), "r"(y), "r"(z), "r"(w), "r"((uint32_t)p) : "memory");
}
__device__ __forceinline__ void stsm_x4(uint32_t addr, uint32_t r0, uint32_t r1, uint32_t r2, uint32_t r3) {
    asm volatile("stmatrix.sync.aligned.m8n8.x4.shared.b16 [%0], {%1, %2, %3, %4};\n"
                 :: "r"(addr), "r"(r0), "r"(r1), "r"(r2), "r"(r3) : "memory");
}
__device__ __forceinline__ void stsm_x2(uint32_t addr, uint32_t r0, uint32_t r1) {
    asm volatile("stmatrix.sync.aligned.m8n8.x2.shared.b16 [%0], {%1, %2};\n" :: "r"(addr), "r"(r0), "r"(r1) : "memory");
}
__device__ __forceinline__ void sts128(uint32_t addr, uint32_t r0, uint32_t r1, uint32_t r2, uint32_t r3) {
    asm volatile("st.shared.v4.b32 [%0], {%1, %2, %3, %4};\n" :: "r"(addr), "r"(r0), "r"(r1), "r"(r2), "r"(r3) : "memory");
}
__device__ __forceinline__ void sts128_if(uint32_t p, uint32_t addr, uint32_t r0, uint32_t r1, uint32_t r2, uint32_t r3) {
    asm volatile("{\n.reg .pred q;\nsetp.ne.b32 q, %5, 0;\n@q st.shared.v4.b32 [%0], {%1, %2, %3, %4};\n}\n"
                 :: "r"(addr), "r"(r0), "r"(r1), "r"(r2), "r"(r3), "r"(p) : "memory");
}
__device__ __forceinline__ void sts32(uint32_t addr, uint32_t v) {
    asm volatile("st.shared.b32 [%0], %1;\n" :: "r"(addr), "r"(v) : "memory");
}
__device__ __forceinline__ uint32_t lds32(uint32_t addr) {
    uint32_t v;
    asm volatile("ld.shared.b32 %0, [%1];\n" : "=r"(v) : "r"(addr) : "memory");
    return v;
}
__device__ __forceinline__ void ldg_nc_v4(uint32_t (&r)[4], const void* p) {
    asm volatile("ld.global.nc.L1::no_allocate.v4.u32 {%0, %1, %2, %3}, [%4];\n"
                 : "=r"(r[0]), "=r"(r[1]), "=r"(r[2]), "=r"(r[3]) : "l"(p));
}
__device__ __forceinline__ uint32_t ldg_u32(const void* p) {
    uint32_t v;
    asm volatile("ld.global.nc.L1::evict_first.u32 %0, [%1];\n" : "=r"(v) : "l"(p));
    return v;
}
__device__ __forceinline__ void ldg_u64(const void* p, uint32_t& a, uint32_t& b) {
    asm volatile("ld.global.nc.L1::evict_first.v2.u32 {%0, %1}, [%2];\n" : "=r"(a), "=r"(b) : "l"(p));
}
__device__ __forceinline__ void prefetch_l2(const void* p) {
    asm volatile("prefetch.global.L2 [%0];\n" :: "l"(p));
}
__device__ __forceinline__ void cp_async16(uint32_t dst, const void* src) {
    asm volatile("cp.async.cg.shared.global [%0], [%1], 16;\n" :: "r"(dst), "l"(src) : "memory");
}
__device__ __forceinline__ float ex2_ftz(float x) {
    float y;
    asm("ex2.approx.ftz.f32 %0, %1;\n" : "=f"(y) : "f"(x));
    return y;
}
__device__ __forceinline__ float lg2_ftz(float x) {
    float y;
    asm("lg2.approx.ftz.f32 %0, %1;\n" : "=f"(y) : "f"(x));
    return y;
}
__device__ __forceinline__ float rcp_ftz(float x) {
    float y;
    asm("rcp.approx.ftz.f32 %0, %1;\n" : "=f"(y) : "f"(x));
    return y;
}
__device__ __forceinline__ float rsqrt_ftz(float x) {
    float y;
    asm("rsqrt.approx.ftz.f32 %0, %1;\n" : "=f"(y) : "f"(x));
    return y;
}

__device__ __forceinline__ bool elect_one() {
    uint32_t p;
    asm volatile("{\n.reg .pred q;\nelect.sync _|q, 0xffffffff;\nselp.u32 %0, 1, 0, q;\n}\n" : "=r"(p));
    return p != 0;
}
__device__ __forceinline__ void ldsm_x4(uint32_t (&r)[4], uint32_t addr) {
    asm volatile("ldmatrix.sync.aligned.m8n8.x4.shared.b16 {%0, %1, %2, %3}, [%4];\n"
                 : "=r"(r[0]), "=r"(r[1]), "=r"(r[2]), "=r"(r[3]) : "r"(addr) : "memory");
}
__device__ __forceinline__ void ldsm_x2(uint32_t& r0, uint32_t& r1, uint32_t addr) {
    asm volatile("ldmatrix.sync.aligned.m8n8.x2.shared.b16 {%0, %1}, [%2];\n" : "=r"(r0), "=r"(r1) : "r"(addr) : "memory");
}
__device__ __forceinline__ void tma_2d(uint32_t dst, const CUtensorMap* map, uint32_t bar, int c0, int c1) {
    asm volatile("cp.async.bulk.tensor.2d.shared::cluster.global.mbarrier::complete_tx::bytes [%0], [%1, {%3, %4}], [%2];\n"
                 :: "r"(dst), "l"(reinterpret_cast<uint64_t>(map)), "r"(bar), "r"(c0), "r"(c1) : "memory");
}
__device__ __forceinline__ void tma_3d(uint32_t dst, const CUtensorMap* map, uint32_t bar, int c0, int c1, int c2) {
    asm volatile("cp.async.bulk.tensor.3d.shared::cluster.global.mbarrier::complete_tx::bytes [%0], [%1, {%3, %4, %5}], [%2];\n"
                 :: "r"(dst), "l"(reinterpret_cast<uint64_t>(map)), "r"(bar), "r"(c0), "r"(c1), "r"(c2) : "memory");
}
constexpr uint64_t EVICT_FIRST = 0x12F0000000000000ull;
__device__ __forceinline__ void tma_3d_x(uint32_t dst, const CUtensorMap* map, uint32_t bar, int c0, int c1, int c2) {
    if (CH & 50)
        asm volatile("cp.async.bulk.tensor.3d.shared::cluster.global.mbarrier::complete_tx::bytes.L2::cache_hint [%0], [%1, {%3, %4, %5}], [%2], %6;\n"
                     :: "r"(dst), "l"(reinterpret_cast<uint64_t>(map)), "r"(bar), "r"(c0), "r"(c1), "r"(c2),
                        "l"((CH & 2) || (blockIdx.x & 1) == ((CH >> 5) & 1) ? EVICT_FIRST : 0x1000000000000000ull) : "memory");
    else tma_3d(dst, map, bar, c0, c1, c2);
}
__device__ __forceinline__ void tma_store_4d(const CUtensorMap* map, uint32_t src, int c0, int c1, int c2, int c3) {
    asm volatile("cp.async.bulk.tensor.4d.global.shared::cta.tile.bulk_group [%0, {%2, %3, %4, %5}], [%1];\n"
                 :: "l"(reinterpret_cast<uint64_t>(map)), "r"(src), "r"(c0), "r"(c1), "r"(c2), "r"(c3) : "memory");
}
__device__ __forceinline__ void mbar_arrive_if(uint32_t bar, uint32_t cnt) {
    asm volatile("{\n.reg .pred q;\nsetp.ne.b32 q, %1, 0;\n@q mbarrier.arrive.shared::cta.b64 _, [%0], %1;\n}\n"
                 :: "r"(bar), "r"(cnt) : "memory");
}

template <int BOFF, int AOFF, int NA>
__device__ __forceinline__ void mma_qkv_a(float (&d)[48], const uint32_t (&a)[NA][4], uint64_t descB) {
    asm volatile(
        "{\n"
        ".reg .pred p0, p1;\n"
        ".reg .b64 ta, ta0, tb, tb0;\n"
        "setp.ne.b32 p0, 0, 0;\n"
        "setp.eq.b32 p1, 0, 0;\n"
        "add.s64 tb0, %72, %73;\n"
        "add.s64 tb, tb0, 0;\n"
        "wgmma.mma_async.sync.aligned.m64n96k16.f32.bf16.bf16 {%0, %1, %2, %3, %4, %5, %6, %7, %8, %9, %10, %11, %12, %13, %14, %15, %16, %17, %18, %19, %20, %21, %22, %23, %24, %25, %26, %27, %28, %29, %30, %31, %32, %33, %34, %35, %36, %37, %38, %39, %40, %41, %42, %43, %44, %45, %46, %47}, {%48, %49, %50, %51}, tb, p0, 1, 1, 1;\n"
        "add.s64 tb, tb0, 32;\n"
        "wgmma.mma_async.sync.aligned.m64n96k16.f32.bf16.bf16 {%0, %1, %2, %3, %4, %5, %6, %7, %8, %9, %10, %11, %12, %13, %14, %15, %16, %17, %18, %19, %20, %21, %22, %23, %24, %25, %26, %27, %28, %29, %30, %31, %32, %33, %34, %35, %36, %37, %38, %39, %40, %41, %42, %43, %44, %45, %46, %47}, {%52, %53, %54, %55}, tb, p1, 1, 1, 1;\n"
        "add.s64 tb, tb0, 64;\n"
        "wgmma.mma_async.sync.aligned.m64n96k16.f32.bf16.bf16 {%0, %1, %2, %3, %4, %5, %6, %7, %8, %9, %10, %11, %12, %13, %14, %15, %16, %17, %18, %19, %20, %21, %22, %23, %24, %25, %26, %27, %28, %29, %30, %31, %32, %33, %34, %35, %36, %37, %38, %39, %40, %41, %42, %43, %44, %45, %46, %47}, {%56, %57, %58, %59}, tb, p1, 1, 1, 1;\n"
        "add.s64 tb, tb0, 96;\n"
        "wgmma.mma_async.sync.aligned.m64n96k16.f32.bf16.bf16 {%0, %1, %2, %3, %4, %5, %6, %7, %8, %9, %10, %11, %12, %13, %14, %15, %16, %17, %18, %19, %20, %21, %22, %23, %24, %25, %26, %27, %28, %29, %30, %31, %32, %33, %34, %35, %36, %37, %38, %39, %40, %41, %42, %43, %44, %45, %46, %47}, {%60, %61, %62, %63}, tb, p1, 1, 1, 1;\n"
        "add.s64 tb, tb0, 1536;\n"
        "wgmma.mma_async.sync.aligned.m64n96k16.f32.bf16.bf16 {%0, %1, %2, %3, %4, %5, %6, %7, %8, %9, %10, %11, %12, %13, %14, %15, %16, %17, %18, %19, %20, %21, %22, %23, %24, %25, %26, %27, %28, %29, %30, %31, %32, %33, %34, %35, %36, %37, %38, %39, %40, %41, %42, %43, %44, %45, %46, %47}, {%64, %65, %66, %67}, tb, p1, 1, 1, 1;\n"
        "add.s64 tb, tb0, 1568;\n"
        "wgmma.mma_async.sync.aligned.m64n96k16.f32.bf16.bf16 {%0, %1, %2, %3, %4, %5, %6, %7, %8, %9, %10, %11, %12, %13, %14, %15, %16, %17, %18, %19, %20, %21, %22, %23, %24, %25, %26, %27, %28, %29, %30, %31, %32, %33, %34, %35, %36, %37, %38, %39, %40, %41, %42, %43, %44, %45, %46, %47}, {%68, %69, %70, %71}, tb, p1, 1, 1, 1;\n"
        "}\n"
        : "=f"(d[0]), "=f"(d[1]), "=f"(d[2]), "=f"(d[3]), "=f"(d[4]), "=f"(d[5]), "=f"(d[6]), "=f"(d[7]), "=f"(d[8]), "=f"(d[9]), "=f"(d[10]), "=f"(d[11]), "=f"(d[12]), "=f"(d[13]), "=f"(d[14]), "=f"(d[15]), "=f"(d[16]), "=f"(d[17]), "=f"(d[18]), "=f"(d[19]), "=f"(d[20]), "=f"(d[21]), "=f"(d[22]), "=f"(d[23]), "=f"(d[24]), "=f"(d[25]), "=f"(d[26]), "=f"(d[27]), "=f"(d[28]), "=f"(d[29]), "=f"(d[30]), "=f"(d[31]), "=f"(d[32]), "=f"(d[33]), "=f"(d[34]), "=f"(d[35]), "=f"(d[36]), "=f"(d[37]), "=f"(d[38]), "=f"(d[39]), "=f"(d[40]), "=f"(d[41]), "=f"(d[42]), "=f"(d[43]), "=f"(d[44]), "=f"(d[45]), "=f"(d[46]), "=f"(d[47])
        : "r"(a[AOFF + 0][0]), "r"(a[AOFF + 0][1]), "r"(a[AOFF + 0][2]), "r"(a[AOFF + 0][3]), "r"(a[AOFF + 1][0]), "r"(a[AOFF + 1][1]), "r"(a[AOFF + 1][2]), "r"(a[AOFF + 1][3]), "r"(a[AOFF + 2][0]), "r"(a[AOFF + 2][1]), "r"(a[AOFF + 2][2]), "r"(a[AOFF + 2][3]), "r"(a[AOFF + 3][0]), "r"(a[AOFF + 3][1]), "r"(a[AOFF + 3][2]), "r"(a[AOFF + 3][3]), "r"(a[AOFF + 4][0]), "r"(a[AOFF + 4][1]), "r"(a[AOFF + 4][2]), "r"(a[AOFF + 4][3]), "r"(a[AOFF + 5][0]), "r"(a[AOFF + 5][1]), "r"(a[AOFF + 5][2]), "r"(a[AOFF + 5][3]), "l"(descB), "n"(BOFF >> 4));
}

template <int BOFF, int AOFF, int NA>
__device__ __forceinline__ void mma_qkv_b(float (&d)[48], const uint32_t (&a)[NA][4], uint64_t descB) {
    asm volatile(
        "{\n"
        ".reg .pred p0, p1;\n"
        ".reg .b64 ta, ta0, tb, tb0;\n"
        "setp.ne.b32 p0, 0, 0;\n"
        "setp.eq.b32 p1, 0, 0;\n"
        "add.s64 tb0, %72, %73;\n"
        "add.s64 tb, tb0, 1600;\n"
        "wgmma.mma_async.sync.aligned.m64n96k16.f32.bf16.bf16 {%0, %1, %2, %3, %4, %5, %6, %7, %8, %9, %10, %11, %12, %13, %14, %15, %16, %17, %18, %19, %20, %21, %22, %23, %24, %25, %26, %27, %28, %29, %30, %31, %32, %33, %34, %35, %36, %37, %38, %39, %40, %41, %42, %43, %44, %45, %46, %47}, {%48, %49, %50, %51}, tb, p1, 1, 1, 1;\n"
        "add.s64 tb, tb0, 1632;\n"
        "wgmma.mma_async.sync.aligned.m64n96k16.f32.bf16.bf16 {%0, %1, %2, %3, %4, %5, %6, %7, %8, %9, %10, %11, %12, %13, %14, %15, %16, %17, %18, %19, %20, %21, %22, %23, %24, %25, %26, %27, %28, %29, %30, %31, %32, %33, %34, %35, %36, %37, %38, %39, %40, %41, %42, %43, %44, %45, %46, %47}, {%52, %53, %54, %55}, tb, p1, 1, 1, 1;\n"
        "add.s64 tb, tb0, 3072;\n"
        "wgmma.mma_async.sync.aligned.m64n96k16.f32.bf16.bf16 {%0, %1, %2, %3, %4, %5, %6, %7, %8, %9, %10, %11, %12, %13, %14, %15, %16, %17, %18, %19, %20, %21, %22, %23, %24, %25, %26, %27, %28, %29, %30, %31, %32, %33, %34, %35, %36, %37, %38, %39, %40, %41, %42, %43, %44, %45, %46, %47}, {%56, %57, %58, %59}, tb, p1, 1, 1, 1;\n"
        "add.s64 tb, tb0, 3104;\n"
        "wgmma.mma_async.sync.aligned.m64n96k16.f32.bf16.bf16 {%0, %1, %2, %3, %4, %5, %6, %7, %8, %9, %10, %11, %12, %13, %14, %15, %16, %17, %18, %19, %20, %21, %22, %23, %24, %25, %26, %27, %28, %29, %30, %31, %32, %33, %34, %35, %36, %37, %38, %39, %40, %41, %42, %43, %44, %45, %46, %47}, {%60, %61, %62, %63}, tb, p1, 1, 1, 1;\n"
        "add.s64 tb, tb0, 3136;\n"
        "wgmma.mma_async.sync.aligned.m64n96k16.f32.bf16.bf16 {%0, %1, %2, %3, %4, %5, %6, %7, %8, %9, %10, %11, %12, %13, %14, %15, %16, %17, %18, %19, %20, %21, %22, %23, %24, %25, %26, %27, %28, %29, %30, %31, %32, %33, %34, %35, %36, %37, %38, %39, %40, %41, %42, %43, %44, %45, %46, %47}, {%64, %65, %66, %67}, tb, p1, 1, 1, 1;\n"
        "add.s64 tb, tb0, 3168;\n"
        "wgmma.mma_async.sync.aligned.m64n96k16.f32.bf16.bf16 {%0, %1, %2, %3, %4, %5, %6, %7, %8, %9, %10, %11, %12, %13, %14, %15, %16, %17, %18, %19, %20, %21, %22, %23, %24, %25, %26, %27, %28, %29, %30, %31, %32, %33, %34, %35, %36, %37, %38, %39, %40, %41, %42, %43, %44, %45, %46, %47}, {%68, %69, %70, %71}, tb, p1, 1, 1, 1;\n"
        "}\n"
        : "+f"(d[0]), "+f"(d[1]), "+f"(d[2]), "+f"(d[3]), "+f"(d[4]), "+f"(d[5]), "+f"(d[6]), "+f"(d[7]), "+f"(d[8]), "+f"(d[9]), "+f"(d[10]), "+f"(d[11]), "+f"(d[12]), "+f"(d[13]), "+f"(d[14]), "+f"(d[15]), "+f"(d[16]), "+f"(d[17]), "+f"(d[18]), "+f"(d[19]), "+f"(d[20]), "+f"(d[21]), "+f"(d[22]), "+f"(d[23]), "+f"(d[24]), "+f"(d[25]), "+f"(d[26]), "+f"(d[27]), "+f"(d[28]), "+f"(d[29]), "+f"(d[30]), "+f"(d[31]), "+f"(d[32]), "+f"(d[33]), "+f"(d[34]), "+f"(d[35]), "+f"(d[36]), "+f"(d[37]), "+f"(d[38]), "+f"(d[39]), "+f"(d[40]), "+f"(d[41]), "+f"(d[42]), "+f"(d[43]), "+f"(d[44]), "+f"(d[45]), "+f"(d[46]), "+f"(d[47])
        : "r"(a[AOFF + 0][0]), "r"(a[AOFF + 0][1]), "r"(a[AOFF + 0][2]), "r"(a[AOFF + 0][3]), "r"(a[AOFF + 1][0]), "r"(a[AOFF + 1][1]), "r"(a[AOFF + 1][2]), "r"(a[AOFF + 1][3]), "r"(a[AOFF + 2][0]), "r"(a[AOFF + 2][1]), "r"(a[AOFF + 2][2]), "r"(a[AOFF + 2][3]), "r"(a[AOFF + 3][0]), "r"(a[AOFF + 3][1]), "r"(a[AOFF + 3][2]), "r"(a[AOFF + 3][3]), "r"(a[AOFF + 4][0]), "r"(a[AOFF + 4][1]), "r"(a[AOFF + 4][2]), "r"(a[AOFF + 4][3]), "r"(a[AOFF + 5][0]), "r"(a[AOFF + 5][1]), "r"(a[AOFF + 5][2]), "r"(a[AOFF + 5][3]), "l"(descB), "n"(BOFF >> 4));
}

template <int BOFF, int AOFF, int NA>
__device__ __forceinline__ void mma_v_a(float (&d)[48], const uint32_t (&a)[NA][4], uint64_t descB) {
    asm volatile(
        "{\n"
        ".reg .pred p0, p1;\n"
        ".reg .b64 ta, ta0, tb, tb0;\n"
        "setp.ne.b32 p0, 0, 0;\n"
        "setp.eq.b32 p1, 0, 0;\n"
        "add.s64 tb0, %72, %73;\n"
        "add.s64 tb, tb0, 0;\n"
        "wgmma.mma_async.sync.aligned.m64n96k16.f32.bf16.bf16 {%0, %1, %2, %3, %4, %5, %6, %7, %8, %9, %10, %11, %12, %13, %14, %15, %16, %17, %18, %19, %20, %21, %22, %23, %24, %25, %26, %27, %28, %29, %30, %31, %32, %33, %34, %35, %36, %37, %38, %39, %40, %41, %42, %43, %44, %45, %46, %47}, {%48, %49, %50, %51}, tb, p0, 1, 1, 1;\n"
        "add.s64 tb, tb0, 32;\n"
        "wgmma.mma_async.sync.aligned.m64n96k16.f32.bf16.bf16 {%0, %1, %2, %3, %4, %5, %6, %7, %8, %9, %10, %11, %12, %13, %14, %15, %16, %17, %18, %19, %20, %21, %22, %23, %24, %25, %26, %27, %28, %29, %30, %31, %32, %33, %34, %35, %36, %37, %38, %39, %40, %41, %42, %43, %44, %45, %46, %47}, {%52, %53, %54, %55}, tb, p1, 1, 1, 1;\n"
        "add.s64 tb, tb0, 64;\n"
        "wgmma.mma_async.sync.aligned.m64n96k16.f32.bf16.bf16 {%0, %1, %2, %3, %4, %5, %6, %7, %8, %9, %10, %11, %12, %13, %14, %15, %16, %17, %18, %19, %20, %21, %22, %23, %24, %25, %26, %27, %28, %29, %30, %31, %32, %33, %34, %35, %36, %37, %38, %39, %40, %41, %42, %43, %44, %45, %46, %47}, {%56, %57, %58, %59}, tb, p1, 1, 1, 1;\n"
        "add.s64 tb, tb0, 96;\n"
        "wgmma.mma_async.sync.aligned.m64n96k16.f32.bf16.bf16 {%0, %1, %2, %3, %4, %5, %6, %7, %8, %9, %10, %11, %12, %13, %14, %15, %16, %17, %18, %19, %20, %21, %22, %23, %24, %25, %26, %27, %28, %29, %30, %31, %32, %33, %34, %35, %36, %37, %38, %39, %40, %41, %42, %43, %44, %45, %46, %47}, {%60, %61, %62, %63}, tb, p1, 1, 1, 1;\n"
        "add.s64 tb, tb0, 128;\n"
        "wgmma.mma_async.sync.aligned.m64n96k16.f32.bf16.bf16 {%0, %1, %2, %3, %4, %5, %6, %7, %8, %9, %10, %11, %12, %13, %14, %15, %16, %17, %18, %19, %20, %21, %22, %23, %24, %25, %26, %27, %28, %29, %30, %31, %32, %33, %34, %35, %36, %37, %38, %39, %40, %41, %42, %43, %44, %45, %46, %47}, {%64, %65, %66, %67}, tb, p1, 1, 1, 1;\n"
        "add.s64 tb, tb0, 160;\n"
        "wgmma.mma_async.sync.aligned.m64n96k16.f32.bf16.bf16 {%0, %1, %2, %3, %4, %5, %6, %7, %8, %9, %10, %11, %12, %13, %14, %15, %16, %17, %18, %19, %20, %21, %22, %23, %24, %25, %26, %27, %28, %29, %30, %31, %32, %33, %34, %35, %36, %37, %38, %39, %40, %41, %42, %43, %44, %45, %46, %47}, {%68, %69, %70, %71}, tb, p1, 1, 1, 1;\n"
        "}\n"
        : "=f"(d[0]), "=f"(d[1]), "=f"(d[2]), "=f"(d[3]), "=f"(d[4]), "=f"(d[5]), "=f"(d[6]), "=f"(d[7]), "=f"(d[8]), "=f"(d[9]), "=f"(d[10]), "=f"(d[11]), "=f"(d[12]), "=f"(d[13]), "=f"(d[14]), "=f"(d[15]), "=f"(d[16]), "=f"(d[17]), "=f"(d[18]), "=f"(d[19]), "=f"(d[20]), "=f"(d[21]), "=f"(d[22]), "=f"(d[23]), "=f"(d[24]), "=f"(d[25]), "=f"(d[26]), "=f"(d[27]), "=f"(d[28]), "=f"(d[29]), "=f"(d[30]), "=f"(d[31]), "=f"(d[32]), "=f"(d[33]), "=f"(d[34]), "=f"(d[35]), "=f"(d[36]), "=f"(d[37]), "=f"(d[38]), "=f"(d[39]), "=f"(d[40]), "=f"(d[41]), "=f"(d[42]), "=f"(d[43]), "=f"(d[44]), "=f"(d[45]), "=f"(d[46]), "=f"(d[47])
        : "r"(a[AOFF + 0][0]), "r"(a[AOFF + 0][1]), "r"(a[AOFF + 0][2]), "r"(a[AOFF + 0][3]), "r"(a[AOFF + 1][0]), "r"(a[AOFF + 1][1]), "r"(a[AOFF + 1][2]), "r"(a[AOFF + 1][3]), "r"(a[AOFF + 2][0]), "r"(a[AOFF + 2][1]), "r"(a[AOFF + 2][2]), "r"(a[AOFF + 2][3]), "r"(a[AOFF + 3][0]), "r"(a[AOFF + 3][1]), "r"(a[AOFF + 3][2]), "r"(a[AOFF + 3][3]), "r"(a[AOFF + 4][0]), "r"(a[AOFF + 4][1]), "r"(a[AOFF + 4][2]), "r"(a[AOFF + 4][3]), "r"(a[AOFF + 5][0]), "r"(a[AOFF + 5][1]), "r"(a[AOFF + 5][2]), "r"(a[AOFF + 5][3]), "l"(descB), "n"(BOFF >> 4));
}

template <int BOFF, int AOFF, int NA>
__device__ __forceinline__ void mma_v_b(float (&d)[48], const uint32_t (&a)[NA][4], uint64_t descB) {
    asm volatile(
        "{\n"
        ".reg .pred p0, p1;\n"
        ".reg .b64 ta, ta0, tb, tb0;\n"
        "setp.ne.b32 p0, 0, 0;\n"
        "setp.eq.b32 p1, 0, 0;\n"
        "add.s64 tb0, %72, %73;\n"
        "add.s64 tb, tb0, 192;\n"
        "wgmma.mma_async.sync.aligned.m64n96k16.f32.bf16.bf16 {%0, %1, %2, %3, %4, %5, %6, %7, %8, %9, %10, %11, %12, %13, %14, %15, %16, %17, %18, %19, %20, %21, %22, %23, %24, %25, %26, %27, %28, %29, %30, %31, %32, %33, %34, %35, %36, %37, %38, %39, %40, %41, %42, %43, %44, %45, %46, %47}, {%48, %49, %50, %51}, tb, p1, 1, 1, 1;\n"
        "add.s64 tb, tb0, 224;\n"
        "wgmma.mma_async.sync.aligned.m64n96k16.f32.bf16.bf16 {%0, %1, %2, %3, %4, %5, %6, %7, %8, %9, %10, %11, %12, %13, %14, %15, %16, %17, %18, %19, %20, %21, %22, %23, %24, %25, %26, %27, %28, %29, %30, %31, %32, %33, %34, %35, %36, %37, %38, %39, %40, %41, %42, %43, %44, %45, %46, %47}, {%52, %53, %54, %55}, tb, p1, 1, 1, 1;\n"
        "add.s64 tb, tb0, 256;\n"
        "wgmma.mma_async.sync.aligned.m64n96k16.f32.bf16.bf16 {%0, %1, %2, %3, %4, %5, %6, %7, %8, %9, %10, %11, %12, %13, %14, %15, %16, %17, %18, %19, %20, %21, %22, %23, %24, %25, %26, %27, %28, %29, %30, %31, %32, %33, %34, %35, %36, %37, %38, %39, %40, %41, %42, %43, %44, %45, %46, %47}, {%56, %57, %58, %59}, tb, p1, 1, 1, 1;\n"
        "add.s64 tb, tb0, 288;\n"
        "wgmma.mma_async.sync.aligned.m64n96k16.f32.bf16.bf16 {%0, %1, %2, %3, %4, %5, %6, %7, %8, %9, %10, %11, %12, %13, %14, %15, %16, %17, %18, %19, %20, %21, %22, %23, %24, %25, %26, %27, %28, %29, %30, %31, %32, %33, %34, %35, %36, %37, %38, %39, %40, %41, %42, %43, %44, %45, %46, %47}, {%60, %61, %62, %63}, tb, p1, 1, 1, 1;\n"
        "add.s64 tb, tb0, 320;\n"
        "wgmma.mma_async.sync.aligned.m64n96k16.f32.bf16.bf16 {%0, %1, %2, %3, %4, %5, %6, %7, %8, %9, %10, %11, %12, %13, %14, %15, %16, %17, %18, %19, %20, %21, %22, %23, %24, %25, %26, %27, %28, %29, %30, %31, %32, %33, %34, %35, %36, %37, %38, %39, %40, %41, %42, %43, %44, %45, %46, %47}, {%64, %65, %66, %67}, tb, p1, 1, 1, 1;\n"
        "add.s64 tb, tb0, 352;\n"
        "wgmma.mma_async.sync.aligned.m64n96k16.f32.bf16.bf16 {%0, %1, %2, %3, %4, %5, %6, %7, %8, %9, %10, %11, %12, %13, %14, %15, %16, %17, %18, %19, %20, %21, %22, %23, %24, %25, %26, %27, %28, %29, %30, %31, %32, %33, %34, %35, %36, %37, %38, %39, %40, %41, %42, %43, %44, %45, %46, %47}, {%68, %69, %70, %71}, tb, p1, 1, 1, 1;\n"
        "}\n"
        : "+f"(d[0]), "+f"(d[1]), "+f"(d[2]), "+f"(d[3]), "+f"(d[4]), "+f"(d[5]), "+f"(d[6]), "+f"(d[7]), "+f"(d[8]), "+f"(d[9]), "+f"(d[10]), "+f"(d[11]), "+f"(d[12]), "+f"(d[13]), "+f"(d[14]), "+f"(d[15]), "+f"(d[16]), "+f"(d[17]), "+f"(d[18]), "+f"(d[19]), "+f"(d[20]), "+f"(d[21]), "+f"(d[22]), "+f"(d[23]), "+f"(d[24]), "+f"(d[25]), "+f"(d[26]), "+f"(d[27]), "+f"(d[28]), "+f"(d[29]), "+f"(d[30]), "+f"(d[31]), "+f"(d[32]), "+f"(d[33]), "+f"(d[34]), "+f"(d[35]), "+f"(d[36]), "+f"(d[37]), "+f"(d[38]), "+f"(d[39]), "+f"(d[40]), "+f"(d[41]), "+f"(d[42]), "+f"(d[43]), "+f"(d[44]), "+f"(d[45]), "+f"(d[46]), "+f"(d[47])
        : "r"(a[AOFF + 0][0]), "r"(a[AOFF + 0][1]), "r"(a[AOFF + 0][2]), "r"(a[AOFF + 0][3]), "r"(a[AOFF + 1][0]), "r"(a[AOFF + 1][1]), "r"(a[AOFF + 1][2]), "r"(a[AOFF + 1][3]), "r"(a[AOFF + 2][0]), "r"(a[AOFF + 2][1]), "r"(a[AOFF + 2][2]), "r"(a[AOFF + 2][3]), "r"(a[AOFF + 3][0]), "r"(a[AOFF + 3][1]), "r"(a[AOFF + 3][2]), "r"(a[AOFF + 3][3]), "r"(a[AOFF + 4][0]), "r"(a[AOFF + 4][1]), "r"(a[AOFF + 4][2]), "r"(a[AOFF + 4][3]), "r"(a[AOFF + 5][0]), "r"(a[AOFF + 5][1]), "r"(a[AOFF + 5][2]), "r"(a[AOFF + 5][3]), "l"(descB), "n"(BOFF >> 4));
}

template <int BOFF, int AOFF, int NA>
__device__ __forceinline__ void mma_w_a(float (&d)[48], const uint32_t (&a)[NA][4], uint64_t descB) {
    asm volatile(
        "{\n"
        ".reg .pred p0, p1;\n"
        ".reg .b64 ta, ta0, tb, tb0;\n"
        "setp.ne.b32 p0, 0, 0;\n"
        "setp.eq.b32 p1, 0, 0;\n"
        "add.s64 tb0, %72, %73;\n"
        "add.s64 tb, tb0, 0;\n"
        "wgmma.mma_async.sync.aligned.m64n96k16.f32.bf16.bf16 {%0, %1, %2, %3, %4, %5, %6, %7, %8, %9, %10, %11, %12, %13, %14, %15, %16, %17, %18, %19, %20, %21, %22, %23, %24, %25, %26, %27, %28, %29, %30, %31, %32, %33, %34, %35, %36, %37, %38, %39, %40, %41, %42, %43, %44, %45, %46, %47}, {%48, %49, %50, %51}, tb, p0, 1, 1, 1;\n"
        "add.s64 tb, tb0, 64;\n"
        "wgmma.mma_async.sync.aligned.m64n96k16.f32.bf16.bf16 {%0, %1, %2, %3, %4, %5, %6, %7, %8, %9, %10, %11, %12, %13, %14, %15, %16, %17, %18, %19, %20, %21, %22, %23, %24, %25, %26, %27, %28, %29, %30, %31, %32, %33, %34, %35, %36, %37, %38, %39, %40, %41, %42, %43, %44, %45, %46, %47}, {%52, %53, %54, %55}, tb, p1, 1, 1, 1;\n"
        "add.s64 tb, tb0, 128;\n"
        "wgmma.mma_async.sync.aligned.m64n96k16.f32.bf16.bf16 {%0, %1, %2, %3, %4, %5, %6, %7, %8, %9, %10, %11, %12, %13, %14, %15, %16, %17, %18, %19, %20, %21, %22, %23, %24, %25, %26, %27, %28, %29, %30, %31, %32, %33, %34, %35, %36, %37, %38, %39, %40, %41, %42, %43, %44, %45, %46, %47}, {%56, %57, %58, %59}, tb, p1, 1, 1, 1;\n"
        "add.s64 tb, tb0, 192;\n"
        "wgmma.mma_async.sync.aligned.m64n96k16.f32.bf16.bf16 {%0, %1, %2, %3, %4, %5, %6, %7, %8, %9, %10, %11, %12, %13, %14, %15, %16, %17, %18, %19, %20, %21, %22, %23, %24, %25, %26, %27, %28, %29, %30, %31, %32, %33, %34, %35, %36, %37, %38, %39, %40, %41, %42, %43, %44, %45, %46, %47}, {%60, %61, %62, %63}, tb, p1, 1, 1, 1;\n"
        "add.s64 tb, tb0, 256;\n"
        "wgmma.mma_async.sync.aligned.m64n96k16.f32.bf16.bf16 {%0, %1, %2, %3, %4, %5, %6, %7, %8, %9, %10, %11, %12, %13, %14, %15, %16, %17, %18, %19, %20, %21, %22, %23, %24, %25, %26, %27, %28, %29, %30, %31, %32, %33, %34, %35, %36, %37, %38, %39, %40, %41, %42, %43, %44, %45, %46, %47}, {%64, %65, %66, %67}, tb, p1, 1, 1, 1;\n"
        "add.s64 tb, tb0, 320;\n"
        "wgmma.mma_async.sync.aligned.m64n96k16.f32.bf16.bf16 {%0, %1, %2, %3, %4, %5, %6, %7, %8, %9, %10, %11, %12, %13, %14, %15, %16, %17, %18, %19, %20, %21, %22, %23, %24, %25, %26, %27, %28, %29, %30, %31, %32, %33, %34, %35, %36, %37, %38, %39, %40, %41, %42, %43, %44, %45, %46, %47}, {%68, %69, %70, %71}, tb, p1, 1, 1, 1;\n"
        "}\n"
        : "=f"(d[0]), "=f"(d[1]), "=f"(d[2]), "=f"(d[3]), "=f"(d[4]), "=f"(d[5]), "=f"(d[6]), "=f"(d[7]), "=f"(d[8]), "=f"(d[9]), "=f"(d[10]), "=f"(d[11]), "=f"(d[12]), "=f"(d[13]), "=f"(d[14]), "=f"(d[15]), "=f"(d[16]), "=f"(d[17]), "=f"(d[18]), "=f"(d[19]), "=f"(d[20]), "=f"(d[21]), "=f"(d[22]), "=f"(d[23]), "=f"(d[24]), "=f"(d[25]), "=f"(d[26]), "=f"(d[27]), "=f"(d[28]), "=f"(d[29]), "=f"(d[30]), "=f"(d[31]), "=f"(d[32]), "=f"(d[33]), "=f"(d[34]), "=f"(d[35]), "=f"(d[36]), "=f"(d[37]), "=f"(d[38]), "=f"(d[39]), "=f"(d[40]), "=f"(d[41]), "=f"(d[42]), "=f"(d[43]), "=f"(d[44]), "=f"(d[45]), "=f"(d[46]), "=f"(d[47])
        : "r"(a[AOFF + 0][0]), "r"(a[AOFF + 0][1]), "r"(a[AOFF + 0][2]), "r"(a[AOFF + 0][3]), "r"(a[AOFF + 1][0]), "r"(a[AOFF + 1][1]), "r"(a[AOFF + 1][2]), "r"(a[AOFF + 1][3]), "r"(a[AOFF + 2][0]), "r"(a[AOFF + 2][1]), "r"(a[AOFF + 2][2]), "r"(a[AOFF + 2][3]), "r"(a[AOFF + 3][0]), "r"(a[AOFF + 3][1]), "r"(a[AOFF + 3][2]), "r"(a[AOFF + 3][3]), "r"(a[AOFF + 4][0]), "r"(a[AOFF + 4][1]), "r"(a[AOFF + 4][2]), "r"(a[AOFF + 4][3]), "r"(a[AOFF + 5][0]), "r"(a[AOFF + 5][1]), "r"(a[AOFF + 5][2]), "r"(a[AOFF + 5][3]), "l"(descB), "n"(BOFF >> 4));
}

template <int BOFF, int AOFF, int NA>
__device__ __forceinline__ void mma_w_b(float (&d)[48], const uint32_t (&a)[NA][4], uint64_t descB) {
    asm volatile(
        "{\n"
        ".reg .pred p0, p1;\n"
        ".reg .b64 ta, ta0, tb, tb0;\n"
        "setp.ne.b32 p0, 0, 0;\n"
        "setp.eq.b32 p1, 0, 0;\n"
        "add.s64 tb0, %72, %73;\n"
        "add.s64 tb, tb0, 384;\n"
        "wgmma.mma_async.sync.aligned.m64n96k16.f32.bf16.bf16 {%0, %1, %2, %3, %4, %5, %6, %7, %8, %9, %10, %11, %12, %13, %14, %15, %16, %17, %18, %19, %20, %21, %22, %23, %24, %25, %26, %27, %28, %29, %30, %31, %32, %33, %34, %35, %36, %37, %38, %39, %40, %41, %42, %43, %44, %45, %46, %47}, {%48, %49, %50, %51}, tb, p1, 1, 1, 1;\n"
        "add.s64 tb, tb0, 448;\n"
        "wgmma.mma_async.sync.aligned.m64n96k16.f32.bf16.bf16 {%0, %1, %2, %3, %4, %5, %6, %7, %8, %9, %10, %11, %12, %13, %14, %15, %16, %17, %18, %19, %20, %21, %22, %23, %24, %25, %26, %27, %28, %29, %30, %31, %32, %33, %34, %35, %36, %37, %38, %39, %40, %41, %42, %43, %44, %45, %46, %47}, {%52, %53, %54, %55}, tb, p1, 1, 1, 1;\n"
        "add.s64 tb, tb0, 512;\n"
        "wgmma.mma_async.sync.aligned.m64n96k16.f32.bf16.bf16 {%0, %1, %2, %3, %4, %5, %6, %7, %8, %9, %10, %11, %12, %13, %14, %15, %16, %17, %18, %19, %20, %21, %22, %23, %24, %25, %26, %27, %28, %29, %30, %31, %32, %33, %34, %35, %36, %37, %38, %39, %40, %41, %42, %43, %44, %45, %46, %47}, {%56, %57, %58, %59}, tb, p1, 1, 1, 1;\n"
        "add.s64 tb, tb0, 576;\n"
        "wgmma.mma_async.sync.aligned.m64n96k16.f32.bf16.bf16 {%0, %1, %2, %3, %4, %5, %6, %7, %8, %9, %10, %11, %12, %13, %14, %15, %16, %17, %18, %19, %20, %21, %22, %23, %24, %25, %26, %27, %28, %29, %30, %31, %32, %33, %34, %35, %36, %37, %38, %39, %40, %41, %42, %43, %44, %45, %46, %47}, {%60, %61, %62, %63}, tb, p1, 1, 1, 1;\n"
        "add.s64 tb, tb0, 640;\n"
        "wgmma.mma_async.sync.aligned.m64n96k16.f32.bf16.bf16 {%0, %1, %2, %3, %4, %5, %6, %7, %8, %9, %10, %11, %12, %13, %14, %15, %16, %17, %18, %19, %20, %21, %22, %23, %24, %25, %26, %27, %28, %29, %30, %31, %32, %33, %34, %35, %36, %37, %38, %39, %40, %41, %42, %43, %44, %45, %46, %47}, {%64, %65, %66, %67}, tb, p1, 1, 1, 1;\n"
        "add.s64 tb, tb0, 704;\n"
        "wgmma.mma_async.sync.aligned.m64n96k16.f32.bf16.bf16 {%0, %1, %2, %3, %4, %5, %6, %7, %8, %9, %10, %11, %12, %13, %14, %15, %16, %17, %18, %19, %20, %21, %22, %23, %24, %25, %26, %27, %28, %29, %30, %31, %32, %33, %34, %35, %36, %37, %38, %39, %40, %41, %42, %43, %44, %45, %46, %47}, {%68, %69, %70, %71}, tb, p1, 1, 1, 1;\n"
        "}\n"
        : "+f"(d[0]), "+f"(d[1]), "+f"(d[2]), "+f"(d[3]), "+f"(d[4]), "+f"(d[5]), "+f"(d[6]), "+f"(d[7]), "+f"(d[8]), "+f"(d[9]), "+f"(d[10]), "+f"(d[11]), "+f"(d[12]), "+f"(d[13]), "+f"(d[14]), "+f"(d[15]), "+f"(d[16]), "+f"(d[17]), "+f"(d[18]), "+f"(d[19]), "+f"(d[20]), "+f"(d[21]), "+f"(d[22]), "+f"(d[23]), "+f"(d[24]), "+f"(d[25]), "+f"(d[26]), "+f"(d[27]), "+f"(d[28]), "+f"(d[29]), "+f"(d[30]), "+f"(d[31]), "+f"(d[32]), "+f"(d[33]), "+f"(d[34]), "+f"(d[35]), "+f"(d[36]), "+f"(d[37]), "+f"(d[38]), "+f"(d[39]), "+f"(d[40]), "+f"(d[41]), "+f"(d[42]), "+f"(d[43]), "+f"(d[44]), "+f"(d[45]), "+f"(d[46]), "+f"(d[47])
        : "r"(a[AOFF + 0][0]), "r"(a[AOFF + 0][1]), "r"(a[AOFF + 0][2]), "r"(a[AOFF + 0][3]), "r"(a[AOFF + 1][0]), "r"(a[AOFF + 1][1]), "r"(a[AOFF + 1][2]), "r"(a[AOFF + 1][3]), "r"(a[AOFF + 2][0]), "r"(a[AOFF + 2][1]), "r"(a[AOFF + 2][2]), "r"(a[AOFF + 2][3]), "r"(a[AOFF + 3][0]), "r"(a[AOFF + 3][1]), "r"(a[AOFF + 3][2]), "r"(a[AOFF + 3][3]), "r"(a[AOFF + 4][0]), "r"(a[AOFF + 4][1]), "r"(a[AOFF + 4][2]), "r"(a[AOFF + 4][3]), "r"(a[AOFF + 5][0]), "r"(a[AOFF + 5][1]), "r"(a[AOFF + 5][2]), "r"(a[AOFF + 5][3]), "l"(descB), "n"(BOFF >> 4));
}
template <int V, int S0, int S1> struct Rng;
template <> struct Rng<0, 0, 3> {
template <int BOFF, int AOFF, int NA>
static __device__ __forceinline__ void run(float (&d)[48], const uint32_t (&a)[NA][4], uint64_t descB) {
    asm volatile(
        "{\n"
        ".reg .pred p0, p1;\n"
        ".reg .b64 ta, ta0, tb, tb0;\n"
        "setp.ne.b32 p0, 0, 0;\n"
        "setp.eq.b32 p1, 0, 0;\n"
        "add.s64 tb0, %60, %61;\n"
        "add.s64 tb, tb0, 0;\n"
        "wgmma.mma_async.sync.aligned.m64n96k16.f32.bf16.bf16 {%0, %1, %2, %3, %4, %5, %6, %7, %8, %9, %10, %11, %12, %13, %14, %15, %16, %17, %18, %19, %20, %21, %22, %23, %24, %25, %26, %27, %28, %29, %30, %31, %32, %33, %34, %35, %36, %37, %38, %39, %40, %41, %42, %43, %44, %45, %46, %47}, {%48, %49, %50, %51}, tb, p0, 1, 1, 1;\n"
        "add.s64 tb, tb0, 32;\n"
        "wgmma.mma_async.sync.aligned.m64n96k16.f32.bf16.bf16 {%0, %1, %2, %3, %4, %5, %6, %7, %8, %9, %10, %11, %12, %13, %14, %15, %16, %17, %18, %19, %20, %21, %22, %23, %24, %25, %26, %27, %28, %29, %30, %31, %32, %33, %34, %35, %36, %37, %38, %39, %40, %41, %42, %43, %44, %45, %46, %47}, {%52, %53, %54, %55}, tb, p1, 1, 1, 1;\n"
        "add.s64 tb, tb0, 64;\n"
        "wgmma.mma_async.sync.aligned.m64n96k16.f32.bf16.bf16 {%0, %1, %2, %3, %4, %5, %6, %7, %8, %9, %10, %11, %12, %13, %14, %15, %16, %17, %18, %19, %20, %21, %22, %23, %24, %25, %26, %27, %28, %29, %30, %31, %32, %33, %34, %35, %36, %37, %38, %39, %40, %41, %42, %43, %44, %45, %46, %47}, {%56, %57, %58, %59}, tb, p1, 1, 1, 1;\n"
        "}\n"
        : "=f"(d[0]), "=f"(d[1]), "=f"(d[2]), "=f"(d[3]), "=f"(d[4]), "=f"(d[5]), "=f"(d[6]), "=f"(d[7]), "=f"(d[8]), "=f"(d[9]), "=f"(d[10]), "=f"(d[11]), "=f"(d[12]), "=f"(d[13]), "=f"(d[14]), "=f"(d[15]), "=f"(d[16]), "=f"(d[17]), "=f"(d[18]), "=f"(d[19]), "=f"(d[20]), "=f"(d[21]), "=f"(d[22]), "=f"(d[23]), "=f"(d[24]), "=f"(d[25]), "=f"(d[26]), "=f"(d[27]), "=f"(d[28]), "=f"(d[29]), "=f"(d[30]), "=f"(d[31]), "=f"(d[32]), "=f"(d[33]), "=f"(d[34]), "=f"(d[35]), "=f"(d[36]), "=f"(d[37]), "=f"(d[38]), "=f"(d[39]), "=f"(d[40]), "=f"(d[41]), "=f"(d[42]), "=f"(d[43]), "=f"(d[44]), "=f"(d[45]), "=f"(d[46]), "=f"(d[47])
        : "r"(a[AOFF + 0][0]), "r"(a[AOFF + 0][1]), "r"(a[AOFF + 0][2]), "r"(a[AOFF + 0][3]), "r"(a[AOFF + 1][0]), "r"(a[AOFF + 1][1]), "r"(a[AOFF + 1][2]), "r"(a[AOFF + 1][3]), "r"(a[AOFF + 2][0]), "r"(a[AOFF + 2][1]), "r"(a[AOFF + 2][2]), "r"(a[AOFF + 2][3]), "l"(descB), "n"(BOFF >> 4));
}
};
template <> struct Rng<1, 0, 3> {
template <int BOFF, int AOFF, int NA>
static __device__ __forceinline__ void run(float (&d)[48], const uint32_t (&a)[NA][4], uint64_t descB) {
    asm volatile(
        "{\n"
        ".reg .pred p0, p1;\n"
        ".reg .b64 ta, ta0, tb, tb0;\n"
        "setp.ne.b32 p0, 0, 0;\n"
        "setp.eq.b32 p1, 0, 0;\n"
        "add.s64 tb0, %60, %61;\n"
        "add.s64 tb, tb0, 0;\n"
        "wgmma.mma_async.sync.aligned.m64n96k16.f32.bf16.bf16 {%0, %1, %2, %3, %4, %5, %6, %7, %8, %9, %10, %11, %12, %13, %14, %15, %16, %17, %18, %19, %20, %21, %22, %23, %24, %25, %26, %27, %28, %29, %30, %31, %32, %33, %34, %35, %36, %37, %38, %39, %40, %41, %42, %43, %44, %45, %46, %47}, {%48, %49, %50, %51}, tb, p0, 1, 1, 1;\n"
        "add.s64 tb, tb0, 32;\n"
        "wgmma.mma_async.sync.aligned.m64n96k16.f32.bf16.bf16 {%0, %1, %2, %3, %4, %5, %6, %7, %8, %9, %10, %11, %12, %13, %14, %15, %16, %17, %18, %19, %20, %21, %22, %23, %24, %25, %26, %27, %28, %29, %30, %31, %32, %33, %34, %35, %36, %37, %38, %39, %40, %41, %42, %43, %44, %45, %46, %47}, {%52, %53, %54, %55}, tb, p1, 1, 1, 1;\n"
        "add.s64 tb, tb0, 64;\n"
        "wgmma.mma_async.sync.aligned.m64n96k16.f32.bf16.bf16 {%0, %1, %2, %3, %4, %5, %6, %7, %8, %9, %10, %11, %12, %13, %14, %15, %16, %17, %18, %19, %20, %21, %22, %23, %24, %25, %26, %27, %28, %29, %30, %31, %32, %33, %34, %35, %36, %37, %38, %39, %40, %41, %42, %43, %44, %45, %46, %47}, {%56, %57, %58, %59}, tb, p1, 1, 1, 1;\n"
        "}\n"
        : "=f"(d[0]), "=f"(d[1]), "=f"(d[2]), "=f"(d[3]), "=f"(d[4]), "=f"(d[5]), "=f"(d[6]), "=f"(d[7]), "=f"(d[8]), "=f"(d[9]), "=f"(d[10]), "=f"(d[11]), "=f"(d[12]), "=f"(d[13]), "=f"(d[14]), "=f"(d[15]), "=f"(d[16]), "=f"(d[17]), "=f"(d[18]), "=f"(d[19]), "=f"(d[20]), "=f"(d[21]), "=f"(d[22]), "=f"(d[23]), "=f"(d[24]), "=f"(d[25]), "=f"(d[26]), "=f"(d[27]), "=f"(d[28]), "=f"(d[29]), "=f"(d[30]), "=f"(d[31]), "=f"(d[32]), "=f"(d[33]), "=f"(d[34]), "=f"(d[35]), "=f"(d[36]), "=f"(d[37]), "=f"(d[38]), "=f"(d[39]), "=f"(d[40]), "=f"(d[41]), "=f"(d[42]), "=f"(d[43]), "=f"(d[44]), "=f"(d[45]), "=f"(d[46]), "=f"(d[47])
        : "r"(a[AOFF + 0][0]), "r"(a[AOFF + 0][1]), "r"(a[AOFF + 0][2]), "r"(a[AOFF + 0][3]), "r"(a[AOFF + 1][0]), "r"(a[AOFF + 1][1]), "r"(a[AOFF + 1][2]), "r"(a[AOFF + 1][3]), "r"(a[AOFF + 2][0]), "r"(a[AOFF + 2][1]), "r"(a[AOFF + 2][2]), "r"(a[AOFF + 2][3]), "l"(descB), "n"(BOFF >> 4));
}
};
template <> struct Rng<0, 0, 4> {
template <int BOFF, int AOFF, int NA>
static __device__ __forceinline__ void run(float (&d)[48], const uint32_t (&a)[NA][4], uint64_t descB) {
    asm volatile(
        "{\n"
        ".reg .pred p0, p1;\n"
        ".reg .b64 ta, ta0, tb, tb0;\n"
        "setp.ne.b32 p0, 0, 0;\n"
        "setp.eq.b32 p1, 0, 0;\n"
        "add.s64 tb0, %64, %65;\n"
        "add.s64 tb, tb0, 0;\n"
        "wgmma.mma_async.sync.aligned.m64n96k16.f32.bf16.bf16 {%0, %1, %2, %3, %4, %5, %6, %7, %8, %9, %10, %11, %12, %13, %14, %15, %16, %17, %18, %19, %20, %21, %22, %23, %24, %25, %26, %27, %28, %29, %30, %31, %32, %33, %34, %35, %36, %37, %38, %39, %40, %41, %42, %43, %44, %45, %46, %47}, {%48, %49, %50, %51}, tb, p0, 1, 1, 1;\n"
        "add.s64 tb, tb0, 32;\n"
        "wgmma.mma_async.sync.aligned.m64n96k16.f32.bf16.bf16 {%0, %1, %2, %3, %4, %5, %6, %7, %8, %9, %10, %11, %12, %13, %14, %15, %16, %17, %18, %19, %20, %21, %22, %23, %24, %25, %26, %27, %28, %29, %30, %31, %32, %33, %34, %35, %36, %37, %38, %39, %40, %41, %42, %43, %44, %45, %46, %47}, {%52, %53, %54, %55}, tb, p1, 1, 1, 1;\n"
        "add.s64 tb, tb0, 64;\n"
        "wgmma.mma_async.sync.aligned.m64n96k16.f32.bf16.bf16 {%0, %1, %2, %3, %4, %5, %6, %7, %8, %9, %10, %11, %12, %13, %14, %15, %16, %17, %18, %19, %20, %21, %22, %23, %24, %25, %26, %27, %28, %29, %30, %31, %32, %33, %34, %35, %36, %37, %38, %39, %40, %41, %42, %43, %44, %45, %46, %47}, {%56, %57, %58, %59}, tb, p1, 1, 1, 1;\n"
        "add.s64 tb, tb0, 96;\n"
        "wgmma.mma_async.sync.aligned.m64n96k16.f32.bf16.bf16 {%0, %1, %2, %3, %4, %5, %6, %7, %8, %9, %10, %11, %12, %13, %14, %15, %16, %17, %18, %19, %20, %21, %22, %23, %24, %25, %26, %27, %28, %29, %30, %31, %32, %33, %34, %35, %36, %37, %38, %39, %40, %41, %42, %43, %44, %45, %46, %47}, {%60, %61, %62, %63}, tb, p1, 1, 1, 1;\n"
        "}\n"
        : "=f"(d[0]), "=f"(d[1]), "=f"(d[2]), "=f"(d[3]), "=f"(d[4]), "=f"(d[5]), "=f"(d[6]), "=f"(d[7]), "=f"(d[8]), "=f"(d[9]), "=f"(d[10]), "=f"(d[11]), "=f"(d[12]), "=f"(d[13]), "=f"(d[14]), "=f"(d[15]), "=f"(d[16]), "=f"(d[17]), "=f"(d[18]), "=f"(d[19]), "=f"(d[20]), "=f"(d[21]), "=f"(d[22]), "=f"(d[23]), "=f"(d[24]), "=f"(d[25]), "=f"(d[26]), "=f"(d[27]), "=f"(d[28]), "=f"(d[29]), "=f"(d[30]), "=f"(d[31]), "=f"(d[32]), "=f"(d[33]), "=f"(d[34]), "=f"(d[35]), "=f"(d[36]), "=f"(d[37]), "=f"(d[38]), "=f"(d[39]), "=f"(d[40]), "=f"(d[41]), "=f"(d[42]), "=f"(d[43]), "=f"(d[44]), "=f"(d[45]), "=f"(d[46]), "=f"(d[47])
        : "r"(a[AOFF + 0][0]), "r"(a[AOFF + 0][1]), "r"(a[AOFF + 0][2]), "r"(a[AOFF + 0][3]), "r"(a[AOFF + 1][0]), "r"(a[AOFF + 1][1]), "r"(a[AOFF + 1][2]), "r"(a[AOFF + 1][3]), "r"(a[AOFF + 2][0]), "r"(a[AOFF + 2][1]), "r"(a[AOFF + 2][2]), "r"(a[AOFF + 2][3]), "r"(a[AOFF + 3][0]), "r"(a[AOFF + 3][1]), "r"(a[AOFF + 3][2]), "r"(a[AOFF + 3][3]), "l"(descB), "n"(BOFF >> 4));
}
};
template <> struct Rng<1, 0, 4> {
template <int BOFF, int AOFF, int NA>
static __device__ __forceinline__ void run(float (&d)[48], const uint32_t (&a)[NA][4], uint64_t descB) {
    asm volatile(
        "{\n"
        ".reg .pred p0, p1;\n"
        ".reg .b64 ta, ta0, tb, tb0;\n"
        "setp.ne.b32 p0, 0, 0;\n"
        "setp.eq.b32 p1, 0, 0;\n"
        "add.s64 tb0, %64, %65;\n"
        "add.s64 tb, tb0, 0;\n"
        "wgmma.mma_async.sync.aligned.m64n96k16.f32.bf16.bf16 {%0, %1, %2, %3, %4, %5, %6, %7, %8, %9, %10, %11, %12, %13, %14, %15, %16, %17, %18, %19, %20, %21, %22, %23, %24, %25, %26, %27, %28, %29, %30, %31, %32, %33, %34, %35, %36, %37, %38, %39, %40, %41, %42, %43, %44, %45, %46, %47}, {%48, %49, %50, %51}, tb, p0, 1, 1, 1;\n"
        "add.s64 tb, tb0, 32;\n"
        "wgmma.mma_async.sync.aligned.m64n96k16.f32.bf16.bf16 {%0, %1, %2, %3, %4, %5, %6, %7, %8, %9, %10, %11, %12, %13, %14, %15, %16, %17, %18, %19, %20, %21, %22, %23, %24, %25, %26, %27, %28, %29, %30, %31, %32, %33, %34, %35, %36, %37, %38, %39, %40, %41, %42, %43, %44, %45, %46, %47}, {%52, %53, %54, %55}, tb, p1, 1, 1, 1;\n"
        "add.s64 tb, tb0, 64;\n"
        "wgmma.mma_async.sync.aligned.m64n96k16.f32.bf16.bf16 {%0, %1, %2, %3, %4, %5, %6, %7, %8, %9, %10, %11, %12, %13, %14, %15, %16, %17, %18, %19, %20, %21, %22, %23, %24, %25, %26, %27, %28, %29, %30, %31, %32, %33, %34, %35, %36, %37, %38, %39, %40, %41, %42, %43, %44, %45, %46, %47}, {%56, %57, %58, %59}, tb, p1, 1, 1, 1;\n"
        "add.s64 tb, tb0, 96;\n"
        "wgmma.mma_async.sync.aligned.m64n96k16.f32.bf16.bf16 {%0, %1, %2, %3, %4, %5, %6, %7, %8, %9, %10, %11, %12, %13, %14, %15, %16, %17, %18, %19, %20, %21, %22, %23, %24, %25, %26, %27, %28, %29, %30, %31, %32, %33, %34, %35, %36, %37, %38, %39, %40, %41, %42, %43, %44, %45, %46, %47}, {%60, %61, %62, %63}, tb, p1, 1, 1, 1;\n"
        "}\n"
        : "=f"(d[0]), "=f"(d[1]), "=f"(d[2]), "=f"(d[3]), "=f"(d[4]), "=f"(d[5]), "=f"(d[6]), "=f"(d[7]), "=f"(d[8]), "=f"(d[9]), "=f"(d[10]), "=f"(d[11]), "=f"(d[12]), "=f"(d[13]), "=f"(d[14]), "=f"(d[15]), "=f"(d[16]), "=f"(d[17]), "=f"(d[18]), "=f"(d[19]), "=f"(d[20]), "=f"(d[21]), "=f"(d[22]), "=f"(d[23]), "=f"(d[24]), "=f"(d[25]), "=f"(d[26]), "=f"(d[27]), "=f"(d[28]), "=f"(d[29]), "=f"(d[30]), "=f"(d[31]), "=f"(d[32]), "=f"(d[33]), "=f"(d[34]), "=f"(d[35]), "=f"(d[36]), "=f"(d[37]), "=f"(d[38]), "=f"(d[39]), "=f"(d[40]), "=f"(d[41]), "=f"(d[42]), "=f"(d[43]), "=f"(d[44]), "=f"(d[45]), "=f"(d[46]), "=f"(d[47])
        : "r"(a[AOFF + 0][0]), "r"(a[AOFF + 0][1]), "r"(a[AOFF + 0][2]), "r"(a[AOFF + 0][3]), "r"(a[AOFF + 1][0]), "r"(a[AOFF + 1][1]), "r"(a[AOFF + 1][2]), "r"(a[AOFF + 1][3]), "r"(a[AOFF + 2][0]), "r"(a[AOFF + 2][1]), "r"(a[AOFF + 2][2]), "r"(a[AOFF + 2][3]), "r"(a[AOFF + 3][0]), "r"(a[AOFF + 3][1]), "r"(a[AOFF + 3][2]), "r"(a[AOFF + 3][3]), "l"(descB), "n"(BOFF >> 4));
}
};
template <> struct Rng<0, 0, 5> {
template <int BOFF, int AOFF, int NA>
static __device__ __forceinline__ void run(float (&d)[48], const uint32_t (&a)[NA][4], uint64_t descB) {
    asm volatile(
        "{\n"
        ".reg .pred p0, p1;\n"
        ".reg .b64 ta, ta0, tb, tb0;\n"
        "setp.ne.b32 p0, 0, 0;\n"
        "setp.eq.b32 p1, 0, 0;\n"
        "add.s64 tb0, %68, %69;\n"
        "add.s64 tb, tb0, 0;\n"
        "wgmma.mma_async.sync.aligned.m64n96k16.f32.bf16.bf16 {%0, %1, %2, %3, %4, %5, %6, %7, %8, %9, %10, %11, %12, %13, %14, %15, %16, %17, %18, %19, %20, %21, %22, %23, %24, %25, %26, %27, %28, %29, %30, %31, %32, %33, %34, %35, %36, %37, %38, %39, %40, %41, %42, %43, %44, %45, %46, %47}, {%48, %49, %50, %51}, tb, p0, 1, 1, 1;\n"
        "add.s64 tb, tb0, 32;\n"
        "wgmma.mma_async.sync.aligned.m64n96k16.f32.bf16.bf16 {%0, %1, %2, %3, %4, %5, %6, %7, %8, %9, %10, %11, %12, %13, %14, %15, %16, %17, %18, %19, %20, %21, %22, %23, %24, %25, %26, %27, %28, %29, %30, %31, %32, %33, %34, %35, %36, %37, %38, %39, %40, %41, %42, %43, %44, %45, %46, %47}, {%52, %53, %54, %55}, tb, p1, 1, 1, 1;\n"
        "add.s64 tb, tb0, 64;\n"
        "wgmma.mma_async.sync.aligned.m64n96k16.f32.bf16.bf16 {%0, %1, %2, %3, %4, %5, %6, %7, %8, %9, %10, %11, %12, %13, %14, %15, %16, %17, %18, %19, %20, %21, %22, %23, %24, %25, %26, %27, %28, %29, %30, %31, %32, %33, %34, %35, %36, %37, %38, %39, %40, %41, %42, %43, %44, %45, %46, %47}, {%56, %57, %58, %59}, tb, p1, 1, 1, 1;\n"
        "add.s64 tb, tb0, 96;\n"
        "wgmma.mma_async.sync.aligned.m64n96k16.f32.bf16.bf16 {%0, %1, %2, %3, %4, %5, %6, %7, %8, %9, %10, %11, %12, %13, %14, %15, %16, %17, %18, %19, %20, %21, %22, %23, %24, %25, %26, %27, %28, %29, %30, %31, %32, %33, %34, %35, %36, %37, %38, %39, %40, %41, %42, %43, %44, %45, %46, %47}, {%60, %61, %62, %63}, tb, p1, 1, 1, 1;\n"
        "add.s64 tb, tb0, 1536;\n"
        "wgmma.mma_async.sync.aligned.m64n96k16.f32.bf16.bf16 {%0, %1, %2, %3, %4, %5, %6, %7, %8, %9, %10, %11, %12, %13, %14, %15, %16, %17, %18, %19, %20, %21, %22, %23, %24, %25, %26, %27, %28, %29, %30, %31, %32, %33, %34, %35, %36, %37, %38, %39, %40, %41, %42, %43, %44, %45, %46, %47}, {%64, %65, %66, %67}, tb, p1, 1, 1, 1;\n"
        "}\n"
        : "=f"(d[0]), "=f"(d[1]), "=f"(d[2]), "=f"(d[3]), "=f"(d[4]), "=f"(d[5]), "=f"(d[6]), "=f"(d[7]), "=f"(d[8]), "=f"(d[9]), "=f"(d[10]), "=f"(d[11]), "=f"(d[12]), "=f"(d[13]), "=f"(d[14]), "=f"(d[15]), "=f"(d[16]), "=f"(d[17]), "=f"(d[18]), "=f"(d[19]), "=f"(d[20]), "=f"(d[21]), "=f"(d[22]), "=f"(d[23]), "=f"(d[24]), "=f"(d[25]), "=f"(d[26]), "=f"(d[27]), "=f"(d[28]), "=f"(d[29]), "=f"(d[30]), "=f"(d[31]), "=f"(d[32]), "=f"(d[33]), "=f"(d[34]), "=f"(d[35]), "=f"(d[36]), "=f"(d[37]), "=f"(d[38]), "=f"(d[39]), "=f"(d[40]), "=f"(d[41]), "=f"(d[42]), "=f"(d[43]), "=f"(d[44]), "=f"(d[45]), "=f"(d[46]), "=f"(d[47])
        : "r"(a[AOFF + 0][0]), "r"(a[AOFF + 0][1]), "r"(a[AOFF + 0][2]), "r"(a[AOFF + 0][3]), "r"(a[AOFF + 1][0]), "r"(a[AOFF + 1][1]), "r"(a[AOFF + 1][2]), "r"(a[AOFF + 1][3]), "r"(a[AOFF + 2][0]), "r"(a[AOFF + 2][1]), "r"(a[AOFF + 2][2]), "r"(a[AOFF + 2][3]), "r"(a[AOFF + 3][0]), "r"(a[AOFF + 3][1]), "r"(a[AOFF + 3][2]), "r"(a[AOFF + 3][3]), "r"(a[AOFF + 4][0]), "r"(a[AOFF + 4][1]), "r"(a[AOFF + 4][2]), "r"(a[AOFF + 4][3]), "l"(descB), "n"(BOFF >> 4));
}
};
template <> struct Rng<1, 0, 5> {
template <int BOFF, int AOFF, int NA>
static __device__ __forceinline__ void run(float (&d)[48], const uint32_t (&a)[NA][4], uint64_t descB) {
    asm volatile(
        "{\n"
        ".reg .pred p0, p1;\n"
        ".reg .b64 ta, ta0, tb, tb0;\n"
        "setp.ne.b32 p0, 0, 0;\n"
        "setp.eq.b32 p1, 0, 0;\n"
        "add.s64 tb0, %68, %69;\n"
        "add.s64 tb, tb0, 0;\n"
        "wgmma.mma_async.sync.aligned.m64n96k16.f32.bf16.bf16 {%0, %1, %2, %3, %4, %5, %6, %7, %8, %9, %10, %11, %12, %13, %14, %15, %16, %17, %18, %19, %20, %21, %22, %23, %24, %25, %26, %27, %28, %29, %30, %31, %32, %33, %34, %35, %36, %37, %38, %39, %40, %41, %42, %43, %44, %45, %46, %47}, {%48, %49, %50, %51}, tb, p0, 1, 1, 1;\n"
        "add.s64 tb, tb0, 32;\n"
        "wgmma.mma_async.sync.aligned.m64n96k16.f32.bf16.bf16 {%0, %1, %2, %3, %4, %5, %6, %7, %8, %9, %10, %11, %12, %13, %14, %15, %16, %17, %18, %19, %20, %21, %22, %23, %24, %25, %26, %27, %28, %29, %30, %31, %32, %33, %34, %35, %36, %37, %38, %39, %40, %41, %42, %43, %44, %45, %46, %47}, {%52, %53, %54, %55}, tb, p1, 1, 1, 1;\n"
        "add.s64 tb, tb0, 64;\n"
        "wgmma.mma_async.sync.aligned.m64n96k16.f32.bf16.bf16 {%0, %1, %2, %3, %4, %5, %6, %7, %8, %9, %10, %11, %12, %13, %14, %15, %16, %17, %18, %19, %20, %21, %22, %23, %24, %25, %26, %27, %28, %29, %30, %31, %32, %33, %34, %35, %36, %37, %38, %39, %40, %41, %42, %43, %44, %45, %46, %47}, {%56, %57, %58, %59}, tb, p1, 1, 1, 1;\n"
        "add.s64 tb, tb0, 96;\n"
        "wgmma.mma_async.sync.aligned.m64n96k16.f32.bf16.bf16 {%0, %1, %2, %3, %4, %5, %6, %7, %8, %9, %10, %11, %12, %13, %14, %15, %16, %17, %18, %19, %20, %21, %22, %23, %24, %25, %26, %27, %28, %29, %30, %31, %32, %33, %34, %35, %36, %37, %38, %39, %40, %41, %42, %43, %44, %45, %46, %47}, {%60, %61, %62, %63}, tb, p1, 1, 1, 1;\n"
        "add.s64 tb, tb0, 128;\n"
        "wgmma.mma_async.sync.aligned.m64n96k16.f32.bf16.bf16 {%0, %1, %2, %3, %4, %5, %6, %7, %8, %9, %10, %11, %12, %13, %14, %15, %16, %17, %18, %19, %20, %21, %22, %23, %24, %25, %26, %27, %28, %29, %30, %31, %32, %33, %34, %35, %36, %37, %38, %39, %40, %41, %42, %43, %44, %45, %46, %47}, {%64, %65, %66, %67}, tb, p1, 1, 1, 1;\n"
        "}\n"
        : "=f"(d[0]), "=f"(d[1]), "=f"(d[2]), "=f"(d[3]), "=f"(d[4]), "=f"(d[5]), "=f"(d[6]), "=f"(d[7]), "=f"(d[8]), "=f"(d[9]), "=f"(d[10]), "=f"(d[11]), "=f"(d[12]), "=f"(d[13]), "=f"(d[14]), "=f"(d[15]), "=f"(d[16]), "=f"(d[17]), "=f"(d[18]), "=f"(d[19]), "=f"(d[20]), "=f"(d[21]), "=f"(d[22]), "=f"(d[23]), "=f"(d[24]), "=f"(d[25]), "=f"(d[26]), "=f"(d[27]), "=f"(d[28]), "=f"(d[29]), "=f"(d[30]), "=f"(d[31]), "=f"(d[32]), "=f"(d[33]), "=f"(d[34]), "=f"(d[35]), "=f"(d[36]), "=f"(d[37]), "=f"(d[38]), "=f"(d[39]), "=f"(d[40]), "=f"(d[41]), "=f"(d[42]), "=f"(d[43]), "=f"(d[44]), "=f"(d[45]), "=f"(d[46]), "=f"(d[47])
        : "r"(a[AOFF + 0][0]), "r"(a[AOFF + 0][1]), "r"(a[AOFF + 0][2]), "r"(a[AOFF + 0][3]), "r"(a[AOFF + 1][0]), "r"(a[AOFF + 1][1]), "r"(a[AOFF + 1][2]), "r"(a[AOFF + 1][3]), "r"(a[AOFF + 2][0]), "r"(a[AOFF + 2][1]), "r"(a[AOFF + 2][2]), "r"(a[AOFF + 2][3]), "r"(a[AOFF + 3][0]), "r"(a[AOFF + 3][1]), "r"(a[AOFF + 3][2]), "r"(a[AOFF + 3][3]), "r"(a[AOFF + 4][0]), "r"(a[AOFF + 4][1]), "r"(a[AOFF + 4][2]), "r"(a[AOFF + 4][3]), "l"(descB), "n"(BOFF >> 4));
}
};
template <> struct Rng<0, 0, 6> {
template <int BOFF, int AOFF, int NA>
static __device__ __forceinline__ void run(float (&d)[48], const uint32_t (&a)[NA][4], uint64_t descB) {
    asm volatile(
        "{\n"
        ".reg .pred p0, p1;\n"
        ".reg .b64 ta, ta0, tb, tb0;\n"
        "setp.ne.b32 p0, 0, 0;\n"
        "setp.eq.b32 p1, 0, 0;\n"
        "add.s64 tb0, %72, %73;\n"
        "add.s64 tb, tb0, 0;\n"
        "wgmma.mma_async.sync.aligned.m64n96k16.f32.bf16.bf16 {%0, %1, %2, %3, %4, %5, %6, %7, %8, %9, %10, %11, %12, %13, %14, %15, %16, %17, %18, %19, %20, %21, %22, %23, %24, %25, %26, %27, %28, %29, %30, %31, %32, %33, %34, %35, %36, %37, %38, %39, %40, %41, %42, %43, %44, %45, %46, %47}, {%48, %49, %50, %51}, tb, p0, 1, 1, 1;\n"
        "add.s64 tb, tb0, 32;\n"
        "wgmma.mma_async.sync.aligned.m64n96k16.f32.bf16.bf16 {%0, %1, %2, %3, %4, %5, %6, %7, %8, %9, %10, %11, %12, %13, %14, %15, %16, %17, %18, %19, %20, %21, %22, %23, %24, %25, %26, %27, %28, %29, %30, %31, %32, %33, %34, %35, %36, %37, %38, %39, %40, %41, %42, %43, %44, %45, %46, %47}, {%52, %53, %54, %55}, tb, p1, 1, 1, 1;\n"
        "add.s64 tb, tb0, 64;\n"
        "wgmma.mma_async.sync.aligned.m64n96k16.f32.bf16.bf16 {%0, %1, %2, %3, %4, %5, %6, %7, %8, %9, %10, %11, %12, %13, %14, %15, %16, %17, %18, %19, %20, %21, %22, %23, %24, %25, %26, %27, %28, %29, %30, %31, %32, %33, %34, %35, %36, %37, %38, %39, %40, %41, %42, %43, %44, %45, %46, %47}, {%56, %57, %58, %59}, tb, p1, 1, 1, 1;\n"
        "add.s64 tb, tb0, 96;\n"
        "wgmma.mma_async.sync.aligned.m64n96k16.f32.bf16.bf16 {%0, %1, %2, %3, %4, %5, %6, %7, %8, %9, %10, %11, %12, %13, %14, %15, %16, %17, %18, %19, %20, %21, %22, %23, %24, %25, %26, %27, %28, %29, %30, %31, %32, %33, %34, %35, %36, %37, %38, %39, %40, %41, %42, %43, %44, %45, %46, %47}, {%60, %61, %62, %63}, tb, p1, 1, 1, 1;\n"
        "add.s64 tb, tb0, 1536;\n"
        "wgmma.mma_async.sync.aligned.m64n96k16.f32.bf16.bf16 {%0, %1, %2, %3, %4, %5, %6, %7, %8, %9, %10, %11, %12, %13, %14, %15, %16, %17, %18, %19, %20, %21, %22, %23, %24, %25, %26, %27, %28, %29, %30, %31, %32, %33, %34, %35, %36, %37, %38, %39, %40, %41, %42, %43, %44, %45, %46, %47}, {%64, %65, %66, %67}, tb, p1, 1, 1, 1;\n"
        "add.s64 tb, tb0, 1568;\n"
        "wgmma.mma_async.sync.aligned.m64n96k16.f32.bf16.bf16 {%0, %1, %2, %3, %4, %5, %6, %7, %8, %9, %10, %11, %12, %13, %14, %15, %16, %17, %18, %19, %20, %21, %22, %23, %24, %25, %26, %27, %28, %29, %30, %31, %32, %33, %34, %35, %36, %37, %38, %39, %40, %41, %42, %43, %44, %45, %46, %47}, {%68, %69, %70, %71}, tb, p1, 1, 1, 1;\n"
        "}\n"
        : "=f"(d[0]), "=f"(d[1]), "=f"(d[2]), "=f"(d[3]), "=f"(d[4]), "=f"(d[5]), "=f"(d[6]), "=f"(d[7]), "=f"(d[8]), "=f"(d[9]), "=f"(d[10]), "=f"(d[11]), "=f"(d[12]), "=f"(d[13]), "=f"(d[14]), "=f"(d[15]), "=f"(d[16]), "=f"(d[17]), "=f"(d[18]), "=f"(d[19]), "=f"(d[20]), "=f"(d[21]), "=f"(d[22]), "=f"(d[23]), "=f"(d[24]), "=f"(d[25]), "=f"(d[26]), "=f"(d[27]), "=f"(d[28]), "=f"(d[29]), "=f"(d[30]), "=f"(d[31]), "=f"(d[32]), "=f"(d[33]), "=f"(d[34]), "=f"(d[35]), "=f"(d[36]), "=f"(d[37]), "=f"(d[38]), "=f"(d[39]), "=f"(d[40]), "=f"(d[41]), "=f"(d[42]), "=f"(d[43]), "=f"(d[44]), "=f"(d[45]), "=f"(d[46]), "=f"(d[47])
        : "r"(a[AOFF + 0][0]), "r"(a[AOFF + 0][1]), "r"(a[AOFF + 0][2]), "r"(a[AOFF + 0][3]), "r"(a[AOFF + 1][0]), "r"(a[AOFF + 1][1]), "r"(a[AOFF + 1][2]), "r"(a[AOFF + 1][3]), "r"(a[AOFF + 2][0]), "r"(a[AOFF + 2][1]), "r"(a[AOFF + 2][2]), "r"(a[AOFF + 2][3]), "r"(a[AOFF + 3][0]), "r"(a[AOFF + 3][1]), "r"(a[AOFF + 3][2]), "r"(a[AOFF + 3][3]), "r"(a[AOFF + 4][0]), "r"(a[AOFF + 4][1]), "r"(a[AOFF + 4][2]), "r"(a[AOFF + 4][3]), "r"(a[AOFF + 5][0]), "r"(a[AOFF + 5][1]), "r"(a[AOFF + 5][2]), "r"(a[AOFF + 5][3]), "l"(descB), "n"(BOFF >> 4));
}
};
template <> struct Rng<1, 0, 6> {
template <int BOFF, int AOFF, int NA>
static __device__ __forceinline__ void run(float (&d)[48], const uint32_t (&a)[NA][4], uint64_t descB) {
    asm volatile(
        "{\n"
        ".reg .pred p0, p1;\n"
        ".reg .b64 ta, ta0, tb, tb0;\n"
        "setp.ne.b32 p0, 0, 0;\n"
        "setp.eq.b32 p1, 0, 0;\n"
        "add.s64 tb0, %72, %73;\n"
        "add.s64 tb, tb0, 0;\n"
        "wgmma.mma_async.sync.aligned.m64n96k16.f32.bf16.bf16 {%0, %1, %2, %3, %4, %5, %6, %7, %8, %9, %10, %11, %12, %13, %14, %15, %16, %17, %18, %19, %20, %21, %22, %23, %24, %25, %26, %27, %28, %29, %30, %31, %32, %33, %34, %35, %36, %37, %38, %39, %40, %41, %42, %43, %44, %45, %46, %47}, {%48, %49, %50, %51}, tb, p0, 1, 1, 1;\n"
        "add.s64 tb, tb0, 32;\n"
        "wgmma.mma_async.sync.aligned.m64n96k16.f32.bf16.bf16 {%0, %1, %2, %3, %4, %5, %6, %7, %8, %9, %10, %11, %12, %13, %14, %15, %16, %17, %18, %19, %20, %21, %22, %23, %24, %25, %26, %27, %28, %29, %30, %31, %32, %33, %34, %35, %36, %37, %38, %39, %40, %41, %42, %43, %44, %45, %46, %47}, {%52, %53, %54, %55}, tb, p1, 1, 1, 1;\n"
        "add.s64 tb, tb0, 64;\n"
        "wgmma.mma_async.sync.aligned.m64n96k16.f32.bf16.bf16 {%0, %1, %2, %3, %4, %5, %6, %7, %8, %9, %10, %11, %12, %13, %14, %15, %16, %17, %18, %19, %20, %21, %22, %23, %24, %25, %26, %27, %28, %29, %30, %31, %32, %33, %34, %35, %36, %37, %38, %39, %40, %41, %42, %43, %44, %45, %46, %47}, {%56, %57, %58, %59}, tb, p1, 1, 1, 1;\n"
        "add.s64 tb, tb0, 96;\n"
        "wgmma.mma_async.sync.aligned.m64n96k16.f32.bf16.bf16 {%0, %1, %2, %3, %4, %5, %6, %7, %8, %9, %10, %11, %12, %13, %14, %15, %16, %17, %18, %19, %20, %21, %22, %23, %24, %25, %26, %27, %28, %29, %30, %31, %32, %33, %34, %35, %36, %37, %38, %39, %40, %41, %42, %43, %44, %45, %46, %47}, {%60, %61, %62, %63}, tb, p1, 1, 1, 1;\n"
        "add.s64 tb, tb0, 128;\n"
        "wgmma.mma_async.sync.aligned.m64n96k16.f32.bf16.bf16 {%0, %1, %2, %3, %4, %5, %6, %7, %8, %9, %10, %11, %12, %13, %14, %15, %16, %17, %18, %19, %20, %21, %22, %23, %24, %25, %26, %27, %28, %29, %30, %31, %32, %33, %34, %35, %36, %37, %38, %39, %40, %41, %42, %43, %44, %45, %46, %47}, {%64, %65, %66, %67}, tb, p1, 1, 1, 1;\n"
        "add.s64 tb, tb0, 160;\n"
        "wgmma.mma_async.sync.aligned.m64n96k16.f32.bf16.bf16 {%0, %1, %2, %3, %4, %5, %6, %7, %8, %9, %10, %11, %12, %13, %14, %15, %16, %17, %18, %19, %20, %21, %22, %23, %24, %25, %26, %27, %28, %29, %30, %31, %32, %33, %34, %35, %36, %37, %38, %39, %40, %41, %42, %43, %44, %45, %46, %47}, {%68, %69, %70, %71}, tb, p1, 1, 1, 1;\n"
        "}\n"
        : "=f"(d[0]), "=f"(d[1]), "=f"(d[2]), "=f"(d[3]), "=f"(d[4]), "=f"(d[5]), "=f"(d[6]), "=f"(d[7]), "=f"(d[8]), "=f"(d[9]), "=f"(d[10]), "=f"(d[11]), "=f"(d[12]), "=f"(d[13]), "=f"(d[14]), "=f"(d[15]), "=f"(d[16]), "=f"(d[17]), "=f"(d[18]), "=f"(d[19]), "=f"(d[20]), "=f"(d[21]), "=f"(d[22]), "=f"(d[23]), "=f"(d[24]), "=f"(d[25]), "=f"(d[26]), "=f"(d[27]), "=f"(d[28]), "=f"(d[29]), "=f"(d[30]), "=f"(d[31]), "=f"(d[32]), "=f"(d[33]), "=f"(d[34]), "=f"(d[35]), "=f"(d[36]), "=f"(d[37]), "=f"(d[38]), "=f"(d[39]), "=f"(d[40]), "=f"(d[41]), "=f"(d[42]), "=f"(d[43]), "=f"(d[44]), "=f"(d[45]), "=f"(d[46]), "=f"(d[47])
        : "r"(a[AOFF + 0][0]), "r"(a[AOFF + 0][1]), "r"(a[AOFF + 0][2]), "r"(a[AOFF + 0][3]), "r"(a[AOFF + 1][0]), "r"(a[AOFF + 1][1]), "r"(a[AOFF + 1][2]), "r"(a[AOFF + 1][3]), "r"(a[AOFF + 2][0]), "r"(a[AOFF + 2][1]), "r"(a[AOFF + 2][2]), "r"(a[AOFF + 2][3]), "r"(a[AOFF + 3][0]), "r"(a[AOFF + 3][1]), "r"(a[AOFF + 3][2]), "r"(a[AOFF + 3][3]), "r"(a[AOFF + 4][0]), "r"(a[AOFF + 4][1]), "r"(a[AOFF + 4][2]), "r"(a[AOFF + 4][3]), "r"(a[AOFF + 5][0]), "r"(a[AOFF + 5][1]), "r"(a[AOFF + 5][2]), "r"(a[AOFF + 5][3]), "l"(descB), "n"(BOFF >> 4));
}
};
template <> struct Rng<0, 3, 7> {
template <int BOFF, int AOFF, int NA>
static __device__ __forceinline__ void run(float (&d)[48], const uint32_t (&a)[NA][4], uint64_t descB) {
    asm volatile(
        "{\n"
        ".reg .pred p0, p1;\n"
        ".reg .b64 ta, ta0, tb, tb0;\n"
        "setp.ne.b32 p0, 0, 0;\n"
        "setp.eq.b32 p1, 0, 0;\n"
        "add.s64 tb0, %64, %65;\n"
        "add.s64 tb, tb0, 96;\n"
        "wgmma.mma_async.sync.aligned.m64n96k16.f32.bf16.bf16 {%0, %1, %2, %3, %4, %5, %6, %7, %8, %9, %10, %11, %12, %13, %14, %15, %16, %17, %18, %19, %20, %21, %22, %23, %24, %25, %26, %27, %28, %29, %30, %31, %32, %33, %34, %35, %36, %37, %38, %39, %40, %41, %42, %43, %44, %45, %46, %47}, {%48, %49, %50, %51}, tb, p1, 1, 1, 1;\n"
        "add.s64 tb, tb0, 1536;\n"
        "wgmma.mma_async.sync.aligned.m64n96k16.f32.bf16.bf16 {%0, %1, %2, %3, %4, %5, %6, %7, %8, %9, %10, %11, %12, %13, %14, %15, %16, %17, %18, %19, %20, %21, %22, %23, %24, %25, %26, %27, %28, %29, %30, %31, %32, %33, %34, %35, %36, %37, %38, %39, %40, %41, %42, %43, %44, %45, %46, %47}, {%52, %53, %54, %55}, tb, p1, 1, 1, 1;\n"
        "add.s64 tb, tb0, 1568;\n"
        "wgmma.mma_async.sync.aligned.m64n96k16.f32.bf16.bf16 {%0, %1, %2, %3, %4, %5, %6, %7, %8, %9, %10, %11, %12, %13, %14, %15, %16, %17, %18, %19, %20, %21, %22, %23, %24, %25, %26, %27, %28, %29, %30, %31, %32, %33, %34, %35, %36, %37, %38, %39, %40, %41, %42, %43, %44, %45, %46, %47}, {%56, %57, %58, %59}, tb, p1, 1, 1, 1;\n"
        "add.s64 tb, tb0, 1600;\n"
        "wgmma.mma_async.sync.aligned.m64n96k16.f32.bf16.bf16 {%0, %1, %2, %3, %4, %5, %6, %7, %8, %9, %10, %11, %12, %13, %14, %15, %16, %17, %18, %19, %20, %21, %22, %23, %24, %25, %26, %27, %28, %29, %30, %31, %32, %33, %34, %35, %36, %37, %38, %39, %40, %41, %42, %43, %44, %45, %46, %47}, {%60, %61, %62, %63}, tb, p1, 1, 1, 1;\n"
        "}\n"
        : "+f"(d[0]), "+f"(d[1]), "+f"(d[2]), "+f"(d[3]), "+f"(d[4]), "+f"(d[5]), "+f"(d[6]), "+f"(d[7]), "+f"(d[8]), "+f"(d[9]), "+f"(d[10]), "+f"(d[11]), "+f"(d[12]), "+f"(d[13]), "+f"(d[14]), "+f"(d[15]), "+f"(d[16]), "+f"(d[17]), "+f"(d[18]), "+f"(d[19]), "+f"(d[20]), "+f"(d[21]), "+f"(d[22]), "+f"(d[23]), "+f"(d[24]), "+f"(d[25]), "+f"(d[26]), "+f"(d[27]), "+f"(d[28]), "+f"(d[29]), "+f"(d[30]), "+f"(d[31]), "+f"(d[32]), "+f"(d[33]), "+f"(d[34]), "+f"(d[35]), "+f"(d[36]), "+f"(d[37]), "+f"(d[38]), "+f"(d[39]), "+f"(d[40]), "+f"(d[41]), "+f"(d[42]), "+f"(d[43]), "+f"(d[44]), "+f"(d[45]), "+f"(d[46]), "+f"(d[47])
        : "r"(a[AOFF + 0][0]), "r"(a[AOFF + 0][1]), "r"(a[AOFF + 0][2]), "r"(a[AOFF + 0][3]), "r"(a[AOFF + 1][0]), "r"(a[AOFF + 1][1]), "r"(a[AOFF + 1][2]), "r"(a[AOFF + 1][3]), "r"(a[AOFF + 2][0]), "r"(a[AOFF + 2][1]), "r"(a[AOFF + 2][2]), "r"(a[AOFF + 2][3]), "r"(a[AOFF + 3][0]), "r"(a[AOFF + 3][1]), "r"(a[AOFF + 3][2]), "r"(a[AOFF + 3][3]), "l"(descB), "n"(BOFF >> 4));
}
};
template <> struct Rng<1, 3, 7> {
template <int BOFF, int AOFF, int NA>
static __device__ __forceinline__ void run(float (&d)[48], const uint32_t (&a)[NA][4], uint64_t descB) {
    asm volatile(
        "{\n"
        ".reg .pred p0, p1;\n"
        ".reg .b64 ta, ta0, tb, tb0;\n"
        "setp.ne.b32 p0, 0, 0;\n"
        "setp.eq.b32 p1, 0, 0;\n"
        "add.s64 tb0, %64, %65;\n"
        "add.s64 tb, tb0, 96;\n"
        "wgmma.mma_async.sync.aligned.m64n96k16.f32.bf16.bf16 {%0, %1, %2, %3, %4, %5, %6, %7, %8, %9, %10, %11, %12, %13, %14, %15, %16, %17, %18, %19, %20, %21, %22, %23, %24, %25, %26, %27, %28, %29, %30, %31, %32, %33, %34, %35, %36, %37, %38, %39, %40, %41, %42, %43, %44, %45, %46, %47}, {%48, %49, %50, %51}, tb, p1, 1, 1, 1;\n"
        "add.s64 tb, tb0, 128;\n"
        "wgmma.mma_async.sync.aligned.m64n96k16.f32.bf16.bf16 {%0, %1, %2, %3, %4, %5, %6, %7, %8, %9, %10, %11, %12, %13, %14, %15, %16, %17, %18, %19, %20, %21, %22, %23, %24, %25, %26, %27, %28, %29, %30, %31, %32, %33, %34, %35, %36, %37, %38, %39, %40, %41, %42, %43, %44, %45, %46, %47}, {%52, %53, %54, %55}, tb, p1, 1, 1, 1;\n"
        "add.s64 tb, tb0, 160;\n"
        "wgmma.mma_async.sync.aligned.m64n96k16.f32.bf16.bf16 {%0, %1, %2, %3, %4, %5, %6, %7, %8, %9, %10, %11, %12, %13, %14, %15, %16, %17, %18, %19, %20, %21, %22, %23, %24, %25, %26, %27, %28, %29, %30, %31, %32, %33, %34, %35, %36, %37, %38, %39, %40, %41, %42, %43, %44, %45, %46, %47}, {%56, %57, %58, %59}, tb, p1, 1, 1, 1;\n"
        "add.s64 tb, tb0, 192;\n"
        "wgmma.mma_async.sync.aligned.m64n96k16.f32.bf16.bf16 {%0, %1, %2, %3, %4, %5, %6, %7, %8, %9, %10, %11, %12, %13, %14, %15, %16, %17, %18, %19, %20, %21, %22, %23, %24, %25, %26, %27, %28, %29, %30, %31, %32, %33, %34, %35, %36, %37, %38, %39, %40, %41, %42, %43, %44, %45, %46, %47}, {%60, %61, %62, %63}, tb, p1, 1, 1, 1;\n"
        "}\n"
        : "+f"(d[0]), "+f"(d[1]), "+f"(d[2]), "+f"(d[3]), "+f"(d[4]), "+f"(d[5]), "+f"(d[6]), "+f"(d[7]), "+f"(d[8]), "+f"(d[9]), "+f"(d[10]), "+f"(d[11]), "+f"(d[12]), "+f"(d[13]), "+f"(d[14]), "+f"(d[15]), "+f"(d[16]), "+f"(d[17]), "+f"(d[18]), "+f"(d[19]), "+f"(d[20]), "+f"(d[21]), "+f"(d[22]), "+f"(d[23]), "+f"(d[24]), "+f"(d[25]), "+f"(d[26]), "+f"(d[27]), "+f"(d[28]), "+f"(d[29]), "+f"(d[30]), "+f"(d[31]), "+f"(d[32]), "+f"(d[33]), "+f"(d[34]), "+f"(d[35]), "+f"(d[36]), "+f"(d[37]), "+f"(d[38]), "+f"(d[39]), "+f"(d[40]), "+f"(d[41]), "+f"(d[42]), "+f"(d[43]), "+f"(d[44]), "+f"(d[45]), "+f"(d[46]), "+f"(d[47])
        : "r"(a[AOFF + 0][0]), "r"(a[AOFF + 0][1]), "r"(a[AOFF + 0][2]), "r"(a[AOFF + 0][3]), "r"(a[AOFF + 1][0]), "r"(a[AOFF + 1][1]), "r"(a[AOFF + 1][2]), "r"(a[AOFF + 1][3]), "r"(a[AOFF + 2][0]), "r"(a[AOFF + 2][1]), "r"(a[AOFF + 2][2]), "r"(a[AOFF + 2][3]), "r"(a[AOFF + 3][0]), "r"(a[AOFF + 3][1]), "r"(a[AOFF + 3][2]), "r"(a[AOFF + 3][3]), "l"(descB), "n"(BOFF >> 4));
}
};
template <> struct Rng<0, 3, 8> {
template <int BOFF, int AOFF, int NA>
static __device__ __forceinline__ void run(float (&d)[48], const uint32_t (&a)[NA][4], uint64_t descB) {
    asm volatile(
        "{\n"
        ".reg .pred p0, p1;\n"
        ".reg .b64 ta, ta0, tb, tb0;\n"
        "setp.ne.b32 p0, 0, 0;\n"
        "setp.eq.b32 p1, 0, 0;\n"
        "add.s64 tb0, %68, %69;\n"
        "add.s64 tb, tb0, 96;\n"
        "wgmma.mma_async.sync.aligned.m64n96k16.f32.bf16.bf16 {%0, %1, %2, %3, %4, %5, %6, %7, %8, %9, %10, %11, %12, %13, %14, %15, %16, %17, %18, %19, %20, %21, %22, %23, %24, %25, %26, %27, %28, %29, %30, %31, %32, %33, %34, %35, %36, %37, %38, %39, %40, %41, %42, %43, %44, %45, %46, %47}, {%48, %49, %50, %51}, tb, p1, 1, 1, 1;\n"
        "add.s64 tb, tb0, 1536;\n"
        "wgmma.mma_async.sync.aligned.m64n96k16.f32.bf16.bf16 {%0, %1, %2, %3, %4, %5, %6, %7, %8, %9, %10, %11, %12, %13, %14, %15, %16, %17, %18, %19, %20, %21, %22, %23, %24, %25, %26, %27, %28, %29, %30, %31, %32, %33, %34, %35, %36, %37, %38, %39, %40, %41, %42, %43, %44, %45, %46, %47}, {%52, %53, %54, %55}, tb, p1, 1, 1, 1;\n"
        "add.s64 tb, tb0, 1568;\n"
        "wgmma.mma_async.sync.aligned.m64n96k16.f32.bf16.bf16 {%0, %1, %2, %3, %4, %5, %6, %7, %8, %9, %10, %11, %12, %13, %14, %15, %16, %17, %18, %19, %20, %21, %22, %23, %24, %25, %26, %27, %28, %29, %30, %31, %32, %33, %34, %35, %36, %37, %38, %39, %40, %41, %42, %43, %44, %45, %46, %47}, {%56, %57, %58, %59}, tb, p1, 1, 1, 1;\n"
        "add.s64 tb, tb0, 1600;\n"
        "wgmma.mma_async.sync.aligned.m64n96k16.f32.bf16.bf16 {%0, %1, %2, %3, %4, %5, %6, %7, %8, %9, %10, %11, %12, %13, %14, %15, %16, %17, %18, %19, %20, %21, %22, %23, %24, %25, %26, %27, %28, %29, %30, %31, %32, %33, %34, %35, %36, %37, %38, %39, %40, %41, %42, %43, %44, %45, %46, %47}, {%60, %61, %62, %63}, tb, p1, 1, 1, 1;\n"
        "add.s64 tb, tb0, 1632;\n"
        "wgmma.mma_async.sync.aligned.m64n96k16.f32.bf16.bf16 {%0, %1, %2, %3, %4, %5, %6, %7, %8, %9, %10, %11, %12, %13, %14, %15, %16, %17, %18, %19, %20, %21, %22, %23, %24, %25, %26, %27, %28, %29, %30, %31, %32, %33, %34, %35, %36, %37, %38, %39, %40, %41, %42, %43, %44, %45, %46, %47}, {%64, %65, %66, %67}, tb, p1, 1, 1, 1;\n"
        "}\n"
        : "+f"(d[0]), "+f"(d[1]), "+f"(d[2]), "+f"(d[3]), "+f"(d[4]), "+f"(d[5]), "+f"(d[6]), "+f"(d[7]), "+f"(d[8]), "+f"(d[9]), "+f"(d[10]), "+f"(d[11]), "+f"(d[12]), "+f"(d[13]), "+f"(d[14]), "+f"(d[15]), "+f"(d[16]), "+f"(d[17]), "+f"(d[18]), "+f"(d[19]), "+f"(d[20]), "+f"(d[21]), "+f"(d[22]), "+f"(d[23]), "+f"(d[24]), "+f"(d[25]), "+f"(d[26]), "+f"(d[27]), "+f"(d[28]), "+f"(d[29]), "+f"(d[30]), "+f"(d[31]), "+f"(d[32]), "+f"(d[33]), "+f"(d[34]), "+f"(d[35]), "+f"(d[36]), "+f"(d[37]), "+f"(d[38]), "+f"(d[39]), "+f"(d[40]), "+f"(d[41]), "+f"(d[42]), "+f"(d[43]), "+f"(d[44]), "+f"(d[45]), "+f"(d[46]), "+f"(d[47])
        : "r"(a[AOFF + 0][0]), "r"(a[AOFF + 0][1]), "r"(a[AOFF + 0][2]), "r"(a[AOFF + 0][3]), "r"(a[AOFF + 1][0]), "r"(a[AOFF + 1][1]), "r"(a[AOFF + 1][2]), "r"(a[AOFF + 1][3]), "r"(a[AOFF + 2][0]), "r"(a[AOFF + 2][1]), "r"(a[AOFF + 2][2]), "r"(a[AOFF + 2][3]), "r"(a[AOFF + 3][0]), "r"(a[AOFF + 3][1]), "r"(a[AOFF + 3][2]), "r"(a[AOFF + 3][3]), "r"(a[AOFF + 4][0]), "r"(a[AOFF + 4][1]), "r"(a[AOFF + 4][2]), "r"(a[AOFF + 4][3]), "l"(descB), "n"(BOFF >> 4));
}
};
template <> struct Rng<1, 3, 8> {
template <int BOFF, int AOFF, int NA>
static __device__ __forceinline__ void run(float (&d)[48], const uint32_t (&a)[NA][4], uint64_t descB) {
    asm volatile(
        "{\n"
        ".reg .pred p0, p1;\n"
        ".reg .b64 ta, ta0, tb, tb0;\n"
        "setp.ne.b32 p0, 0, 0;\n"
        "setp.eq.b32 p1, 0, 0;\n"
        "add.s64 tb0, %68, %69;\n"
        "add.s64 tb, tb0, 96;\n"
        "wgmma.mma_async.sync.aligned.m64n96k16.f32.bf16.bf16 {%0, %1, %2, %3, %4, %5, %6, %7, %8, %9, %10, %11, %12, %13, %14, %15, %16, %17, %18, %19, %20, %21, %22, %23, %24, %25, %26, %27, %28, %29, %30, %31, %32, %33, %34, %35, %36, %37, %38, %39, %40, %41, %42, %43, %44, %45, %46, %47}, {%48, %49, %50, %51}, tb, p1, 1, 1, 1;\n"
        "add.s64 tb, tb0, 128;\n"
        "wgmma.mma_async.sync.aligned.m64n96k16.f32.bf16.bf16 {%0, %1, %2, %3, %4, %5, %6, %7, %8, %9, %10, %11, %12, %13, %14, %15, %16, %17, %18, %19, %20, %21, %22, %23, %24, %25, %26, %27, %28, %29, %30, %31, %32, %33, %34, %35, %36, %37, %38, %39, %40, %41, %42, %43, %44, %45, %46, %47}, {%52, %53, %54, %55}, tb, p1, 1, 1, 1;\n"
        "add.s64 tb, tb0, 160;\n"
        "wgmma.mma_async.sync.aligned.m64n96k16.f32.bf16.bf16 {%0, %1, %2, %3, %4, %5, %6, %7, %8, %9, %10, %11, %12, %13, %14, %15, %16, %17, %18, %19, %20, %21, %22, %23, %24, %25, %26, %27, %28, %29, %30, %31, %32, %33, %34, %35, %36, %37, %38, %39, %40, %41, %42, %43, %44, %45, %46, %47}, {%56, %57, %58, %59}, tb, p1, 1, 1, 1;\n"
        "add.s64 tb, tb0, 192;\n"
        "wgmma.mma_async.sync.aligned.m64n96k16.f32.bf16.bf16 {%0, %1, %2, %3, %4, %5, %6, %7, %8, %9, %10, %11, %12, %13, %14, %15, %16, %17, %18, %19, %20, %21, %22, %23, %24, %25, %26, %27, %28, %29, %30, %31, %32, %33, %34, %35, %36, %37, %38, %39, %40, %41, %42, %43, %44, %45, %46, %47}, {%60, %61, %62, %63}, tb, p1, 1, 1, 1;\n"
        "add.s64 tb, tb0, 224;\n"
        "wgmma.mma_async.sync.aligned.m64n96k16.f32.bf16.bf16 {%0, %1, %2, %3, %4, %5, %6, %7, %8, %9, %10, %11, %12, %13, %14, %15, %16, %17, %18, %19, %20, %21, %22, %23, %24, %25, %26, %27, %28, %29, %30, %31, %32, %33, %34, %35, %36, %37, %38, %39, %40, %41, %42, %43, %44, %45, %46, %47}, {%64, %65, %66, %67}, tb, p1, 1, 1, 1;\n"
        "}\n"
        : "+f"(d[0]), "+f"(d[1]), "+f"(d[2]), "+f"(d[3]), "+f"(d[4]), "+f"(d[5]), "+f"(d[6]), "+f"(d[7]), "+f"(d[8]), "+f"(d[9]), "+f"(d[10]), "+f"(d[11]), "+f"(d[12]), "+f"(d[13]), "+f"(d[14]), "+f"(d[15]), "+f"(d[16]), "+f"(d[17]), "+f"(d[18]), "+f"(d[19]), "+f"(d[20]), "+f"(d[21]), "+f"(d[22]), "+f"(d[23]), "+f"(d[24]), "+f"(d[25]), "+f"(d[26]), "+f"(d[27]), "+f"(d[28]), "+f"(d[29]), "+f"(d[30]), "+f"(d[31]), "+f"(d[32]), "+f"(d[33]), "+f"(d[34]), "+f"(d[35]), "+f"(d[36]), "+f"(d[37]), "+f"(d[38]), "+f"(d[39]), "+f"(d[40]), "+f"(d[41]), "+f"(d[42]), "+f"(d[43]), "+f"(d[44]), "+f"(d[45]), "+f"(d[46]), "+f"(d[47])
        : "r"(a[AOFF + 0][0]), "r"(a[AOFF + 0][1]), "r"(a[AOFF + 0][2]), "r"(a[AOFF + 0][3]), "r"(a[AOFF + 1][0]), "r"(a[AOFF + 1][1]), "r"(a[AOFF + 1][2]), "r"(a[AOFF + 1][3]), "r"(a[AOFF + 2][0]), "r"(a[AOFF + 2][1]), "r"(a[AOFF + 2][2]), "r"(a[AOFF + 2][3]), "r"(a[AOFF + 3][0]), "r"(a[AOFF + 3][1]), "r"(a[AOFF + 3][2]), "r"(a[AOFF + 3][3]), "r"(a[AOFF + 4][0]), "r"(a[AOFF + 4][1]), "r"(a[AOFF + 4][2]), "r"(a[AOFF + 4][3]), "l"(descB), "n"(BOFF >> 4));
}
};
template <> struct Rng<0, 3, 12> {
template <int BOFF, int AOFF, int NA>
static __device__ __forceinline__ void run(float (&d)[48], const uint32_t (&a)[NA][4], uint64_t descB) {
    asm volatile(
        "{\n"
        ".reg .pred p0, p1;\n"
        ".reg .b64 ta, ta0, tb, tb0;\n"
        "setp.ne.b32 p0, 0, 0;\n"
        "setp.eq.b32 p1, 0, 0;\n"
        "add.s64 tb0, %84, %85;\n"
        "add.s64 tb, tb0, 96;\n"
        "wgmma.mma_async.sync.aligned.m64n96k16.f32.bf16.bf16 {%0, %1, %2, %3, %4, %5, %6, %7, %8, %9, %10, %11, %12, %13, %14, %15, %16, %17, %18, %19, %20, %21, %22, %23, %24, %25, %26, %27, %28, %29, %30, %31, %32, %33, %34, %35, %36, %37, %38, %39, %40, %41, %42, %43, %44, %45, %46, %47}, {%48, %49, %50, %51}, tb, p1, 1, 1, 1;\n"
        "add.s64 tb, tb0, 1536;\n"
        "wgmma.mma_async.sync.aligned.m64n96k16.f32.bf16.bf16 {%0, %1, %2, %3, %4, %5, %6, %7, %8, %9, %10, %11, %12, %13, %14, %15, %16, %17, %18, %19, %20, %21, %22, %23, %24, %25, %26, %27, %28, %29, %30, %31, %32, %33, %34, %35, %36, %37, %38, %39, %40, %41, %42, %43, %44, %45, %46, %47}, {%52, %53, %54, %55}, tb, p1, 1, 1, 1;\n"
        "add.s64 tb, tb0, 1568;\n"
        "wgmma.mma_async.sync.aligned.m64n96k16.f32.bf16.bf16 {%0, %1, %2, %3, %4, %5, %6, %7, %8, %9, %10, %11, %12, %13, %14, %15, %16, %17, %18, %19, %20, %21, %22, %23, %24, %25, %26, %27, %28, %29, %30, %31, %32, %33, %34, %35, %36, %37, %38, %39, %40, %41, %42, %43, %44, %45, %46, %47}, {%56, %57, %58, %59}, tb, p1, 1, 1, 1;\n"
        "add.s64 tb, tb0, 1600;\n"
        "wgmma.mma_async.sync.aligned.m64n96k16.f32.bf16.bf16 {%0, %1, %2, %3, %4, %5, %6, %7, %8, %9, %10, %11, %12, %13, %14, %15, %16, %17, %18, %19, %20, %21, %22, %23, %24, %25, %26, %27, %28, %29, %30, %31, %32, %33, %34, %35, %36, %37, %38, %39, %40, %41, %42, %43, %44, %45, %46, %47}, {%60, %61, %62, %63}, tb, p1, 1, 1, 1;\n"
        "add.s64 tb, tb0, 1632;\n"
        "wgmma.mma_async.sync.aligned.m64n96k16.f32.bf16.bf16 {%0, %1, %2, %3, %4, %5, %6, %7, %8, %9, %10, %11, %12, %13, %14, %15, %16, %17, %18, %19, %20, %21, %22, %23, %24, %25, %26, %27, %28, %29, %30, %31, %32, %33, %34, %35, %36, %37, %38, %39, %40, %41, %42, %43, %44, %45, %46, %47}, {%64, %65, %66, %67}, tb, p1, 1, 1, 1;\n"
        "add.s64 tb, tb0, 3072;\n"
        "wgmma.mma_async.sync.aligned.m64n96k16.f32.bf16.bf16 {%0, %1, %2, %3, %4, %5, %6, %7, %8, %9, %10, %11, %12, %13, %14, %15, %16, %17, %18, %19, %20, %21, %22, %23, %24, %25, %26, %27, %28, %29, %30, %31, %32, %33, %34, %35, %36, %37, %38, %39, %40, %41, %42, %43, %44, %45, %46, %47}, {%68, %69, %70, %71}, tb, p1, 1, 1, 1;\n"
        "add.s64 tb, tb0, 3104;\n"
        "wgmma.mma_async.sync.aligned.m64n96k16.f32.bf16.bf16 {%0, %1, %2, %3, %4, %5, %6, %7, %8, %9, %10, %11, %12, %13, %14, %15, %16, %17, %18, %19, %20, %21, %22, %23, %24, %25, %26, %27, %28, %29, %30, %31, %32, %33, %34, %35, %36, %37, %38, %39, %40, %41, %42, %43, %44, %45, %46, %47}, {%72, %73, %74, %75}, tb, p1, 1, 1, 1;\n"
        "add.s64 tb, tb0, 3136;\n"
        "wgmma.mma_async.sync.aligned.m64n96k16.f32.bf16.bf16 {%0, %1, %2, %3, %4, %5, %6, %7, %8, %9, %10, %11, %12, %13, %14, %15, %16, %17, %18, %19, %20, %21, %22, %23, %24, %25, %26, %27, %28, %29, %30, %31, %32, %33, %34, %35, %36, %37, %38, %39, %40, %41, %42, %43, %44, %45, %46, %47}, {%76, %77, %78, %79}, tb, p1, 1, 1, 1;\n"
        "add.s64 tb, tb0, 3168;\n"
        "wgmma.mma_async.sync.aligned.m64n96k16.f32.bf16.bf16 {%0, %1, %2, %3, %4, %5, %6, %7, %8, %9, %10, %11, %12, %13, %14, %15, %16, %17, %18, %19, %20, %21, %22, %23, %24, %25, %26, %27, %28, %29, %30, %31, %32, %33, %34, %35, %36, %37, %38, %39, %40, %41, %42, %43, %44, %45, %46, %47}, {%80, %81, %82, %83}, tb, p1, 1, 1, 1;\n"
        "}\n"
        : "+f"(d[0]), "+f"(d[1]), "+f"(d[2]), "+f"(d[3]), "+f"(d[4]), "+f"(d[5]), "+f"(d[6]), "+f"(d[7]), "+f"(d[8]), "+f"(d[9]), "+f"(d[10]), "+f"(d[11]), "+f"(d[12]), "+f"(d[13]), "+f"(d[14]), "+f"(d[15]), "+f"(d[16]), "+f"(d[17]), "+f"(d[18]), "+f"(d[19]), "+f"(d[20]), "+f"(d[21]), "+f"(d[22]), "+f"(d[23]), "+f"(d[24]), "+f"(d[25]), "+f"(d[26]), "+f"(d[27]), "+f"(d[28]), "+f"(d[29]), "+f"(d[30]), "+f"(d[31]), "+f"(d[32]), "+f"(d[33]), "+f"(d[34]), "+f"(d[35]), "+f"(d[36]), "+f"(d[37]), "+f"(d[38]), "+f"(d[39]), "+f"(d[40]), "+f"(d[41]), "+f"(d[42]), "+f"(d[43]), "+f"(d[44]), "+f"(d[45]), "+f"(d[46]), "+f"(d[47])
        : "r"(a[AOFF + 0][0]), "r"(a[AOFF + 0][1]), "r"(a[AOFF + 0][2]), "r"(a[AOFF + 0][3]), "r"(a[AOFF + 1][0]), "r"(a[AOFF + 1][1]), "r"(a[AOFF + 1][2]), "r"(a[AOFF + 1][3]), "r"(a[AOFF + 2][0]), "r"(a[AOFF + 2][1]), "r"(a[AOFF + 2][2]), "r"(a[AOFF + 2][3]), "r"(a[AOFF + 3][0]), "r"(a[AOFF + 3][1]), "r"(a[AOFF + 3][2]), "r"(a[AOFF + 3][3]), "r"(a[AOFF + 4][0]), "r"(a[AOFF + 4][1]), "r"(a[AOFF + 4][2]), "r"(a[AOFF + 4][3]), "r"(a[AOFF + 5][0]), "r"(a[AOFF + 5][1]), "r"(a[AOFF + 5][2]), "r"(a[AOFF + 5][3]), "r"(a[AOFF + 6][0]), "r"(a[AOFF + 6][1]), "r"(a[AOFF + 6][2]), "r"(a[AOFF + 6][3]), "r"(a[AOFF + 7][0]), "r"(a[AOFF + 7][1]), "r"(a[AOFF + 7][2]), "r"(a[AOFF + 7][3]), "r"(a[AOFF + 8][0]), "r"(a[AOFF + 8][1]), "r"(a[AOFF + 8][2]), "r"(a[AOFF + 8][3]), "l"(descB), "n"(BOFF >> 4));
}
};
template <> struct Rng<1, 3, 12> {
template <int BOFF, int AOFF, int NA>
static __device__ __forceinline__ void run(float (&d)[48], const uint32_t (&a)[NA][4], uint64_t descB) {
    asm volatile(
        "{\n"
        ".reg .pred p0, p1;\n"
        ".reg .b64 ta, ta0, tb, tb0;\n"
        "setp.ne.b32 p0, 0, 0;\n"
        "setp.eq.b32 p1, 0, 0;\n"
        "add.s64 tb0, %84, %85;\n"
        "add.s64 tb, tb0, 96;\n"
        "wgmma.mma_async.sync.aligned.m64n96k16.f32.bf16.bf16 {%0, %1, %2, %3, %4, %5, %6, %7, %8, %9, %10, %11, %12, %13, %14, %15, %16, %17, %18, %19, %20, %21, %22, %23, %24, %25, %26, %27, %28, %29, %30, %31, %32, %33, %34, %35, %36, %37, %38, %39, %40, %41, %42, %43, %44, %45, %46, %47}, {%48, %49, %50, %51}, tb, p1, 1, 1, 1;\n"
        "add.s64 tb, tb0, 128;\n"
        "wgmma.mma_async.sync.aligned.m64n96k16.f32.bf16.bf16 {%0, %1, %2, %3, %4, %5, %6, %7, %8, %9, %10, %11, %12, %13, %14, %15, %16, %17, %18, %19, %20, %21, %22, %23, %24, %25, %26, %27, %28, %29, %30, %31, %32, %33, %34, %35, %36, %37, %38, %39, %40, %41, %42, %43, %44, %45, %46, %47}, {%52, %53, %54, %55}, tb, p1, 1, 1, 1;\n"
        "add.s64 tb, tb0, 160;\n"
        "wgmma.mma_async.sync.aligned.m64n96k16.f32.bf16.bf16 {%0, %1, %2, %3, %4, %5, %6, %7, %8, %9, %10, %11, %12, %13, %14, %15, %16, %17, %18, %19, %20, %21, %22, %23, %24, %25, %26, %27, %28, %29, %30, %31, %32, %33, %34, %35, %36, %37, %38, %39, %40, %41, %42, %43, %44, %45, %46, %47}, {%56, %57, %58, %59}, tb, p1, 1, 1, 1;\n"
        "add.s64 tb, tb0, 192;\n"
        "wgmma.mma_async.sync.aligned.m64n96k16.f32.bf16.bf16 {%0, %1, %2, %3, %4, %5, %6, %7, %8, %9, %10, %11, %12, %13, %14, %15, %16, %17, %18, %19, %20, %21, %22, %23, %24, %25, %26, %27, %28, %29, %30, %31, %32, %33, %34, %35, %36, %37, %38, %39, %40, %41, %42, %43, %44, %45, %46, %47}, {%60, %61, %62, %63}, tb, p1, 1, 1, 1;\n"
        "add.s64 tb, tb0, 224;\n"
        "wgmma.mma_async.sync.aligned.m64n96k16.f32.bf16.bf16 {%0, %1, %2, %3, %4, %5, %6, %7, %8, %9, %10, %11, %12, %13, %14, %15, %16, %17, %18, %19, %20, %21, %22, %23, %24, %25, %26, %27, %28, %29, %30, %31, %32, %33, %34, %35, %36, %37, %38, %39, %40, %41, %42, %43, %44, %45, %46, %47}, {%64, %65, %66, %67}, tb, p1, 1, 1, 1;\n"
        "add.s64 tb, tb0, 256;\n"
        "wgmma.mma_async.sync.aligned.m64n96k16.f32.bf16.bf16 {%0, %1, %2, %3, %4, %5, %6, %7, %8, %9, %10, %11, %12, %13, %14, %15, %16, %17, %18, %19, %20, %21, %22, %23, %24, %25, %26, %27, %28, %29, %30, %31, %32, %33, %34, %35, %36, %37, %38, %39, %40, %41, %42, %43, %44, %45, %46, %47}, {%68, %69, %70, %71}, tb, p1, 1, 1, 1;\n"
        "add.s64 tb, tb0, 288;\n"
        "wgmma.mma_async.sync.aligned.m64n96k16.f32.bf16.bf16 {%0, %1, %2, %3, %4, %5, %6, %7, %8, %9, %10, %11, %12, %13, %14, %15, %16, %17, %18, %19, %20, %21, %22, %23, %24, %25, %26, %27, %28, %29, %30, %31, %32, %33, %34, %35, %36, %37, %38, %39, %40, %41, %42, %43, %44, %45, %46, %47}, {%72, %73, %74, %75}, tb, p1, 1, 1, 1;\n"
        "add.s64 tb, tb0, 320;\n"
        "wgmma.mma_async.sync.aligned.m64n96k16.f32.bf16.bf16 {%0, %1, %2, %3, %4, %5, %6, %7, %8, %9, %10, %11, %12, %13, %14, %15, %16, %17, %18, %19, %20, %21, %22, %23, %24, %25, %26, %27, %28, %29, %30, %31, %32, %33, %34, %35, %36, %37, %38, %39, %40, %41, %42, %43, %44, %45, %46, %47}, {%76, %77, %78, %79}, tb, p1, 1, 1, 1;\n"
        "add.s64 tb, tb0, 352;\n"
        "wgmma.mma_async.sync.aligned.m64n96k16.f32.bf16.bf16 {%0, %1, %2, %3, %4, %5, %6, %7, %8, %9, %10, %11, %12, %13, %14, %15, %16, %17, %18, %19, %20, %21, %22, %23, %24, %25, %26, %27, %28, %29, %30, %31, %32, %33, %34, %35, %36, %37, %38, %39, %40, %41, %42, %43, %44, %45, %46, %47}, {%80, %81, %82, %83}, tb, p1, 1, 1, 1;\n"
        "}\n"
        : "+f"(d[0]), "+f"(d[1]), "+f"(d[2]), "+f"(d[3]), "+f"(d[4]), "+f"(d[5]), "+f"(d[6]), "+f"(d[7]), "+f"(d[8]), "+f"(d[9]), "+f"(d[10]), "+f"(d[11]), "+f"(d[12]), "+f"(d[13]), "+f"(d[14]), "+f"(d[15]), "+f"(d[16]), "+f"(d[17]), "+f"(d[18]), "+f"(d[19]), "+f"(d[20]), "+f"(d[21]), "+f"(d[22]), "+f"(d[23]), "+f"(d[24]), "+f"(d[25]), "+f"(d[26]), "+f"(d[27]), "+f"(d[28]), "+f"(d[29]), "+f"(d[30]), "+f"(d[31]), "+f"(d[32]), "+f"(d[33]), "+f"(d[34]), "+f"(d[35]), "+f"(d[36]), "+f"(d[37]), "+f"(d[38]), "+f"(d[39]), "+f"(d[40]), "+f"(d[41]), "+f"(d[42]), "+f"(d[43]), "+f"(d[44]), "+f"(d[45]), "+f"(d[46]), "+f"(d[47])
        : "r"(a[AOFF + 0][0]), "r"(a[AOFF + 0][1]), "r"(a[AOFF + 0][2]), "r"(a[AOFF + 0][3]), "r"(a[AOFF + 1][0]), "r"(a[AOFF + 1][1]), "r"(a[AOFF + 1][2]), "r"(a[AOFF + 1][3]), "r"(a[AOFF + 2][0]), "r"(a[AOFF + 2][1]), "r"(a[AOFF + 2][2]), "r"(a[AOFF + 2][3]), "r"(a[AOFF + 3][0]), "r"(a[AOFF + 3][1]), "r"(a[AOFF + 3][2]), "r"(a[AOFF + 3][3]), "r"(a[AOFF + 4][0]), "r"(a[AOFF + 4][1]), "r"(a[AOFF + 4][2]), "r"(a[AOFF + 4][3]), "r"(a[AOFF + 5][0]), "r"(a[AOFF + 5][1]), "r"(a[AOFF + 5][2]), "r"(a[AOFF + 5][3]), "r"(a[AOFF + 6][0]), "r"(a[AOFF + 6][1]), "r"(a[AOFF + 6][2]), "r"(a[AOFF + 6][3]), "r"(a[AOFF + 7][0]), "r"(a[AOFF + 7][1]), "r"(a[AOFF + 7][2]), "r"(a[AOFF + 7][3]), "r"(a[AOFF + 8][0]), "r"(a[AOFF + 8][1]), "r"(a[AOFF + 8][2]), "r"(a[AOFF + 8][3]), "l"(descB), "n"(BOFF >> 4));
}
};
template <> struct Rng<0, 4, 6> {
template <int BOFF, int AOFF, int NA>
static __device__ __forceinline__ void run(float (&d)[48], const uint32_t (&a)[NA][4], uint64_t descB) {
    asm volatile(
        "{\n"
        ".reg .pred p0, p1;\n"
        ".reg .b64 ta, ta0, tb, tb0;\n"
        "setp.ne.b32 p0, 0, 0;\n"
        "setp.eq.b32 p1, 0, 0;\n"
        "add.s64 tb0, %56, %57;\n"
        "add.s64 tb, tb0, 1536;\n"
        "wgmma.mma_async.sync.aligned.m64n96k16.f32.bf16.bf16 {%0, %1, %2, %3, %4, %5, %6, %7, %8, %9, %10, %11, %12, %13, %14, %15, %16, %17, %18, %19, %20, %21, %22, %23, %24, %25, %26, %27, %28, %29, %30, %31, %32, %33, %34, %35, %36, %37, %38, %39, %40, %41, %42, %43, %44, %45, %46, %47}, {%48, %49, %50, %51}, tb, p1, 1, 1, 1;\n"
        "add.s64 tb, tb0, 1568;\n"
        "wgmma.mma_async.sync.aligned.m64n96k16.f32.bf16.bf16 {%0, %1, %2, %3, %4, %5, %6, %7, %8, %9, %10, %11, %12, %13, %14, %15, %16, %17, %18, %19, %20, %21, %22, %23, %24, %25, %26, %27, %28, %29, %30, %31, %32, %33, %34, %35, %36, %37, %38, %39, %40, %41, %42, %43, %44, %45, %46, %47}, {%52, %53, %54, %55}, tb, p1, 1, 1, 1;\n"
        "}\n"
        : "+f"(d[0]), "+f"(d[1]), "+f"(d[2]), "+f"(d[3]), "+f"(d[4]), "+f"(d[5]), "+f"(d[6]), "+f"(d[7]), "+f"(d[8]), "+f"(d[9]), "+f"(d[10]), "+f"(d[11]), "+f"(d[12]), "+f"(d[13]), "+f"(d[14]), "+f"(d[15]), "+f"(d[16]), "+f"(d[17]), "+f"(d[18]), "+f"(d[19]), "+f"(d[20]), "+f"(d[21]), "+f"(d[22]), "+f"(d[23]), "+f"(d[24]), "+f"(d[25]), "+f"(d[26]), "+f"(d[27]), "+f"(d[28]), "+f"(d[29]), "+f"(d[30]), "+f"(d[31]), "+f"(d[32]), "+f"(d[33]), "+f"(d[34]), "+f"(d[35]), "+f"(d[36]), "+f"(d[37]), "+f"(d[38]), "+f"(d[39]), "+f"(d[40]), "+f"(d[41]), "+f"(d[42]), "+f"(d[43]), "+f"(d[44]), "+f"(d[45]), "+f"(d[46]), "+f"(d[47])
        : "r"(a[AOFF + 0][0]), "r"(a[AOFF + 0][1]), "r"(a[AOFF + 0][2]), "r"(a[AOFF + 0][3]), "r"(a[AOFF + 1][0]), "r"(a[AOFF + 1][1]), "r"(a[AOFF + 1][2]), "r"(a[AOFF + 1][3]), "l"(descB), "n"(BOFF >> 4));
}
};
template <> struct Rng<1, 4, 6> {
template <int BOFF, int AOFF, int NA>
static __device__ __forceinline__ void run(float (&d)[48], const uint32_t (&a)[NA][4], uint64_t descB) {
    asm volatile(
        "{\n"
        ".reg .pred p0, p1;\n"
        ".reg .b64 ta, ta0, tb, tb0;\n"
        "setp.ne.b32 p0, 0, 0;\n"
        "setp.eq.b32 p1, 0, 0;\n"
        "add.s64 tb0, %56, %57;\n"
        "add.s64 tb, tb0, 128;\n"
        "wgmma.mma_async.sync.aligned.m64n96k16.f32.bf16.bf16 {%0, %1, %2, %3, %4, %5, %6, %7, %8, %9, %10, %11, %12, %13, %14, %15, %16, %17, %18, %19, %20, %21, %22, %23, %24, %25, %26, %27, %28, %29, %30, %31, %32, %33, %34, %35, %36, %37, %38, %39, %40, %41, %42, %43, %44, %45, %46, %47}, {%48, %49, %50, %51}, tb, p1, 1, 1, 1;\n"
        "add.s64 tb, tb0, 160;\n"
        "wgmma.mma_async.sync.aligned.m64n96k16.f32.bf16.bf16 {%0, %1, %2, %3, %4, %5, %6, %7, %8, %9, %10, %11, %12, %13, %14, %15, %16, %17, %18, %19, %20, %21, %22, %23, %24, %25, %26, %27, %28, %29, %30, %31, %32, %33, %34, %35, %36, %37, %38, %39, %40, %41, %42, %43, %44, %45, %46, %47}, {%52, %53, %54, %55}, tb, p1, 1, 1, 1;\n"
        "}\n"
        : "+f"(d[0]), "+f"(d[1]), "+f"(d[2]), "+f"(d[3]), "+f"(d[4]), "+f"(d[5]), "+f"(d[6]), "+f"(d[7]), "+f"(d[8]), "+f"(d[9]), "+f"(d[10]), "+f"(d[11]), "+f"(d[12]), "+f"(d[13]), "+f"(d[14]), "+f"(d[15]), "+f"(d[16]), "+f"(d[17]), "+f"(d[18]), "+f"(d[19]), "+f"(d[20]), "+f"(d[21]), "+f"(d[22]), "+f"(d[23]), "+f"(d[24]), "+f"(d[25]), "+f"(d[26]), "+f"(d[27]), "+f"(d[28]), "+f"(d[29]), "+f"(d[30]), "+f"(d[31]), "+f"(d[32]), "+f"(d[33]), "+f"(d[34]), "+f"(d[35]), "+f"(d[36]), "+f"(d[37]), "+f"(d[38]), "+f"(d[39]), "+f"(d[40]), "+f"(d[41]), "+f"(d[42]), "+f"(d[43]), "+f"(d[44]), "+f"(d[45]), "+f"(d[46]), "+f"(d[47])
        : "r"(a[AOFF + 0][0]), "r"(a[AOFF + 0][1]), "r"(a[AOFF + 0][2]), "r"(a[AOFF + 0][3]), "r"(a[AOFF + 1][0]), "r"(a[AOFF + 1][1]), "r"(a[AOFF + 1][2]), "r"(a[AOFF + 1][3]), "l"(descB), "n"(BOFF >> 4));
}
};
template <> struct Rng<0, 4, 7> {
template <int BOFF, int AOFF, int NA>
static __device__ __forceinline__ void run(float (&d)[48], const uint32_t (&a)[NA][4], uint64_t descB) {
    asm volatile(
        "{\n"
        ".reg .pred p0, p1;\n"
        ".reg .b64 ta, ta0, tb, tb0;\n"
        "setp.ne.b32 p0, 0, 0;\n"
        "setp.eq.b32 p1, 0, 0;\n"
        "add.s64 tb0, %60, %61;\n"
        "add.s64 tb, tb0, 1536;\n"
        "wgmma.mma_async.sync.aligned.m64n96k16.f32.bf16.bf16 {%0, %1, %2, %3, %4, %5, %6, %7, %8, %9, %10, %11, %12, %13, %14, %15, %16, %17, %18, %19, %20, %21, %22, %23, %24, %25, %26, %27, %28, %29, %30, %31, %32, %33, %34, %35, %36, %37, %38, %39, %40, %41, %42, %43, %44, %45, %46, %47}, {%48, %49, %50, %51}, tb, p1, 1, 1, 1;\n"
        "add.s64 tb, tb0, 1568;\n"
        "wgmma.mma_async.sync.aligned.m64n96k16.f32.bf16.bf16 {%0, %1, %2, %3, %4, %5, %6, %7, %8, %9, %10, %11, %12, %13, %14, %15, %16, %17, %18, %19, %20, %21, %22, %23, %24, %25, %26, %27, %28, %29, %30, %31, %32, %33, %34, %35, %36, %37, %38, %39, %40, %41, %42, %43, %44, %45, %46, %47}, {%52, %53, %54, %55}, tb, p1, 1, 1, 1;\n"
        "add.s64 tb, tb0, 1600;\n"
        "wgmma.mma_async.sync.aligned.m64n96k16.f32.bf16.bf16 {%0, %1, %2, %3, %4, %5, %6, %7, %8, %9, %10, %11, %12, %13, %14, %15, %16, %17, %18, %19, %20, %21, %22, %23, %24, %25, %26, %27, %28, %29, %30, %31, %32, %33, %34, %35, %36, %37, %38, %39, %40, %41, %42, %43, %44, %45, %46, %47}, {%56, %57, %58, %59}, tb, p1, 1, 1, 1;\n"
        "}\n"
        : "+f"(d[0]), "+f"(d[1]), "+f"(d[2]), "+f"(d[3]), "+f"(d[4]), "+f"(d[5]), "+f"(d[6]), "+f"(d[7]), "+f"(d[8]), "+f"(d[9]), "+f"(d[10]), "+f"(d[11]), "+f"(d[12]), "+f"(d[13]), "+f"(d[14]), "+f"(d[15]), "+f"(d[16]), "+f"(d[17]), "+f"(d[18]), "+f"(d[19]), "+f"(d[20]), "+f"(d[21]), "+f"(d[22]), "+f"(d[23]), "+f"(d[24]), "+f"(d[25]), "+f"(d[26]), "+f"(d[27]), "+f"(d[28]), "+f"(d[29]), "+f"(d[30]), "+f"(d[31]), "+f"(d[32]), "+f"(d[33]), "+f"(d[34]), "+f"(d[35]), "+f"(d[36]), "+f"(d[37]), "+f"(d[38]), "+f"(d[39]), "+f"(d[40]), "+f"(d[41]), "+f"(d[42]), "+f"(d[43]), "+f"(d[44]), "+f"(d[45]), "+f"(d[46]), "+f"(d[47])
        : "r"(a[AOFF + 0][0]), "r"(a[AOFF + 0][1]), "r"(a[AOFF + 0][2]), "r"(a[AOFF + 0][3]), "r"(a[AOFF + 1][0]), "r"(a[AOFF + 1][1]), "r"(a[AOFF + 1][2]), "r"(a[AOFF + 1][3]), "r"(a[AOFF + 2][0]), "r"(a[AOFF + 2][1]), "r"(a[AOFF + 2][2]), "r"(a[AOFF + 2][3]), "l"(descB), "n"(BOFF >> 4));
}
};
template <> struct Rng<1, 4, 7> {
template <int BOFF, int AOFF, int NA>
static __device__ __forceinline__ void run(float (&d)[48], const uint32_t (&a)[NA][4], uint64_t descB) {
    asm volatile(
        "{\n"
        ".reg .pred p0, p1;\n"
        ".reg .b64 ta, ta0, tb, tb0;\n"
        "setp.ne.b32 p0, 0, 0;\n"
        "setp.eq.b32 p1, 0, 0;\n"
        "add.s64 tb0, %60, %61;\n"
        "add.s64 tb, tb0, 128;\n"
        "wgmma.mma_async.sync.aligned.m64n96k16.f32.bf16.bf16 {%0, %1, %2, %3, %4, %5, %6, %7, %8, %9, %10, %11, %12, %13, %14, %15, %16, %17, %18, %19, %20, %21, %22, %23, %24, %25, %26, %27, %28, %29, %30, %31, %32, %33, %34, %35, %36, %37, %38, %39, %40, %41, %42, %43, %44, %45, %46, %47}, {%48, %49, %50, %51}, tb, p1, 1, 1, 1;\n"
        "add.s64 tb, tb0, 160;\n"
        "wgmma.mma_async.sync.aligned.m64n96k16.f32.bf16.bf16 {%0, %1, %2, %3, %4, %5, %6, %7, %8, %9, %10, %11, %12, %13, %14, %15, %16, %17, %18, %19, %20, %21, %22, %23, %24, %25, %26, %27, %28, %29, %30, %31, %32, %33, %34, %35, %36, %37, %38, %39, %40, %41, %42, %43, %44, %45, %46, %47}, {%52, %53, %54, %55}, tb, p1, 1, 1, 1;\n"
        "add.s64 tb, tb0, 192;\n"
        "wgmma.mma_async.sync.aligned.m64n96k16.f32.bf16.bf16 {%0, %1, %2, %3, %4, %5, %6, %7, %8, %9, %10, %11, %12, %13, %14, %15, %16, %17, %18, %19, %20, %21, %22, %23, %24, %25, %26, %27, %28, %29, %30, %31, %32, %33, %34, %35, %36, %37, %38, %39, %40, %41, %42, %43, %44, %45, %46, %47}, {%56, %57, %58, %59}, tb, p1, 1, 1, 1;\n"
        "}\n"
        : "+f"(d[0]), "+f"(d[1]), "+f"(d[2]), "+f"(d[3]), "+f"(d[4]), "+f"(d[5]), "+f"(d[6]), "+f"(d[7]), "+f"(d[8]), "+f"(d[9]), "+f"(d[10]), "+f"(d[11]), "+f"(d[12]), "+f"(d[13]), "+f"(d[14]), "+f"(d[15]), "+f"(d[16]), "+f"(d[17]), "+f"(d[18]), "+f"(d[19]), "+f"(d[20]), "+f"(d[21]), "+f"(d[22]), "+f"(d[23]), "+f"(d[24]), "+f"(d[25]), "+f"(d[26]), "+f"(d[27]), "+f"(d[28]), "+f"(d[29]), "+f"(d[30]), "+f"(d[31]), "+f"(d[32]), "+f"(d[33]), "+f"(d[34]), "+f"(d[35]), "+f"(d[36]), "+f"(d[37]), "+f"(d[38]), "+f"(d[39]), "+f"(d[40]), "+f"(d[41]), "+f"(d[42]), "+f"(d[43]), "+f"(d[44]), "+f"(d[45]), "+f"(d[46]), "+f"(d[47])
        : "r"(a[AOFF + 0][0]), "r"(a[AOFF + 0][1]), "r"(a[AOFF + 0][2]), "r"(a[AOFF + 0][3]), "r"(a[AOFF + 1][0]), "r"(a[AOFF + 1][1]), "r"(a[AOFF + 1][2]), "r"(a[AOFF + 1][3]), "r"(a[AOFF + 2][0]), "r"(a[AOFF + 2][1]), "r"(a[AOFF + 2][2]), "r"(a[AOFF + 2][3]), "l"(descB), "n"(BOFF >> 4));
}
};
template <> struct Rng<0, 4, 8> {
template <int BOFF, int AOFF, int NA>
static __device__ __forceinline__ void run(float (&d)[48], const uint32_t (&a)[NA][4], uint64_t descB) {
    asm volatile(
        "{\n"
        ".reg .pred p0, p1;\n"
        ".reg .b64 ta, ta0, tb, tb0;\n"
        "setp.ne.b32 p0, 0, 0;\n"
        "setp.eq.b32 p1, 0, 0;\n"
        "add.s64 tb0, %64, %65;\n"
        "add.s64 tb, tb0, 1536;\n"
        "wgmma.mma_async.sync.aligned.m64n96k16.f32.bf16.bf16 {%0, %1, %2, %3, %4, %5, %6, %7, %8, %9, %10, %11, %12, %13, %14, %15, %16, %17, %18, %19, %20, %21, %22, %23, %24, %25, %26, %27, %28, %29, %30, %31, %32, %33, %34, %35, %36, %37, %38, %39, %40, %41, %42, %43, %44, %45, %46, %47}, {%48, %49, %50, %51}, tb, p1, 1, 1, 1;\n"
        "add.s64 tb, tb0, 1568;\n"
        "wgmma.mma_async.sync.aligned.m64n96k16.f32.bf16.bf16 {%0, %1, %2, %3, %4, %5, %6, %7, %8, %9, %10, %11, %12, %13, %14, %15, %16, %17, %18, %19, %20, %21, %22, %23, %24, %25, %26, %27, %28, %29, %30, %31, %32, %33, %34, %35, %36, %37, %38, %39, %40, %41, %42, %43, %44, %45, %46, %47}, {%52, %53, %54, %55}, tb, p1, 1, 1, 1;\n"
        "add.s64 tb, tb0, 1600;\n"
        "wgmma.mma_async.sync.aligned.m64n96k16.f32.bf16.bf16 {%0, %1, %2, %3, %4, %5, %6, %7, %8, %9, %10, %11, %12, %13, %14, %15, %16, %17, %18, %19, %20, %21, %22, %23, %24, %25, %26, %27, %28, %29, %30, %31, %32, %33, %34, %35, %36, %37, %38, %39, %40, %41, %42, %43, %44, %45, %46, %47}, {%56, %57, %58, %59}, tb, p1, 1, 1, 1;\n"
        "add.s64 tb, tb0, 1632;\n"
        "wgmma.mma_async.sync.aligned.m64n96k16.f32.bf16.bf16 {%0, %1, %2, %3, %4, %5, %6, %7, %8, %9, %10, %11, %12, %13, %14, %15, %16, %17, %18, %19, %20, %21, %22, %23, %24, %25, %26, %27, %28, %29, %30, %31, %32, %33, %34, %35, %36, %37, %38, %39, %40, %41, %42, %43, %44, %45, %46, %47}, {%60, %61, %62, %63}, tb, p1, 1, 1, 1;\n"
        "}\n"
        : "+f"(d[0]), "+f"(d[1]), "+f"(d[2]), "+f"(d[3]), "+f"(d[4]), "+f"(d[5]), "+f"(d[6]), "+f"(d[7]), "+f"(d[8]), "+f"(d[9]), "+f"(d[10]), "+f"(d[11]), "+f"(d[12]), "+f"(d[13]), "+f"(d[14]), "+f"(d[15]), "+f"(d[16]), "+f"(d[17]), "+f"(d[18]), "+f"(d[19]), "+f"(d[20]), "+f"(d[21]), "+f"(d[22]), "+f"(d[23]), "+f"(d[24]), "+f"(d[25]), "+f"(d[26]), "+f"(d[27]), "+f"(d[28]), "+f"(d[29]), "+f"(d[30]), "+f"(d[31]), "+f"(d[32]), "+f"(d[33]), "+f"(d[34]), "+f"(d[35]), "+f"(d[36]), "+f"(d[37]), "+f"(d[38]), "+f"(d[39]), "+f"(d[40]), "+f"(d[41]), "+f"(d[42]), "+f"(d[43]), "+f"(d[44]), "+f"(d[45]), "+f"(d[46]), "+f"(d[47])
        : "r"(a[AOFF + 0][0]), "r"(a[AOFF + 0][1]), "r"(a[AOFF + 0][2]), "r"(a[AOFF + 0][3]), "r"(a[AOFF + 1][0]), "r"(a[AOFF + 1][1]), "r"(a[AOFF + 1][2]), "r"(a[AOFF + 1][3]), "r"(a[AOFF + 2][0]), "r"(a[AOFF + 2][1]), "r"(a[AOFF + 2][2]), "r"(a[AOFF + 2][3]), "r"(a[AOFF + 3][0]), "r"(a[AOFF + 3][1]), "r"(a[AOFF + 3][2]), "r"(a[AOFF + 3][3]), "l"(descB), "n"(BOFF >> 4));
}
};
template <> struct Rng<1, 4, 8> {
template <int BOFF, int AOFF, int NA>
static __device__ __forceinline__ void run(float (&d)[48], const uint32_t (&a)[NA][4], uint64_t descB) {
    asm volatile(
        "{\n"
        ".reg .pred p0, p1;\n"
        ".reg .b64 ta, ta0, tb, tb0;\n"
        "setp.ne.b32 p0, 0, 0;\n"
        "setp.eq.b32 p1, 0, 0;\n"
        "add.s64 tb0, %64, %65;\n"
        "add.s64 tb, tb0, 128;\n"
        "wgmma.mma_async.sync.aligned.m64n96k16.f32.bf16.bf16 {%0, %1, %2, %3, %4, %5, %6, %7, %8, %9, %10, %11, %12, %13, %14, %15, %16, %17, %18, %19, %20, %21, %22, %23, %24, %25, %26, %27, %28, %29, %30, %31, %32, %33, %34, %35, %36, %37, %38, %39, %40, %41, %42, %43, %44, %45, %46, %47}, {%48, %49, %50, %51}, tb, p1, 1, 1, 1;\n"
        "add.s64 tb, tb0, 160;\n"
        "wgmma.mma_async.sync.aligned.m64n96k16.f32.bf16.bf16 {%0, %1, %2, %3, %4, %5, %6, %7, %8, %9, %10, %11, %12, %13, %14, %15, %16, %17, %18, %19, %20, %21, %22, %23, %24, %25, %26, %27, %28, %29, %30, %31, %32, %33, %34, %35, %36, %37, %38, %39, %40, %41, %42, %43, %44, %45, %46, %47}, {%52, %53, %54, %55}, tb, p1, 1, 1, 1;\n"
        "add.s64 tb, tb0, 192;\n"
        "wgmma.mma_async.sync.aligned.m64n96k16.f32.bf16.bf16 {%0, %1, %2, %3, %4, %5, %6, %7, %8, %9, %10, %11, %12, %13, %14, %15, %16, %17, %18, %19, %20, %21, %22, %23, %24, %25, %26, %27, %28, %29, %30, %31, %32, %33, %34, %35, %36, %37, %38, %39, %40, %41, %42, %43, %44, %45, %46, %47}, {%56, %57, %58, %59}, tb, p1, 1, 1, 1;\n"
        "add.s64 tb, tb0, 224;\n"
        "wgmma.mma_async.sync.aligned.m64n96k16.f32.bf16.bf16 {%0, %1, %2, %3, %4, %5, %6, %7, %8, %9, %10, %11, %12, %13, %14, %15, %16, %17, %18, %19, %20, %21, %22, %23, %24, %25, %26, %27, %28, %29, %30, %31, %32, %33, %34, %35, %36, %37, %38, %39, %40, %41, %42, %43, %44, %45, %46, %47}, {%60, %61, %62, %63}, tb, p1, 1, 1, 1;\n"
        "}\n"
        : "+f"(d[0]), "+f"(d[1]), "+f"(d[2]), "+f"(d[3]), "+f"(d[4]), "+f"(d[5]), "+f"(d[6]), "+f"(d[7]), "+f"(d[8]), "+f"(d[9]), "+f"(d[10]), "+f"(d[11]), "+f"(d[12]), "+f"(d[13]), "+f"(d[14]), "+f"(d[15]), "+f"(d[16]), "+f"(d[17]), "+f"(d[18]), "+f"(d[19]), "+f"(d[20]), "+f"(d[21]), "+f"(d[22]), "+f"(d[23]), "+f"(d[24]), "+f"(d[25]), "+f"(d[26]), "+f"(d[27]), "+f"(d[28]), "+f"(d[29]), "+f"(d[30]), "+f"(d[31]), "+f"(d[32]), "+f"(d[33]), "+f"(d[34]), "+f"(d[35]), "+f"(d[36]), "+f"(d[37]), "+f"(d[38]), "+f"(d[39]), "+f"(d[40]), "+f"(d[41]), "+f"(d[42]), "+f"(d[43]), "+f"(d[44]), "+f"(d[45]), "+f"(d[46]), "+f"(d[47])
        : "r"(a[AOFF + 0][0]), "r"(a[AOFF + 0][1]), "r"(a[AOFF + 0][2]), "r"(a[AOFF + 0][3]), "r"(a[AOFF + 1][0]), "r"(a[AOFF + 1][1]), "r"(a[AOFF + 1][2]), "r"(a[AOFF + 1][3]), "r"(a[AOFF + 2][0]), "r"(a[AOFF + 2][1]), "r"(a[AOFF + 2][2]), "r"(a[AOFF + 2][3]), "r"(a[AOFF + 3][0]), "r"(a[AOFF + 3][1]), "r"(a[AOFF + 3][2]), "r"(a[AOFF + 3][3]), "l"(descB), "n"(BOFF >> 4));
}
};
template <> struct Rng<0, 4, 9> {
template <int BOFF, int AOFF, int NA>
static __device__ __forceinline__ void run(float (&d)[48], const uint32_t (&a)[NA][4], uint64_t descB) {
    asm volatile(
        "{\n"
        ".reg .pred p0, p1;\n"
        ".reg .b64 ta, ta0, tb, tb0;\n"
        "setp.ne.b32 p0, 0, 0;\n"
        "setp.eq.b32 p1, 0, 0;\n"
        "add.s64 tb0, %68, %69;\n"
        "add.s64 tb, tb0, 1536;\n"
        "wgmma.mma_async.sync.aligned.m64n96k16.f32.bf16.bf16 {%0, %1, %2, %3, %4, %5, %6, %7, %8, %9, %10, %11, %12, %13, %14, %15, %16, %17, %18, %19, %20, %21, %22, %23, %24, %25, %26, %27, %28, %29, %30, %31, %32, %33, %34, %35, %36, %37, %38, %39, %40, %41, %42, %43, %44, %45, %46, %47}, {%48, %49, %50, %51}, tb, p1, 1, 1, 1;\n"
        "add.s64 tb, tb0, 1568;\n"
        "wgmma.mma_async.sync.aligned.m64n96k16.f32.bf16.bf16 {%0, %1, %2, %3, %4, %5, %6, %7, %8, %9, %10, %11, %12, %13, %14, %15, %16, %17, %18, %19, %20, %21, %22, %23, %24, %25, %26, %27, %28, %29, %30, %31, %32, %33, %34, %35, %36, %37, %38, %39, %40, %41, %42, %43, %44, %45, %46, %47}, {%52, %53, %54, %55}, tb, p1, 1, 1, 1;\n"
        "add.s64 tb, tb0, 1600;\n"
        "wgmma.mma_async.sync.aligned.m64n96k16.f32.bf16.bf16 {%0, %1, %2, %3, %4, %5, %6, %7, %8, %9, %10, %11, %12, %13, %14, %15, %16, %17, %18, %19, %20, %21, %22, %23, %24, %25, %26, %27, %28, %29, %30, %31, %32, %33, %34, %35, %36, %37, %38, %39, %40, %41, %42, %43, %44, %45, %46, %47}, {%56, %57, %58, %59}, tb, p1, 1, 1, 1;\n"
        "add.s64 tb, tb0, 1632;\n"
        "wgmma.mma_async.sync.aligned.m64n96k16.f32.bf16.bf16 {%0, %1, %2, %3, %4, %5, %6, %7, %8, %9, %10, %11, %12, %13, %14, %15, %16, %17, %18, %19, %20, %21, %22, %23, %24, %25, %26, %27, %28, %29, %30, %31, %32, %33, %34, %35, %36, %37, %38, %39, %40, %41, %42, %43, %44, %45, %46, %47}, {%60, %61, %62, %63}, tb, p1, 1, 1, 1;\n"
        "add.s64 tb, tb0, 3072;\n"
        "wgmma.mma_async.sync.aligned.m64n96k16.f32.bf16.bf16 {%0, %1, %2, %3, %4, %5, %6, %7, %8, %9, %10, %11, %12, %13, %14, %15, %16, %17, %18, %19, %20, %21, %22, %23, %24, %25, %26, %27, %28, %29, %30, %31, %32, %33, %34, %35, %36, %37, %38, %39, %40, %41, %42, %43, %44, %45, %46, %47}, {%64, %65, %66, %67}, tb, p1, 1, 1, 1;\n"
        "}\n"
        : "+f"(d[0]), "+f"(d[1]), "+f"(d[2]), "+f"(d[3]), "+f"(d[4]), "+f"(d[5]), "+f"(d[6]), "+f"(d[7]), "+f"(d[8]), "+f"(d[9]), "+f"(d[10]), "+f"(d[11]), "+f"(d[12]), "+f"(d[13]), "+f"(d[14]), "+f"(d[15]), "+f"(d[16]), "+f"(d[17]), "+f"(d[18]), "+f"(d[19]), "+f"(d[20]), "+f"(d[21]), "+f"(d[22]), "+f"(d[23]), "+f"(d[24]), "+f"(d[25]), "+f"(d[26]), "+f"(d[27]), "+f"(d[28]), "+f"(d[29]), "+f"(d[30]), "+f"(d[31]), "+f"(d[32]), "+f"(d[33]), "+f"(d[34]), "+f"(d[35]), "+f"(d[36]), "+f"(d[37]), "+f"(d[38]), "+f"(d[39]), "+f"(d[40]), "+f"(d[41]), "+f"(d[42]), "+f"(d[43]), "+f"(d[44]), "+f"(d[45]), "+f"(d[46]), "+f"(d[47])
        : "r"(a[AOFF + 0][0]), "r"(a[AOFF + 0][1]), "r"(a[AOFF + 0][2]), "r"(a[AOFF + 0][3]), "r"(a[AOFF + 1][0]), "r"(a[AOFF + 1][1]), "r"(a[AOFF + 1][2]), "r"(a[AOFF + 1][3]), "r"(a[AOFF + 2][0]), "r"(a[AOFF + 2][1]), "r"(a[AOFF + 2][2]), "r"(a[AOFF + 2][3]), "r"(a[AOFF + 3][0]), "r"(a[AOFF + 3][1]), "r"(a[AOFF + 3][2]), "r"(a[AOFF + 3][3]), "r"(a[AOFF + 4][0]), "r"(a[AOFF + 4][1]), "r"(a[AOFF + 4][2]), "r"(a[AOFF + 4][3]), "l"(descB), "n"(BOFF >> 4));
}
};
template <> struct Rng<1, 4, 9> {
template <int BOFF, int AOFF, int NA>
static __device__ __forceinline__ void run(float (&d)[48], const uint32_t (&a)[NA][4], uint64_t descB) {
    asm volatile(
        "{\n"
        ".reg .pred p0, p1;\n"
        ".reg .b64 ta, ta0, tb, tb0;\n"
        "setp.ne.b32 p0, 0, 0;\n"
        "setp.eq.b32 p1, 0, 0;\n"
        "add.s64 tb0, %68, %69;\n"
        "add.s64 tb, tb0, 128;\n"
        "wgmma.mma_async.sync.aligned.m64n96k16.f32.bf16.bf16 {%0, %1, %2, %3, %4, %5, %6, %7, %8, %9, %10, %11, %12, %13, %14, %15, %16, %17, %18, %19, %20, %21, %22, %23, %24, %25, %26, %27, %28, %29, %30, %31, %32, %33, %34, %35, %36, %37, %38, %39, %40, %41, %42, %43, %44, %45, %46, %47}, {%48, %49, %50, %51}, tb, p1, 1, 1, 1;\n"
        "add.s64 tb, tb0, 160;\n"
        "wgmma.mma_async.sync.aligned.m64n96k16.f32.bf16.bf16 {%0, %1, %2, %3, %4, %5, %6, %7, %8, %9, %10, %11, %12, %13, %14, %15, %16, %17, %18, %19, %20, %21, %22, %23, %24, %25, %26, %27, %28, %29, %30, %31, %32, %33, %34, %35, %36, %37, %38, %39, %40, %41, %42, %43, %44, %45, %46, %47}, {%52, %53, %54, %55}, tb, p1, 1, 1, 1;\n"
        "add.s64 tb, tb0, 192;\n"
        "wgmma.mma_async.sync.aligned.m64n96k16.f32.bf16.bf16 {%0, %1, %2, %3, %4, %5, %6, %7, %8, %9, %10, %11, %12, %13, %14, %15, %16, %17, %18, %19, %20, %21, %22, %23, %24, %25, %26, %27, %28, %29, %30, %31, %32, %33, %34, %35, %36, %37, %38, %39, %40, %41, %42, %43, %44, %45, %46, %47}, {%56, %57, %58, %59}, tb, p1, 1, 1, 1;\n"
        "add.s64 tb, tb0, 224;\n"
        "wgmma.mma_async.sync.aligned.m64n96k16.f32.bf16.bf16 {%0, %1, %2, %3, %4, %5, %6, %7, %8, %9, %10, %11, %12, %13, %14, %15, %16, %17, %18, %19, %20, %21, %22, %23, %24, %25, %26, %27, %28, %29, %30, %31, %32, %33, %34, %35, %36, %37, %38, %39, %40, %41, %42, %43, %44, %45, %46, %47}, {%60, %61, %62, %63}, tb, p1, 1, 1, 1;\n"
        "add.s64 tb, tb0, 256;\n"
        "wgmma.mma_async.sync.aligned.m64n96k16.f32.bf16.bf16 {%0, %1, %2, %3, %4, %5, %6, %7, %8, %9, %10, %11, %12, %13, %14, %15, %16, %17, %18, %19, %20, %21, %22, %23, %24, %25, %26, %27, %28, %29, %30, %31, %32, %33, %34, %35, %36, %37, %38, %39, %40, %41, %42, %43, %44, %45, %46, %47}, {%64, %65, %66, %67}, tb, p1, 1, 1, 1;\n"
        "}\n"
        : "+f"(d[0]), "+f"(d[1]), "+f"(d[2]), "+f"(d[3]), "+f"(d[4]), "+f"(d[5]), "+f"(d[6]), "+f"(d[7]), "+f"(d[8]), "+f"(d[9]), "+f"(d[10]), "+f"(d[11]), "+f"(d[12]), "+f"(d[13]), "+f"(d[14]), "+f"(d[15]), "+f"(d[16]), "+f"(d[17]), "+f"(d[18]), "+f"(d[19]), "+f"(d[20]), "+f"(d[21]), "+f"(d[22]), "+f"(d[23]), "+f"(d[24]), "+f"(d[25]), "+f"(d[26]), "+f"(d[27]), "+f"(d[28]), "+f"(d[29]), "+f"(d[30]), "+f"(d[31]), "+f"(d[32]), "+f"(d[33]), "+f"(d[34]), "+f"(d[35]), "+f"(d[36]), "+f"(d[37]), "+f"(d[38]), "+f"(d[39]), "+f"(d[40]), "+f"(d[41]), "+f"(d[42]), "+f"(d[43]), "+f"(d[44]), "+f"(d[45]), "+f"(d[46]), "+f"(d[47])
        : "r"(a[AOFF + 0][0]), "r"(a[AOFF + 0][1]), "r"(a[AOFF + 0][2]), "r"(a[AOFF + 0][3]), "r"(a[AOFF + 1][0]), "r"(a[AOFF + 1][1]), "r"(a[AOFF + 1][2]), "r"(a[AOFF + 1][3]), "r"(a[AOFF + 2][0]), "r"(a[AOFF + 2][1]), "r"(a[AOFF + 2][2]), "r"(a[AOFF + 2][3]), "r"(a[AOFF + 3][0]), "r"(a[AOFF + 3][1]), "r"(a[AOFF + 3][2]), "r"(a[AOFF + 3][3]), "r"(a[AOFF + 4][0]), "r"(a[AOFF + 4][1]), "r"(a[AOFF + 4][2]), "r"(a[AOFF + 4][3]), "l"(descB), "n"(BOFF >> 4));
}
};
template <> struct Rng<0, 4, 12> {
template <int BOFF, int AOFF, int NA>
static __device__ __forceinline__ void run(float (&d)[48], const uint32_t (&a)[NA][4], uint64_t descB) {
    asm volatile(
        "{\n"
        ".reg .pred p0, p1;\n"
        ".reg .b64 ta, ta0, tb, tb0;\n"
        "setp.ne.b32 p0, 0, 0;\n"
        "setp.eq.b32 p1, 0, 0;\n"
        "add.s64 tb0, %80, %81;\n"
        "add.s64 tb, tb0, 1536;\n"
        "wgmma.mma_async.sync.aligned.m64n96k16.f32.bf16.bf16 {%0, %1, %2, %3, %4, %5, %6, %7, %8, %9, %10, %11, %12, %13, %14, %15, %16, %17, %18, %19, %20, %21, %22, %23, %24, %25, %26, %27, %28, %29, %30, %31, %32, %33, %34, %35, %36, %37, %38, %39, %40, %41, %42, %43, %44, %45, %46, %47}, {%48, %49, %50, %51}, tb, p1, 1, 1, 1;\n"
        "add.s64 tb, tb0, 1568;\n"
        "wgmma.mma_async.sync.aligned.m64n96k16.f32.bf16.bf16 {%0, %1, %2, %3, %4, %5, %6, %7, %8, %9, %10, %11, %12, %13, %14, %15, %16, %17, %18, %19, %20, %21, %22, %23, %24, %25, %26, %27, %28, %29, %30, %31, %32, %33, %34, %35, %36, %37, %38, %39, %40, %41, %42, %43, %44, %45, %46, %47}, {%52, %53, %54, %55}, tb, p1, 1, 1, 1;\n"
        "add.s64 tb, tb0, 1600;\n"
        "wgmma.mma_async.sync.aligned.m64n96k16.f32.bf16.bf16 {%0, %1, %2, %3, %4, %5, %6, %7, %8, %9, %10, %11, %12, %13, %14, %15, %16, %17, %18, %19, %20, %21, %22, %23, %24, %25, %26, %27, %28, %29, %30, %31, %32, %33, %34, %35, %36, %37, %38, %39, %40, %41, %42, %43, %44, %45, %46, %47}, {%56, %57, %58, %59}, tb, p1, 1, 1, 1;\n"
        "add.s64 tb, tb0, 1632;\n"
        "wgmma.mma_async.sync.aligned.m64n96k16.f32.bf16.bf16 {%0, %1, %2, %3, %4, %5, %6, %7, %8, %9, %10, %11, %12, %13, %14, %15, %16, %17, %18, %19, %20, %21, %22, %23, %24, %25, %26, %27, %28, %29, %30, %31, %32, %33, %34, %35, %36, %37, %38, %39, %40, %41, %42, %43, %44, %45, %46, %47}, {%60, %61, %62, %63}, tb, p1, 1, 1, 1;\n"
        "add.s64 tb, tb0, 3072;\n"
        "wgmma.mma_async.sync.aligned.m64n96k16.f32.bf16.bf16 {%0, %1, %2, %3, %4, %5, %6, %7, %8, %9, %10, %11, %12, %13, %14, %15, %16, %17, %18, %19, %20, %21, %22, %23, %24, %25, %26, %27, %28, %29, %30, %31, %32, %33, %34, %35, %36, %37, %38, %39, %40, %41, %42, %43, %44, %45, %46, %47}, {%64, %65, %66, %67}, tb, p1, 1, 1, 1;\n"
        "add.s64 tb, tb0, 3104;\n"
        "wgmma.mma_async.sync.aligned.m64n96k16.f32.bf16.bf16 {%0, %1, %2, %3, %4, %5, %6, %7, %8, %9, %10, %11, %12, %13, %14, %15, %16, %17, %18, %19, %20, %21, %22, %23, %24, %25, %26, %27, %28, %29, %30, %31, %32, %33, %34, %35, %36, %37, %38, %39, %40, %41, %42, %43, %44, %45, %46, %47}, {%68, %69, %70, %71}, tb, p1, 1, 1, 1;\n"
        "add.s64 tb, tb0, 3136;\n"
        "wgmma.mma_async.sync.aligned.m64n96k16.f32.bf16.bf16 {%0, %1, %2, %3, %4, %5, %6, %7, %8, %9, %10, %11, %12, %13, %14, %15, %16, %17, %18, %19, %20, %21, %22, %23, %24, %25, %26, %27, %28, %29, %30, %31, %32, %33, %34, %35, %36, %37, %38, %39, %40, %41, %42, %43, %44, %45, %46, %47}, {%72, %73, %74, %75}, tb, p1, 1, 1, 1;\n"
        "add.s64 tb, tb0, 3168;\n"
        "wgmma.mma_async.sync.aligned.m64n96k16.f32.bf16.bf16 {%0, %1, %2, %3, %4, %5, %6, %7, %8, %9, %10, %11, %12, %13, %14, %15, %16, %17, %18, %19, %20, %21, %22, %23, %24, %25, %26, %27, %28, %29, %30, %31, %32, %33, %34, %35, %36, %37, %38, %39, %40, %41, %42, %43, %44, %45, %46, %47}, {%76, %77, %78, %79}, tb, p1, 1, 1, 1;\n"
        "}\n"
        : "+f"(d[0]), "+f"(d[1]), "+f"(d[2]), "+f"(d[3]), "+f"(d[4]), "+f"(d[5]), "+f"(d[6]), "+f"(d[7]), "+f"(d[8]), "+f"(d[9]), "+f"(d[10]), "+f"(d[11]), "+f"(d[12]), "+f"(d[13]), "+f"(d[14]), "+f"(d[15]), "+f"(d[16]), "+f"(d[17]), "+f"(d[18]), "+f"(d[19]), "+f"(d[20]), "+f"(d[21]), "+f"(d[22]), "+f"(d[23]), "+f"(d[24]), "+f"(d[25]), "+f"(d[26]), "+f"(d[27]), "+f"(d[28]), "+f"(d[29]), "+f"(d[30]), "+f"(d[31]), "+f"(d[32]), "+f"(d[33]), "+f"(d[34]), "+f"(d[35]), "+f"(d[36]), "+f"(d[37]), "+f"(d[38]), "+f"(d[39]), "+f"(d[40]), "+f"(d[41]), "+f"(d[42]), "+f"(d[43]), "+f"(d[44]), "+f"(d[45]), "+f"(d[46]), "+f"(d[47])
        : "r"(a[AOFF + 0][0]), "r"(a[AOFF + 0][1]), "r"(a[AOFF + 0][2]), "r"(a[AOFF + 0][3]), "r"(a[AOFF + 1][0]), "r"(a[AOFF + 1][1]), "r"(a[AOFF + 1][2]), "r"(a[AOFF + 1][3]), "r"(a[AOFF + 2][0]), "r"(a[AOFF + 2][1]), "r"(a[AOFF + 2][2]), "r"(a[AOFF + 2][3]), "r"(a[AOFF + 3][0]), "r"(a[AOFF + 3][1]), "r"(a[AOFF + 3][2]), "r"(a[AOFF + 3][3]), "r"(a[AOFF + 4][0]), "r"(a[AOFF + 4][1]), "r"(a[AOFF + 4][2]), "r"(a[AOFF + 4][3]), "r"(a[AOFF + 5][0]), "r"(a[AOFF + 5][1]), "r"(a[AOFF + 5][2]), "r"(a[AOFF + 5][3]), "r"(a[AOFF + 6][0]), "r"(a[AOFF + 6][1]), "r"(a[AOFF + 6][2]), "r"(a[AOFF + 6][3]), "r"(a[AOFF + 7][0]), "r"(a[AOFF + 7][1]), "r"(a[AOFF + 7][2]), "r"(a[AOFF + 7][3]), "l"(descB), "n"(BOFF >> 4));
}
};
template <> struct Rng<1, 4, 12> {
template <int BOFF, int AOFF, int NA>
static __device__ __forceinline__ void run(float (&d)[48], const uint32_t (&a)[NA][4], uint64_t descB) {
    asm volatile(
        "{\n"
        ".reg .pred p0, p1;\n"
        ".reg .b64 ta, ta0, tb, tb0;\n"
        "setp.ne.b32 p0, 0, 0;\n"
        "setp.eq.b32 p1, 0, 0;\n"
        "add.s64 tb0, %80, %81;\n"
        "add.s64 tb, tb0, 128;\n"
        "wgmma.mma_async.sync.aligned.m64n96k16.f32.bf16.bf16 {%0, %1, %2, %3, %4, %5, %6, %7, %8, %9, %10, %11, %12, %13, %14, %15, %16, %17, %18, %19, %20, %21, %22, %23, %24, %25, %26, %27, %28, %29, %30, %31, %32, %33, %34, %35, %36, %37, %38, %39, %40, %41, %42, %43, %44, %45, %46, %47}, {%48, %49, %50, %51}, tb, p1, 1, 1, 1;\n"
        "add.s64 tb, tb0, 160;\n"
        "wgmma.mma_async.sync.aligned.m64n96k16.f32.bf16.bf16 {%0, %1, %2, %3, %4, %5, %6, %7, %8, %9, %10, %11, %12, %13, %14, %15, %16, %17, %18, %19, %20, %21, %22, %23, %24, %25, %26, %27, %28, %29, %30, %31, %32, %33, %34, %35, %36, %37, %38, %39, %40, %41, %42, %43, %44, %45, %46, %47}, {%52, %53, %54, %55}, tb, p1, 1, 1, 1;\n"
        "add.s64 tb, tb0, 192;\n"
        "wgmma.mma_async.sync.aligned.m64n96k16.f32.bf16.bf16 {%0, %1, %2, %3, %4, %5, %6, %7, %8, %9, %10, %11, %12, %13, %14, %15, %16, %17, %18, %19, %20, %21, %22, %23, %24, %25, %26, %27, %28, %29, %30, %31, %32, %33, %34, %35, %36, %37, %38, %39, %40, %41, %42, %43, %44, %45, %46, %47}, {%56, %57, %58, %59}, tb, p1, 1, 1, 1;\n"
        "add.s64 tb, tb0, 224;\n"
        "wgmma.mma_async.sync.aligned.m64n96k16.f32.bf16.bf16 {%0, %1, %2, %3, %4, %5, %6, %7, %8, %9, %10, %11, %12, %13, %14, %15, %16, %17, %18, %19, %20, %21, %22, %23, %24, %25, %26, %27, %28, %29, %30, %31, %32, %33, %34, %35, %36, %37, %38, %39, %40, %41, %42, %43, %44, %45, %46, %47}, {%60, %61, %62, %63}, tb, p1, 1, 1, 1;\n"
        "add.s64 tb, tb0, 256;\n"
        "wgmma.mma_async.sync.aligned.m64n96k16.f32.bf16.bf16 {%0, %1, %2, %3, %4, %5, %6, %7, %8, %9, %10, %11, %12, %13, %14, %15, %16, %17, %18, %19, %20, %21, %22, %23, %24, %25, %26, %27, %28, %29, %30, %31, %32, %33, %34, %35, %36, %37, %38, %39, %40, %41, %42, %43, %44, %45, %46, %47}, {%64, %65, %66, %67}, tb, p1, 1, 1, 1;\n"
        "add.s64 tb, tb0, 288;\n"
        "wgmma.mma_async.sync.aligned.m64n96k16.f32.bf16.bf16 {%0, %1, %2, %3, %4, %5, %6, %7, %8, %9, %10, %11, %12, %13, %14, %15, %16, %17, %18, %19, %20, %21, %22, %23, %24, %25, %26, %27, %28, %29, %30, %31, %32, %33, %34, %35, %36, %37, %38, %39, %40, %41, %42, %43, %44, %45, %46, %47}, {%68, %69, %70, %71}, tb, p1, 1, 1, 1;\n"
        "add.s64 tb, tb0, 320;\n"
        "wgmma.mma_async.sync.aligned.m64n96k16.f32.bf16.bf16 {%0, %1, %2, %3, %4, %5, %6, %7, %8, %9, %10, %11, %12, %13, %14, %15, %16, %17, %18, %19, %20, %21, %22, %23, %24, %25, %26, %27, %28, %29, %30, %31, %32, %33, %34, %35, %36, %37, %38, %39, %40, %41, %42, %43, %44, %45, %46, %47}, {%72, %73, %74, %75}, tb, p1, 1, 1, 1;\n"
        "add.s64 tb, tb0, 352;\n"
        "wgmma.mma_async.sync.aligned.m64n96k16.f32.bf16.bf16 {%0, %1, %2, %3, %4, %5, %6, %7, %8, %9, %10, %11, %12, %13, %14, %15, %16, %17, %18, %19, %20, %21, %22, %23, %24, %25, %26, %27, %28, %29, %30, %31, %32, %33, %34, %35, %36, %37, %38, %39, %40, %41, %42, %43, %44, %45, %46, %47}, {%76, %77, %78, %79}, tb, p1, 1, 1, 1;\n"
        "}\n"
        : "+f"(d[0]), "+f"(d[1]), "+f"(d[2]), "+f"(d[3]), "+f"(d[4]), "+f"(d[5]), "+f"(d[6]), "+f"(d[7]), "+f"(d[8]), "+f"(d[9]), "+f"(d[10]), "+f"(d[11]), "+f"(d[12]), "+f"(d[13]), "+f"(d[14]), "+f"(d[15]), "+f"(d[16]), "+f"(d[17]), "+f"(d[18]), "+f"(d[19]), "+f"(d[20]), "+f"(d[21]), "+f"(d[22]), "+f"(d[23]), "+f"(d[24]), "+f"(d[25]), "+f"(d[26]), "+f"(d[27]), "+f"(d[28]), "+f"(d[29]), "+f"(d[30]), "+f"(d[31]), "+f"(d[32]), "+f"(d[33]), "+f"(d[34]), "+f"(d[35]), "+f"(d[36]), "+f"(d[37]), "+f"(d[38]), "+f"(d[39]), "+f"(d[40]), "+f"(d[41]), "+f"(d[42]), "+f"(d[43]), "+f"(d[44]), "+f"(d[45]), "+f"(d[46]), "+f"(d[47])
        : "r"(a[AOFF + 0][0]), "r"(a[AOFF + 0][1]), "r"(a[AOFF + 0][2]), "r"(a[AOFF + 0][3]), "r"(a[AOFF + 1][0]), "r"(a[AOFF + 1][1]), "r"(a[AOFF + 1][2]), "r"(a[AOFF + 1][3]), "r"(a[AOFF + 2][0]), "r"(a[AOFF + 2][1]), "r"(a[AOFF + 2][2]), "r"(a[AOFF + 2][3]), "r"(a[AOFF + 3][0]), "r"(a[AOFF + 3][1]), "r"(a[AOFF + 3][2]), "r"(a[AOFF + 3][3]), "r"(a[AOFF + 4][0]), "r"(a[AOFF + 4][1]), "r"(a[AOFF + 4][2]), "r"(a[AOFF + 4][3]), "r"(a[AOFF + 5][0]), "r"(a[AOFF + 5][1]), "r"(a[AOFF + 5][2]), "r"(a[AOFF + 5][3]), "r"(a[AOFF + 6][0]), "r"(a[AOFF + 6][1]), "r"(a[AOFF + 6][2]), "r"(a[AOFF + 6][3]), "r"(a[AOFF + 7][0]), "r"(a[AOFF + 7][1]), "r"(a[AOFF + 7][2]), "r"(a[AOFF + 7][3]), "l"(descB), "n"(BOFF >> 4));
}
};
template <> struct Rng<0, 5, 8> {
template <int BOFF, int AOFF, int NA>
static __device__ __forceinline__ void run(float (&d)[48], const uint32_t (&a)[NA][4], uint64_t descB) {
    asm volatile(
        "{\n"
        ".reg .pred p0, p1;\n"
        ".reg .b64 ta, ta0, tb, tb0;\n"
        "setp.ne.b32 p0, 0, 0;\n"
        "setp.eq.b32 p1, 0, 0;\n"
        "add.s64 tb0, %60, %61;\n"
        "add.s64 tb, tb0, 1568;\n"
        "wgmma.mma_async.sync.aligned.m64n96k16.f32.bf16.bf16 {%0, %1, %2, %3, %4, %5, %6, %7, %8, %9, %10, %11, %12, %13, %14, %15, %16, %17, %18, %19, %20, %21, %22, %23, %24, %25, %26, %27, %28, %29, %30, %31, %32, %33, %34, %35, %36, %37, %38, %39, %40, %41, %42, %43, %44, %45, %46, %47}, {%48, %49, %50, %51}, tb, p1, 1, 1, 1;\n"
        "add.s64 tb, tb0, 1600;\n"
        "wgmma.mma_async.sync.aligned.m64n96k16.f32.bf16.bf16 {%0, %1, %2, %3, %4, %5, %6, %7, %8, %9, %10, %11, %12, %13, %14, %15, %16, %17, %18, %19, %20, %21, %22, %23, %24, %25, %26, %27, %28, %29, %30, %31, %32, %33, %34, %35, %36, %37, %38, %39, %40, %41, %42, %43, %44, %45, %46, %47}, {%52, %53, %54, %55}, tb, p1, 1, 1, 1;\n"
        "add.s64 tb, tb0, 1632;\n"
        "wgmma.mma_async.sync.aligned.m64n96k16.f32.bf16.bf16 {%0, %1, %2, %3, %4, %5, %6, %7, %8, %9, %10, %11, %12, %13, %14, %15, %16, %17, %18, %19, %20, %21, %22, %23, %24, %25, %26, %27, %28, %29, %30, %31, %32, %33, %34, %35, %36, %37, %38, %39, %40, %41, %42, %43, %44, %45, %46, %47}, {%56, %57, %58, %59}, tb, p1, 1, 1, 1;\n"
        "}\n"
        : "+f"(d[0]), "+f"(d[1]), "+f"(d[2]), "+f"(d[3]), "+f"(d[4]), "+f"(d[5]), "+f"(d[6]), "+f"(d[7]), "+f"(d[8]), "+f"(d[9]), "+f"(d[10]), "+f"(d[11]), "+f"(d[12]), "+f"(d[13]), "+f"(d[14]), "+f"(d[15]), "+f"(d[16]), "+f"(d[17]), "+f"(d[18]), "+f"(d[19]), "+f"(d[20]), "+f"(d[21]), "+f"(d[22]), "+f"(d[23]), "+f"(d[24]), "+f"(d[25]), "+f"(d[26]), "+f"(d[27]), "+f"(d[28]), "+f"(d[29]), "+f"(d[30]), "+f"(d[31]), "+f"(d[32]), "+f"(d[33]), "+f"(d[34]), "+f"(d[35]), "+f"(d[36]), "+f"(d[37]), "+f"(d[38]), "+f"(d[39]), "+f"(d[40]), "+f"(d[41]), "+f"(d[42]), "+f"(d[43]), "+f"(d[44]), "+f"(d[45]), "+f"(d[46]), "+f"(d[47])
        : "r"(a[AOFF + 0][0]), "r"(a[AOFF + 0][1]), "r"(a[AOFF + 0][2]), "r"(a[AOFF + 0][3]), "r"(a[AOFF + 1][0]), "r"(a[AOFF + 1][1]), "r"(a[AOFF + 1][2]), "r"(a[AOFF + 1][3]), "r"(a[AOFF + 2][0]), "r"(a[AOFF + 2][1]), "r"(a[AOFF + 2][2]), "r"(a[AOFF + 2][3]), "l"(descB), "n"(BOFF >> 4));
}
};
template <> struct Rng<1, 5, 8> {
template <int BOFF, int AOFF, int NA>
static __device__ __forceinline__ void run(float (&d)[48], const uint32_t (&a)[NA][4], uint64_t descB) {
    asm volatile(
        "{\n"
        ".reg .pred p0, p1;\n"
        ".reg .b64 ta, ta0, tb, tb0;\n"
        "setp.ne.b32 p0, 0, 0;\n"
        "setp.eq.b32 p1, 0, 0;\n"
        "add.s64 tb0, %60, %61;\n"
        "add.s64 tb, tb0, 160;\n"
        "wgmma.mma_async.sync.aligned.m64n96k16.f32.bf16.bf16 {%0, %1, %2, %3, %4, %5, %6, %7, %8, %9, %10, %11, %12, %13, %14, %15, %16, %17, %18, %19, %20, %21, %22, %23, %24, %25, %26, %27, %28, %29, %30, %31, %32, %33, %34, %35, %36, %37, %38, %39, %40, %41, %42, %43, %44, %45, %46, %47}, {%48, %49, %50, %51}, tb, p1, 1, 1, 1;\n"
        "add.s64 tb, tb0, 192;\n"
        "wgmma.mma_async.sync.aligned.m64n96k16.f32.bf16.bf16 {%0, %1, %2, %3, %4, %5, %6, %7, %8, %9, %10, %11, %12, %13, %14, %15, %16, %17, %18, %19, %20, %21, %22, %23, %24, %25, %26, %27, %28, %29, %30, %31, %32, %33, %34, %35, %36, %37, %38, %39, %40, %41, %42, %43, %44, %45, %46, %47}, {%52, %53, %54, %55}, tb, p1, 1, 1, 1;\n"
        "add.s64 tb, tb0, 224;\n"
        "wgmma.mma_async.sync.aligned.m64n96k16.f32.bf16.bf16 {%0, %1, %2, %3, %4, %5, %6, %7, %8, %9, %10, %11, %12, %13, %14, %15, %16, %17, %18, %19, %20, %21, %22, %23, %24, %25, %26, %27, %28, %29, %30, %31, %32, %33, %34, %35, %36, %37, %38, %39, %40, %41, %42, %43, %44, %45, %46, %47}, {%56, %57, %58, %59}, tb, p1, 1, 1, 1;\n"
        "}\n"
        : "+f"(d[0]), "+f"(d[1]), "+f"(d[2]), "+f"(d[3]), "+f"(d[4]), "+f"(d[5]), "+f"(d[6]), "+f"(d[7]), "+f"(d[8]), "+f"(d[9]), "+f"(d[10]), "+f"(d[11]), "+f"(d[12]), "+f"(d[13]), "+f"(d[14]), "+f"(d[15]), "+f"(d[16]), "+f"(d[17]), "+f"(d[18]), "+f"(d[19]), "+f"(d[20]), "+f"(d[21]), "+f"(d[22]), "+f"(d[23]), "+f"(d[24]), "+f"(d[25]), "+f"(d[26]), "+f"(d[27]), "+f"(d[28]), "+f"(d[29]), "+f"(d[30]), "+f"(d[31]), "+f"(d[32]), "+f"(d[33]), "+f"(d[34]), "+f"(d[35]), "+f"(d[36]), "+f"(d[37]), "+f"(d[38]), "+f"(d[39]), "+f"(d[40]), "+f"(d[41]), "+f"(d[42]), "+f"(d[43]), "+f"(d[44]), "+f"(d[45]), "+f"(d[46]), "+f"(d[47])
        : "r"(a[AOFF + 0][0]), "r"(a[AOFF + 0][1]), "r"(a[AOFF + 0][2]), "r"(a[AOFF + 0][3]), "r"(a[AOFF + 1][0]), "r"(a[AOFF + 1][1]), "r"(a[AOFF + 1][2]), "r"(a[AOFF + 1][3]), "r"(a[AOFF + 2][0]), "r"(a[AOFF + 2][1]), "r"(a[AOFF + 2][2]), "r"(a[AOFF + 2][3]), "l"(descB), "n"(BOFF >> 4));
}
};
template <> struct Rng<0, 5, 9> {
template <int BOFF, int AOFF, int NA>
static __device__ __forceinline__ void run(float (&d)[48], const uint32_t (&a)[NA][4], uint64_t descB) {
    asm volatile(
        "{\n"
        ".reg .pred p0, p1;\n"
        ".reg .b64 ta, ta0, tb, tb0;\n"
        "setp.ne.b32 p0, 0, 0;\n"
        "setp.eq.b32 p1, 0, 0;\n"
        "add.s64 tb0, %64, %65;\n"
        "add.s64 tb, tb0, 1568;\n"
        "wgmma.mma_async.sync.aligned.m64n96k16.f32.bf16.bf16 {%0, %1, %2, %3, %4, %5, %6, %7, %8, %9, %10, %11, %12, %13, %14, %15, %16, %17, %18, %19, %20, %21, %22, %23, %24, %25, %26, %27, %28, %29, %30, %31, %32, %33, %34, %35, %36, %37, %38, %39, %40, %41, %42, %43, %44, %45, %46, %47}, {%48, %49, %50, %51}, tb, p1, 1, 1, 1;\n"
        "add.s64 tb, tb0, 1600;\n"
        "wgmma.mma_async.sync.aligned.m64n96k16.f32.bf16.bf16 {%0, %1, %2, %3, %4, %5, %6, %7, %8, %9, %10, %11, %12, %13, %14, %15, %16, %17, %18, %19, %20, %21, %22, %23, %24, %25, %26, %27, %28, %29, %30, %31, %32, %33, %34, %35, %36, %37, %38, %39, %40, %41, %42, %43, %44, %45, %46, %47}, {%52, %53, %54, %55}, tb, p1, 1, 1, 1;\n"
        "add.s64 tb, tb0, 1632;\n"
        "wgmma.mma_async.sync.aligned.m64n96k16.f32.bf16.bf16 {%0, %1, %2, %3, %4, %5, %6, %7, %8, %9, %10, %11, %12, %13, %14, %15, %16, %17, %18, %19, %20, %21, %22, %23, %24, %25, %26, %27, %28, %29, %30, %31, %32, %33, %34, %35, %36, %37, %38, %39, %40, %41, %42, %43, %44, %45, %46, %47}, {%56, %57, %58, %59}, tb, p1, 1, 1, 1;\n"
        "add.s64 tb, tb0, 3072;\n"
        "wgmma.mma_async.sync.aligned.m64n96k16.f32.bf16.bf16 {%0, %1, %2, %3, %4, %5, %6, %7, %8, %9, %10, %11, %12, %13, %14, %15, %16, %17, %18, %19, %20, %21, %22, %23, %24, %25, %26, %27, %28, %29, %30, %31, %32, %33, %34, %35, %36, %37, %38, %39, %40, %41, %42, %43, %44, %45, %46, %47}, {%60, %61, %62, %63}, tb, p1, 1, 1, 1;\n"
        "}\n"
        : "+f"(d[0]), "+f"(d[1]), "+f"(d[2]), "+f"(d[3]), "+f"(d[4]), "+f"(d[5]), "+f"(d[6]), "+f"(d[7]), "+f"(d[8]), "+f"(d[9]), "+f"(d[10]), "+f"(d[11]), "+f"(d[12]), "+f"(d[13]), "+f"(d[14]), "+f"(d[15]), "+f"(d[16]), "+f"(d[17]), "+f"(d[18]), "+f"(d[19]), "+f"(d[20]), "+f"(d[21]), "+f"(d[22]), "+f"(d[23]), "+f"(d[24]), "+f"(d[25]), "+f"(d[26]), "+f"(d[27]), "+f"(d[28]), "+f"(d[29]), "+f"(d[30]), "+f"(d[31]), "+f"(d[32]), "+f"(d[33]), "+f"(d[34]), "+f"(d[35]), "+f"(d[36]), "+f"(d[37]), "+f"(d[38]), "+f"(d[39]), "+f"(d[40]), "+f"(d[41]), "+f"(d[42]), "+f"(d[43]), "+f"(d[44]), "+f"(d[45]), "+f"(d[46]), "+f"(d[47])
        : "r"(a[AOFF + 0][0]), "r"(a[AOFF + 0][1]), "r"(a[AOFF + 0][2]), "r"(a[AOFF + 0][3]), "r"(a[AOFF + 1][0]), "r"(a[AOFF + 1][1]), "r"(a[AOFF + 1][2]), "r"(a[AOFF + 1][3]), "r"(a[AOFF + 2][0]), "r"(a[AOFF + 2][1]), "r"(a[AOFF + 2][2]), "r"(a[AOFF + 2][3]), "r"(a[AOFF + 3][0]), "r"(a[AOFF + 3][1]), "r"(a[AOFF + 3][2]), "r"(a[AOFF + 3][3]), "l"(descB), "n"(BOFF >> 4));
}
};
template <> struct Rng<1, 5, 9> {
template <int BOFF, int AOFF, int NA>
static __device__ __forceinline__ void run(float (&d)[48], const uint32_t (&a)[NA][4], uint64_t descB) {
    asm volatile(
        "{\n"
        ".reg .pred p0, p1;\n"
        ".reg .b64 ta, ta0, tb, tb0;\n"
        "setp.ne.b32 p0, 0, 0;\n"
        "setp.eq.b32 p1, 0, 0;\n"
        "add.s64 tb0, %64, %65;\n"
        "add.s64 tb, tb0, 160;\n"
        "wgmma.mma_async.sync.aligned.m64n96k16.f32.bf16.bf16 {%0, %1, %2, %3, %4, %5, %6, %7, %8, %9, %10, %11, %12, %13, %14, %15, %16, %17, %18, %19, %20, %21, %22, %23, %24, %25, %26, %27, %28, %29, %30, %31, %32, %33, %34, %35, %36, %37, %38, %39, %40, %41, %42, %43, %44, %45, %46, %47}, {%48, %49, %50, %51}, tb, p1, 1, 1, 1;\n"
        "add.s64 tb, tb0, 192;\n"
        "wgmma.mma_async.sync.aligned.m64n96k16.f32.bf16.bf16 {%0, %1, %2, %3, %4, %5, %6, %7, %8, %9, %10, %11, %12, %13, %14, %15, %16, %17, %18, %19, %20, %21, %22, %23, %24, %25, %26, %27, %28, %29, %30, %31, %32, %33, %34, %35, %36, %37, %38, %39, %40, %41, %42, %43, %44, %45, %46, %47}, {%52, %53, %54, %55}, tb, p1, 1, 1, 1;\n"
        "add.s64 tb, tb0, 224;\n"
        "wgmma.mma_async.sync.aligned.m64n96k16.f32.bf16.bf16 {%0, %1, %2, %3, %4, %5, %6, %7, %8, %9, %10, %11, %12, %13, %14, %15, %16, %17, %18, %19, %20, %21, %22, %23, %24, %25, %26, %27, %28, %29, %30, %31, %32, %33, %34, %35, %36, %37, %38, %39, %40, %41, %42, %43, %44, %45, %46, %47}, {%56, %57, %58, %59}, tb, p1, 1, 1, 1;\n"
        "add.s64 tb, tb0, 256;\n"
        "wgmma.mma_async.sync.aligned.m64n96k16.f32.bf16.bf16 {%0, %1, %2, %3, %4, %5, %6, %7, %8, %9, %10, %11, %12, %13, %14, %15, %16, %17, %18, %19, %20, %21, %22, %23, %24, %25, %26, %27, %28, %29, %30, %31, %32, %33, %34, %35, %36, %37, %38, %39, %40, %41, %42, %43, %44, %45, %46, %47}, {%60, %61, %62, %63}, tb, p1, 1, 1, 1;\n"
        "}\n"
        : "+f"(d[0]), "+f"(d[1]), "+f"(d[2]), "+f"(d[3]), "+f"(d[4]), "+f"(d[5]), "+f"(d[6]), "+f"(d[7]), "+f"(d[8]), "+f"(d[9]), "+f"(d[10]), "+f"(d[11]), "+f"(d[12]), "+f"(d[13]), "+f"(d[14]), "+f"(d[15]), "+f"(d[16]), "+f"(d[17]), "+f"(d[18]), "+f"(d[19]), "+f"(d[20]), "+f"(d[21]), "+f"(d[22]), "+f"(d[23]), "+f"(d[24]), "+f"(d[25]), "+f"(d[26]), "+f"(d[27]), "+f"(d[28]), "+f"(d[29]), "+f"(d[30]), "+f"(d[31]), "+f"(d[32]), "+f"(d[33]), "+f"(d[34]), "+f"(d[35]), "+f"(d[36]), "+f"(d[37]), "+f"(d[38]), "+f"(d[39]), "+f"(d[40]), "+f"(d[41]), "+f"(d[42]), "+f"(d[43]), "+f"(d[44]), "+f"(d[45]), "+f"(d[46]), "+f"(d[47])
        : "r"(a[AOFF + 0][0]), "r"(a[AOFF + 0][1]), "r"(a[AOFF + 0][2]), "r"(a[AOFF + 0][3]), "r"(a[AOFF + 1][0]), "r"(a[AOFF + 1][1]), "r"(a[AOFF + 1][2]), "r"(a[AOFF + 1][3]), "r"(a[AOFF + 2][0]), "r"(a[AOFF + 2][1]), "r"(a[AOFF + 2][2]), "r"(a[AOFF + 2][3]), "r"(a[AOFF + 3][0]), "r"(a[AOFF + 3][1]), "r"(a[AOFF + 3][2]), "r"(a[AOFF + 3][3]), "l"(descB), "n"(BOFF >> 4));
}
};
template <> struct Rng<0, 5, 10> {
template <int BOFF, int AOFF, int NA>
static __device__ __forceinline__ void run(float (&d)[48], const uint32_t (&a)[NA][4], uint64_t descB) {
    asm volatile(
        "{\n"
        ".reg .pred p0, p1;\n"
        ".reg .b64 ta, ta0, tb, tb0;\n"
        "setp.ne.b32 p0, 0, 0;\n"
        "setp.eq.b32 p1, 0, 0;\n"
        "add.s64 tb0, %68, %69;\n"
        "add.s64 tb, tb0, 1568;\n"
        "wgmma.mma_async.sync.aligned.m64n96k16.f32.bf16.bf16 {%0, %1, %2, %3, %4, %5, %6, %7, %8, %9, %10, %11, %12, %13, %14, %15, %16, %17, %18, %19, %20, %21, %22, %23, %24, %25, %26, %27, %28, %29, %30, %31, %32, %33, %34, %35, %36, %37, %38, %39, %40, %41, %42, %43, %44, %45, %46, %47}, {%48, %49, %50, %51}, tb, p1, 1, 1, 1;\n"
        "add.s64 tb, tb0, 1600;\n"
        "wgmma.mma_async.sync.aligned.m64n96k16.f32.bf16.bf16 {%0, %1, %2, %3, %4, %5, %6, %7, %8, %9, %10, %11, %12, %13, %14, %15, %16, %17, %18, %19, %20, %21, %22, %23, %24, %25, %26, %27, %28, %29, %30, %31, %32, %33, %34, %35, %36, %37, %38, %39, %40, %41, %42, %43, %44, %45, %46, %47}, {%52, %53, %54, %55}, tb, p1, 1, 1, 1;\n"
        "add.s64 tb, tb0, 1632;\n"
        "wgmma.mma_async.sync.aligned.m64n96k16.f32.bf16.bf16 {%0, %1, %2, %3, %4, %5, %6, %7, %8, %9, %10, %11, %12, %13, %14, %15, %16, %17, %18, %19, %20, %21, %22, %23, %24, %25, %26, %27, %28, %29, %30, %31, %32, %33, %34, %35, %36, %37, %38, %39, %40, %41, %42, %43, %44, %45, %46, %47}, {%56, %57, %58, %59}, tb, p1, 1, 1, 1;\n"
        "add.s64 tb, tb0, 3072;\n"
        "wgmma.mma_async.sync.aligned.m64n96k16.f32.bf16.bf16 {%0, %1, %2, %3, %4, %5, %6, %7, %8, %9, %10, %11, %12, %13, %14, %15, %16, %17, %18, %19, %20, %21, %22, %23, %24, %25, %26, %27, %28, %29, %30, %31, %32, %33, %34, %35, %36, %37, %38, %39, %40, %41, %42, %43, %44, %45, %46, %47}, {%60, %61, %62, %63}, tb, p1, 1, 1, 1;\n"
        "add.s64 tb, tb0, 3104;\n"
        "wgmma.mma_async.sync.aligned.m64n96k16.f32.bf16.bf16 {%0, %1, %2, %3, %4, %5, %6, %7, %8, %9, %10, %11, %12, %13, %14, %15, %16, %17, %18, %19, %20, %21, %22, %23, %24, %25, %26, %27, %28, %29, %30, %31, %32, %33, %34, %35, %36, %37, %38, %39, %40, %41, %42, %43, %44, %45, %46, %47}, {%64, %65, %66, %67}, tb, p1, 1, 1, 1;\n"
        "}\n"
        : "+f"(d[0]), "+f"(d[1]), "+f"(d[2]), "+f"(d[3]), "+f"(d[4]), "+f"(d[5]), "+f"(d[6]), "+f"(d[7]), "+f"(d[8]), "+f"(d[9]), "+f"(d[10]), "+f"(d[11]), "+f"(d[12]), "+f"(d[13]), "+f"(d[14]), "+f"(d[15]), "+f"(d[16]), "+f"(d[17]), "+f"(d[18]), "+f"(d[19]), "+f"(d[20]), "+f"(d[21]), "+f"(d[22]), "+f"(d[23]), "+f"(d[24]), "+f"(d[25]), "+f"(d[26]), "+f"(d[27]), "+f"(d[28]), "+f"(d[29]), "+f"(d[30]), "+f"(d[31]), "+f"(d[32]), "+f"(d[33]), "+f"(d[34]), "+f"(d[35]), "+f"(d[36]), "+f"(d[37]), "+f"(d[38]), "+f"(d[39]), "+f"(d[40]), "+f"(d[41]), "+f"(d[42]), "+f"(d[43]), "+f"(d[44]), "+f"(d[45]), "+f"(d[46]), "+f"(d[47])
        : "r"(a[AOFF + 0][0]), "r"(a[AOFF + 0][1]), "r"(a[AOFF + 0][2]), "r"(a[AOFF + 0][3]), "r"(a[AOFF + 1][0]), "r"(a[AOFF + 1][1]), "r"(a[AOFF + 1][2]), "r"(a[AOFF + 1][3]), "r"(a[AOFF + 2][0]), "r"(a[AOFF + 2][1]), "r"(a[AOFF + 2][2]), "r"(a[AOFF + 2][3]), "r"(a[AOFF + 3][0]), "r"(a[AOFF + 3][1]), "r"(a[AOFF + 3][2]), "r"(a[AOFF + 3][3]), "r"(a[AOFF + 4][0]), "r"(a[AOFF + 4][1]), "r"(a[AOFF + 4][2]), "r"(a[AOFF + 4][3]), "l"(descB), "n"(BOFF >> 4));
}
};
template <> struct Rng<1, 5, 10> {
template <int BOFF, int AOFF, int NA>
static __device__ __forceinline__ void run(float (&d)[48], const uint32_t (&a)[NA][4], uint64_t descB) {
    asm volatile(
        "{\n"
        ".reg .pred p0, p1;\n"
        ".reg .b64 ta, ta0, tb, tb0;\n"
        "setp.ne.b32 p0, 0, 0;\n"
        "setp.eq.b32 p1, 0, 0;\n"
        "add.s64 tb0, %68, %69;\n"
        "add.s64 tb, tb0, 160;\n"
        "wgmma.mma_async.sync.aligned.m64n96k16.f32.bf16.bf16 {%0, %1, %2, %3, %4, %5, %6, %7, %8, %9, %10, %11, %12, %13, %14, %15, %16, %17, %18, %19, %20, %21, %22, %23, %24, %25, %26, %27, %28, %29, %30, %31, %32, %33, %34, %35, %36, %37, %38, %39, %40, %41, %42, %43, %44, %45, %46, %47}, {%48, %49, %50, %51}, tb, p1, 1, 1, 1;\n"
        "add.s64 tb, tb0, 192;\n"
        "wgmma.mma_async.sync.aligned.m64n96k16.f32.bf16.bf16 {%0, %1, %2, %3, %4, %5, %6, %7, %8, %9, %10, %11, %12, %13, %14, %15, %16, %17, %18, %19, %20, %21, %22, %23, %24, %25, %26, %27, %28, %29, %30, %31, %32, %33, %34, %35, %36, %37, %38, %39, %40, %41, %42, %43, %44, %45, %46, %47}, {%52, %53, %54, %55}, tb, p1, 1, 1, 1;\n"
        "add.s64 tb, tb0, 224;\n"
        "wgmma.mma_async.sync.aligned.m64n96k16.f32.bf16.bf16 {%0, %1, %2, %3, %4, %5, %6, %7, %8, %9, %10, %11, %12, %13, %14, %15, %16, %17, %18, %19, %20, %21, %22, %23, %24, %25, %26, %27, %28, %29, %30, %31, %32, %33, %34, %35, %36, %37, %38, %39, %40, %41, %42, %43, %44, %45, %46, %47}, {%56, %57, %58, %59}, tb, p1, 1, 1, 1;\n"
        "add.s64 tb, tb0, 256;\n"
        "wgmma.mma_async.sync.aligned.m64n96k16.f32.bf16.bf16 {%0, %1, %2, %3, %4, %5, %6, %7, %8, %9, %10, %11, %12, %13, %14, %15, %16, %17, %18, %19, %20, %21, %22, %23, %24, %25, %26, %27, %28, %29, %30, %31, %32, %33, %34, %35, %36, %37, %38, %39, %40, %41, %42, %43, %44, %45, %46, %47}, {%60, %61, %62, %63}, tb, p1, 1, 1, 1;\n"
        "add.s64 tb, tb0, 288;\n"
        "wgmma.mma_async.sync.aligned.m64n96k16.f32.bf16.bf16 {%0, %1, %2, %3, %4, %5, %6, %7, %8, %9, %10, %11, %12, %13, %14, %15, %16, %17, %18, %19, %20, %21, %22, %23, %24, %25, %26, %27, %28, %29, %30, %31, %32, %33, %34, %35, %36, %37, %38, %39, %40, %41, %42, %43, %44, %45, %46, %47}, {%64, %65, %66, %67}, tb, p1, 1, 1, 1;\n"
        "}\n"
        : "+f"(d[0]), "+f"(d[1]), "+f"(d[2]), "+f"(d[3]), "+f"(d[4]), "+f"(d[5]), "+f"(d[6]), "+f"(d[7]), "+f"(d[8]), "+f"(d[9]), "+f"(d[10]), "+f"(d[11]), "+f"(d[12]), "+f"(d[13]), "+f"(d[14]), "+f"(d[15]), "+f"(d[16]), "+f"(d[17]), "+f"(d[18]), "+f"(d[19]), "+f"(d[20]), "+f"(d[21]), "+f"(d[22]), "+f"(d[23]), "+f"(d[24]), "+f"(d[25]), "+f"(d[26]), "+f"(d[27]), "+f"(d[28]), "+f"(d[29]), "+f"(d[30]), "+f"(d[31]), "+f"(d[32]), "+f"(d[33]), "+f"(d[34]), "+f"(d[35]), "+f"(d[36]), "+f"(d[37]), "+f"(d[38]), "+f"(d[39]), "+f"(d[40]), "+f"(d[41]), "+f"(d[42]), "+f"(d[43]), "+f"(d[44]), "+f"(d[45]), "+f"(d[46]), "+f"(d[47])
        : "r"(a[AOFF + 0][0]), "r"(a[AOFF + 0][1]), "r"(a[AOFF + 0][2]), "r"(a[AOFF + 0][3]), "r"(a[AOFF + 1][0]), "r"(a[AOFF + 1][1]), "r"(a[AOFF + 1][2]), "r"(a[AOFF + 1][3]), "r"(a[AOFF + 2][0]), "r"(a[AOFF + 2][1]), "r"(a[AOFF + 2][2]), "r"(a[AOFF + 2][3]), "r"(a[AOFF + 3][0]), "r"(a[AOFF + 3][1]), "r"(a[AOFF + 3][2]), "r"(a[AOFF + 3][3]), "r"(a[AOFF + 4][0]), "r"(a[AOFF + 4][1]), "r"(a[AOFF + 4][2]), "r"(a[AOFF + 4][3]), "l"(descB), "n"(BOFF >> 4));
}
};
template <> struct Rng<0, 5, 12> {
template <int BOFF, int AOFF, int NA>
static __device__ __forceinline__ void run(float (&d)[48], const uint32_t (&a)[NA][4], uint64_t descB) {
    asm volatile(
        "{\n"
        ".reg .pred p0, p1;\n"
        ".reg .b64 ta, ta0, tb, tb0;\n"
        "setp.ne.b32 p0, 0, 0;\n"
        "setp.eq.b32 p1, 0, 0;\n"
        "add.s64 tb0, %76, %77;\n"
        "add.s64 tb, tb0, 1568;\n"
        "wgmma.mma_async.sync.aligned.m64n96k16.f32.bf16.bf16 {%0, %1, %2, %3, %4, %5, %6, %7, %8, %9, %10, %11, %12, %13, %14, %15, %16, %17, %18, %19, %20, %21, %22, %23, %24, %25, %26, %27, %28, %29, %30, %31, %32, %33, %34, %35, %36, %37, %38, %39, %40, %41, %42, %43, %44, %45, %46, %47}, {%48, %49, %50, %51}, tb, p1, 1, 1, 1;\n"
        "add.s64 tb, tb0, 1600;\n"
        "wgmma.mma_async.sync.aligned.m64n96k16.f32.bf16.bf16 {%0, %1, %2, %3, %4, %5, %6, %7, %8, %9, %10, %11, %12, %13, %14, %15, %16, %17, %18, %19, %20, %21, %22, %23, %24, %25, %26, %27, %28, %29, %30, %31, %32, %33, %34, %35, %36, %37, %38, %39, %40, %41, %42, %43, %44, %45, %46, %47}, {%52, %53, %54, %55}, tb, p1, 1, 1, 1;\n"
        "add.s64 tb, tb0, 1632;\n"
        "wgmma.mma_async.sync.aligned.m64n96k16.f32.bf16.bf16 {%0, %1, %2, %3, %4, %5, %6, %7, %8, %9, %10, %11, %12, %13, %14, %15, %16, %17, %18, %19, %20, %21, %22, %23, %24, %25, %26, %27, %28, %29, %30, %31, %32, %33, %34, %35, %36, %37, %38, %39, %40, %41, %42, %43, %44, %45, %46, %47}, {%56, %57, %58, %59}, tb, p1, 1, 1, 1;\n"
        "add.s64 tb, tb0, 3072;\n"
        "wgmma.mma_async.sync.aligned.m64n96k16.f32.bf16.bf16 {%0, %1, %2, %3, %4, %5, %6, %7, %8, %9, %10, %11, %12, %13, %14, %15, %16, %17, %18, %19, %20, %21, %22, %23, %24, %25, %26, %27, %28, %29, %30, %31, %32, %33, %34, %35, %36, %37, %38, %39, %40, %41, %42, %43, %44, %45, %46, %47}, {%60, %61, %62, %63}, tb, p1, 1, 1, 1;\n"
        "add.s64 tb, tb0, 3104;\n"
        "wgmma.mma_async.sync.aligned.m64n96k16.f32.bf16.bf16 {%0, %1, %2, %3, %4, %5, %6, %7, %8, %9, %10, %11, %12, %13, %14, %15, %16, %17, %18, %19, %20, %21, %22, %23, %24, %25, %26, %27, %28, %29, %30, %31, %32, %33, %34, %35, %36, %37, %38, %39, %40, %41, %42, %43, %44, %45, %46, %47}, {%64, %65, %66, %67}, tb, p1, 1, 1, 1;\n"
        "add.s64 tb, tb0, 3136;\n"
        "wgmma.mma_async.sync.aligned.m64n96k16.f32.bf16.bf16 {%0, %1, %2, %3, %4, %5, %6, %7, %8, %9, %10, %11, %12, %13, %14, %15, %16, %17, %18, %19, %20, %21, %22, %23, %24, %25, %26, %27, %28, %29, %30, %31, %32, %33, %34, %35, %36, %37, %38, %39, %40, %41, %42, %43, %44, %45, %46, %47}, {%68, %69, %70, %71}, tb, p1, 1, 1, 1;\n"
        "add.s64 tb, tb0, 3168;\n"
        "wgmma.mma_async.sync.aligned.m64n96k16.f32.bf16.bf16 {%0, %1, %2, %3, %4, %5, %6, %7, %8, %9, %10, %11, %12, %13, %14, %15, %16, %17, %18, %19, %20, %21, %22, %23, %24, %25, %26, %27, %28, %29, %30, %31, %32, %33, %34, %35, %36, %37, %38, %39, %40, %41, %42, %43, %44, %45, %46, %47}, {%72, %73, %74, %75}, tb, p1, 1, 1, 1;\n"
        "}\n"
        : "+f"(d[0]), "+f"(d[1]), "+f"(d[2]), "+f"(d[3]), "+f"(d[4]), "+f"(d[5]), "+f"(d[6]), "+f"(d[7]), "+f"(d[8]), "+f"(d[9]), "+f"(d[10]), "+f"(d[11]), "+f"(d[12]), "+f"(d[13]), "+f"(d[14]), "+f"(d[15]), "+f"(d[16]), "+f"(d[17]), "+f"(d[18]), "+f"(d[19]), "+f"(d[20]), "+f"(d[21]), "+f"(d[22]), "+f"(d[23]), "+f"(d[24]), "+f"(d[25]), "+f"(d[26]), "+f"(d[27]), "+f"(d[28]), "+f"(d[29]), "+f"(d[30]), "+f"(d[31]), "+f"(d[32]), "+f"(d[33]), "+f"(d[34]), "+f"(d[35]), "+f"(d[36]), "+f"(d[37]), "+f"(d[38]), "+f"(d[39]), "+f"(d[40]), "+f"(d[41]), "+f"(d[42]), "+f"(d[43]), "+f"(d[44]), "+f"(d[45]), "+f"(d[46]), "+f"(d[47])
        : "r"(a[AOFF + 0][0]), "r"(a[AOFF + 0][1]), "r"(a[AOFF + 0][2]), "r"(a[AOFF + 0][3]), "r"(a[AOFF + 1][0]), "r"(a[AOFF + 1][1]), "r"(a[AOFF + 1][2]), "r"(a[AOFF + 1][3]), "r"(a[AOFF + 2][0]), "r"(a[AOFF + 2][1]), "r"(a[AOFF + 2][2]), "r"(a[AOFF + 2][3]), "r"(a[AOFF + 3][0]), "r"(a[AOFF + 3][1]), "r"(a[AOFF + 3][2]), "r"(a[AOFF + 3][3]), "r"(a[AOFF + 4][0]), "r"(a[AOFF + 4][1]), "r"(a[AOFF + 4][2]), "r"(a[AOFF + 4][3]), "r"(a[AOFF + 5][0]), "r"(a[AOFF + 5][1]), "r"(a[AOFF + 5][2]), "r"(a[AOFF + 5][3]), "r"(a[AOFF + 6][0]), "r"(a[AOFF + 6][1]), "r"(a[AOFF + 6][2]), "r"(a[AOFF + 6][3]), "l"(descB), "n"(BOFF >> 4));
}
};
template <> struct Rng<1, 5, 12> {
template <int BOFF, int AOFF, int NA>
static __device__ __forceinline__ void run(float (&d)[48], const uint32_t (&a)[NA][4], uint64_t descB) {
    asm volatile(
        "{\n"
        ".reg .pred p0, p1;\n"
        ".reg .b64 ta, ta0, tb, tb0;\n"
        "setp.ne.b32 p0, 0, 0;\n"
        "setp.eq.b32 p1, 0, 0;\n"
        "add.s64 tb0, %76, %77;\n"
        "add.s64 tb, tb0, 160;\n"
        "wgmma.mma_async.sync.aligned.m64n96k16.f32.bf16.bf16 {%0, %1, %2, %3, %4, %5, %6, %7, %8, %9, %10, %11, %12, %13, %14, %15, %16, %17, %18, %19, %20, %21, %22, %23, %24, %25, %26, %27, %28, %29, %30, %31, %32, %33, %34, %35, %36, %37, %38, %39, %40, %41, %42, %43, %44, %45, %46, %47}, {%48, %49, %50, %51}, tb, p1, 1, 1, 1;\n"
        "add.s64 tb, tb0, 192;\n"
        "wgmma.mma_async.sync.aligned.m64n96k16.f32.bf16.bf16 {%0, %1, %2, %3, %4, %5, %6, %7, %8, %9, %10, %11, %12, %13, %14, %15, %16, %17, %18, %19, %20, %21, %22, %23, %24, %25, %26, %27, %28, %29, %30, %31, %32, %33, %34, %35, %36, %37, %38, %39, %40, %41, %42, %43, %44, %45, %46, %47}, {%52, %53, %54, %55}, tb, p1, 1, 1, 1;\n"
        "add.s64 tb, tb0, 224;\n"
        "wgmma.mma_async.sync.aligned.m64n96k16.f32.bf16.bf16 {%0, %1, %2, %3, %4, %5, %6, %7, %8, %9, %10, %11, %12, %13, %14, %15, %16, %17, %18, %19, %20, %21, %22, %23, %24, %25, %26, %27, %28, %29, %30, %31, %32, %33, %34, %35, %36, %37, %38, %39, %40, %41, %42, %43, %44, %45, %46, %47}, {%56, %57, %58, %59}, tb, p1, 1, 1, 1;\n"
        "add.s64 tb, tb0, 256;\n"
        "wgmma.mma_async.sync.aligned.m64n96k16.f32.bf16.bf16 {%0, %1, %2, %3, %4, %5, %6, %7, %8, %9, %10, %11, %12, %13, %14, %15, %16, %17, %18, %19, %20, %21, %22, %23, %24, %25, %26, %27, %28, %29, %30, %31, %32, %33, %34, %35, %36, %37, %38, %39, %40, %41, %42, %43, %44, %45, %46, %47}, {%60, %61, %62, %63}, tb, p1, 1, 1, 1;\n"
        "add.s64 tb, tb0, 288;\n"
        "wgmma.mma_async.sync.aligned.m64n96k16.f32.bf16.bf16 {%0, %1, %2, %3, %4, %5, %6, %7, %8, %9, %10, %11, %12, %13, %14, %15, %16, %17, %18, %19, %20, %21, %22, %23, %24, %25, %26, %27, %28, %29, %30, %31, %32, %33, %34, %35, %36, %37, %38, %39, %40, %41, %42, %43, %44, %45, %46, %47}, {%64, %65, %66, %67}, tb, p1, 1, 1, 1;\n"
        "add.s64 tb, tb0, 320;\n"
        "wgmma.mma_async.sync.aligned.m64n96k16.f32.bf16.bf16 {%0, %1, %2, %3, %4, %5, %6, %7, %8, %9, %10, %11, %12, %13, %14, %15, %16, %17, %18, %19, %20, %21, %22, %23, %24, %25, %26, %27, %28, %29, %30, %31, %32, %33, %34, %35, %36, %37, %38, %39, %40, %41, %42, %43, %44, %45, %46, %47}, {%68, %69, %70, %71}, tb, p1, 1, 1, 1;\n"
        "add.s64 tb, tb0, 352;\n"
        "wgmma.mma_async.sync.aligned.m64n96k16.f32.bf16.bf16 {%0, %1, %2, %3, %4, %5, %6, %7, %8, %9, %10, %11, %12, %13, %14, %15, %16, %17, %18, %19, %20, %21, %22, %23, %24, %25, %26, %27, %28, %29, %30, %31, %32, %33, %34, %35, %36, %37, %38, %39, %40, %41, %42, %43, %44, %45, %46, %47}, {%72, %73, %74, %75}, tb, p1, 1, 1, 1;\n"
        "}\n"
        : "+f"(d[0]), "+f"(d[1]), "+f"(d[2]), "+f"(d[3]), "+f"(d[4]), "+f"(d[5]), "+f"(d[6]), "+f"(d[7]), "+f"(d[8]), "+f"(d[9]), "+f"(d[10]), "+f"(d[11]), "+f"(d[12]), "+f"(d[13]), "+f"(d[14]), "+f"(d[15]), "+f"(d[16]), "+f"(d[17]), "+f"(d[18]), "+f"(d[19]), "+f"(d[20]), "+f"(d[21]), "+f"(d[22]), "+f"(d[23]), "+f"(d[24]), "+f"(d[25]), "+f"(d[26]), "+f"(d[27]), "+f"(d[28]), "+f"(d[29]), "+f"(d[30]), "+f"(d[31]), "+f"(d[32]), "+f"(d[33]), "+f"(d[34]), "+f"(d[35]), "+f"(d[36]), "+f"(d[37]), "+f"(d[38]), "+f"(d[39]), "+f"(d[40]), "+f"(d[41]), "+f"(d[42]), "+f"(d[43]), "+f"(d[44]), "+f"(d[45]), "+f"(d[46]), "+f"(d[47])
        : "r"(a[AOFF + 0][0]), "r"(a[AOFF + 0][1]), "r"(a[AOFF + 0][2]), "r"(a[AOFF + 0][3]), "r"(a[AOFF + 1][0]), "r"(a[AOFF + 1][1]), "r"(a[AOFF + 1][2]), "r"(a[AOFF + 1][3]), "r"(a[AOFF + 2][0]), "r"(a[AOFF + 2][1]), "r"(a[AOFF + 2][2]), "r"(a[AOFF + 2][3]), "r"(a[AOFF + 3][0]), "r"(a[AOFF + 3][1]), "r"(a[AOFF + 3][2]), "r"(a[AOFF + 3][3]), "r"(a[AOFF + 4][0]), "r"(a[AOFF + 4][1]), "r"(a[AOFF + 4][2]), "r"(a[AOFF + 4][3]), "r"(a[AOFF + 5][0]), "r"(a[AOFF + 5][1]), "r"(a[AOFF + 5][2]), "r"(a[AOFF + 5][3]), "r"(a[AOFF + 6][0]), "r"(a[AOFF + 6][1]), "r"(a[AOFF + 6][2]), "r"(a[AOFF + 6][3]), "l"(descB), "n"(BOFF >> 4));
}
};
template <> struct Rng<0, 6, 9> {
template <int BOFF, int AOFF, int NA>
static __device__ __forceinline__ void run(float (&d)[48], const uint32_t (&a)[NA][4], uint64_t descB) {
    asm volatile(
        "{\n"
        ".reg .pred p0, p1;\n"
        ".reg .b64 ta, ta0, tb, tb0;\n"
        "setp.ne.b32 p0, 0, 0;\n"
        "setp.eq.b32 p1, 0, 0;\n"
        "add.s64 tb0, %60, %61;\n"
        "add.s64 tb, tb0, 1600;\n"
        "wgmma.mma_async.sync.aligned.m64n96k16.f32.bf16.bf16 {%0, %1, %2, %3, %4, %5, %6, %7, %8, %9, %10, %11, %12, %13, %14, %15, %16, %17, %18, %19, %20, %21, %22, %23, %24, %25, %26, %27, %28, %29, %30, %31, %32, %33, %34, %35, %36, %37, %38, %39, %40, %41, %42, %43, %44, %45, %46, %47}, {%48, %49, %50, %51}, tb, p1, 1, 1, 1;\n"
        "add.s64 tb, tb0, 1632;\n"
        "wgmma.mma_async.sync.aligned.m64n96k16.f32.bf16.bf16 {%0, %1, %2, %3, %4, %5, %6, %7, %8, %9, %10, %11, %12, %13, %14, %15, %16, %17, %18, %19, %20, %21, %22, %23, %24, %25, %26, %27, %28, %29, %30, %31, %32, %33, %34, %35, %36, %37, %38, %39, %40, %41, %42, %43, %44, %45, %46, %47}, {%52, %53, %54, %55}, tb, p1, 1, 1, 1;\n"
        "add.s64 tb, tb0, 3072;\n"
        "wgmma.mma_async.sync.aligned.m64n96k16.f32.bf16.bf16 {%0, %1, %2, %3, %4, %5, %6, %7, %8, %9, %10, %11, %12, %13, %14, %15, %16, %17, %18, %19, %20, %21, %22, %23, %24, %25, %26, %27, %28, %29, %30, %31, %32, %33, %34, %35, %36, %37, %38, %39, %40, %41, %42, %43, %44, %45, %46, %47}, {%56, %57, %58, %59}, tb, p1, 1, 1, 1;\n"
        "}\n"
        : "+f"(d[0]), "+f"(d[1]), "+f"(d[2]), "+f"(d[3]), "+f"(d[4]), "+f"(d[5]), "+f"(d[6]), "+f"(d[7]), "+f"(d[8]), "+f"(d[9]), "+f"(d[10]), "+f"(d[11]), "+f"(d[12]), "+f"(d[13]), "+f"(d[14]), "+f"(d[15]), "+f"(d[16]), "+f"(d[17]), "+f"(d[18]), "+f"(d[19]), "+f"(d[20]), "+f"(d[21]), "+f"(d[22]), "+f"(d[23]), "+f"(d[24]), "+f"(d[25]), "+f"(d[26]), "+f"(d[27]), "+f"(d[28]), "+f"(d[29]), "+f"(d[30]), "+f"(d[31]), "+f"(d[32]), "+f"(d[33]), "+f"(d[34]), "+f"(d[35]), "+f"(d[36]), "+f"(d[37]), "+f"(d[38]), "+f"(d[39]), "+f"(d[40]), "+f"(d[41]), "+f"(d[42]), "+f"(d[43]), "+f"(d[44]), "+f"(d[45]), "+f"(d[46]), "+f"(d[47])
        : "r"(a[AOFF + 0][0]), "r"(a[AOFF + 0][1]), "r"(a[AOFF + 0][2]), "r"(a[AOFF + 0][3]), "r"(a[AOFF + 1][0]), "r"(a[AOFF + 1][1]), "r"(a[AOFF + 1][2]), "r"(a[AOFF + 1][3]), "r"(a[AOFF + 2][0]), "r"(a[AOFF + 2][1]), "r"(a[AOFF + 2][2]), "r"(a[AOFF + 2][3]), "l"(descB), "n"(BOFF >> 4));
}
};
template <> struct Rng<1, 6, 9> {
template <int BOFF, int AOFF, int NA>
static __device__ __forceinline__ void run(float (&d)[48], const uint32_t (&a)[NA][4], uint64_t descB) {
    asm volatile(
        "{\n"
        ".reg .pred p0, p1;\n"
        ".reg .b64 ta, ta0, tb, tb0;\n"
        "setp.ne.b32 p0, 0, 0;\n"
        "setp.eq.b32 p1, 0, 0;\n"
        "add.s64 tb0, %60, %61;\n"
        "add.s64 tb, tb0, 192;\n"
        "wgmma.mma_async.sync.aligned.m64n96k16.f32.bf16.bf16 {%0, %1, %2, %3, %4, %5, %6, %7, %8, %9, %10, %11, %12, %13, %14, %15, %16, %17, %18, %19, %20, %21, %22, %23, %24, %25, %26, %27, %28, %29, %30, %31, %32, %33, %34, %35, %36, %37, %38, %39, %40, %41, %42, %43, %44, %45, %46, %47}, {%48, %49, %50, %51}, tb, p1, 1, 1, 1;\n"
        "add.s64 tb, tb0, 224;\n"
        "wgmma.mma_async.sync.aligned.m64n96k16.f32.bf16.bf16 {%0, %1, %2, %3, %4, %5, %6, %7, %8, %9, %10, %11, %12, %13, %14, %15, %16, %17, %18, %19, %20, %21, %22, %23, %24, %25, %26, %27, %28, %29, %30, %31, %32, %33, %34, %35, %36, %37, %38, %39, %40, %41, %42, %43, %44, %45, %46, %47}, {%52, %53, %54, %55}, tb, p1, 1, 1, 1;\n"
        "add.s64 tb, tb0, 256;\n"
        "wgmma.mma_async.sync.aligned.m64n96k16.f32.bf16.bf16 {%0, %1, %2, %3, %4, %5, %6, %7, %8, %9, %10, %11, %12, %13, %14, %15, %16, %17, %18, %19, %20, %21, %22, %23, %24, %25, %26, %27, %28, %29, %30, %31, %32, %33, %34, %35, %36, %37, %38, %39, %40, %41, %42, %43, %44, %45, %46, %47}, {%56, %57, %58, %59}, tb, p1, 1, 1, 1;\n"
        "}\n"
        : "+f"(d[0]), "+f"(d[1]), "+f"(d[2]), "+f"(d[3]), "+f"(d[4]), "+f"(d[5]), "+f"(d[6]), "+f"(d[7]), "+f"(d[8]), "+f"(d[9]), "+f"(d[10]), "+f"(d[11]), "+f"(d[12]), "+f"(d[13]), "+f"(d[14]), "+f"(d[15]), "+f"(d[16]), "+f"(d[17]), "+f"(d[18]), "+f"(d[19]), "+f"(d[20]), "+f"(d[21]), "+f"(d[22]), "+f"(d[23]), "+f"(d[24]), "+f"(d[25]), "+f"(d[26]), "+f"(d[27]), "+f"(d[28]), "+f"(d[29]), "+f"(d[30]), "+f"(d[31]), "+f"(d[32]), "+f"(d[33]), "+f"(d[34]), "+f"(d[35]), "+f"(d[36]), "+f"(d[37]), "+f"(d[38]), "+f"(d[39]), "+f"(d[40]), "+f"(d[41]), "+f"(d[42]), "+f"(d[43]), "+f"(d[44]), "+f"(d[45]), "+f"(d[46]), "+f"(d[47])
        : "r"(a[AOFF + 0][0]), "r"(a[AOFF + 0][1]), "r"(a[AOFF + 0][2]), "r"(a[AOFF + 0][3]), "r"(a[AOFF + 1][0]), "r"(a[AOFF + 1][1]), "r"(a[AOFF + 1][2]), "r"(a[AOFF + 1][3]), "r"(a[AOFF + 2][0]), "r"(a[AOFF + 2][1]), "r"(a[AOFF + 2][2]), "r"(a[AOFF + 2][3]), "l"(descB), "n"(BOFF >> 4));
}
};
template <> struct Rng<0, 6, 10> {
template <int BOFF, int AOFF, int NA>
static __device__ __forceinline__ void run(float (&d)[48], const uint32_t (&a)[NA][4], uint64_t descB) {
    asm volatile(
        "{\n"
        ".reg .pred p0, p1;\n"
        ".reg .b64 ta, ta0, tb, tb0;\n"
        "setp.ne.b32 p0, 0, 0;\n"
        "setp.eq.b32 p1, 0, 0;\n"
        "add.s64 tb0, %64, %65;\n"
        "add.s64 tb, tb0, 1600;\n"
        "wgmma.mma_async.sync.aligned.m64n96k16.f32.bf16.bf16 {%0, %1, %2, %3, %4, %5, %6, %7, %8, %9, %10, %11, %12, %13, %14, %15, %16, %17, %18, %19, %20, %21, %22, %23, %24, %25, %26, %27, %28, %29, %30, %31, %32, %33, %34, %35, %36, %37, %38, %39, %40, %41, %42, %43, %44, %45, %46, %47}, {%48, %49, %50, %51}, tb, p1, 1, 1, 1;\n"
        "add.s64 tb, tb0, 1632;\n"
        "wgmma.mma_async.sync.aligned.m64n96k16.f32.bf16.bf16 {%0, %1, %2, %3, %4, %5, %6, %7, %8, %9, %10, %11, %12, %13, %14, %15, %16, %17, %18, %19, %20, %21, %22, %23, %24, %25, %26, %27, %28, %29, %30, %31, %32, %33, %34, %35, %36, %37, %38, %39, %40, %41, %42, %43, %44, %45, %46, %47}, {%52, %53, %54, %55}, tb, p1, 1, 1, 1;\n"
        "add.s64 tb, tb0, 3072;\n"
        "wgmma.mma_async.sync.aligned.m64n96k16.f32.bf16.bf16 {%0, %1, %2, %3, %4, %5, %6, %7, %8, %9, %10, %11, %12, %13, %14, %15, %16, %17, %18, %19, %20, %21, %22, %23, %24, %25, %26, %27, %28, %29, %30, %31, %32, %33, %34, %35, %36, %37, %38, %39, %40, %41, %42, %43, %44, %45, %46, %47}, {%56, %57, %58, %59}, tb, p1, 1, 1, 1;\n"
        "add.s64 tb, tb0, 3104;\n"
        "wgmma.mma_async.sync.aligned.m64n96k16.f32.bf16.bf16 {%0, %1, %2, %3, %4, %5, %6, %7, %8, %9, %10, %11, %12, %13, %14, %15, %16, %17, %18, %19, %20, %21, %22, %23, %24, %25, %26, %27, %28, %29, %30, %31, %32, %33, %34, %35, %36, %37, %38, %39, %40, %41, %42, %43, %44, %45, %46, %47}, {%60, %61, %62, %63}, tb, p1, 1, 1, 1;\n"
        "}\n"
        : "+f"(d[0]), "+f"(d[1]), "+f"(d[2]), "+f"(d[3]), "+f"(d[4]), "+f"(d[5]), "+f"(d[6]), "+f"(d[7]), "+f"(d[8]), "+f"(d[9]), "+f"(d[10]), "+f"(d[11]), "+f"(d[12]), "+f"(d[13]), "+f"(d[14]), "+f"(d[15]), "+f"(d[16]), "+f"(d[17]), "+f"(d[18]), "+f"(d[19]), "+f"(d[20]), "+f"(d[21]), "+f"(d[22]), "+f"(d[23]), "+f"(d[24]), "+f"(d[25]), "+f"(d[26]), "+f"(d[27]), "+f"(d[28]), "+f"(d[29]), "+f"(d[30]), "+f"(d[31]), "+f"(d[32]), "+f"(d[33]), "+f"(d[34]), "+f"(d[35]), "+f"(d[36]), "+f"(d[37]), "+f"(d[38]), "+f"(d[39]), "+f"(d[40]), "+f"(d[41]), "+f"(d[42]), "+f"(d[43]), "+f"(d[44]), "+f"(d[45]), "+f"(d[46]), "+f"(d[47])
        : "r"(a[AOFF + 0][0]), "r"(a[AOFF + 0][1]), "r"(a[AOFF + 0][2]), "r"(a[AOFF + 0][3]), "r"(a[AOFF + 1][0]), "r"(a[AOFF + 1][1]), "r"(a[AOFF + 1][2]), "r"(a[AOFF + 1][3]), "r"(a[AOFF + 2][0]), "r"(a[AOFF + 2][1]), "r"(a[AOFF + 2][2]), "r"(a[AOFF + 2][3]), "r"(a[AOFF + 3][0]), "r"(a[AOFF + 3][1]), "r"(a[AOFF + 3][2]), "r"(a[AOFF + 3][3]), "l"(descB), "n"(BOFF >> 4));
}
};
template <> struct Rng<1, 6, 10> {
template <int BOFF, int AOFF, int NA>
static __device__ __forceinline__ void run(float (&d)[48], const uint32_t (&a)[NA][4], uint64_t descB) {
    asm volatile(
        "{\n"
        ".reg .pred p0, p1;\n"
        ".reg .b64 ta, ta0, tb, tb0;\n"
        "setp.ne.b32 p0, 0, 0;\n"
        "setp.eq.b32 p1, 0, 0;\n"
        "add.s64 tb0, %64, %65;\n"
        "add.s64 tb, tb0, 192;\n"
        "wgmma.mma_async.sync.aligned.m64n96k16.f32.bf16.bf16 {%0, %1, %2, %3, %4, %5, %6, %7, %8, %9, %10, %11, %12, %13, %14, %15, %16, %17, %18, %19, %20, %21, %22, %23, %24, %25, %26, %27, %28, %29, %30, %31, %32, %33, %34, %35, %36, %37, %38, %39, %40, %41, %42, %43, %44, %45, %46, %47}, {%48, %49, %50, %51}, tb, p1, 1, 1, 1;\n"
        "add.s64 tb, tb0, 224;\n"
        "wgmma.mma_async.sync.aligned.m64n96k16.f32.bf16.bf16 {%0, %1, %2, %3, %4, %5, %6, %7, %8, %9, %10, %11, %12, %13, %14, %15, %16, %17, %18, %19, %20, %21, %22, %23, %24, %25, %26, %27, %28, %29, %30, %31, %32, %33, %34, %35, %36, %37, %38, %39, %40, %41, %42, %43, %44, %45, %46, %47}, {%52, %53, %54, %55}, tb, p1, 1, 1, 1;\n"
        "add.s64 tb, tb0, 256;\n"
        "wgmma.mma_async.sync.aligned.m64n96k16.f32.bf16.bf16 {%0, %1, %2, %3, %4, %5, %6, %7, %8, %9, %10, %11, %12, %13, %14, %15, %16, %17, %18, %19, %20, %21, %22, %23, %24, %25, %26, %27, %28, %29, %30, %31, %32, %33, %34, %35, %36, %37, %38, %39, %40, %41, %42, %43, %44, %45, %46, %47}, {%56, %57, %58, %59}, tb, p1, 1, 1, 1;\n"
        "add.s64 tb, tb0, 288;\n"
        "wgmma.mma_async.sync.aligned.m64n96k16.f32.bf16.bf16 {%0, %1, %2, %3, %4, %5, %6, %7, %8, %9, %10, %11, %12, %13, %14, %15, %16, %17, %18, %19, %20, %21, %22, %23, %24, %25, %26, %27, %28, %29, %30, %31, %32, %33, %34, %35, %36, %37, %38, %39, %40, %41, %42, %43, %44, %45, %46, %47}, {%60, %61, %62, %63}, tb, p1, 1, 1, 1;\n"
        "}\n"
        : "+f"(d[0]), "+f"(d[1]), "+f"(d[2]), "+f"(d[3]), "+f"(d[4]), "+f"(d[5]), "+f"(d[6]), "+f"(d[7]), "+f"(d[8]), "+f"(d[9]), "+f"(d[10]), "+f"(d[11]), "+f"(d[12]), "+f"(d[13]), "+f"(d[14]), "+f"(d[15]), "+f"(d[16]), "+f"(d[17]), "+f"(d[18]), "+f"(d[19]), "+f"(d[20]), "+f"(d[21]), "+f"(d[22]), "+f"(d[23]), "+f"(d[24]), "+f"(d[25]), "+f"(d[26]), "+f"(d[27]), "+f"(d[28]), "+f"(d[29]), "+f"(d[30]), "+f"(d[31]), "+f"(d[32]), "+f"(d[33]), "+f"(d[34]), "+f"(d[35]), "+f"(d[36]), "+f"(d[37]), "+f"(d[38]), "+f"(d[39]), "+f"(d[40]), "+f"(d[41]), "+f"(d[42]), "+f"(d[43]), "+f"(d[44]), "+f"(d[45]), "+f"(d[46]), "+f"(d[47])
        : "r"(a[AOFF + 0][0]), "r"(a[AOFF + 0][1]), "r"(a[AOFF + 0][2]), "r"(a[AOFF + 0][3]), "r"(a[AOFF + 1][0]), "r"(a[AOFF + 1][1]), "r"(a[AOFF + 1][2]), "r"(a[AOFF + 1][3]), "r"(a[AOFF + 2][0]), "r"(a[AOFF + 2][1]), "r"(a[AOFF + 2][2]), "r"(a[AOFF + 2][3]), "r"(a[AOFF + 3][0]), "r"(a[AOFF + 3][1]), "r"(a[AOFF + 3][2]), "r"(a[AOFF + 3][3]), "l"(descB), "n"(BOFF >> 4));
}
};
template <> struct Rng<0, 6, 12> {
template <int BOFF, int AOFF, int NA>
static __device__ __forceinline__ void run(float (&d)[48], const uint32_t (&a)[NA][4], uint64_t descB) {
    asm volatile(
        "{\n"
        ".reg .pred p0, p1;\n"
        ".reg .b64 ta, ta0, tb, tb0;\n"
        "setp.ne.b32 p0, 0, 0;\n"
        "setp.eq.b32 p1, 0, 0;\n"
        "add.s64 tb0, %72, %73;\n"
        "add.s64 tb, tb0, 1600;\n"
        "wgmma.mma_async.sync.aligned.m64n96k16.f32.bf16.bf16 {%0, %1, %2, %3, %4, %5, %6, %7, %8, %9, %10, %11, %12, %13, %14, %15, %16, %17, %18, %19, %20, %21, %22, %23, %24, %25, %26, %27, %28, %29, %30, %31, %32, %33, %34, %35, %36, %37, %38, %39, %40, %41, %42, %43, %44, %45, %46, %47}, {%48, %49, %50, %51}, tb, p1, 1, 1, 1;\n"
        "add.s64 tb, tb0, 1632;\n"
        "wgmma.mma_async.sync.aligned.m64n96k16.f32.bf16.bf16 {%0, %1, %2, %3, %4, %5, %6, %7, %8, %9, %10, %11, %12, %13, %14, %15, %16, %17, %18, %19, %20, %21, %22, %23, %24, %25, %26, %27, %28, %29, %30, %31, %32, %33, %34, %35, %36, %37, %38, %39, %40, %41, %42, %43, %44, %45, %46, %47}, {%52, %53, %54, %55}, tb, p1, 1, 1, 1;\n"
        "add.s64 tb, tb0, 3072;\n"
        "wgmma.mma_async.sync.aligned.m64n96k16.f32.bf16.bf16 {%0, %1, %2, %3, %4, %5, %6, %7, %8, %9, %10, %11, %12, %13, %14, %15, %16, %17, %18, %19, %20, %21, %22, %23, %24, %25, %26, %27, %28, %29, %30, %31, %32, %33, %34, %35, %36, %37, %38, %39, %40, %41, %42, %43, %44, %45, %46, %47}, {%56, %57, %58, %59}, tb, p1, 1, 1, 1;\n"
        "add.s64 tb, tb0, 3104;\n"
        "wgmma.mma_async.sync.aligned.m64n96k16.f32.bf16.bf16 {%0, %1, %2, %3, %4, %5, %6, %7, %8, %9, %10, %11, %12, %13, %14, %15, %16, %17, %18, %19, %20, %21, %22, %23, %24, %25, %26, %27, %28, %29, %30, %31, %32, %33, %34, %35, %36, %37, %38, %39, %40, %41, %42, %43, %44, %45, %46, %47}, {%60, %61, %62, %63}, tb, p1, 1, 1, 1;\n"
        "add.s64 tb, tb0, 3136;\n"
        "wgmma.mma_async.sync.aligned.m64n96k16.f32.bf16.bf16 {%0, %1, %2, %3, %4, %5, %6, %7, %8, %9, %10, %11, %12, %13, %14, %15, %16, %17, %18, %19, %20, %21, %22, %23, %24, %25, %26, %27, %28, %29, %30, %31, %32, %33, %34, %35, %36, %37, %38, %39, %40, %41, %42, %43, %44, %45, %46, %47}, {%64, %65, %66, %67}, tb, p1, 1, 1, 1;\n"
        "add.s64 tb, tb0, 3168;\n"
        "wgmma.mma_async.sync.aligned.m64n96k16.f32.bf16.bf16 {%0, %1, %2, %3, %4, %5, %6, %7, %8, %9, %10, %11, %12, %13, %14, %15, %16, %17, %18, %19, %20, %21, %22, %23, %24, %25, %26, %27, %28, %29, %30, %31, %32, %33, %34, %35, %36, %37, %38, %39, %40, %41, %42, %43, %44, %45, %46, %47}, {%68, %69, %70, %71}, tb, p1, 1, 1, 1;\n"
        "}\n"
        : "+f"(d[0]), "+f"(d[1]), "+f"(d[2]), "+f"(d[3]), "+f"(d[4]), "+f"(d[5]), "+f"(d[6]), "+f"(d[7]), "+f"(d[8]), "+f"(d[9]), "+f"(d[10]), "+f"(d[11]), "+f"(d[12]), "+f"(d[13]), "+f"(d[14]), "+f"(d[15]), "+f"(d[16]), "+f"(d[17]), "+f"(d[18]), "+f"(d[19]), "+f"(d[20]), "+f"(d[21]), "+f"(d[22]), "+f"(d[23]), "+f"(d[24]), "+f"(d[25]), "+f"(d[26]), "+f"(d[27]), "+f"(d[28]), "+f"(d[29]), "+f"(d[30]), "+f"(d[31]), "+f"(d[32]), "+f"(d[33]), "+f"(d[34]), "+f"(d[35]), "+f"(d[36]), "+f"(d[37]), "+f"(d[38]), "+f"(d[39]), "+f"(d[40]), "+f"(d[41]), "+f"(d[42]), "+f"(d[43]), "+f"(d[44]), "+f"(d[45]), "+f"(d[46]), "+f"(d[47])
        : "r"(a[AOFF + 0][0]), "r"(a[AOFF + 0][1]), "r"(a[AOFF + 0][2]), "r"(a[AOFF + 0][3]), "r"(a[AOFF + 1][0]), "r"(a[AOFF + 1][1]), "r"(a[AOFF + 1][2]), "r"(a[AOFF + 1][3]), "r"(a[AOFF + 2][0]), "r"(a[AOFF + 2][1]), "r"(a[AOFF + 2][2]), "r"(a[AOFF + 2][3]), "r"(a[AOFF + 3][0]), "r"(a[AOFF + 3][1]), "r"(a[AOFF + 3][2]), "r"(a[AOFF + 3][3]), "r"(a[AOFF + 4][0]), "r"(a[AOFF + 4][1]), "r"(a[AOFF + 4][2]), "r"(a[AOFF + 4][3]), "r"(a[AOFF + 5][0]), "r"(a[AOFF + 5][1]), "r"(a[AOFF + 5][2]), "r"(a[AOFF + 5][3]), "l"(descB), "n"(BOFF >> 4));
}
};
template <> struct Rng<1, 6, 12> {
template <int BOFF, int AOFF, int NA>
static __device__ __forceinline__ void run(float (&d)[48], const uint32_t (&a)[NA][4], uint64_t descB) {
    asm volatile(
        "{\n"
        ".reg .pred p0, p1;\n"
        ".reg .b64 ta, ta0, tb, tb0;\n"
        "setp.ne.b32 p0, 0, 0;\n"
        "setp.eq.b32 p1, 0, 0;\n"
        "add.s64 tb0, %72, %73;\n"
        "add.s64 tb, tb0, 192;\n"
        "wgmma.mma_async.sync.aligned.m64n96k16.f32.bf16.bf16 {%0, %1, %2, %3, %4, %5, %6, %7, %8, %9, %10, %11, %12, %13, %14, %15, %16, %17, %18, %19, %20, %21, %22, %23, %24, %25, %26, %27, %28, %29, %30, %31, %32, %33, %34, %35, %36, %37, %38, %39, %40, %41, %42, %43, %44, %45, %46, %47}, {%48, %49, %50, %51}, tb, p1, 1, 1, 1;\n"
        "add.s64 tb, tb0, 224;\n"
        "wgmma.mma_async.sync.aligned.m64n96k16.f32.bf16.bf16 {%0, %1, %2, %3, %4, %5, %6, %7, %8, %9, %10, %11, %12, %13, %14, %15, %16, %17, %18, %19, %20, %21, %22, %23, %24, %25, %26, %27, %28, %29, %30, %31, %32, %33, %34, %35, %36, %37, %38, %39, %40, %41, %42, %43, %44, %45, %46, %47}, {%52, %53, %54, %55}, tb, p1, 1, 1, 1;\n"
        "add.s64 tb, tb0, 256;\n"
        "wgmma.mma_async.sync.aligned.m64n96k16.f32.bf16.bf16 {%0, %1, %2, %3, %4, %5, %6, %7, %8, %9, %10, %11, %12, %13, %14, %15, %16, %17, %18, %19, %20, %21, %22, %23, %24, %25, %26, %27, %28, %29, %30, %31, %32, %33, %34, %35, %36, %37, %38, %39, %40, %41, %42, %43, %44, %45, %46, %47}, {%56, %57, %58, %59}, tb, p1, 1, 1, 1;\n"
        "add.s64 tb, tb0, 288;\n"
        "wgmma.mma_async.sync.aligned.m64n96k16.f32.bf16.bf16 {%0, %1, %2, %3, %4, %5, %6, %7, %8, %9, %10, %11, %12, %13, %14, %15, %16, %17, %18, %19, %20, %21, %22, %23, %24, %25, %26, %27, %28, %29, %30, %31, %32, %33, %34, %35, %36, %37, %38, %39, %40, %41, %42, %43, %44, %45, %46, %47}, {%60, %61, %62, %63}, tb, p1, 1, 1, 1;\n"
        "add.s64 tb, tb0, 320;\n"
        "wgmma.mma_async.sync.aligned.m64n96k16.f32.bf16.bf16 {%0, %1, %2, %3, %4, %5, %6, %7, %8, %9, %10, %11, %12, %13, %14, %15, %16, %17, %18, %19, %20, %21, %22, %23, %24, %25, %26, %27, %28, %29, %30, %31, %32, %33, %34, %35, %36, %37, %38, %39, %40, %41, %42, %43, %44, %45, %46, %47}, {%64, %65, %66, %67}, tb, p1, 1, 1, 1;\n"
        "add.s64 tb, tb0, 352;\n"
        "wgmma.mma_async.sync.aligned.m64n96k16.f32.bf16.bf16 {%0, %1, %2, %3, %4, %5, %6, %7, %8, %9, %10, %11, %12, %13, %14, %15, %16, %17, %18, %19, %20, %21, %22, %23, %24, %25, %26, %27, %28, %29, %30, %31, %32, %33, %34, %35, %36, %37, %38, %39, %40, %41, %42, %43, %44, %45, %46, %47}, {%68, %69, %70, %71}, tb, p1, 1, 1, 1;\n"
        "}\n"
        : "+f"(d[0]), "+f"(d[1]), "+f"(d[2]), "+f"(d[3]), "+f"(d[4]), "+f"(d[5]), "+f"(d[6]), "+f"(d[7]), "+f"(d[8]), "+f"(d[9]), "+f"(d[10]), "+f"(d[11]), "+f"(d[12]), "+f"(d[13]), "+f"(d[14]), "+f"(d[15]), "+f"(d[16]), "+f"(d[17]), "+f"(d[18]), "+f"(d[19]), "+f"(d[20]), "+f"(d[21]), "+f"(d[22]), "+f"(d[23]), "+f"(d[24]), "+f"(d[25]), "+f"(d[26]), "+f"(d[27]), "+f"(d[28]), "+f"(d[29]), "+f"(d[30]), "+f"(d[31]), "+f"(d[32]), "+f"(d[33]), "+f"(d[34]), "+f"(d[35]), "+f"(d[36]), "+f"(d[37]), "+f"(d[38]), "+f"(d[39]), "+f"(d[40]), "+f"(d[41]), "+f"(d[42]), "+f"(d[43]), "+f"(d[44]), "+f"(d[45]), "+f"(d[46]), "+f"(d[47])
        : "r"(a[AOFF + 0][0]), "r"(a[AOFF + 0][1]), "r"(a[AOFF + 0][2]), "r"(a[AOFF + 0][3]), "r"(a[AOFF + 1][0]), "r"(a[AOFF + 1][1]), "r"(a[AOFF + 1][2]), "r"(a[AOFF + 1][3]), "r"(a[AOFF + 2][0]), "r"(a[AOFF + 2][1]), "r"(a[AOFF + 2][2]), "r"(a[AOFF + 2][3]), "r"(a[AOFF + 3][0]), "r"(a[AOFF + 3][1]), "r"(a[AOFF + 3][2]), "r"(a[AOFF + 3][3]), "r"(a[AOFF + 4][0]), "r"(a[AOFF + 4][1]), "r"(a[AOFF + 4][2]), "r"(a[AOFF + 4][3]), "r"(a[AOFF + 5][0]), "r"(a[AOFF + 5][1]), "r"(a[AOFF + 5][2]), "r"(a[AOFF + 5][3]), "l"(descB), "n"(BOFF >> 4));
}
};
template <> struct Rng<0, 7, 12> {
template <int BOFF, int AOFF, int NA>
static __device__ __forceinline__ void run(float (&d)[48], const uint32_t (&a)[NA][4], uint64_t descB) {
    asm volatile(
        "{\n"
        ".reg .pred p0, p1;\n"
        ".reg .b64 ta, ta0, tb, tb0;\n"
        "setp.ne.b32 p0, 0, 0;\n"
        "setp.eq.b32 p1, 0, 0;\n"
        "add.s64 tb0, %68, %69;\n"
        "add.s64 tb, tb0, 1632;\n"
        "wgmma.mma_async.sync.aligned.m64n96k16.f32.bf16.bf16 {%0, %1, %2, %3, %4, %5, %6, %7, %8, %9, %10, %11, %12, %13, %14, %15, %16, %17, %18, %19, %20, %21, %22, %23, %24, %25, %26, %27, %28, %29, %30, %31, %32, %33, %34, %35, %36, %37, %38, %39, %40, %41, %42, %43, %44, %45, %46, %47}, {%48, %49, %50, %51}, tb, p1, 1, 1, 1;\n"
        "add.s64 tb, tb0, 3072;\n"
        "wgmma.mma_async.sync.aligned.m64n96k16.f32.bf16.bf16 {%0, %1, %2, %3, %4, %5, %6, %7, %8, %9, %10, %11, %12, %13, %14, %15, %16, %17, %18, %19, %20, %21, %22, %23, %24, %25, %26, %27, %28, %29, %30, %31, %32, %33, %34, %35, %36, %37, %38, %39, %40, %41, %42, %43, %44, %45, %46, %47}, {%52, %53, %54, %55}, tb, p1, 1, 1, 1;\n"
        "add.s64 tb, tb0, 3104;\n"
        "wgmma.mma_async.sync.aligned.m64n96k16.f32.bf16.bf16 {%0, %1, %2, %3, %4, %5, %6, %7, %8, %9, %10, %11, %12, %13, %14, %15, %16, %17, %18, %19, %20, %21, %22, %23, %24, %25, %26, %27, %28, %29, %30, %31, %32, %33, %34, %35, %36, %37, %38, %39, %40, %41, %42, %43, %44, %45, %46, %47}, {%56, %57, %58, %59}, tb, p1, 1, 1, 1;\n"
        "add.s64 tb, tb0, 3136;\n"
        "wgmma.mma_async.sync.aligned.m64n96k16.f32.bf16.bf16 {%0, %1, %2, %3, %4, %5, %6, %7, %8, %9, %10, %11, %12, %13, %14, %15, %16, %17, %18, %19, %20, %21, %22, %23, %24, %25, %26, %27, %28, %29, %30, %31, %32, %33, %34, %35, %36, %37, %38, %39, %40, %41, %42, %43, %44, %45, %46, %47}, {%60, %61, %62, %63}, tb, p1, 1, 1, 1;\n"
        "add.s64 tb, tb0, 3168;\n"
        "wgmma.mma_async.sync.aligned.m64n96k16.f32.bf16.bf16 {%0, %1, %2, %3, %4, %5, %6, %7, %8, %9, %10, %11, %12, %13, %14, %15, %16, %17, %18, %19, %20, %21, %22, %23, %24, %25, %26, %27, %28, %29, %30, %31, %32, %33, %34, %35, %36, %37, %38, %39, %40, %41, %42, %43, %44, %45, %46, %47}, {%64, %65, %66, %67}, tb, p1, 1, 1, 1;\n"
        "}\n"
        : "+f"(d[0]), "+f"(d[1]), "+f"(d[2]), "+f"(d[3]), "+f"(d[4]), "+f"(d[5]), "+f"(d[6]), "+f"(d[7]), "+f"(d[8]), "+f"(d[9]), "+f"(d[10]), "+f"(d[11]), "+f"(d[12]), "+f"(d[13]), "+f"(d[14]), "+f"(d[15]), "+f"(d[16]), "+f"(d[17]), "+f"(d[18]), "+f"(d[19]), "+f"(d[20]), "+f"(d[21]), "+f"(d[22]), "+f"(d[23]), "+f"(d[24]), "+f"(d[25]), "+f"(d[26]), "+f"(d[27]), "+f"(d[28]), "+f"(d[29]), "+f"(d[30]), "+f"(d[31]), "+f"(d[32]), "+f"(d[33]), "+f"(d[34]), "+f"(d[35]), "+f"(d[36]), "+f"(d[37]), "+f"(d[38]), "+f"(d[39]), "+f"(d[40]), "+f"(d[41]), "+f"(d[42]), "+f"(d[43]), "+f"(d[44]), "+f"(d[45]), "+f"(d[46]), "+f"(d[47])
        : "r"(a[AOFF + 0][0]), "r"(a[AOFF + 0][1]), "r"(a[AOFF + 0][2]), "r"(a[AOFF + 0][3]), "r"(a[AOFF + 1][0]), "r"(a[AOFF + 1][1]), "r"(a[AOFF + 1][2]), "r"(a[AOFF + 1][3]), "r"(a[AOFF + 2][0]), "r"(a[AOFF + 2][1]), "r"(a[AOFF + 2][2]), "r"(a[AOFF + 2][3]), "r"(a[AOFF + 3][0]), "r"(a[AOFF + 3][1]), "r"(a[AOFF + 3][2]), "r"(a[AOFF + 3][3]), "r"(a[AOFF + 4][0]), "r"(a[AOFF + 4][1]), "r"(a[AOFF + 4][2]), "r"(a[AOFF + 4][3]), "l"(descB), "n"(BOFF >> 4));
}
};
template <> struct Rng<1, 7, 12> {
template <int BOFF, int AOFF, int NA>
static __device__ __forceinline__ void run(float (&d)[48], const uint32_t (&a)[NA][4], uint64_t descB) {
    asm volatile(
        "{\n"
        ".reg .pred p0, p1;\n"
        ".reg .b64 ta, ta0, tb, tb0;\n"
        "setp.ne.b32 p0, 0, 0;\n"
        "setp.eq.b32 p1, 0, 0;\n"
        "add.s64 tb0, %68, %69;\n"
        "add.s64 tb, tb0, 224;\n"
        "wgmma.mma_async.sync.aligned.m64n96k16.f32.bf16.bf16 {%0, %1, %2, %3, %4, %5, %6, %7, %8, %9, %10, %11, %12, %13, %14, %15, %16, %17, %18, %19, %20, %21, %22, %23, %24, %25, %26, %27, %28, %29, %30, %31, %32, %33, %34, %35, %36, %37, %38, %39, %40, %41, %42, %43, %44, %45, %46, %47}, {%48, %49, %50, %51}, tb, p1, 1, 1, 1;\n"
        "add.s64 tb, tb0, 256;\n"
        "wgmma.mma_async.sync.aligned.m64n96k16.f32.bf16.bf16 {%0, %1, %2, %3, %4, %5, %6, %7, %8, %9, %10, %11, %12, %13, %14, %15, %16, %17, %18, %19, %20, %21, %22, %23, %24, %25, %26, %27, %28, %29, %30, %31, %32, %33, %34, %35, %36, %37, %38, %39, %40, %41, %42, %43, %44, %45, %46, %47}, {%52, %53, %54, %55}, tb, p1, 1, 1, 1;\n"
        "add.s64 tb, tb0, 288;\n"
        "wgmma.mma_async.sync.aligned.m64n96k16.f32.bf16.bf16 {%0, %1, %2, %3, %4, %5, %6, %7, %8, %9, %10, %11, %12, %13, %14, %15, %16, %17, %18, %19, %20, %21, %22, %23, %24, %25, %26, %27, %28, %29, %30, %31, %32, %33, %34, %35, %36, %37, %38, %39, %40, %41, %42, %43, %44, %45, %46, %47}, {%56, %57, %58, %59}, tb, p1, 1, 1, 1;\n"
        "add.s64 tb, tb0, 320;\n"
        "wgmma.mma_async.sync.aligned.m64n96k16.f32.bf16.bf16 {%0, %1, %2, %3, %4, %5, %6, %7, %8, %9, %10, %11, %12, %13, %14, %15, %16, %17, %18, %19, %20, %21, %22, %23, %24, %25, %26, %27, %28, %29, %30, %31, %32, %33, %34, %35, %36, %37, %38, %39, %40, %41, %42, %43, %44, %45, %46, %47}, {%60, %61, %62, %63}, tb, p1, 1, 1, 1;\n"
        "add.s64 tb, tb0, 352;\n"
        "wgmma.mma_async.sync.aligned.m64n96k16.f32.bf16.bf16 {%0, %1, %2, %3, %4, %5, %6, %7, %8, %9, %10, %11, %12, %13, %14, %15, %16, %17, %18, %19, %20, %21, %22, %23, %24, %25, %26, %27, %28, %29, %30, %31, %32, %33, %34, %35, %36, %37, %38, %39, %40, %41, %42, %43, %44, %45, %46, %47}, {%64, %65, %66, %67}, tb, p1, 1, 1, 1;\n"
        "}\n"
        : "+f"(d[0]), "+f"(d[1]), "+f"(d[2]), "+f"(d[3]), "+f"(d[4]), "+f"(d[5]), "+f"(d[6]), "+f"(d[7]), "+f"(d[8]), "+f"(d[9]), "+f"(d[10]), "+f"(d[11]), "+f"(d[12]), "+f"(d[13]), "+f"(d[14]), "+f"(d[15]), "+f"(d[16]), "+f"(d[17]), "+f"(d[18]), "+f"(d[19]), "+f"(d[20]), "+f"(d[21]), "+f"(d[22]), "+f"(d[23]), "+f"(d[24]), "+f"(d[25]), "+f"(d[26]), "+f"(d[27]), "+f"(d[28]), "+f"(d[29]), "+f"(d[30]), "+f"(d[31]), "+f"(d[32]), "+f"(d[33]), "+f"(d[34]), "+f"(d[35]), "+f"(d[36]), "+f"(d[37]), "+f"(d[38]), "+f"(d[39]), "+f"(d[40]), "+f"(d[41]), "+f"(d[42]), "+f"(d[43]), "+f"(d[44]), "+f"(d[45]), "+f"(d[46]), "+f"(d[47])
        : "r"(a[AOFF + 0][0]), "r"(a[AOFF + 0][1]), "r"(a[AOFF + 0][2]), "r"(a[AOFF + 0][3]), "r"(a[AOFF + 1][0]), "r"(a[AOFF + 1][1]), "r"(a[AOFF + 1][2]), "r"(a[AOFF + 1][3]), "r"(a[AOFF + 2][0]), "r"(a[AOFF + 2][1]), "r"(a[AOFF + 2][2]), "r"(a[AOFF + 2][3]), "r"(a[AOFF + 3][0]), "r"(a[AOFF + 3][1]), "r"(a[AOFF + 3][2]), "r"(a[AOFF + 3][3]), "r"(a[AOFF + 4][0]), "r"(a[AOFF + 4][1]), "r"(a[AOFF + 4][2]), "r"(a[AOFF + 4][3]), "l"(descB), "n"(BOFF >> 4));
}
};
template <> struct Rng<0, 8, 12> {
template <int BOFF, int AOFF, int NA>
static __device__ __forceinline__ void run(float (&d)[48], const uint32_t (&a)[NA][4], uint64_t descB) {
    asm volatile(
        "{\n"
        ".reg .pred p0, p1;\n"
        ".reg .b64 ta, ta0, tb, tb0;\n"
        "setp.ne.b32 p0, 0, 0;\n"
        "setp.eq.b32 p1, 0, 0;\n"
        "add.s64 tb0, %64, %65;\n"
        "add.s64 tb, tb0, 3072;\n"
        "wgmma.mma_async.sync.aligned.m64n96k16.f32.bf16.bf16 {%0, %1, %2, %3, %4, %5, %6, %7, %8, %9, %10, %11, %12, %13, %14, %15, %16, %17, %18, %19, %20, %21, %22, %23, %24, %25, %26, %27, %28, %29, %30, %31, %32, %33, %34, %35, %36, %37, %38, %39, %40, %41, %42, %43, %44, %45, %46, %47}, {%48, %49, %50, %51}, tb, p1, 1, 1, 1;\n"
        "add.s64 tb, tb0, 3104;\n"
        "wgmma.mma_async.sync.aligned.m64n96k16.f32.bf16.bf16 {%0, %1, %2, %3, %4, %5, %6, %7, %8, %9, %10, %11, %12, %13, %14, %15, %16, %17, %18, %19, %20, %21, %22, %23, %24, %25, %26, %27, %28, %29, %30, %31, %32, %33, %34, %35, %36, %37, %38, %39, %40, %41, %42, %43, %44, %45, %46, %47}, {%52, %53, %54, %55}, tb, p1, 1, 1, 1;\n"
        "add.s64 tb, tb0, 3136;\n"
        "wgmma.mma_async.sync.aligned.m64n96k16.f32.bf16.bf16 {%0, %1, %2, %3, %4, %5, %6, %7, %8, %9, %10, %11, %12, %13, %14, %15, %16, %17, %18, %19, %20, %21, %22, %23, %24, %25, %26, %27, %28, %29, %30, %31, %32, %33, %34, %35, %36, %37, %38, %39, %40, %41, %42, %43, %44, %45, %46, %47}, {%56, %57, %58, %59}, tb, p1, 1, 1, 1;\n"
        "add.s64 tb, tb0, 3168;\n"
        "wgmma.mma_async.sync.aligned.m64n96k16.f32.bf16.bf16 {%0, %1, %2, %3, %4, %5, %6, %7, %8, %9, %10, %11, %12, %13, %14, %15, %16, %17, %18, %19, %20, %21, %22, %23, %24, %25, %26, %27, %28, %29, %30, %31, %32, %33, %34, %35, %36, %37, %38, %39, %40, %41, %42, %43, %44, %45, %46, %47}, {%60, %61, %62, %63}, tb, p1, 1, 1, 1;\n"
        "}\n"
        : "+f"(d[0]), "+f"(d[1]), "+f"(d[2]), "+f"(d[3]), "+f"(d[4]), "+f"(d[5]), "+f"(d[6]), "+f"(d[7]), "+f"(d[8]), "+f"(d[9]), "+f"(d[10]), "+f"(d[11]), "+f"(d[12]), "+f"(d[13]), "+f"(d[14]), "+f"(d[15]), "+f"(d[16]), "+f"(d[17]), "+f"(d[18]), "+f"(d[19]), "+f"(d[20]), "+f"(d[21]), "+f"(d[22]), "+f"(d[23]), "+f"(d[24]), "+f"(d[25]), "+f"(d[26]), "+f"(d[27]), "+f"(d[28]), "+f"(d[29]), "+f"(d[30]), "+f"(d[31]), "+f"(d[32]), "+f"(d[33]), "+f"(d[34]), "+f"(d[35]), "+f"(d[36]), "+f"(d[37]), "+f"(d[38]), "+f"(d[39]), "+f"(d[40]), "+f"(d[41]), "+f"(d[42]), "+f"(d[43]), "+f"(d[44]), "+f"(d[45]), "+f"(d[46]), "+f"(d[47])
        : "r"(a[AOFF + 0][0]), "r"(a[AOFF + 0][1]), "r"(a[AOFF + 0][2]), "r"(a[AOFF + 0][3]), "r"(a[AOFF + 1][0]), "r"(a[AOFF + 1][1]), "r"(a[AOFF + 1][2]), "r"(a[AOFF + 1][3]), "r"(a[AOFF + 2][0]), "r"(a[AOFF + 2][1]), "r"(a[AOFF + 2][2]), "r"(a[AOFF + 2][3]), "r"(a[AOFF + 3][0]), "r"(a[AOFF + 3][1]), "r"(a[AOFF + 3][2]), "r"(a[AOFF + 3][3]), "l"(descB), "n"(BOFF >> 4));
}
};
template <> struct Rng<1, 8, 12> {
template <int BOFF, int AOFF, int NA>
static __device__ __forceinline__ void run(float (&d)[48], const uint32_t (&a)[NA][4], uint64_t descB) {
    asm volatile(
        "{\n"
        ".reg .pred p0, p1;\n"
        ".reg .b64 ta, ta0, tb, tb0;\n"
        "setp.ne.b32 p0, 0, 0;\n"
        "setp.eq.b32 p1, 0, 0;\n"
        "add.s64 tb0, %64, %65;\n"
        "add.s64 tb, tb0, 256;\n"
        "wgmma.mma_async.sync.aligned.m64n96k16.f32.bf16.bf16 {%0, %1, %2, %3, %4, %5, %6, %7, %8, %9, %10, %11, %12, %13, %14, %15, %16, %17, %18, %19, %20, %21, %22, %23, %24, %25, %26, %27, %28, %29, %30, %31, %32, %33, %34, %35, %36, %37, %38, %39, %40, %41, %42, %43, %44, %45, %46, %47}, {%48, %49, %50, %51}, tb, p1, 1, 1, 1;\n"
        "add.s64 tb, tb0, 288;\n"
        "wgmma.mma_async.sync.aligned.m64n96k16.f32.bf16.bf16 {%0, %1, %2, %3, %4, %5, %6, %7, %8, %9, %10, %11, %12, %13, %14, %15, %16, %17, %18, %19, %20, %21, %22, %23, %24, %25, %26, %27, %28, %29, %30, %31, %32, %33, %34, %35, %36, %37, %38, %39, %40, %41, %42, %43, %44, %45, %46, %47}, {%52, %53, %54, %55}, tb, p1, 1, 1, 1;\n"
        "add.s64 tb, tb0, 320;\n"
        "wgmma.mma_async.sync.aligned.m64n96k16.f32.bf16.bf16 {%0, %1, %2, %3, %4, %5, %6, %7, %8, %9, %10, %11, %12, %13, %14, %15, %16, %17, %18, %19, %20, %21, %22, %23, %24, %25, %26, %27, %28, %29, %30, %31, %32, %33, %34, %35, %36, %37, %38, %39, %40, %41, %42, %43, %44, %45, %46, %47}, {%56, %57, %58, %59}, tb, p1, 1, 1, 1;\n"
        "add.s64 tb, tb0, 352;\n"
        "wgmma.mma_async.sync.aligned.m64n96k16.f32.bf16.bf16 {%0, %1, %2, %3, %4, %5, %6, %7, %8, %9, %10, %11, %12, %13, %14, %15, %16, %17, %18, %19, %20, %21, %22, %23, %24, %25, %26, %27, %28, %29, %30, %31, %32, %33, %34, %35, %36, %37, %38, %39, %40, %41, %42, %43, %44, %45, %46, %47}, {%60, %61, %62, %63}, tb, p1, 1, 1, 1;\n"
        "}\n"
        : "+f"(d[0]), "+f"(d[1]), "+f"(d[2]), "+f"(d[3]), "+f"(d[4]), "+f"(d[5]), "+f"(d[6]), "+f"(d[7]), "+f"(d[8]), "+f"(d[9]), "+f"(d[10]), "+f"(d[11]), "+f"(d[12]), "+f"(d[13]), "+f"(d[14]), "+f"(d[15]), "+f"(d[16]), "+f"(d[17]), "+f"(d[18]), "+f"(d[19]), "+f"(d[20]), "+f"(d[21]), "+f"(d[22]), "+f"(d[23]), "+f"(d[24]), "+f"(d[25]), "+f"(d[26]), "+f"(d[27]), "+f"(d[28]), "+f"(d[29]), "+f"(d[30]), "+f"(d[31]), "+f"(d[32]), "+f"(d[33]), "+f"(d[34]), "+f"(d[35]), "+f"(d[36]), "+f"(d[37]), "+f"(d[38]), "+f"(d[39]), "+f"(d[40]), "+f"(d[41]), "+f"(d[42]), "+f"(d[43]), "+f"(d[44]), "+f"(d[45]), "+f"(d[46]), "+f"(d[47])
        : "r"(a[AOFF + 0][0]), "r"(a[AOFF + 0][1]), "r"(a[AOFF + 0][2]), "r"(a[AOFF + 0][3]), "r"(a[AOFF + 1][0]), "r"(a[AOFF + 1][1]), "r"(a[AOFF + 1][2]), "r"(a[AOFF + 1][3]), "r"(a[AOFF + 2][0]), "r"(a[AOFF + 2][1]), "r"(a[AOFF + 2][2]), "r"(a[AOFF + 2][3]), "r"(a[AOFF + 3][0]), "r"(a[AOFF + 3][1]), "r"(a[AOFF + 3][2]), "r"(a[AOFF + 3][3]), "l"(descB), "n"(BOFF >> 4));
}
};
template <> struct Rng<0, 9, 12> {
template <int BOFF, int AOFF, int NA>
static __device__ __forceinline__ void run(float (&d)[48], const uint32_t (&a)[NA][4], uint64_t descB) {
    asm volatile(
        "{\n"
        ".reg .pred p0, p1;\n"
        ".reg .b64 ta, ta0, tb, tb0;\n"
        "setp.ne.b32 p0, 0, 0;\n"
        "setp.eq.b32 p1, 0, 0;\n"
        "add.s64 tb0, %60, %61;\n"
        "add.s64 tb, tb0, 3104;\n"
        "wgmma.mma_async.sync.aligned.m64n96k16.f32.bf16.bf16 {%0, %1, %2, %3, %4, %5, %6, %7, %8, %9, %10, %11, %12, %13, %14, %15, %16, %17, %18, %19, %20, %21, %22, %23, %24, %25, %26, %27, %28, %29, %30, %31, %32, %33, %34, %35, %36, %37, %38, %39, %40, %41, %42, %43, %44, %45, %46, %47}, {%48, %49, %50, %51}, tb, p1, 1, 1, 1;\n"
        "add.s64 tb, tb0, 3136;\n"
        "wgmma.mma_async.sync.aligned.m64n96k16.f32.bf16.bf16 {%0, %1, %2, %3, %4, %5, %6, %7, %8, %9, %10, %11, %12, %13, %14, %15, %16, %17, %18, %19, %20, %21, %22, %23, %24, %25, %26, %27, %28, %29, %30, %31, %32, %33, %34, %35, %36, %37, %38, %39, %40, %41, %42, %43, %44, %45, %46, %47}, {%52, %53, %54, %55}, tb, p1, 1, 1, 1;\n"
        "add.s64 tb, tb0, 3168;\n"
        "wgmma.mma_async.sync.aligned.m64n96k16.f32.bf16.bf16 {%0, %1, %2, %3, %4, %5, %6, %7, %8, %9, %10, %11, %12, %13, %14, %15, %16, %17, %18, %19, %20, %21, %22, %23, %24, %25, %26, %27, %28, %29, %30, %31, %32, %33, %34, %35, %36, %37, %38, %39, %40, %41, %42, %43, %44, %45, %46, %47}, {%56, %57, %58, %59}, tb, p1, 1, 1, 1;\n"
        "}\n"
        : "+f"(d[0]), "+f"(d[1]), "+f"(d[2]), "+f"(d[3]), "+f"(d[4]), "+f"(d[5]), "+f"(d[6]), "+f"(d[7]), "+f"(d[8]), "+f"(d[9]), "+f"(d[10]), "+f"(d[11]), "+f"(d[12]), "+f"(d[13]), "+f"(d[14]), "+f"(d[15]), "+f"(d[16]), "+f"(d[17]), "+f"(d[18]), "+f"(d[19]), "+f"(d[20]), "+f"(d[21]), "+f"(d[22]), "+f"(d[23]), "+f"(d[24]), "+f"(d[25]), "+f"(d[26]), "+f"(d[27]), "+f"(d[28]), "+f"(d[29]), "+f"(d[30]), "+f"(d[31]), "+f"(d[32]), "+f"(d[33]), "+f"(d[34]), "+f"(d[35]), "+f"(d[36]), "+f"(d[37]), "+f"(d[38]), "+f"(d[39]), "+f"(d[40]), "+f"(d[41]), "+f"(d[42]), "+f"(d[43]), "+f"(d[44]), "+f"(d[45]), "+f"(d[46]), "+f"(d[47])
        : "r"(a[AOFF + 0][0]), "r"(a[AOFF + 0][1]), "r"(a[AOFF + 0][2]), "r"(a[AOFF + 0][3]), "r"(a[AOFF + 1][0]), "r"(a[AOFF + 1][1]), "r"(a[AOFF + 1][2]), "r"(a[AOFF + 1][3]), "r"(a[AOFF + 2][0]), "r"(a[AOFF + 2][1]), "r"(a[AOFF + 2][2]), "r"(a[AOFF + 2][3]), "l"(descB), "n"(BOFF >> 4));
}
};
template <> struct Rng<1, 9, 12> {
template <int BOFF, int AOFF, int NA>
static __device__ __forceinline__ void run(float (&d)[48], const uint32_t (&a)[NA][4], uint64_t descB) {
    asm volatile(
        "{\n"
        ".reg .pred p0, p1;\n"
        ".reg .b64 ta, ta0, tb, tb0;\n"
        "setp.ne.b32 p0, 0, 0;\n"
        "setp.eq.b32 p1, 0, 0;\n"
        "add.s64 tb0, %60, %61;\n"
        "add.s64 tb, tb0, 288;\n"
        "wgmma.mma_async.sync.aligned.m64n96k16.f32.bf16.bf16 {%0, %1, %2, %3, %4, %5, %6, %7, %8, %9, %10, %11, %12, %13, %14, %15, %16, %17, %18, %19, %20, %21, %22, %23, %24, %25, %26, %27, %28, %29, %30, %31, %32, %33, %34, %35, %36, %37, %38, %39, %40, %41, %42, %43, %44, %45, %46, %47}, {%48, %49, %50, %51}, tb, p1, 1, 1, 1;\n"
        "add.s64 tb, tb0, 320;\n"
        "wgmma.mma_async.sync.aligned.m64n96k16.f32.bf16.bf16 {%0, %1, %2, %3, %4, %5, %6, %7, %8, %9, %10, %11, %12, %13, %14, %15, %16, %17, %18, %19, %20, %21, %22, %23, %24, %25, %26, %27, %28, %29, %30, %31, %32, %33, %34, %35, %36, %37, %38, %39, %40, %41, %42, %43, %44, %45, %46, %47}, {%52, %53, %54, %55}, tb, p1, 1, 1, 1;\n"
        "add.s64 tb, tb0, 352;\n"
        "wgmma.mma_async.sync.aligned.m64n96k16.f32.bf16.bf16 {%0, %1, %2, %3, %4, %5, %6, %7, %8, %9, %10, %11, %12, %13, %14, %15, %16, %17, %18, %19, %20, %21, %22, %23, %24, %25, %26, %27, %28, %29, %30, %31, %32, %33, %34, %35, %36, %37, %38, %39, %40, %41, %42, %43, %44, %45, %46, %47}, {%56, %57, %58, %59}, tb, p1, 1, 1, 1;\n"
        "}\n"
        : "+f"(d[0]), "+f"(d[1]), "+f"(d[2]), "+f"(d[3]), "+f"(d[4]), "+f"(d[5]), "+f"(d[6]), "+f"(d[7]), "+f"(d[8]), "+f"(d[9]), "+f"(d[10]), "+f"(d[11]), "+f"(d[12]), "+f"(d[13]), "+f"(d[14]), "+f"(d[15]), "+f"(d[16]), "+f"(d[17]), "+f"(d[18]), "+f"(d[19]), "+f"(d[20]), "+f"(d[21]), "+f"(d[22]), "+f"(d[23]), "+f"(d[24]), "+f"(d[25]), "+f"(d[26]), "+f"(d[27]), "+f"(d[28]), "+f"(d[29]), "+f"(d[30]), "+f"(d[31]), "+f"(d[32]), "+f"(d[33]), "+f"(d[34]), "+f"(d[35]), "+f"(d[36]), "+f"(d[37]), "+f"(d[38]), "+f"(d[39]), "+f"(d[40]), "+f"(d[41]), "+f"(d[42]), "+f"(d[43]), "+f"(d[44]), "+f"(d[45]), "+f"(d[46]), "+f"(d[47])
        : "r"(a[AOFF + 0][0]), "r"(a[AOFF + 0][1]), "r"(a[AOFF + 0][2]), "r"(a[AOFF + 0][3]), "r"(a[AOFF + 1][0]), "r"(a[AOFF + 1][1]), "r"(a[AOFF + 1][2]), "r"(a[AOFF + 1][3]), "r"(a[AOFF + 2][0]), "r"(a[AOFF + 2][1]), "r"(a[AOFF + 2][2]), "r"(a[AOFF + 2][3]), "l"(descB), "n"(BOFF >> 4));
}
};
template <> struct Rng<0, 10, 12> {
template <int BOFF, int AOFF, int NA>
static __device__ __forceinline__ void run(float (&d)[48], const uint32_t (&a)[NA][4], uint64_t descB) {
    asm volatile(
        "{\n"
        ".reg .pred p0, p1;\n"
        ".reg .b64 ta, ta0, tb, tb0;\n"
        "setp.ne.b32 p0, 0, 0;\n"
        "setp.eq.b32 p1, 0, 0;\n"
        "add.s64 tb0, %56, %57;\n"
        "add.s64 tb, tb0, 3136;\n"
        "wgmma.mma_async.sync.aligned.m64n96k16.f32.bf16.bf16 {%0, %1, %2, %3, %4, %5, %6, %7, %8, %9, %10, %11, %12, %13, %14, %15, %16, %17, %18, %19, %20, %21, %22, %23, %24, %25, %26, %27, %28, %29, %30, %31, %32, %33, %34, %35, %36, %37, %38, %39, %40, %41, %42, %43, %44, %45, %46, %47}, {%48, %49, %50, %51}, tb, p1, 1, 1, 1;\n"
        "add.s64 tb, tb0, 3168;\n"
        "wgmma.mma_async.sync.aligned.m64n96k16.f32.bf16.bf16 {%0, %1, %2, %3, %4, %5, %6, %7, %8, %9, %10, %11, %12, %13, %14, %15, %16, %17, %18, %19, %20, %21, %22, %23, %24, %25, %26, %27, %28, %29, %30, %31, %32, %33, %34, %35, %36, %37, %38, %39, %40, %41, %42, %43, %44, %45, %46, %47}, {%52, %53, %54, %55}, tb, p1, 1, 1, 1;\n"
        "}\n"
        : "+f"(d[0]), "+f"(d[1]), "+f"(d[2]), "+f"(d[3]), "+f"(d[4]), "+f"(d[5]), "+f"(d[6]), "+f"(d[7]), "+f"(d[8]), "+f"(d[9]), "+f"(d[10]), "+f"(d[11]), "+f"(d[12]), "+f"(d[13]), "+f"(d[14]), "+f"(d[15]), "+f"(d[16]), "+f"(d[17]), "+f"(d[18]), "+f"(d[19]), "+f"(d[20]), "+f"(d[21]), "+f"(d[22]), "+f"(d[23]), "+f"(d[24]), "+f"(d[25]), "+f"(d[26]), "+f"(d[27]), "+f"(d[28]), "+f"(d[29]), "+f"(d[30]), "+f"(d[31]), "+f"(d[32]), "+f"(d[33]), "+f"(d[34]), "+f"(d[35]), "+f"(d[36]), "+f"(d[37]), "+f"(d[38]), "+f"(d[39]), "+f"(d[40]), "+f"(d[41]), "+f"(d[42]), "+f"(d[43]), "+f"(d[44]), "+f"(d[45]), "+f"(d[46]), "+f"(d[47])
        : "r"(a[AOFF + 0][0]), "r"(a[AOFF + 0][1]), "r"(a[AOFF + 0][2]), "r"(a[AOFF + 0][3]), "r"(a[AOFF + 1][0]), "r"(a[AOFF + 1][1]), "r"(a[AOFF + 1][2]), "r"(a[AOFF + 1][3]), "l"(descB), "n"(BOFF >> 4));
}
};
template <> struct Rng<1, 10, 12> {
template <int BOFF, int AOFF, int NA>
static __device__ __forceinline__ void run(float (&d)[48], const uint32_t (&a)[NA][4], uint64_t descB) {
    asm volatile(
        "{\n"
        ".reg .pred p0, p1;\n"
        ".reg .b64 ta, ta0, tb, tb0;\n"
        "setp.ne.b32 p0, 0, 0;\n"
        "setp.eq.b32 p1, 0, 0;\n"
        "add.s64 tb0, %56, %57;\n"
        "add.s64 tb, tb0, 320;\n"
        "wgmma.mma_async.sync.aligned.m64n96k16.f32.bf16.bf16 {%0, %1, %2, %3, %4, %5, %6, %7, %8, %9, %10, %11, %12, %13, %14, %15, %16, %17, %18, %19, %20, %21, %22, %23, %24, %25, %26, %27, %28, %29, %30, %31, %32, %33, %34, %35, %36, %37, %38, %39, %40, %41, %42, %43, %44, %45, %46, %47}, {%48, %49, %50, %51}, tb, p1, 1, 1, 1;\n"
        "add.s64 tb, tb0, 352;\n"
        "wgmma.mma_async.sync.aligned.m64n96k16.f32.bf16.bf16 {%0, %1, %2, %3, %4, %5, %6, %7, %8, %9, %10, %11, %12, %13, %14, %15, %16, %17, %18, %19, %20, %21, %22, %23, %24, %25, %26, %27, %28, %29, %30, %31, %32, %33, %34, %35, %36, %37, %38, %39, %40, %41, %42, %43, %44, %45, %46, %47}, {%52, %53, %54, %55}, tb, p1, 1, 1, 1;\n"
        "}\n"
        : "+f"(d[0]), "+f"(d[1]), "+f"(d[2]), "+f"(d[3]), "+f"(d[4]), "+f"(d[5]), "+f"(d[6]), "+f"(d[7]), "+f"(d[8]), "+f"(d[9]), "+f"(d[10]), "+f"(d[11]), "+f"(d[12]), "+f"(d[13]), "+f"(d[14]), "+f"(d[15]), "+f"(d[16]), "+f"(d[17]), "+f"(d[18]), "+f"(d[19]), "+f"(d[20]), "+f"(d[21]), "+f"(d[22]), "+f"(d[23]), "+f"(d[24]), "+f"(d[25]), "+f"(d[26]), "+f"(d[27]), "+f"(d[28]), "+f"(d[29]), "+f"(d[30]), "+f"(d[31]), "+f"(d[32]), "+f"(d[33]), "+f"(d[34]), "+f"(d[35]), "+f"(d[36]), "+f"(d[37]), "+f"(d[38]), "+f"(d[39]), "+f"(d[40]), "+f"(d[41]), "+f"(d[42]), "+f"(d[43]), "+f"(d[44]), "+f"(d[45]), "+f"(d[46]), "+f"(d[47])
        : "r"(a[AOFF + 0][0]), "r"(a[AOFF + 0][1]), "r"(a[AOFF + 0][2]), "r"(a[AOFF + 0][3]), "r"(a[AOFF + 1][0]), "r"(a[AOFF + 1][1]), "r"(a[AOFF + 1][2]), "r"(a[AOFF + 1][3]), "l"(descB), "n"(BOFF >> 4));
}
};
template <int V, int BOFF, int S0, int S1>
__device__ __forceinline__ void mma_rng(float (&d)[48], const uint32_t (&a)[12][4], uint64_t descB) {
    if constexpr (S0 < S1) Rng<V, S0, S1>::template run<BOFF, S0, 12>(d, a, descB);
}

template <int AOFF, int BOFF>
__device__ __forceinline__ void mma_qk0(float (&d)[28], uint64_t descA, uint64_t descB) {
    asm volatile(
        "{\n"
        ".reg .pred p0, p1;\n"
        ".reg .b64 ta, ta0, tb, tb0;\n"
        "setp.ne.b32 p0, 0, 0;\n"
        "setp.eq.b32 p1, 0, 0;\n"
        "add.s64 tb0, %30, %31;\n"
        "add.s64 ta0, %28, %29;\n"
        "add.s64 tb, tb0, 4;\n"
        "add.s64 ta, ta0, 0;\n"
        "wgmma.mma_async.sync.aligned.m64n56k16.f32.bf16.bf16 {%0, %1, %2, %3, %4, %5, %6, %7, %8, %9, %10, %11, %12, %13, %14, %15, %16, %17, %18, %19, %20, %21, %22, %23, %24, %25, %26, %27}, ta, tb, p0, 1, 1, 0, 0;\n"
        "add.s64 tb, tb0, 1572;\n"
        "add.s64 ta, ta0, 1568;\n"
        "wgmma.mma_async.sync.aligned.m64n56k16.f32.bf16.bf16 {%0, %1, %2, %3, %4, %5, %6, %7, %8, %9, %10, %11, %12, %13, %14, %15, %16, %17, %18, %19, %20, %21, %22, %23, %24, %25, %26, %27}, ta, tb, p1, 1, 1, 0, 0;\n"
        "add.s64 tb, tb0, 3140;\n"
        "add.s64 ta, ta0, 3136;\n"
        "wgmma.mma_async.sync.aligned.m64n56k16.f32.bf16.bf16 {%0, %1, %2, %3, %4, %5, %6, %7, %8, %9, %10, %11, %12, %13, %14, %15, %16, %17, %18, %19, %20, %21, %22, %23, %24, %25, %26, %27}, ta, tb, p1, 1, 1, 0, 0;\n"
        "}\n"
        : "=f"(d[0]), "=f"(d[1]), "=f"(d[2]), "=f"(d[3]), "=f"(d[4]), "=f"(d[5]), "=f"(d[6]), "=f"(d[7]), "=f"(d[8]), "=f"(d[9]), "=f"(d[10]), "=f"(d[11]), "=f"(d[12]), "=f"(d[13]), "=f"(d[14]), "=f"(d[15]), "=f"(d[16]), "=f"(d[17]), "=f"(d[18]), "=f"(d[19]), "=f"(d[20]), "=f"(d[21]), "=f"(d[22]), "=f"(d[23]), "=f"(d[24]), "=f"(d[25]), "=f"(d[26]), "=f"(d[27])
        : "l"(descA), "n"(AOFF >> 4), "l"(descB), "n"(BOFF >> 4));
}

template <int AOFF, int BOFF>
__device__ __forceinline__ void mma_qk1(float (&d)[28], uint64_t descA, uint64_t descB) {
    asm volatile(
        "{\n"
        ".reg .pred p0, p1;\n"
        ".reg .b64 ta, ta0, tb, tb0;\n"
        "setp.ne.b32 p0, 0, 0;\n"
        "setp.eq.b32 p1, 0, 0;\n"
        "add.s64 tb0, %30, %31;\n"
        "add.s64 ta0, %28, %29;\n"
        "add.s64 tb, tb0, 6;\n"
        "add.s64 ta, ta0, 2;\n"
        "wgmma.mma_async.sync.aligned.m64n56k16.f32.bf16.bf16 {%0, %1, %2, %3, %4, %5, %6, %7, %8, %9, %10, %11, %12, %13, %14, %15, %16, %17, %18, %19, %20, %21, %22, %23, %24, %25, %26, %27}, ta, tb, p0, 1, 1, 0, 0;\n"
        "add.s64 tb, tb0, 1574;\n"
        "add.s64 ta, ta0, 1570;\n"
        "wgmma.mma_async.sync.aligned.m64n56k16.f32.bf16.bf16 {%0, %1, %2, %3, %4, %5, %6, %7, %8, %9, %10, %11, %12, %13, %14, %15, %16, %17, %18, %19, %20, %21, %22, %23, %24, %25, %26, %27}, ta, tb, p1, 1, 1, 0, 0;\n"
        "add.s64 tb, tb0, 3142;\n"
        "add.s64 ta, ta0, 3138;\n"
        "wgmma.mma_async.sync.aligned.m64n56k16.f32.bf16.bf16 {%0, %1, %2, %3, %4, %5, %6, %7, %8, %9, %10, %11, %12, %13, %14, %15, %16, %17, %18, %19, %20, %21, %22, %23, %24, %25, %26, %27}, ta, tb, p1, 1, 1, 0, 0;\n"
        "}\n"
        : "=f"(d[0]), "=f"(d[1]), "=f"(d[2]), "=f"(d[3]), "=f"(d[4]), "=f"(d[5]), "=f"(d[6]), "=f"(d[7]), "=f"(d[8]), "=f"(d[9]), "=f"(d[10]), "=f"(d[11]), "=f"(d[12]), "=f"(d[13]), "=f"(d[14]), "=f"(d[15]), "=f"(d[16]), "=f"(d[17]), "=f"(d[18]), "=f"(d[19]), "=f"(d[20]), "=f"(d[21]), "=f"(d[22]), "=f"(d[23]), "=f"(d[24]), "=f"(d[25]), "=f"(d[26]), "=f"(d[27])
        : "l"(descA), "n"(AOFF >> 4), "l"(descB), "n"(BOFF >> 4));
}

template <int BOFF, int AOFF, int NA>
__device__ __forceinline__ void mma_pv(float (&d)[28], const uint32_t (&a)[NA][4], uint64_t descB) {
    asm volatile(
        "{\n"
        ".reg .pred p0, p1;\n"
        ".reg .b64 ta, ta0, tb, tb0;\n"
        "setp.ne.b32 p0, 0, 0;\n"
        "setp.eq.b32 p1, 0, 0;\n"
        "add.s64 tb0, %44, %45;\n"
        "add.s64 tb, tb0, 0;\n"
        "wgmma.mma_async.sync.aligned.m64n56k16.f32.bf16.bf16 {%0, %1, %2, %3, %4, %5, %6, %7, %8, %9, %10, %11, %12, %13, %14, %15, %16, %17, %18, %19, %20, %21, %22, %23, %24, %25, %26, %27}, {%28, %29, %30, %31}, tb, p0, 1, 1, 1;\n"
        "add.s64 tb, tb0, 16;\n"
        "wgmma.mma_async.sync.aligned.m64n56k16.f32.bf16.bf16 {%0, %1, %2, %3, %4, %5, %6, %7, %8, %9, %10, %11, %12, %13, %14, %15, %16, %17, %18, %19, %20, %21, %22, %23, %24, %25, %26, %27}, {%32, %33, %34, %35}, tb, p1, 1, 1, 1;\n"
        "add.s64 tb, tb0, 32;\n"
        "wgmma.mma_async.sync.aligned.m64n56k16.f32.bf16.bf16 {%0, %1, %2, %3, %4, %5, %6, %7, %8, %9, %10, %11, %12, %13, %14, %15, %16, %17, %18, %19, %20, %21, %22, %23, %24, %25, %26, %27}, {%36, %37, %38, %39}, tb, p1, 1, 1, 1;\n"
        "add.s64 tb, tb0, 48;\n"
        "wgmma.mma_async.sync.aligned.m64n56k16.f32.bf16.bf16 {%0, %1, %2, %3, %4, %5, %6, %7, %8, %9, %10, %11, %12, %13, %14, %15, %16, %17, %18, %19, %20, %21, %22, %23, %24, %25, %26, %27}, {%40, %41, %42, %43}, tb, p1, 1, 1, 1;\n"
        "}\n"
        : "=f"(d[0]), "=f"(d[1]), "=f"(d[2]), "=f"(d[3]), "=f"(d[4]), "=f"(d[5]), "=f"(d[6]), "=f"(d[7]), "=f"(d[8]), "=f"(d[9]), "=f"(d[10]), "=f"(d[11]), "=f"(d[12]), "=f"(d[13]), "=f"(d[14]), "=f"(d[15]), "=f"(d[16]), "=f"(d[17]), "=f"(d[18]), "=f"(d[19]), "=f"(d[20]), "=f"(d[21]), "=f"(d[22]), "=f"(d[23]), "=f"(d[24]), "=f"(d[25]), "=f"(d[26]), "=f"(d[27])
        : "r"(a[AOFF + 0][0]), "r"(a[AOFF + 0][1]), "r"(a[AOFF + 0][2]), "r"(a[AOFF + 0][3]), "r"(a[AOFF + 1][0]), "r"(a[AOFF + 1][1]), "r"(a[AOFF + 1][2]), "r"(a[AOFF + 1][3]), "r"(a[AOFF + 2][0]), "r"(a[AOFF + 2][1]), "r"(a[AOFF + 2][2]), "r"(a[AOFF + 2][3]), "r"(a[AOFF + 3][0]), "r"(a[AOFF + 3][1]), "r"(a[AOFF + 3][2]), "r"(a[AOFF + 3][3]), "l"(descB), "n"(BOFF >> 4));
}

template <int AOFF, int BOFF>
__device__ __forceinline__ void mma_proj(float (&d)[96], uint64_t descA, uint64_t descB) {
    asm volatile(
        "{\n"
        ".reg .pred p0, p1;\n"
        ".reg .b64 ta, ta0, tb, tb0;\n"
        "setp.ne.b32 p0, 0, 0;\n"
        "setp.eq.b32 p1, 0, 0;\n"
        "add.s64 tb0, %98, %99;\n"
        "add.s64 ta0, %96, %97;\n"
        "add.s64 tb, tb0, 0;\n"
        "add.s64 ta, ta0, 0;\n"
        "wgmma.mma_async.sync.aligned.m64n192k16.f32.bf16.bf16 {%0, %1, %2, %3, %4, %5, %6, %7, %8, %9, %10, %11, %12, %13, %14, %15, %16, %17, %18, %19, %20, %21, %22, %23, %24, %25, %26, %27, %28, %29, %30, %31, %32, %33, %34, %35, %36, %37, %38, %39, %40, %41, %42, %43, %44, %45, %46, %47, %48, %49, %50, %51, %52, %53, %54, %55, %56, %57, %58, %59, %60, %61, %62, %63, %64, %65, %66, %67, %68, %69, %70, %71, %72, %73, %74, %75, %76, %77, %78, %79, %80, %81, %82, %83, %84, %85, %86, %87, %88, %89, %90, %91, %92, %93, %94, %95}, ta, tb, p0, 1, 1, 0, 1;\n"
        "add.s64 tb, tb0, 64;\n"
        "add.s64 ta, ta0, 2;\n"
        "wgmma.mma_async.sync.aligned.m64n192k16.f32.bf16.bf16 {%0, %1, %2, %3, %4, %5, %6, %7, %8, %9, %10, %11, %12, %13, %14, %15, %16, %17, %18, %19, %20, %21, %22, %23, %24, %25, %26, %27, %28, %29, %30, %31, %32, %33, %34, %35, %36, %37, %38, %39, %40, %41, %42, %43, %44, %45, %46, %47, %48, %49, %50, %51, %52, %53, %54, %55, %56, %57, %58, %59, %60, %61, %62, %63, %64, %65, %66, %67, %68, %69, %70, %71, %72, %73, %74, %75, %76, %77, %78, %79, %80, %81, %82, %83, %84, %85, %86, %87, %88, %89, %90, %91, %92, %93, %94, %95}, ta, tb, p1, 1, 1, 0, 1;\n"
        "add.s64 tb, tb0, 128;\n"
        "add.s64 ta, ta0, 4;\n"
        "wgmma.mma_async.sync.aligned.m64n192k16.f32.bf16.bf16 {%0, %1, %2, %3, %4, %5, %6, %7, %8, %9, %10, %11, %12, %13, %14, %15, %16, %17, %18, %19, %20, %21, %22, %23, %24, %25, %26, %27, %28, %29, %30, %31, %32, %33, %34, %35, %36, %37, %38, %39, %40, %41, %42, %43, %44, %45, %46, %47, %48, %49, %50, %51, %52, %53, %54, %55, %56, %57, %58, %59, %60, %61, %62, %63, %64, %65, %66, %67, %68, %69, %70, %71, %72, %73, %74, %75, %76, %77, %78, %79, %80, %81, %82, %83, %84, %85, %86, %87, %88, %89, %90, %91, %92, %93, %94, %95}, ta, tb, p1, 1, 1, 0, 1;\n"
        "add.s64 tb, tb0, 192;\n"
        "add.s64 ta, ta0, 6;\n"
        "wgmma.mma_async.sync.aligned.m64n192k16.f32.bf16.bf16 {%0, %1, %2, %3, %4, %5, %6, %7, %8, %9, %10, %11, %12, %13, %14, %15, %16, %17, %18, %19, %20, %21, %22, %23, %24, %25, %26, %27, %28, %29, %30, %31, %32, %33, %34, %35, %36, %37, %38, %39, %40, %41, %42, %43, %44, %45, %46, %47, %48, %49, %50, %51, %52, %53, %54, %55, %56, %57, %58, %59, %60, %61, %62, %63, %64, %65, %66, %67, %68, %69, %70, %71, %72, %73, %74, %75, %76, %77, %78, %79, %80, %81, %82, %83, %84, %85, %86, %87, %88, %89, %90, %91, %92, %93, %94, %95}, ta, tb, p1, 1, 1, 0, 1;\n"
        "add.s64 tb, tb0, 256;\n"
        "add.s64 ta, ta0, 512;\n"
        "wgmma.mma_async.sync.aligned.m64n192k16.f32.bf16.bf16 {%0, %1, %2, %3, %4, %5, %6, %7, %8, %9, %10, %11, %12, %13, %14, %15, %16, %17, %18, %19, %20, %21, %22, %23, %24, %25, %26, %27, %28, %29, %30, %31, %32, %33, %34, %35, %36, %37, %38, %39, %40, %41, %42, %43, %44, %45, %46, %47, %48, %49, %50, %51, %52, %53, %54, %55, %56, %57, %58, %59, %60, %61, %62, %63, %64, %65, %66, %67, %68, %69, %70, %71, %72, %73, %74, %75, %76, %77, %78, %79, %80, %81, %82, %83, %84, %85, %86, %87, %88, %89, %90, %91, %92, %93, %94, %95}, ta, tb, p1, 1, 1, 0, 1;\n"
        "add.s64 tb, tb0, 320;\n"
        "add.s64 ta, ta0, 514;\n"
        "wgmma.mma_async.sync.aligned.m64n192k16.f32.bf16.bf16 {%0, %1, %2, %3, %4, %5, %6, %7, %8, %9, %10, %11, %12, %13, %14, %15, %16, %17, %18, %19, %20, %21, %22, %23, %24, %25, %26, %27, %28, %29, %30, %31, %32, %33, %34, %35, %36, %37, %38, %39, %40, %41, %42, %43, %44, %45, %46, %47, %48, %49, %50, %51, %52, %53, %54, %55, %56, %57, %58, %59, %60, %61, %62, %63, %64, %65, %66, %67, %68, %69, %70, %71, %72, %73, %74, %75, %76, %77, %78, %79, %80, %81, %82, %83, %84, %85, %86, %87, %88, %89, %90, %91, %92, %93, %94, %95}, ta, tb, p1, 1, 1, 0, 1;\n"
        "add.s64 tb, tb0, 384;\n"
        "add.s64 ta, ta0, 516;\n"
        "wgmma.mma_async.sync.aligned.m64n192k16.f32.bf16.bf16 {%0, %1, %2, %3, %4, %5, %6, %7, %8, %9, %10, %11, %12, %13, %14, %15, %16, %17, %18, %19, %20, %21, %22, %23, %24, %25, %26, %27, %28, %29, %30, %31, %32, %33, %34, %35, %36, %37, %38, %39, %40, %41, %42, %43, %44, %45, %46, %47, %48, %49, %50, %51, %52, %53, %54, %55, %56, %57, %58, %59, %60, %61, %62, %63, %64, %65, %66, %67, %68, %69, %70, %71, %72, %73, %74, %75, %76, %77, %78, %79, %80, %81, %82, %83, %84, %85, %86, %87, %88, %89, %90, %91, %92, %93, %94, %95}, ta, tb, p1, 1, 1, 0, 1;\n"
        "add.s64 tb, tb0, 448;\n"
        "add.s64 ta, ta0, 518;\n"
        "wgmma.mma_async.sync.aligned.m64n192k16.f32.bf16.bf16 {%0, %1, %2, %3, %4, %5, %6, %7, %8, %9, %10, %11, %12, %13, %14, %15, %16, %17, %18, %19, %20, %21, %22, %23, %24, %25, %26, %27, %28, %29, %30, %31, %32, %33, %34, %35, %36, %37, %38, %39, %40, %41, %42, %43, %44, %45, %46, %47, %48, %49, %50, %51, %52, %53, %54, %55, %56, %57, %58, %59, %60, %61, %62, %63, %64, %65, %66, %67, %68, %69, %70, %71, %72, %73, %74, %75, %76, %77, %78, %79, %80, %81, %82, %83, %84, %85, %86, %87, %88, %89, %90, %91, %92, %93, %94, %95}, ta, tb, p1, 1, 1, 0, 1;\n"
        "add.s64 tb, tb0, 512;\n"
        "add.s64 ta, ta0, 1024;\n"
        "wgmma.mma_async.sync.aligned.m64n192k16.f32.bf16.bf16 {%0, %1, %2, %3, %4, %5, %6, %7, %8, %9, %10, %11, %12, %13, %14, %15, %16, %17, %18, %19, %20, %21, %22, %23, %24, %25, %26, %27, %28, %29, %30, %31, %32, %33, %34, %35, %36, %37, %38, %39, %40, %41, %42, %43, %44, %45, %46, %47, %48, %49, %50, %51, %52, %53, %54, %55, %56, %57, %58, %59, %60, %61, %62, %63, %64, %65, %66, %67, %68, %69, %70, %71, %72, %73, %74, %75, %76, %77, %78, %79, %80, %81, %82, %83, %84, %85, %86, %87, %88, %89, %90, %91, %92, %93, %94, %95}, ta, tb, p1, 1, 1, 0, 1;\n"
        "add.s64 tb, tb0, 576;\n"
        "add.s64 ta, ta0, 1026;\n"
        "wgmma.mma_async.sync.aligned.m64n192k16.f32.bf16.bf16 {%0, %1, %2, %3, %4, %5, %6, %7, %8, %9, %10, %11, %12, %13, %14, %15, %16, %17, %18, %19, %20, %21, %22, %23, %24, %25, %26, %27, %28, %29, %30, %31, %32, %33, %34, %35, %36, %37, %38, %39, %40, %41, %42, %43, %44, %45, %46, %47, %48, %49, %50, %51, %52, %53, %54, %55, %56, %57, %58, %59, %60, %61, %62, %63, %64, %65, %66, %67, %68, %69, %70, %71, %72, %73, %74, %75, %76, %77, %78, %79, %80, %81, %82, %83, %84, %85, %86, %87, %88, %89, %90, %91, %92, %93, %94, %95}, ta, tb, p1, 1, 1, 0, 1;\n"
        "add.s64 tb, tb0, 640;\n"
        "add.s64 ta, ta0, 1028;\n"
        "wgmma.mma_async.sync.aligned.m64n192k16.f32.bf16.bf16 {%0, %1, %2, %3, %4, %5, %6, %7, %8, %9, %10, %11, %12, %13, %14, %15, %16, %17, %18, %19, %20, %21, %22, %23, %24, %25, %26, %27, %28, %29, %30, %31, %32, %33, %34, %35, %36, %37, %38, %39, %40, %41, %42, %43, %44, %45, %46, %47, %48, %49, %50, %51, %52, %53, %54, %55, %56, %57, %58, %59, %60, %61, %62, %63, %64, %65, %66, %67, %68, %69, %70, %71, %72, %73, %74, %75, %76, %77, %78, %79, %80, %81, %82, %83, %84, %85, %86, %87, %88, %89, %90, %91, %92, %93, %94, %95}, ta, tb, p1, 1, 1, 0, 1;\n"
        "add.s64 tb, tb0, 704;\n"
        "add.s64 ta, ta0, 1030;\n"
        "wgmma.mma_async.sync.aligned.m64n192k16.f32.bf16.bf16 {%0, %1, %2, %3, %4, %5, %6, %7, %8, %9, %10, %11, %12, %13, %14, %15, %16, %17, %18, %19, %20, %21, %22, %23, %24, %25, %26, %27, %28, %29, %30, %31, %32, %33, %34, %35, %36, %37, %38, %39, %40, %41, %42, %43, %44, %45, %46, %47, %48, %49, %50, %51, %52, %53, %54, %55, %56, %57, %58, %59, %60, %61, %62, %63, %64, %65, %66, %67, %68, %69, %70, %71, %72, %73, %74, %75, %76, %77, %78, %79, %80, %81, %82, %83, %84, %85, %86, %87, %88, %89, %90, %91, %92, %93, %94, %95}, ta, tb, p1, 1, 1, 0, 1;\n"
        "}\n"
        : "+f"(d[0]), "+f"(d[1]), "+f"(d[2]), "+f"(d[3]), "+f"(d[4]), "+f"(d[5]), "+f"(d[6]), "+f"(d[7]), "+f"(d[8]), "+f"(d[9]), "+f"(d[10]), "+f"(d[11]), "+f"(d[12]), "+f"(d[13]), "+f"(d[14]), "+f"(d[15]), "+f"(d[16]), "+f"(d[17]), "+f"(d[18]), "+f"(d[19]), "+f"(d[20]), "+f"(d[21]), "+f"(d[22]), "+f"(d[23]), "+f"(d[24]), "+f"(d[25]), "+f"(d[26]), "+f"(d[27]), "+f"(d[28]), "+f"(d[29]), "+f"(d[30]), "+f"(d[31]), "+f"(d[32]), "+f"(d[33]), "+f"(d[34]), "+f"(d[35]), "+f"(d[36]), "+f"(d[37]), "+f"(d[38]), "+f"(d[39]), "+f"(d[40]), "+f"(d[41]), "+f"(d[42]), "+f"(d[43]), "+f"(d[44]), "+f"(d[45]), "+f"(d[46]), "+f"(d[47]), "+f"(d[48]), "+f"(d[49]), "+f"(d[50]), "+f"(d[51]), "+f"(d[52]), "+f"(d[53]), "+f"(d[54]), "+f"(d[55]), "+f"(d[56]), "+f"(d[57]), "+f"(d[58]), "+f"(d[59]), "+f"(d[60]), "+f"(d[61]), "+f"(d[62]), "+f"(d[63]), "+f"(d[64]), "+f"(d[65]), "+f"(d[66]), "+f"(d[67]), "+f"(d[68]), "+f"(d[69]), "+f"(d[70]), "+f"(d[71]), "+f"(d[72]), "+f"(d[73]), "+f"(d[74]), "+f"(d[75]), "+f"(d[76]), "+f"(d[77]), "+f"(d[78]), "+f"(d[79]), "+f"(d[80]), "+f"(d[81]), "+f"(d[82]), "+f"(d[83]), "+f"(d[84]), "+f"(d[85]), "+f"(d[86]), "+f"(d[87]), "+f"(d[88]), "+f"(d[89]), "+f"(d[90]), "+f"(d[91]), "+f"(d[92]), "+f"(d[93]), "+f"(d[94]), "+f"(d[95])
        : "l"(descA), "n"(AOFF >> 4), "l"(descB), "n"(BOFF >> 4));
}

template <int AOFF, int BOFF>
__device__ __forceinline__ void mma_proj64(float (&d)[32], uint64_t descA, uint64_t descB) {
    asm volatile(
        "{\n"
        ".reg .pred p0, p1;\n"
        ".reg .b64 ta, ta0, tb, tb0;\n"
        "setp.ne.b32 p0, 0, 0;\n"
        "setp.eq.b32 p1, 0, 0;\n"
        "add.s64 tb0, %34, %35;\n"
        "add.s64 ta0, %32, %33;\n"
        "add.s64 tb, tb0, 0;\n"
        "add.s64 ta, ta0, 0;\n"
        "wgmma.mma_async.sync.aligned.m64n64k16.f32.bf16.bf16 {%0, %1, %2, %3, %4, %5, %6, %7, %8, %9, %10, %11, %12, %13, %14, %15, %16, %17, %18, %19, %20, %21, %22, %23, %24, %25, %26, %27, %28, %29, %30, %31}, ta, tb, p0, 1, 1, 0, 1;\n"
        "add.s64 tb, tb0, 64;\n"
        "add.s64 ta, ta0, 2;\n"
        "wgmma.mma_async.sync.aligned.m64n64k16.f32.bf16.bf16 {%0, %1, %2, %3, %4, %5, %6, %7, %8, %9, %10, %11, %12, %13, %14, %15, %16, %17, %18, %19, %20, %21, %22, %23, %24, %25, %26, %27, %28, %29, %30, %31}, ta, tb, p1, 1, 1, 0, 1;\n"
        "add.s64 tb, tb0, 128;\n"
        "add.s64 ta, ta0, 4;\n"
        "wgmma.mma_async.sync.aligned.m64n64k16.f32.bf16.bf16 {%0, %1, %2, %3, %4, %5, %6, %7, %8, %9, %10, %11, %12, %13, %14, %15, %16, %17, %18, %19, %20, %21, %22, %23, %24, %25, %26, %27, %28, %29, %30, %31}, ta, tb, p1, 1, 1, 0, 1;\n"
        "add.s64 tb, tb0, 192;\n"
        "add.s64 ta, ta0, 6;\n"
        "wgmma.mma_async.sync.aligned.m64n64k16.f32.bf16.bf16 {%0, %1, %2, %3, %4, %5, %6, %7, %8, %9, %10, %11, %12, %13, %14, %15, %16, %17, %18, %19, %20, %21, %22, %23, %24, %25, %26, %27, %28, %29, %30, %31}, ta, tb, p1, 1, 1, 0, 1;\n"
        "add.s64 tb, tb0, 256;\n"
        "add.s64 ta, ta0, 512;\n"
        "wgmma.mma_async.sync.aligned.m64n64k16.f32.bf16.bf16 {%0, %1, %2, %3, %4, %5, %6, %7, %8, %9, %10, %11, %12, %13, %14, %15, %16, %17, %18, %19, %20, %21, %22, %23, %24, %25, %26, %27, %28, %29, %30, %31}, ta, tb, p1, 1, 1, 0, 1;\n"
        "add.s64 tb, tb0, 320;\n"
        "add.s64 ta, ta0, 514;\n"
        "wgmma.mma_async.sync.aligned.m64n64k16.f32.bf16.bf16 {%0, %1, %2, %3, %4, %5, %6, %7, %8, %9, %10, %11, %12, %13, %14, %15, %16, %17, %18, %19, %20, %21, %22, %23, %24, %25, %26, %27, %28, %29, %30, %31}, ta, tb, p1, 1, 1, 0, 1;\n"
        "add.s64 tb, tb0, 384;\n"
        "add.s64 ta, ta0, 516;\n"
        "wgmma.mma_async.sync.aligned.m64n64k16.f32.bf16.bf16 {%0, %1, %2, %3, %4, %5, %6, %7, %8, %9, %10, %11, %12, %13, %14, %15, %16, %17, %18, %19, %20, %21, %22, %23, %24, %25, %26, %27, %28, %29, %30, %31}, ta, tb, p1, 1, 1, 0, 1;\n"
        "add.s64 tb, tb0, 448;\n"
        "add.s64 ta, ta0, 518;\n"
        "wgmma.mma_async.sync.aligned.m64n64k16.f32.bf16.bf16 {%0, %1, %2, %3, %4, %5, %6, %7, %8, %9, %10, %11, %12, %13, %14, %15, %16, %17, %18, %19, %20, %21, %22, %23, %24, %25, %26, %27, %28, %29, %30, %31}, ta, tb, p1, 1, 1, 0, 1;\n"
        "add.s64 tb, tb0, 512;\n"
        "add.s64 ta, ta0, 1024;\n"
        "wgmma.mma_async.sync.aligned.m64n64k16.f32.bf16.bf16 {%0, %1, %2, %3, %4, %5, %6, %7, %8, %9, %10, %11, %12, %13, %14, %15, %16, %17, %18, %19, %20, %21, %22, %23, %24, %25, %26, %27, %28, %29, %30, %31}, ta, tb, p1, 1, 1, 0, 1;\n"
        "add.s64 tb, tb0, 576;\n"
        "add.s64 ta, ta0, 1026;\n"
        "wgmma.mma_async.sync.aligned.m64n64k16.f32.bf16.bf16 {%0, %1, %2, %3, %4, %5, %6, %7, %8, %9, %10, %11, %12, %13, %14, %15, %16, %17, %18, %19, %20, %21, %22, %23, %24, %25, %26, %27, %28, %29, %30, %31}, ta, tb, p1, 1, 1, 0, 1;\n"
        "add.s64 tb, tb0, 640;\n"
        "add.s64 ta, ta0, 1028;\n"
        "wgmma.mma_async.sync.aligned.m64n64k16.f32.bf16.bf16 {%0, %1, %2, %3, %4, %5, %6, %7, %8, %9, %10, %11, %12, %13, %14, %15, %16, %17, %18, %19, %20, %21, %22, %23, %24, %25, %26, %27, %28, %29, %30, %31}, ta, tb, p1, 1, 1, 0, 1;\n"
        "add.s64 tb, tb0, 704;\n"
        "add.s64 ta, ta0, 1030;\n"
        "wgmma.mma_async.sync.aligned.m64n64k16.f32.bf16.bf16 {%0, %1, %2, %3, %4, %5, %6, %7, %8, %9, %10, %11, %12, %13, %14, %15, %16, %17, %18, %19, %20, %21, %22, %23, %24, %25, %26, %27, %28, %29, %30, %31}, ta, tb, p1, 1, 1, 0, 1;\n"
        "}\n"
        : "=f"(d[0]), "=f"(d[1]), "=f"(d[2]), "=f"(d[3]), "=f"(d[4]), "=f"(d[5]), "=f"(d[6]), "=f"(d[7]), "=f"(d[8]), "=f"(d[9]), "=f"(d[10]), "=f"(d[11]), "=f"(d[12]), "=f"(d[13]), "=f"(d[14]), "=f"(d[15]), "=f"(d[16]), "=f"(d[17]), "=f"(d[18]), "=f"(d[19]), "=f"(d[20]), "=f"(d[21]), "=f"(d[22]), "=f"(d[23]), "=f"(d[24]), "=f"(d[25]), "=f"(d[26]), "=f"(d[27]), "=f"(d[28]), "=f"(d[29]), "=f"(d[30]), "=f"(d[31])
        : "l"(descA), "n"(AOFF >> 4), "l"(descB), "n"(BOFF >> 4));
}

struct Params {
    const __nv_bfloat16* x;
    const __nv_bfloat16* wqkv;
    const __nv_bfloat16* wo;
    const __nv_bfloat16* logit_scale;
    const __nv_bfloat16* cpb_w1;
    const __nv_bfloat16* cpb_w2;
    const __nv_bfloat16* rel_coords;
    const int*           rel_idx;
    const __nv_bfloat16* mask;
    __nv_bfloat16*       out;
    unsigned long long   z1;
};

struct Q {
    static constexpr int npair = NPAIR, nh = NH, hw = NH ? HW : 0;
    static constexpr uint32_t need = ROW_DONE;
    static constexpr int nq = (NWINDOWS - hw) / NPAIR, nr = (NWINDOWS - hw) % NPAIR;
    static constexpr int nr2 = 2 * nr, nt0 = (nq * TOK + 63) / 64, nt1 = ((nq + 1) * TOK + 63) / 64;
    static constexpr int hq = NH ? HW / (NH ? NH : 1) : 0, hr = NPAIR + (NH ? HW % (NH ? NH : 1) : 0), hr2 = 2 * hr;
    static constexpr int ht0 = (hq * TOK + 63) / 64, ht1 = ((hq + 1) * TOK + 63) / 64;
    static constexpr int t1 = TILES - NTAIL;
};
#define PQ(f) Q::f
#define GRID 132

struct Maps {
    CUtensorMap x77, x47, x37, x44, x43, x34, x33;
    CUtensorMap w64, w32, w;
    CUtensorMap s47, s37, s43, s33;
    CUtensorMap o, ob;
};

__device__ __forceinline__ uint32_t row_token(uint32_t r) {
    return r < 28 ? r + 3 * (r >> 2) : r - 24 + 4 * (((r - 28) * 11) >> 5);
}
__device__ __forceinline__ int unrot(int r) { return r ? r - 1 : NWS - 1; }
__device__ __forceinline__ void finish(uint32_t total) {
    __threadfence();
    if (atomicAdd(&g_done, 1u) == total - 1) {
        for (int i = 0; i <= NWS; i++) g_cnt[i] = 0;
        g_done = 0;
    }
}

__global__ void __launch_bounds__(NTHREADS, 1)
swin_window_attn_kernel(const Params P, const __grid_constant__ Maps M) {
    const CUtensorMap &xmap = M.x77, &omap = M.o, &omapb = M.ob, &wmap = M.w;
    extern __shared__ __align__(1024) uint8_t smem[];
    constexpr uint32_t sbase = 1024;
    if (smem_u32(smem) != sbase) return;
    const int tid = threadIdx.x;
    const int wg = __shfl_sync(0xffffffffu, tid >> 7, 0);
    const int warp = __shfl_sync(0xffffffffu, (tid >> 5) & 3, 0);
    const int lane = tid & 31;
    const int g = lane >> 2, c = lane & 3;

    TR(26, wg);
    TP(wg);
    if (tid == 0) TC(0);
    const bool attn = (int)blockIdx.x < 2 * (PQ(npair) + PQ(nh));
    const int pair = blockIdx.x >> 1, half = blockIdx.x & 1;
    const int nwin = pair < PQ(npair) ? PQ(nq) + (pair < PQ(nr) ? 1 : 0) : PQ(hq) + (pair < PQ(hr) ? 1 : 0);
    const int w0 = pair < PQ(npair) ? PQ(hw) + pair : pair - PQ(npair), wstep = pair < PQ(npair) ? PQ(npair) : PQ(nh);
    const int wr0 = w0 >= NWS, wq0 = w0 - wr0 * NWS;
    const int ntiles = (nwin * TOK + 63) >> 6;
    const uint32_t bars = sbase + SM_BAR;
    auto load_x = [&](uint32_t dst, uint32_t bar, uint32_t bar2, int wh, int ww) {
        const int x0 = 7 * ww + 3, y0 = 7 * wh + 3, x1 = ww == NWS - 1 ? 0 : x0 + 4;
        if (wh < NWS - 1) {
#pragma unroll
            for (int ch = 0; ch < 3; ch++) tma_3d_x(dst + ch * QK_CHUNK, &M.x47, bar, ch * 64, x0, y0);
#pragma unroll
            for (int ch = 0; ch < 3; ch++) tma_3d_x(dst + ch * QK_CHUNK + 28 * 128, &M.x37, bar2, ch * 64, x1, y0);
        } else {
#pragma unroll
            for (int ch = 0; ch < 3; ch++) {
                tma_3d_x(dst + ch * QK_CHUNK, &M.x44, bar, ch * 64, x0, y0);
                tma_3d_x(dst + ch * QK_CHUNK + 16 * 128, &M.x43, bar, ch * 64, x0, 0);
            }
#pragma unroll
            for (int ch = 0; ch < 3; ch++) {
                tma_3d_x(dst + ch * QK_CHUNK + 28 * 128, &M.x34, bar2, ch * 64, x1, y0);
                tma_3d_x(dst + ch * QK_CHUNK + 40 * 128, &M.x33, bar2, ch * 64, x1, 0);
            }
        }
    };
    if (EPF >= 6 && tid == 128) {
        const char* p = reinterpret_cast<const char*>(P.x) + (blockIdx.x & 127) * 1024;
        if (EPF == 6) {
            asm volatile("cp.async.bulk.prefetch.L2.global [%0], 16;\n" :: "l"(p) : "memory");
            asm volatile("cp.async.bulk.prefetch.L2.global [%0], 16;\n" :: "l"(p + (size_t)(IMG - 4) * (IMG * 384)) : "memory");
            asm volatile("cp.async.bulk.prefetch.L2.global [%0], 16;\n" :: "l"(p + (size_t)9 * (IMG * 384)) : "memory");
        } else {
            prefetch_l2(p);
            prefetch_l2(p + (size_t)(IMG - 4) * (IMG * 384));
            prefetch_l2(p + (size_t)9 * (IMG * 384));
        }
    }
    if (EPF >= 4 && EPF < 6 && tid >= 128 && tid < (EPF == 5 ? 192 : 160) && attn && elect_one()) {
        const int q = w0 + (half + (tid >> 5 & 1) * 2) * wstep, r = q / NWS, ww = unrot(q - r * NWS);
        int y = 7 * unrot(r) + 3;
        const char* p = reinterpret_cast<const char*>(P.x) + (7 * ww + 3) * 384;
#pragma unroll 1
        for (int i = 0; i < 7; i++, y++) {
            if (y == IMG) y = 0;
            asm volatile("cp.async.bulk.prefetch.L2.global [%0], %1;\n" :: "l"(p + (size_t)y * (IMG * 384)), "r"(ww == NWS - 1 ? 1536 : 2688) : "memory");
        }
    }
    if (EPF && EPF < 4 && (wg == 1 || wg == 2)) {
        const int i = tid - 128, q = w0 + half * wstep, r = q >= NWS;
        const int px = (i * 171) >> 9, py = (px * 37) >> 8;
        int y = 7 * unrot(r) + 3 + py, x = 7 * unrot(q - r * NWS) + 3 + px - 7 * py;
        if (y >= IMG) y -= IMG;
        if (x >= IMG) x -= IMG;
        const char* p = reinterpret_cast<const char*>(P.x) + (size_t)(y * IMG + x) * 384 + (i - 3 * px) * 128;
        if (EPW && i >= 147) p = reinterpret_cast<const char*>(P.wqkv) + min((int)blockIdx.x * 14 + i - 147, 1727) * 128;
        if (i < 147 ? attn : EPW && i < 161) {
            if (EPF == 1) asm volatile("prefetch.global.L2 [%0];\n" :: "l"(p) : "memory");
            if (EPF == 2) { uint32_t d; asm volatile("ld.global.nc.L2::128B.b32 %0, [%1];\n" : "=r"(d) : "l"(p) : "memory"); }
            if (EPF == 3) for (int j = 0; j < 4; j++) asm volatile("prefetch.global.L2 [%0];\n" :: "l"(p + 32 * j) : "memory");
        }
    }
    uint32_t ls = 0;
    if (wg == 0) {
        TP(28);
        if (attn && warp < (WSEQ ? 1 : 3) && elect_one()) {
#pragma unroll
            for (int i = 0; i < (WSEQ ? 3 : 1); i++) mbar_init(bars + B_WRAW + 16 - 8 * (warp + i), 1);
            fence_async_smem();
            if (HDEL && pair >= PQ(npair)) {
                const uint32_t c0 = clock();
                while (clock() - c0 < HDEL) __nanosleep(100);
            }
            TP(29);
#pragma unroll 1
            for (int i0 = warp; i0 < warp + (WSEQ ? 3 : 1); i0++) {
                const int i = WROT == 1 ? (i0 + pair) % 3 : WROT == 2 ? (pair & 1 ? 2 - i0 : i0) : WROT == 3 ? 2 - i0 : i0;
                const uint32_t bar = bars + B_WRAW + 16 - 8 * i, dst = sbase + i * 24576;
                mbar_arrive_expect_tx(bar, 24576);
                tma_3d(dst, &M.w64, bar, half * 128, 64 * i, 0);
                tma_3d(dst + 16384, &M.w32, bar, 64 + half * 32, 64 * i, 0);
            }
            TP(30);
        }
        __syncwarp();
        if (WFIRST && warp == 0) asm volatile("bar.arrive 3, 96;\n" ::: "memory");
        if (PPAR && warp == 0) nb_arrive<416>(11);
        if (attn) asm volatile("ld.global.nc.u16 %0, [%1];\n" : "=r"(ls) : "l"(P.logit_scale + 2 * half + (GORD == 2 ? c >> 1 : c & 1)));
    } else if (wg == 3) {
        if (warp == 3) {
            if (elect_one()) {
#pragma unroll
                for (int i = 0; i < 6; i++)
                    asm volatile("prefetch.tensormap [%0];\n" :: "l"(reinterpret_cast<uint64_t>(&M.x44 + (i < 4 ? i : i - 6))) : "memory");
            }
            if (attn)
#pragma unroll
                for (int i = 0; i < 4; i++) sts128(sbase + SM_V + i * V_STRIDE + (lane < 16 ? lane * 16 : V_STRIDE - 64 + (lane & 3) * 16), 0, 0, 0, 0);
            sts32(sbase + SM_FLAG + lane * 4, 0);
            fence_async_smem();
            asm volatile("bar.arrive 0, 256;\nbar.arrive 11, %0;\n" :: "n"(PPAR ? 416 : 384) : "memory");
        } else if (warp != 1) {
            if (tid == 384) {
                for (int b = 0; b < 4; b++) mbar_init(bars + B_XFULL + b * 8, 2);
                asm volatile("mbarrier.expect_tx.relaxed.cta.shared::cta.b64 [%0], %1;\n" :: "r"(bars + B_XFULL + 8), "r"(3 * 21 * 128) : "memory");
                fence_async_smem();
            }
            __syncwarp();
            asm volatile("bar.arrive 0, 256;\nbar.arrive 11, %0;\n" :: "n"(PPAR ? 416 : 384) : "memory");
            nb_sync<WFIRST ? 96 : 64>(3);
            if (attn && elect_one()) {
                const int j = warp >> 1, q = w0 + j * wstep, r = q >= NWS;
                mbar_arrive_expect_tx(bars + B_XFULL, j ? 3 * 28 * 128 : 3 * XCH);
                load_x(sbase + SM_QK + j * XCH, bars + B_XFULL, bars + B_XFULL + j * 8, unrot(r), unrot(q - r * NWS));
                TP(26 + j);
            }
            __syncwarp();
        } else {
            if (lane == 0) {
                for (int b = 0; b < 4; b++) {
                    mbar_init(bars + B_QKRAW + b * 8, 4);
                    mbar_init(bars + B_VRAW + b * 8, 4);
                    mbar_init(bars + B_VFREE + b * 8, 2);
                    mbar_init(bars + B_QKFREE + b * 8, (NB & 1) ? 1 : 4);
                    mbar_init(bars + B_ODONE + b * 8, 4);
                }
                mbar_init(bars + B_WFULL, 1);
                mbar_init(bars + B_MFULL, 1);
                mbar_init(bars + B_MCONS, 4);
                sts32(bars + B_PROG, 0);
                if (SDEF == 4) sts32(bars + B_PROG + 8, 0);
                for (int b = 0; b < 4; b++) mbar_init(bars + B_STORED + b * 8, 1);
                for (int b = 0; b < 6; b++) {
                    mbar_init(sbase + SM_PBAR + b * 8, 1);
                    mbar_init(sbase + SM_PBAR + 48 + b * 8, PSTORE ? 1 : 4);
                    mbar_init(sbase + SM_PBAR + 104 + b * 8, 4);
                }
                mbar_init(sbase + SM_PBAR + 96, 13);
                fence_async_smem();
            }
            __syncwarp();
            TP(19);
            asm volatile("bar.arrive 0, 256;\nbar.arrive 11, %0;\n" :: "n"(PPAR ? 416 : 384) : "memory");
        }
        asm volatile("bar.sync 2, 128;\n" ::: "memory");
        if (warp == 3 && lane < 8)
            asm volatile("prefetch.tensormap [%0];\n" :: "l"(reinterpret_cast<uint64_t>(&M.x77 + (lane ? lane + 8 : 0))) : "memory");
        TP(13);
    }
    uint32_t ridx[26];
    uint32_t rc, w2[16];
    uint4 w1[4];
    if (attn && (wg == 1 || wg == 2)) {
        rc = reinterpret_cast<const uint32_t*>(P.rel_coords)[min(tid - 128, 168)];
#pragma unroll
        for (int i = 0; i < 4; i++) w1[i] = reinterpret_cast<const uint4*>(P.cpb_w1)[i];
#pragma unroll
        for (int u = 0; u < 16; u++) w2[u] = reinterpret_cast<const uint32_t*>(P.cpb_w2)[2 * u + half];
        ls = reinterpret_cast<const uint32_t*>(P.logit_scale)[half];
        asm volatile("" ::: "memory");
        uint32_t col[7];
#pragma unroll
        for (int j = 0; j < 7; j++) {
            const uint32_t n = j ? 8 * ((j + 5) >> 1) + ((j + 1) & 1) : 0;
            col[j] = prmt(0, row_token(n) | row_token(n + 2) << 8 | row_token(n + 4) << 16 | row_token(n + 6) << 24, 4 + c);
        }
#pragma unroll
        for (int rh = 0; rh < 2; rh++) {
            const uint32_t* ri = reinterpret_cast<const uint32_t*>(P.rel_idx) + row_token(min(warp * 16 + g + 8 * rh, TOK - 1)) * TOK;
            asm volatile("" : "+l"(ri));
#pragma unroll
            for (int j = 0; j < 12; j++) ridx[13 * rh + j] = j < 6 ? (ri + col[0])[14 * (j >> 1) + (j & 1)] : ri[col[j - 5]];
            ridx[13 * rh + 12] = ri[48];
        }
    }
    if (wg == 1) TP(31);
    if (wg == 0) asm volatile("bar.sync 0, 256;\n" ::: "memory");
    else if (wg < 3) nb_sync<PPAR ? 416 : 384>(11);
    TP(4 + wg);

    const uint32_t nfinish = GRID + 4 * (PQ(npair) + PQ(nh));
#define PROJ_SCHEDULE                                                                                   \
    int bid = blockIdx.x;                                                                               \
    asm volatile("" : "+r"(bid));                      \
    const bool at = bid < 2 * PQ(npair);                                                                  \
    const int tile0 = at ? PQ(t1) + 2 * PQ(npair) - 1 - bid : bid - 2 * PQ(npair);                                              \
    const int tstep = at ? 2 * PQ(npair) : GRID - 2 * PQ(npair);                                  \
    const int tend = at ? TILES : PQ(t1);                                                                \
    const int nl = (TILES - 1 - tile0) / (2 * PQ(npair));        \
    const int tend1 = COOP && at ? tile0 + (nl + 1 - COOP) * tstep : tend;
    if (wg == 3) {
        asm volatile("setmaxnreg.dec.sync.aligned.u32 %0;\n" :: "n"(REG_H));
        if (attn && warp == 1 && !(XP & 1)) {
            uint32_t fph = 0, cph = 0, mis = 0, busy = 0;
            auto load = [&](int k, uint32_t dst) {
                const int wi = w0 + k * wstep, wr = wi / NWS;
                const uint32_t off = (uint32_t)(unrot(wr) * NWS + unrot(wi - wr * NWS)) * 4802u;
                mis = mis << 4 | (off & 15);
                if (busy) {
                    mbar_wait(bars + B_MCONS, cph);
                    cph ^= 1;
                    fence_async_smem();
                    busy = 0;
                }
                if (elect_one()) {
                    uint32_t bytes = 4816;
                    if (wi == 0) {
                        bytes = 4800;
                        asm volatile("st.shared.u16 [%0], %1;\n" :: "r"(sbase + SM_MASK + 4800),
                                     "h"(reinterpret_cast<const uint16_t*>(P.mask)[NWINDOWS * TOK * TOK - 1]) : "memory");
                    }
                    asm volatile("mbarrier.expect_tx.relaxed.cta.shared::cta.b64 [%0], %1;\n" :: "r"(bars + B_MFULL), "r"(bytes) : "memory");
                    if (dst == sbase + SM_MASK) mbar_arrive(bars + B_MFULL);
                    asm volatile("cp.async.bulk.shared::cluster.global.mbarrier::complete_tx::bytes.L2::cache_hint [%0], [%1], %2, [%3], %4;\n"
                                 :: "r"(dst), "l"(reinterpret_cast<const char*>(P.mask) + (off & ~15u)),
                                    "r"(bytes), "r"(bars + B_MFULL), "l"(EVICT_FIRST) : "memory");
                }
            };
            auto landed = [&]() {
                mbar_wait_s<HS & 1>(bars + B_MFULL, fph);
                fph ^= 1;
            };
            auto flag = [&](int k, uint32_t f) {
                asm volatile("st.volatile.shared.u8 [%0], %1;\n" :: "r"(sbase + SM_FLAG + k), "r"(f) : "memory");
                TR(18, k);
                if (k < 2) TP(14 + k);
            };
            auto pace = [&](int need) {
                int done = 0;
#pragma unroll 1
                for (uint32_t n = 0; n < (1u << 22); n++) {
                    asm volatile("ld.volatile.shared.b32 %0, [%1];\n" : "=r"(done) : "r"(bars + B_PROG) : "memory");
                    if (done >= need) break;
                    __nanosleep(PSLEEP);
                }
                return done;
            };
            auto buffer = [&](int k) { return sbase + (k == 0 || k > 3 ? SM_MASK : SM_V + 2 * V_STRIDE + 256 + (k >> 1) * 4816); };
            if (MWAIT) mbar_wait(bars + (MWAIT == 1 ? B_XFULL : MWAIT == 2 ? B_WRAW : B_WRAW + 8), 0);
#pragma unroll 1
            for (int k = 2 + half; k >= 0; k = (k >> 1) - (k == 0)) load(k, buffer(k));
            uint32_t todo = 0;
            int sp = 0;
#pragma unroll 1
            for (int k = 0, kn; sp < nwin; k = kn) {
                int done = 0;
                if (k < nwin) {
                    done = pace(MD ? k - MLEAD - MD : k + 2 < nwin ? k - MLEAD : k - 3);
                    if (MD) done = __shfl_sync(0xffffffffu, done, 0);
                    const uint32_t buf = buffer(k);
                    if (buf == sbase + SM_MASK) landed();
                    TR(17, k);
                    uint32_t any;
                    asm volatile("ld.shared.u16 %0, [%1];\n" : "=r"(any)
                                 : "r"(buf + (mis & 15) + ((lane & 8) ? 4800 - 14 : 0) + (lane & 7) * 2) : "memory");
                    mis >>= 4;
#pragma unroll
                    for (int i = 0; i < 10; i++) {
                        uint32_t v[4];
                        asm volatile("ld.shared.v4.b32 {%0, %1, %2, %3}, [%4];\n" : "=r"(v[0]), "=r"(v[1]), "=r"(v[2]), "=r"(v[3])
                                     : "r"(buf + lane * 16 + (i < 9 ? 16 + i * 512 : 4800 - 512)) : "memory");
                        any |= (v[0] | v[1]) | (v[2] | v[3]);
                    }
                    const uint32_t masked = __any_sync(0xffffffffu, any & 0x7FFF7FFFu);
                    if (k >= 2) asm volatile("st.relaxed.gpu.global.u32 [%0], %1;\n" :: "l"(g_flag + pair * 128 + k), "r"(1 + masked) : "memory");
                    if (masked && k) todo |= 1u << (k - sp);
                    else {
                        if (k == 0) __threadfence_block();
                        flag(k, 1 + masked);
                        busy |= masked;
                    }
                }
                if ((k >> 1) == 1 && lane == 0) mbar_arrive(bars + B_VFREE + 8);
                const int lim = MD && k < nwin ? min(k, done + MLEAD) : k;
#pragma unroll
                for (int pass = MD ? 1 : 0; pass >= 0; pass--) {
                if (pass == 0 && k > 2 && k <= nwin) {
                    uint32_t f;
#pragma unroll 1
                    for (uint32_t n = 0; n < (1u << 22); n++) {
                        asm volatile("ld.relaxed.gpu.global.u32 %0, [%1];\n" : "=r"(f) : "l"(g_flag + pair * 128 + k - 1) : "memory");
                        if (__all_sync(0xffffffffu, f)) break;
                        __nanosleep(PSLEEP);
                    }
                    g_flag[pair * 128 + k - 1] = 0;
                    if (f != 1) todo |= 1u << (k - 1 - sp);
                    else flag(k - 1, 1);
                }
#pragma unroll 1
                for (; sp < lim && sp < k - pass; sp++, todo >>= 1)
                    if (todo & 1) {
                        load(sp, sbase + SM_MASK);
                        landed();
                        __threadfence_block();
                        flag(sp, 2);
                        busy = 1;
                    }
                }
                kn = k >= 2 ? k + 2 : k + 1 + (k & half);
                if (kn < nwin && kn > 3) load(kn, sbase + SM_MASK);
                if (MP2 && kn + 2 * MP2 < nwin && kn > 1) {
                    const int wi = w0 + (kn + 2 * MP2) * wstep, wr = wi / NWS;
                    const uint32_t off = (uint32_t)(unrot(wr) * NWS + unrot(wi - wr * NWS)) * 4802u;
                    if (elect_one())
                        asm volatile("cp.async.bulk.prefetch.L2.global [%0], 4816;\n" :: "l"(reinterpret_cast<const char*>(P.mask) + (off & ~15u)) : "memory");
                }
            }
            if (MD) pace(nwin - 4);
        }
        if (!elect_one()) return;
        if (warp == 0) {
          if (attn) {
            const int kmax = (64 * ntiles + 63) / TOK;
            int wr = wr0, wq = wq0, npf = 0;
            int pr2 = (w0 + PF_DIST * wstep) / NWS, pq2 = w0 + PF_DIST * wstep - pr2 * NWS;
#pragma unroll 1
            for (int k = -4; k + 4 <= kmax; k++) {
                const int row0 = (k + 4) * TOK;
                const uint32_t dst = sbase + SM_QK + (k & 3) * XCH, bar = bars + B_XFULL + ((row0 >> 6) & 3) * 8;
                const bool alone = (row0 & 63) >= 64 - TOK && (row0 & 63) < TOK;
                const int wh = unrot(wr), ww = unrot(wq), ph2 = unrot(pr2), pw2 = unrot(pq2);
                const bool done = k < -2;
                if (k == WVK) {
                    if (WVW) mbar_wait(bars + (WVW == 1 ? B_XFULL : WVW == 2 ? B_WRAW : B_WRAW + 8), 0);
                    TP(24);
                    mbar_arrive_expect_tx(bars + B_WFULL, 6 * W_ATOM);
                    tma_3d(sbase + SM_WV, &wmap, bars + B_WFULL, 0, 0, V64 ? 12 + half * 3 : 24 + half * 6);
                }
                const uint32_t bar2 = (row0 & 63) >= 64 - 28 ? bars + B_XFULL + (((row0 >> 6) + 1) & 3) * 8 : bar;
                if (alone && !done) mbar_arrive(bar);
                if (!done && !(k + 4 >= nwin && k >= 0)) {
                    if (bar2 != bar) asm volatile("mbarrier.expect_tx.relaxed.cta.shared::cta.b64 [%0], %1;\n" :: "r"(bar2), "r"(3 * 21 * 128) : "memory");
                    mbar_arrive_expect_tx(bar, bar2 != bar ? 3 * 28 * 128 : 3 * XCH);
                }
                if (SDEF == 4 && k >= 0 && k + 4 < nwin) {
                    const int t1 = (TOK * (k + 1) - 1) >> 6;
                    mbar_wait(bars + B_QKRAW + (t1 & 3) * 8, (t1 >> 2) & 1);
                    asm volatile("st.volatile.shared.v2.b32 [%0], {%1, %2};\n" :: "r"(bars + B_PROG + 8), "r"(k), "r"(clock32()) : "memory");
                }
                if (k >= 0 && k + 4 < nwin && wh < NWS - 1) {
                    const int x0 = 7 * ww + 3, y0 = 7 * wh + 3, x1 = ww == NWS - 1 ? 0 : x0 + 4;
                    asm volatile("bar.sync %0, 160;\n"
                                 "cp.async.bulk.tensor.3d.shared::cluster.global.mbarrier::complete_tx::bytes [%1], [%7, {%14, %11, %13}], [%9];\n"
                                 "cp.async.bulk.tensor.3d.shared::cluster.global.mbarrier::complete_tx::bytes [%2], [%7, {%15, %11, %13}], [%9];\n"
                                 "cp.async.bulk.tensor.3d.shared::cluster.global.mbarrier::complete_tx::bytes [%3], [%7, {%16, %11, %13}], [%9];\n"
                                 "cp.async.bulk.tensor.3d.shared::cluster.global.mbarrier::complete_tx::bytes [%4], [%8, {%14, %12, %13}], [%10];\n"
                                 "cp.async.bulk.tensor.3d.shared::cluster.global.mbarrier::complete_tx::bytes [%5], [%8, {%15, %12, %13}], [%10];\n"
                                 "cp.async.bulk.tensor.3d.shared::cluster.global.mbarrier::complete_tx::bytes [%6], [%8, {%16, %12, %13}], [%10];\n"
                                 :: "r"(NB_QKFREE + (k & 1) + (EXD ? __umulhi(__umulhi((x0 | y0 | x1) + dst, bar2), bar) : 0)), "r"(dst), "r"(dst + QK_CHUNK), "r"(dst + 2 * QK_CHUNK), "r"(dst + 28 * 128),
                                    "r"(dst + QK_CHUNK + 28 * 128), "r"(dst + 2 * QK_CHUNK + 28 * 128),
                                    "l"(reinterpret_cast<uint64_t>(&M.x47)), "l"(reinterpret_cast<uint64_t>(&M.x37)), "r"(bar), "r"(bar2),
                                    "r"(x0), "r"(x1), "r"(y0), "r"(0), "r"(64), "r"(128) : "memory");
                } else {
                if (NB & 1) {
                    if (k >= 0) nb_sync<160>(NB_QKFREE + (k & 1));
                } else mbar_wait(bars + B_QKFREE + (k & 3) * 8, (k >> 2) & 1);
                if (!EXH && alone && !done) mbar_arrive(bar);
                if (k + 4 >= nwin && k >= 0) {
                    mbar_arrive(bar);
                    continue;
                }
                TR(20, k + 4);
                if (k < 0) TP(44 + k);
                if (!done) load_x(dst, bar, bar2, wh, ww);
                }
                TR(25, k + 4);
                asm volatile("st.volatile.shared.b32 [%0], %1;\n" :: "r"(bars + B_PROG), "r"(max(k + 1, 0)) : "memory");
                if (NOPF || (PFM >= 7 && k > 0)) {
                } else if (PFM == 6) {
                    npf++;
                    const int t1 = (TOK * (k + 2) - 1) >> 6;
                    if (half == 0 && (k < 0 || npf > 2 || !mbar_test(bars + B_QKRAW + (t1 & 3) * 8, (t1 >> 2) & 1))) {
#pragma unroll 1
                        for (; npf > 0; npf--) {
                            if (pr2 < NWS)
                                asm volatile("cp.async.bulk.prefetch.tensor.3d.L2.global.tile [%0, {%1, %2, %3}];\n"
                                             :: "l"(reinterpret_cast<uint64_t>(&xmap)), "r"(0), "r"(7 * unrot(pq2) + 3), "r"(7 * unrot(pr2) + 3) : "memory");
                            pq2 += wstep; if (pq2 >= NWS) { pq2 -= NWS; pr2++; }
                        }
                    }
                } else if (PFM == 2) {
                    if (pr2 < NWS && half == 0) {
                        const char* xp = reinterpret_cast<const char*>(P.x) + (size_t)((7 * ph2 + 3) * IMG + 7 * pw2 + 3) * 384;
#pragma unroll 1
                        for (int r = 0; r < (ph2 == NWS - 1 ? 3 : 7); r++)
                            asm volatile("cp.async.bulk.prefetch.L2.global [%0], 2688;\n" :: "l"(xp + r * (IMG * 384)) : "memory");
                    }
                } else if (PFM == 1 ? ((k ^ half) & 1) : PFM == 4 ? half == 1 : PFM == 5 ? 1 : half == 0) {
                    if (pr2 < NWS) {
#pragma unroll
                        for (int ch = 0; ch < (PF1 ? 1 : 3); ch++)
                            if (CH & 8)
                            asm volatile("cp.async.bulk.prefetch.tensor.3d.L2.global.tile.L2::cache_hint [%0, {%1, %2, %3}], %4;\n"
                                         :: "l"(reinterpret_cast<uint64_t>(&xmap)), "r"(ch * 64), "r"(7 * pw2 + 3), "r"(7 * ph2 + 3), "l"(EVICT_FIRST)
                                         : "memory");
                            else
                            asm volatile("cp.async.bulk.prefetch.tensor.3d.L2.global.tile [%0, {%1, %2, %3}];\n"
                                         :: "l"(reinterpret_cast<uint64_t>(&xmap)), "r"(ch * 64), "r"(7 * pw2 + 3), "r"(7 * ph2 + 3)
                                         : "memory");
                        if (PFW && pw2 == NWS - 1)
                            asm volatile("cp.async.bulk.prefetch.tensor.3d.L2.global.tile [%0, {%1, %2, %3}];\n"
                                         :: "l"(reinterpret_cast<uint64_t>(&xmap)), "r"(0), "r"(-4), "r"(7 * ph2 + 3) : "memory");
                    }
                }
                wq += wstep; if (wq >= NWS) { wq -= NWS; wr++; }
                if (PFM != 6) { pq2 += wstep; if (pq2 >= NWS) { pq2 -= NWS; pr2++; } }
            }
            if (!VLATE) mbar_wait(bars + B_VRAW + ((ntiles - 1) & 3) * 8, ((ntiles - 1) >> 2) & 1);
          }
            PROJ_SCHEDULE
            int st = 0, ready = -1, pwa = 0, pwi = -1;
            auto look = [&](uint32_t bar, uint32_t par) {
#pragma unroll 1
                for (uint32_t n = 0; n < (1u << 22) && ready < NWS - LOOKE && !mbar_test(bar, par); n++) {
                    uint32_t a;
                    asm volatile("ld.acquire.gpu.global.u32 %0, [%1];\n" : "=r"(a) : "l"(g_cnt + ready + 1) : "memory");
                    if (a >= PQ(need)) {
                        ready++;
                        asm volatile("fence.proxy.async.global;\n" ::: "memory");
                    }
                }
            };
            uint32_t ph = 1;
#pragma unroll 1
            for (int t = tile0; t < tend; t += tstep) {
                const int p0 = (t < TILES_A) ? SEG_B + 64 * t : 64 * (t - TILES_A);
                const int w1 = (t < TILES_A) ? 0 : min((p0 + 63 + 4 * IMG) / (7 * IMG), NWS - 1);
                if (bid < 2 * (PQ(npair) + PQ(nh)) && t == tile0 + tstep) {
                    if (LOOKA && at) look(sbase + SM_PBAR + 96, 0);
                    mbar_wait(sbase + SM_PBAR + 96, 0);
                    fence_async_smem();
                }
                if (CHK && !at) {
#pragma unroll 1
                    for (uint32_t n = 0; ready < w1 && n < (1u << 24); n++) {
                        if (n) __nanosleep(32);
                        asm volatile("ld.acquire.cta.shared.b32 %0, [%1];\n" : "=r"(ready) : "r"(sbase + SM_FLAG + 124) : "memory");
                        ready--;
                    }
                } else if (ready < w1) {
                    ready = max(ready, w1 - 2);
#pragma unroll 1
                    while (ready < w1) {
                        ready++;
#pragma unroll 1
                        for (uint32_t n = 0; n < (1u << 22); n++) {
                            uint32_t a;
                            asm volatile("ld.acquire.gpu.global.u32 %0, [%1];\n" : "=r"(a) : "l"(g_cnt + ready) : "memory");
                            if (a >= PQ(need)) break;
                            if (PSL2 >= 0) __nanosleep(PSL2);
                            else if (!at) __nanosleep(64);
                        }
                    }
                    asm volatile("fence.proxy.async.global;\n" ::: "memory");
                }
                if (VLATE && attn && t == tile0) {
                    if (VLATE == 2 && at) look(bars + B_VRAW + ((ntiles - 1) & 3) * 8, ((ntiles - 1) >> 2) & 1);
                    mbar_wait(bars + B_VRAW + ((ntiles - 1) & 3) * 8, ((ntiles - 1) >> 2) & 1);
                }
                TRH(9, (t - tile0) / tstep);
                mbar_wait_s<(HS & 4) != 0>(sbase + SM_PBAR + 48 + st * 8, ph);
                TRH(5, (t - tile0) / tstep);
                if (PEXP & 2) mbar_arrive(sbase + SM_PBAR + st * 8); else {
                mbar_arrive_expect_tx(sbase + SM_PBAR + st * 8, STAGE_BYTES);
#pragma unroll
                for (int ch = 0; ch < 3; ch++)
                    tma_2d(sbase + SM_STAGE + st * STAGE_BYTES + ch * 8192, &omap, sbase + SM_PBAR + st * 8, ch * 64, (PEXP & 4) ? p0 & 8191 : p0);
                }
                if (++st == 6) { st = 0; ph ^= 1; }
            }
            finish(nfinish);
        } else if (!attn) {
        } else if (warp == 1) {
          {
            if (PQ(t1) < TILES) {
#pragma unroll 1
                for (uint32_t n = 0; n < (1u << 22); n++) {
                    uint32_t a;
                    asm volatile("ld.acquire.gpu.global.u32 %0, [%1];\n" : "=r"(a) : "l"(g_cnt + NWS) : "memory");
                    if (a) break;
                    __nanosleep(64);
                }
                asm volatile("fence.proxy.async.global;\n" ::: "memory");
                if (blockIdx.x % 6 == 0)
                    asm volatile("cp.async.bulk.prefetch.L2.global [%0], 4096;\n" :: "l"(g_wo + blockIdx.x / 6 % 18 * 4096) : "memory");
                if (NB & 4) mbar_wait(bars + B_QKRAW, 0);
                else mbar_wait(bars + B_QKRAW + ((ntiles - 1) & 3) * 8, ((ntiles - 1) >> 2) & 1);
                mbar_arrive_expect_tx(bars + B_WRAW, 73728);
#pragma unroll
                for (int i = 0; i < 4; i++) {
                    const uint32_t o = ((i + pair) & 3) * 18432;
                    asm volatile("cp.async.bulk.shared::cluster.global.mbarrier::complete_tx::bytes [%0], [%1], 18432, [%2];\n"
                                 :: "r"(sbase + SM_WO + o), "l"(g_wo + o), "r"(bars + B_WRAW) : "memory");
                }
            }
            finish(nfinish);
          }
        } else if (warp == 2) {
            int wh = wr0, ww = wq0, nb = wr0 + 1, k = 0;
#pragma unroll 1
            for (int j = 0; k < nwin; j++) {
                mbar_wait_s<HS & 1>(bars + B_STORED + (j & 1) * 8, (j >> 1) & 1);
                mbar_arrive(bars + B_PUBD + (j & 1) * 8);
                if (SELFP && (wh == NWS - 1 || pair >= PQ(npair))) break;
                if (PUBM != 1) asm volatile("fence.release.gpu;\n" ::: "memory");
#pragma unroll 1
                for (; wh < nb && k < nwin; k++) {
                    asm volatile("red.relaxed.gpu.global.add.u32 [%0], 1;\n" :: "l"(g_cnt + wh) : "memory");
                    ww += wstep; if (ww >= NWS) { ww -= NWS; wh++; }
                }
                nb = wh >= PBE ? wh + 1 : (wh | 1) + 1;
            }
            if (!SELFP) TC(7);
            finish(nfinish);
        } else {
            for (int t = 0; t < 2; t++) mbar_arrive_n(bars + B_VFREE + t * 8, M01 == 2 ? 2 - t : 2);
            int wr = wr0, wq = wq0, nb = wr0 + 1, j = 0, npf = 0, tprev = 0, klast = 0, wlast = wr0;
            int pr2 = (w0 + (PF_DIST + 5) * wstep) / NWS, pq2 = w0 + (PF_DIST + 5) * wstep - pr2 * NWS;
#pragma unroll 1
            for (int k = 0; k < nwin; k++) {
                const uint32_t src = sbase + SM_V + (k & 3) * V_STRIDE;
                const int wh = unrot(wr), ww = unrot(wq);
                const int x0 = 7 * ww + 3, y0 = 7 * wh + 3;
                if (NB & 2) nb_sync<160>(NB_ODONE + (k & 3));
                else mbar_wait_s<(HS & 2) != 0>(bars + B_ODONE + (k & 3) * 8, (k >> 2) & 1);
                if (SDEF) {
                    const int t1 = (TOK * (k + 2) - 1) >> 6, t2 = (TOK * (k + 3) - 1) >> 6;
                    int need = 0;
                    if (SDEF == 4) {
                        int tag, tq;
                        asm volatile("ld.volatile.shared.v2.b32 {%0, %1}, [%2];\n" : "=r"(tag), "=r"(tq) : "r"(bars + B_PROG + 8) : "memory");
                        const int now = clock32();
                        if (tag == k + 1 && now - tq > STH && now - tprev > STH + STP) need = k + 2;
                        tprev = now;
                    } else
                    if (SDEF == 3 || mbar_test(bars + B_QKRAW + (t1 & 3) * 8, (t1 >> 2) & 1)) need = k + 2;
                    if (SDEF == 2 && mbar_test(bars + B_QKRAW + (t2 & 3) * 8, (t2 >> 2) & 1)) need = k + 3;
                    need = min(need, nwin - 4);
#pragma unroll 1
                    for (int n = 0; n < (SDV == 2 ? 0 : 4096); n++) {
                        int done;
                        asm volatile("ld.volatile.shared.b32 %0, [%1];\n" : "=r"(done) : "r"(bars + B_PROG) : "memory");
                        if (done >= need) break;
                        __nanosleep(SDN);
                    }
                    if (SDV && need == k + 2) mbar_wait(bars + B_VRAW + (t1 & 3) * 8, (t1 >> 2) & 1);
                }
                fence_async_smem();
                TR(22, k);
                const int x1 = ww == NWS - 1 ? 0 : x0 + 4;
                if (!(XP & 2)) tma_store_4d(&M.s47, src, 0, half, x0, y0);
                if (!(XP & 2)) tma_store_4d(&M.s37, src + 28 * O_PITCH, 0, half, x1, y0);
                if (wh == NWS - 1) {
                    tma_store_4d(&M.s43, src + 16 * O_PITCH, 0, half, x0, 0);
                    tma_store_4d(&M.s33, src + 40 * O_PITCH, 0, half, x1, 0);
                }
                asm volatile("cp.async.bulk.commit_group;\n" ::: "memory");
                if (PFM >= 7) {
                    npf++;
                    const int t2 = (TOK * (k + 3) - 1) >> 6;
                    if (half == 0 && (PFM == 8 || npf > 2 || !mbar_test(bars + B_QKRAW + (t2 & 3) * 8, (t2 >> 2) & 1))) {
#pragma unroll 1
                        for (; npf > 0; npf--) {
                            if (pr2 < NWS && k + PF_DIST + 6 - npf < nwin)
                                asm volatile("cp.async.bulk.prefetch.tensor.3d.L2.global.tile [%0, {%1, %2, %3}];\n"
                                             :: "l"(reinterpret_cast<uint64_t>(&xmap)), "r"(0), "r"(7 * unrot(pq2) + 3), "r"(7 * unrot(pr2) + 3) : "memory");
                            pq2 += wstep; if (pq2 >= NWS) { pq2 -= NWS; pr2++; }
                        }
                    }
                }
                asm volatile("cp.async.bulk.wait_group.read 0;\n" ::: "memory");
                {
                    const int row0 = (k + 4) * TOK;
                    mbar_arrive_n(bars + B_VFREE + ((row0 >> 6) & 3) * 8, ((row0 & 63) >= 64 - TOK && (row0 & 63) < TOK) ? 2 : 1);
                }
                TR(23, k);
                if (k == nwin - 1) mbar_arrive(sbase + SM_PBAR + 96);
                wq += wstep; if (wq >= NWS) { wq -= NWS; wr++; }
                if (wr >= nb || k == nwin - 1) {
                    nb = wr >= PBE ? wr + 1 : (wr | 1) + 1;
                    asm volatile("cp.async.bulk.wait_group 0;\n" ::: "memory");
                    if (WFEN) asm volatile("fence.proxy.async.global;\n" ::: "memory");
                    if (SELFP && k == nwin - 1) {
                        asm volatile("red.release.gpu.global.add.u32 [%0], %1;\n" :: "l"(g_cnt + wlast), "r"(nwin - klast) : "memory");
                        TC(7);
                    }
                    klast = k + 1;
                    wlast = wr;
                    mbar_wait(bars + B_PUBD + (j & 1) * 8, ((j >> 1) + 1) & 1);
                    mbar_arrive(bars + B_STORED + (j & 1) * 8);
                    j++;
                }
            }
        }
        if (CHK && warp == 2) {
            PROJ_SCHEDULE
            const int tl = tile0 + (tend - 1 - tile0) / tstep * tstep, wl = min((64 * (tl - TILES_A) + 63 + 4 * IMG) / (7 * IMG), NWS - 1);
#pragma unroll 1
            for (int r = 0; !at && r <= wl; r++) {
#pragma unroll 1
                for (uint32_t n = 0; n < (1u << 22); n++) {
                    uint32_t a;
                    asm volatile("ld.acquire.gpu.global.u32 %0, [%1];\n" : "=r"(a) : "l"(g_cnt + r) : "memory");
                    if (a >= PQ(need)) break;
                    __nanosleep(CHKS);
                }
                asm volatile("fence.proxy.async.global;\n" ::: "memory");
                asm volatile("st.release.cta.shared.b32 [%0], %1;\n" :: "r"(sbase + SM_FLAG + 124), "r"(r + 1) : "memory");
            }
        }
        if (PSTORE && warp == 1) {
            PROJ_SCHEDULE
            int st = 0, prev = -1;
            uint32_t ph = 0;
#pragma unroll 1
            for (int t = tile0; t < tend1; t += tstep) {
                const int p0 = (t < TILES_A) ? SEG_B + 64 * t : 64 * (t - TILES_A);
                mbar_wait_s<(HS & 4) != 0>(sbase + SM_PBAR + 104 + st * 8, ph);
                fence_async_smem();
#pragma unroll
                for (int ch = 0; ch < ((PEXP & 1) ? 0 : 3); ch++)
                    if (CH & 1)
                    asm volatile("cp.async.bulk.tensor.2d.global.shared::cta.tile.bulk_group.L2::cache_hint [%0, {%2, %3}], [%1], %4;\n"
                                 :: "l"(reinterpret_cast<uint64_t>(t < TILES_A ? &omap : &omapb)),
                                    "r"(sbase + SM_STAGE + st * STAGE_BYTES + ch * 8192), "r"(ch * 64), "r"(p0), "l"(EVICT_FIRST) : "memory");
                    else
                    asm volatile("cp.async.bulk.tensor.2d.global.shared::cta.tile.bulk_group [%0, {%2, %3}], [%1];\n"
                                 :: "l"(reinterpret_cast<uint64_t>(t < TILES_A ? &omap : &omapb)),
                                    "r"(sbase + SM_STAGE + st * STAGE_BYTES + ch * 8192), "r"(ch * 64), "r"((PEXP & 8) ? (p0 & 8191) + 16384 : p0) : "memory");
                asm volatile("cp.async.bulk.commit_group;\n" ::: "memory");
                TRH(6, (t - tile0) / tstep);
                if (prev >= 0) {
                    asm volatile("cp.async.bulk.wait_group.read 1;\n" ::: "memory");
                    mbar_arrive(sbase + SM_PBAR + 48 + prev * 8);
                    TRH(21, (t - tile0) / tstep - 1);
                }
                prev = st;
                if (++st == 6) { st = 0; ph ^= 1; }
            }
            if (ENDR) asm volatile("cp.async.bulk.wait_group.read 0;\n" ::: "memory");
            else asm volatile("cp.async.bulk.wait_group 0;\n" ::: "memory");
            TR(30, 0);
            if (!(COOP && at)) TC(1);
        }
        return;
    }
    auto permute = [&](int i0, int i1) {
            uint32_t src[3][4], dst[3];
#pragma unroll
            for (int it = 0; it < 3; it++) {
                const int o = warp * 12 + it * 4 + (lane >> 3), r = (o / 6) * 8 + (lane & 7), u = o % 6;
#pragma unroll
                for (int h = 0; h < (GORD == 2 ? 0 : 2); h++) {
                    const int v = u + 6 * h + 4 * half;
                    const bool wide = v >> 3 == half;
                    src[it][h] = wide ? r * 128 + (((v ^ r) & 7) << 4) : 16384 + r * 64 + (((v ^ (r >> 1)) & 3) << 4);
                    src[it][2 + h] = src[it][h] + (wide ? 8192 : 4096);
                }
                dst[it] = sbase + u * 4096 + r * 32 + ((lane >> 2) & 1) * 16;
            }
            TP(16);
#pragma unroll 1
            for (int i = i0; i < i1; i++) {
                uint4 w[3][4];
                mbar_wait(bars + B_WRAW + 16 - 8 * i, 0);
                TP(20 + i);
#pragma unroll
                for (int it = 0; it < 3; it++)
#pragma unroll
                    for (int m = 0; m < 4; m++) w[it][m] = *reinterpret_cast<const uint4*>(smem + src[it][m] + i * 24576);
                wg_bar(PPAR ? 12 + wg : 7);
#pragma unroll
                for (int it = 0; it < 3; it++) {
                    const uint32_t d = dst[it] + i * 24576;
                    sts128(d, w[it][0].x, w[it][1].x, w[it][2].x, w[it][3].x);
                    sts128(d ^ 16, w[it][0].y, w[it][1].y, w[it][2].y, w[it][3].y);
                    sts128(d + 2048, w[it][0].z, w[it][1].z, w[it][2].z, w[it][3].z);
                    sts128((d ^ 16) + 2048, w[it][0].w, w[it][1].w, w[it][2].w, w[it][3].w);
                }
            }
        };
    if (PPAR && attn) {
        permute(wg, wg + 1);
        if (wg) nb_arrive<384>(15);
    }
    if (!attn) {
        asm volatile("setmaxnreg.inc.sync.aligned.u32 160;\n");
    } else if (wg == 0) {
        if (!PPAR) permute(0, 3);
        asm volatile("setmaxnreg.inc.sync.aligned.u32 %0;\n" :: "n"(REG_G));
        float qs = 1.f;
        if (GORD == 2 || c < 2) qs = round_bf16(expf(round_bf16(fminf(fmaxf(bf16lo(ls), -100.f), 4.6052f)))) * LOG2E;
        uint32_t xa[12][4];
        float accA[48], accB[48], accV[48];
        uint32_t rho = warp * 16 + (lane & 15), rq = warp * 16 + g;
        uint32_t hi = lane >> 4, lane0 = lane == 0, c2 = 2 * c;
        asm volatile("" : "+r"(hi), "+r"(lane0), "+r"(c2));
        auto row_addr = [&](uint32_t (&ax)[4], uint32_t r) {
            ax[0] = sbase + SM_QK + r * 128 + (((r & 7) ^ hi) << 4);
#pragma unroll
            for (int i = 1; i < 4; i++) ax[i] = ax[0] ^ (32 * i);
        };
#define XADDR(ax, s) ((ax)[((s) & 3) ^ (((s) >> 1) & 2)] + ((s) >> 2) * QK_CHUNK)
        uint64_t descW = make_desc(sbase, 2048, 256, 3);
        const uint32_t zero = (uint32_t)P.z1;
        const uint32_t vbase = sbase + SM_V + (lane >> 4) * GRP;
        const uint32_t ones = 0x3F803F80u, ones2 = ones;
        TP(10);
        {
            uint32_t ax[4];
            row_addr(ax, rho);
            mbar_wait(bars + B_XFULL, 0);
#pragma unroll
            for (int s = 0; s < 12; s++) ldsm_x4(xa[s], XADDR(ax, s));
        }
        TP(8);
        if (PPAR) nb_sync<384>(15); else wg_bar(7);
        fence_async_smem();
        TP(9);
        wgmma_fence();
        mma_qkv_a<SM_WA, 0>(accA, xa, descW);
        mma_qkv_b<SM_WA, KLO>(accA, xa, descW);
        wgmma_commit();
        mma_qkv_a<SM_WB, 0>(accB, xa, descW);
        wgmma_commit();
        TP(11);
        mbar_wait(bars + B_WFULL, 0);
        TP(12);
        if (tid == 0) TC(3);
        const int nt = (int)blockIdx.x < 2 * PQ(npair) ? ((int)blockIdx.x < PQ(nr2) ? PQ(nt1) : PQ(nt0)) : ((int)blockIdx.x < PQ(hr2) ? PQ(ht1) : PQ(ht0));
        for (int t = 0; t < nt; t++) {
            descW += P.z1;
            float ss[4];
            uint32_t pk[2][24];
            wgmma_wait<1>();
            reg_fence(accA);
            TR(0, t);
            TA(1, 0);
            if (t < 12 && (t < 4 || (t & 1))) TP(t < 4 ? 32 + t : 34 + (t >> 1));
#pragma unroll
            for (int i = 0; i < 4; i++) ss[i] = accA[i] * accA[i];
#pragma unroll
            for (int i = 4; i < 48; i++) ss[i & 3] = fmaf(accA[i], accA[i], ss[i & 3]);
            mma_qkv_b<SM_WB, KLO>(accB, xa, descW);
            wgmma_commit();
            TA(1, 1);
            sched_fence(zero, __float_as_uint(ss[0]), __float_as_uint(ss[1]), __float_as_uint(ss[2]), __float_as_uint(ss[3]));
#pragma unroll
            for (int j = 0; j < 12; j++) {
                pk[0][j] = pack_bf16(accA[4 * j], accA[4 * j + 1]);
                pk[1][j] = pack_bf16(accA[4 * j + 2], accA[4 * j + 3]);
                asm volatile("" : "+r"(pk[0][j]), "+r"(pk[1][j]));
            }
            wgmma_fence();
            if (V64) mma_w_a<0, 0>(accV, xa, descW + D_WV64); else mma_v_a<D_WV, 0>(accV, xa, descW);
            wgmma_commit();
            TA(1, 2);
            uint32_t av = vbase + rho * 16 + ((rho * 1338) >> 16) * (V_STRIDE - GRP);
            uint32_t aq[2];
            aq[0] = sbase + SM_QK + rq * 128 + (((rq & 7) ^ c2) << 4);
            aq[1] = aq[0] + 1024;
            if (rq >= 4 * TOK - 8) aq[1] = (aq[1] - QK_CHUNK) ^ 64;
            rho += 64;
            if (rho >= 4 * TOK) rho -= 4 * TOK;
            rq += 64;
            if (rq >= 4 * TOK) rq -= 4 * TOK;
            uint32_t an[4];
            row_addr(an, rho);
            const uint32_t bt = bars + (t & 3) * 8, pt = (t >> 2) & 1, bn = bars + ((t + 1) & 3) * 8, pn = ((t + 1) >> 2) & 1;
            uint32_t xok;
            wgmma_wait<1>();
            reg_fence(accB);
            TA(1, 3);
#pragma unroll
            for (int i = 0; i < 48; i++) ss[i & 3] = fmaf(accB[i], accB[i], ss[i & 3]);
            ss[0] += ss[1]; ss[2] += ss[3];
            if (V64) mma_w_b<0, KLO>(accV, xa, descW + D_WV64); else mma_v_b<D_WV, KLO>(accV, xa, descW);
            wgmma_commit();
            TA(1, 4);
            sched_fence(zero, __float_as_uint(ss[0]), __float_as_uint(ss[2]), av, aq[0], aq[1], an[0], an[1], an[2], an[3], rho, rq);
            const float f0 = rsqrt_ftz(ss[0] + 1e-12f) * qs, f1 = rsqrt_ftz(ss[2] + 1e-12f) * qs;
            const uint32_t f2[2] = {pack_bf16(f0, f0), pack_bf16(f1, f1)};
#pragma unroll
            for (int j = 0; j < 12; j++) {
                pk[0][12 + j] = (FM & 1) ? pack_bf16(accB[4 * j] * f0, accB[4 * j + 1] * f0) : pack_bf16(accB[4 * j], accB[4 * j + 1]);
                pk[1][12 + j] = (FM & 1) ? pack_bf16(accB[4 * j + 2] * f1, accB[4 * j + 3] * f1) : pack_bf16(accB[4 * j + 2], accB[4 * j + 3]);
            }
            auto qk_store = [&](int u0, int u1) {
#pragma unroll
                for (int u = u0; u < u1; u++)
#pragma unroll
                    for (int r = 0; r < 2; r++)
                        if ((FM & 1) && u >= 3)
                        sts128((aq[r] ^ ((u & 1) * 16 + (u & 2) * 32)) + (u >> 1) * QK_CHUNK, pk[r][4 * u], pk[r][4 * u + 1], pk[r][4 * u + 2], pk[r][4 * u + 3]);
                        else
                        sts128((aq[r] ^ ((u & 1) * 16 + (u & 2) * 32)) + (u >> 1) * QK_CHUNK,
                               hmul2_bf16(pk[r][4 * u], f2[r]), hmul2_bf16(pk[r][4 * u + 1], f2[r]),
                               hmul2_bf16(pk[r][4 * u + 2], f2[r]), hmul2_bf16(pk[r][4 * u + 3], f2[r]));
            };
            qk_store(0, XPOS - 1);
            xok = mbar_test(bn + B_XFULL, pn);
            qk_store(XPOS - 1, QSPLIT);
            if (EARLYQ) {
                __syncwarp();
                mbar_arrive_if(bt + B_QKRAW, lane0);
            }
            TR(1, t);
            TA(1, 5);
            mbar_wait_unless(xok, bn + B_XFULL, pn);
            TR(2, t);
            wgmma_wait<1>();
            TA(1, 6);
#pragma unroll
            for (int s = 0; s < (LDE == 2 ? 12 : KLO); s++) ldsm_x4(xa[s], XADDR(an, s));
            qk_store(QSPLIT, 6 - QPOST);
            if (QPOST) {
                wgmma_fence();
                mma_qkv_a<SM_WA, 0>(accA, xa, descW);
                wgmma_commit();
                qk_store(6 - QPOST, 6);
            }
            if (!EARLYQ) {
                __syncwarp();
                mbar_arrive_if(bt + B_QKRAW, lane0);
            }
            TR(3, t);
            TA(1, 7);
            if (!QPOST) {
                wgmma_fence();
                mma_qkv_a<SM_WA, 0>(accA, xa, descW);
                wgmma_commit();
            }
            TA(1, 8);
            wgmma_wait<1>();
            reg_fence(accV);
            TA(1, 9);
#pragma unroll
            for (int s = KLO; s < 12; s++) ldsm_x4(xa[s], XADDR(an, s));
            const uint32_t vok = mbar_test(bt + B_VFREE, pt);
            uint32_t vp[24];
#pragma unroll
            for (int j = 0; j < 24; j++) vp[j] = pack_bf16(accV[2 * j], accV[2 * j + 1]);
            reg_fence(vp);
            wgmma_fence();
            mma_qkv_b<SM_WA, KLO>(accA, xa, descW);
            wgmma_commit();
            TA(1, 10);
            mbar_wait_unless(vok, bt + B_VFREE, pt);
#pragma unroll
            for (int p = 0; p < 6; p++)
                stsm_x4(av + (p < 3 ? 2 * p : 2 * p + 1) * GRP, vp[4 * p], vp[4 * p + 1], vp[4 * p + 2], vp[4 * p + 3]);
            stsm_x2(av + 6 * GRP, ones, ones2);
            __syncwarp();
            mbar_arrive_if(bt + B_VRAW, lane0);
            TR(4, t);
            if (MERGEW != 1) wgmma_fence();
            mma_qkv_a<SM_WB, 0>(accB, xa, descW);
            wgmma_commit();
            TA(1, 11);
        }
        TAEND(1);
        wgmma_wait<0>();
        reg_fence(accA);
        reg_fence(accB);
        asm volatile("setmaxnreg.dec.sync.aligned.u32 160;\n");
    } else {
        if (REG_A > 128) asm volatile("setmaxnreg.inc.sync.aligned.u32 %0;\n" :: "n"(REG_A));
        {
            const float c0 = bf16lo(rc), c1 = bf16hi(rc);
            float a0 = 0.f, a1 = 0.f;
#pragma unroll
            for (int u = 0; u < 16; u += 2) {
                const uint32_t p = reinterpret_cast<const uint32_t*>(w1)[u >> 1], q = reinterpret_cast<const uint32_t*>(w1)[8 + (u >> 1)];
                uint32_t h;
                asm("cvt.rn.relu.bf16x2.f32 %0, %1, %2;\n" : "=r"(h) : "f"(c0 * bf16hi(p) + c1 * bf16hi(q)), "f"(c0 * bf16lo(p) + c1 * bf16lo(q)));
                a0 += bf16lo(h) * bf16lo(w2[u]);
                a1 += bf16lo(h) * bf16hi(w2[u]);
                a0 += bf16hi(h) * bf16lo(w2[u + 1]);
                a1 += bf16hi(h) * bf16hi(w2[u + 1]);
            }
            const float s0 = round_bf16(__fdividef(1.f, 1.f + expf(-round_bf16(a0))));
            const float s1 = round_bf16(__fdividef(1.f, 1.f + expf(-round_bf16(a1))));
            if (tid - 128 < 169) sts32(sbase + SM_TAB + (tid - 128) * 4, pack_bf16(exp2f(fmaf(s0, 16.f * LOG2E, -12.f)), exp2f(fmaf(s1, 16.f * LOG2E, -12.f))));
        }
        asm volatile("bar.sync 1, 256;\n" ::: "memory");
        uint32_t eb[26];
        {
            const uint32_t* tab = reinterpret_cast<const uint32_t*>(smem + SM_TAB);
#pragma unroll
            for (int i = 0; i < 13; i++) {
                const uint32_t lo = tab[min(ridx[i < 12 ? 13 * (i & 1) + (i & ~1) : 12], 168u)];
                const uint32_t hi = tab[min(ridx[i < 12 ? 13 * (i & 1) + (i | 1) : 25], 168u)];
                eb[i]      = prmt(lo, hi, 0x5410);
                eb[13 + i] = prmt(lo, hi, 0x7632);
            }
            if (c != 0) eb[12] = eb[25] = 0;
            if (EBZ) {
                const uint32_t k0 = warp * 16 + g < TOK ? ~0u : 0u, k1 = warp < 3 ? ~0u : 0u;
#pragma unroll
                for (int i = 0; i < 26; i++) eb[i] &= i % 13 == 12 ? (k0 & 0xFFFFu) | (k1 & 0xFFFF0000u) : ((i % 13) & 1) ? k1 : k0;
            }
        }
        uint32_t slow = (bf16lo(ls) <= LS_FAST ? 0 : 1) | (bf16hi(ls) <= LS_FAST ? 0 : 2);
        reg_fence(eb);
        if (SLOWH == 2) sts32(bars + B_PROG + 4, slow);
        wg_bar(3 + wg);
        if ((tid & 127) == 0) mbar_arrive(bars + B_VFREE + 16);
        const uint32_t ov0 = warp * 16 + g < TOK, ov1 = warp < 3;
        const uint64_t descK0 = make_desc(sbase + SM_QK, 16, 1024, 1);
        const uint64_t descV0 = make_desc(sbase + SM_V, 128, GRP, 0);
        slow = __shfl_sync(0xffffffffu, slow, 0);
        const uint32_t barw = bars + (wg - 1) * 8;
        const uint64_t descKw = descK0 + (uint64_t)((wg - 1) * (XCH >> 4)), descVw = descV0 + (uint64_t)((wg - 1) * (V_STRIDE >> 4));
        const uint32_t oa = sbase + SM_V + (wg - 1) * V_STRIDE + (warp * 16 + g) * O_PITCH + c * 48;
        uint32_t qok = 0;
        const uint32_t zero = (uint32_t)P.z1;
        auto window = [&](auto IT_, int k) {
            constexpr int IT = decltype(IT_)::value;
            const uint32_t bar = barw + 16 * IT;
            const int tl = (k * TOK + TOK - 1) >> 6, tn = ((k + 2) * TOK + TOK - 1) >> 6;
            const uint32_t bt = bars + (tl & 3) * 8, pt = (tl >> 2) & 1;
            TR(8, k);
            if (k < 2) TP(44 + k);
            float sc0[28], sc1[28];
            TR(10, k);
            TA(2, 0);
            if (NB & 4) nb_sync<256>(NB_QKRAW + 2 * IT - 1 + wg);
            else mbar_wait_unless(qok, bt + B_QKRAW, pt);
            fence_async_smem();
            TR(11, k);
            TA(2, 1);
            if (k == 0) TP(17);
            wgmma_fence();
            mma_qk0<2 * IT * XCH, 2 * IT * XCH>(sc0, descKw, descKw);
            mma_qk1<2 * IT * XCH, 2 * IT * XCH>(sc1, descKw, descKw);
            wgmma_commit();
            TA(2, 2);
            uint32_t vok = PVL || VT ? 0 : mbar_test(bt + B_VRAW, pt);
            uint32_t mflag = 1;
            if (!(XP & 1)) asm volatile("ld.volatile.shared.u8 %0, [%1];\n" : "=r"(mflag) : "r"(sbase + SM_FLAG + k) : "memory");
            wgmma_wait<0>();
            reg_fence(sc0);
            reg_fence(sc1);
            if (NB & 1) nb_arrive<160>(NB_QKFREE - 1 + wg);
            else if (lane == 0) mbar_arrive(bar + B_QKFREE);
            TR(12, k);
            TA(2, 3);
            if (k == 0) TP(18);
            if (mflag != 1) {
              asm volatile(
                "{\n.reg .pred p;\n.reg .u32 n;\nmov.u32 n, 0;\n"
                "WAIT_%=:\n"
                "ld.volatile.shared.u8 %0, [%1];\n"
                "setp.ne.u32 p, %0, 0;\n"
                "@p bra DONE_%=;\n"
                "add.u32 n, n, 1;\n"
                "setp.lt.u32 p, n, 16777216;\n"
                "@p bra WAIT_%=;\n"
                "trap;\n"
                "DONE_%=:\n}\n" : "=r"(mflag) : "r"(sbase + SM_FLAG + k) : "memory");
              if (mflag == 2) {
                uint32_t mk[13];
                __threadfence_block();
                uint32_t u = threadIdx.x, bid = blockIdx.x;
                asm volatile("" : "+r"(u), "+r"(bid));
                const uint32_t r0 = ((u >> 1) & 48) + ((u >> 2) & 7);
                const int pr = bid >> 1, wi = pr < PQ(npair) ? PQ(hw) + pr + k * PQ(npair) : pr - PQ(npair) + k * PQ(nh), wr = wi / NWS;
                const uint32_t mp = sbase + SM_MASK + (((unrot(wr) * NWS + unrot(wi - wr * NWS)) * 2) & 15);
                const uint32_t mr[2] = {mp + row_token(min(r0, TOK - 1u)) * (2 * TOK), mp + row_token(min(r0 + 8, TOK - 1u)) * (2 * TOK)};
                const uint32_t c0 = 2 * row_token(2 * (u & 3));
#pragma unroll
                for (int i = 0; i < 13; i++) {
                    const uint32_t a0 = i < 6 ? mr[i & 1] + c0 + 28 * (i >> 1) : i < 12 ? mr[i & 1] + 2 * row_token(2 * (u & 3) + 8 * (i >> 1)) : mr[0] + 2 * TOK - 2;
                    const uint32_t a1 = i < 6 ? a0 + 2 : i < 12 ? mr[i & 1] + 2 * row_token(2 * (u & 3) + 8 * (i >> 1) + 1) : mr[1] + 2 * TOK - 2;
                    uint32_t lo, hi;
                    asm volatile("ld.shared.u16 %0, [%1];\n" : "=r"(lo) : "r"(a0) : "memory");
                    asm volatile("ld.shared.u16 %0, [%1];\n" : "=r"(hi) : "r"(a1) : "memory");
                    mk[i] = prmt(lo, hi, 0x5410);
                }
                reg_fence(mk);
                __syncwarp();
                if (lane == 0) mbar_arrive(bars + B_MCONS);
                uint32_t m0 = mk[0], m1 = mk[1];
#pragma unroll
                for (int i = 2; i < 12; i += 2) { m0 = hmax2_bf16(m0, mk[i]); m1 = hmax2_bf16(m1, mk[i + 1]); }
                m0 = hmax2_bf16(hmax2_bf16(prmt(m0, m1, 0x5410), prmt(m0, m1, 0x7632)), mk[12]);
                m0 = hmax2_bf16(m0, __shfl_xor_sync(0xffffffffu, m0, 1));
                m0 = hmax2_bf16(m0, __shfl_xor_sync(0xffffffffu, m0, 2));
                const float m[2] = {bf16lo(m0), bf16hi(m0)};
#pragma unroll
                for (int i = 0; i < 13; i++) {
                    const float lo = bf16lo(mk[i]) - m[i & 1], hi = bf16hi(mk[i]) - m[i < 12 ? i & 1 : 1];
                    const int j = i < 12 ? 2 * i + 1 : 26;
                    sc0[2 * i] = fmaf(lo, LOG2E, sc0[2 * i]); sc0[j] = fmaf(hi, LOG2E, sc0[j]);
                    sc1[2 * i] = fmaf(lo, LOG2E, sc1[2 * i]); sc1[j] = fmaf(hi, LOG2E, sc1[j]);
                }
              }
            }
            if (slow) {
                auto shift = [&](float (&S)[28], int h) {
                    float m[2];
#pragma unroll
                    for (int i = 12; i >= 0; i--) {
                        uint32_t e = eb[13 * h + i];
                        asm volatile("" : "+r"(e));
                        const float a = S[2 * i] + lg2_ftz(bf16lo(e)), b = S[i < 12 ? 2 * i + 1 : 26] + lg2_ftz(bf16hi(e));
                        if (i == 12) { m[0] = a; m[1] = b; }
                        else m[i & 1] = fmaxf(m[i & 1], fmaxf(a, b));
                    }
#pragma unroll
                    for (int r = 0; r < 2; r++) {
                        m[r] = fmaxf(m[r], __shfl_xor_sync(0xffffffffu, m[r], 1));
                        m[r] = fmaxf(m[r], __shfl_xor_sync(0xffffffffu, m[r], 2));
                    }
#pragma unroll
                    for (int i = 0; i < 27; i++) S[i] -= m[(i >> 1) & 1];
                };
                uint32_t sl = slow;
                if (SLOWH == 2) asm volatile("ld.volatile.shared.u32 %0, [%1];\n" : "=r"(sl) : "r"(bars + B_PROG + 4) : "memory");
                if (!SLOWH || (sl & 1)) shift(sc0, 0);
                if (!SLOWH || (sl & 2)) shift(sc1, 1);
            }
            auto exps = [&](const float (&S)[28], uint32_t (&e)[13]) {
#pragma unroll
                for (int i = 0; i < 12; i++) e[i] = pack_bf16(ex2_ftz(S[2 * i]), ex2_ftz(S[2 * i + 1]));
                e[12] = hmin2_bf16(pack_bf16(ex2_ftz(S[24]), ex2_ftz(S[26])), 0x7F7F7F7Fu);
            };
            auto probs = [&](const uint32_t (&e)[13], int h, uint32_t (&pa)[4][4]) {
#pragma unroll
                for (int i = 0; i < 12; i++) pa[i >> 2][i & 3] = hmul2_bf16(e[i], eb[13 * h + i]);
                const uint32_t l = hmul2_bf16(e[12], eb[13 * h + 12]);
                pa[3][0] = l & 0xFFFFu;
                pa[3][1] = l >> 16;
                pa[3][2] = 0u; pa[3][3] = 0u;
                reg_fence(pa);
            };
            uint32_t pa0[4][4], pa1[4][4], e[13];
            float o0[28], o1[28];
            TR(13, k);
            TA(2, 10);
            if (k == 0) TP(23);
            exps(sc0, e);
            if (VT) { reg_fence(e); vok = mbar_test(bt + B_VRAW, pt); }
            probs(e, 0, pa0);
            TA(2, 4);
            mbar_wait_unless(vok, bt + B_VRAW, pt);
            fence_async_smem();
            TR(14, k);
            TA(2, 5);
            wgmma_fence();
            mma_pv<2 * IT * V_STRIDE, 0>(o0, pa0, descVw);
            wgmma_commit();
            exps(sc1, e);
            reg_fence(e);
            TA(2, 6);
            wgmma_wait<0>();
            reg_fence(o0);
            TA(2, 7);
            sched_fence_rw(zero, e);
            if (!PVL || PVL == 3) {
                probs(e, 1, pa1);
                wgmma_fence();
            }
            mma_pv<2 * IT * V_STRIDE + 6 * GRP, 0>(o1, pa1, descVw);
            wgmma_commit();
            uint32_t w[24];
            {
                const float il0 = rcp_ftz(o0[24]), il1 = rcp_ftz(o0[26]);
                const uint32_t l0 = pack_bf16(il0, il0), l1 = pack_bf16(il1, il1);
#pragma unroll
                for (int j = 0; j < 12; j++) w[j] = (FM & 2) ? pack_bf16(o0[2 * j] * ((j & 1) ? il1 : il0), o0[2 * j + 1] * ((j & 1) ? il1 : il0)) : hmul2_bf16(pack_bf16(o0[2 * j], o0[2 * j + 1]), (j & 1) ? l1 : l0);
            }
            TA(2, 8);
            wgmma_wait<0>();
            reg_fence(o1);
            TA(2, 9);
            TR(15, k);
            if (k == 0) TP(25);
            wg_bar(3 + wg);
            if (!(NB & 4)) qok = mbar_test(bars + (tn & 3) * 8 + B_QKRAW, (tn >> 2) & 1);
            {
                const float il2 = rcp_ftz(o1[0]), il3 = rcp_ftz(o1[2]);
                const uint32_t l2 = pack_bf16(il2, il2), l3 = pack_bf16(il3, il3);
#pragma unroll
                for (int j = 0; j < 12; j++) w[12 + j] = (FM & 4) ? pack_bf16(o1[2 * j + 4] * ((j & 1) ? il3 : il2), o1[2 * j + 5] * ((j & 1) ? il3 : il2)) : hmul2_bf16(pack_bf16(o1[2 * j + 4], o1[2 * j + 5]), (j & 1) ? l3 : l2);
#pragma unroll
                for (int p = 0; p < 6; p++) {
                    const int j = 8 * (p >> 1) + (p & 1);
                    sts128_if((p & 1) ? ov1 : ov0, oa + 2 * IT * V_STRIDE + (p & 1) * 8 * O_PITCH + (p >> 1) * 16, w[j], w[j + 2], w[j + 4], w[j + 6]);
                }
            }
            if (NB & 2) nb_arrive<160>(NB_ODONE + 2 * IT - 1 + wg);
            else {
                __syncwarp();
                if (lane == 0) mbar_arrive(bar + B_ODONE);
            }
            TR(16, k);
            TA(2, 11);
            if (k < 2) TP(46 + k);
        };
        for (int k = wg - 1;; k += 4) {
            window(std::integral_constant<int, 0>(), k);
            if (k + 2 >= nwin) break;
            window(std::integral_constant<int, 1>(), k + 2);
            if (k + 4 >= nwin) break;
        }
        TAEND(2);
        (void)zero;
        asm volatile("setmaxnreg.inc.sync.aligned.u32 160;\n");
    }

    TR(27, wg);
    if ((tid & 127) == 0) TC(4 + wg);
    if (attn) {
        __syncwarp();
        if (lane == 0) mbar_arrive(sbase + SM_PBAR + 96);
    }
    if (!attn) {
#pragma unroll
        for (int row = tid >> 2; row < 192; row += 96) {
            uint4 w[6];
            const int pr = row % 96, srow = row - pr + (pr % 24) / 12 * 48 + (pr % 12) / 2 * 8 + pr / 24 * 2 + (pr & 1);
#pragma unroll
            for (int a = 0; a < 6; a++) w[a] = *reinterpret_cast<const uint4*>(P.wo + srow * 192 + 32 * a + 8 * c);
            float s = 0.f;
#pragma unroll
            for (int a = 0; a < 6; a++)
                s += ((bf16lo(w[a].x) + bf16hi(w[a].x)) + (bf16lo(w[a].y) + bf16hi(w[a].y))) +
                     ((bf16lo(w[a].z) + bf16hi(w[a].z)) + (bf16lo(w[a].w) + bf16hi(w[a].w)));
            s += __shfl_xor_sync(0xffffffffu, s, 1);
            s += __shfl_xor_sync(0xffffffffu, s, 2);
            s *= (1.f / 192.f);
            const uint32_t d = sbase + SM_WO + row * 64 + ((c ^ ((row >> 1) & 3)) << 4);
#pragma unroll
            for (int a = 0; a < 6; a++)
                sts128(d + a * 12288, pack_bf16(bf16lo(w[a].x) - s, bf16hi(w[a].x) - s), pack_bf16(bf16lo(w[a].y) - s, bf16hi(w[a].y) - s),
                       pack_bf16(bf16lo(w[a].z) - s, bf16hi(w[a].z) - s), pack_bf16(bf16lo(w[a].w) - s, bf16hi(w[a].w) - s));
        }
        fence_async_smem();
        asm volatile("bar.sync 6, 384;\n" ::: "memory");
        if (tid == 0 && (int)blockIdx.x == 2 * (PQ(npair) + PQ(nh))) {
            asm volatile("cp.async.bulk.global.shared::cta.bulk_group [%0], [%1], 73728;\n" :: "l"(g_wo), "r"(sbase + SM_WO) : "memory");
            asm volatile("cp.async.bulk.commit_group;\n" ::: "memory");
            asm volatile("cp.async.bulk.wait_group 0;\n" ::: "memory");
            asm volatile("fence.proxy.async.global;\n" ::: "memory");
            asm volatile("red.release.gpu.global.add.u32 [%0], 1;\n" :: "l"(g_cnt + NWS) : "memory");
        }
        __syncwarp();
    } else if (PQ(t1) < TILES) {
        mbar_wait(sbase + SM_BAR + B_WRAW, 1);
    }
    TR(27, 4 + wg);
    if (tid == 0) TC(2);
    {
        PROJ_SCHEDULE
        uint64_t descW = make_desc(sbase + SM_WO, 12288, 512, 2);
        const uint64_t descA = make_desc(sbase + SM_STAGE + wg * STAGE_BYTES, 16, 1024, 1);
        const uint32_t bar = sbase + SM_PBAR + wg * 8;
        const uint32_t yrel = sbase + SM_STAGE + wg * STAGE_BYTES + (warp * 16 + (lane & 15)) * 128 + (((lane & 7) ^ (lane >> 4)) << 4);
        float acc[96];
#pragma unroll
        for (int i = 0; i < 96; i++) acc[i] = 0.f;
        uint32_t it = 0;
        for (int tile = tile0 + wg * tstep; tile < tend1; tile += 3 * tstep, it++) {
            descW += P.z1;
            mbar_wait_s<(HS & 8) != 0>(bar + (it & 1) * 24, (it >> 1) & 1);
            TR(28, it * 3 + wg);
            if (it > 0 || wg > 0) asm volatile("bar.sync %0, 256;\n" :: "r"(8 + wg) : "memory");
            wgmma_fence();
            mma_proj<0, 0>(acc, descA + (uint64_t)((it & 1) * (3 * STAGE_BYTES >> 4)), descW);
            wgmma_commit();
            if (tile + tstep < tend1) asm volatile("bar.arrive %0, 256;\n" :: "r"(wg == 2 ? 8 : 9 + wg) : "memory");
            wgmma_wait<0>();
            reg_fence(acc);
            float a[4];
#pragma unroll
            for (int i = 0; i < 4; i++) a[i] = acc[i] * acc[i];
#pragma unroll
            for (int j = 1; j < 24; j++)
#pragma unroll
                for (int i = 0; i < 4; i++) a[i] = fmaf(acc[4 * j + i], acc[4 * j + i], a[i]);
            float s0 = a[0] + a[1], s1 = a[2] + a[3];
            s0 += __shfl_xor_sync(0xffffffffu, s0, 1);
            s1 += __shfl_xor_sync(0xffffffffu, s1, 1);
            s0 += __shfl_xor_sync(0xffffffffu, s0, 2);
            s1 += __shfl_xor_sync(0xffffffffu, s1, 2);
            const float rs0 = rsqrt_ftz(fmaf(s0, 1.f / 192.f, 1e-5f));
            const float rs1 = rsqrt_ftz(fmaf(s1, 1.f / 192.f, 1e-5f));
            const uint32_t ya = yrel + (it & 1) * 3 * STAGE_BYTES;
#pragma unroll
            for (int p = 0; p < 12; p++)
                stsm_x4((ya ^ (32 * (p & 3))) + (p >> 2) * 8192,
                        pack_bf16(acc[8 * p] * rs0, acc[8 * p + 1] * rs0), pack_bf16(acc[8 * p + 2] * rs1, acc[8 * p + 3] * rs1),
                        pack_bf16(acc[8 * p + 4] * rs0, acc[8 * p + 5] * rs0), pack_bf16(acc[8 * p + 6] * rs1, acc[8 * p + 7] * rs1));
            __syncwarp();
            if (lane == 0) mbar_arrive(bar + 104 + (it & 1) * 24);
            TR(29, it * 3 + wg);
        }
#pragma unroll 1
        for (int j = nl + 1 - COOP; COOP && at && j <= nl; j++) {
            float d[32];
            const uint32_t stage = sbase + SM_STAGE + j * STAGE_BYTES;
            mbar_wait(sbase + SM_PBAR + j * 8, 0);
            wgmma_fence();
            mma_proj64<0, 0>(d, make_desc(stage, 16, 1024, 1), descW + (uint64_t)(wg * (2 * 12288 >> 4)));
            wgmma_commit();
            wgmma_wait<0>();
            reg_fence(d);
            float a[4];
#pragma unroll
            for (int i = 0; i < 4; i++) a[i] = d[i] * d[i];
#pragma unroll
            for (int j = 1; j < 8; j++)
#pragma unroll
                for (int i = 0; i < 4; i++) a[i] = fmaf(d[4 * j + i], d[4 * j + i], a[i]);
            const uint32_t sa = sbase + SM_MASK - (j & 1) * 3072 + (warp * 16 + g) * 48;
            sts32(sa + wg * 16 + c * 4, __float_as_uint(a[0] + a[1]));
            sts32(sa + wg * 16 + c * 4 + 8 * 48, __float_as_uint(a[2] + a[3]));
            nb_sync<384>(15);
            float rs[2];
#pragma unroll
            for (int r = 0; r < 2; r++) {
                float v[12];
#pragma unroll
                for (int i = 0; i < 3; i++)
                    asm volatile("ld.shared.v4.f32 {%0, %1, %2, %3}, [%4];\n" : "=f"(v[4 * i]), "=f"(v[4 * i + 1]), "=f"(v[4 * i + 2]), "=f"(v[4 * i + 3])
                                 : "r"(sa + r * 8 * 48 + i * 16) : "memory");
                const float s = ((v[0] + v[1]) + (v[2] + v[3])) + ((v[4] + v[5]) + (v[6] + v[7])) + ((v[8] + v[9]) + (v[10] + v[11]));
                rs[r] = rsqrt_ftz(fmaf(s, 1.f / 192.f, 1e-5f));
            }
            const uint32_t ya = stage + wg * 8192 + (warp * 16 + (lane & 15)) * 128 + (((lane & 7) ^ (lane >> 4)) << 4);
#pragma unroll
            for (int p = 0; p < 4; p++)
                stsm_x4(ya ^ (32 * p),
                        pack_bf16(d[8 * p] * rs[0], d[8 * p + 1] * rs[0]), pack_bf16(d[8 * p + 2] * rs[1], d[8 * p + 3] * rs[1]),
                        pack_bf16(d[8 * p + 4] * rs[0], d[8 * p + 5] * rs[0]), pack_bf16(d[8 * p + 6] * rs[1], d[8 * p + 7] * rs[1]));
            fence_async_smem();
            wg_bar(12 + wg);
            if (warp == 0 && elect_one()) {
                asm volatile("cp.async.bulk.tensor.2d.global.shared::cta.tile.bulk_group.L2::cache_hint [%0, {%2, %3}], [%1], %4;\n"
                             :: "l"(reinterpret_cast<uint64_t>(&omapb)), "r"(stage + wg * 8192), "r"(wg * 64), "r"(64 * (tile0 + j * tstep - TILES_A)),
                                "l"(EVICT_FIRST) : "memory");
                asm volatile("cp.async.bulk.commit_group;\n" ::: "memory");
                if (j == nl) {
                    if (ENDR) asm volatile("cp.async.bulk.wait_group.read 0;\n" ::: "memory");
                    else asm volatile("cp.async.bulk.wait_group 0;\n" ::: "memory");
                }
                if (wg == 0) TC(1);
            }
        }
    }
}

}

typedef CUresult (*PFN_encodeTiled)(CUtensorMap*, CUtensorMapDataType, cuuint32_t, void*, const cuuint64_t*,
                                    const cuuint64_t*, const cuuint32_t*, const cuuint32_t*, CUtensorMapInterleave,
                                    CUtensorMapSwizzle, CUtensorMapL2promotion, CUtensorMapFloatOOBfill);

extern "C" void kernel_launch(void* const* d_in, const int* in_sizes, int n_in, void* d_out, int out_size) {
    swin::Params P;
    P.x           = (const __nv_bfloat16*)d_in[0];
    P.wqkv        = (const __nv_bfloat16*)d_in[1];
    P.wo          = (const __nv_bfloat16*)d_in[2];
    P.logit_scale = (const __nv_bfloat16*)d_in[3];
    P.cpb_w1      = (const __nv_bfloat16*)d_in[4];
    P.cpb_w2      = (const __nv_bfloat16*)d_in[5];
    P.rel_coords  = (const __nv_bfloat16*)d_in[6];
    P.rel_idx     = (const int*)d_in[7];
    P.mask        = (const __nv_bfloat16*)d_in[8];
    P.out         = (__nv_bfloat16*)d_out;
    P.z1 = 0;
    static PFN_encodeTiled encode = nullptr;
    if (!encode) {
        cudaFuncSetAttribute(swin::swin_window_attn_kernel, cudaFuncAttributeMaxDynamicSharedMemorySize, swin::SM_TOTAL);
        cudaDriverEntryPointQueryResult qr;
        cudaGetDriverEntryPoint("cuTensorMapEncodeTiled", (void**)&encode, cudaEnableDefault, &qr);
    }
    swin::Maps M;
    const cuuint32_t estr[4] = {1, 1, 1, 1};
    auto make = [&](CUtensorMap* m, const void* base, int rank, const cuuint64_t* gdim, const cuuint64_t* gstr,
                    const cuuint32_t* box, CUtensorMapSwizzle swz = CU_TENSOR_MAP_SWIZZLE_128B) {
        CUresult r = encode(m, CU_TENSOR_MAP_DATA_TYPE_BFLOAT16, rank, const_cast<void*>(base), gdim, gstr, box, estr,
               CU_TENSOR_MAP_INTERLEAVE_NONE, swz, CU_TENSOR_MAP_L2_PROMOTION_L2_128B,
               CU_TENSOR_MAP_FLOAT_OOB_FILL_NONE);
        (void)r;
    };
    {
        const cuuint64_t gdim[3] = {192, swin::IMG, swin::IMG}, gstr[2] = {384, swin::IMG * 384};
        const cuuint32_t box[7][3] = {{64, 7, 7}, {64, 4, 7}, {64, 3, 7}, {64, 4, 4}, {64, 4, 3}, {64, 3, 4}, {64, 3, 3}};
        for (int i = 0; i < 7; i++) make(&M.x77 + i, P.x, 3, gdim, gstr, box[i]);
        const cuuint32_t boxp[3] = {192, 7, 7};
        if (PF1) make(&M.x77, P.x, 3, gdim, gstr, boxp, CU_TENSOR_MAP_SWIZZLE_NONE);
    }
    {
        const cuuint64_t gdim[2] = {192, (cuuint64_t)swin::NPIX}, gstr[1] = {384};
        const cuuint32_t box64[2] = {64, 64};
        make(&M.o, d_out, 2, gdim, gstr, box64);
        const cuuint64_t gdimb[2] = {192, (cuuint64_t)swin::SEG_B};
        make(&M.ob, d_out, 2, gdimb, gstr, box64);
    }
    {
        const cuuint64_t gdim[3] = {V64 ? 32 : 16, 192, V64 ? 18 : 36}, gstr[2] = {1152, V64 ? 64 : 32};
        const cuuint32_t box[3] = {V64 ? 32 : 16, 192, V64 ? 3 : 6};
        make(&M.w, P.wqkv, 3, gdim, gstr, box, V64 ? CU_TENSOR_MAP_SWIZZLE_64B : CU_TENSOR_MAP_SWIZZLE_32B);
        const cuuint64_t gdim3[3] = {192, 192, 3}, gstr3[2] = {1152, 384};
        const cuuint32_t box64[3] = {64, 64, 2}, box32[3] = {32, 64, 2};
        make(&M.w64, P.wqkv, 3, gdim3, gstr3, box64);
        make(&M.w32, P.wqkv, 3, gdim3, gstr3, box32, CU_TENSOR_MAP_SWIZZLE_64B);
    }
    {
        const cuuint64_t gdim[4] = {96, 2, swin::IMG, swin::IMG}, gstr[3] = {192, 384, swin::IMG * 384};
        const cuuint32_t box[4][4] = {{96, 1, 4, 7}, {96, 1, 3, 7}, {96, 1, 4, 3}, {96, 1, 3, 3}};
        for (int i = 0; i < 4; i++) make(&M.s47 + i, d_out, 4, gdim, gstr, box[i], CU_TENSOR_MAP_SWIZZLE_NONE);
    }
    swin::swin_window_attn_kernel<<<132, swin::NTHREADS, swin::SM_TOTAL>>>(P, M);
}
```

```cpp
#include <cuda_runtime.h>
#include <cuda.h>
#include <cuda_bf16.h>
#include <stdint.h>
#include <type_traits>

namespace swin {
#define STR_(x) #x
#define STR(x) STR_(x)
#define HINT ""

#define NPAIR 53
#define PF_DIST 2
#define QSPLIT 4
#define CLUSTER 0
#define NOPF 0
#define NTAIL 318
#define PSTORE 1
#define PORDER 1
#define GORD 0
#define GF1 1
#define MERGEW 0
#define MWAIT 0
#define PSLEEP 200
#define CH 5
#define NB 1
#define SCM 0
#define MPF 2
#define MLEAD 4
#define PFM 0
#define PFK 4
#define XP 0
#define KLO 6
#define VPOS 1
#define XSPLIT 1
#define SEQ 1
#define PREL 0
#define PEXP 0
#define PFD 0
#define PFW 1
#define WVK -4
#define WSEQ 1
#define PF1 1
#define WFIRST 1
#define MPRE 1
#define SLOWH 2
#define LS_FAST 4.f
#define ENDR 1
#define EBZ 1
#define HSQ 0
#define AFENCE 0
#define FM 0
#define QPOST 0
#define EARLYQ 0
#define KL 4
#define VB1 4
#define VA0 1
#define K1 3
#define Q1 2
#define RWF 3
#define PUBM 2
#define NH 12
#define HW 29
#define HDEL 0
#define CONSTQ 1
#define V64 1
#define M01 2
#define PPAR 1
#define EPF 0
#define EPW 1
#define HS 0
#define MP2 1
#define SDEF 1
#define EXH 2
#define EXD 1
#define STH 200
#define STP 100
#define LDE 0
#define MD 0
#define COOP 0
#define PVL 0
#define VT 1
#define SDV 0
#define WROT 0
#define WVW 0
#define PSL2 64
#define SELFP 0
#define CHK 1
#define CHKS 100
#define LOOKA 1
#define VLATE 0
#define LOOKE 1
#define LAZY 0
#define CHKB 0
#define QT 0
#define SDN 0
#define XPOS 4
#define PBE 70
#define WFEN 1
#define REG_G 224
#define REG_A 128
#define REG_H 32
constexpr int IMG      = 511;
constexpr int NWS      = 73;
constexpr int NWINDOWS = NWS * NWS;
constexpr int TOK      = 49;
constexpr int NPIX     = IMG * IMG;
constexpr int NTHREADS = 512;

constexpr int W_ATOM = 6144;
constexpr int SM_WA = 0, SM_WB = 6 * 2048, SM_WV = 12 * W_ATOM, D_WV = SM_WV + ((W_ATOM - 2048) << 16);
constexpr int GRP   = TOK * 16;
constexpr int XCH   = TOK * 128;
constexpr int SM_V  = 18 * W_ATOM, V_STRIDE = 10240, O_PITCH = 192;
constexpr int SM_QK = SM_V + 4 * V_STRIDE, QK_CHUNK = 4 * XCH;
constexpr int SM_MASK = SM_QK + 3 * QK_CHUNK;
constexpr int SM_TAB  = SM_V + 3 * V_STRIDE + 256;
constexpr int SM_BAR  = SM_MASK + 4816;
constexpr int B_XFULL = 0, B_WRAW = 32, B_QKRAW = 64, B_QKFREE = 96, B_VFREE = 128, B_ODONE = 160,
              B_PROG = 192, B_VRAW = 224, B_MFULL = 256, B_MCONS = 272, B_WFULL = 280, B_STORED = 288, B_PUBD = 304;
constexpr int SM_FLAG = SM_BAR + 320;
constexpr int SM_A_END = SM_FLAG + 128;
static_assert(SM_QK % 1024 == 0 && 13 * GRP <= V_STRIDE && V_STRIDE % 128 == 0, "layout");
constexpr int SM_WO    = 0;
constexpr int SM_STAGE = 73728;
constexpr int STAGE_BYTES = 24576;
constexpr int SM_PBAR  = SM_A_END;
#define TA(role, idx)
#define TAEND(role)
constexpr int SM_TOTAL = SM_PBAR + 152;
#define TP(idx)
static_assert(SM_STAGE + 6 * STAGE_BYTES <= SM_BAR, "smem");
static_assert(SM_TOTAL <= 232448, "smem");
static_assert(SM_STAGE + 6 * STAGE_BYTES + 3072 <= SM_MASK && NTAIL >= 2 * NPAIR * (COOP + 1) && NTAIL <= 12 * NPAIR, "shared tiles");
static_assert(SM_BAR % 8 == 0 && NWINDOWS / NPAIR < 123, "barrier alignment, flags");

constexpr int SEG_B   = (IMG - 4) * IMG;
constexpr int TILES_A = (NPIX - SEG_B + 63) / 64;
constexpr int TILES   = TILES_A + (SEG_B + 63) / 64;
constexpr uint32_t ROW_DONE = NWS * 2;

__device__ uint32_t g_cnt[NWS + 7];
__device__ __align__(128) uint8_t g_wo[73728];
__device__ uint32_t g_flag[66 * 128];
__device__ uint32_t g_done;

#define TR(ev, idx)
#define TC(slot)
#define TS(i)
#define TRH(ev, idx)
constexpr float LOG2E = 1.4426950408889634f;
__device__ __forceinline__ int clock32() { int c; asm volatile("mov.u32 %0, %%clock;" : "=r"(c) :: "memory"); return c; }

__device__ __forceinline__ uint32_t smem_u32(const void* p) {
    return (uint32_t)__cvta_generic_to_shared(p);
}
__device__ __forceinline__ uint64_t make_desc(uint32_t saddr, uint32_t lbo, uint32_t sbo, uint32_t swz = 0) {
    return (uint64_t)((saddr & 0x3FFFF) >> 4) | ((uint64_t)(lbo >> 4) << 16) | ((uint64_t)(sbo >> 4) << 32) |
           ((uint64_t)swz << 62);
}
__host__ __device__ constexpr uint64_t make_desc_c(uint32_t saddr, uint32_t lbo, uint32_t sbo, uint32_t swz) {
    return (uint64_t)(saddr >> 4) | ((uint64_t)(lbo >> 4) << 16) | ((uint64_t)(sbo >> 4) << 32) | ((uint64_t)swz << 62);
}
constexpr uint64_t D_WV64 = make_desc_c(SM_WV, 12288, 512, 2) - make_desc_c(0, 2048, 256, 3);
__device__ __forceinline__ void wgmma_fence()  { asm volatile("wgmma.fence.sync.aligned;\n" ::: "memory"); }
__device__ __forceinline__ void wgmma_commit() { asm volatile("wgmma.commit_group.sync.aligned;\n" ::: "memory"); }
template <int N> __device__ __forceinline__ void wgmma_wait() {
    asm volatile("wgmma.wait_group.sync.aligned %0;\n" :: "n"(N) : "memory");
}
__device__ __forceinline__ void fence_async_smem() { asm volatile("fence.proxy.async.shared::cta;\n" ::: "memory"); }
template <int N> __device__ __forceinline__ void nb_sync(int id) { asm volatile("bar.sync %0, %1;\n" :: "r"(id), "n"(N) : "memory"); }
template <int N> __device__ __forceinline__ void nb_arrive(int id) { asm volatile("bar.arrive %0, %1;\n" :: "r"(id), "n"(N) : "memory"); }
constexpr int NB_ODONE = 0, NB_QKFREE = 6, NB_QKRAW = 12;
__device__ __forceinline__ void wg_bar(int id) { asm volatile("bar.sync %0, 128;\n" :: "r"(id) : "memory"); }

template <int N> __device__ __forceinline__ void reg_fence(float (&v)[N]) {
#pragma unroll
    for (int i = 0; i < N; i++) asm volatile("" : "+f"(v[i]) :: "memory");
}
template <int N> __device__ __forceinline__ void reg_fence(uint32_t (&v)[N]) {
#pragma unroll
    for (int i = 0; i < N; i++) asm volatile("" : "+r"(v[i]) :: "memory");
}
template <int N, int M> __device__ __forceinline__ void reg_fence(uint32_t (&v)[N][M]) {
#pragma unroll
    for (int i = 0; i < N; i++) reg_fence(v[i]);
}

__device__ __forceinline__ uint32_t pack_bf16(float lo, float hi) {
    uint32_t r;
    asm("cvt.rn.bf16x2.f32 %0, %1, %2;\n" : "=r"(r) : "f"(hi), "f"(lo));
    return r;
}
__device__ __forceinline__ float bf16lo(uint32_t v) { return __uint_as_float(v << 16); }
__device__ __forceinline__ float bf16hi(uint32_t v) { return __uint_as_float(v & 0xFFFF0000u); }
__device__ __forceinline__ uint32_t hadd2_bf16(uint32_t a, uint32_t b) {
    uint32_t r;
    asm("add.rn.bf16x2 %0, %1, %2;\n" : "=r"(r) : "r"(a), "r"(b));
    return r;
}
__device__ __forceinline__ uint32_t hmul2_bf16(uint32_t a, uint32_t b) {
    uint32_t r;
    asm("mul.rn.bf16x2 %0, %1, %2;\n" : "=r"(r) : "r"(a), "r"(b));
    return r;
}
__device__ __forceinline__ uint32_t hsub2_bf16(uint32_t a, uint32_t b) {
    uint32_t r;
    asm("sub.rn.bf16x2 %0, %1, %2;\n" : "=r"(r) : "r"(a), "r"(b));
    return r;
}
__device__ __forceinline__ uint32_t hfma2_bf16(uint32_t a, uint32_t b, uint32_t c) {
    uint32_t r;
    asm("fma.rn.bf16x2 %0, %1, %2, %3;\n" : "=r"(r) : "r"(a), "r"(b), "r"(c));
    return r;
}
__device__ __forceinline__ uint32_t hmax2_bf16(uint32_t a, uint32_t b) {
    uint32_t r;
    asm("max.bf16x2 %0, %1, %2;\n" : "=r"(r) : "r"(a), "r"(b));
    return r;
}
__device__ __forceinline__ uint32_t hmin2_bf16(uint32_t a, uint32_t b) {
    uint32_t r;
    asm("min.bf16x2 %0, %1, %2;\n" : "=r"(r) : "r"(a), "r"(b));
    return r;
}
__device__ __forceinline__ uint32_t ex2_bf16x2(uint32_t a) {
    uint32_t r;
    asm("ex2.approx.ftz.bf16x2 %0, %1;\n" : "=r"(r) : "r"(a));
    return r;
}
__device__ __forceinline__ uint32_t ex2_bf16lo(uint32_t a) {
    uint32_t r;
    asm("{\n.reg .b16 l, h;\nmov.b32 {l, h}, %1;\nex2.approx.ftz.bf16 l, l;\ncvt.u32.u16 %0, l;\n}\n" : "=r"(r) : "r"(a));
    return r;
}
__device__ __forceinline__ uint32_t mbar_test(uint32_t bar, uint32_t parity) {
    uint32_t ok;
    asm volatile("{\n.reg .pred p;\nmbarrier.test_wait.parity.shared::cta.b64 p, [%1], %2;\nselp.u32 %0, 1, 0, p;\n}\n"
                 : "=r"(ok) : "r"(bar), "r"(parity) : "memory");
    return ok;
}
__device__ __forceinline__ uint32_t prmt(uint32_t a, uint32_t b, uint32_t sel) {
    uint32_t r;
    asm("prmt.b32 %0, %1, %2, %3;\n" : "=r"(r) : "r"(a), "r"(b), "r"(sel));
    return r;
}
__device__ __forceinline__ float round_bf16(float x) { return __bfloat162float(__float2bfloat16_rn(x)); }

__device__ __forceinline__ void mbar_init(uint32_t bar, uint32_t count) {
    asm volatile("mbarrier.init.shared::cta.b64 [%0], %1;\n" :: "r"(bar), "r"(count) : "memory");
}
__device__ __forceinline__ void mbar_wait(uint32_t bar, uint32_t parity) {
    asm volatile(
        "{\n"
        ".reg .pred p;\n"
        ".reg .u32 n;\n"
        "mov.u32 n, 0;\n"
        "WAIT_%=:\n"
        "mbarrier.try_wait.parity.shared::cta.b64 p, [%0], %1" HINT ";\n"
        "@p bra DONE_%=;\n"
        "add.u32 n, n, 1;\n"
        "setp.lt.u32 p, n, 4194304;\n"
        "@p bra WAIT_%=;\n"
        "trap;\n"
        "DONE_%=:\n"
        "}\n" :: "r"(bar), "r"(parity) : "memory");
}
template <bool S> __device__ __forceinline__ void mbar_wait_s(uint32_t bar, uint32_t parity) {
    if (!S) mbar_wait(bar, parity);
    else asm volatile(
        "{\n"
        ".reg .pred p;\n"
        ".reg .u32 n;\n"
        "mov.u32 n, 0;\n"
        "WAIT_%=:\n"
        "mbarrier.try_wait.parity.shared::cta.b64 p, [%0], %1, 4000;\n"
        "@p bra DONE_%=;\n"
        "add.u32 n, n, 1;\n"
        "setp.lt.u32 p, n, 262144;\n"
        "@p bra WAIT_%=;\n"
        "trap;\n"
        "DONE_%=:\n"
        "}\n" :: "r"(bar), "r"(parity) : "memory");
}
__device__ __forceinline__ void mbar_wait4(uint32_t b0, uint32_t p0, uint32_t b1, uint32_t p1, uint32_t b2, uint32_t p2,
                                           uint32_t b3, uint32_t p3) {
    asm volatile(
        "{\n"
        ".reg .pred p, q, r, s;\n"
        ".reg .u32 n;\n"
        "mov.u32 n, 0;\n"
        "WAIT_%=:\n"
        "mbarrier.try_wait.parity.shared::cta.b64 p, [%0], %1" HINT ";\n"
        "mbarrier.try_wait.parity.shared::cta.b64 q, [%2], %3" HINT ";\n"
        "mbarrier.try_wait.parity.shared::cta.b64 r, [%4], %5" HINT ";\n"
        "mbarrier.try_wait.parity.shared::cta.b64 s, [%6], %7" HINT ";\n"
        "and.pred p, p, q;\n"
        "and.pred r, r, s;\n"
        "and.pred p, p, r;\n"
        "@p bra DONE_%=;\n"
        "add.u32 n, n, 1;\n"
        "setp.lt.u32 p, n, 4194304;\n"
        "@p bra WAIT_%=;\n"
        "trap;\n"
        "DONE_%=:\n"
        "}\n" :: "r"(b0), "r"(p0), "r"(b1), "r"(p1), "r"(b2), "r"(p2), "r"(b3), "r"(p3) : "memory");
}
__device__ __forceinline__ void mbar_wait2(uint32_t b0, uint32_t p0, uint32_t b1, uint32_t p1) {
    asm volatile(
        "{\n"
        ".reg .pred p, q;\n"
        ".reg .u32 n;\n"
        "mov.u32 n, 0;\n"
        "WAIT_%=:\n"
        "mbarrier.try_wait.parity.shared::cta.b64 p, [%0], %1" HINT ";\n"
        "mbarrier.try_wait.parity.shared::cta.b64 q, [%2], %3" HINT ";\n"
        "and.pred p, p, q;\n"
        "@p bra DONE_%=;\n"
        "add.u32 n, n, 1;\n"
        "setp.lt.u32 p, n, 4194304;\n"
        "@p bra WAIT_%=;\n"
        "trap;\n"
        "DONE_%=:\n"
        "}\n" :: "r"(b0), "r"(p0), "r"(b1), "r"(p1) : "memory");
}
#define HINTA ""
__device__ __forceinline__ void mbar_wait_unless(uint32_t ok, uint32_t bar, uint32_t parity) {
    asm volatile(
        "{\n"
        ".reg .pred p;\n"
        ".reg .u32 n;\n"
        "setp.ne.u32 p, %2, 0;\n"
        "vote.sync.all.pred p, p, 0xffffffff;\n"
        "@p bra DONE_%=;\n"
        "mov.u32 n, 0;\n"
        "WAIT_%=:\n"
        "mbarrier.try_wait.parity.shared::cta.b64 p, [%0], %1" HINTA ";\n"
        "@p bra DONE_%=;\n"
        "add.u32 n, n, 1;\n"
        "setp.lt.u32 p, n, 4194304;\n"
        "@p bra WAIT_%=;\n"
        "trap;\n"
        "DONE_%=:\n"
        "}\n" :: "r"(bar), "r"(parity), "r"(ok) : "memory");
}
__device__ __forceinline__ void mbar_wait2_unless(uint32_t ok, uint32_t b0, uint32_t p0, uint32_t b1, uint32_t p1) {
    asm volatile(
        "{\n"
        ".reg .pred p, q;\n"
        ".reg .u32 n;\n"
        "setp.ne.u32 p, %4, 0;\n"
        "vote.sync.all.pred p, p, 0xffffffff;\n"
        "@p bra DONE_%=;\n"
        "mov.u32 n, 0;\n"
        "WAIT_%=:\n"
        "mbarrier.try_wait.parity.shared::cta.b64 p, [%0], %1" HINT ";\n"
        "mbarrier.try_wait.parity.shared::cta.b64 q, [%2], %3" HINT ";\n"
        "and.pred p, p, q;\n"
        "@p bra DONE_%=;\n"
        "add.u32 n, n, 1;\n"
        "setp.lt.u32 p, n, 4194304;\n"
        "@p bra WAIT_%=;\n"
        "trap;\n"
        "DONE_%=:\n"
        "}\n" :: "r"(b0), "r"(p0), "r"(b1), "r"(p1), "r"(ok) : "memory");
}
__device__ __forceinline__ void mbar_wait4_unless(uint32_t ok, uint32_t b0, uint32_t p0, uint32_t b1, uint32_t p1, uint32_t b2,
                                                  uint32_t p2, uint32_t b3, uint32_t p3) {
    asm volatile(
        "{\n"
        ".reg .pred p, q, r, s;\n"
        ".reg .u32 n;\n"
        "setp.ne.u32 p, %8, 0;\n"
        "vote.sync.all.pred p, p, 0xffffffff;\n"
        "@p bra DONE_%=;\n"
        "mov.u32 n, 0;\n"
        "WAIT_%=:\n"
        "mbarrier.try_wait.parity.shared::cta.b64 p, [%0], %1" HINT ";\n"
        "mbarrier.try_wait.parity.shared::cta.b64 q, [%2], %3" HINT ";\n"
        "mbarrier.try_wait.parity.shared::cta.b64 r, [%4], %5" HINT ";\n"
        "mbarrier.try_wait.parity.shared::cta.b64 s, [%6], %7" HINT ";\n"
        "and.pred p, p, q;\n"
        "and.pred r, r, s;\n"
        "and.pred p, p, r;\n"
        "@p bra DONE_%=;\n"
        "add.u32 n, n, 1;\n"
        "setp.lt.u32 p, n, 4194304;\n"
        "@p bra WAIT_%=;\n"
        "trap;\n"
        "DONE_%=:\n"
        "}\n" :: "r"(b0), "r"(p0), "r"(b1), "r"(p1), "r"(b2), "r"(p2), "r"(b3), "r"(p3), "r"(ok) : "memory");
}
__device__ __forceinline__ void sched_fence(uint32_t zero, uint32_t a, uint32_t b, uint32_t c, uint32_t d, uint32_t e = 0,
                                            uint32_t f = 0, uint32_t g = 0, uint32_t h = 0, uint32_t i = 0, uint32_t j = 0,
                                            uint32_t k = 0) {
    asm volatile("{\n.reg .pred p;\n.reg .u32 n;\nsetp.eq.u32 p, %0, 0;\n@p bra.uni DONE_%=;\nmov.u32 n, %0;\nSPIN_%=:\n"
                 "nanosleep.u32 %1;\nnanosleep.u32 %2;\nnanosleep.u32 %3;\nnanosleep.u32 %4;\nnanosleep.u32 %5;\n"
                 "nanosleep.u32 %6;\nnanosleep.u32 %7;\nnanosleep.u32 %8;\nnanosleep.u32 %9;\nnanosleep.u32 %10;\n"
                 "nanosleep.u32 %11;\nsub.u32 n, n, 1;\nsetp.ne.u32 p, n, 0;\n@p bra.uni SPIN_%=;\nDONE_%=:\n}\n"
                 :: "r"(zero), "r"(a), "r"(b), "r"(c), "r"(d), "r"(e), "r"(f), "r"(g), "r"(h), "r"(i), "r"(j), "r"(k) : "memory");
}
__device__ __forceinline__ void sched_fence2(uint32_t zero, float& x, float& y, uint32_t a, uint32_t b, uint32_t c, uint32_t d = 0,
                                             uint32_t e = 0, uint32_t f = 0) {
    asm volatile("{\n.reg .pred p;\n.reg .u32 n;\nsetp.eq.u32 p, %2, 0;\n@p bra.uni DONE_%=;\nmov.u32 n, %2;\nSPIN_%=:\n"
                 "add.f32 %0, %0, %1;\nadd.f32 %1, %1, %0;\nnanosleep.u32 %3;\nnanosleep.u32 %4;\nnanosleep.u32 %5;\n"
                 "nanosleep.u32 %6;\nnanosleep.u32 %7;\nnanosleep.u32 %8;\n"
                 "sub.u32 n, n, 1;\nsetp.ne.u32 p, n, 0;\n@p bra.uni SPIN_%=;\nDONE_%=:\n}\n"
                 : "+f"(x), "+f"(y) : "r"(zero), "r"(a), "r"(b), "r"(c), "r"(d), "r"(e), "r"(f) : "memory");
}
template <int N> __device__ __forceinline__ void use_regs(const uint32_t* v) {
    if constexpr (N >= 4) {
        asm volatile("nanosleep.u32 %0;\nnanosleep.u32 %1;\nnanosleep.u32 %2;\nnanosleep.u32 %3;\n" :: "r"(v[0]), "r"(v[1]), "r"(v[2]), "r"(v[3]) : "memory");
        use_regs<N - 4>(v + 4);
    } else if constexpr (N > 0) {
        asm volatile("nanosleep.u32 %0;\n" :: "r"(v[0]) : "memory");
        use_regs<N - 1>(v + 1);
    }
}
template <int N> __device__ __forceinline__ void sched_fence_n(uint32_t zero, const uint32_t (&v)[N]) {
    if (__builtin_expect(zero != 0, 0)) {
#pragma unroll 1
        for (uint32_t n = zero; n; n--) use_regs<N>(v);
    }
}
__device__ __forceinline__ void sched_fence_rw(uint32_t zero, uint32_t (&v)[13]) {
    asm volatile("{\n.reg .pred p;\n.reg .u32 n;\nsetp.eq.u32 p, %13, 0;\n@p bra.uni DONE_%=;\nmov.u32 n, %13;\nSPIN_%=:\n"
                 "add.u32 %0, %0, %1;\nadd.u32 %1, %1, %2;\nadd.u32 %2, %2, %3;\nadd.u32 %3, %3, %4;\nadd.u32 %4, %4, %5;\n"
                 "add.u32 %5, %5, %6;\nadd.u32 %6, %6, %7;\nadd.u32 %7, %7, %8;\nadd.u32 %8, %8, %9;\nadd.u32 %9, %9, %10;\n"
                 "add.u32 %10, %10, %11;\nadd.u32 %11, %11, %12;\nadd.u32 %12, %12, %0;\n"
                 "sub.u32 n, n, 1;\nsetp.ne.u32 p, n, 0;\n@p bra.uni SPIN_%=;\nDONE_%=:\n}\n"
                 : "+r"(v[0]), "+r"(v[1]), "+r"(v[2]), "+r"(v[3]), "+r"(v[4]), "+r"(v[5]), "+r"(v[6]), "+r"(v[7]), "+r"(v[8]),
                   "+r"(v[9]), "+r"(v[10]), "+r"(v[11]), "+r"(v[12]) : "r"(zero) : "memory");
}
__device__ __forceinline__ void mbar_arrive(uint32_t bar) {
    asm volatile("mbarrier.arrive.shared::cta.b64 _, [%0];\n" :: "r"(bar) : "memory");
}
__device__ __forceinline__ void mbar_arrive_n(uint32_t bar, uint32_t n) {
    asm volatile("mbarrier.arrive.shared::cta.b64 _, [%0], %1;\n" :: "r"(bar), "r"(n) : "memory");
}
__device__ __forceinline__ void mbar_arrive_expect_tx(uint32_t bar, uint32_t bytes) {
    asm volatile("mbarrier.arrive.expect_tx.shared::cta.b64 _, [%0], %1;\n" :: "r"(bar), "r"(bytes) : "memory");
}
__device__ __forceinline__ void stg128_if(bool p, void* addr, uint32_t x, uint32_t y, uint32_t z, uint32_t w) {
    asm volatile("{\n.reg .pred q;\nsetp.ne.b32 q, %5, 0;\n@q st.global.L1::no_allocate.v4.b32 [%0], {%1, %2, %3, %4};\n}\n"
                 :: "l"(addr), "r"(x), "r"(y), "r"(z), "r"(w), "r"((uint32_t)p) : "memory");
}
__device__ __forceinline__ void stsm_x4(uint32_t addr, uint32_t r0, uint32_t r1, uint32_t r2, uint32_t r3) {
    asm volatile("stmatrix.sync.aligned.m8n8.x4.shared.b16 [%0], {%1, %2, %3, %4};\n"
                 :: "r"(addr), "r"(r0), "r"(r1), "r"(r2), "r"(r3) : "memory");
}
__device__ __forceinline__ void stsm_x2(uint32_t addr, uint32_t r0, uint32_t r1) {
    asm volatile("stmatrix.sync.aligned.m8n8.x2.shared.b16 [%0], {%1, %2};\n" :: "r"(addr), "r"(r0), "r"(r1) : "memory");
}
__device__ __forceinline__ void sts128(uint32_t addr, uint32_t r0, uint32_t r1, uint32_t r2, uint32_t r3) {
    asm volatile("st.shared.v4.b32 [%0], {%1, %2, %3, %4};\n" :: "r"(addr), "r"(r0), "r"(r1), "r"(r2), "r"(r3) : "memory");
}
__device__ __forceinline__ void sts128_if(uint32_t p, uint32_t addr, uint32_t r0, uint32_t r1, uint32_t r2, uint32_t r3) {
    asm volatile("{\n.reg .pred q;\nsetp.ne.b32 q, %5, 0;\n@q st.shared.v4.b32 [%0], {%1, %2, %3, %4};\n}\n"
                 :: "r"(addr), "r"(r0), "r"(r1), "r"(r2), "r"(r3), "r"(p) : "memory");
}
__device__ __forceinline__ void sts32(uint32_t addr, uint32_t v) {
    asm volatile("st.shared.b32 [%0], %1;\n" :: "r"(addr), "r"(v) : "memory");
}
__device__ __forceinline__ uint32_t lds32(uint32_t addr) {
    uint32_t v;
    asm volatile("ld.shared.b32 %0, [%1];\n" : "=r"(v) : "r"(addr) : "memory");
    return v;
}
__device__ __forceinline__ void ldg_nc_v4(uint32_t (&r)[4], const void* p) {
    asm volatile("ld.global.nc.L1::no_allocate.v4.u32 {%0, %1, %2, %3}, [%4];\n"
                 : "=r"(r[0]), "=r"(r[1]), "=r"(r[2]), "=r"(r[3]) : "l"(p));
}
__device__ __forceinline__ uint32_t ldg_u32(const void* p) {
    uint32_t v;
    asm volatile("ld.global.nc.L1::evict_first.u32 %0, [%1];\n" : "=r"(v) : "l"(p));
    return v;
}
__device__ __forceinline__ void ldg_u64(const void* p, uint32_t& a, uint32_t& b) {
    asm volatile("ld.global.nc.L1::evict_first.v2.u32 {%0, %1}, [%2];\n" : "=r"(a), "=r"(b) : "l"(p));
}
__device__ __forceinline__ void prefetch_l2(const void* p) {
    asm volatile("prefetch.global.L2 [%0];\n" :: "l"(p));
}
__device__ __forceinline__ void cp_async16(uint32_t dst, const void* src) {
    asm volatile("cp.async.cg.shared.global [%0], [%1], 16;\n" :: "r"(dst), "l"(src) : "memory");
}
__device__ __forceinline__ float ex2_ftz(float x) {
    float y;
    asm("ex2.approx.ftz.f32 %0, %1;\n" : "=f"(y) : "f"(x));
    return y;
}
__device__ __forceinline__ float lg2_ftz(float x) {
    float y;
    asm("lg2.approx.ftz.f32 %0, %1;\n" : "=f"(y) : "f"(x));
    return y;
}
__device__ __forceinline__ float rcp_ftz(float x) {
    float y;
    asm("rcp.approx.ftz.f32 %0, %1;\n" : "=f"(y) : "f"(x));
    return y;
}
__device__ __forceinline__ float rsqrt_ftz(float x) {
    float y;
    asm("rsqrt.approx.ftz.f32 %0, %1;\n" : "=f"(y) : "f"(x));
    return y;
}

__device__ __forceinline__ bool elect_one() {
    uint32_t p;
    asm volatile("{\n.reg .pred q;\nelect.sync _|q, 0xffffffff;\nselp.u32 %0, 1, 0, q;\n}\n" : "=r"(p));
    return p != 0;
}
__device__ __forceinline__ void ldsm_x4(uint32_t (&r)[4], uint32_t addr) {
    asm volatile("ldmatrix.sync.aligned.m8n8.x4.shared.b16 {%0, %1, %2, %3}, [%4];\n"
                 : "=r"(r[0]), "=r"(r[1]), "=r"(r[2]), "=r"(r[3]) : "r"(addr) : "memory");
}
__device__ __forceinline__ void ldsm_x2(uint32_t& r0, uint32_t& r1, uint32_t addr) {
    asm volatile("ldmatrix.sync.aligned.m8n8.x2.shared.b16 {%0, %1}, [%2];\n" : "=r"(r0), "=r"(r1) : "r"(addr) : "memory");
}
__device__ __forceinline__ void tma_2d(uint32_t dst, const CUtensorMap* map, uint32_t bar, int c0, int c1) {
    asm volatile("cp.async.bulk.tensor.2d.shared::cluster.global.mbarrier::complete_tx::bytes [%0], [%1, {%3, %4}], [%2];\n"
                 :: "r"(dst), "l"(reinterpret_cast<uint64_t>(map)), "r"(bar), "r"(c0), "r"(c1) : "memory");
}
__device__ __forceinline__ void tma_3d(uint32_t dst, const CUtensorMap* map, uint32_t bar, int c0, int c1, int c2) {
    asm volatile("cp.async.bulk.tensor.3d.shared::cluster.global.mbarrier::complete_tx::bytes [%0], [%1, {%3, %4, %5}], [%2];\n"
                 :: "r"(dst), "l"(reinterpret_cast<uint64_t>(map)), "r"(bar), "r"(c0), "r"(c1), "r"(c2) : "memory");
}
constexpr uint64_t EVICT_FIRST = 0x12F0000000000000ull;
__device__ __forceinline__ void tma_3d_x(uint32_t dst, const CUtensorMap* map, uint32_t bar, int c0, int c1, int c2) {
    if (CH & 50)
        asm volatile("cp.async.bulk.tensor.3d.shared::cluster.global.mbarrier::complete_tx::bytes.L2::cache_hint [%0], [%1, {%3, %4, %5}], [%2], %6;\n"
                     :: "r"(dst), "l"(reinterpret_cast<uint64_t>(map)), "r"(bar), "r"(c0), "r"(c1), "r"(c2),
                        "l"((CH & 2) || (blockIdx.x & 1) == ((CH >> 5) & 1) ? EVICT_FIRST : 0x1000000000000000ull) : "memory");
    else tma_3d(dst, map, bar, c0, c1, c2);
}
__device__ __forceinline__ void tma_store_4d(const CUtensorMap* map, uint32_t src, int c0, int c1, int c2, int c3) {
    asm volatile("cp.async.bulk.tensor.4d.global.shared::cta.tile.bulk_group [%0, {%2, %3, %4, %5}], [%1];\n"
                 :: "l"(reinterpret_cast<uint64_t>(map)), "r"(src), "r"(c0), "r"(c1), "r"(c2), "r"(c3) : "memory");
}
__device__ __forceinline__ void mbar_arrive_if(uint32_t bar, uint32_t cnt) {
    asm volatile("{\n.reg .pred q;\nsetp.ne.b32 q, %1, 0;\n@q mbarrier.arrive.shared::cta.b64 _, [%0], %1;\n}\n"
                 :: "r"(bar), "r"(cnt) : "memory");
}

template <int BOFF, int AOFF, int NA>
__device__ __forceinline__ void mma_qkv_a(float (&d)[48], const uint32_t (&a)[NA][4], uint64_t descB) {
    asm volatile(
        "{\n"
        ".reg .pred p0, p1;\n"
        ".reg .b64 ta, ta0, tb, tb0;\n"
        "setp.ne.b32 p0, 0, 0;\n"
        "setp.eq.b32 p1, 0, 0;\n"
        "add.s64 tb0, %72, %73;\n"
        "add.s64 tb, tb0, 0;\n"
        "wgmma.mma_async.sync.aligned.m64n96k16.f32.bf16.bf16 {%0, %1, %2, %3, %4, %5, %6, %7, %8, %9, %10, %11, %12, %13, %14, %15, %16, %17, %18, %19, %20, %21, %22, %23, %24, %25, %26, %27, %28, %29, %30, %31, %32, %33, %34, %35, %36, %37, %38, %39, %40, %41, %42, %43, %44, %45, %46, %47}, {%48, %49, %50, %51}, tb, p0, 1, 1, 1;\n"
        "add.s64 tb, tb0, 32;\n"
        "wgmma.mma_async.sync.aligned.m64n96k16.f32.bf16.bf16 {%0, %1, %2, %3, %4, %5, %6, %7, %8, %9, %10, %11, %12, %13, %14, %15, %16, %17, %18, %19, %20, %21, %22, %23, %24, %25, %26, %27, %28, %29, %30, %31, %32, %33, %34, %35, %36, %37, %38, %39, %40, %41, %42, %43, %44, %45, %46, %47}, {%52, %53, %54, %55}, tb, p1, 1, 1, 1;\n"
        "add.s64 tb, tb0, 64;\n"
        "wgmma.mma_async.sync.aligned.m64n96k16.f32.bf16.bf16 {%0, %1, %2, %3, %4, %5, %6, %7, %8, %9, %10, %11, %12, %13, %14, %15, %16, %17, %18, %19, %20, %21, %22, %23, %24, %25, %26, %27, %28, %29, %30, %31, %32, %33, %34, %35, %36, %37, %38, %39, %40, %41, %42, %43, %44, %45, %46, %47}, {%56, %57, %58, %59}, tb, p1, 1, 1, 1;\n"
        "add.s64 tb, tb0, 96;\n"
        "wgmma.mma_async.sync.aligned.m64n96k16.f32.bf16.bf16 {%0, %1, %2, %3, %4, %5, %6, %7, %8, %9, %10, %11, %12, %13, %14, %15, %16, %17, %18, %19, %20, %21, %22, %23, %24, %25, %26, %27, %28, %29, %30, %31, %32, %33, %34, %35, %36, %37, %38, %39, %40, %41, %42, %43, %44, %45, %46, %47}, {%60, %61, %62, %63}, tb, p1, 1, 1, 1;\n"
        "add.s64 tb, tb0, 1536;\n"
        "wgmma.mma_async.sync.aligned.m64n96k16.f32.bf16.bf16 {%0, %1, %2, %3, %4, %5, %6, %7, %8, %9, %10, %11, %12, %13, %14, %15, %16, %17, %18, %19, %20, %21, %22, %23, %24, %25, %26, %27, %28, %29, %30, %31, %32, %33, %34, %35, %36, %37, %38, %39, %40, %41, %42, %43, %44, %45, %46, %47}, {%64, %65, %66, %67}, tb, p1, 1, 1, 1;\n"
        "add.s64 tb, tb0, 1568;\n"
        "wgmma.mma_async.sync.aligned.m64n96k16.f32.bf16.bf16 {%0, %1, %2, %3, %4, %5, %6, %7, %8, %9, %10, %11, %12, %13, %14, %15, %16, %17, %18, %19, %20, %21, %22, %23, %24, %25, %26, %27, %28, %29, %30, %31, %32, %33, %34, %35, %36, %37, %38, %39, %40, %41, %42, %43, %44, %45, %46, %47}, {%68, %69, %70, %71}, tb, p1, 1, 1, 1;\n"
        "}\n"
        : "=f"(d[0]), "=f"(d[1]), "=f"(d[2]), "=f"(d[3]), "=f"(d[4]), "=f"(d[5]), "=f"(d[6]), "=f"(d[7]), "=f"(d[8]), "=f"(d[9]), "=f"(d[10]), "=f"(d[11]), "=f"(d[12]), "=f"(d[13]), "=f"(d[14]), "=f"(d[15]), "=f"(d[16]), "=f"(d[17]), "=f"(d[18]), "=f"(d[19]), "=f"(d[20]), "=f"(d[21]), "=f"(d[22]), "=f"(d[23]), "=f"(d[24]), "=f"(d[25]), "=f"(d[26]), "=f"(d[27]), "=f"(d[28]), "=f"(d[29]), "=f"(d[30]), "=f"(d[31]), "=f"(d[32]), "=f"(d[33]), "=f"(d[34]), "=f"(d[35]), "=f"(d[36]), "=f"(d[37]), "=f"(d[38]), "=f"(d[39]), "=f"(d[40]), "=f"(d[41]), "=f"(d[42]), "=f"(d[43]), "=f"(d[44]), "=f"(d[45]), "=f"(d[46]), "=f"(d[47])
        : "r"(a[AOFF + 0][0]), "r"(a[AOFF + 0][1]), "r"(a[AOFF + 0][2]), "r"(a[AOFF + 0][3]), "r"(a[AOFF + 1][0]), "r"(a[AOFF + 1][1]), "r"(a[AOFF + 1][2]), "r"(a[AOFF + 1][3]), "r"(a[AOFF + 2][0]), "r"(a[AOFF + 2][1]), "r"(a[AOFF + 2][2]), "r"(a[AOFF + 2][3]), "r"(a[AOFF + 3][0]), "r"(a[AOFF + 3][1]), "r"(a[AOFF + 3][2]), "r"(a[AOFF + 3][3]), "r"(a[AOFF + 4][0]), "r"(a[AOFF + 4][1]), "r"(a[AOFF + 4][2]), "r"(a[AOFF + 4][3]), "r"(a[AOFF + 5][0]), "r"(a[AOFF + 5][1]), "r"(a[AOFF + 5][2]), "r"(a[AOFF + 5][3]), "l"(descB), "n"(BOFF >> 4));
}

template <int BOFF, int AOFF, int NA>
__device__ __forceinline__ void mma_qkv_b(float (&d)[48], const uint32_t (&a)[NA][4], uint64_t descB) {
    asm volatile(
        "{\n"
        ".reg .pred p0, p1;\n"
        ".reg .b64 ta, ta0, tb, tb0;\n"
        "setp.ne.b32 p0, 0, 0;\n"
        "setp.eq.b32 p1, 0, 0;\n"
        "add.s64 tb0, %72, %73;\n"
        "add.s64 tb, tb0, 1600;\n"
        "wgmma.mma_async.sync.aligned.m64n96k16.f32.bf16.bf16 {%0, %1, %2, %3, %4, %5, %6, %7, %8, %9, %10, %11, %12, %13, %14, %15, %16, %17, %18, %19, %20, %21, %22, %23, %24, %25, %26, %27, %28, %29, %30, %31, %32, %33, %34, %35, %36, %37, %38, %39, %40, %41, %42, %43, %44, %45, %46, %47}, {%48, %49, %50, %51}, tb, p1, 1, 1, 1;\n"
        "add.s64 tb, tb0, 1632;\n"
        "wgmma.mma_async.sync.aligned.m64n96k16.f32.bf16.bf16 {%0, %1, %2, %3, %4, %5, %6, %7, %8, %9, %10, %11, %12, %13, %14, %15, %16, %17, %18, %19, %20, %21, %22, %23, %24, %25, %26, %27, %28, %29, %30, %31, %32, %33, %34, %35, %36, %37, %38, %39, %40, %41, %42, %43, %44, %45, %46, %47}, {%52, %53, %54, %55}, tb, p1, 1, 1, 1;\n"
        "add.s64 tb, tb0, 3072;\n"
        "wgmma.mma_async.sync.aligned.m64n96k16.f32.bf16.bf16 {%0, %1, %2, %3, %4, %5, %6, %7, %8, %9, %10, %11, %12, %13, %14, %15, %16, %17, %18, %19, %20, %21, %22, %23, %24, %25, %26, %27, %28, %29, %30, %31, %32, %33, %34, %35, %36, %37, %38, %39, %40, %41, %42, %43, %44, %45, %46, %47}, {%56, %57, %58, %59}, tb, p1, 1, 1, 1;\n"
        "add.s64 tb, tb0, 3104;\n"
        "wgmma.mma_async.sync.aligned.m64n96k16.f32.bf16.bf16 {%0, %1, %2, %3, %4, %5, %6, %7, %8, %9, %10, %11, %12, %13, %14, %15, %16, %17, %18, %19, %20, %21, %22, %23, %24, %25, %26, %27, %28, %29, %30, %31, %32, %33, %34, %35, %36, %37, %38, %39, %40, %41, %42, %43, %44, %45, %46, %47}, {%60, %61, %62, %63}, tb, p1, 1, 1, 1;\n"
        "add.s64 tb, tb0, 3136;\n"
        "wgmma.mma_async.sync.aligned.m64n96k16.f32.bf16.bf16 {%0, %1, %2, %3, %4, %5, %6, %7, %8, %9, %10, %11, %12, %13, %14, %15, %16, %17, %18, %19, %20, %21, %22, %23, %24, %25, %26, %27, %28, %29, %30, %31, %32, %33, %34, %35, %36, %37, %38, %39, %40, %41, %42, %43, %44, %45, %46, %47}, {%64, %65, %66, %67}, tb, p1, 1, 1, 1;\n"
        "add.s64 tb, tb0, 3168;\n"
        "wgmma.mma_async.sync.aligned.m64n96k16.f32.bf16.bf16 {%0, %1, %2, %3, %4, %5, %6, %7, %8, %9, %10, %11, %12, %13, %14, %15, %16, %17, %18, %19, %20, %21, %22, %23, %24, %25, %26, %27, %28, %29, %30, %31, %32, %33, %34, %35, %36, %37, %38, %39, %40, %41, %42, %43, %44, %45, %46, %47}, {%68, %69, %70, %71}, tb, p1, 1, 1, 1;\n"
        "}\n"
        : "+f"(d[0]), "+f"(d[1]), "+f"(d[2]), "+f"(d[3]), "+f"(d[4]), "+f"(d[5]), "+f"(d[6]), "+f"(d[7]), "+f"(d[8]), "+f"(d[9]), "+f"(d[10]), "+f"(d[11]), "+f"(d[12]), "+f"(d[13]), "+f"(d[14]), "+f"(d[15]), "+f"(d[16]), "+f"(d[17]), "+f"(d[18]), "+f"(d[19]), "+f"(d[20]), "+f"(d[21]), "+f"(d[22]), "+f"(d[23]), "+f"(d[24]), "+f"(d[25]), "+f"(d[26]), "+f"(d[27]), "+f"(d[28]), "+f"(d[29]), "+f"(d[30]), "+f"(d[31]), "+f"(d[32]), "+f"(d[33]), "+f"(d[34]), "+f"(d[35]), "+f"(d[36]), "+f"(d[37]), "+f"(d[38]), "+f"(d[39]), "+f"(d[40]), "+f"(d[41]), "+f"(d[42]), "+f"(d[43]), "+f"(d[44]), "+f"(d[45]), "+f"(d[46]), "+f"(d[47])
        : "r"(a[AOFF + 0][0]), "r"(a[AOFF + 0][1]), "r"(a[AOFF + 0][2]), "r"(a[AOFF + 0][3]), "r"(a[AOFF + 1][0]), "r"(a[AOFF + 1][1]), "r"(a[AOFF + 1][2]), "r"(a[AOFF + 1][3]), "r"(a[AOFF + 2][0]), "r"(a[AOFF + 2][1]), "r"(a[AOFF + 2][2]), "r"(a[AOFF + 2][3]), "r"(a[AOFF + 3][0]), "r"(a[AOFF + 3][1]), "r"(a[AOFF + 3][2]), "r"(a[AOFF + 3][3]), "r"(a[AOFF + 4][0]), "r"(a[AOFF + 4][1]), "r"(a[AOFF + 4][2]), "r"(a[AOFF + 4][3]), "r"(a[AOFF + 5][0]), "r"(a[AOFF + 5][1]), "r"(a[AOFF + 5][2]), "r"(a[AOFF + 5][3]), "l"(descB), "n"(BOFF >> 4));
}

template <int BOFF, int AOFF, int NA>
__device__ __forceinline__ void mma_v_a(float (&d)[48], const uint32_t (&a)[NA][4], uint64_t descB) {
    asm volatile(
        "{\n"
        ".reg .pred p0, p1;\n"
        ".reg .b64 ta, ta0, tb, tb0;\n"
        "setp.ne.b32 p0, 0, 0;\n"
        "setp.eq.b32 p1, 0, 0;\n"
        "add.s64 tb0, %72, %73;\n"
        "add.s64 tb, tb0, 0;\n"
        "wgmma.mma_async.sync.aligned.m64n96k16.f32.bf16.bf16 {%0, %1, %2, %3, %4, %5, %6, %7, %8, %9, %10, %11, %12, %13, %14, %15, %16, %17, %18, %19, %20, %21, %22, %23, %24, %25, %26, %27, %28, %29, %30, %31, %32, %33, %34, %35, %36, %37, %38, %39, %40, %41, %42, %43, %44, %45, %46, %47}, {%48, %49, %50, %51}, tb, p0, 1, 1, 1;\n"
        "add.s64 tb, tb0, 32;\n"
        "wgmma.mma_async.sync.aligned.m64n96k16.f32.bf16.bf16 {%0, %1, %2, %3, %4, %5, %6, %7, %8, %9, %10, %11, %12, %13, %14, %15, %16, %17, %18, %19, %20, %21, %22, %23, %24, %25, %26, %27, %28, %29, %30, %31, %32, %33, %34, %35, %36, %37, %38, %39, %40, %41, %42, %43, %44, %45, %46, %47}, {%52, %53, %54, %55}, tb, p1, 1, 1, 1;\n"
        "add.s64 tb, tb0, 64;\n"
        "wgmma.mma_async.sync.aligned.m64n96k16.f32.bf16.bf16 {%0, %1, %2, %3, %4, %5, %6, %7, %8, %9, %10, %11, %12, %13, %14, %15, %16, %17, %18, %19, %20, %21, %22, %23, %24, %25, %26, %27, %28, %29, %30, %31, %32, %33, %34, %35, %36, %37, %38, %39, %40, %41, %42, %43, %44, %45, %46, %47}, {%56, %57, %58, %59}, tb, p1, 1, 1, 1;\n"
        "add.s64 tb, tb0, 96;\n"
        "wgmma.mma_async.sync.aligned.m64n96k16.f32.bf16.bf16 {%0, %1, %2, %3, %4, %5, %6, %7, %8, %9, %10, %11, %12, %13, %14, %15, %16, %17, %18, %19, %20, %21, %22, %23, %24, %25, %26, %27, %28, %29, %30, %31, %32, %33, %34, %35, %36, %37, %38, %39, %40, %41, %42, %43, %44, %45, %46, %47}, {%60, %61, %62, %63}, tb, p1, 1, 1, 1;\n"
        "add.s64 tb, tb0, 128;\n"
        "wgmma.mma_async.sync.aligned.m64n96k16.f32.bf16.bf16 {%0, %1, %2, %3, %4, %5, %6, %7, %8, %9, %10, %11, %12, %13, %14, %15, %16, %17, %18, %19, %20, %21, %22, %23, %24, %25, %26, %27, %28, %29, %30, %31, %32, %33, %34, %35, %36, %37, %38, %39, %40, %41, %42, %43, %44, %45, %46, %47}, {%64, %65, %66, %67}, tb, p1, 1, 1, 1;\n"
        "add.s64 tb, tb0, 160;\n"
        "wgmma.mma_async.sync.aligned.m64n96k16.f32.bf16.bf16 {%0, %1, %2, %3, %4, %5, %6, %7, %8, %9, %10, %11, %12, %13, %14, %15, %16, %17, %18, %19, %20, %21, %22, %23, %24, %25, %26, %27, %28, %29, %30, %31, %32, %33, %34, %35, %36, %37, %38, %39, %40, %41, %42, %43, %44, %45, %46, %47}, {%68, %69, %70, %71}, tb, p1, 1, 1, 1;\n"
        "}\n"
        : "=f"(d[0]), "=f"(d[1]), "=f"(d[2]), "=f"(d[3]), "=f"(d[4]), "=f"(d[5]), "=f"(d[6]), "=f"(d[7]), "=f"(d[8]), "=f"(d[9]), "=f"(d[10]), "=f"(d[11]), "=f"(d[12]), "=f"(d[13]), "=f"(d[14]), "=f"(d[15]), "=f"(d[16]), "=f"(d[17]), "=f"(d[18]), "=f"(d[19]), "=f"(d[20]), "=f"(d[21]), "=f"(d[22]), "=f"(d[23]), "=f"(d[24]), "=f"(d[25]), "=f"(d[26]), "=f"(d[27]), "=f"(d[28]), "=f"(d[29]), "=f"(d[30]), "=f"(d[31]), "=f"(d[32]), "=f"(d[33]), "=f"(d[34]), "=f"(d[35]), "=f"(d[36]), "=f"(d[37]), "=f"(d[38]), "=f"(d[39]), "=f"(d[40]), "=f"(d[41]), "=f"(d[42]), "=f"(d[43]), "=f"(d[44]), "=f"(d[45]), "=f"(d[46]), "=f"(d[47])
        : "r"(a[AOFF + 0][0]), "r"(a[AOFF + 0][1]), "r"(a[AOFF + 0][2]), "r"(a[AOFF + 0][3]), "r"(a[AOFF + 1][0]), "r"(a[AOFF + 1][1]), "r"(a[AOFF + 1][2]), "r"(a[AOFF + 1][3]), "r"(a[AOFF + 2][0]), "r"(a[AOFF + 2][1]), "r"(a[AOFF + 2][2]), "r"(a[AOFF + 2][3]), "r"(a[AOFF + 3][0]), "r"(a[AOFF + 3][1]), "r"(a[AOFF + 3][2]), "r"(a[AOFF + 3][3]), "r"(a[AOFF + 4][0]), "r"(a[AOFF + 4][1]), "r"(a[AOFF + 4][2]), "r"(a[AOFF + 4][3]), "r"(a[AOFF + 5][0]), "r"(a[AOFF + 5][1]), "r"(a[AOFF + 5][2]), "r"(a[AOFF + 5][3]), "l"(descB), "n"(BOFF >> 4));
}

template <int BOFF, int AOFF, int NA>
__device__ __forceinline__ void mma_v_b(float (&d)[48], const uint32_t (&a)[NA][4], uint64_t descB) {
    asm volatile(
        "{\n"
        ".reg .pred p0, p1;\n"
        ".reg .b64 ta, ta0, tb, tb0;\n"
        "setp.ne.b32 p0, 0, 0;\n"
        "setp.eq.b32 p1, 0, 0;\n"
        "add.s64 tb0, %72, %73;\n"
        "add.s64 tb, tb0, 192;\n"
        "wgmma.mma_async.sync.aligned.m64n96k16.f32.bf16.bf16 {%0, %1, %2, %3, %4, %5, %6, %7, %8, %9, %10, %11, %12, %13, %14, %15, %16, %17, %18, %19, %20, %21, %22, %23, %24, %25, %26, %27, %28, %29, %30, %31, %32, %33, %34, %35, %36, %37, %38, %39, %40, %41, %42, %43, %44, %45, %46, %47}, {%48, %49, %50, %51}, tb, p1, 1, 1, 1;\n"
        "add.s64 tb, tb0, 224;\n"
        "wgmma.mma_async.sync.aligned.m64n96k16.f32.bf16.bf16 {%0, %1, %2, %3, %4, %5, %6, %7, %8, %9, %10, %11, %12, %13, %14, %15, %16, %17, %18, %19, %20, %21, %22, %23, %24, %25, %26, %27, %28, %29, %30, %31, %32, %33, %34, %35, %36, %37, %38, %39, %40, %41, %42, %43, %44, %45, %46, %47}, {%52, %53, %54, %55}, tb, p1, 1, 1, 1;\n"
        "add.s64 tb, tb0, 256;\n"
        "wgmma.mma_async.sync.aligned.m64n96k16.f32.bf16.bf16 {%0, %1, %2, %3, %4, %5, %6, %7, %8, %9, %10, %11, %12, %13, %14, %15, %16, %17, %18, %19, %20, %21, %22, %23, %24, %25, %26, %27, %28, %29, %30, %31, %32, %33, %34, %35, %36, %37, %38, %39, %40, %41, %42, %43, %44, %45, %46, %47}, {%56, %57, %58, %59}, tb, p1, 1, 1, 1;\n"
        "add.s64 tb, tb0, 288;\n"
        "wgmma.mma_async.sync.aligned.m64n96k16.f32.bf16.bf16 {%0, %1, %2, %3, %4, %5, %6, %7, %8, %9, %10, %11, %12, %13, %14, %15, %16, %17, %18, %19, %20, %21, %22, %23, %24, %25, %26, %27, %28, %29, %30, %31, %32, %33, %34, %35, %36, %37, %38, %39, %40, %41, %42, %43, %44, %45, %46, %47}, {%60, %61, %62, %63}, tb, p1, 1, 1, 1;\n"
        "add.s64 tb, tb0, 320;\n"
        "wgmma.mma_async.sync.aligned.m64n96k16.f32.bf16.bf16 {%0, %1, %2, %3, %4, %5, %6, %7, %8, %9, %10, %11, %12, %13, %14, %15, %16, %17, %18, %19, %20, %21, %22, %23, %24, %25, %26, %27, %28, %29, %30, %31, %32, %33, %34, %35, %36, %37, %38, %39, %40, %41, %42, %43, %44, %45, %46, %47}, {%64, %65, %66, %67}, tb, p1, 1, 1, 1;\n"
        "add.s64 tb, tb0, 352;\n"
        "wgmma.mma_async.sync.aligned.m64n96k16.f32.bf16.bf16 {%0, %1, %2, %3, %4, %5, %6, %7, %8, %9, %10, %11, %12, %13, %14, %15, %16, %17, %18, %19, %20, %21, %22, %23, %24, %25, %26, %27, %28, %29, %30, %31, %32, %33, %34, %35, %36, %37, %38, %39, %40, %41, %42, %43, %44, %45, %46, %47}, {%68, %69, %70, %71}, tb, p1, 1, 1, 1;\n"
        "}\n"
        : "+f"(d[0]), "+f"(d[1]), "+f"(d[2]), "+f"(d[3]), "+f"(d[4]), "+f"(d[5]), "+f"(d[6]), "+f"(d[7]), "+f"(d[8]), "+f"(d[9]), "+f"(d[10]), "+f"(d[11]), "+f"(d[12]), "+f"(d[13]), "+f"(d[14]), "+f"(d[15]), "+f"(d[16]), "+f"(d[17]), "+f"(d[18]), "+f"(d[19]), "+f"(d[20]), "+f"(d[21]), "+f"(d[22]), "+f"(d[23]), "+f"(d[24]), "+f"(d[25]), "+f"(d[26]), "+f"(d[27]), "+f"(d[28]), "+f"(d[29]), "+f"(d[30]), "+f"(d[31]), "+f"(d[32]), "+f"(d[33]), "+f"(d[34]), "+f"(d[35]), "+f"(d[36]), "+f"(d[37]), "+f"(d[38]), "+f"(d[39]), "+f"(d[40]), "+f"(d[41]), "+f"(d[42]), "+f"(d[43]), "+f"(d[44]), "+f"(d[45]), "+f"(d[46]), "+f"(d[47])
        : "r"(a[AOFF + 0][0]), "r"(a[AOFF + 0][1]), "r"(a[AOFF + 0][2]), "r"(a[AOFF + 0][3]), "r"(a[AOFF + 1][0]), "r"(a[AOFF + 1][1]), "r"(a[AOFF + 1][2]), "r"(a[AOFF + 1][3]), "r"(a[AOFF + 2][0]), "r"(a[AOFF + 2][1]), "r"(a[AOFF + 2][2]), "r"(a[AOFF + 2][3]), "r"(a[AOFF + 3][0]), "r"(a[AOFF + 3][1]), "r"(a[AOFF + 3][2]), "r"(a[AOFF + 3][3]), "r"(a[AOFF + 4][0]), "r"(a[AOFF + 4][1]), "r"(a[AOFF + 4][2]), "r"(a[AOFF + 4][3]), "r"(a[AOFF + 5][0]), "r"(a[AOFF + 5][1]), "r"(a[AOFF + 5][2]), "r"(a[AOFF + 5][3]), "l"(descB), "n"(BOFF >> 4));
}

template <int BOFF, int AOFF, int NA>
__device__ __forceinline__ void mma_w_a(float (&d)[48], const uint32_t (&a)[NA][4], uint64_t descB) {
    asm volatile(
        "{\n"
        ".reg .pred p0, p1;\n"
        ".reg .b64 ta, ta0, tb, tb0;\n"
        "setp.ne.b32 p0, 0, 0;\n"
        "setp.eq.b32 p1, 0, 0;\n"
        "add.s64 tb0, %72, %73;\n"
        "add.s64 tb, tb0, 0;\n"
        "wgmma.mma_async.sync.aligned.m64n96k16.f32.bf16.bf16 {%0, %1, %2, %3, %4, %5, %6, %7, %8, %9, %10, %11, %12, %13, %14, %15, %16, %17, %18, %19, %20, %21, %22, %23, %24, %25, %26, %27, %28, %29, %30, %31, %32, %33, %34, %35, %36, %37, %38, %39, %40, %41, %42, %43, %44, %45, %46, %47}, {%48, %49, %50, %51}, tb, p0, 1, 1, 1;\n"
        "add.s64 tb, tb0, 64;\n"
        "wgmma.mma_async.sync.aligned.m64n96k16.f32.bf16.bf16 {%0, %1, %2, %3, %4, %5, %6, %7, %8, %9, %10, %11, %12, %13, %14, %15, %16, %17, %18, %19, %20, %21, %22, %23, %24, %25, %26, %27, %28, %29, %30, %31, %32, %33, %34, %35, %36, %37, %38, %39, %40, %41, %42, %43, %44, %45, %46, %47}, {%52, %53, %54, %55}, tb, p1, 1, 1, 1;\n"
        "add.s64 tb, tb0, 128;\n"
        "wgmma.mma_async.sync.aligned.m64n96k16.f32.bf16.bf16 {%0, %1, %2, %3, %4, %5, %6, %7, %8, %9, %10, %11, %12, %13, %14, %15, %16, %17, %18, %19, %20, %21, %22, %23, %24, %25, %26, %27, %28, %29, %30, %31, %32, %33, %34, %35, %36, %37, %38, %39, %40, %41, %42, %43, %44, %45, %46, %47}, {%56, %57, %58, %59}, tb, p1, 1, 1, 1;\n"
        "add.s64 tb, tb0, 192;\n"
        "wgmma.mma_async.sync.aligned.m64n96k16.f32.bf16.bf16 {%0, %1, %2, %3, %4, %5, %6, %7, %8, %9, %10, %11, %12, %13, %14, %15, %16, %17, %18, %19, %20, %21, %22, %23, %24, %25, %26, %27, %28, %29, %30, %31, %32, %33, %34, %35, %36, %37, %38, %39, %40, %41, %42, %43, %44, %45, %46, %47}, {%60, %61, %62, %63}, tb, p1, 1, 1, 1;\n"
        "add.s64 tb, tb0, 256;\n"
        "wgmma.mma_async.sync.aligned.m64n96k16.f32.bf16.bf16 {%0, %1, %2, %3, %4, %5, %6, %7, %8, %9, %10, %11, %12, %13, %14, %15, %16, %17, %18, %19, %20, %21, %22, %23, %24, %25, %26, %27, %28, %29, %30, %31, %32, %33, %34, %35, %36, %37, %38, %39, %40, %41, %42, %43, %44, %45, %46, %47}, {%64, %65, %66, %67}, tb, p1, 1, 1, 1;\n"
        "add.s64 tb, tb0, 320;\n"
        "wgmma.mma_async.sync.aligned.m64n96k16.f32.bf16.bf16 {%0, %1, %2, %3, %4, %5, %6, %7, %8, %9, %10, %11, %12, %13, %14, %15, %16, %17, %18, %19, %20, %21, %22, %23, %24, %25, %26, %27, %28, %29, %30, %31, %32, %33, %34, %35, %36, %37, %38, %39, %40, %41, %42, %43, %44, %45, %46, %47}, {%68, %69, %70, %71}, tb, p1, 1, 1, 1;\n"
        "}\n"
        : "=f"(d[0]), "=f"(d[1]), "=f"(d[2]), "=f"(d[3]), "=f"(d[4]), "=f"(d[5]), "=f"(d[6]), "=f"(d[7]), "=f"(d[8]), "=f"(d[9]), "=f"(d[10]), "=f"(d[11]), "=f"(d[12]), "=f"(d[13]), "=f"(d[14]), "=f"(d[15]), "=f"(d[16]), "=f"(d[17]), "=f"(d[18]), "=f"(d[19]), "=f"(d[20]), "=f"(d[21]), "=f"(d[22]), "=f"(d[23]), "=f"(d[24]), "=f"(d[25]), "=f"(d[26]), "=f"(d[27]), "=f"(d[28]), "=f"(d[29]), "=f"(d[30]), "=f"(d[31]), "=f"(d[32]), "=f"(d[33]), "=f"(d[34]), "=f"(d[35]), "=f"(d[36]), "=f"(d[37]), "=f"(d[38]), "=f"(d[39]), "=f"(d[40]), "=f"(d[41]), "=f"(d[42]), "=f"(d[43]), "=f"(d[44]), "=f"(d[45]), "=f"(d[46]), "=f"(d[47])
        : "r"(a[AOFF + 0][0]), "r"(a[AOFF + 0][1]), "r"(a[AOFF + 0][2]), "r"(a[AOFF + 0][3]), "r"(a[AOFF + 1][0]), "r"(a[AOFF + 1][1]), "r"(a[AOFF + 1][2]), "r"(a[AOFF + 1][3]), "r"(a[AOFF + 2][0]), "r"(a[AOFF + 2][1]), "r"(a[AOFF + 2][2]), "r"(a[AOFF + 2][3]), "r"(a[AOFF + 3][0]), "r"(a[AOFF + 3][1]), "r"(a[AOFF + 3][2]), "r"(a[AOFF + 3][3]), "r"(a[AOFF + 4][0]), "r"(a[AOFF + 4][1]), "r"(a[AOFF + 4][2]), "r"(a[AOFF + 4][3]), "r"(a[AOFF + 5][0]), "r"(a[AOFF + 5][1]), "r"(a[AOFF + 5][2]), "r"(a[AOFF + 5][3]), "l"(descB), "n"(BOFF >> 4));
}

template <int BOFF, int AOFF, int NA>
__device__ __forceinline__ void mma_w_b(float (&d)[48], const uint32_t (&a)[NA][4], uint64_t descB) {
    asm volatile(
        "{\n"
        ".reg .pred p0, p1;\n"
        ".reg .b64 ta, ta0, tb, tb0;\n"
        "setp.ne.b32 p0, 0, 0;\n"
        "setp.eq.b32 p1, 0, 0;\n"
        "add.s64 tb0, %72, %73;\n"
        "add.s64 tb, tb0, 384;\n"
        "wgmma.mma_async.sync.aligned.m64n96k16.f32.bf16.bf16 {%0, %1, %2, %3, %4, %5, %6, %7, %8, %9, %10, %11, %12, %13, %14, %15, %16, %17, %18, %19, %20, %21, %22, %23, %24, %25, %26, %27, %28, %29, %30, %31, %32, %33, %34, %35, %36, %37, %38, %39, %40, %41, %42, %43, %44, %45, %46, %47}, {%48, %49, %50, %51}, tb, p1, 1, 1, 1;\n"
        "add.s64 tb, tb0, 448;\n"
        "wgmma.mma_async.sync.aligned.m64n96k16.f32.bf16.bf16 {%0, %1, %2, %3, %4, %5, %6, %7, %8, %9, %10, %11, %12, %13, %14, %15, %16, %17, %18, %19, %20, %21, %22, %23, %24, %25, %26, %27, %28, %29, %30, %31, %32, %33, %34, %35, %36, %37, %38, %39, %40, %41, %42, %43, %44, %45, %46, %47}, {%52, %53, %54, %55}, tb, p1, 1, 1, 1;\n"
        "add.s64 tb, tb0, 512;\n"
        "wgmma.mma_async.sync.aligned.m64n96k16.f32.bf16.bf16 {%0, %1, %2, %3, %4, %5, %6, %7, %8, %9, %10, %11, %12, %13, %14, %15, %16, %17, %18, %19, %20, %21, %22, %23, %24, %25, %26, %27, %28, %29, %30, %31, %32, %33, %34, %35, %36, %37, %38, %39, %40, %41, %42, %43, %44, %45, %46, %47}, {%56, %57, %58, %59}, tb, p1, 1, 1, 1;\n"
        "add.s64 tb, tb0, 576;\n"
        "wgmma.mma_async.sync.aligned.m64n96k16.f32.bf16.bf16 {%0, %1, %2, %3, %4, %5, %6, %7, %8, %9, %10, %11, %12, %13, %14, %15, %16, %17, %18, %19, %20, %21, %22, %23, %24, %25, %26, %27, %28, %29, %30, %31, %32, %33, %34, %35, %36, %37, %38, %39, %40, %41, %42, %43, %44, %45, %46, %47}, {%60, %61, %62, %63}, tb, p1, 1, 1, 1;\n"
        "add.s64 tb, tb0, 640;\n"
        "wgmma.mma_async.sync.aligned.m64n96k16.f32.bf16.bf16 {%0, %1, %2, %3, %4, %5, %6, %7, %8, %9, %10, %11, %12, %13, %14, %15, %16, %17, %18, %19, %20, %21, %22, %23, %24, %25, %26, %27, %28, %29, %30, %31, %32, %33, %34, %35, %36, %37, %38, %39, %40, %41, %42, %43, %44, %45, %46, %47}, {%64, %65, %66, %67}, tb, p1, 1, 1, 1;\n"
        "add.s64 tb, tb0, 704;\n"
        "wgmma.mma_async.sync.aligned.m64n96k16.f32.bf16.bf16 {%0, %1, %2, %3, %4, %5, %6, %7, %8, %9, %10, %11, %12, %13, %14, %15, %16, %17, %18, %19, %20, %21, %22, %23, %24, %25, %26, %27, %28, %29, %30, %31, %32, %33, %34, %35, %36, %37, %38, %39, %40, %41, %42, %43, %44, %45, %46, %47}, {%68, %69, %70, %71}, tb, p1, 1, 1, 1;\n"
        "}\n"
        : "+f"(d[0]), "+f"(d[1]), "+f"(d[2]), "+f"(d[3]), "+f"(d[4]), "+f"(d[5]), "+f"(d[6]), "+f"(d[7]), "+f"(d[8]), "+f"(d[9]), "+f"(d[10]), "+f"(d[11]), "+f"(d[12]), "+f"(d[13]), "+f"(d[14]), "+f"(d[15]), "+f"(d[16]), "+f"(d[17]), "+f"(d[18]), "+f"(d[19]), "+f"(d[20]), "+f"(d[21]), "+f"(d[22]), "+f"(d[23]), "+f"(d[24]), "+f"(d[25]), "+f"(d[26]), "+f"(d[27]), "+f"(d[28]), "+f"(d[29]), "+f"(d[30]), "+f"(d[31]), "+f"(d[32]), "+f"(d[33]), "+f"(d[34]), "+f"(d[35]), "+f"(d[36]), "+f"(d[37]), "+f"(d[38]), "+f"(d[39]), "+f"(d[40]), "+f"(d[41]), "+f"(d[42]), "+f"(d[43]), "+f"(d[44]), "+f"(d[45]), "+f"(d[46]), "+f"(d[47])
        : "r"(a[AOFF + 0][0]), "r"(a[AOFF + 0][1]), "r"(a[AOFF + 0][2]), "r"(a[AOFF + 0][3]), "r"(a[AOFF + 1][0]), "r"(a[AOFF + 1][1]), "r"(a[AOFF + 1][2]), "r"(a[AOFF + 1][3]), "r"(a[AOFF + 2][0]), "r"(a[AOFF + 2][1]), "r"(a[AOFF + 2][2]), "r"(a[AOFF + 2][3]), "r"(a[AOFF + 3][0]), "r"(a[AOFF + 3][1]), "r"(a[AOFF + 3][2]), "r"(a[AOFF + 3][3]), "r"(a[AOFF + 4][0]), "r"(a[AOFF + 4][1]), "r"(a[AOFF + 4][2]), "r"(a[AOFF + 4][3]), "r"(a[AOFF + 5][0]), "r"(a[AOFF + 5][1]), "r"(a[AOFF + 5][2]), "r"(a[AOFF + 5][3]), "l"(descB), "n"(BOFF >> 4));
}
template <int V, int S0, int S1> struct Rng;
template <> struct Rng<0, 0, 3> {
template <int BOFF, int AOFF, int NA>
static __device__ __forceinline__ void run(float (&d)[48], const uint32_t (&a)[NA][4], uint64_t descB) {
    asm volatile(
        "{\n"
        ".reg .pred p0, p1;\n"
        ".reg .b64 ta, ta0, tb, tb0;\n"
        "setp.ne.b32 p0, 0, 0;\n"
        "setp.eq.b32 p1, 0, 0;\n"
        "add.s64 tb0, %60, %61;\n"
        "add.s64 tb, tb0, 0;\n"
        "wgmma.mma_async.sync.aligned.m64n96k16.f32.bf16.bf16 {%0, %1, %2, %3, %4, %5, %6, %7, %8, %9, %10, %11, %12, %13, %14, %15, %16, %17, %18, %19, %20, %21, %22, %23, %24, %25, %26, %27, %28, %29, %30, %31, %32, %33, %34, %35, %36, %37, %38, %39, %40, %41, %42, %43, %44, %45, %46, %47}, {%48, %49, %50, %51}, tb, p0, 1, 1, 1;\n"
        "add.s64 tb, tb0, 32;\n"
        "wgmma.mma_async.sync.aligned.m64n96k16.f32.bf16.bf16 {%0, %1, %2, %3, %4, %5, %6, %7, %8, %9, %10, %11, %12, %13, %14, %15, %16, %17, %18, %19, %20, %21, %22, %23, %24, %25, %26, %27, %28, %29, %30, %31, %32, %33, %34, %35, %36, %37, %38, %39, %40, %41, %42, %43, %44, %45, %46, %47}, {%52, %53, %54, %55}, tb, p1, 1, 1, 1;\n"
        "add.s64 tb, tb0, 64;\n"
        "wgmma.mma_async.sync.aligned.m64n96k16.f32.bf16.bf16 {%0, %1, %2, %3, %4, %5, %6, %7, %8, %9, %10, %11, %12, %13, %14, %15, %16, %17, %18, %19, %20, %21, %22, %23, %24, %25, %26, %27, %28, %29, %30, %31, %32, %33, %34, %35, %36, %37, %38, %39, %40, %41, %42, %43, %44, %45, %46, %47}, {%56, %57, %58, %59}, tb, p1, 1, 1, 1;\n"
        "}\n"
        : "=f"(d[0]), "=f"(d[1]), "=f"(d[2]), "=f"(d[3]), "=f"(d[4]), "=f"(d[5]), "=f"(d[6]), "=f"(d[7]), "=f"(d[8]), "=f"(d[9]), "=f"(d[10]), "=f"(d[11]), "=f"(d[12]), "=f"(d[13]), "=f"(d[14]), "=f"(d[15]), "=f"(d[16]), "=f"(d[17]), "=f"(d[18]), "=f"(d[19]), "=f"(d[20]), "=f"(d[21]), "=f"(d[22]), "=f"(d[23]), "=f"(d[24]), "=f"(d[25]), "=f"(d[26]), "=f"(d[27]), "=f"(d[28]), "=f"(d[29]), "=f"(d[30]), "=f"(d[31]), "=f"(d[32]), "=f"(d[33]), "=f"(d[34]), "=f"(d[35]), "=f"(d[36]), "=f"(d[37]), "=f"(d[38]), "=f"(d[39]), "=f"(d[40]), "=f"(d[41]), "=f"(d[42]), "=f"(d[43]), "=f"(d[44]), "=f"(d[45]), "=f"(d[46]), "=f"(d[47])
        : "r"(a[AOFF + 0][0]), "r"(a[AOFF + 0][1]), "r"(a[AOFF + 0][2]), "r"(a[AOFF + 0][3]), "r"(a[AOFF + 1][0]), "r"(a[AOFF + 1][1]), "r"(a[AOFF + 1][2]), "r"(a[AOFF + 1][3]), "r"(a[AOFF + 2][0]), "r"(a[AOFF + 2][1]), "r"(a[AOFF + 2][2]), "r"(a[AOFF + 2][3]), "l"(descB), "n"(BOFF >> 4));
}
};
template <> struct Rng<1, 0, 3> {
template <int BOFF, int AOFF, int NA>
static __device__ __forceinline__ void run(float (&d)[48], const uint32_t (&a)[NA][4], uint64_t descB) {
    asm volatile(
        "{\n"
        ".reg .pred p0, p1;\n"
        ".reg .b64 ta, ta0, tb, tb0;\n"
        "setp.ne.b32 p0, 0, 0;\n"
        "setp.eq.b32 p1, 0, 0;\n"
        "add.s64 tb0, %60, %61;\n"
        "add.s64 tb, tb0, 0;\n"
        "wgmma.mma_async.sync.aligned.m64n96k16.f32.bf16.bf16 {%0, %1, %2, %3, %4, %5, %6, %7, %8, %9, %10, %11, %12, %13, %14, %15, %16, %17, %18, %19, %20, %21, %22, %23, %24, %25, %26, %27, %28, %29, %30, %31, %32, %33, %34, %35, %36, %37, %38, %39, %40, %41, %42, %43, %44, %45, %46, %47}, {%48, %49, %50, %51}, tb, p0, 1, 1, 1;\n"
        "add.s64 tb, tb0, 32;\n"
        "wgmma.mma_async.sync.aligned.m64n96k16.f32.bf16.bf16 {%0, %1, %2, %3, %4, %5, %6, %7, %8, %9, %10, %11, %12, %13, %14, %15, %16, %17, %18, %19, %20, %21, %22, %23, %24, %25, %26, %27, %28, %29, %30, %31, %32, %33, %34, %35, %36, %37, %38, %39, %40, %41, %42, %43, %44, %45, %46, %47}, {%52, %53, %54, %55}, tb, p1, 1, 1, 1;\n"
        "add.s64 tb, tb0, 64;\n"
        "wgmma.mma_async.sync.aligned.m64n96k16.f32.bf16.bf16 {%0, %1, %2, %3, %4, %5, %6, %7, %8, %9, %10, %11, %12, %13, %14, %15, %16, %17, %18, %19, %20, %21, %22, %23, %24, %25, %26, %27, %28, %29, %30, %31, %32, %33, %34, %35, %36, %37, %38, %39, %40, %41, %42, %43, %44, %45, %46, %47}, {%56, %57, %58, %59}, tb, p1, 1, 1, 1;\n"
        "}\n"
        : "=f"(d[0]), "=f"(d[1]), "=f"(d[2]), "=f"(d[3]), "=f"(d[4]), "=f"(d[5]), "=f"(d[6]), "=f"(d[7]), "=f"(d[8]), "=f"(d[9]), "=f"(d[10]), "=f"(d[11]), "=f"(d[12]), "=f"(d[13]), "=f"(d[14]), "=f"(d[15]), "=f"(d[16]), "=f"(d[17]), "=f"(d[18]), "=f"(d[19]), "=f"(d[20]), "=f"(d[21]), "=f"(d[22]), "=f"(d[23]), "=f"(d[24]), "=f"(d[25]), "=f"(d[26]), "=f"(d[27]), "=f"(d[28]), "=f"(d[29]), "=f"(d[30]), "=f"(d[31]), "=f"(d[32]), "=f"(d[33]), "=f"(d[34]), "=f"(d[35]), "=f"(d[36]), "=f"(d[37]), "=f"(d[38]), "=f"(d[39]), "=f"(d[40]), "=f"(d[41]), "=f"(d[42]), "=f"(d[43]), "=f"(d[44]), "=f"(d[45]), "=f"(d[46]), "=f"(d[47])
        : "r"(a[AOFF + 0][0]), "r"(a[AOFF + 0][1]), "r"(a[AOFF + 0][2]), "r"(a[AOFF + 0][3]), "r"(a[AOFF + 1][0]), "r"(a[AOFF + 1][1]), "r"(a[AOFF + 1][2]), "r"(a[AOFF + 1][3]), "r"(a[AOFF + 2][0]), "r"(a[AOFF + 2][1]), "r"(a[AOFF + 2][2]), "r"(a[AOFF + 2][3]), "l"(descB), "n"(BOFF >> 4));
}
};
template <> struct Rng<0, 0, 4> {
template <int BOFF, int AOFF, int NA>
static __device__ __forceinline__ void run(float (&d)[48], const uint32_t (&a)[NA][4], uint64_t descB) {
    asm volatile(
        "{\n"
        ".reg .pred p0, p1;\n"
        ".reg .b64 ta, ta0, tb, tb0;\n"
        "setp.ne.b32 p0, 0, 0;\n"
        "setp.eq.b32 p1, 0, 0;\n"
        "add.s64 tb0, %64, %65;\n"
        "add.s64 tb, tb0, 0;\n"
        "wgmma.mma_async.sync.aligned.m64n96k16.f32.bf16.bf16 {%0, %1, %2, %3, %4, %5, %6, %7, %8, %9, %10, %11, %12, %13, %14, %15, %16, %17, %18, %19, %20, %21, %22, %23, %24, %25, %26, %27, %28, %29, %30, %31, %32, %33, %34, %35, %36, %37, %38, %39, %40, %41, %42, %43, %44, %45, %46, %47}, {%48, %49, %50, %51}, tb, p0, 1, 1, 1;\n"
        "add.s64 tb, tb0, 32;\n"
        "wgmma.mma_async.sync.aligned.m64n96k16.f32.bf16.bf16 {%0, %1, %2, %3, %4, %5, %6, %7, %8, %9, %10, %11, %12, %13, %14, %15, %16, %17, %18, %19, %20, %21, %22, %23, %24, %25, %26, %27, %28, %29, %30, %31, %32, %33, %34, %35, %36, %37, %38, %39, %40, %41, %42, %43, %44, %45, %46, %47}, {%52, %53, %54, %55}, tb, p1, 1, 1, 1;\n"
        "add.s64 tb, tb0, 64;\n"
        "wgmma.mma_async.sync.aligned.m64n96k16.f32.bf16.bf16 {%0, %1, %2, %3, %4, %5, %6, %7, %8, %9, %10, %11, %12, %13, %14, %15, %16, %17, %18, %19, %20, %21, %22, %23, %24, %25, %26, %27, %28, %29, %30, %31, %32, %33, %34, %35, %36, %37, %38, %39, %40, %41, %42, %43, %44, %45, %46, %47}, {%56, %57, %58, %59}, tb, p1, 1, 1, 1;\n"
        "add.s64 tb, tb0, 96;\n"
        "wgmma.mma_async.sync.aligned.m64n96k16.f32.bf16.bf16 {%0, %1, %2, %3, %4, %5, %6, %7, %8, %9, %10, %11, %12, %13, %14, %15, %16, %17, %18, %19, %20, %21, %22, %23, %24, %25, %26, %27, %28, %29, %30, %31, %32, %33, %34, %35, %36, %37, %38, %39, %40, %41, %42, %43, %44, %45, %46, %47}, {%60, %61, %62, %63}, tb, p1, 1, 1, 1;\n"
        "}\n"
        : "=f"(d[0]), "=f"(d[1]), "=f"(d[2]), "=f"(d[3]), "=f"(d[4]), "=f"(d[5]), "=f"(d[6]), "=f"(d[7]), "=f"(d[8]), "=f"(d[9]), "=f"(d[10]), "=f"(d[11]), "=f"(d[12]), "=f"(d[13]), "=f"(d[14]), "=f"(d[15]), "=f"(d[16]), "=f"(d[17]), "=f"(d[18]), "=f"(d[19]), "=f"(d[20]), "=f"(d[21]), "=f"(d[22]), "=f"(d[23]), "=f"(d[24]), "=f"(d[25]), "=f"(d[26]), "=f"(d[27]), "=f"(d[28]), "=f"(d[29]), "=f"(d[30]), "=f"(d[31]), "=f"(d[32]), "=f"(d[33]), "=f"(d[34]), "=f"(d[35]), "=f"(d[36]), "=f"(d[37]), "=f"(d[38]), "=f"(d[39]), "=f"(d[40]), "=f"(d[41]), "=f"(d[42]), "=f"(d[43]), "=f"(d[44]), "=f"(d[45]), "=f"(d[46]), "=f"(d[47])
        : "r"(a[AOFF + 0][0]), "r"(a[AOFF + 0][1]), "r"(a[AOFF + 0][2]), "r"(a[AOFF + 0][3]), "r"(a[AOFF + 1][0]), "r"(a[AOFF + 1][1]), "r"(a[AOFF + 1][2]), "r"(a[AOFF + 1][3]), "r"(a[AOFF + 2][0]), "r"(a[AOFF + 2][1]), "r"(a[AOFF + 2][2]), "r"(a[AOFF + 2][3]), "r"(a[AOFF + 3][0]), "r"(a[AOFF + 3][1]), "r"(a[AOFF + 3][2]), "r"(a[AOFF + 3][3]), "l"(descB), "n"(BOFF >> 4));
}
};
template <> struct Rng<1, 0, 4> {
template <int BOFF, int AOFF, int NA>
static __device__ __forceinline__ void run(float (&d)[48], const uint32_t (&a)[NA][4], uint64_t descB) {
    asm volatile(
        "{\n"
        ".reg .pred p0, p1;\n"
        ".reg .b64 ta, ta0, tb, tb0;\n"
        "setp.ne.b32 p0, 0, 0;\n"
        "setp.eq.b32 p1, 0, 0;\n"
        "add.s64 tb0, %64, %65;\n"
        "add.s64 tb, tb0, 0;\n"
        "wgmma.mma_async.sync.aligned.m64n96k16.f32.bf16.bf16 {%0, %1, %2, %3, %4, %5, %6, %7, %8, %9, %10, %11, %12, %13, %14, %15, %16, %17, %18, %19, %20, %21, %22, %23, %24, %25, %26, %27, %28, %29, %30, %31, %32, %33, %34, %35, %36, %37, %38, %39, %40, %41, %42, %43, %44, %45, %46, %47}, {%48, %49, %50, %51}, tb, p0, 1, 1, 1;\n"
        "add.s64 tb, tb0, 32;\n"
        "wgmma.mma_async.sync.aligned.m64n96k16.f32.bf16.bf16 {%0, %1, %2, %3, %4, %5, %6, %7, %8, %9, %10, %11, %12, %13, %14, %15, %16, %17, %18, %19, %20, %21, %22, %23, %24, %25, %26, %27, %28, %29, %30, %31, %32, %33, %34, %35, %36, %37, %38, %39, %40, %41, %42, %43, %44, %45, %46, %47}, {%52, %53, %54, %55}, tb, p1, 1, 1, 1;\n"
        "add.s64 tb, tb0, 64;\n"
        "wgmma.mma_async.sync.aligned.m64n96k16.f32.bf16.bf16 {%0, %1, %2, %3, %4, %5, %6, %7, %8, %9, %10, %11, %12, %13, %14, %15, %16, %17, %18, %19, %20, %21, %22, %23, %24, %25, %26, %27, %28, %29, %30, %31, %32, %33, %34, %35, %36, %37, %38, %39, %40, %41, %42, %43, %44, %45, %46, %47}, {%56, %57, %58, %59}, tb, p1, 1, 1, 1;\n"
        "add.s64 tb, tb0, 96;\n"
        "wgmma.mma_async.sync.aligned.m64n96k16.f32.bf16.bf16 {%0, %1, %2, %3, %4, %5, %6, %7, %8, %9, %10, %11, %12, %13, %14, %15, %16, %17, %18, %19, %20, %21, %22, %23, %24, %25, %26, %27, %28, %29, %30, %31, %32, %33, %34, %35, %36, %37, %38, %39, %40, %41, %42, %43, %44, %45, %46, %47}, {%60, %61, %62, %63}, tb, p1, 1, 1, 1;\n"
        "}\n"
        : "=f"(d[0]), "=f"(d[1]), "=f"(d[2]), "=f"(d[3]), "=f"(d[4]), "=f"(d[5]), "=f"(d[6]), "=f"(d[7]), "=f"(d[8]), "=f"(d[9]), "=f"(d[10]), "=f"(d[11]), "=f"(d[12]), "=f"(d[13]), "=f"(d[14]), "=f"(d[15]), "=f"(d[16]), "=f"(d[17]), "=f"(d[18]), "=f"(d[19]), "=f"(d[20]), "=f"(d[21]), "=f"(d[22]), "=f"(d[23]), "=f"(d[24]), "=f"(d[25]), "=f"(d[26]), "=f"(d[27]), "=f"(d[28]), "=f"(d[29]), "=f"(d[30]), "=f"(d[31]), "=f"(d[32]), "=f"(d[33]), "=f"(d[34]), "=f"(d[35]), "=f"(d[36]), "=f"(d[37]), "=f"(d[38]), "=f"(d[39]), "=f"(d[40]), "=f"(d[41]), "=f"(d[42]), "=f"(d[43]), "=f"(d[44]), "=f"(d[45]), "=f"(d[46]), "=f"(d[47])
        : "r"(a[AOFF + 0][0]), "r"(a[AOFF + 0][1]), "r"(a[AOFF + 0][2]), "r"(a[AOFF + 0][3]), "r"(a[AOFF + 1][0]), "r"(a[AOFF + 1][1]), "r"(a[AOFF + 1][2]), "r"(a[AOFF + 1][3]), "r"(a[AOFF + 2][0]), "r"(a[AOFF + 2][1]), "r"(a[AOFF + 2][2]), "r"(a[AOFF + 2][3]), "r"(a[AOFF + 3][0]), "r"(a[AOFF + 3][1]), "r"(a[AOFF + 3][2]), "r"(a[AOFF + 3][3]), "l"(descB), "n"(BOFF >> 4));
}
};
template <> struct Rng<0, 0, 5> {
template <int BOFF, int AOFF, int NA>
static __device__ __forceinline__ void run(float (&d)[48], const uint32_t (&a)[NA][4], uint64_t descB) {
    asm volatile(
        "{\n"
        ".reg .pred p0, p1;\n"
        ".reg .b64 ta, ta0, tb, tb0;\n"
        "setp.ne.b32 p0, 0, 0;\n"
        "setp.eq.b32 p1, 0, 0;\n"
        "add.s64 tb0, %68, %69;\n"
        "add.s64 tb, tb0, 0;\n"
        "wgmma.mma_async.sync.aligned.m64n96k16.f32.bf16.bf16 {%0, %1, %2, %3, %4, %5, %6, %7, %8, %9, %10, %11, %12, %13, %14, %15, %16, %17, %18, %19, %20, %21, %22, %23, %24, %25, %26, %27, %28, %29, %30, %31, %32, %33, %34, %35, %36, %37, %38, %39, %40, %41, %42, %43, %44, %45, %46, %47}, {%48, %49, %50, %51}, tb, p0, 1, 1, 1;\n"
        "add.s64 tb, tb0, 32;\n"
        "wgmma.mma_async.sync.aligned.m64n96k16.f32.bf16.bf16 {%0, %1, %2, %3, %4, %5, %6, %7, %8, %9, %10, %11, %12, %13, %14, %15, %16, %17, %18, %19, %20, %21, %22, %23, %24, %25, %26, %27, %28, %29, %30, %31, %32, %33, %34, %35, %36, %37, %38, %39, %40, %41, %42, %43, %44, %45, %46, %47}, {%52, %53, %54, %55}, tb, p1, 1, 1, 1;\n"
        "add.s64 tb, tb0, 64;\n"
        "wgmma.mma_async.sync.aligned.m64n96k16.f32.bf16.bf16 {%0, %1, %2, %3, %4, %5, %6, %7, %8, %9, %10, %11, %12, %13, %14, %15, %16, %17, %18, %19, %20, %21, %22, %23, %24, %25, %26, %27, %28, %29, %30, %31, %32, %33, %34, %35, %36, %37, %38, %39, %40, %41, %42, %43, %44, %45, %46, %47}, {%56, %57, %58, %59}, tb, p1, 1, 1, 1;\n"
        "add.s64 tb, tb0, 96;\n"
        "wgmma.mma_async.sync.aligned.m64n96k16.f32.bf16.bf16 {%0, %1, %2, %3, %4, %5, %6, %7, %8, %9, %10, %11, %12, %13, %14, %15, %16, %17, %18, %19, %20, %21, %22, %23, %24, %25, %26, %27, %28, %29, %30, %31, %32, %33, %34, %35, %36, %37, %38, %39, %40, %41, %42, %43, %44, %45, %46, %47}, {%60, %61, %62, %63}, tb, p1, 1, 1, 1;\n"
        "add.s64 tb, tb0, 1536;\n"
        "wgmma.mma_async.sync.aligned.m64n96k16.f32.bf16.bf16 {%0, %1, %2, %3, %4, %5, %6, %7, %8, %9, %10, %11, %12, %13, %14, %15, %16, %17, %18, %19, %20, %21, %22, %23, %24, %25, %26, %27, %28, %29, %30, %31, %32, %33, %34, %35, %36, %37, %38, %39, %40, %41, %42, %43, %44, %45, %46, %47}, {%64, %65, %66, %67}, tb, p1, 1, 1, 1;\n"
        "}\n"
        : "=f"(d[0]), "=f"(d[1]), "=f"(d[2]), "=f"(d[3]), "=f"(d[4]), "=f"(d[5]), "=f"(d[6]), "=f"(d[7]), "=f"(d[8]), "=f"(d[9]), "=f"(d[10]), "=f"(d[11]), "=f"(d[12]), "=f"(d[13]), "=f"(d[14]), "=f"(d[15]), "=f"(d[16]), "=f"(d[17]), "=f"(d[18]), "=f"(d[19]), "=f"(d[20]), "=f"(d[21]), "=f"(d[22]), "=f"(d[23]), "=f"(d[24]), "=f"(d[25]), "=f"(d[26]), "=f"(d[27]), "=f"(d[28]), "=f"(d[29]), "=f"(d[30]), "=f"(d[31]), "=f"(d[32]), "=f"(d[33]), "=f"(d[34]), "=f"(d[35]), "=f"(d[36]), "=f"(d[37]), "=f"(d[38]), "=f"(d[39]), "=f"(d[40]), "=f"(d[41]), "=f"(d[42]), "=f"(d[43]), "=f"(d[44]), "=f"(d[45]), "=f"(d[46]), "=f"(d[47])
        : "r"(a[AOFF + 0][0]), "r"(a[AOFF + 0][1]), "r"(a[AOFF + 0][2]), "r"(a[AOFF + 0][3]), "r"(a[AOFF + 1][0]), "r"(a[AOFF + 1][1]), "r"(a[AOFF + 1][2]), "r"(a[AOFF + 1][3]), "r"(a[AOFF + 2][0]), "r"(a[AOFF + 2][1]), "r"(a[AOFF + 2][2]), "r"(a[AOFF + 2][3]), "r"(a[AOFF + 3][0]), "r"(a[AOFF + 3][1]), "r"(a[AOFF + 3][2]), "r"(a[AOFF + 3][3]), "r"(a[AOFF + 4][0]), "r"(a[AOFF + 4][1]), "r"(a[AOFF + 4][2]), "r"(a[AOFF + 4][3]), "l"(descB), "n"(BOFF >> 4));
}
};
template <> struct Rng<1, 0, 5> {
template <int BOFF, int AOFF, int NA>
static __device__ __forceinline__ void run(float (&d)[48], const uint32_t (&a)[NA][4], uint64_t descB) {
    asm volatile(
        "{\n"
        ".reg .pred p0, p1;\n"
        ".reg .b64 ta, ta0, tb, tb0;\n"
        "setp.ne.b32 p0, 0, 0;\n"
        "setp.eq.b32 p1, 0, 0;\n"
        "add.s64 tb0, %68, %69;\n"
        "add.s64 tb, tb0, 0;\n"
        "wgmma.mma_async.sync.aligned.m64n96k16.f32.bf16.bf16 {%0, %1, %2, %3, %4, %5, %6, %7, %8, %9, %10, %11, %12, %13, %14, %15, %16, %17, %18, %19, %20, %21, %22, %23, %24, %25, %26, %27, %28, %29, %30, %31, %32, %33, %34, %35, %36, %37, %38, %39, %40, %41, %42, %43, %44, %45, %46, %47}, {%48, %49, %50, %51}, tb, p0, 1, 1, 1;\n"
        "add.s64 tb, tb0, 32;\n"
        "wgmma.mma_async.sync.aligned.m64n96k16.f32.bf16.bf16 {%0, %1, %2, %3, %4, %5, %6, %7, %8, %9, %10, %11, %12, %13, %14, %15, %16, %17, %18, %19, %20, %21, %22, %23, %24, %25, %26, %27, %28, %29, %30, %31, %32, %33, %34, %35, %36, %37, %38, %39, %40, %41, %42, %43, %44, %45, %46, %47}, {%52, %53, %54, %55}, tb, p1, 1, 1, 1;\n"
        "add.s64 tb, tb0, 64;\n"
        "wgmma.mma_async.sync.aligned.m64n96k16.f32.bf16.bf16 {%0, %1, %2, %3, %4, %5, %6, %7, %8, %9, %10, %11, %12, %13, %14, %15, %16, %17, %18, %19, %20, %21, %22, %23, %24, %25, %26, %27, %28, %29, %30, %31, %32, %33, %34, %35, %36, %37, %38, %39, %40, %41, %42, %43, %44, %45, %46, %47}, {%56, %57, %58, %59}, tb, p1, 1, 1, 1;\n"
        "add.s64 tb, tb0, 96;\n"
        "wgmma.mma_async.sync.aligned.m64n96k16.f32.bf16.bf16 {%0, %1, %2, %3, %4, %5, %6, %7, %8, %9, %10, %11, %12, %13, %14, %15, %16, %17, %18, %19, %20, %21, %22, %23, %24, %25, %26, %27, %28, %29, %30, %31, %32, %33, %34, %35, %36, %37, %38, %39, %40, %41, %42, %43, %44, %45, %46, %47}, {%60, %61, %62, %63}, tb, p1, 1, 1, 1;\n"
        "add.s64 tb, tb0, 128;\n"
        "wgmma.mma_async.sync.aligned.m64n96k16.f32.bf16.bf16 {%0, %1, %2, %3, %4, %5, %6, %7, %8, %9, %10, %11, %12, %13, %14, %15, %16, %17, %18, %19, %20, %21, %22, %23, %24, %25, %26, %27, %28, %29, %30, %31, %32, %33, %34, %35, %36, %37, %38, %39, %40, %41, %42, %43, %44, %45, %46, %47}, {%64, %65, %66, %67}, tb, p1, 1, 1, 1;\n"
        "}\n"
        : "=f"(d[0]), "=f"(d[1]), "=f"(d[2]), "=f"(d[3]), "=f"(d[4]), "=f"(d[5]), "=f"(d[6]), "=f"(d[7]), "=f"(d[8]), "=f"(d[9]), "=f"(d[10]), "=f"(d[11]), "=f"(d[12]), "=f"(d[13]), "=f"(d[14]), "=f"(d[15]), "=f"(d[16]), "=f"(d[17]), "=f"(d[18]), "=f"(d[19]), "=f"(d[20]), "=f"(d[21]), "=f"(d[22]), "=f"(d[23]), "=f"(d[24]), "=f"(d[25]), "=f"(d[26]), "=f"(d[27]), "=f"(d[28]), "=f"(d[29]), "=f"(d[30]), "=f"(d[31]), "=f"(d[32]), "=f"(d[33]), "=f"(d[34]), "=f"(d[35]), "=f"(d[36]), "=f"(d[37]), "=f"(d[38]), "=f"(d[39]), "=f"(d[40]), "=f"(d[41]), "=f"(d[42]), "=f"(d[43]), "=f"(d[44]), "=f"(d[45]), "=f"(d[46]), "=f"(d[47])
        : "r"(a[AOFF + 0][0]), "r"(a[AOFF + 0][1]), "r"(a[AOFF + 0][2]), "r"(a[AOFF + 0][3]), "r"(a[AOFF + 1][0]), "r"(a[AOFF + 1][1]), "r"(a[AOFF + 1][2]), "r"(a[AOFF + 1][3]), "r"(a[AOFF + 2][0]), "r"(a[AOFF + 2][1]), "r"(a[AOFF + 2][2]), "r"(a[AOFF + 2][3]), "r"(a[AOFF + 3][0]), "r"(a[AOFF + 3][1]), "r"(a[AOFF + 3][2]), "r"(a[AOFF + 3][3]), "r"(a[AOFF + 4][0]), "r"(a[AOFF + 4][1]), "r"(a[AOFF + 4][2]), "r"(a[AOFF + 4][3]), "l"(descB), "n"(BOFF >> 4));
}
};
template <> struct Rng<0, 0, 6> {
template <int BOFF, int AOFF, int NA>
static __device__ __forceinline__ void run(float (&d)[48], const uint32_t (&a)[NA][4], uint64_t descB) {
    asm volatile(
        "{\n"
        ".reg .pred p0, p1;\n"
        ".reg .b64 ta, ta0, tb, tb0;\n"
        "setp.ne.b32 p0, 0, 0;\n"
        "setp.eq.b32 p1, 0, 0;\n"
        "add.s64 tb0, %72, %73;\n"
        "add.s64 tb, tb0, 0;\n"
        "wgmma.mma_async.sync.aligned.m64n96k16.f32.bf16.bf16 {%0, %1, %2, %3, %4, %5, %6, %7, %8, %9, %10, %11, %12, %13, %14, %15, %16, %17, %18, %19, %20, %21, %22, %23, %24, %25, %26, %27, %28, %29, %30, %31, %32, %33, %34, %35, %36, %37, %38, %39, %40, %41, %42, %43, %44, %45, %46, %47}, {%48, %49, %50, %51}, tb, p0, 1, 1, 1;\n"
        "add.s64 tb, tb0, 32;\n"
        "wgmma.mma_async.sync.aligned.m64n96k16.f32.bf16.bf16 {%0, %1, %2, %3, %4, %5, %6, %7, %8, %9, %10, %11, %12, %13, %14, %15, %16, %17, %18, %19, %20, %21, %22, %23, %24, %25, %26, %27, %28, %29, %30, %31, %32, %33, %34, %35, %36, %37, %38, %39, %40, %41, %42, %43, %44, %45, %46, %47}, {%52, %53, %54, %55}, tb, p1, 1, 1, 1;\n"
        "add.s64 tb, tb0, 64;\n"
        "wgmma.mma_async.sync.aligned.m64n96k16.f32.bf16.bf16 {%0, %1, %2, %3, %4, %5, %6, %7, %8, %9, %10, %11, %12, %13, %14, %15, %16, %17, %18, %19, %20, %21, %22, %23, %24, %25, %26, %27, %28, %29, %30, %31, %32, %33, %34, %35, %36, %37, %38, %39, %40, %41, %42, %43, %44, %45, %46, %47}, {%56, %57, %58, %59}, tb, p1, 1, 1, 1;\n"
        "add.s64 tb, tb0, 96;\n"
        "wgmma.mma_async.sync.aligned.m64n96k16.f32.bf16.bf16 {%0, %1, %2, %3, %4, %5, %6, %7, %8, %9, %10, %11, %12, %13, %14, %15, %16, %17, %18, %19, %20, %21, %22, %23, %24, %25, %26, %27, %28, %29, %30, %31, %32, %33, %34, %35, %36, %37, %38, %39, %40, %41, %42, %43, %44, %45, %46, %47}, {%60, %61, %62, %63}, tb, p1, 1, 1, 1;\n"
        "add.s64 tb, tb0, 1536;\n"
        "wgmma.mma_async.sync.aligned.m64n96k16.f32.bf16.bf16 {%0, %1, %2, %3, %4, %5, %6, %7, %8, %9, %10, %11, %12, %13, %14, %15, %16, %17, %18, %19, %20, %21, %22, %23, %24, %25, %26, %27, %28, %29, %30, %31, %32, %33, %34, %35, %36, %37, %38, %39, %40, %41, %42, %43, %44, %45, %46, %47}, {%64, %65, %66, %67}, tb, p1, 1, 1, 1;\n"
        "add.s64 tb, tb0, 1568;\n"
        "wgmma.mma_async.sync.aligned.m64n96k16.f32.bf16.bf16 {%0, %1, %2, %3, %4, %5, %6, %7, %8, %9, %10, %11, %12, %13, %14, %15, %16, %17, %18, %19, %20, %21, %22, %23, %24, %25, %26, %27, %28, %29, %30, %31, %32, %33, %34, %35, %36, %37, %38, %39, %40, %41, %42, %43, %44, %45, %46, %47}, {%68, %69, %70, %71}, tb, p1, 1, 1, 1;\n"
        "}\n"
        : "=f"(d[0]), "=f"(d[1]), "=f"(d[2]), "=f"(d[3]), "=f"(d[4]), "=f"(d[5]), "=f"(d[6]), "=f"(d[7]), "=f"(d[8]), "=f"(d[9]), "=f"(d[10]), "=f"(d[11]), "=f"(d[12]), "=f"(d[13]), "=f"(d[14]), "=f"(d[15]), "=f"(d[16]), "=f"(d[17]), "=f"(d[18]), "=f"(d[19]), "=f"(d[20]), "=f"(d[21]), "=f"(d[22]), "=f"(d[23]), "=f"(d[24]), "=f"(d[25]), "=f"(d[26]), "=f"(d[27]), "=f"(d[28]), "=f"(d[29]), "=f"(d[30]), "=f"(d[31]), "=f"(d[32]), "=f"(d[33]), "=f"(d[34]), "=f"(d[35]), "=f"(d[36]), "=f"(d[37]), "=f"(d[38]), "=f"(d[39]), "=f"(d[40]), "=f"(d[41]), "=f"(d[42]), "=f"(d[43]), "=f"(d[44]), "=f"(d[45]), "=f"(d[46]), "=f"(d[47])
        : "r"(a[AOFF + 0][0]), "r"(a[AOFF + 0][1]), "r"(a[AOFF + 0][2]), "r"(a[AOFF + 0][3]), "r"(a[AOFF + 1][0]), "r"(a[AOFF + 1][1]), "r"(a[AOFF + 1][2]), "r"(a[AOFF + 1][3]), "r"(a[AOFF + 2][0]), "r"(a[AOFF + 2][1]), "r"(a[AOFF + 2][2]), "r"(a[AOFF + 2][3]), "r"(a[AOFF + 3][0]), "r"(a[AOFF + 3][1]), "r"(a[AOFF + 3][2]), "r"(a[AOFF + 3][3]), "r"(a[AOFF + 4][0]), "r"(a[AOFF + 4][1]), "r"(a[AOFF + 4][2]), "r"(a[AOFF + 4][3]), "r"(a[AOFF + 5][0]), "r"(a[AOFF + 5][1]), "r"(a[AOFF + 5][2]), "r"(a[AOFF + 5][3]), "l"(descB), "n"(BOFF >> 4));
}
};
template <> struct Rng<1, 0, 6> {
template <int BOFF, int AOFF, int NA>
static __device__ __forceinline__ void run(float (&d)[48], const uint32_t (&a)[NA][4], uint64_t descB) {
    asm volatile(
        "{\n"
        ".reg .pred p0, p1;\n"
        ".reg .b64 ta, ta0, tb, tb0;\n"
        "setp.ne.b32 p0, 0, 0;\n"
        "setp.eq.b32 p1, 0, 0;\n"
        "add.s64 tb0, %72, %73;\n"
        "add.s64 tb, tb0, 0;\n"
        "wgmma.mma_async.sync.aligned.m64n96k16.f32.bf16.bf16 {%0, %1, %2, %3, %4, %5, %6, %7, %8, %9, %10, %11, %12, %13, %14, %15, %16, %17, %18, %19, %20, %21, %22, %23, %24, %25, %26, %27, %28, %29, %30, %31, %32, %33, %34, %35, %36, %37, %38, %39, %40, %41, %42, %43, %44, %45, %46, %47}, {%48, %49, %50, %51}, tb, p0, 1, 1, 1;\n"
        "add.s64 tb, tb0, 32;\n"
        "wgmma.mma_async.sync.aligned.m64n96k16.f32.bf16.bf16 {%0, %1, %2, %3, %4, %5, %6, %7, %8, %9, %10, %11, %12, %13, %14, %15, %16, %17, %18, %19, %20, %21, %22, %23, %24, %25, %26, %27, %28, %29, %30, %31, %32, %33, %34, %35, %36, %37, %38, %39, %40, %41, %42, %43, %44, %45, %46, %47}, {%52, %53, %54, %55}, tb, p1, 1, 1, 1;\n"
        "add.s64 tb, tb0, 64;\n"
        "wgmma.mma_async.sync.aligned.m64n96k16.f32.bf16.bf16 {%0, %1, %2, %3, %4, %5, %6, %7, %8, %9, %10, %11, %12, %13, %14, %15, %16, %17, %18, %19, %20, %21, %22, %23, %24, %25, %26, %27, %28, %29, %30, %31, %32, %33, %34, %35, %36, %37, %38, %39, %40, %41, %42, %43, %44, %45, %46, %47}, {%56, %57, %58, %59}, tb, p1, 1, 1, 1;\n"
        "add.s64 tb, tb0, 96;\n"
        "wgmma.mma_async.sync.aligned.m64n96k16.f32.bf16.bf16 {%0, %1, %2, %3, %4, %5, %6, %7, %8, %9, %10, %11, %12, %13, %14, %15, %16, %17, %18, %19, %20, %21, %22, %23, %24, %25, %26, %27, %28, %29, %30, %31, %32, %33, %34, %35, %36, %37, %38, %39, %40, %41, %42, %43, %44, %45, %46, %47}, {%60, %61, %62, %63}, tb, p1, 1, 1, 1;\n"
        "add.s64 tb, tb0, 128;\n"
        "wgmma.mma_async.sync.aligned.m64n96k16.f32.bf16.bf16 {%0, %1, %2, %3, %4, %5, %6, %7, %8, %9, %10, %11, %12, %13, %14, %15, %16, %17, %18, %19, %20, %21, %22, %23, %24, %25, %26, %27, %28, %29, %30, %31, %32, %33, %34, %35, %36, %37, %38, %39, %40, %41, %42, %43, %44, %45, %46, %47}, {%64, %65, %66, %67}, tb, p1, 1, 1, 1;\n"
        "add.s64 tb, tb0, 160;\n"
        "wgmma.mma_async.sync.aligned.m64n96k16.f32.bf16.bf16 {%0, %1, %2, %3, %4, %5, %6, %7, %8, %9, %10, %11, %12, %13, %14, %15, %16, %17, %18, %19, %20, %21, %22, %23, %24, %25, %26, %27, %28, %29, %30, %31, %32, %33, %34, %35, %36, %37, %38, %39, %40, %41, %42, %43, %44, %45, %46, %47}, {%68, %69, %70, %71}, tb, p1, 1, 1, 1;\n"
        "}\n"
        : "=f"(d[0]), "=f"(d[1]), "=f"(d[2]), "=f"(d[3]), "=f"(d[4]), "=f"(d[5]), "=f"(d[6]), "=f"(d[7]), "=f"(d[8]), "=f"(d[9]), "=f"(d[10]), "=f"(d[11]), "=f"(d[12]), "=f"(d[13]), "=f"(d[14]), "=f"(d[15]), "=f"(d[16]), "=f"(d[17]), "=f"(d[18]), "=f"(d[19]), "=f"(d[20]), "=f"(d[21]), "=f"(d[22]), "=f"(d[23]), "=f"(d[24]), "=f"(d[25]), "=f"(d[26]), "=f"(d[27]), "=f"(d[28]), "=f"(d[29]), "=f"(d[30]), "=f"(d[31]), "=f"(d[32]), "=f"(d[33]), "=f"(d[34]), "=f"(d[35]), "=f"(d[36]), "=f"(d[37]), "=f"(d[38]), "=f"(d[39]), "=f"(d[40]), "=f"(d[41]), "=f"(d[42]), "=f"(d[43]), "=f"(d[44]), "=f"(d[45]), "=f"(d[46]), "=f"(d[47])
        : "r"(a[AOFF + 0][0]), "r"(a[AOFF + 0][1]), "r"(a[AOFF + 0][2]), "r"(a[AOFF + 0][3]), "r"(a[AOFF + 1][0]), "r"(a[AOFF + 1][1]), "r"(a[AOFF + 1][2]), "r"(a[AOFF + 1][3]), "r"(a[AOFF + 2][0]), "r"(a[AOFF + 2][1]), "r"(a[AOFF + 2][2]), "r"(a[AOFF + 2][3]), "r"(a[AOFF + 3][0]), "r"(a[AOFF + 3][1]), "r"(a[AOFF + 3][2]), "r"(a[AOFF + 3][3]), "r"(a[AOFF + 4][0]), "r"(a[AOFF + 4][1]), "r"(a[AOFF + 4][2]), "r"(a[AOFF + 4][3]), "r"(a[AOFF + 5][0]), "r"(a[AOFF + 5][1]), "r"(a[AOFF + 5][2]), "r"(a[AOFF + 5][3]), "l"(descB), "n"(BOFF >> 4));
}
};
template <> struct Rng<0, 3, 7> {
template <int BOFF, int AOFF, int NA>
static __device__ __forceinline__ void run(float (&d)[48], const uint32_t (&a)[NA][4], uint64_t descB) {
    asm volatile(
        "{\n"
        ".reg .pred p0, p1;\n"
        ".reg .b64 ta, ta0, tb, tb0;\n"
        "setp.ne.b32 p0, 0, 0;\n"
        "setp.eq.b32 p1, 0, 0;\n"
        "add.s64 tb0, %64, %65;\n"
        "add.s64 tb, tb0, 96;\n"
        "wgmma.mma_async.sync.aligned.m64n96k16.f32.bf16.bf16 {%0, %1, %2, %3, %4, %5, %6, %7, %8, %9, %10, %11, %12, %13, %14, %15, %16, %17, %18, %19, %20, %21, %22, %23, %24, %25, %26, %27, %28, %29, %30, %31, %32, %33, %34, %35, %36, %37, %38, %39, %40, %41, %42, %43, %44, %45, %46, %47}, {%48, %49, %50, %51}, tb, p1, 1, 1, 1;\n"
        "add.s64 tb, tb0, 1536;\n"
        "wgmma.mma_async.sync.aligned.m64n96k16.f32.bf16.bf16 {%0, %1, %2, %3, %4, %5, %6, %7, %8, %9, %10, %11, %12, %13, %14, %15, %16, %17, %18, %19, %20, %21, %22, %23, %24, %25, %26, %27, %28, %29, %30, %31, %32, %33, %34, %35, %36, %37, %38, %39, %40, %41, %42, %43, %44, %45, %46, %47}, {%52, %53, %54, %55}, tb, p1, 1, 1, 1;\n"
        "add.s64 tb, tb0, 1568;\n"
        "wgmma.mma_async.sync.aligned.m64n96k16.f32.bf16.bf16 {%0, %1, %2, %3, %4, %5, %6, %7, %8, %9, %10, %11, %12, %13, %14, %15, %16, %17, %18, %19, %20, %21, %22, %23, %24, %25, %26, %27, %28, %29, %30, %31, %32, %33, %34, %35, %36, %37, %38, %39, %40, %41, %42, %43, %44, %45, %46, %47}, {%56, %57, %58, %59}, tb, p1, 1, 1, 1;\n"
        "add.s64 tb, tb0, 1600;\n"
        "wgmma.mma_async.sync.aligned.m64n96k16.f32.bf16.bf16 {%0, %1, %2, %3, %4, %5, %6, %7, %8, %9, %10, %11, %12, %13, %14, %15, %16, %17, %18, %19, %20, %21, %22, %23, %24, %25, %26, %27, %28, %29, %30, %31, %32, %33, %34, %35, %36, %37, %38, %39, %40, %41, %42, %43, %44, %45, %46, %47}, {%60, %61, %62, %63}, tb, p1, 1, 1, 1;\n"
        "}\n"
        : "+f"(d[0]), "+f"(d[1]), "+f"(d[2]), "+f"(d[3]), "+f"(d[4]), "+f"(d[5]), "+f"(d[6]), "+f"(d[7]), "+f"(d[8]), "+f"(d[9]), "+f"(d[10]), "+f"(d[11]), "+f"(d[12]), "+f"(d[13]), "+f"(d[14]), "+f"(d[15]), "+f"(d[16]), "+f"(d[17]), "+f"(d[18]), "+f"(d[19]), "+f"(d[20]), "+f"(d[21]), "+f"(d[22]), "+f"(d[23]), "+f"(d[24]), "+f"(d[25]), "+f"(d[26]), "+f"(d[27]), "+f"(d[28]), "+f"(d[29]), "+f"(d[30]), "+f"(d[31]), "+f"(d[32]), "+f"(d[33]), "+f"(d[34]), "+f"(d[35]), "+f"(d[36]), "+f"(d[37]), "+f"(d[38]), "+f"(d[39]), "+f"(d[40]), "+f"(d[41]), "+f"(d[42]), "+f"(d[43]), "+f"(d[44]), "+f"(d[45]), "+f"(d[46]), "+f"(d[47])
        : "r"(a[AOFF + 0][0]), "r"(a[AOFF + 0][1]), "r"(a[AOFF + 0][2]), "r"(a[AOFF + 0][3]), "r"(a[AOFF + 1][0]), "r"(a[AOFF + 1][1]), "r"(a[AOFF + 1][2]), "r"(a[AOFF + 1][3]), "r"(a[AOFF + 2][0]), "r"(a[AOFF + 2][1]), "r"(a[AOFF + 2][2]), "r"(a[AOFF + 2][3]), "r"(a[AOFF + 3][0]), "r"(a[AOFF + 3][1]), "r"(a[AOFF + 3][2]), "r"(a[AOFF + 3][3]), "l"(descB), "n"(BOFF >> 4));
}
};
template <> struct Rng<1, 3, 7> {
template <int BOFF, int AOFF, int NA>
static __device__ __forceinline__ void run(float (&d)[48], const uint32_t (&a)[NA][4], uint64_t descB) {
    asm volatile(
        "{\n"
        ".reg .pred p0, p1;\n"
        ".reg .b64 ta, ta0, tb, tb0;\n"
        "setp.ne.b32 p0, 0, 0;\n"
        "setp.eq.b32 p1, 0, 0;\n"
        "add.s64 tb0, %64, %65;\n"
        "add.s64 tb, tb0, 96;\n"
        "wgmma.mma_async.sync.aligned.m64n96k16.f32.bf16.bf16 {%0, %1, %2, %3, %4, %5, %6, %7, %8, %9, %10, %11, %12, %13, %14, %15, %16, %17, %18, %19, %20, %21, %22, %23, %24, %25, %26, %27, %28, %29, %30, %31, %32, %33, %34, %35, %36, %37, %38, %39, %40, %41, %42, %43, %44, %45, %46, %47}, {%48, %49, %50, %51}, tb, p1, 1, 1, 1;\n"
        "add.s64 tb, tb0, 128;\n"
        "wgmma.mma_async.sync.aligned.m64n96k16.f32.bf16.bf16 {%0, %1, %2, %3, %4, %5, %6, %7, %8, %9, %10, %11, %12, %13, %14, %15, %16, %17, %18, %19, %20, %21, %22, %23, %24, %25, %26, %27, %28, %29, %30, %31, %32, %33, %34, %35, %36, %37, %38, %39, %40, %41, %42, %43, %44, %45, %46, %47}, {%52, %53, %54, %55}, tb, p1, 1, 1, 1;\n"
        "add.s64 tb, tb0, 160;\n"
        "wgmma.mma_async.sync.aligned.m64n96k16.f32.bf16.bf16 {%0, %1, %2, %3, %4, %5, %6, %7, %8, %9, %10, %11, %12, %13, %14, %15, %16, %17, %18, %19, %20, %21, %22, %23, %24, %25, %26, %27, %28, %29, %30, %31, %32, %33, %34, %35, %36, %37, %38, %39, %40, %41, %42, %43, %44, %45, %46, %47}, {%56, %57, %58, %59}, tb, p1, 1, 1, 1;\n"
        "add.s64 tb, tb0, 192;\n"
        "wgmma.mma_async.sync.aligned.m64n96k16.f32.bf16.bf16 {%0, %1, %2, %3, %4, %5, %6, %7, %8, %9, %10, %11, %12, %13, %14, %15, %16, %17, %18, %19, %20, %21, %22, %23, %24, %25, %26, %27, %28, %29, %30, %31, %32, %33, %34, %35, %36, %37, %38, %39, %40, %41, %42, %43, %44, %45, %46, %47}, {%60, %61, %62, %63}, tb, p1, 1, 1, 1;\n"
        "}\n"
        : "+f"(d[0]), "+f"(d[1]), "+f"(d[2]), "+f"(d[3]), "+f"(d[4]), "+f"(d[5]), "+f"(d[6]), "+f"(d[7]), "+f"(d[8]), "+f"(d[9]), "+f"(d[10]), "+f"(d[11]), "+f"(d[12]), "+f"(d[13]), "+f"(d[14]), "+f"(d[15]), "+f"(d[16]), "+f"(d[17]), "+f"(d[18]), "+f"(d[19]), "+f"(d[20]), "+f"(d[21]), "+f"(d[22]), "+f"(d[23]), "+f"(d[24]), "+f"(d[25]), "+f"(d[26]), "+f"(d[27]), "+f"(d[28]), "+f"(d[29]), "+f"(d[30]), "+f"(d[31]), "+f"(d[32]), "+f"(d[33]), "+f"(d[34]), "+f"(d[35]), "+f"(d[36]), "+f"(d[37]), "+f"(d[38]), "+f"(d[39]), "+f"(d[40]), "+f"(d[41]), "+f"(d[42]), "+f"(d[43]), "+f"(d[44]), "+f"(d[45]), "+f"(d[46]), "+f"(d[47])
        : "r"(a[AOFF + 0][0]), "r"(a[AOFF + 0][1]), "r"(a[AOFF + 0][2]), "r"(a[AOFF + 0][3]), "r"(a[AOFF + 1][0]), "r"(a[AOFF + 1][1]), "r"(a[AOFF + 1][2]), "r"(a[AOFF + 1][3]), "r"(a[AOFF + 2][0]), "r"(a[AOFF + 2][1]), "r"(a[AOFF + 2][2]), "r"(a[AOFF + 2][3]), "r"(a[AOFF + 3][0]), "r"(a[AOFF + 3][1]), "r"(a[AOFF + 3][2]), "r"(a[AOFF + 3][3]), "l"(descB), "n"(BOFF >> 4));
}
};
template <> struct Rng<0, 3, 8> {
template <int BOFF, int AOFF, int NA>
static __device__ __forceinline__ void run(float (&d)[48], const uint32_t (&a)[NA][4], uint64_t descB) {
    asm volatile(
        "{\n"
        ".reg .pred p0, p1;\n"
        ".reg .b64 ta, ta0, tb, tb0;\n"
        "setp.ne.b32 p0, 0, 0;\n"
        "setp.eq.b32 p1, 0, 0;\n"
        "add.s64 tb0, %68, %69;\n"
        "add.s64 tb, tb0, 96;\n"
        "wgmma.mma_async.sync.aligned.m64n96k16.f32.bf16.bf16 {%0, %1, %2, %3, %4, %5, %6, %7, %8, %9, %10, %11, %12, %13, %14, %15, %16, %17, %18, %19, %20, %21, %22, %23, %24, %25, %26, %27, %28, %29, %30, %31, %32, %33, %34, %35, %36, %37, %38, %39, %40, %41, %42, %43, %44, %45, %46, %47}, {%48, %49, %50, %51}, tb, p1, 1, 1, 1;\n"
        "add.s64 tb, tb0, 1536;\n"
        "wgmma.mma_async.sync.aligned.m64n96k16.f32.bf16.bf16 {%0, %1, %2, %3, %4, %5, %6, %7, %8, %9, %10, %11, %12, %13, %14, %15, %16, %17, %18, %19, %20, %21, %22, %23, %24, %25, %26, %27, %28, %29, %30, %31, %32, %33, %34, %35, %36, %37, %38, %39, %40, %41, %42, %43, %44, %45, %46, %47}, {%52, %53, %54, %55}, tb, p1, 1, 1, 1;\n"
        "add.s64 tb, tb0, 1568;\n"
        "wgmma.mma_async.sync.aligned.m64n96k16.f32.bf16.bf16 {%0, %1, %2, %3, %4, %5, %6, %7, %8, %9, %10, %11, %12, %13, %14, %15, %16, %17, %18, %19, %20, %21, %22, %23, %24, %25, %26, %27, %28, %29, %30, %31, %32, %33, %34, %35, %36, %37, %38, %39, %40, %41, %42, %43, %44, %45, %46, %47}, {%56, %57, %58, %59}, tb, p1, 1, 1, 1;\n"
        "add.s64 tb, tb0, 1600;\n"
        "wgmma.mma_async.sync.aligned.m64n96k16.f32.bf16.bf16 {%0, %1, %2, %3, %4, %5, %6, %7, %8, %9, %10, %11, %12, %13, %14, %15, %16, %17, %18, %19, %20, %21, %22, %23, %24, %25, %26, %27, %28, %29, %30, %31, %32, %33, %34, %35, %36, %37, %38, %39, %40, %41, %42, %43, %44, %45, %46, %47}, {%60, %61, %62, %63}, tb, p1, 1, 1, 1;\n"
        "add.s64 tb, tb0, 1632;\n"
        "wgmma.mma_async.sync.aligned.m64n96k16.f32.bf16.bf16 {%0, %1, %2, %3, %4, %5, %6, %7, %8, %9, %10, %11, %12, %13, %14, %15, %16, %17, %18, %19, %20, %21, %22, %23, %24, %25, %26, %27, %28, %29, %30, %31, %32, %33, %34, %35, %36, %37, %38, %39, %40, %41, %42, %43, %44, %45, %46, %47}, {%64, %65, %66, %67}, tb, p1, 1, 1, 1;\n"
        "}\n"
        : "+f"(d[0]), "+f"(d[1]), "+f"(d[2]), "+f"(d[3]), "+f"(d[4]), "+f"(d[5]), "+f"(d[6]), "+f"(d[7]), "+f"(d[8]), "+f"(d[9]), "+f"(d[10]), "+f"(d[11]), "+f"(d[12]), "+f"(d[13]), "+f"(d[14]), "+f"(d[15]), "+f"(d[16]), "+f"(d[17]), "+f"(d[18]), "+f"(d[19]), "+f"(d[20]), "+f"(d[21]), "+f"(d[22]), "+f"(d[23]), "+f"(d[24]), "+f"(d[25]), "+f"(d[26]), "+f"(d[27]), "+f"(d[28]), "+f"(d[29]), "+f"(d[30]), "+f"(d[31]), "+f"(d[32]), "+f"(d[33]), "+f"(d[34]), "+f"(d[35]), "+f"(d[36]), "+f"(d[37]), "+f"(d[38]), "+f"(d[39]), "+f"(d[40]), "+f"(d[41]), "+f"(d[42]), "+f"(d[43]), "+f"(d[44]), "+f"(d[45]), "+f"(d[46]), "+f"(d[47])
        : "r"(a[AOFF + 0][0]), "r"(a[AOFF + 0][1]), "r"(a[AOFF + 0][2]), "r"(a[AOFF + 0][3]), "r"(a[AOFF + 1][0]), "r"(a[AOFF + 1][1]), "r"(a[AOFF + 1][2]), "r"(a[AOFF + 1][3]), "r"(a[AOFF + 2][0]), "r"(a[AOFF + 2][1]), "r"(a[AOFF + 2][2]), "r"(a[AOFF + 2][3]), "r"(a[AOFF + 3][0]), "r"(a[AOFF + 3][1]), "r"(a[AOFF + 3][2]), "r"(a[AOFF + 3][3]), "r"(a[AOFF + 4][0]), "r"(a[AOFF + 4][1]), "r"(a[AOFF + 4][2]), "r"(a[AOFF + 4][3]), "l"(descB), "n"(BOFF >> 4));
}
};
template <> struct Rng<1, 3, 8> {
template <int BOFF, int AOFF, int NA>
static __device__ __forceinline__ void run(float (&d)[48], const uint32_t (&a)[NA][4], uint64_t descB) {
    asm volatile(
        "{\n"
        ".reg .pred p0, p1;\n"
        ".reg .b64 ta, ta0, tb, tb0;\n"
        "setp.ne.b32 p0, 0, 0;\n"
        "setp.eq.b32 p1, 0, 0;\n"
        "add.s64 tb0, %68, %69;\n"
        "add.s64 tb, tb0, 96;\n"
        "wgmma.mma_async.sync.aligned.m64n96k16.f32.bf16.bf16 {%0, %1, %2, %3, %4, %5, %6, %7, %8, %9, %10, %11, %12, %13, %14, %15, %16, %17, %18, %19, %20, %21, %22, %23, %24, %25, %26, %27, %28, %29, %30, %31, %32, %33, %34, %35, %36, %37, %38, %39, %40, %41, %42, %43, %44, %45, %46, %47}, {%48, %49, %50, %51}, tb, p1, 1, 1, 1;\n"
        "add.s64 tb, tb0, 128;\n"
        "wgmma.mma_async.sync.aligned.m64n96k16.f32.bf16.bf16 {%0, %1, %2, %3, %4, %5, %6, %7, %8, %9, %10, %11, %12, %13, %14, %15, %16, %17, %18, %19, %20, %21, %22, %23, %24, %25, %26, %27, %28, %29, %30, %31, %32, %33, %34, %35, %36, %37, %38, %39, %40, %41, %42, %43, %44, %45, %46, %47}, {%52, %53, %54, %55}, tb, p1, 1, 1, 1;\n"
        "add.s64 tb, tb0, 160;\n"
        "wgmma.mma_async.sync.aligned.m64n96k16.f32.bf16.bf16 {%0, %1, %2, %3, %4, %5, %6, %7, %8, %9, %10, %11, %12, %13, %14, %15, %16, %17, %18, %19, %20, %21, %22, %23, %24, %25, %26, %27, %28, %29, %30, %31, %32, %33, %34, %35, %36, %37, %38, %39, %40, %41, %42, %43, %44, %45, %46, %47}, {%56, %57, %58, %59}, tb, p1, 1, 1, 1;\n"
        "add.s64 tb, tb0, 192;\n"
        "wgmma.mma_async.sync.aligned.m64n96k16.f32.bf16.bf16 {%0, %1, %2, %3, %4, %5, %6, %7, %8, %9, %10, %11, %12, %13, %14, %15, %16, %17, %18, %19, %20, %21, %22, %23, %24, %25, %26, %27, %28, %29, %30, %31, %32, %33, %34, %35, %36, %37, %38, %39, %40, %41, %42, %43, %44, %45, %46, %47}, {%60, %61, %62, %63}, tb, p1, 1, 1, 1;\n"
        "add.s64 tb, tb0, 224;\n"
        "wgmma.mma_async.sync.aligned.m64n96k16.f32.bf16.bf16 {%0, %1, %2, %3, %4, %5, %6, %7, %8, %9, %10, %11, %12, %13, %14, %15, %16, %17, %18, %19, %20, %21, %22, %23, %24, %25, %26, %27, %28, %29, %30, %31, %32, %33, %34, %35, %36, %37, %38, %39, %40, %41, %42, %43, %44, %45, %46, %47}, {%64, %65, %66, %67}, tb, p1, 1, 1, 1;\n"
        "}\n"
        : "+f"(d[0]), "+f"(d[1]), "+f"(d[2]), "+f"(d[3]), "+f"(d[4]), "+f"(d[5]), "+f"(d[6]), "+f"(d[7]), "+f"(d[8]), "+f"(d[9]), "+f"(d[10]), "+f"(d[11]), "+f"(d[12]), "+f"(d[13]), "+f"(d[14]), "+f"(d[15]), "+f"(d[16]), "+f"(d[17]), "+f"(d[18]), "+f"(d[19]), "+f"(d[20]), "+f"(d[21]), "+f"(d[22]), "+f"(d[23]), "+f"(d[24]), "+f"(d[25]), "+f"(d[26]), "+f"(d[27]), "+f"(d[28]), "+f"(d[29]), "+f"(d[30]), "+f"(d[31]), "+f"(d[32]), "+f"(d[33]), "+f"(d[34]), "+f"(d[35]), "+f"(d[36]), "+f"(d[37]), "+f"(d[38]), "+f"(d[39]), "+f"(d[40]), "+f"(d[41]), "+f"(d[42]), "+f"(d[43]), "+f"(d[44]), "+f"(d[45]), "+f"(d[46]), "+f"(d[47])
        : "r"(a[AOFF + 0][0]), "r"(a[AOFF + 0][1]), "r"(a[AOFF + 0][2]), "r"(a[AOFF + 0][3]), "r"(a[AOFF + 1][0]), "r"(a[AOFF + 1][1]), "r"(a[AOFF + 1][2]), "r"(a[AOFF + 1][3]), "r"(a[AOFF + 2][0]), "r"(a[AOFF + 2][1]), "r"(a[AOFF + 2][2]), "r"(a[AOFF + 2][3]), "r"(a[AOFF + 3][0]), "r"(a[AOFF + 3][1]), "r"(a[AOFF + 3][2]), "r"(a[AOFF + 3][3]), "r"(a[AOFF + 4][0]), "r"(a[AOFF + 4][1]), "r"(a[AOFF + 4][2]), "r"(a[AOFF + 4][3]), "l"(descB), "n"(BOFF >> 4));
}
};
template <> struct Rng<0, 3, 12> {
template <int BOFF, int AOFF, int NA>
static __device__ __forceinline__ void run(float (&d)[48], const uint32_t (&a)[NA][4], uint64_t descB) {
    asm volatile(
        "{\n"
        ".reg .pred p0, p1;\n"
        ".reg .b64 ta, ta0, tb, tb0;\n"
        "setp.ne.b32 p0, 0, 0;\n"
        "setp.eq.b32 p1, 0, 0;\n"
        "add.s64 tb0, %84, %85;\n"
        "add.s64 tb, tb0, 96;\n"
        "wgmma.mma_async.sync.aligned.m64n96k16.f32.bf16.bf16 {%0, %1, %2, %3, %4, %5, %6, %7, %8, %9, %10, %11, %12, %13, %14, %15, %16, %17, %18, %19, %20, %21, %22, %23, %24, %25, %26, %27, %28, %29, %30, %31, %32, %33, %34, %35, %36, %37, %38, %39, %40, %41, %42, %43, %44, %45, %46, %47}, {%48, %49, %50, %51}, tb, p1, 1, 1, 1;\n"
        "add.s64 tb, tb0, 1536;\n"
        "wgmma.mma_async.sync.aligned.m64n96k16.f32.bf16.bf16 {%0, %1, %2, %3, %4, %5, %6, %7, %8, %9, %10, %11, %12, %13, %14, %15, %16, %17, %18, %19, %20, %21, %22, %23, %24, %25, %26, %27, %28, %29, %30, %31, %32, %33, %34, %35, %36, %37, %38, %39, %40, %41, %42, %43, %44, %45, %46, %47}, {%52, %53, %54, %55}, tb, p1, 1, 1, 1;\n"
        "add.s64 tb, tb0, 1568;\n"
        "wgmma.mma_async.sync.aligned.m64n96k16.f32.bf16.bf16 {%0, %1, %2, %3, %4, %5, %6, %7, %8, %9, %10, %11, %12, %13, %14, %15, %16, %17, %18, %19, %20, %21, %22, %23, %24, %25, %26, %27, %28, %29, %30, %31, %32, %33, %34, %35, %36, %37, %38, %39, %40, %41, %42, %43, %44, %45, %46, %47}, {%56, %57, %58, %59}, tb, p1, 1, 1, 1;\n"
        "add.s64 tb, tb0, 1600;\n"
        "wgmma.mma_async.sync.aligned.m64n96k16.f32.bf16.bf16 {%0, %1, %2, %3, %4, %5, %6, %7, %8, %9, %10, %11, %12, %13, %14, %15, %16, %17, %18, %19, %20, %21, %22, %23, %24, %25, %26, %27, %28, %29, %30, %31, %32, %33, %34, %35, %36, %37, %38, %39, %40, %41, %42, %43, %44, %45, %46, %47}, {%60, %61, %62, %63}, tb, p1, 1, 1, 1;\n"
        "add.s64 tb, tb0, 1632;\n"
        "wgmma.mma_async.sync.aligned.m64n96k16.f32.bf16.bf16 {%0, %1, %2, %3, %4, %5, %6, %7, %8, %9, %10, %11, %12, %13, %14, %15, %16, %17, %18, %19, %20, %21, %22, %23, %24, %25, %26, %27, %28, %29, %30, %31, %32, %33, %34, %35, %36, %37, %38, %39, %40, %41, %42, %43, %44, %45, %46, %47}, {%64, %65, %66, %67}, tb, p1, 1, 1, 1;\n"
        "add.s64 tb, tb0, 3072;\n"
        "wgmma.mma_async.sync.aligned.m64n96k16.f32.bf16.bf16 {%0, %1, %2, %3, %4, %5, %6, %7, %8, %9, %10, %11, %12, %13, %14, %15, %16, %17, %18, %19, %20, %21, %22, %23, %24, %25, %26, %27, %28, %29, %30, %31, %32, %33, %34, %35, %36, %37, %38, %39, %40, %41, %42, %43, %44, %45, %46, %47}, {%68, %69, %70, %71}, tb, p1, 1, 1, 1;\n"
        "add.s64 tb, tb0, 3104;\n"
        "wgmma.mma_async.sync.aligned.m64n96k16.f32.bf16.bf16 {%0, %1, %2, %3, %4, %5, %6, %7, %8, %9, %10, %11, %12, %13, %14, %15, %16, %17, %18, %19, %20, %21, %22, %23, %24, %25, %26, %27, %28, %29, %30, %31, %32, %33, %34, %35, %36, %37, %38, %39, %40, %41, %42, %43, %44, %45, %46, %47}, {%72, %73, %74, %75}, tb, p1, 1, 1, 1;\n"
        "add.s64 tb, tb0, 3136;\n"
        "wgmma.mma_async.sync.aligned.m64n96k16.f32.bf16.bf16 {%0, %1, %2, %3, %4, %5, %6, %7, %8, %9, %10, %11, %12, %13, %14, %15, %16, %17, %18, %19, %20, %21, %22, %23, %24, %25, %26, %27, %28, %29, %30, %31, %32, %33, %34, %35, %36, %37, %38, %39, %40, %41, %42, %43, %44, %45, %46, %47}, {%76, %77, %78, %79}, tb, p1, 1, 1, 1;\n"
        "add.s64 tb, tb0, 3168;\n"
        "wgmma.mma_async.sync.aligned.m64n96k16.f32.bf16.bf16 {%0, %1, %2, %3, %4, %5, %6, %7, %8, %9, %10, %11, %12, %13, %14, %15, %16, %17, %18, %19, %20, %21, %22, %23, %24, %25, %26, %27, %28, %29, %30, %31, %32, %33, %34, %35, %36, %37, %38, %39, %40, %41, %42, %43, %44, %45, %46, %47}, {%80, %81, %82, %83}, tb, p1, 1, 1, 1;\n"
        "}\n"
        : "+f"(d[0]), "+f"(d[1]), "+f"(d[2]), "+f"(d[3]), "+f"(d[4]), "+f"(d[5]), "+f"(d[6]), "+f"(d[7]), "+f"(d[8]), "+f"(d[9]), "+f"(d[10]), "+f"(d[11]), "+f"(d[12]), "+f"(d[13]), "+f"(d[14]), "+f"(d[15]), "+f"(d[16]), "+f"(d[17]), "+f"(d[18]), "+f"(d[19]), "+f"(d[20]), "+f"(d[21]), "+f"(d[22]), "+f"(d[23]), "+f"(d[24]), "+f"(d[25]), "+f"(d[26]), "+f"(d[27]), "+f"(d[28]), "+f"(d[29]), "+f"(d[30]), "+f"(d[31]), "+f"(d[32]), "+f"(d[33]), "+f"(d[34]), "+f"(d[35]), "+f"(d[36]), "+f"(d[37]), "+f"(d[38]), "+f"(d[39]), "+f"(d[40]), "+f"(d[41]), "+f"(d[42]), "+f"(d[43]), "+f"(d[44]), "+f"(d[45]), "+f"(d[46]), "+f"(d[47])
        : "r"(a[AOFF + 0][0]), "r"(a[AOFF + 0][1]), "r"(a[AOFF + 0][2]), "r"(a[AOFF + 0][3]), "r"(a[AOFF + 1][0]), "r"(a[AOFF + 1][1]), "r"(a[AOFF + 1][2]), "r"(a[AOFF + 1][3]), "r"(a[AOFF + 2][0]), "r"(a[AOFF + 2][1]), "r"(a[AOFF + 2][2]), "r"(a[AOFF + 2][3]), "r"(a[AOFF + 3][0]), "r"(a[AOFF + 3][1]), "r"(a[AOFF + 3][2]), "r"(a[AOFF + 3][3]), "r"(a[AOFF + 4][0]), "r"(a[AOFF + 4][1]), "r"(a[AOFF + 4][2]), "r"(a[AOFF + 4][3]), "r"(a[AOFF + 5][0]), "r"(a[AOFF + 5][1]), "r"(a[AOFF + 5][2]), "r"(a[AOFF + 5][3]), "r"(a[AOFF + 6][0]), "r"(a[AOFF + 6][1]), "r"(a[AOFF + 6][2]), "r"(a[AOFF + 6][3]), "r"(a[AOFF + 7][0]), "r"(a[AOFF + 7][1]), "r"(a[AOFF + 7][2]), "r"(a[AOFF + 7][3]), "r"(a[AOFF + 8][0]), "r"(a[AOFF + 8][1]), "r"(a[AOFF + 8][2]), "r"(a[AOFF + 8][3]), "l"(descB), "n"(BOFF >> 4));
}
};
template <> struct Rng<1, 3, 12> {
template <int BOFF, int AOFF, int NA>
static __device__ __forceinline__ void run(float (&d)[48], const uint32_t (&a)[NA][4], uint64_t descB) {
    asm volatile(
        "{\n"
        ".reg .pred p0, p1;\n"
        ".reg .b64 ta, ta0, tb, tb0;\n"
        "setp.ne.b32 p0, 0, 0;\n"
        "setp.eq.b32 p1, 0, 0;\n"
        "add.s64 tb0, %84, %85;\n"
        "add.s64 tb, tb0, 96;\n"
        "wgmma.mma_async.sync.aligned.m64n96k16.f32.bf16.bf16 {%0, %1, %2, %3, %4, %5, %6, %7, %8, %9, %10, %11, %12, %13, %14, %15, %16, %17, %18, %19, %20, %21, %22, %23, %24, %25, %26, %27, %28, %29, %30, %31, %32, %33, %34, %35, %36, %37, %38, %39, %40, %41, %42, %43, %44, %45, %46, %47}, {%48, %49, %50, %51}, tb, p1, 1, 1, 1;\n"
        "add.s64 tb, tb0, 128;\n"
        "wgmma.mma_async.sync.aligned.m64n96k16.f32.bf16.bf16 {%0, %1, %2, %3, %4, %5, %6, %7, %8, %9, %10, %11, %12, %13, %14, %15, %16, %17, %18, %19, %20, %21, %22, %23, %24, %25, %26, %27, %28, %29, %30, %31, %32, %33, %34, %35, %36, %37, %38, %39, %40, %41, %42, %43, %44, %45, %46, %47}, {%52, %53, %54, %55}, tb, p1, 1, 1, 1;\n"
        "add.s64 tb, tb0, 160;\n"
        "wgmma.mma_async.sync.aligned.m64n96k16.f32.bf16.bf16 {%0, %1, %2, %3, %4, %5, %6, %7, %8, %9, %10, %11, %12, %13, %14, %15, %16, %17, %18, %19, %20, %21, %22, %23, %24, %25, %26, %27, %28, %29, %30, %31, %32, %33, %34, %35, %36, %37, %38, %39, %40, %41, %42, %43, %44, %45, %46, %47}, {%56, %57, %58, %59}, tb, p1, 1, 1, 1;\n"
        "add.s64 tb, tb0, 192;\n"
        "wgmma.mma_async.sync.aligned.m64n96k16.f32.bf16.bf16 {%0, %1, %2, %3, %4, %5, %6, %7, %8, %9, %10, %11, %12, %13, %14, %15, %16, %17, %18, %19, %20, %21, %22, %23, %24, %25, %26, %27, %28, %29, %30, %31, %32, %33, %34, %35, %36, %37, %38, %39, %40, %41, %42, %43, %44, %45, %46, %47}, {%60, %61, %62, %63}, tb, p1, 1, 1, 1;\n"
        "add.s64 tb, tb0, 224;\n"
        "wgmma.mma_async.sync.aligned.m64n96k16.f32.bf16.bf16 {%0, %1, %2, %3, %4, %5, %6, %7, %8, %9, %10, %11, %12, %13, %14, %15, %16, %17, %18, %19, %20, %21, %22, %23, %24, %25, %26, %27, %28, %29, %30, %31, %32, %33, %34, %35, %36, %37, %38, %39, %40, %41, %42, %43, %44, %45, %46, %47}, {%64, %65, %66, %67}, tb, p1, 1, 1, 1;\n"
        "add.s64 tb, tb0, 256;\n"
        "wgmma.mma_async.sync.aligned.m64n96k16.f32.bf16.bf16 {%0, %1, %2, %3, %4, %5, %6, %7, %8, %9, %10, %11, %12, %13, %14, %15, %16, %17, %18, %19, %20, %21, %22, %23, %24, %25, %26, %27, %28, %29, %30, %31, %32, %33, %34, %35, %36, %37, %38, %39, %40, %41, %42, %43, %44, %45, %46, %47}, {%68, %69, %70, %71}, tb, p1, 1, 1, 1;\n"
        "add.s64 tb, tb0, 288;\n"
        "wgmma.mma_async.sync.aligned.m64n96k16.f32.bf16.bf16 {%0, %1, %2, %3, %4, %5, %6, %7, %8, %9, %10, %11, %12, %13, %14, %15, %16, %17, %18, %19, %20, %21, %22, %23, %24, %25, %26, %27, %28, %29, %30, %31, %32, %33, %34, %35, %36, %37, %38, %39, %40, %41, %42, %43, %44, %45, %46, %47}, {%72, %73, %74, %75}, tb, p1, 1, 1, 1;\n"
        "add.s64 tb, tb0, 320;\n"
        "wgmma.mma_async.sync.aligned.m64n96k16.f32.bf16.bf16 {%0, %1, %2, %3, %4, %5, %6, %7, %8, %9, %10, %11, %12, %13, %14, %15, %16, %17, %18, %19, %20, %21, %22, %23, %24, %25, %26, %27, %28, %29, %30, %31, %32, %33, %34, %35, %36, %37, %38, %39, %40, %41, %42, %43, %44, %45, %46, %47}, {%76, %77, %78, %79}, tb, p1, 1, 1, 1;\n"
        "add.s64 tb, tb0, 352;\n"
        "wgmma.mma_async.sync.aligned.m64n96k16.f32.bf16.bf16 {%0, %1, %2, %3, %4, %5, %6, %7, %8, %9, %10, %11, %12, %13, %14, %15, %16, %17, %18, %19, %20, %21, %22, %23, %24, %25, %26, %27, %28, %29, %30, %31, %32, %33, %34, %35, %36, %37, %38, %39, %40, %41, %42, %43, %44, %45, %46, %47}, {%80, %81, %82, %83}, tb, p1, 1, 1, 1;\n"
        "}\n"
        : "+f"(d[0]), "+f"(d[1]), "+f"(d[2]), "+f"(d[3]), "+f"(d[4]), "+f"(d[5]), "+f"(d[6]), "+f"(d[7]), "+f"(d[8]), "+f"(d[9]), "+f"(d[10]), "+f"(d[11]), "+f"(d[12]), "+f"(d[13]), "+f"(d[14]), "+f"(d[15]), "+f"(d[16]), "+f"(d[17]), "+f"(d[18]), "+f"(d[19]), "+f"(d[20]), "+f"(d[21]), "+f"(d[22]), "+f"(d[23]), "+f"(d[24]), "+f"(d[25]), "+f"(d[26]), "+f"(d[27]), "+f"(d[28]), "+f"(d[29]), "+f"(d[30]), "+f"(d[31]), "+f"(d[32]), "+f"(d[33]), "+f"(d[34]), "+f"(d[35]), "+f"(d[36]), "+f"(d[37]), "+f"(d[38]), "+f"(d[39]), "+f"(d[40]), "+f"(d[41]), "+f"(d[42]), "+f"(d[43]), "+f"(d[44]), "+f"(d[45]), "+f"(d[46]), "+f"(d[47])
        : "r"(a[AOFF + 0][0]), "r"(a[AOFF + 0][1]), "r"(a[AOFF + 0][2]), "r"(a[AOFF + 0][3]), "r"(a[AOFF + 1][0]), "r"(a[AOFF + 1][1]), "r"(a[AOFF + 1][2]), "r"(a[AOFF + 1][3]), "r"(a[AOFF + 2][0]), "r"(a[AOFF + 2][1]), "r"(a[AOFF + 2][2]), "r"(a[AOFF + 2][3]), "r"(a[AOFF + 3][0]), "r"(a[AOFF + 3][1]), "r"(a[AOFF + 3][2]), "r"(a[AOFF + 3][3]), "r"(a[AOFF + 4][0]), "r"(a[AOFF + 4][1]), "r"(a[AOFF + 4][2]), "r"(a[AOFF + 4][3]), "r"(a[AOFF + 5][0]), "r"(a[AOFF + 5][1]), "r"(a[AOFF + 5][2]), "r"(a[AOFF + 5][3]), "r"(a[AOFF + 6][0]), "r"(a[AOFF + 6][1]), "r"(a[AOFF + 6][2]), "r"(a[AOFF + 6][3]), "r"(a[AOFF + 7][0]), "r"(a[AOFF + 7][1]), "r"(a[AOFF + 7][2]), "r"(a[AOFF + 7][3]), "r"(a[AOFF + 8][0]), "r"(a[AOFF + 8][1]), "r"(a[AOFF + 8][2]), "r"(a[AOFF + 8][3]), "l"(descB), "n"(BOFF >> 4));
}
};
template <> struct Rng<0, 4, 6> {
template <int BOFF, int AOFF, int NA>
static __device__ __forceinline__ void run(float (&d)[48], const uint32_t (&a)[NA][4], uint64_t descB) {
    asm volatile(
        "{\n"
        ".reg .pred p0, p1;\n"
        ".reg .b64 ta, ta0, tb, tb0;\n"
        "setp.ne.b32 p0, 0, 0;\n"
        "setp.eq.b32 p1, 0, 0;\n"
        "add.s64 tb0, %56, %57;\n"
        "add.s64 tb, tb0, 1536;\n"
        "wgmma.mma_async.sync.aligned.m64n96k16.f32.bf16.bf16 {%0, %1, %2, %3, %4, %5, %6, %7, %8, %9, %10, %11, %12, %13, %14, %15, %16, %17, %18, %19, %20, %21, %22, %23, %24, %25, %26, %27, %28, %29, %30, %31, %32, %33, %34, %35, %36, %37, %38, %39, %40, %41, %42, %43, %44, %45, %46, %47}, {%48, %49, %50, %51}, tb, p1, 1, 1, 1;\n"
        "add.s64 tb, tb0, 1568;\n"
        "wgmma.mma_async.sync.aligned.m64n96k16.f32.bf16.bf16 {%0, %1, %2, %3, %4, %5, %6, %7, %8, %9, %10, %11, %12, %13, %14, %15, %16, %17, %18, %19, %20, %21, %22, %23, %24, %25, %26, %27, %28, %29, %30, %31, %32, %33, %34, %35, %36, %37, %38, %39, %40, %41, %42, %43, %44, %45, %46, %47}, {%52, %53, %54, %55}, tb, p1, 1, 1, 1;\n"
        "}\n"
        : "+f"(d[0]), "+f"(d[1]), "+f"(d[2]), "+f"(d[3]), "+f"(d[4]), "+f"(d[5]), "+f"(d[6]), "+f"(d[7]), "+f"(d[8]), "+f"(d[9]), "+f"(d[10]), "+f"(d[11]), "+f"(d[12]), "+f"(d[13]), "+f"(d[14]), "+f"(d[15]), "+f"(d[16]), "+f"(d[17]), "+f"(d[18]), "+f"(d[19]), "+f"(d[20]), "+f"(d[21]), "+f"(d[22]), "+f"(d[23]), "+f"(d[24]), "+f"(d[25]), "+f"(d[26]), "+f"(d[27]), "+f"(d[28]), "+f"(d[29]), "+f"(d[30]), "+f"(d[31]), "+f"(d[32]), "+f"(d[33]), "+f"(d[34]), "+f"(d[35]), "+f"(d[36]), "+f"(d[37]), "+f"(d[38]), "+f"(d[39]), "+f"(d[40]), "+f"(d[41]), "+f"(d[42]), "+f"(d[43]), "+f"(d[44]), "+f"(d[45]), "+f"(d[46]), "+f"(d[47])
        : "r"(a[AOFF + 0][0]), "r"(a[AOFF + 0][1]), "r"(a[AOFF + 0][2]), "r"(a[AOFF + 0][3]), "r"(a[AOFF + 1][0]), "r"(a[AOFF + 1][1]), "r"(a[AOFF + 1][2]), "r"(a[AOFF + 1][3]), "l"(descB), "n"(BOFF >> 4));
}
};
template <> struct Rng<1, 4, 6> {
template <int BOFF, int AOFF, int NA>
static __device__ __forceinline__ void run(float (&d)[48], const uint32_t (&a)[NA][4], uint64_t descB) {
    asm volatile(
        "{\n"
        ".reg .pred p0, p1;\n"
        ".reg .b64 ta, ta0, tb, tb0;\n"
        "setp.ne.b32 p0, 0, 0;\n"
        "setp.eq.b32 p1, 0, 0;\n"
        "add.s64 tb0, %56, %57;\n"
        "add.s64 tb, tb0, 128;\n"
        "wgmma.mma_async.sync.aligned.m64n96k16.f32.bf16.bf16 {%0, %1, %2, %3, %4, %5, %6, %7, %8, %9, %10, %11, %12, %13, %14, %15, %16, %17, %18, %19, %20, %21, %22, %23, %24, %25, %26, %27, %28, %29, %30, %31, %32, %33, %34, %35, %36, %37, %38, %39, %40, %41, %42, %43, %44, %45, %46, %47}, {%48, %49, %50, %51}, tb, p1, 1, 1, 1;\n"
        "add.s64 tb, tb0, 160;\n"
        "wgmma.mma_async.sync.aligned.m64n96k16.f32.bf16.bf16 {%0, %1, %2, %3, %4, %5, %6, %7, %8, %9, %10, %11, %12, %13, %14, %15, %16, %17, %18, %19, %20, %21, %22, %23, %24, %25, %26, %27, %28, %29, %30, %31, %32, %33, %34, %35, %36, %37, %38, %39, %40, %41, %42, %43, %44, %45, %46, %47}, {%52, %53, %54, %55}, tb, p1, 1, 1, 1;\n"
        "}\n"
        : "+f"(d[0]), "+f"(d[1]), "+f"(d[2]), "+f"(d[3]), "+f"(d[4]), "+f"(d[5]), "+f"(d[6]), "+f"(d[7]), "+f"(d[8]), "+f"(d[9]), "+f"(d[10]), "+f"(d[11]), "+f"(d[12]), "+f"(d[13]), "+f"(d[14]), "+f"(d[15]), "+f"(d[16]), "+f"(d[17]), "+f"(d[18]), "+f"(d[19]), "+f"(d[20]), "+f"(d[21]), "+f"(d[22]), "+f"(d[23]), "+f"(d[24]), "+f"(d[25]), "+f"(d[26]), "+f"(d[27]), "+f"(d[28]), "+f"(d[29]), "+f"(d[30]), "+f"(d[31]), "+f"(d[32]), "+f"(d[33]), "+f"(d[34]), "+f"(d[35]), "+f"(d[36]), "+f"(d[37]), "+f"(d[38]), "+f"(d[39]), "+f"(d[40]), "+f"(d[41]), "+f"(d[42]), "+f"(d[43]), "+f"(d[44]), "+f"(d[45]), "+f"(d[46]), "+f"(d[47])
        : "r"(a[AOFF + 0][0]), "r"(a[AOFF + 0][1]), "r"(a[AOFF + 0][2]), "r"(a[AOFF + 0][3]), "r"(a[AOFF + 1][0]), "r"(a[AOFF + 1][1]), "r"(a[AOFF + 1][2]), "r"(a[AOFF + 1][3]), "l"(descB), "n"(BOFF >> 4));
}
};
template <> struct Rng<0, 4, 7> {
template <int BOFF, int AOFF, int NA>
static __device__ __forceinline__ void run(float (&d)[48], const uint32_t (&a)[NA][4], uint64_t descB) {
    asm volatile(
        "{\n"
        ".reg .pred p0, p1;\n"
        ".reg .b64 ta, ta0, tb, tb0;\n"
        "setp.ne.b32 p0, 0, 0;\n"
        "setp.eq.b32 p1, 0, 0;\n"
        "add.s64 tb0, %60, %61;\n"
        "add.s64 tb, tb0, 1536;\n"
        "wgmma.mma_async.sync.aligned.m64n96k16.f32.bf16.bf16 {%0, %1, %2, %3, %4, %5, %6, %7, %8, %9, %10, %11, %12, %13, %14, %15, %16, %17, %18, %19, %20, %21, %22, %23, %24, %25, %26, %27, %28, %29, %30, %31, %32, %33, %34, %35, %36, %37, %38, %39, %40, %41, %42, %43, %44, %45, %46, %47}, {%48, %49, %50, %51}, tb, p1, 1, 1, 1;\n"
        "add.s64 tb, tb0, 1568;\n"
        "wgmma.mma_async.sync.aligned.m64n96k16.f32.bf16.bf16 {%0, %1, %2, %3, %4, %5, %6, %7, %8, %9, %10, %11, %12, %13, %14, %15, %16, %17, %18, %19, %20, %21, %22, %23, %24, %25, %26, %27, %28, %29, %30, %31, %32, %33, %34, %35, %36, %37, %38, %39, %40, %41, %42, %43, %44, %45, %46, %47}, {%52, %53, %54, %55}, tb, p1, 1, 1, 1;\n"
        "add.s64 tb, tb0, 1600;\n"
        "wgmma.mma_async.sync.aligned.m64n96k16.f32.bf16.bf16 {%0, %1, %2, %3, %4, %5, %6, %7, %8, %9, %10, %11, %12, %13, %14, %15, %16, %17, %18, %19, %20, %21, %22, %23, %24, %25, %26, %27, %28, %29, %30, %31, %32, %33, %34, %35, %36, %37, %38, %39, %40, %41, %42, %43, %44, %45, %46, %47}, {%56, %57, %58, %59}, tb, p1, 1, 1, 1;\n"
        "}\n"
        : "+f"(d[0]), "+f"(d[1]), "+f"(d[2]), "+f"(d[3]), "+f"(d[4]), "+f"(d[5]), "+f"(d[6]), "+f"(d[7]), "+f"(d[8]), "+f"(d[9]), "+f"(d[10]), "+f"(d[11]), "+f"(d[12]), "+f"(d[13]), "+f"(d[14]), "+f"(d[15]), "+f"(d[16]), "+f"(d[17]), "+f"(d[18]), "+f"(d[19]), "+f"(d[20]), "+f"(d[21]), "+f"(d[22]), "+f"(d[23]), "+f"(d[24]), "+f"(d[25]), "+f"(d[26]), "+f"(d[27]), "+f"(d[28]), "+f"(d[29]), "+f"(d[30]), "+f"(d[31]), "+f"(d[32]), "+f"(d[33]), "+f"(d[34]), "+f"(d[35]), "+f"(d[36]), "+f"(d[37]), "+f"(d[38]), "+f"(d[39]), "+f"(d[40]), "+f"(d[41]), "+f"(d[42]), "+f"(d[43]), "+f"(d[44]), "+f"(d[45]), "+f"(d[46]), "+f"(d[47])
        : "r"(a[AOFF + 0][0]), "r"(a[AOFF + 0][1]), "r"(a[AOFF + 0][2]), "r"(a[AOFF + 0][3]), "r"(a[AOFF + 1][0]), "r"(a[AOFF + 1][1]), "r"(a[AOFF + 1][2]), "r"(a[AOFF + 1][3]), "r"(a[AOFF + 2][0]), "r"(a[AOFF + 2][1]), "r"(a[AOFF + 2][2]), "r"(a[AOFF + 2][3]), "l"(descB), "n"(BOFF >> 4));
}
};
template <> struct Rng<1, 4, 7> {
template <int BOFF, int AOFF, int NA>
static __device__ __forceinline__ void run(float (&d)[48], const uint32_t (&a)[NA][4], uint64_t descB) {
    asm volatile(
        "{\n"
        ".reg .pred p0, p1;\n"
        ".reg .b64 ta, ta0, tb, tb0;\n"
        "setp.ne.b32 p0, 0, 0;\n"
        "setp.eq.b32 p1, 0, 0;\n"
        "add.s64 tb0, %60, %61;\n"
        "add.s64 tb, tb0, 128;\n"
        "wgmma.mma_async.sync.aligned.m64n96k16.f32.bf16.bf16 {%0, %1, %2, %3, %4, %5, %6, %7, %8, %9, %10, %11, %12, %13, %14, %15, %16, %17, %18, %19, %20, %21, %22, %23, %24, %25, %26, %27, %28, %29, %30, %31, %32, %33, %34, %35, %36, %37, %38, %39, %40, %41, %42, %43, %44, %45, %46, %47}, {%48, %49, %50, %51}, tb, p1, 1, 1, 1;\n"
        "add.s64 tb, tb0, 160;\n"
        "wgmma.mma_async.sync.aligned.m64n96k16.f32.bf16.bf16 {%0, %1, %2, %3, %4, %5, %6, %7, %8, %9, %10, %11, %12, %13, %14, %15, %16, %17, %18, %19, %20, %21, %22, %23, %24, %25, %26, %27, %28, %29, %30, %31, %32, %33, %34, %35, %36, %37, %38, %39, %40, %41, %42, %43, %44, %45, %46, %47}, {%52, %53, %54, %55}, tb, p1, 1, 1, 1;\n"
        "add.s64 tb, tb0, 192;\n"
        "wgmma.mma_async.sync.aligned.m64n96k16.f32.bf16.bf16 {%0, %1, %2, %3, %4, %5, %6, %7, %8, %9, %10, %11, %12, %13, %14, %15, %16, %17, %18, %19, %20, %21, %22, %23, %24, %25, %26, %27, %28, %29, %30, %31, %32, %33, %34, %35, %36, %37, %38, %39, %40, %41, %42, %43, %44, %45, %46, %47}, {%56, %57, %58, %59}, tb, p1, 1, 1, 1;\n"
        "}\n"
        : "+f"(d[0]), "+f"(d[1]), "+f"(d[2]), "+f"(d[3]), "+f"(d[4]), "+f"(d[5]), "+f"(d[6]), "+f"(d[7]), "+f"(d[8]), "+f"(d[9]), "+f"(d[10]), "+f"(d[11]), "+f"(d[12]), "+f"(d[13]), "+f"(d[14]), "+f"(d[15]), "+f"(d[16]), "+f"(d[17]), "+f"(d[18]), "+f"(d[19]), "+f"(d[20]), "+f"(d[21]), "+f"(d[22]), "+f"(d[23]), "+f"(d[24]), "+f"(d[25]), "+f"(d[26]), "+f"(d[27]), "+f"(d[28]), "+f"(d[29]), "+f"(d[30]), "+f"(d[31]), "+f"(d[32]), "+f"(d[33]), "+f"(d[34]), "+f"(d[35]), "+f"(d[36]), "+f"(d[37]), "+f"(d[38]), "+f"(d[39]), "+f"(d[40]), "+f"(d[41]), "+f"(d[42]), "+f"(d[43]), "+f"(d[44]), "+f"(d[45]), "+f"(d[46]), "+f"(d[47])
        : "r"(a[AOFF + 0][0]), "r"(a[AOFF + 0][1]), "r"(a[AOFF + 0][2]), "r"(a[AOFF + 0][3]), "r"(a[AOFF + 1][0]), "r"(a[AOFF + 1][1]), "r"(a[AOFF + 1][2]), "r"(a[AOFF + 1][3]), "r"(a[AOFF + 2][0]), "r"(a[AOFF + 2][1]), "r"(a[AOFF + 2][2]), "r"(a[AOFF + 2][3]), "l"(descB), "n"(BOFF >> 4));
}
};
template <> struct Rng<0, 4, 8> {
template <int BOFF, int AOFF, int NA>
static __device__ __forceinline__ void run(float (&d)[48], const uint32_t (&a)[NA][4], uint64_t descB) {
    asm volatile(
        "{\n"
        ".reg .pred p0, p1;\n"
        ".reg .b64 ta, ta0, tb, tb0;\n"
        "setp.ne.b32 p0, 0, 0;\n"
        "setp.eq.b32 p1, 0, 0;\n"
        "add.s64 tb0, %64, %65;\n"
        "add.s64 tb, tb0, 1536;\n"
        "wgmma.mma_async.sync.aligned.m64n96k16.f32.bf16.bf16 {%0, %1, %2, %3, %4, %5, %6, %7, %8, %9, %10, %11, %12, %13, %14, %15, %16, %17, %18, %19, %20, %21, %22, %23, %24, %25, %26, %27, %28, %29, %30, %31, %32, %33, %34, %35, %36, %37, %38, %39, %40, %41, %42, %43, %44, %45, %46, %47}, {%48, %49, %50, %51}, tb, p1, 1, 1, 1;\n"
        "add.s64 tb, tb0, 1568;\n"
        "wgmma.mma_async.sync.aligned.m64n96k16.f32.bf16.bf16 {%0, %1, %2, %3, %4, %5, %6, %7, %8, %9, %10, %11, %12, %13, %14, %15, %16, %17, %18, %19, %20, %21, %22, %23, %24, %25, %26, %27, %28, %29, %30, %31, %32, %33, %34, %35, %36, %37, %38, %39, %40, %41, %42, %43, %44, %45, %46, %47}, {%52, %53, %54, %55}, tb, p1, 1, 1, 1;\n"
        "add.s64 tb, tb0, 1600;\n"
        "wgmma.mma_async.sync.aligned.m64n96k16.f32.bf16.bf16 {%0, %1, %2, %3, %4, %5, %6, %7, %8, %9, %10, %11, %12, %13, %14, %15, %16, %17, %18, %19, %20, %21, %22, %23, %24, %25, %26, %27, %28, %29, %30, %31, %32, %33, %34, %35, %36, %37, %38, %39, %40, %41, %42, %43, %44, %45, %46, %47}, {%56, %57, %58, %59}, tb, p1, 1, 1, 1;\n"
        "add.s64 tb, tb0, 1632;\n"
        "wgmma.mma_async.sync.aligned.m64n96k16.f32.bf16.bf16 {%0, %1, %2, %3, %4, %5, %6, %7, %8, %9, %10, %11, %12, %13, %14, %15, %16, %17, %18, %19, %20, %21, %22, %23, %24, %25, %26, %27, %28, %29, %30, %31, %32, %33, %34, %35, %36, %37, %38, %39, %40, %41, %42, %43, %44, %45, %46, %47}, {%60, %61, %62, %63}, tb, p1, 1, 1, 1;\n"
        "}\n"
        : "+f"(d[0]), "+f"(d[1]), "+f"(d[2]), "+f"(d[3]), "+f"(d[4]), "+f"(d[5]), "+f"(d[6]), "+f"(d[7]), "+f"(d[8]), "+f"(d[9]), "+f"(d[10]), "+f"(d[11]), "+f"(d[12]), "+f"(d[13]), "+f"(d[14]), "+f"(d[15]), "+f"(d[16]), "+f"(d[17]), "+f"(d[18]), "+f"(d[19]), "+f"(d[20]), "+f"(d[21]), "+f"(d[22]), "+f"(d[23]), "+f"(d[24]), "+f"(d[25]), "+f"(d[26]), "+f"(d[27]), "+f"(d[28]), "+f"(d[29]), "+f"(d[30]), "+f"(d[31]), "+f"(d[32]), "+f"(d[33]), "+f"(d[34]), "+f"(d[35]), "+f"(d[36]), "+f"(d[37]), "+f"(d[38]), "+f"(d[39]), "+f"(d[40]), "+f"(d[41]), "+f"(d[42]), "+f"(d[43]), "+f"(d[44]), "+f"(d[45]), "+f"(d[46]), "+f"(d[47])
        : "r"(a[AOFF + 0][0]), "r"(a[AOFF + 0][1]), "r"(a[AOFF + 0][2]), "r"(a[AOFF + 0][3]), "r"(a[AOFF + 1][0]), "r"(a[AOFF + 1][1]), "r"(a[AOFF + 1][2]), "r"(a[AOFF + 1][3]), "r"(a[AOFF + 2][0]), "r"(a[AOFF + 2][1]), "r"(a[AOFF + 2][2]), "r"(a[AOFF + 2][3]), "r"(a[AOFF + 3][0]), "r"(a[AOFF + 3][1]), "r"(a[AOFF + 3][2]), "r"(a[AOFF + 3][3]), "l"(descB), "n"(BOFF >> 4));
}
};
template <> struct Rng<1, 4, 8> {
template <int BOFF, int AOFF, int NA>
static __device__ __forceinline__ void run(float (&d)[48], const uint32_t (&a)[NA][4], uint64_t descB) {
    asm volatile(
        "{\n"
        ".reg .pred p0, p1;\n"
        ".reg .b64 ta, ta0, tb, tb0;\n"
        "setp.ne.b32 p0, 0, 0;\n"
        "setp.eq.b32 p1, 0, 0;\n"
        "add.s64 tb0, %64, %65;\n"
        "add.s64 tb, tb0, 128;\n"
        "wgmma.mma_async.sync.aligned.m64n96k16.f32.bf16.bf16 {%0, %1, %2, %3, %4, %5, %6, %7, %8, %9, %10, %11, %12, %13, %14, %15, %16, %17, %18, %19, %20, %21, %22, %23, %24, %25, %26, %27, %28, %29, %30, %31, %32, %33, %34, %35, %36, %37, %38, %39, %40, %41, %42, %43, %44, %45, %46, %47}, {%48, %49, %50, %51}, tb, p1, 1, 1, 1;\n"
        "add.s64 tb, tb0, 160;\n"
        "wgmma.mma_async.sync.aligned.m64n96k16.f32.bf16.bf16 {%0, %1, %2, %3, %4, %5, %6, %7, %8, %9, %10, %11, %12, %13, %14, %15, %16, %17, %18, %19, %20, %21, %22, %23, %24, %25, %26, %27, %28, %29, %30, %31, %32, %33, %34, %35, %36, %37, %38, %39, %40, %41, %42, %43, %44, %45, %46, %47}, {%52, %53, %54, %55}, tb, p1, 1, 1, 1;\n"
        "add.s64 tb, tb0, 192;\n"
        "wgmma.mma_async.sync.aligned.m64n96k16.f32.bf16.bf16 {%0, %1, %2, %3, %4, %5, %6, %7, %8, %9, %10, %11, %12, %13, %14, %15, %16, %17, %18, %19, %20, %21, %22, %23, %24, %25, %26, %27, %28, %29, %30, %31, %32, %33, %34, %35, %36, %37, %38, %39, %40, %41, %42, %43, %44, %45, %46, %47}, {%56, %57, %58, %59}, tb, p1, 1, 1, 1;\n"
        "add.s64 tb, tb0, 224;\n"
        "wgmma.mma_async.sync.aligned.m64n96k16.f32.bf16.bf16 {%0, %1, %2, %3, %4, %5, %6, %7, %8, %9, %10, %11, %12, %13, %14, %15, %16, %17, %18, %19, %20, %21, %22, %23, %24, %25, %26, %27, %28, %29, %30, %31, %32, %33, %34, %35, %36, %37, %38, %39, %40, %41, %42, %43, %44, %45, %46, %47}, {%60, %61, %62, %63}, tb, p1, 1, 1, 1;\n"
        "}\n"
        : "+f"(d[0]), "+f"(d[1]), "+f"(d[2]), "+f"(d[3]), "+f"(d[4]), "+f"(d[5]), "+f"(d[6]), "+f"(d[7]), "+f"(d[8]), "+f"(d[9]), "+f"(d[10]), "+f"(d[11]), "+f"(d[12]), "+f"(d[13]), "+f"(d[14]), "+f"(d[15]), "+f"(d[16]), "+f"(d[17]), "+f"(d[18]), "+f"(d[19]), "+f"(d[20]), "+f"(d[21]), "+f"(d[22]), "+f"(d[23]), "+f"(d[24]), "+f"(d[25]), "+f"(d[26]), "+f"(d[27]), "+f"(d[28]), "+f"(d[29]), "+f"(d[30]), "+f"(d[31]), "+f"(d[32]), "+f"(d[33]), "+f"(d[34]), "+f"(d[35]), "+f"(d[36]), "+f"(d[37]), "+f"(d[38]), "+f"(d[39]), "+f"(d[40]), "+f"(d[41]), "+f"(d[42]), "+f"(d[43]), "+f"(d[44]), "+f"(d[45]), "+f"(d[46]), "+f"(d[47])
        : "r"(a[AOFF + 0][0]), "r"(a[AOFF + 0][1]), "r"(a[AOFF + 0][2]), "r"(a[AOFF + 0][3]), "r"(a[AOFF + 1][0]), "r"(a[AOFF + 1][1]), "r"(a[AOFF + 1][2]), "r"(a[AOFF + 1][3]), "r"(a[AOFF + 2][0]), "r"(a[AOFF + 2][1]), "r"(a[AOFF + 2][2]), "r"(a[AOFF + 2][3]), "r"(a[AOFF + 3][0]), "r"(a[AOFF + 3][1]), "r"(a[AOFF + 3][2]), "r"(a[AOFF + 3][3]), "l"(descB), "n"(BOFF >> 4));
}
};
template <> struct Rng<0, 4, 9> {
template <int BOFF, int AOFF, int NA>
static __device__ __forceinline__ void run(float (&d)[48], const uint32_t (&a)[NA][4], uint64_t descB) {
    asm volatile(
        "{\n"
        ".reg .pred p0, p1;\n"
        ".reg .b64 ta, ta0, tb, tb0;\n"
        "setp.ne.b32 p0, 0, 0;\n"
        "setp.eq.b32 p1, 0, 0;\n"
        "add.s64 tb0, %68, %69;\n"
        "add.s64 tb, tb0, 1536;\n"
        "wgmma.mma_async.sync.aligned.m64n96k16.f32.bf16.bf16 {%0, %1, %2, %3, %4, %5, %6, %7, %8, %9, %10, %11, %12, %13, %14, %15, %16, %17, %18, %19, %20, %21, %22, %23, %24, %25, %26, %27, %28, %29, %30, %31, %32, %33, %34, %35, %36, %37, %38, %39, %40, %41, %42, %43, %44, %45, %46, %47}, {%48, %49, %50, %51}, tb, p1, 1, 1, 1;\n"
        "add.s64 tb, tb0, 1568;\n"
        "wgmma.mma_async.sync.aligned.m64n96k16.f32.bf16.bf16 {%0, %1, %2, %3, %4, %5, %6, %7, %8, %9, %10, %11, %12, %13, %14, %15, %16, %17, %18, %19, %20, %21, %22, %23, %24, %25, %26, %27, %28, %29, %30, %31, %32, %33, %34, %35, %36, %37, %38, %39, %40, %41, %42, %43, %44, %45, %46, %47}, {%52, %53, %54, %55}, tb, p1, 1, 1, 1;\n"
        "add.s64 tb, tb0, 1600;\n"
        "wgmma.mma_async.sync.aligned.m64n96k16.f32.bf16.bf16 {%0, %1, %2, %3, %4, %5, %6, %7, %8, %9, %10, %11, %12, %13, %14, %15, %16, %17, %18, %19, %20, %21, %22, %23, %24, %25, %26, %27, %28, %29, %30, %31, %32, %33, %34, %35, %36, %37, %38, %39, %40, %41, %42, %43, %44, %45, %46, %47}, {%56, %57, %58, %59}, tb, p1, 1, 1, 1;\n"
        "add.s64 tb, tb0, 1632;\n"
        "wgmma.mma_async.sync.aligned.m64n96k16.f32.bf16.bf16 {%0, %1, %2, %3, %4, %5, %6, %7, %8, %9, %10, %11, %12, %13, %14, %15, %16, %17, %18, %19, %20, %21, %22, %23, %24, %25, %26, %27, %28, %29, %30, %31, %32, %33, %34, %35, %36, %37, %38, %39, %40, %41, %42, %43, %44, %45, %46, %47}, {%60, %61, %62, %63}, tb, p1, 1, 1, 1;\n"
        "add.s64 tb, tb0, 3072;\n"
        "wgmma.mma_async.sync.aligned.m64n96k16.f32.bf16.bf16 {%0, %1, %2, %3, %4, %5, %6, %7, %8, %9, %10, %11, %12, %13, %14, %15, %16, %17, %18, %19, %20, %21, %22, %23, %24, %25, %26, %27, %28, %29, %30, %31, %32, %33, %34, %35, %36, %37, %38, %39, %40, %41, %42, %43, %44, %45, %46, %47}, {%64, %65, %66, %67}, tb, p1, 1, 1, 1;\n"
        "}\n"
        : "+f"(d[0]), "+f"(d[1]), "+f"(d[2]), "+f"(d[3]), "+f"(d[4]), "+f"(d[5]), "+f"(d[6]), "+f"(d[7]), "+f"(d[8]), "+f"(d[9]), "+f"(d[10]), "+f"(d[11]), "+f"(d[12]), "+f"(d[13]), "+f"(d[14]), "+f"(d[15]), "+f"(d[16]), "+f"(d[17]), "+f"(d[18]), "+f"(d[19]), "+f"(d[20]), "+f"(d[21]), "+f"(d[22]), "+f"(d[23]), "+f"(d[24]), "+f"(d[25]), "+f"(d[26]), "+f"(d[27]), "+f"(d[28]), "+f"(d[29]), "+f"(d[30]), "+f"(d[31]), "+f"(d[32]), "+f"(d[33]), "+f"(d[34]), "+f"(d[35]), "+f"(d[36]), "+f"(d[37]), "+f"(d[38]), "+f"(d[39]), "+f"(d[40]), "+f"(d[41]), "+f"(d[42]), "+f"(d[43]), "+f"(d[44]), "+f"(d[45]), "+f"(d[46]), "+f"(d[47])
        : "r"(a[AOFF + 0][0]), "r"(a[AOFF + 0][1]), "r"(a[AOFF + 0][2]), "r"(a[AOFF + 0][3]), "r"(a[AOFF + 1][0]), "r"(a[AOFF + 1][1]), "r"(a[AOFF + 1][2]), "r"(a[AOFF + 1][3]), "r"(a[AOFF + 2][0]), "r"(a[AOFF + 2][1]), "r"(a[AOFF + 2][2]), "r"(a[AOFF + 2][3]), "r"(a[AOFF + 3][0]), "r"(a[AOFF + 3][1]), "r"(a[AOFF + 3][2]), "r"(a[AOFF + 3][3]), "r"(a[AOFF + 4][0]), "r"(a[AOFF + 4][1]), "r"(a[AOFF + 4][2]), "r"(a[AOFF + 4][3]), "l"(descB), "n"(BOFF >> 4));
}
};
template <> struct Rng<1, 4, 9> {
template <int BOFF, int AOFF, int NA>
static __device__ __forceinline__ void run(float (&d)[48], const uint32_t (&a)[NA][4], uint64_t descB) {
    asm volatile(
        "{\n"
        ".reg .pred p0, p1;\n"
        ".reg .b64 ta, ta0, tb, tb0;\n"
        "setp.ne.b32 p0, 0, 0;\n"
        "setp.eq.b32 p1, 0, 0;\n"
        "add.s64 tb0, %68, %69;\n"
        "add.s64 tb, tb0, 128;\n"
        "wgmma.mma_async.sync.aligned.m64n96k16.f32.bf16.bf16 {%0, %1, %2, %3, %4, %5, %6, %7, %8, %9, %10, %11, %12, %13, %14, %15, %16, %17, %18, %19, %20, %21, %22, %23, %24, %25, %26, %27, %28, %29, %30, %31, %32, %33, %34, %35, %36, %37, %38, %39, %40, %41, %42, %43, %44, %45, %46, %47}, {%48, %49, %50, %51}, tb, p1, 1, 1, 1;\n"
        "add.s64 tb, tb0, 160;\n"
        "wgmma.mma_async.sync.aligned.m64n96k16.f32.bf16.bf16 {%0, %1, %2, %3, %4, %5, %6, %7, %8, %9, %10, %11, %12, %13, %14, %15, %16, %17, %18, %19, %20, %21, %22, %23, %24, %25, %26, %27, %28, %29, %30, %31, %32, %33, %34, %35, %36, %37, %38, %39, %40, %41, %42, %43, %44, %45, %46, %47}, {%52, %53, %54, %55}, tb, p1, 1, 1, 1;\n"
        "add.s64 tb, tb0, 192;\n"
        "wgmma.mma_async.sync.aligned.m64n96k16.f32.bf16.bf16 {%0, %1, %2, %3, %4, %5, %6, %7, %8, %9, %10, %11, %12, %13, %14, %15, %16, %17, %18, %19, %20, %21, %22, %23, %24, %25, %26, %27, %28, %29, %30, %31, %32, %33, %34, %35, %36, %37, %38, %39, %40, %41, %42, %43, %44, %45, %46, %47}, {%56, %57, %58, %59}, tb, p1, 1, 1, 1;\n"
        "add.s64 tb, tb0, 224;\n"
        "wgmma.mma_async.sync.aligned.m64n96k16.f32.bf16.bf16 {%0, %1, %2, %3, %4, %5, %6, %7, %8, %9, %10, %11, %12, %13, %14, %15, %16, %17, %18, %19, %20, %21, %22, %23, %24, %25, %26, %27, %28, %29, %30, %31, %32, %33, %34, %35, %36, %37, %38, %39, %40, %41, %42, %43, %44, %45, %46, %47}, {%60, %61, %62, %63}, tb, p1, 1, 1, 1;\n"
        "add.s64 tb, tb0, 256;\n"
        "wgmma.mma_async.sync.aligned.m64n96k16.f32.bf16.bf16 {%0, %1, %2, %3, %4, %5, %6, %7, %8, %9, %10, %11, %12, %13, %14, %15, %16, %17, %18, %19, %20, %21, %22, %23, %24, %25, %26, %27, %28, %29, %30, %31, %32, %33, %34, %35, %36, %37, %38, %39, %40, %41, %42, %43, %44, %45, %46, %47}, {%64, %65, %66, %67}, tb, p1, 1, 1, 1;\n"
        "}\n"
        : "+f"(d[0]), "+f"(d[1]), "+f"(d[2]), "+f"(d[3]), "+f"(d[4]), "+f"(d[5]), "+f"(d[6]), "+f"(d[7]), "+f"(d[8]), "+f"(d[9]), "+f"(d[10]), "+f"(d[11]), "+f"(d[12]), "+f"(d[13]), "+f"(d[14]), "+f"(d[15]), "+f"(d[16]), "+f"(d[17]), "+f"(d[18]), "+f"(d[19]), "+f"(d[20]), "+f"(d[21]), "+f"(d[22]), "+f"(d[23]), "+f"(d[24]), "+f"(d[25]), "+f"(d[26]), "+f"(d[27]), "+f"(d[28]), "+f"(d[29]), "+f"(d[30]), "+f"(d[31]), "+f"(d[32]), "+f"(d[33]), "+f"(d[34]), "+f"(d[35]), "+f"(d[36]), "+f"(d[37]), "+f"(d[38]), "+f"(d[39]), "+f"(d[40]), "+f"(d[41]), "+f"(d[42]), "+f"(d[43]), "+f"(d[44]), "+f"(d[45]), "+f"(d[46]), "+f"(d[47])
        : "r"(a[AOFF + 0][0]), "r"(a[AOFF + 0][1]), "r"(a[AOFF + 0][2]), "r"(a[AOFF + 0][3]), "r"(a[AOFF + 1][0]), "r"(a[AOFF + 1][1]), "r"(a[AOFF + 1][2]), "r"(a[AOFF + 1][3]), "r"(a[AOFF + 2][0]), "r"(a[AOFF + 2][1]), "r"(a[AOFF + 2][2]), "r"(a[AOFF + 2][3]), "r"(a[AOFF + 3][0]), "r"(a[AOFF + 3][1]), "r"(a[AOFF + 3][2]), "r"(a[AOFF + 3][3]), "r"(a[AOFF + 4][0]), "r"(a[AOFF + 4][1]), "r"(a[AOFF + 4][2]), "r"(a[AOFF + 4][3]), "l"(descB), "n"(BOFF >> 4));
}
};
template <> struct Rng<0, 4, 12> {
template <int BOFF, int AOFF, int NA>
static __device__ __forceinline__ void run(float (&d)[48], const uint32_t (&a)[NA][4], uint64_t descB) {
    asm volatile(
        "{\n"
        ".reg .pred p0, p1;\n"
        ".reg .b64 ta, ta0, tb, tb0;\n"
        "setp.ne.b32 p0, 0, 0;\n"
        "setp.eq.b32 p1, 0, 0;\n"
        "add.s64 tb0, %80, %81;\n"
        "add.s64 tb, tb0, 1536;\n"
        "wgmma.mma_async.sync.aligned.m64n96k16.f32.bf16.bf16 {%0, %1, %2, %3, %4, %5, %6, %7, %8, %9, %10, %11, %12, %13, %14, %15, %16, %17, %18, %19, %20, %21, %22, %23, %24, %25, %26, %27, %28, %29, %30, %31, %32, %33, %34, %35, %36, %37, %38, %39, %40, %41, %42, %43, %44, %45, %46, %47}, {%48, %49, %50, %51}, tb, p1, 1, 1, 1;\n"
        "add.s64 tb, tb0, 1568;\n"
        "wgmma.mma_async.sync.aligned.m64n96k16.f32.bf16.bf16 {%0, %1, %2, %3, %4, %5, %6, %7, %8, %9, %10, %11, %12, %13, %14, %15, %16, %17, %18, %19, %20, %21, %22, %23, %24, %25, %26, %27, %28, %29, %30, %31, %32, %33, %34, %35, %36, %37, %38, %39, %40, %41, %42, %43, %44, %45, %46, %47}, {%52, %53, %54, %55}, tb, p1, 1, 1, 1;\n"
        "add.s64 tb, tb0, 1600;\n"
        "wgmma.mma_async.sync.aligned.m64n96k16.f32.bf16.bf16 {%0, %1, %2, %3, %4, %5, %6, %7, %8, %9, %10, %11, %12, %13, %14, %15, %16, %17, %18, %19, %20, %21, %22, %23, %24, %25, %26, %27, %28, %29, %30, %31, %32, %33, %34, %35, %36, %37, %38, %39, %40, %41, %42, %43, %44, %45, %46, %47}, {%56, %57, %58, %59}, tb, p1, 1, 1, 1;\n"
        "add.s64 tb, tb0, 1632;\n"
        "wgmma.mma_async.sync.aligned.m64n96k16.f32.bf16.bf16 {%0, %1, %2, %3, %4, %5, %6, %7, %8, %9, %10, %11, %12, %13, %14, %15, %16, %17, %18, %19, %20, %21, %22, %23, %24, %25, %26, %27, %28, %29, %30, %31, %32, %33, %34, %35, %36, %37, %38, %39, %40, %41, %42, %43, %44, %45, %46, %47}, {%60, %61, %62, %63}, tb, p1, 1, 1, 1;\n"
        "add.s64 tb, tb0, 3072;\n"
        "wgmma.mma_async.sync.aligned.m64n96k16.f32.bf16.bf16 {%0, %1, %2, %3, %4, %5, %6, %7, %8, %9, %10, %11, %12, %13, %14, %15, %16, %17, %18, %19, %20, %21, %22, %23, %24, %25, %26, %27, %28, %29, %30, %31, %32, %33, %34, %35, %36, %37, %38, %39, %40, %41, %42, %43, %44, %45, %46, %47}, {%64, %65, %66, %67}, tb, p1, 1, 1, 1;\n"
        "add.s64 tb, tb0, 3104;\n"
        "wgmma.mma_async.sync.aligned.m64n96k16.f32.bf16.bf16 {%0, %1, %2, %3, %4, %5, %6, %7, %8, %9, %10, %11, %12, %13, %14, %15, %16, %17, %18, %19, %20, %21, %22, %23, %24, %25, %26, %27, %28, %29, %30, %31, %32, %33, %34, %35, %36, %37, %38, %39, %40, %41, %42, %43, %44, %45, %46, %47}, {%68, %69, %70, %71}, tb, p1, 1, 1, 1;\n"
        "add.s64 tb, tb0, 3136;\n"
        "wgmma.mma_async.sync.aligned.m64n96k16.f32.bf16.bf16 {%0, %1, %2, %3, %4, %5, %6, %7, %8, %9, %10, %11, %12, %13, %14, %15, %16, %17, %18, %19, %20, %21, %22, %23, %24, %25, %26, %27, %28, %29, %30, %31, %32, %33, %34, %35, %36, %37, %38, %39, %40, %41, %42, %43, %44, %45, %46, %47}, {%72, %73, %74, %75}, tb, p1, 1, 1, 1;\n"
        "add.s64 tb, tb0, 3168;\n"
        "wgmma.mma_async.sync.aligned.m64n96k16.f32.bf16.bf16 {%0, %1, %2, %3, %4, %5, %6, %7, %8, %9, %10, %11, %12, %13, %14, %15, %16, %17, %18, %19, %20, %21, %22, %23, %24, %25, %26, %27, %28, %29, %30, %31, %32, %33, %34, %35, %36, %37, %38, %39, %40, %41, %42, %43, %44, %45, %46, %47}, {%76, %77, %78, %79}, tb, p1, 1, 1, 1;\n"
        "}\n"
        : "+f"(d[0]), "+f"(d[1]), "+f"(d[2]), "+f"(d[3]), "+f"(d[4]), "+f"(d[5]), "+f"(d[6]), "+f"(d[7]), "+f"(d[8]), "+f"(d[9]), "+f"(d[10]), "+f"(d[11]), "+f"(d[12]), "+f"(d[13]), "+f"(d[14]), "+f"(d[15]), "+f"(d[16]), "+f"(d[17]), "+f"(d[18]), "+f"(d[19]), "+f"(d[20]), "+f"(d[21]), "+f"(d[22]), "+f"(d[23]), "+f"(d[24]), "+f"(d[25]), "+f"(d[26]), "+f"(d[27]), "+f"(d[28]), "+f"(d[29]), "+f"(d[30]), "+f"(d[31]), "+f"(d[32]), "+f"(d[33]), "+f"(d[34]), "+f"(d[35]), "+f"(d[36]), "+f"(d[37]), "+f"(d[38]), "+f"(d[39]), "+f"(d[40]), "+f"(d[41]), "+f"(d[42]), "+f"(d[43]), "+f"(d[44]), "+f"(d[45]), "+f"(d[46]), "+f"(d[47])
        : "r"(a[AOFF + 0][0]), "r"(a[AOFF + 0][1]), "r"(a[AOFF + 0][2]), "r"(a[AOFF + 0][3]), "r"(a[AOFF + 1][0]), "r"(a[AOFF + 1][1]), "r"(a[AOFF + 1][2]), "r"(a[AOFF + 1][3]), "r"(a[AOFF + 2][0]), "r"(a[AOFF + 2][1]), "r"(a[AOFF + 2][2]), "r"(a[AOFF + 2][3]), "r"(a[AOFF + 3][0]), "r"(a[AOFF + 3][1]), "r"(a[AOFF + 3][2]), "r"(a[AOFF + 3][3]), "r"(a[AOFF + 4][0]), "r"(a[AOFF + 4][1]), "r"(a[AOFF + 4][2]), "r"(a[AOFF + 4][3]), "r"(a[AOFF + 5][0]), "r"(a[AOFF + 5][1]), "r"(a[AOFF + 5][2]), "r"(a[AOFF + 5][3]), "r"(a[AOFF + 6][0]), "r"(a[AOFF + 6][1]), "r"(a[AOFF + 6][2]), "r"(a[AOFF + 6][3]), "r"(a[AOFF + 7][0]), "r"(a[AOFF + 7][1]), "r"(a[AOFF + 7][2]), "r"(a[AOFF + 7][3]), "l"(descB), "n"(BOFF >> 4));
}
};
template <> struct Rng<1, 4, 12> {
template <int BOFF, int AOFF, int NA>
static __device__ __forceinline__ void run(float (&d)[48], const uint32_t (&a)[NA][4], uint64_t descB) {
    asm volatile(
        "{\n"
        ".reg .pred p0, p1;\n"
        ".reg .b64 ta, ta0, tb, tb0;\n"
        "setp.ne.b32 p0, 0, 0;\n"
        "setp.eq.b32 p1, 0, 0;\n"
        "add.s64 tb0, %80, %81;\n"
        "add.s64 tb, tb0, 128;\n"
        "wgmma.mma_async.sync.aligned.m64n96k16.f32.bf16.bf16 {%0, %1, %2, %3, %4, %5, %6, %7, %8, %9, %10, %11, %12, %13, %14, %15, %16, %17, %18, %19, %20, %21, %22, %23, %24, %25, %26, %27, %28, %29, %30, %31, %32, %33, %34, %35, %36, %37, %38, %39, %40, %41, %42, %43, %44, %45, %46, %47}, {%48, %49, %50, %51}, tb, p1, 1, 1, 1;\n"
        "add.s64 tb, tb0, 160;\n"
        "wgmma.mma_async.sync.aligned.m64n96k16.f32.bf16.bf16 {%0, %1, %2, %3, %4, %5, %6, %7, %8, %9, %10, %11, %12, %13, %14, %15, %16, %17, %18, %19, %20, %21, %22, %23, %24, %25, %26, %27, %28, %29, %30, %31, %32, %33, %34, %35, %36, %37, %38, %39, %40, %41, %42, %43, %44, %45, %46, %47}, {%52, %53, %54, %55}, tb, p1, 1, 1, 1;\n"
        "add.s64 tb, tb0, 192;\n"
        "wgmma.mma_async.sync.aligned.m64n96k16.f32.bf16.bf16 {%0, %1, %2, %3, %4, %5, %6, %7, %8, %9, %10, %11, %12, %13, %14, %15, %16, %17, %18, %19, %20, %21, %22, %23, %24, %25, %26, %27, %28, %29, %30, %31, %32, %33, %34, %35, %36, %37, %38, %39, %40, %41, %42, %43, %44, %45, %46, %47}, {%56, %57, %58, %59}, tb, p1, 1, 1, 1;\n"
        "add.s64 tb, tb0, 224;\n"
        "wgmma.mma_async.sync.aligned.m64n96k16.f32.bf16.bf16 {%0, %1, %2, %3, %4, %5, %6, %7, %8, %9, %10, %11, %12, %13, %14, %15, %16, %17, %18, %19, %20, %21, %22, %23, %24, %25, %26, %27, %28, %29, %30, %31, %32, %33, %34, %35, %36, %37, %38, %39, %40, %41, %42, %43, %44, %45, %46, %47}, {%60, %61, %62, %63}, tb, p1, 1, 1, 1;\n"
        "add.s64 tb, tb0, 256;\n"
        "wgmma.mma_async.sync.aligned.m64n96k16.f32.bf16.bf16 {%0, %1, %2, %3, %4, %5, %6, %7, %8, %9, %10, %11, %12, %13, %14, %15, %16, %17, %18, %19, %20, %21, %22, %23, %24, %25, %26, %27, %28, %29, %30, %31, %32, %33, %34, %35, %36, %37, %38, %39, %40, %41, %42, %43, %44, %45, %46, %47}, {%64, %65, %66, %67}, tb, p1, 1, 1, 1;\n"
        "add.s64 tb, tb0, 288;\n"
        "wgmma.mma_async.sync.aligned.m64n96k16.f32.bf16.bf16 {%0, %1, %2, %3, %4, %5, %6, %7, %8, %9, %10, %11, %12, %13, %14, %15, %16, %17, %18, %19, %20, %21, %22, %23, %24, %25, %26, %27, %28, %29, %30, %31, %32, %33, %34, %35, %36, %37, %38, %39, %40, %41, %42, %43, %44, %45, %46, %47}, {%68, %69, %70, %71}, tb, p1, 1, 1, 1;\n"
        "add.s64 tb, tb0, 320;\n"
        "wgmma.mma_async.sync.aligned.m64n96k16.f32.bf16.bf16 {%0, %1, %2, %3, %4, %5, %6, %7, %8, %9, %10, %11, %12, %13, %14, %15, %16, %17, %18, %19, %20, %21, %22, %23, %24, %25, %26, %27, %28, %29, %30, %31, %32, %33, %34, %35, %36, %37, %38, %39, %40, %41, %42, %43, %44, %45, %46, %47}, {%72, %73, %74, %75}, tb, p1, 1, 1, 1;\n"
        "add.s64 tb, tb0, 352;\n"
        "wgmma.mma_async.sync.aligned.m64n96k16.f32.bf16.bf16 {%0, %1, %2, %3, %4, %5, %6, %7, %8, %9, %10, %11, %12, %13, %14, %15, %16, %17, %18, %19, %20, %21, %22, %23, %24, %25, %26, %27, %28, %29, %30, %31, %32, %33, %34, %35, %36, %37, %38, %39, %40, %41, %42, %43, %44, %45, %46, %47}, {%76, %77, %78, %79}, tb, p1, 1, 1, 1;\n"
        "}\n"
        : "+f"(d[0]), "+f"(d[1]), "+f"(d[2]), "+f"(d[3]), "+f"(d[4]), "+f"(d[5]), "+f"(d[6]), "+f"(d[7]), "+f"(d[8]), "+f"(d[9]), "+f"(d[10]), "+f"(d[11]), "+f"(d[12]), "+f"(d[13]), "+f"(d[14]), "+f"(d[15]), "+f"(d[16]), "+f"(d[17]), "+f"(d[18]), "+f"(d[19]), "+f"(d[20]), "+f"(d[21]), "+f"(d[22]), "+f"(d[23]), "+f"(d[24]), "+f"(d[25]), "+f"(d[26]), "+f"(d[27]), "+f"(d[28]), "+f"(d[29]), "+f"(d[30]), "+f"(d[31]), "+f"(d[32]), "+f"(d[33]), "+f"(d[34]), "+f"(d[35]), "+f"(d[36]), "+f"(d[37]), "+f"(d[38]), "+f"(d[39]), "+f"(d[40]), "+f"(d[41]), "+f"(d[42]), "+f"(d[43]), "+f"(d[44]), "+f"(d[45]), "+f"(d[46]), "+f"(d[47])
        : "r"(a[AOFF + 0][0]), "r"(a[AOFF + 0][1]), "r"(a[AOFF + 0][2]), "r"(a[AOFF + 0][3]), "r"(a[AOFF + 1][0]), "r"(a[AOFF + 1][1]), "r"(a[AOFF + 1][2]), "r"(a[AOFF + 1][3]), "r"(a[AOFF + 2][0]), "r"(a[AOFF + 2][1]), "r"(a[AOFF + 2][2]), "r"(a[AOFF + 2][3]), "r"(a[AOFF + 3][0]), "r"(a[AOFF + 3][1]), "r"(a[AOFF + 3][2]), "r"(a[AOFF + 3][3]), "r"(a[AOFF + 4][0]), "r"(a[AOFF + 4][1]), "r"(a[AOFF + 4][2]), "r"(a[AOFF + 4][3]), "r"(a[AOFF + 5][0]), "r"(a[AOFF + 5][1]), "r"(a[AOFF + 5][2]), "r"(a[AOFF + 5][3]), "r"(a[AOFF + 6][0]), "r"(a[AOFF + 6][1]), "r"(a[AOFF + 6][2]), "r"(a[AOFF + 6][3]), "r"(a[AOFF + 7][0]), "r"(a[AOFF + 7][1]), "r"(a[AOFF + 7][2]), "r"(a[AOFF + 7][3]), "l"(descB), "n"(BOFF >> 4));
}
};
template <> struct Rng<0, 5, 8> {
template <int BOFF, int AOFF, int NA>
static __device__ __forceinline__ void run(float (&d)[48], const uint32_t (&a)[NA][4], uint64_t descB) {
    asm volatile(
        "{\n"
        ".reg .pred p0, p1;\n"
        ".reg .b64 ta, ta0, tb, tb0;\n"
        "setp.ne.b32 p0, 0, 0;\n"
        "setp.eq.b32 p1, 0, 0;\n"
        "add.s64 tb0, %60, %61;\n"
        "add.s64 tb, tb0, 1568;\n"
        "wgmma.mma_async.sync.aligned.m64n96k16.f32.bf16.bf16 {%0, %1, %2, %3, %4, %5, %6, %7, %8, %9, %10, %11, %12, %13, %14, %15, %16, %17, %18, %19, %20, %21, %22, %23, %24, %25, %26, %27, %28, %29, %30, %31, %32, %33, %34, %35, %36, %37, %38, %39, %40, %41, %42, %43, %44, %45, %46, %47}, {%48, %49, %50, %51}, tb, p1, 1, 1, 1;\n"
        "add.s64 tb, tb0, 1600;\n"
        "wgmma.mma_async.sync.aligned.m64n96k16.f32.bf16.bf16 {%0, %1, %2, %3, %4, %5, %6, %7, %8, %9, %10, %11, %12, %13, %14, %15, %16, %17, %18, %19, %20, %21, %22, %23, %24, %25, %26, %27, %28, %29, %30, %31, %32, %33, %34, %35, %36, %37, %38, %39, %40, %41, %42, %43, %44, %45, %46, %47}, {%52, %53, %54, %55}, tb, p1, 1, 1, 1;\n"
        "add.s64 tb, tb0, 1632;\n"
        "wgmma.mma_async.sync.aligned.m64n96k16.f32.bf16.bf16 {%0, %1, %2, %3, %4, %5, %6, %7, %8, %9, %10, %11, %12, %13, %14, %15, %16, %17, %18, %19, %20, %21, %22, %23, %24, %25, %26, %27, %28, %29, %30, %31, %32, %33, %34, %35, %36, %37, %38, %39, %40, %41, %42, %43, %44, %45, %46, %47}, {%56, %57, %58, %59}, tb, p1, 1, 1, 1;\n"
        "}\n"
        : "+f"(d[0]), "+f"(d[1]), "+f"(d[2]), "+f"(d[3]), "+f"(d[4]), "+f"(d[5]), "+f"(d[6]), "+f"(d[7]), "+f"(d[8]), "+f"(d[9]), "+f"(d[10]), "+f"(d[11]), "+f"(d[12]), "+f"(d[13]), "+f"(d[14]), "+f"(d[15]), "+f"(d[16]), "+f"(d[17]), "+f"(d[18]), "+f"(d[19]), "+f"(d[20]), "+f"(d[21]), "+f"(d[22]), "+f"(d[23]), "+f"(d[24]), "+f"(d[25]), "+f"(d[26]), "+f"(d[27]), "+f"(d[28]), "+f"(d[29]), "+f"(d[30]), "+f"(d[31]), "+f"(d[32]), "+f"(d[33]), "+f"(d[34]), "+f"(d[35]), "+f"(d[36]), "+f"(d[37]), "+f"(d[38]), "+f"(d[39]), "+f"(d[40]), "+f"(d[41]), "+f"(d[42]), "+f"(d[43]), "+f"(d[44]), "+f"(d[45]), "+f"(d[46]), "+f"(d[47])
        : "r"(a[AOFF + 0][0]), "r"(a[AOFF + 0][1]), "r"(a[AOFF + 0][2]), "r"(a[AOFF + 0][3]), "r"(a[AOFF + 1][0]), "r"(a[AOFF + 1][1]), "r"(a[AOFF + 1][2]), "r"(a[AOFF + 1][3]), "r"(a[AOFF + 2][0]), "r"(a[AOFF + 2][1]), "r"(a[AOFF + 2][2]), "r"(a[AOFF + 2][3]), "l"(descB), "n"(BOFF >> 4));
}
};
template <> struct Rng<1, 5, 8> {
template <int BOFF, int AOFF, int NA>
static __device__ __forceinline__ void run(float (&d)[48], const uint32_t (&a)[NA][4], uint64_t descB) {
    asm volatile(
        "{\n"
        ".reg .pred p0, p1;\n"
        ".reg .b64 ta, ta0, tb, tb0;\n"
        "setp.ne.b32 p0, 0, 0;\n"
        "setp.eq.b32 p1, 0, 0;\n"
        "add.s64 tb0, %60, %61;\n"
        "add.s64 tb, tb0, 160;\n"
        "wgmma.mma_async.sync.aligned.m64n96k16.f32.bf16.bf16 {%0, %1, %2, %3, %4, %5, %6, %7, %8, %9, %10, %11, %12, %13, %14, %15, %16, %17, %18, %19, %20, %21, %22, %23, %24, %25, %26, %27, %28, %29, %30, %31, %32, %33, %34, %35, %36, %37, %38, %39, %40, %41, %42, %43, %44, %45, %46, %47}, {%48, %49, %50, %51}, tb, p1, 1, 1, 1;\n"
        "add.s64 tb, tb0, 192;\n"
        "wgmma.mma_async.sync.aligned.m64n96k16.f32.bf16.bf16 {%0, %1, %2, %3, %4, %5, %6, %7, %8, %9, %10, %11, %12, %13, %14, %15, %16, %17, %18, %19, %20, %21, %22, %23, %24, %25, %26, %27, %28, %29, %30, %31, %32, %33, %34, %35, %36, %37, %38, %39, %40, %41, %42, %43, %44, %45, %46, %47}, {%52, %53, %54, %55}, tb, p1, 1, 1, 1;\n"
        "add.s64 tb, tb0, 224;\n"
        "wgmma.mma_async.sync.aligned.m64n96k16.f32.bf16.bf16 {%0, %1, %2, %3, %4, %5, %6, %7, %8, %9, %10, %11, %12, %13, %14, %15, %16, %17, %18, %19, %20, %21, %22, %23, %24, %25, %26, %27, %28, %29, %30, %31, %32, %33, %34, %35, %36, %37, %38, %39, %40, %41, %42, %43, %44, %45, %46, %47}, {%56, %57, %58, %59}, tb, p1, 1, 1, 1;\n"
        "}\n"
        : "+f"(d[0]), "+f"(d[1]), "+f"(d[2]), "+f"(d[3]), "+f"(d[4]), "+f"(d[5]), "+f"(d[6]), "+f"(d[7]), "+f"(d[8]), "+f"(d[9]), "+f"(d[10]), "+f"(d[11]), "+f"(d[12]), "+f"(d[13]), "+f"(d[14]), "+f"(d[15]), "+f"(d[16]), "+f"(d[17]), "+f"(d[18]), "+f"(d[19]), "+f"(d[20]), "+f"(d[21]), "+f"(d[22]), "+f"(d[23]), "+f"(d[24]), "+f"(d[25]), "+f"(d[26]), "+f"(d[27]), "+f"(d[28]), "+f"(d[29]), "+f"(d[30]), "+f"(d[31]), "+f"(d[32]), "+f"(d[33]), "+f"(d[34]), "+f"(d[35]), "+f"(d[36]), "+f"(d[37]), "+f"(d[38]), "+f"(d[39]), "+f"(d[40]), "+f"(d[41]), "+f"(d[42]), "+f"(d[43]), "+f"(d[44]), "+f"(d[45]), "+f"(d[46]), "+f"(d[47])
        : "r"(a[AOFF + 0][0]), "r"(a[AOFF + 0][1]), "r"(a[AOFF + 0][2]), "r"(a[AOFF + 0][3]), "r"(a[AOFF + 1][0]), "r"(a[AOFF + 1][1]), "r"(a[AOFF + 1][2]), "r"(a[AOFF + 1][3]), "r"(a[AOFF + 2][0]), "r"(a[AOFF + 2][1]), "r"(a[AOFF + 2][2]), "r"(a[AOFF + 2][3]), "l"(descB), "n"(BOFF >> 4));
}
};
template <> struct Rng<0, 5, 9> {
template <int BOFF, int AOFF, int NA>
static __device__ __forceinline__ void run(float (&d)[48], const uint32_t (&a)[NA][4], uint64_t descB) {
    asm volatile(
        "{\n"
        ".reg .pred p0, p1;\n"
        ".reg .b64 ta, ta0, tb, tb0;\n"
        "setp.ne.b32 p0, 0, 0;\n"
        "setp.eq.b32 p1, 0, 0;\n"
        "add.s64 tb0, %64, %65;\n"
        "add.s64 tb, tb0, 1568;\n"
        "wgmma.mma_async.sync.aligned.m64n96k16.f32.bf16.bf16 {%0, %1, %2, %3, %4, %5, %6, %7, %8, %9, %10, %11, %12, %13, %14, %15, %16, %17, %18, %19, %20, %21, %22, %23, %24, %25, %26, %27, %28, %29, %30, %31, %32, %33, %34, %35, %36, %37, %38, %39, %40, %41, %42, %43, %44, %45, %46, %47}, {%48, %49, %50, %51}, tb, p1, 1, 1, 1;\n"
        "add.s64 tb, tb0, 1600;\n"
        "wgmma.mma_async.sync.aligned.m64n96k16.f32.bf16.bf16 {%0, %1, %2, %3, %4, %5, %6, %7, %8, %9, %10, %11, %12, %13, %14, %15, %16, %17, %18, %19, %20, %21, %22, %23, %24, %25, %26, %27, %28, %29, %30, %31, %32, %33, %34, %35, %36, %37, %38, %39, %40, %41, %42, %43, %44, %45, %46, %47}, {%52, %53, %54, %55}, tb, p1, 1, 1, 1;\n"
        "add.s64 tb, tb0, 1632;\n"
        "wgmma.mma_async.sync.aligned.m64n96k16.f32.bf16.bf16 {%0, %1, %2, %3, %4, %5, %6, %7, %8, %9, %10, %11, %12, %13, %14, %15, %16, %17, %18, %19, %20, %21, %22, %23, %24, %25, %26, %27, %28, %29, %30, %31, %32, %33, %34, %35, %36, %37, %38, %39, %40, %41, %42, %43, %44, %45, %46, %47}, {%56, %57, %58, %59}, tb, p1, 1, 1, 1;\n"
        "add.s64 tb, tb0, 3072;\n"
        "wgmma.mma_async.sync.aligned.m64n96k16.f32.bf16.bf16 {%0, %1, %2, %3, %4, %5, %6, %7, %8, %9, %10, %11, %12, %13, %14, %15, %16, %17, %18, %19, %20, %21, %22, %23, %24, %25, %26, %27, %28, %29, %30, %31, %32, %33, %34, %35, %36, %37, %38, %39, %40, %41, %42, %43, %44, %45, %46, %47}, {%60, %61, %62, %63}, tb, p1, 1, 1, 1;\n"
        "}\n"
        : "+f"(d[0]), "+f"(d[1]), "+f"(d[2]), "+f"(d[3]), "+f"(d[4]), "+f"(d[5]), "+f"(d[6]), "+f"(d[7]), "+f"(d[8]), "+f"(d[9]), "+f"(d[10]), "+f"(d[11]), "+f"(d[12]), "+f"(d[13]), "+f"(d[14]), "+f"(d[15]), "+f"(d[16]), "+f"(d[17]), "+f"(d[18]), "+f"(d[19]), "+f"(d[20]), "+f"(d[21]), "+f"(d[22]), "+f"(d[23]), "+f"(d[24]), "+f"(d[25]), "+f"(d[26]), "+f"(d[27]), "+f"(d[28]), "+f"(d[29]), "+f"(d[30]), "+f"(d[31]), "+f"(d[32]), "+f"(d[33]), "+f"(d[34]), "+f"(d[35]), "+f"(d[36]), "+f"(d[37]), "+f"(d[38]), "+f"(d[39]), "+f"(d[40]), "+f"(d[41]), "+f"(d[42]), "+f"(d[43]), "+f"(d[44]), "+f"(d[45]), "+f"(d[46]), "+f"(d[47])
        : "r"(a[AOFF + 0][0]), "r"(a[AOFF + 0][1]), "r"(a[AOFF + 0][2]), "r"(a[AOFF + 0][3]), "r"(a[AOFF + 1][0]), "r"(a[AOFF + 1][1]), "r"(a[AOFF + 1][2]), "r"(a[AOFF + 1][3]), "r"(a[AOFF + 2][0]), "r"(a[AOFF + 2][1]), "r"(a[AOFF + 2][2]), "r"(a[AOFF + 2][3]), "r"(a[AOFF + 3][0]), "r"(a[AOFF + 3][1]), "r"(a[AOFF + 3][2]), "r"(a[AOFF + 3][3]), "l"(descB), "n"(BOFF >> 4));
}
};
template <> struct Rng<1, 5, 9> {
template <int BOFF, int AOFF, int NA>
static __device__ __forceinline__ void run(float (&d)[48], const uint32_t (&a)[NA][4], uint64_t descB) {
    asm volatile(
        "{\n"
        ".reg .pred p0, p1;\n"
        ".reg .b64 ta, ta0, tb, tb0;\n"
        "setp.ne.b32 p0, 0, 0;\n"
        "setp.eq.b32 p1, 0, 0;\n"
        "add.s64 tb0, %64, %65;\n"
        "add.s64 tb, tb0, 160;\n"
        "wgmma.mma_async.sync.aligned.m64n96k16.f32.bf16.bf16 {%0, %1, %2, %3, %4, %5, %6, %7, %8, %9, %10, %11, %12, %13, %14, %15, %16, %17, %18, %19, %20, %21, %22, %23, %24, %25, %26, %27, %28, %29, %30, %31, %32, %33, %34, %35, %36, %37, %38, %39, %40, %41, %42, %43, %44, %45, %46, %47}, {%48, %49, %50, %51}, tb, p1, 1, 1, 1;\n"
        "add.s64 tb, tb0, 192;\n"
        "wgmma.mma_async.sync.aligned.m64n96k16.f32.bf16.bf16 {%0, %1, %2, %3, %4, %5, %6, %7, %8, %9, %10, %11, %12, %13, %14, %15, %16, %17, %18, %19, %20, %21, %22, %23, %24, %25, %26, %27, %28, %29, %30, %31, %32, %33, %34, %35, %36, %37, %38, %39, %40, %41, %42, %43, %44, %45, %46, %47}, {%52, %53, %54, %55}, tb, p1, 1, 1, 1;\n"
        "add.s64 tb, tb0, 224;\n"
        "wgmma.mma_async.sync.aligned.m64n96k16.f32.bf16.bf16 {%0, %1, %2, %3, %4, %5, %6, %7, %8, %9, %10, %11, %12, %13, %14, %15, %16, %17, %18, %19, %20, %21, %22, %23, %24, %25, %26, %27, %28, %29, %30, %31, %32, %33, %34, %35, %36, %37, %38, %39, %40, %41, %42, %43, %44, %45, %46, %47}, {%56, %57, %58, %59}, tb, p1, 1, 1, 1;\n"
        "add.s64 tb, tb0, 256;\n"
        "wgmma.mma_async.sync.aligned.m64n96k16.f32.bf16.bf16 {%0, %1, %2, %3, %4, %5, %6, %7, %8, %9, %10, %11, %12, %13, %14, %15, %16, %17, %18, %19, %20, %21, %22, %23, %24, %25, %26, %27, %28, %29, %30, %31, %32, %33, %34, %35, %36, %37, %38, %39, %40, %41, %42, %43, %44, %45, %46, %47}, {%60, %61, %62, %63}, tb, p1, 1, 1, 1;\n"
        "}\n"
        : "+f"(d[0]), "+f"(d[1]), "+f"(d[2]), "+f"(d[3]), "+f"(d[4]), "+f"(d[5]), "+f"(d[6]), "+f"(d[7]), "+f"(d[8]), "+f"(d[9]), "+f"(d[10]), "+f"(d[11]), "+f"(d[12]), "+f"(d[13]), "+f"(d[14]), "+f"(d[15]), "+f"(d[16]), "+f"(d[17]), "+f"(d[18]), "+f"(d[19]), "+f"(d[20]), "+f"(d[21]), "+f"(d[22]), "+f"(d[23]), "+f"(d[24]), "+f"(d[25]), "+f"(d[26]), "+f"(d[27]), "+f"(d[28]), "+f"(d[29]), "+f"(d[30]), "+f"(d[31]), "+f"(d[32]), "+f"(d[33]), "+f"(d[34]), "+f"(d[35]), "+f"(d[36]), "+f"(d[37]), "+f"(d[38]), "+f"(d[39]), "+f"(d[40]), "+f"(d[41]), "+f"(d[42]), "+f"(d[43]), "+f"(d[44]), "+f"(d[45]), "+f"(d[46]), "+f"(d[47])
        : "r"(a[AOFF + 0][0]), "r"(a[AOFF + 0][1]), "r"(a[AOFF + 0][2]), "r"(a[AOFF + 0][3]), "r"(a[AOFF + 1][0]), "r"(a[AOFF + 1][1]), "r"(a[AOFF + 1][2]), "r"(a[AOFF + 1][3]), "r"(a[AOFF + 2][0]), "r"(a[AOFF + 2][1]), "r"(a[AOFF + 2][2]), "r"(a[AOFF + 2][3]), "r"(a[AOFF + 3][0]), "r"(a[AOFF + 3][1]), "r"(a[AOFF + 3][2]), "r"(a[AOFF + 3][3]), "l"(descB), "n"(BOFF >> 4));
}
};
template <> struct Rng<0, 5, 10> {
template <int BOFF, int AOFF, int NA>
static __device__ __forceinline__ void run(float (&d)[48], const uint32_t (&a)[NA][4], uint64_t descB) {
    asm volatile(
        "{\n"
        ".reg .pred p0, p1;\n"
        ".reg .b64 ta, ta0, tb, tb0;\n"
        "setp.ne.b32 p0, 0, 0;\n"
        "setp.eq.b32 p1, 0, 0;\n"
        "add.s64 tb0, %68, %69;\n"
        "add.s64 tb, tb0, 1568;\n"
        "wgmma.mma_async.sync.aligned.m64n96k16.f32.bf16.bf16 {%0, %1, %2, %3, %4, %5, %6, %7, %8, %9, %10, %11, %12, %13, %14, %15, %16, %17, %18, %19, %20, %21, %22, %23, %24, %25, %26, %27, %28, %29, %30, %31, %32, %33, %34, %35, %36, %37, %38, %39, %40, %41, %42, %43, %44, %45, %46, %47}, {%48, %49, %50, %51}, tb, p1, 1, 1, 1;\n"
        "add.s64 tb, tb0, 1600;\n"
        "wgmma.mma_async.sync.aligned.m64n96k16.f32.bf16.bf16 {%0, %1, %2, %3, %4, %5, %6, %7, %8, %9, %10, %11, %12, %13, %14, %15, %16, %17, %18, %19, %20, %21, %22, %23, %24, %25, %26, %27, %28, %29, %30, %31, %32, %33, %34, %35, %36, %37, %38, %39, %40, %41, %42, %43, %44, %45, %46, %47}, {%52, %53, %54, %55}, tb, p1, 1, 1, 1;\n"
        "add.s64 tb, tb0, 1632;\n"
        "wgmma.mma_async.sync.aligned.m64n96k16.f32.bf16.bf16 {%0, %1, %2, %3, %4, %5, %6, %7, %8, %9, %10, %11, %12, %13, %14, %15, %16, %17, %18, %19, %20, %21, %22, %23, %24, %25, %26, %27, %28, %29, %30, %31, %32, %33, %34, %35, %36, %37, %38, %39, %40, %41, %42, %43, %44, %45, %46, %47}, {%56, %57, %58, %59}, tb, p1, 1, 1, 1;\n"
        "add.s64 tb, tb0, 3072;\n"
        "wgmma.mma_async.sync.aligned.m64n96k16.f32.bf16.bf16 {%0, %1, %2, %3, %4, %5, %6, %7, %8, %9, %10, %11, %12, %13, %14, %15, %16, %17, %18, %19, %20, %21, %22, %23, %24, %25, %26, %27, %28, %29, %30, %31, %32, %33, %34, %35, %36, %37, %38, %39, %40, %41, %42, %43, %44, %45, %46, %47}, {%60, %61, %62, %63}, tb, p1, 1, 1, 1;\n"
        "add.s64 tb, tb0, 3104;\n"
        "wgmma.mma_async.sync.aligned.m64n96k16.f32.bf16.bf16 {%0, %1, %2, %3, %4, %5, %6, %7, %8, %9, %10, %11, %12, %13, %14, %15, %16, %17, %18, %19, %20, %21, %22, %23, %24, %25, %26, %27, %28, %29, %30, %31, %32, %33, %34, %35, %36, %37, %38, %39, %40, %41, %42, %43, %44, %45, %46, %47}, {%64, %65, %66, %67}, tb, p1, 1, 1, 1;\n"
        "}\n"
        : "+f"(d[0]), "+f"(d[1]), "+f"(d[2]), "+f"(d[3]), "+f"(d[4]), "+f"(d[5]), "+f"(d[6]), "+f"(d[7]), "+f"(d[8]), "+f"(d[9]), "+f"(d[10]), "+f"(d[11]), "+f"(d[12]), "+f"(d[13]), "+f"(d[14]), "+f"(d[15]), "+f"(d[16]), "+f"(d[17]), "+f"(d[18]), "+f"(d[19]), "+f"(d[20]), "+f"(d[21]), "+f"(d[22]), "+f"(d[23]), "+f"(d[24]), "+f"(d[25]), "+f"(d[26]), "+f"(d[27]), "+f"(d[28]), "+f"(d[29]), "+f"(d[30]), "+f"(d[31]), "+f"(d[32]), "+f"(d[33]), "+f"(d[34]), "+f"(d[35]), "+f"(d[36]), "+f"(d[37]), "+f"(d[38]), "+f"(d[39]), "+f"(d[40]), "+f"(d[41]), "+f"(d[42]), "+f"(d[43]), "+f"(d[44]), "+f"(d[45]), "+f"(d[46]), "+f"(d[47])
        : "r"(a[AOFF + 0][0]), "r"(a[AOFF + 0][1]), "r"(a[AOFF + 0][2]), "r"(a[AOFF + 0][3]), "r"(a[AOFF + 1][0]), "r"(a[AOFF + 1][1]), "r"(a[AOFF + 1][2]), "r"(a[AOFF + 1][3]), "r"(a[AOFF + 2][0]), "r"(a[AOFF + 2][1]), "r"(a[AOFF + 2][2]), "r"(a[AOFF + 2][3]), "r"(a[AOFF + 3][0]), "r"(a[AOFF + 3][1]), "r"(a[AOFF + 3][2]), "r"(a[AOFF + 3][3]), "r"(a[AOFF + 4][0]), "r"(a[AOFF + 4][1]), "r"(a[AOFF + 4][2]), "r"(a[AOFF + 4][3]), "l"(descB), "n"(BOFF >> 4));
}
};
template <> struct Rng<1, 5, 10> {
template <int BOFF, int AOFF, int NA>
static __device__ __forceinline__ void run(float (&d)[48], const uint32_t (&a)[NA][4], uint64_t descB) {
    asm volatile(
        "{\n"
        ".reg .pred p0, p1;\n"
        ".reg .b64 ta, ta0, tb, tb0;\n"
        "setp.ne.b32 p0, 0, 0;\n"
        "setp.eq.b32 p1, 0, 0;\n"
        "add.s64 tb0, %68, %69;\n"
        "add.s64 tb, tb0, 160;\n"
        "wgmma.mma_async.sync.aligned.m64n96k16.f32.bf16.bf16 {%0, %1, %2, %3, %4, %5, %6, %7, %8, %9, %10, %11, %12, %13, %14, %15, %16, %17, %18, %19, %20, %21, %22, %23, %24, %25, %26, %27, %28, %29, %30, %31, %32, %33, %34, %35, %36, %37, %38, %39, %40, %41, %42, %43, %44, %45, %46, %47}, {%48, %49, %50, %51}, tb, p1, 1, 1, 1;\n"
        "add.s64 tb, tb0, 192;\n"
        "wgmma.mma_async.sync.aligned.m64n96k16.f32.bf16.bf16 {%0, %1, %2, %3, %4, %5, %6, %7, %8, %9, %10, %11, %12, %13, %14, %15, %16, %17, %18, %19, %20, %21, %22, %23, %24, %25, %26, %27, %28, %29, %30, %31, %32, %33, %34, %35, %36, %37, %38, %39, %40, %41, %42, %43, %44, %45, %46, %47}, {%52, %53, %54, %55}, tb, p1, 1, 1, 1;\n"
        "add.s64 tb, tb0, 224;\n"
        "wgmma.mma_async.sync.aligned.m64n96k16.f32.bf16.bf16 {%0, %1, %2, %3, %4, %5, %6, %7, %8, %9, %10, %11, %12, %13, %14, %15, %16, %17, %18, %19, %20, %21, %22, %23, %24, %25, %26, %27, %28, %29, %30, %31, %32, %33, %34, %35, %36, %37, %38, %39, %40, %41, %42, %43, %44, %45, %46, %47}, {%56, %57, %58, %59}, tb, p1, 1, 1, 1;\n"
        "add.s64 tb, tb0, 256;\n"
        "wgmma.mma_async.sync.aligned.m64n96k16.f32.bf16.bf16 {%0, %1, %2, %3, %4, %5, %6, %7, %8, %9, %10, %11, %12, %13, %14, %15, %16, %17, %18, %19, %20, %21, %22, %23, %24, %25, %26, %27, %28, %29, %30, %31, %32, %33, %34, %35, %36, %37, %38, %39, %40, %41, %42, %43, %44, %45, %46, %47}, {%60, %61, %62, %63}, tb, p1, 1, 1, 1;\n"
        "add.s64 tb, tb0, 288;\n"
        "wgmma.mma_async.sync.aligned.m64n96k16.f32.bf16.bf16 {%0, %1, %2, %3, %4, %5, %6, %7, %8, %9, %10, %11, %12, %13, %14, %15, %16, %17, %18, %19, %20, %21, %22, %23, %24, %25, %26, %27, %28, %29, %30, %31, %32, %33, %34, %35, %36, %37, %38, %39, %40, %41, %42, %43, %44, %45, %46, %47}, {%64, %65, %66, %67}, tb, p1, 1, 1, 1;\n"
        "}\n"
        : "+f"(d[0]), "+f"(d[1]), "+f"(d[2]), "+f"(d[3]), "+f"(d[4]), "+f"(d[5]), "+f"(d[6]), "+f"(d[7]), "+f"(d[8]), "+f"(d[9]), "+f"(d[10]), "+f"(d[11]), "+f"(d[12]), "+f"(d[13]), "+f"(d[14]), "+f"(d[15]), "+f"(d[16]), "+f"(d[17]), "+f"(d[18]), "+f"(d[19]), "+f"(d[20]), "+f"(d[21]), "+f"(d[22]), "+f"(d[23]), "+f"(d[24]), "+f"(d[25]), "+f"(d[26]), "+f"(d[27]), "+f"(d[28]), "+f"(d[29]), "+f"(d[30]), "+f"(d[31]), "+f"(d[32]), "+f"(d[33]), "+f"(d[34]), "+f"(d[35]), "+f"(d[36]), "+f"(d[37]), "+f"(d[38]), "+f"(d[39]), "+f"(d[40]), "+f"(d[41]), "+f"(d[42]), "+f"(d[43]), "+f"(d[44]), "+f"(d[45]), "+f"(d[46]), "+f"(d[47])
        : "r"(a[AOFF + 0][0]), "r"(a[AOFF + 0][1]), "r"(a[AOFF + 0][2]), "r"(a[AOFF + 0][3]), "r"(a[AOFF + 1][0]), "r"(a[AOFF + 1][1]), "r"(a[AOFF + 1][2]), "r"(a[AOFF + 1][3]), "r"(a[AOFF + 2][0]), "r"(a[AOFF + 2][1]), "r"(a[AOFF + 2][2]), "r"(a[AOFF + 2][3]), "r"(a[AOFF + 3][0]), "r"(a[AOFF + 3][1]), "r"(a[AOFF + 3][2]), "r"(a[AOFF + 3][3]), "r"(a[AOFF + 4][0]), "r"(a[AOFF + 4][1]), "r"(a[AOFF + 4][2]), "r"(a[AOFF + 4][3]), "l"(descB), "n"(BOFF >> 4));
}
};
template <> struct Rng<0, 5, 12> {
template <int BOFF, int AOFF, int NA>
static __device__ __forceinline__ void run(float (&d)[48], const uint32_t (&a)[NA][4], uint64_t descB) {
    asm volatile(
        "{\n"
        ".reg .pred p0, p1;\n"
        ".reg .b64 ta, ta0, tb, tb0;\n"
        "setp.ne.b32 p0, 0, 0;\n"
        "setp.eq.b32 p1, 0, 0;\n"
        "add.s64 tb0, %76, %77;\n"
        "add.s64 tb, tb0, 1568;\n"
        "wgmma.mma_async.sync.aligned.m64n96k16.f32.bf16.bf16 {%0, %1, %2, %3, %4, %5, %6, %7, %8, %9, %10, %11, %12, %13, %14, %15, %16, %17, %18, %19, %20, %21, %22, %23, %24, %25, %26, %27, %28, %29, %30, %31, %32, %33, %34, %35, %36, %37, %38, %39, %40, %41, %42, %43, %44, %45, %46, %47}, {%48, %49, %50, %51}, tb, p1, 1, 1, 1;\n"
        "add.s64 tb, tb0, 1600;\n"
        "wgmma.mma_async.sync.aligned.m64n96k16.f32.bf16.bf16 {%0, %1, %2, %3, %4, %5, %6, %7, %8, %9, %10, %11, %12, %13, %14, %15, %16, %17, %18, %19, %20, %21, %22, %23, %24, %25, %26, %27, %28, %29, %30, %31, %32, %33, %34, %35, %36, %37, %38, %39, %40, %41, %42, %43, %44, %45, %46, %47}, {%52, %53, %54, %55}, tb, p1, 1, 1, 1;\n"
        "add.s64 tb, tb0, 1632;\n"
        "wgmma.mma_async.sync.aligned.m64n96k16.f32.bf16.bf16 {%0, %1, %2, %3, %4, %5, %6, %7, %8, %9, %10, %11, %12, %13, %14, %15, %16, %17, %18, %19, %20, %21, %22, %23, %24, %25, %26, %27, %28, %29, %30, %31, %32, %33, %34, %35, %36, %37, %38, %39, %40, %41, %42, %43, %44, %45, %46, %47}, {%56, %57, %58, %59}, tb, p1, 1, 1, 1;\n"
        "add.s64 tb, tb0, 3072;\n"
        "wgmma.mma_async.sync.aligned.m64n96k16.f32.bf16.bf16 {%0, %1, %2, %3, %4, %5, %6, %7, %8, %9, %10, %11, %12, %13, %14, %15, %16, %17, %18, %19, %20, %21, %22, %23, %24, %25, %26, %27, %28, %29, %30, %31, %32, %33, %34, %35, %36, %37, %38, %39, %40, %41, %42, %43, %44, %45, %46, %47}, {%60, %61, %62, %63}, tb, p1, 1, 1, 1;\n"
        "add.s64 tb, tb0, 3104;\n"
        "wgmma.mma_async.sync.aligned.m64n96k16.f32.bf16.bf16 {%0, %1, %2, %3, %4, %5, %6, %7, %8, %9, %10, %11, %12, %13, %14, %15, %16, %17, %18, %19, %20, %21, %22, %23, %24, %25, %26, %27, %28, %29, %30, %31, %32, %33, %34, %35, %36, %37, %38, %39, %40, %41, %42, %43, %44, %45, %46, %47}, {%64, %65, %66, %67}, tb, p1, 1, 1, 1;\n"
        "add.s64 tb, tb0, 3136;\n"
        "wgmma.mma_async.sync.aligned.m64n96k16.f32.bf16.bf16 {%0, %1, %2, %3, %4, %5, %6, %7, %8, %9, %10, %11, %12, %13, %14, %15, %16, %17, %18, %19, %20, %21, %22, %23, %24, %25, %26, %27, %28, %29, %30, %31, %32, %33, %34, %35, %36, %37, %38, %39, %40, %41, %42, %43, %44, %45, %46, %47}, {%68, %69, %70, %71}, tb, p1, 1, 1, 1;\n"
        "add.s64 tb, tb0, 3168;\n"
        "wgmma.mma_async.sync.aligned.m64n96k16.f32.bf16.bf16 {%0, %1, %2, %3, %4, %5, %6, %7, %8, %9, %10, %11, %12, %13, %14, %15, %16, %17, %18, %19, %20, %21, %22, %23, %24, %25, %26, %27, %28, %29, %30, %31, %32, %33, %34, %35, %36, %37, %38, %39, %40, %41, %42, %43, %44, %45, %46, %47}, {%72, %73, %74, %75}, tb, p1, 1, 1, 1;\n"
        "}\n"
        : "+f"(d[0]), "+f"(d[1]), "+f"(d[2]), "+f"(d[3]), "+f"(d[4]), "+f"(d[5]), "+f"(d[6]), "+f"(d[7]), "+f"(d[8]), "+f"(d[9]), "+f"(d[10]), "+f"(d[11]), "+f"(d[12]), "+f"(d[13]), "+f"(d[14]), "+f"(d[15]), "+f"(d[16]), "+f"(d[17]), "+f"(d[18]), "+f"(d[19]), "+f"(d[20]), "+f"(d[21]), "+f"(d[22]), "+f"(d[23]), "+f"(d[24]), "+f"(d[25]), "+f"(d[26]), "+f"(d[27]), "+f"(d[28]), "+f"(d[29]), "+f"(d[30]), "+f"(d[31]), "+f"(d[32]), "+f"(d[33]), "+f"(d[34]), "+f"(d[35]), "+f"(d[36]), "+f"(d[37]), "+f"(d[38]), "+f"(d[39]), "+f"(d[40]), "+f"(d[41]), "+f"(d[42]), "+f"(d[43]), "+f"(d[44]), "+f"(d[45]), "+f"(d[46]), "+f"(d[47])
        : "r"(a[AOFF + 0][0]), "r"(a[AOFF + 0][1]), "r"(a[AOFF + 0][2]), "r"(a[AOFF + 0][3]), "r"(a[AOFF + 1][0]), "r"(a[AOFF + 1][1]), "r"(a[AOFF + 1][2]), "r"(a[AOFF + 1][3]), "r"(a[AOFF + 2][0]), "r"(a[AOFF + 2][1]), "r"(a[AOFF + 2][2]), "r"(a[AOFF + 2][3]), "r"(a[AOFF + 3][0]), "r"(a[AOFF + 3][1]), "r"(a[AOFF + 3][2]), "r"(a[AOFF + 3][3]), "r"(a[AOFF + 4][0]), "r"(a[AOFF + 4][1]), "r"(a[AOFF + 4][2]), "r"(a[AOFF + 4][3]), "r"(a[AOFF + 5][0]), "r"(a[AOFF + 5][1]), "r"(a[AOFF + 5][2]), "r"(a[AOFF + 5][3]), "r"(a[AOFF + 6][0]), "r"(a[AOFF + 6][1]), "r"(a[AOFF + 6][2]), "r"(a[AOFF + 6][3]), "l"(descB), "n"(BOFF >> 4));
}
};
template <> struct Rng<1, 5, 12> {
template <int BOFF, int AOFF, int NA>
static __device__ __forceinline__ void run(float (&d)[48], const uint32_t (&a)[NA][4], uint64_t descB) {
    asm volatile(
        "{\n"
        ".reg .pred p0, p1;\n"
        ".reg .b64 ta, ta0, tb, tb0;\n"
        "setp.ne.b32 p0, 0, 0;\n"
        "setp.eq.b32 p1, 0, 0;\n"
        "add.s64 tb0, %76, %77;\n"
        "add.s64 tb, tb0, 160;\n"
        "wgmma.mma_async.sync.aligned.m64n96k16.f32.bf16.bf16 {%0, %1, %2, %3, %4, %5, %6, %7, %8, %9, %10, %11, %12, %13, %14, %15, %16, %17, %18, %19, %20, %21, %22, %23, %24, %25, %26, %27, %28, %29, %30, %31, %32, %33, %34, %35, %36, %37, %38, %39, %40, %41, %42, %43, %44, %45, %46, %47}, {%48, %49, %50, %51}, tb, p1, 1, 1, 1;\n"
        "add.s64 tb, tb0, 192;\n"
        "wgmma.mma_async.sync.aligned.m64n96k16.f32.bf16.bf16 {%0, %1, %2, %3, %4, %5, %6, %7, %8, %9, %10, %11, %12, %13, %14, %15, %16, %17, %18, %19, %20, %21, %22, %23, %24, %25, %26, %27, %28, %29, %30, %31, %32, %33, %34, %35, %36, %37, %38, %39, %40, %41, %42, %43, %44, %45, %46, %47}, {%52, %53, %54, %55}, tb, p1, 1, 1, 1;\n"
        "add.s64 tb, tb0, 224;\n"
        "wgmma.mma_async.sync.aligned.m64n96k16.f32.bf16.bf16 {%0, %1, %2, %3, %4, %5, %6, %7, %8, %9, %10, %11, %12, %13, %14, %15, %16, %17, %18, %19, %20, %21, %22, %23, %24, %25, %26, %27, %28, %29, %30, %31, %32, %33, %34, %35, %36, %37, %38, %39, %40, %41, %42, %43, %44, %45, %46, %47}, {%56, %57, %58, %59}, tb, p1, 1, 1, 1;\n"
        "add.s64 tb, tb0, 256;\n"
        "wgmma.mma_async.sync.aligned.m64n96k16.f32.bf16.bf16 {%0, %1, %2, %3, %4, %5, %6, %7, %8, %9, %10, %11, %12, %13, %14, %15, %16, %17, %18, %19, %20, %21, %22, %23, %24, %25, %26, %27, %28, %29, %30, %31, %32, %33, %34, %35, %36, %37, %38, %39, %40, %41, %42, %43, %44, %45, %46, %47}, {%60, %61, %62, %63}, tb, p1, 1, 1, 1;\n"
        "add.s64 tb, tb0, 288;\n"
        "wgmma.mma_async.sync.aligned.m64n96k16.f32.bf16.bf16 {%0, %1, %2, %3, %4, %5, %6, %7, %8, %9, %10, %11, %12, %13, %14, %15, %16, %17, %18, %19, %20, %21, %22, %23, %24, %25, %26, %27, %28, %29, %30, %31, %32, %33, %34, %35, %36, %37, %38, %39, %40, %41, %42, %43, %44, %45, %46, %47}, {%64, %65, %66, %67}, tb, p1, 1, 1, 1;\n"
        "add.s64 tb, tb0, 320;\n"
        "wgmma.mma_async.sync.aligned.m64n96k16.f32.bf16.bf16 {%0, %1, %2, %3, %4, %5, %6, %7, %8, %9, %10, %11, %12, %13, %14, %15, %16, %17, %18, %19, %20, %21, %22, %23, %24, %25, %26, %27, %28, %29, %30, %31, %32, %33, %34, %35, %36, %37, %38, %39, %40, %41, %42, %43, %44, %45, %46, %47}, {%68, %69, %70, %71}, tb, p1, 1, 1, 1;\n"
        "add.s64 tb, tb0, 352;\n"
        "wgmma.mma_async.sync.aligned.m64n96k16.f32.bf16.bf16 {%0, %1, %2, %3, %4, %5, %6, %7, %8, %9, %10, %11, %12, %13, %14, %15, %16, %17, %18, %19, %20, %21, %22, %23, %24, %25, %26, %27, %28, %29, %30, %31, %32, %33, %34, %35, %36, %37, %38, %39, %40, %41, %42, %43, %44, %45, %46, %47}, {%72, %73, %74, %75}, tb, p1, 1, 1, 1;\n"
        "}\n"
        : "+f"(d[0]), "+f"(d[1]), "+f"(d[2]), "+f"(d[3]), "+f"(d[4]), "+f"(d[5]), "+f"(d[6]), "+f"(d[7]), "+f"(d[8]), "+f"(d[9]), "+f"(d[10]), "+f"(d[11]), "+f"(d[12]), "+f"(d[13]), "+f"(d[14]), "+f"(d[15]), "+f"(d[16]), "+f"(d[17]), "+f"(d[18]), "+f"(d[19]), "+f"(d[20]), "+f"(d[21]), "+f"(d[22]), "+f"(d[23]), "+f"(d[24]), "+f"(d[25]), "+f"(d[26]), "+f"(d[27]), "+f"(d[28]), "+f"(d[29]), "+f"(d[30]), "+f"(d[31]), "+f"(d[32]), "+f"(d[33]), "+f"(d[34]), "+f"(d[35]), "+f"(d[36]), "+f"(d[37]), "+f"(d[38]), "+f"(d[39]), "+f"(d[40]), "+f"(d[41]), "+f"(d[42]), "+f"(d[43]), "+f"(d[44]), "+f"(d[45]), "+f"(d[46]), "+f"(d[47])
        : "r"(a[AOFF + 0][0]), "r"(a[AOFF + 0][1]), "r"(a[AOFF + 0][2]), "r"(a[AOFF + 0][3]), "r"(a[AOFF + 1][0]), "r"(a[AOFF + 1][1]), "r"(a[AOFF + 1][2]), "r"(a[AOFF + 1][3]), "r"(a[AOFF + 2][0]), "r"(a[AOFF + 2][1]), "r"(a[AOFF + 2][2]), "r"(a[AOFF + 2][3]), "r"(a[AOFF + 3][0]), "r"(a[AOFF + 3][1]), "r"(a[AOFF + 3][2]), "r"(a[AOFF + 3][3]), "r"(a[AOFF + 4][0]), "r"(a[AOFF + 4][1]), "r"(a[AOFF + 4][2]), "r"(a[AOFF + 4][3]), "r"(a[AOFF + 5][0]), "r"(a[AOFF + 5][1]), "r"(a[AOFF + 5][2]), "r"(a[AOFF + 5][3]), "r"(a[AOFF + 6][0]), "r"(a[AOFF + 6][1]), "r"(a[AOFF + 6][2]), "r"(a[AOFF + 6][3]), "l"(descB), "n"(BOFF >> 4));
}
};
template <> struct Rng<0, 6, 9> {
template <int BOFF, int AOFF, int NA>
static __device__ __forceinline__ void run(float (&d)[48], const uint32_t (&a)[NA][4], uint64_t descB) {
    asm volatile(
        "{\n"
        ".reg .pred p0, p1;\n"
        ".reg .b64 ta, ta0, tb, tb0;\n"
        "setp.ne.b32 p0, 0, 0;\n"
        "setp.eq.b32 p1, 0, 0;\n"
        "add.s64 tb0, %60, %61;\n"
        "add.s64 tb, tb0, 1600;\n"
        "wgmma.mma_async.sync.aligned.m64n96k16.f32.bf16.bf16 {%0, %1, %2, %3, %4, %5, %6, %7, %8, %9, %10, %11, %12, %13, %14, %15, %16, %17, %18, %19, %20, %21, %22, %23, %24, %25, %26, %27, %28, %29, %30, %31, %32, %33, %34, %35, %36, %37, %38, %39, %40, %41, %42, %43, %44, %45, %46, %47}, {%48, %49, %50, %51}, tb, p1, 1, 1, 1;\n"
        "add.s64 tb, tb0, 1632;\n"
        "wgmma.mma_async.sync.aligned.m64n96k16.f32.bf16.bf16 {%0, %1, %2, %3, %4, %5, %6, %7, %8, %9, %10, %11, %12, %13, %14, %15, %16, %17, %18, %19, %20, %21, %22, %23, %24, %25, %26, %27, %28, %29, %30, %31, %32, %33, %34, %35, %36, %37, %38, %39, %40, %41, %42, %43, %44, %45, %46, %47}, {%52, %53, %54, %55}, tb, p1, 1, 1, 1;\n"
        "add.s64 tb, tb0, 3072;\n"
        "wgmma.mma_async.sync.aligned.m64n96k16.f32.bf16.bf16 {%0, %1, %2, %3, %4, %5, %6, %7, %8, %9, %10, %11, %12, %13, %14, %15, %16, %17, %18, %19, %20, %21, %22, %23, %24, %25, %26, %27, %28, %29, %30, %31, %32, %33, %34, %35, %36, %37, %38, %39, %40, %41, %42, %43, %44, %45, %46, %47}, {%56, %57, %58, %59}, tb, p1, 1, 1, 1;\n"
        "}\n"
        : "+f"(d[0]), "+f"(d[1]), "+f"(d[2]), "+f"(d[3]), "+f"(d[4]), "+f"(d[5]), "+f"(d[6]), "+f"(d[7]), "+f"(d[8]), "+f"(d[9]), "+f"(d[10]), "+f"(d[11]), "+f"(d[12]), "+f"(d[13]), "+f"(d[14]), "+f"(d[15]), "+f"(d[16]), "+f"(d[17]), "+f"(d[18]), "+f"(d[19]), "+f"(d[20]), "+f"(d[21]), "+f"(d[22]), "+f"(d[23]), "+f"(d[24]), "+f"(d[25]), "+f"(d[26]), "+f"(d[27]), "+f"(d[28]), "+f"(d[29]), "+f"(d[30]), "+f"(d[31]), "+f"(d[32]), "+f"(d[33]), "+f"(d[34]), "+f"(d[35]), "+f"(d[36]), "+f"(d[37]), "+f"(d[38]), "+f"(d[39]), "+f"(d[40]), "+f"(d[41]), "+f"(d[42]), "+f"(d[43]), "+f"(d[44]), "+f"(d[45]), "+f"(d[46]), "+f"(d[47])
        : "r"(a[AOFF + 0][0]), "r"(a[AOFF + 0][1]), "r"(a[AOFF + 0][2]), "r"(a[AOFF + 0][3]), "r"(a[AOFF + 1][0]), "r"(a[AOFF + 1][1]), "r"(a[AOFF + 1][2]), "r"(a[AOFF + 1][3]), "r"(a[AOFF + 2][0]), "r"(a[AOFF + 2][1]), "r"(a[AOFF + 2][2]), "r"(a[AOFF + 2][3]), "l"(descB), "n"(BOFF >> 4));
}
};
template <> struct Rng<1, 6, 9> {
template <int BOFF, int AOFF, int NA>
static __device__ __forceinline__ void run(float (&d)[48], const uint32_t (&a)[NA][4], uint64_t descB) {
    asm volatile(
        "{\n"
        ".reg .pred p0, p1;\n"
        ".reg .b64 ta, ta0, tb, tb0;\n"
        "setp.ne.b32 p0, 0, 0;\n"
        "setp.eq.b32 p1, 0, 0;\n"
        "add.s64 tb0, %60, %61;\n"
        "add.s64 tb, tb0, 192;\n"
        "wgmma.mma_async.sync.aligned.m64n96k16.f32.bf16.bf16 {%0, %1, %2, %3, %4, %5, %6, %7, %8, %9, %10, %11, %12, %13, %14, %15, %16, %17, %18, %19, %20, %21, %22, %23, %24, %25, %26, %27, %28, %29, %30, %31, %32, %33, %34, %35, %36, %37, %38, %39, %40, %41, %42, %43, %44, %45, %46, %47}, {%48, %49, %50, %51}, tb, p1, 1, 1, 1;\n"
        "add.s64 tb, tb0, 224;\n"
        "wgmma.mma_async.sync.aligned.m64n96k16.f32.bf16.bf16 {%0, %1, %2, %3, %4, %5, %6, %7, %8, %9, %10, %11, %12, %13, %14, %15, %16, %17, %18, %19, %20, %21, %22, %23, %24, %25, %26, %27, %28, %29, %30, %31, %32, %33, %34, %35, %36, %37, %38, %39, %40, %41, %42, %43, %44, %45, %46, %47}, {%52, %53, %54, %55}, tb, p1, 1, 1, 1;\n"
        "add.s64 tb, tb0, 256;\n"
        "wgmma.mma_async.sync.aligned.m64n96k16.f32.bf16.bf16 {%0, %1, %2, %3, %4, %5, %6, %7, %8, %9, %10, %11, %12, %13, %14, %15, %16, %17, %18, %19, %20, %21, %22, %23, %24, %25, %26, %27, %28, %29, %30, %31, %32, %33, %34, %35, %36, %37, %38, %39, %40, %41, %42, %43, %44, %45, %46, %47}, {%56, %57, %58, %59}, tb, p1, 1, 1, 1;\n"
        "}\n"
        : "+f"(d[0]), "+f"(d[1]), "+f"(d[2]), "+f"(d[3]), "+f"(d[4]), "+f"(d[5]), "+f"(d[6]), "+f"(d[7]), "+f"(d[8]), "+f"(d[9]), "+f"(d[10]), "+f"(d[11]), "+f"(d[12]), "+f"(d[13]), "+f"(d[14]), "+f"(d[15]), "+f"(d[16]), "+f"(d[17]), "+f"(d[18]), "+f"(d[19]), "+f"(d[20]), "+f"(d[21]), "+f"(d[22]), "+f"(d[23]), "+f"(d[24]), "+f"(d[25]), "+f"(d[26]), "+f"(d[27]), "+f"(d[28]), "+f"(d[29]), "+f"(d[30]), "+f"(d[31]), "+f"(d[32]), "+f"(d[33]), "+f"(d[34]), "+f"(d[35]), "+f"(d[36]), "+f"(d[37]), "+f"(d[38]), "+f"(d[39]), "+f"(d[40]), "+f"(d[41]), "+f"(d[42]), "+f"(d[43]), "+f"(d[44]), "+f"(d[45]), "+f"(d[46]), "+f"(d[47])
        : "r"(a[AOFF + 0][0]), "r"(a[AOFF + 0][1]), "r"(a[AOFF + 0][2]), "r"(a[AOFF + 0][3]), "r"(a[AOFF + 1][0]), "r"(a[AOFF + 1][1]), "r"(a[AOFF + 1][2]), "r"(a[AOFF + 1][3]), "r"(a[AOFF + 2][0]), "r"(a[AOFF + 2][1]), "r"(a[AOFF + 2][2]), "r"(a[AOFF + 2][3]), "l"(descB), "n"(BOFF >> 4));
}
};
template <> struct Rng<0, 6, 10> {
template <int BOFF, int AOFF, int NA>
static __device__ __forceinline__ void run(float (&d)[48], const uint32_t (&a)[NA][4], uint64_t descB) {
    asm volatile(
        "{\n"
        ".reg .pred p0, p1;\n"
        ".reg .b64 ta, ta0, tb, tb0;\n"
        "setp.ne.b32 p0, 0, 0;\n"
        "setp.eq.b32 p1, 0, 0;\n"
        "add.s64 tb0, %64, %65;\n"
        "add.s64 tb, tb0, 1600;\n"
        "wgmma.mma_async.sync.aligned.m64n96k16.f32.bf16.bf16 {%0, %1, %2, %3, %4, %5, %6, %7, %8, %9, %10, %11, %12, %13, %14, %15, %16, %17, %18, %19, %20, %21, %22, %23, %24, %25, %26, %27, %28, %29, %30, %31, %32, %33, %34, %35, %36, %37, %38, %39, %40, %41, %42, %43, %44, %45, %46, %47}, {%48, %49, %50, %51}, tb, p1, 1, 1, 1;\n"
        "add.s64 tb, tb0, 1632;\n"
        "wgmma.mma_async.sync.aligned.m64n96k16.f32.bf16.bf16 {%0, %1, %2, %3, %4, %5, %6, %7, %8, %9, %10, %11, %12, %13, %14, %15, %16, %17, %18, %19, %20, %21, %22, %23, %24, %25, %26, %27, %28, %29, %30, %31, %32, %33, %34, %35, %36, %37, %38, %39, %40, %41, %42, %43, %44, %45, %46, %47}, {%52, %53, %54, %55}, tb, p1, 1, 1, 1;\n"
        "add.s64 tb, tb0, 3072;\n"
        "wgmma.mma_async.sync.aligned.m64n96k16.f32.bf16.bf16 {%0, %1, %2, %3, %4, %5, %6, %7, %8, %9, %10, %11, %12, %13, %14, %15, %16, %17, %18, %19, %20, %21, %22, %23, %24, %25, %26, %27, %28, %29, %30, %31, %32, %33, %34, %35, %36, %37, %38, %39, %40, %41, %42, %43, %44, %45, %46, %47}, {%56, %57, %58, %59}, tb, p1, 1, 1, 1;\n"
        "add.s64 tb, tb0, 3104;\n"
        "wgmma.mma_async.sync.aligned.m64n96k16.f32.bf16.bf16 {%0, %1, %2, %3, %4, %5, %6, %7, %8, %9, %10, %11, %12, %13, %14, %15, %16, %17, %18, %19, %20, %21, %22, %23, %24, %25, %26, %27, %28, %29, %30, %31, %32, %33, %34, %35, %36, %37, %38, %39, %40, %41, %42, %43, %44, %45, %46, %47}, {%60, %61, %62, %63}, tb, p1, 1, 1, 1;\n"
        "}\n"
        : "+f"(d[0]), "+f"(d[1]), "+f"(d[2]), "+f"(d[3]), "+f"(d[4]), "+f"(d[5]), "+f"(d[6]), "+f"(d[7]), "+f"(d[8]), "+f"(d[9]), "+f"(d[10]), "+f"(d[11]), "+f"(d[12]), "+f"(d[13]), "+f"(d[14]), "+f"(d[15]), "+f"(d[16]), "+f"(d[17]), "+f"(d[18]), "+f"(d[19]), "+f"(d[20]), "+f"(d[21]), "+f"(d[22]), "+f"(d[23]), "+f"(d[24]), "+f"(d[25]), "+f"(d[26]), "+f"(d[27]), "+f"(d[28]), "+f"(d[29]), "+f"(d[30]), "+f"(d[31]), "+f"(d[32]), "+f"(d[33]), "+f"(d[34]), "+f"(d[35]), "+f"(d[36]), "+f"(d[37]), "+f"(d[38]), "+f"(d[39]), "+f"(d[40]), "+f"(d[41]), "+f"(d[42]), "+f"(d[43]), "+f"(d[44]), "+f"(d[45]), "+f"(d[46]), "+f"(d[47])
        : "r"(a[AOFF + 0][0]), "r"(a[AOFF + 0][1]), "r"(a[AOFF + 0][2]), "r"(a[AOFF + 0][3]), "r"(a[AOFF + 1][0]), "r"(a[AOFF + 1][1]), "r"(a[AOFF + 1][2]), "r"(a[AOFF + 1][3]), "r"(a[AOFF + 2][0]), "r"(a[AOFF + 2][1]), "r"(a[AOFF + 2][2]), "r"(a[AOFF + 2][3]), "r"(a[AOFF + 3][0]), "r"(a[AOFF + 3][1]), "r"(a[AOFF + 3][2]), "r"(a[AOFF + 3][3]), "l"(descB), "n"(BOFF >> 4));
}
};
template <> struct Rng<1, 6, 10> {
template <int BOFF, int AOFF, int NA>
static __device__ __forceinline__ void run(float (&d)[48], const uint32_t (&a)[NA][4], uint64_t descB) {
    asm volatile(
        "{\n"
        ".reg .pred p0, p1;\n"
        ".reg .b64 ta, ta0, tb, tb0;\n"
        "setp.ne.b32 p0, 0, 0;\n"
        "setp.eq.b32 p1, 0, 0;\n"
        "add.s64 tb0, %64, %65;\n"
        "add.s64 tb, tb0, 192;\n"
        "wgmma.mma_async.sync.aligned.m64n96k16.f32.bf16.bf16 {%0, %1, %2, %3, %4, %5, %6, %7, %8, %9, %10, %11, %12, %13, %14, %15, %16, %17, %18, %19, %20, %21, %22, %23, %24, %25, %26, %27, %28, %29, %30, %31, %32, %33, %34, %35, %36, %37, %38, %39, %40, %41, %42, %43, %44, %45, %46, %47}, {%48, %49, %50, %51}, tb, p1, 1, 1, 1;\n"
        "add.s64 tb, tb0, 224;\n"
        "wgmma.mma_async.sync.aligned.m64n96k16.f32.bf16.bf16 {%0, %1, %2, %3, %4, %5, %6, %7, %8, %9, %10, %11, %12, %13, %14, %15, %16, %17, %18, %19, %20, %21, %22, %23, %24, %25, %26, %27, %28, %29, %30, %31, %32, %33, %34, %35, %36, %37, %38, %39, %40, %41, %42, %43, %44, %45, %46, %47}, {%52, %53, %54, %55}, tb, p1, 1, 1, 1;\n"
        "add.s64 tb, tb0, 256;\n"
        "wgmma.mma_async.sync.aligned.m64n96k16.f32.bf16.bf16 {%0, %1, %2, %3, %4, %5, %6, %7, %8, %9, %10, %11, %12, %13, %14, %15, %16, %17, %18, %19, %20, %21, %22, %23, %24, %25, %26, %27, %28, %29, %30, %31, %32, %33, %34, %35, %36, %37, %38, %39, %40, %41, %42, %43, %44, %45, %46, %47}, {%56, %57, %58, %59}, tb, p1, 1, 1, 1;\n"
        "add.s64 tb, tb0, 288;\n"
        "wgmma.mma_async.sync.aligned.m64n96k16.f32.bf16.bf16 {%0, %1, %2, %3, %4, %5, %6, %7, %8, %9, %10, %11, %12, %13, %14, %15, %16, %17, %18, %19, %20, %21, %22, %23, %24, %25, %26, %27, %28, %29, %30, %31, %32, %33, %34, %35, %36, %37, %38, %39, %40, %41, %42, %43, %44, %45, %46, %47}, {%60, %61, %62, %63}, tb, p1, 1, 1, 1;\n"
        "}\n"
        : "+f"(d[0]), "+f"(d[1]), "+f"(d[2]), "+f"(d[3]), "+f"(d[4]), "+f"(d[5]), "+f"(d[6]), "+f"(d[7]), "+f"(d[8]), "+f"(d[9]), "+f"(d[10]), "+f"(d[11]), "+f"(d[12]), "+f"(d[13]), "+f"(d[14]), "+f"(d[15]), "+f"(d[16]), "+f"(d[17]), "+f"(d[18]), "+f"(d[19]), "+f"(d[20]), "+f"(d[21]), "+f"(d[22]), "+f"(d[23]), "+f"(d[24]), "+f"(d[25]), "+f"(d[26]), "+f"(d[27]), "+f"(d[28]), "+f"(d[29]), "+f"(d[30]), "+f"(d[31]), "+f"(d[32]), "+f"(d[33]), "+f"(d[34]), "+f"(d[35]), "+f"(d[36]), "+f"(d[37]), "+f"(d[38]), "+f"(d[39]), "+f"(d[40]), "+f"(d[41]), "+f"(d[42]), "+f"(d[43]), "+f"(d[44]), "+f"(d[45]), "+f"(d[46]), "+f"(d[47])
        : "r"(a[AOFF + 0][0]), "r"(a[AOFF + 0][1]), "r"(a[AOFF + 0][2]), "r"(a[AOFF + 0][3]), "r"(a[AOFF + 1][0]), "r"(a[AOFF + 1][1]), "r"(a[AOFF + 1][2]), "r"(a[AOFF + 1][3]), "r"(a[AOFF + 2][0]), "r"(a[AOFF + 2][1]), "r"(a[AOFF + 2][2]), "r"(a[AOFF + 2][3]), "r"(a[AOFF + 3][0]), "r"(a[AOFF + 3][1]), "r"(a[AOFF + 3][2]), "r"(a[AOFF + 3][3]), "l"(descB), "n"(BOFF >> 4));
}
};
template <> struct Rng<0, 6, 12> {
template <int BOFF, int AOFF, int NA>
static __device__ __forceinline__ void run(float (&d)[48], const uint32_t (&a)[NA][4], uint64_t descB) {
    asm volatile(
        "{\n"
        ".reg .pred p0, p1;\n"
        ".reg .b64 ta, ta0, tb, tb0;\n"
        "setp.ne.b32 p0, 0, 0;\n"
        "setp.eq.b32 p1, 0, 0;\n"
        "add.s64 tb0, %72, %73;\n"
        "add.s64 tb, tb0, 1600;\n"
        "wgmma.mma_async.sync.aligned.m64n96k16.f32.bf16.bf16 {%0, %1, %2, %3, %4, %5, %6, %7, %8, %9, %10, %11, %12, %13, %14, %15, %16, %17, %18, %19, %20, %21, %22, %23, %24, %25, %26, %27, %28, %29, %30, %31, %32, %33, %34, %35, %36, %37, %38, %39, %40, %41, %42, %43, %44, %45, %46, %47}, {%48, %49, %50, %51}, tb, p1, 1, 1, 1;\n"
        "add.s64 tb, tb0, 1632;\n"
        "wgmma.mma_async.sync.aligned.m64n96k16.f32.bf16.bf16 {%0, %1, %2, %3, %4, %5, %6, %7, %8, %9, %10, %11, %12, %13, %14, %15, %16, %17, %18, %19, %20, %21, %22, %23, %24, %25, %26, %27, %28, %29, %30, %31, %32, %33, %34, %35, %36, %37, %38, %39, %40, %41, %42, %43, %44, %45, %46, %47}, {%52, %53, %54, %55}, tb, p1, 1, 1, 1;\n"
        "add.s64 tb, tb0, 3072;\n"
        "wgmma.mma_async.sync.aligned.m64n96k16.f32.bf16.bf16 {%0, %1, %2, %3, %4, %5, %6, %7, %8, %9, %10, %11, %12, %13, %14, %15, %16, %17, %18, %19, %20, %21, %22, %23, %24, %25, %26, %27, %28, %29, %30, %31, %32, %33, %34, %35, %36, %37, %38, %39, %40, %41, %42, %43, %44, %45, %46, %47}, {%56, %57, %58, %59}, tb, p1, 1, 1, 1;\n"
        "add.s64 tb, tb0, 3104;\n"
        "wgmma.mma_async.sync.aligned.m64n96k16.f32.bf16.bf16 {%0, %1, %2, %3, %4, %5, %6, %7, %8, %9, %10, %11, %12, %13, %14, %15, %16, %17, %18, %19, %20, %21, %22, %23, %24, %25, %26, %27, %28, %29, %30, %31, %32, %33, %34, %35, %36, %37, %38, %39, %40, %41, %42, %43, %44, %45, %46, %47}, {%60, %61, %62, %63}, tb, p1, 1, 1, 1;\n"
        "add.s64 tb, tb0, 3136;\n"
        "wgmma.mma_async.sync.aligned.m64n96k16.f32.bf16.bf16 {%0, %1, %2, %3, %4, %5, %6, %7, %8, %9, %10, %11, %12, %13, %14, %15, %16, %17, %18, %19, %20, %21, %22, %23, %24, %25, %26, %27, %28, %29, %30, %31, %32, %33, %34, %35, %36, %37, %38, %39, %40, %41, %42, %43, %44, %45, %46, %47}, {%64, %65, %66, %67}, tb, p1, 1, 1, 1;\n"
        "add.s64 tb, tb0, 3168;\n"
        "wgmma.mma_async.sync.aligned.m64n96k16.f32.bf16.bf16 {%0, %1, %2, %3, %4, %5, %6, %7, %8, %9, %10, %11, %12, %13, %14, %15, %16, %17, %18, %19, %20, %21, %22, %23, %24, %25, %26, %27, %28, %29, %30, %31, %32, %33, %34, %35, %36, %37, %38, %39, %40, %41, %42, %43, %44, %45, %46, %47}, {%68, %69, %70, %71}, tb, p1, 1, 1, 1;\n"
        "}\n"
        : "+f"(d[0]), "+f"(d[1]), "+f"(d[2]), "+f"(d[3]), "+f"(d[4]), "+f"(d[5]), "+f"(d[6]), "+f"(d[7]), "+f"(d[8]), "+f"(d[9]), "+f"(d[10]), "+f"(d[11]), "+f"(d[12]), "+f"(d[13]), "+f"(d[14]), "+f"(d[15]), "+f"(d[16]), "+f"(d[17]), "+f"(d[18]), "+f"(d[19]), "+f"(d[20]), "+f"(d[21]), "+f"(d[22]), "+f"(d[23]), "+f"(d[24]), "+f"(d[25]), "+f"(d[26]), "+f"(d[27]), "+f"(d[28]), "+f"(d[29]), "+f"(d[30]), "+f"(d[31]), "+f"(d[32]), "+f"(d[33]), "+f"(d[34]), "+f"(d[35]), "+f"(d[36]), "+f"(d[37]), "+f"(d[38]), "+f"(d[39]), "+f"(d[40]), "+f"(d[41]), "+f"(d[42]), "+f"(d[43]), "+f"(d[44]), "+f"(d[45]), "+f"(d[46]), "+f"(d[47])
        : "r"(a[AOFF + 0][0]), "r"(a[AOFF + 0][1]), "r"(a[AOFF + 0][2]), "r"(a[AOFF + 0][3]), "r"(a[AOFF + 1][0]), "r"(a[AOFF + 1][1]), "r"(a[AOFF + 1][2]), "r"(a[AOFF + 1][3]), "r"(a[AOFF + 2][0]), "r"(a[AOFF + 2][1]), "r"(a[AOFF + 2][2]), "r"(a[AOFF + 2][3]), "r"(a[AOFF + 3][0]), "r"(a[AOFF + 3][1]), "r"(a[AOFF + 3][2]), "r"(a[AOFF + 3][3]), "r"(a[AOFF + 4][0]), "r"(a[AOFF + 4][1]), "r"(a[AOFF + 4][2]), "r"(a[AOFF + 4][3]), "r"(a[AOFF + 5][0]), "r"(a[AOFF + 5][1]), "r"(a[AOFF + 5][2]), "r"(a[AOFF + 5][3]), "l"(descB), "n"(BOFF >> 4));
}
};
template <> struct Rng<1, 6, 12> {
template <int BOFF, int AOFF, int NA>
static __device__ __forceinline__ void run(float (&d)[48], const uint32_t (&a)[NA][4], uint64_t descB) {
    asm volatile(
        "{\n"
        ".reg .pred p0, p1;\n"
        ".reg .b64 ta, ta0, tb, tb0;\n"
        "setp.ne.b32 p0, 0, 0;\n"
        "setp.eq.b32 p1, 0, 0;\n"
        "add.s64 tb0, %72, %73;\n"
        "add.s64 tb, tb0, 192;\n"
        "wgmma.mma_async.sync.aligned.m64n96k16.f32.bf16.bf16 {%0, %1, %2, %3, %4, %5, %6, %7, %8, %9, %10, %11, %12, %13, %14, %15, %16, %17, %18, %19, %20, %21, %22, %23, %24, %25, %26, %27, %28, %29, %30, %31, %32, %33, %34, %35, %36, %37, %38, %39, %40, %41, %42, %43, %44, %45, %46, %47}, {%48, %49, %50, %51}, tb, p1, 1, 1, 1;\n"
        "add.s64 tb, tb0, 224;\n"
        "wgmma.mma_async.sync.aligned.m64n96k16.f32.bf16.bf16 {%0, %1, %2, %3, %4, %5, %6, %7, %8, %9, %10, %11, %12, %13, %14, %15, %16, %17, %18, %19, %20, %21, %22, %23, %24, %25, %26, %27, %28, %29, %30, %31, %32, %33, %34, %35, %36, %37, %38, %39, %40, %41, %42, %43, %44, %45, %46, %47}, {%52, %53, %54, %55}, tb, p1, 1, 1, 1;\n"
        "add.s64 tb, tb0, 256;\n"
        "wgmma.mma_async.sync.aligned.m64n96k16.f32.bf16.bf16 {%0, %1, %2, %3, %4, %5, %6, %7, %8, %9, %10, %11, %12, %13, %14, %15, %16, %17, %18, %19, %20, %21, %22, %23, %24, %25, %26, %27, %28, %29, %30, %31, %32, %33, %34, %35, %36, %37, %38, %39, %40, %41, %42, %43, %44, %45, %46, %47}, {%56, %57, %58, %59}, tb, p1, 1, 1, 1;\n"
        "add.s64 tb, tb0, 288;\n"
        "wgmma.mma_async.sync.aligned.m64n96k16.f32.bf16.bf16 {%0, %1, %2, %3, %4, %5, %6, %7, %8, %9, %10, %11, %12, %13, %14, %15, %16, %17, %18, %19, %20, %21, %22, %23, %24, %25, %26, %27, %28, %29, %30, %31, %32, %33, %34, %35, %36, %37, %38, %39, %40, %41, %42, %43, %44, %45, %46, %47}, {%60, %61, %62, %63}, tb, p1, 1, 1, 1;\n"
        "add.s64 tb, tb0, 320;\n"
        "wgmma.mma_async.sync.aligned.m64n96k16.f32.bf16.bf16 {%0, %1, %2, %3, %4, %5, %6, %7, %8, %9, %10, %11, %12, %13, %14, %15, %16, %17, %18, %19, %20, %21, %22, %23, %24, %25, %26, %27, %28, %29, %30, %31, %32, %33, %34, %35, %36, %37, %38, %39, %40, %41, %42, %43, %44, %45, %46, %47}, {%64, %65, %66, %67}, tb, p1, 1, 1, 1;\n"
        "add.s64 tb, tb0, 352;\n"
        "wgmma.mma_async.sync.aligned.m64n96k16.f32.bf16.bf16 {%0, %1, %2, %3, %4, %5, %6, %7, %8, %9, %10, %11, %12, %13, %14, %15, %16, %17, %18, %19, %20, %21, %22, %23, %24, %25, %26, %27, %28, %29, %30, %31, %32, %33, %34, %35, %36, %37, %38, %39, %40, %41, %42, %43, %44, %45, %46, %47}, {%68, %69, %70, %71}, tb, p1, 1, 1, 1;\n"
        "}\n"
        : "+f"(d[0]), "+f"(d[1]), "+f"(d[2]), "+f"(d[3]), "+f"(d[4]), "+f"(d[5]), "+f"(d[6]), "+f"(d[7]), "+f"(d[8]), "+f"(d[9]), "+f"(d[10]), "+f"(d[11]), "+f"(d[12]), "+f"(d[13]), "+f"(d[14]), "+f"(d[15]), "+f"(d[16]), "+f"(d[17]), "+f"(d[18]), "+f"(d[19]), "+f"(d[20]), "+f"(d[21]), "+f"(d[22]), "+f"(d[23]), "+f"(d[24]), "+f"(d[25]), "+f"(d[26]), "+f"(d[27]), "+f"(d[28]), "+f"(d[29]), "+f"(d[30]), "+f"(d[31]), "+f"(d[32]), "+f"(d[33]), "+f"(d[34]), "+f"(d[35]), "+f"(d[36]), "+f"(d[37]), "+f"(d[38]), "+f"(d[39]), "+f"(d[40]), "+f"(d[41]), "+f"(d[42]), "+f"(d[43]), "+f"(d[44]), "+f"(d[45]), "+f"(d[46]), "+f"(d[47])
        : "r"(a[AOFF + 0][0]), "r"(a[AOFF + 0][1]), "r"(a[AOFF + 0][2]), "r"(a[AOFF + 0][3]), "r"(a[AOFF + 1][0]), "r"(a[AOFF + 1][1]), "r"(a[AOFF + 1][2]), "r"(a[AOFF + 1][3]), "r"(a[AOFF + 2][0]), "r"(a[AOFF + 2][1]), "r"(a[AOFF + 2][2]), "r"(a[AOFF + 2][3]), "r"(a[AOFF + 3][0]), "r"(a[AOFF + 3][1]), "r"(a[AOFF + 3][2]), "r"(a[AOFF + 3][3]), "r"(a[AOFF + 4][0]), "r"(a[AOFF + 4][1]), "r"(a[AOFF + 4][2]), "r"(a[AOFF + 4][3]), "r"(a[AOFF + 5][0]), "r"(a[AOFF + 5][1]), "r"(a[AOFF + 5][2]), "r"(a[AOFF + 5][3]), "l"(descB), "n"(BOFF >> 4));
}
};
template <> struct Rng<0, 7, 12> {
template <int BOFF, int AOFF, int NA>
static __device__ __forceinline__ void run(float (&d)[48], const uint32_t (&a)[NA][4], uint64_t descB) {
    asm volatile(
        "{\n"
        ".reg .pred p0, p1;\n"
        ".reg .b64 ta, ta0, tb, tb0;\n"
        "setp.ne.b32 p0, 0, 0;\n"
        "setp.eq.b32 p1, 0, 0;\n"
        "add.s64 tb0, %68, %69;\n"
        "add.s64 tb, tb0, 1632;\n"
        "wgmma.mma_async.sync.aligned.m64n96k16.f32.bf16.bf16 {%0, %1, %2, %3, %4, %5, %6, %7, %8, %9, %10, %11, %12, %13, %14, %15, %16, %17, %18, %19, %20, %21, %22, %23, %24, %25, %26, %27, %28, %29, %30, %31, %32, %33, %34, %35, %36, %37, %38, %39, %40, %41, %42, %43, %44, %45, %46, %47}, {%48, %49, %50, %51}, tb, p1, 1, 1, 1;\n"
        "add.s64 tb, tb0, 3072;\n"
        "wgmma.mma_async.sync.aligned.m64n96k16.f32.bf16.bf16 {%0, %1, %2, %3, %4, %5, %6, %7, %8, %9, %10, %11, %12, %13, %14, %15, %16, %17, %18, %19, %20, %21, %22, %23, %24, %25, %26, %27, %28, %29, %30, %31, %32, %33, %34, %35, %36, %37, %38, %39, %40, %41, %42, %43, %44, %45, %46, %47}, {%52, %53, %54, %55}, tb, p1, 1, 1, 1;\n"
        "add.s64 tb, tb0, 3104;\n"
        "wgmma.mma_async.sync.aligned.m64n96k16.f32.bf16.bf16 {%0, %1, %2, %3, %4, %5, %6, %7, %8, %9, %10, %11, %12, %13, %14, %15, %16, %17, %18, %19, %20, %21, %22, %23, %24, %25, %26, %27, %28, %29, %30, %31, %32, %33, %34, %35, %36, %37, %38, %39, %40, %41, %42, %43, %44, %45, %46, %47}, {%56, %57, %58, %59}, tb, p1, 1, 1, 1;\n"
        "add.s64 tb, tb0, 3136;\n"
        "wgmma.mma_async.sync.aligned.m64n96k16.f32.bf16.bf16 {%0, %1, %2, %3, %4, %5, %6, %7, %8, %9, %10, %11, %12, %13, %14, %15, %16, %17, %18, %19, %20, %21, %22, %23, %24, %25, %26, %27, %28, %29, %30, %31, %32, %33, %34, %35, %36, %37, %38, %39, %40, %41, %42, %43, %44, %45, %46, %47}, {%60, %61, %62, %63}, tb, p1, 1, 1, 1;\n"
        "add.s64 tb, tb0, 3168;\n"
        "wgmma.mma_async.sync.aligned.m64n96k16.f32.bf16.bf16 {%0, %1, %2, %3, %4, %5, %6, %7, %8, %9, %10, %11, %12, %13, %14, %15, %16, %17, %18, %19, %20, %21, %22, %23, %24, %25, %26, %27, %28, %29, %30, %31, %32, %33, %34, %35, %36, %37, %38, %39, %40, %41, %42, %43, %44, %45, %46, %47}, {%64, %65, %66, %67}, tb, p1, 1, 1, 1;\n"
        "}\n"
        : "+f"(d[0]), "+f"(d[1]), "+f"(d[2]), "+f"(d[3]), "+f"(d[4]), "+f"(d[5]), "+f"(d[6]), "+f"(d[7]), "+f"(d[8]), "+f"(d[9]), "+f"(d[10]), "+f"(d[11]), "+f"(d[12]), "+f"(d[13]), "+f"(d[14]), "+f"(d[15]), "+f"(d[16]), "+f"(d[17]), "+f"(d[18]), "+f"(d[19]), "+f"(d[20]), "+f"(d[21]), "+f"(d[22]), "+f"(d[23]), "+f"(d[24]), "+f"(d[25]), "+f"(d[26]), "+f"(d[27]), "+f"(d[28]), "+f"(d[29]), "+f"(d[30]), "+f"(d[31]), "+f"(d[32]), "+f"(d[33]), "+f"(d[34]), "+f"(d[35]), "+f"(d[36]), "+f"(d[37]), "+f"(d[38]), "+f"(d[39]), "+f"(d[40]), "+f"(d[41]), "+f"(d[42]), "+f"(d[43]), "+f"(d[44]), "+f"(d[45]), "+f"(d[46]), "+f"(d[47])
        : "r"(a[AOFF + 0][0]), "r"(a[AOFF + 0][1]), "r"(a[AOFF + 0][2]), "r"(a[AOFF + 0][3]), "r"(a[AOFF + 1][0]), "r"(a[AOFF + 1][1]), "r"(a[AOFF + 1][2]), "r"(a[AOFF + 1][3]), "r"(a[AOFF + 2][0]), "r"(a[AOFF + 2][1]), "r"(a[AOFF + 2][2]), "r"(a[AOFF + 2][3]), "r"(a[AOFF + 3][0]), "r"(a[AOFF + 3][1]), "r"(a[AOFF + 3][2]), "r"(a[AOFF + 3][3]), "r"(a[AOFF + 4][0]), "r"(a[AOFF + 4][1]), "r"(a[AOFF + 4][2]), "r"(a[AOFF + 4][3]), "l"(descB), "n"(BOFF >> 4));
}
};
template <> struct Rng<1, 7, 12> {
template <int BOFF, int AOFF, int NA>
static __device__ __forceinline__ void run(float (&d)[48], const uint32_t (&a)[NA][4], uint64_t descB) {
    asm volatile(
        "{\n"
        ".reg .pred p0, p1;\n"
        ".reg .b64 ta, ta0, tb, tb0;\n"
        "setp.ne.b32 p0, 0, 0;\n"
        "setp.eq.b32 p1, 0, 0;\n"
        "add.s64 tb0, %68, %69;\n"
        "add.s64 tb, tb0, 224;\n"
        "wgmma.mma_async.sync.aligned.m64n96k16.f32.bf16.bf16 {%0, %1, %2, %3, %4, %5, %6, %7, %8, %9, %10, %11, %12, %13, %14, %15, %16, %17, %18, %19, %20, %21, %22, %23, %24, %25, %26, %27, %28, %29, %30, %31, %32, %33, %34, %35, %36, %37, %38, %39, %40, %41, %42, %43, %44, %45, %46, %47}, {%48, %49, %50, %51}, tb, p1, 1, 1, 1;\n"
        "add.s64 tb, tb0, 256;\n"
        "wgmma.mma_async.sync.aligned.m64n96k16.f32.bf16.bf16 {%0, %1, %2, %3, %4, %5, %6, %7, %8, %9, %10, %11, %12, %13, %14, %15, %16, %17, %18, %19, %20, %21, %22, %23, %24, %25, %26, %27, %28, %29, %30, %31, %32, %33, %34, %35, %36, %37, %38, %39, %40, %41, %42, %43, %44, %45, %46, %47}, {%52, %53, %54, %55}, tb, p1, 1, 1, 1;\n"
        "add.s64 tb, tb0, 288;\n"
        "wgmma.mma_async.sync.aligned.m64n96k16.f32.bf16.bf16 {%0, %1, %2, %3, %4, %5, %6, %7, %8, %9, %10, %11, %12, %13, %14, %15, %16, %17, %18, %19, %20, %21, %22, %23, %24, %25, %26, %27, %28, %29, %30, %31, %32, %33, %34, %35, %36, %37, %38, %39, %40, %41, %42, %43, %44, %45, %46, %47}, {%56, %57, %58, %59}, tb, p1, 1, 1, 1;\n"
        "add.s64 tb, tb0, 320;\n"
        "wgmma.mma_async.sync.aligned.m64n96k16.f32.bf16.bf16 {%0, %1, %2, %3, %4, %5, %6, %7, %8, %9, %10, %11, %12, %13, %14, %15, %16, %17, %18, %19, %20, %21, %22, %23, %24, %25, %26, %27, %28, %29, %30, %31, %32, %33, %34, %35, %36, %37, %38, %39, %40, %41, %42, %43, %44, %45, %46, %47}, {%60, %61, %62, %63}, tb, p1, 1, 1, 1;\n"
        "add.s64 tb, tb0, 352;\n"
        "wgmma.mma_async.sync.aligned.m64n96k16.f32.bf16.bf16 {%0, %1, %2, %3, %4, %5, %6, %7, %8, %9, %10, %11, %12, %13, %14, %15, %16, %17, %18, %19, %20, %21, %22, %23, %24, %25, %26, %27, %28, %29, %30, %31, %32, %33, %34, %35, %36, %37, %38, %39, %40, %41, %42, %43, %44, %45, %46, %47}, {%64, %65, %66, %67}, tb, p1, 1, 1, 1;\n"
        "}\n"
        : "+f"(d[0]), "+f"(d[1]), "+f"(d[2]), "+f"(d[3]), "+f"(d[4]), "+f"(d[5]), "+f"(d[6]), "+f"(d[7]), "+f"(d[8]), "+f"(d[9]), "+f"(d[10]), "+f"(d[11]), "+f"(d[12]), "+f"(d[13]), "+f"(d[14]), "+f"(d[15]), "+f"(d[16]), "+f"(d[17]), "+f"(d[18]), "+f"(d[19]), "+f"(d[20]), "+f"(d[21]), "+f"(d[22]), "+f"(d[23]), "+f"(d[24]), "+f"(d[25]), "+f"(d[26]), "+f"(d[27]), "+f"(d[28]), "+f"(d[29]), "+f"(d[30]), "+f"(d[31]), "+f"(d[32]), "+f"(d[33]), "+f"(d[34]), "+f"(d[35]), "+f"(d[36]), "+f"(d[37]), "+f"(d[38]), "+f"(d[39]), "+f"(d[40]), "+f"(d[41]), "+f"(d[42]), "+f"(d[43]), "+f"(d[44]), "+f"(d[45]), "+f"(d[46]), "+f"(d[47])
        : "r"(a[AOFF + 0][0]), "r"(a[AOFF + 0][1]), "r"(a[AOFF + 0][2]), "r"(a[AOFF + 0][3]), "r"(a[AOFF + 1][0]), "r"(a[AOFF + 1][1]), "r"(a[AOFF + 1][2]), "r"(a[AOFF + 1][3]), "r"(a[AOFF + 2][0]), "r"(a[AOFF + 2][1]), "r"(a[AOFF + 2][2]), "r"(a[AOFF + 2][3]), "r"(a[AOFF + 3][0]), "r"(a[AOFF + 3][1]), "r"(a[AOFF + 3][2]), "r"(a[AOFF + 3][3]), "r"(a[AOFF + 4][0]), "r"(a[AOFF + 4][1]), "r"(a[AOFF + 4][2]), "r"(a[AOFF + 4][3]), "l"(descB), "n"(BOFF >> 4));
}
};
template <> struct Rng<0, 8, 12> {
template <int BOFF, int AOFF, int NA>
static __device__ __forceinline__ void run(float (&d)[48], const uint32_t (&a)[NA][4], uint64_t descB) {
    asm volatile(
        "{\n"
        ".reg .pred p0, p1;\n"
        ".reg .b64 ta, ta0, tb, tb0;\n"
        "setp.ne.b32 p0, 0, 0;\n"
        "setp.eq.b32 p1, 0, 0;\n"
        "add.s64 tb0, %64, %65;\n"
        "add.s64 tb, tb0, 3072;\n"
        "wgmma.mma_async.sync.aligned.m64n96k16.f32.bf16.bf16 {%0, %1, %2, %3, %4, %5, %6, %7, %8, %9, %10, %11, %12, %13, %14, %15, %16, %17, %18, %19, %20, %21, %22, %23, %24, %25, %26, %27, %28, %29, %30, %31, %32, %33, %34, %35, %36, %37, %38, %39, %40, %41, %42, %43, %44, %45, %46, %47}, {%48, %49, %50, %51}, tb, p1, 1, 1, 1;\n"
        "add.s64 tb, tb0, 3104;\n"
        "wgmma.mma_async.sync.aligned.m64n96k16.f32.bf16.bf16 {%0, %1, %2, %3, %4, %5, %6, %7, %8, %9, %10, %11, %12, %13, %14, %15, %16, %17, %18, %19, %20, %21, %22, %23, %24, %25, %26, %27, %28, %29, %30, %31, %32, %33, %34, %35, %36, %37, %38, %39, %40, %41, %42, %43, %44, %45, %46, %47}, {%52, %53, %54, %55}, tb, p1, 1, 1, 1;\n"
        "add.s64 tb, tb0, 3136;\n"
        "wgmma.mma_async.sync.aligned.m64n96k16.f32.bf16.bf16 {%0, %1, %2, %3, %4, %5, %6, %7, %8, %9, %10, %11, %12, %13, %14, %15, %16, %17, %18, %19, %20, %21, %22, %23, %24, %25, %26, %27, %28, %29, %30, %31, %32, %33, %34, %35, %36, %37, %38, %39, %40, %41, %42, %43, %44, %45, %46, %47}, {%56, %57, %58, %59}, tb, p1, 1, 1, 1;\n"
        "add.s64 tb, tb0, 3168;\n"
        "wgmma.mma_async.sync.aligned.m64n96k16.f32.bf16.bf16 {%0, %1, %2, %3, %4, %5, %6, %7, %8, %9, %10, %11, %12, %13, %14, %15, %16, %17, %18, %19, %20, %21, %22, %23, %24, %25, %26, %27, %28, %29, %30, %31, %32, %33, %34, %35, %36, %37, %38, %39, %40, %41, %42, %43, %44, %45, %46, %47}, {%60, %61, %62, %63}, tb, p1, 1, 1, 1;\n"
        "}\n"
        : "+f"(d[0]), "+f"(d[1]), "+f"(d[2]), "+f"(d[3]), "+f"(d[4]), "+f"(d[5]), "+f"(d[6]), "+f"(d[7]), "+f"(d[8]), "+f"(d[9]), "+f"(d[10]), "+f"(d[11]), "+f"(d[12]), "+f"(d[13]), "+f"(d[14]), "+f"(d[15]), "+f"(d[16]), "+f"(d[17]), "+f"(d[18]), "+f"(d[19]), "+f"(d[20]), "+f"(d[21]), "+f"(d[22]), "+f"(d[23]), "+f"(d[24]), "+f"(d[25]), "+f"(d[26]), "+f"(d[27]), "+f"(d[28]), "+f"(d[29]), "+f"(d[30]), "+f"(d[31]), "+f"(d[32]), "+f"(d[33]), "+f"(d[34]), "+f"(d[35]), "+f"(d[36]), "+f"(d[37]), "+f"(d[38]), "+f"(d[39]), "+f"(d[40]), "+f"(d[41]), "+f"(d[42]), "+f"(d[43]), "+f"(d[44]), "+f"(d[45]), "+f"(d[46]), "+f"(d[47])
        : "r"(a[AOFF + 0][0]), "r"(a[AOFF + 0][1]), "r"(a[AOFF + 0][2]), "r"(a[AOFF + 0][3]), "r"(a[AOFF + 1][0]), "r"(a[AOFF + 1][1]), "r"(a[AOFF + 1][2]), "r"(a[AOFF + 1][3]), "r"(a[AOFF + 2][0]), "r"(a[AOFF + 2][1]), "r"(a[AOFF + 2][2]), "r"(a[AOFF + 2][3]), "r"(a[AOFF + 3][0]), "r"(a[AOFF + 3][1]), "r"(a[AOFF + 3][2]), "r"(a[AOFF + 3][3]), "l"(descB), "n"(BOFF >> 4));
}
};
template <> struct Rng<1, 8, 12> {
template <int BOFF, int AOFF, int NA>
static __device__ __forceinline__ void run(float (&d)[48], const uint32_t (&a)[NA][4], uint64_t descB) {
    asm volatile(
        "{\n"
        ".reg .pred p0, p1;\n"
        ".reg .b64 ta, ta0, tb, tb0;\n"
        "setp.ne.b32 p0, 0, 0;\n"
        "setp.eq.b32 p1, 0, 0;\n"
        "add.s64 tb0, %64, %65;\n"
        "add.s64 tb, tb0, 256;\n"
        "wgmma.mma_async.sync.aligned.m64n96k16.f32.bf16.bf16 {%0, %1, %2, %3, %4, %5, %6, %7, %8, %9, %10, %11, %12, %13, %14, %15, %16, %17, %18, %19, %20, %21, %22, %23, %24, %25, %26, %27, %28, %29, %30, %31, %32, %33, %34, %35, %36, %37, %38, %39, %40, %41, %42, %43, %44, %45, %46, %47}, {%48, %49, %50, %51}, tb, p1, 1, 1, 1;\n"
        "add.s64 tb, tb0, 288;\n"
        "wgmma.mma_async.sync.aligned.m64n96k16.f32.bf16.bf16 {%0, %1, %2, %3, %4, %5, %6, %7, %8, %9, %10, %11, %12, %13, %14, %15, %16, %17, %18, %19, %20, %21, %22, %23, %24, %25, %26, %27, %28, %29, %30, %31, %32, %33, %34, %35, %36, %37, %38, %39, %40, %41, %42, %43, %44, %45, %46, %47}, {%52, %53, %54, %55}, tb, p1, 1, 1, 1;\n"
        "add.s64 tb, tb0, 320;\n"
        "wgmma.mma_async.sync.aligned.m64n96k16.f32.bf16.bf16 {%0, %1, %2, %3, %4, %5, %6, %7, %8, %9, %10, %11, %12, %13, %14, %15, %16, %17, %18, %19, %20, %21, %22, %23, %24, %25, %26, %27, %28, %29, %30, %31, %32, %33, %34, %35, %36, %37, %38, %39, %40, %41, %42, %43, %44, %45, %46, %47}, {%56, %57, %58, %59}, tb, p1, 1, 1, 1;\n"
        "add.s64 tb, tb0, 352;\n"
        "wgmma.mma_async.sync.aligned.m64n96k16.f32.bf16.bf16 {%0, %1, %2, %3, %4, %5, %6, %7, %8, %9, %10, %11, %12, %13, %14, %15, %16, %17, %18, %19, %20, %21, %22, %23, %24, %25, %26, %27, %28, %29, %30, %31, %32, %33, %34, %35, %36, %37, %38, %39, %40, %41, %42, %43, %44, %45, %46, %47}, {%60, %61, %62, %63}, tb, p1, 1, 1, 1;\n"
        "}\n"
        : "+f"(d[0]), "+f"(d[1]), "+f"(d[2]), "+f"(d[3]), "+f"(d[4]), "+f"(d[5]), "+f"(d[6]), "+f"(d[7]), "+f"(d[8]), "+f"(d[9]), "+f"(d[10]), "+f"(d[11]), "+f"(d[12]), "+f"(d[13]), "+f"(d[14]), "+f"(d[15]), "+f"(d[16]), "+f"(d[17]), "+f"(d[18]), "+f"(d[19]), "+f"(d[20]), "+f"(d[21]), "+f"(d[22]), "+f"(d[23]), "+f"(d[24]), "+f"(d[25]), "+f"(d[26]), "+f"(d[27]), "+f"(d[28]), "+f"(d[29]), "+f"(d[30]), "+f"(d[31]), "+f"(d[32]), "+f"(d[33]), "+f"(d[34]), "+f"(d[35]), "+f"(d[36]), "+f"(d[37]), "+f"(d[38]), "+f"(d[39]), "+f"(d[40]), "+f"(d[41]), "+f"(d[42]), "+f"(d[43]), "+f"(d[44]), "+f"(d[45]), "+f"(d[46]), "+f"(d[47])
        : "r"(a[AOFF + 0][0]), "r"(a[AOFF + 0][1]), "r"(a[AOFF + 0][2]), "r"(a[AOFF + 0][3]), "r"(a[AOFF + 1][0]), "r"(a[AOFF + 1][1]), "r"(a[AOFF + 1][2]), "r"(a[AOFF + 1][3]), "r"(a[AOFF + 2][0]), "r"(a[AOFF + 2][1]), "r"(a[AOFF + 2][2]), "r"(a[AOFF + 2][3]), "r"(a[AOFF + 3][0]), "r"(a[AOFF + 3][1]), "r"(a[AOFF + 3][2]), "r"(a[AOFF + 3][3]), "l"(descB), "n"(BOFF >> 4));
}
};
template <> struct Rng<0, 9, 12> {
template <int BOFF, int AOFF, int NA>
static __device__ __forceinline__ void run(float (&d)[48], const uint32_t (&a)[NA][4], uint64_t descB) {
    asm volatile(
        "{\n"
        ".reg .pred p0, p1;\n"
        ".reg .b64 ta, ta0, tb, tb0;\n"
        "setp.ne.b32 p0, 0, 0;\n"
        "setp.eq.b32 p1, 0, 0;\n"
        "add.s64 tb0, %60, %61;\n"
        "add.s64 tb, tb0, 3104;\n"
        "wgmma.mma_async.sync.aligned.m64n96k16.f32.bf16.bf16 {%0, %1, %2, %3, %4, %5, %6, %7, %8, %9, %10, %11, %12, %13, %14, %15, %16, %17, %18, %19, %20, %21, %22, %23, %24, %25, %26, %27, %28, %29, %30, %31, %32, %33, %34, %35, %36, %37, %38, %39, %40, %41, %42, %43, %44, %45, %46, %47}, {%48, %49, %50, %51}, tb, p1, 1, 1, 1;\n"
        "add.s64 tb, tb0, 3136;\n"
        "wgmma.mma_async.sync.aligned.m64n96k16.f32.bf16.bf16 {%0, %1, %2, %3, %4, %5, %6, %7, %8, %9, %10, %11, %12, %13, %14, %15, %16, %17, %18, %19, %20, %21, %22, %23, %24, %25, %26, %27, %28, %29, %30, %31, %32, %33, %34, %35, %36, %37, %38, %39, %40, %41, %42, %43, %44, %45, %46, %47}, {%52, %53, %54, %55}, tb, p1, 1, 1, 1;\n"
        "add.s64 tb, tb0, 3168;\n"
        "wgmma.mma_async.sync.aligned.m64n96k16.f32.bf16.bf16 {%0, %1, %2, %3, %4, %5, %6, %7, %8, %9, %10, %11, %12, %13, %14, %15, %16, %17, %18, %19, %20, %21, %22, %23, %24, %25, %26, %27, %28, %29, %30, %31, %32, %33, %34, %35, %36, %37, %38, %39, %40, %41, %42, %43, %44, %45, %46, %47}, {%56, %57, %58, %59}, tb, p1, 1, 1, 1;\n"
        "}\n"
        : "+f"(d[0]), "+f"(d[1]), "+f"(d[2]), "+f"(d[3]), "+f"(d[4]), "+f"(d[5]), "+f"(d[6]), "+f"(d[7]), "+f"(d[8]), "+f"(d[9]), "+f"(d[10]), "+f"(d[11]), "+f"(d[12]), "+f"(d[13]), "+f"(d[14]), "+f"(d[15]), "+f"(d[16]), "+f"(d[17]), "+f"(d[18]), "+f"(d[19]), "+f"(d[20]), "+f"(d[21]), "+f"(d[22]), "+f"(d[23]), "+f"(d[24]), "+f"(d[25]), "+f"(d[26]), "+f"(d[27]), "+f"(d[28]), "+f"(d[29]), "+f"(d[30]), "+f"(d[31]), "+f"(d[32]), "+f"(d[33]), "+f"(d[34]), "+f"(d[35]), "+f"(d[36]), "+f"(d[37]), "+f"(d[38]), "+f"(d[39]), "+f"(d[40]), "+f"(d[41]), "+f"(d[42]), "+f"(d[43]), "+f"(d[44]), "+f"(d[45]), "+f"(d[46]), "+f"(d[47])
        : "r"(a[AOFF + 0][0]), "r"(a[AOFF + 0][1]), "r"(a[AOFF + 0][2]), "r"(a[AOFF + 0][3]), "r"(a[AOFF + 1][0]), "r"(a[AOFF + 1][1]), "r"(a[AOFF + 1][2]), "r"(a[AOFF + 1][3]), "r"(a[AOFF + 2][0]), "r"(a[AOFF + 2][1]), "r"(a[AOFF + 2][2]), "r"(a[AOFF + 2][3]), "l"(descB), "n"(BOFF >> 4));
}
};
template <> struct Rng<1, 9, 12> {
template <int BOFF, int AOFF, int NA>
static __device__ __forceinline__ void run(float (&d)[48], const uint32_t (&a)[NA][4], uint64_t descB) {
    asm volatile(
        "{\n"
        ".reg .pred p0, p1;\n"
        ".reg .b64 ta, ta0, tb, tb0;\n"
        "setp.ne.b32 p0, 0, 0;\n"
        "setp.eq.b32 p1, 0, 0;\n"
        "add.s64 tb0, %60, %61;\n"
        "add.s64 tb, tb0, 288;\n"
        "wgmma.mma_async.sync.aligned.m64n96k16.f32.bf16.bf16 {%0, %1, %2, %3, %4, %5, %6, %7, %8, %9, %10, %11, %12, %13, %14, %15, %16, %17, %18, %19, %20, %21, %22, %23, %24, %25, %26, %27, %28, %29, %30, %31, %32, %33, %34, %35, %36, %37, %38, %39, %40, %41, %42, %43, %44, %45, %46, %47}, {%48, %49, %50, %51}, tb, p1, 1, 1, 1;\n"
        "add.s64 tb, tb0, 320;\n"
        "wgmma.mma_async.sync.aligned.m64n96k16.f32.bf16.bf16 {%0, %1, %2, %3, %4, %5, %6, %7, %8, %9, %10, %11, %12, %13, %14, %15, %16, %17, %18, %19, %20, %21, %22, %23, %24, %25, %26, %27, %28, %29, %30, %31, %32, %33, %34, %35, %36, %37, %38, %39, %40, %41, %42, %43, %44, %45, %46, %47}, {%52, %53, %54, %55}, tb, p1, 1, 1, 1;\n"
        "add.s64 tb, tb0, 352;\n"
        "wgmma.mma_async.sync.aligned.m64n96k16.f32.bf16.bf16 {%0, %1, %2, %3, %4, %5, %6, %7, %8, %9, %10, %11, %12, %13, %14, %15, %16, %17, %18, %19, %20, %21, %22, %23, %24, %25, %26, %27, %28, %29, %30, %31, %32, %33, %34, %35, %36, %37, %38, %39, %40, %41, %42, %43, %44, %45, %46, %47}, {%56, %57, %58, %59}, tb, p1, 1, 1, 1;\n"
        "}\n"
        : "+f"(d[0]), "+f"(d[1]), "+f"(d[2]), "+f"(d[3]), "+f"(d[4]), "+f"(d[5]), "+f"(d[6]), "+f"(d[7]), "+f"(d[8]), "+f"(d[9]), "+f"(d[10]), "+f"(d[11]), "+f"(d[12]), "+f"(d[13]), "+f"(d[14]), "+f"(d[15]), "+f"(d[16]), "+f"(d[17]), "+f"(d[18]), "+f"(d[19]), "+f"(d[20]), "+f"(d[21]), "+f"(d[22]), "+f"(d[23]), "+f"(d[24]), "+f"(d[25]), "+f"(d[26]), "+f"(d[27]), "+f"(d[28]), "+f"(d[29]), "+f"(d[30]), "+f"(d[31]), "+f"(d[32]), "+f"(d[33]), "+f"(d[34]), "+f"(d[35]), "+f"(d[36]), "+f"(d[37]), "+f"(d[38]), "+f"(d[39]), "+f"(d[40]), "+f"(d[41]), "+f"(d[42]), "+f"(d[43]), "+f"(d[44]), "+f"(d[45]), "+f"(d[46]), "+f"(d[47])
        : "r"(a[AOFF + 0][0]), "r"(a[AOFF + 0][1]), "r"(a[AOFF + 0][2]), "r"(a[AOFF + 0][3]), "r"(a[AOFF + 1][0]), "r"(a[AOFF + 1][1]), "r"(a[AOFF + 1][2]), "r"(a[AOFF + 1][3]), "r"(a[AOFF + 2][0]), "r"(a[AOFF + 2][1]), "r"(a[AOFF + 2][2]), "r"(a[AOFF + 2][3]), "l"(descB), "n"(BOFF >> 4));
}
};
template <> struct Rng<0, 10, 12> {
template <int BOFF, int AOFF, int NA>
static __device__ __forceinline__ void run(float (&d)[48], const uint32_t (&a)[NA][4], uint64_t descB) {
    asm volatile(
        "{\n"
        ".reg .pred p0, p1;\n"
        ".reg .b64 ta, ta0, tb, tb0;\n"
        "setp.ne.b32 p0, 0, 0;\n"
        "setp.eq.b32 p1, 0, 0;\n"
        "add.s64 tb0, %56, %57;\n"
        "add.s64 tb, tb0, 3136;\n"
        "wgmma.mma_async.sync.aligned.m64n96k16.f32.bf16.bf16 {%0, %1, %2, %3, %4, %5, %6, %7, %8, %9, %10, %11, %12, %13, %14, %15, %16, %17, %18, %19, %20, %21, %22, %23, %24, %25, %26, %27, %28, %29, %30, %31, %32, %33, %34, %35, %36, %37, %38, %39, %40, %41, %42, %43, %44, %45, %46, %47}, {%48, %49, %50, %51}, tb, p1, 1, 1, 1;\n"
        "add.s64 tb, tb0, 3168;\n"
        "wgmma.mma_async.sync.aligned.m64n96k16.f32.bf16.bf16 {%0, %1, %2, %3, %4, %5, %6, %7, %8, %9, %10, %11, %12, %13, %14, %15, %16, %17, %18, %19, %20, %21, %22, %23, %24, %25, %26, %27, %28, %29, %30, %31, %32, %33, %34, %35, %36, %37, %38, %39, %40, %41, %42, %43, %44, %45, %46, %47}, {%52, %53, %54, %55}, tb, p1, 1, 1, 1;\n"
        "}\n"
        : "+f"(d[0]), "+f"(d[1]), "+f"(d[2]), "+f"(d[3]), "+f"(d[4]), "+f"(d[5]), "+f"(d[6]), "+f"(d[7]), "+f"(d[8]), "+f"(d[9]), "+f"(d[10]), "+f"(d[11]), "+f"(d[12]), "+f"(d[13]), "+f"(d[14]), "+f"(d[15]), "+f"(d[16]), "+f"(d[17]), "+f"(d[18]), "+f"(d[19]), "+f"(d[20]), "+f"(d[21]), "+f"(d[22]), "+f"(d[23]), "+f"(d[24]), "+f"(d[25]), "+f"(d[26]), "+f"(d[27]), "+f"(d[28]), "+f"(d[29]), "+f"(d[30]), "+f"(d[31]), "+f"(d[32]), "+f"(d[33]), "+f"(d[34]), "+f"(d[35]), "+f"(d[36]), "+f"(d[37]), "+f"(d[38]), "+f"(d[39]), "+f"(d[40]), "+f"(d[41]), "+f"(d[42]), "+f"(d[43]), "+f"(d[44]), "+f"(d[45]), "+f"(d[46]), "+f"(d[47])
        : "r"(a[AOFF + 0][0]), "r"(a[AOFF + 0][1]), "r"(a[AOFF + 0][2]), "r"(a[AOFF + 0][3]), "r"(a[AOFF + 1][0]), "r"(a[AOFF + 1][1]), "r"(a[AOFF + 1][2]), "r"(a[AOFF + 1][3]), "l"(descB), "n"(BOFF >> 4));
}
};
template <> struct Rng<1, 10, 12> {
template <int BOFF, int AOFF, int NA>
static __device__ __forceinline__ void run(float (&d)[48], const uint32_t (&a)[NA][4], uint64_t descB) {
    asm volatile(
        "{\n"
        ".reg .pred p0, p1;\n"
        ".reg .b64 ta, ta0, tb, tb0;\n"
        "setp.ne.b32 p0, 0, 0;\n"
        "setp.eq.b32 p1, 0, 0;\n"
        "add.s64 tb0, %56, %57;\n"
        "add.s64 tb, tb0, 320;\n"
        "wgmma.mma_async.sync.aligned.m64n96k16.f32.bf16.bf16 {%0, %1, %2, %3, %4, %5, %6, %7, %8, %9, %10, %11, %12, %13, %14, %15, %16, %17, %18, %19, %20, %21, %22, %23, %24, %25, %26, %27, %28, %29, %30, %31, %32, %33, %34, %35, %36, %37, %38, %39, %40, %41, %42, %43, %44, %45, %46, %47}, {%48, %49, %50, %51}, tb, p1, 1, 1, 1;\n"
        "add.s64 tb, tb0, 352;\n"
        "wgmma.mma_async.sync.aligned.m64n96k16.f32.bf16.bf16 {%0, %1, %2, %3, %4, %5, %6, %7, %8, %9, %10, %11, %12, %13, %14, %15, %16, %17, %18, %19, %20, %21, %22, %23, %24, %25, %26, %27, %28, %29, %30, %31, %32, %33, %34, %35, %36, %37, %38, %39, %40, %41, %42, %43, %44, %45, %46, %47}, {%52, %53, %54, %55}, tb, p1, 1, 1, 1;\n"
        "}\n"
        : "+f"(d[0]), "+f"(d[1]), "+f"(d[2]), "+f"(d[3]), "+f"(d[4]), "+f"(d[5]), "+f"(d[6]), "+f"(d[7]), "+f"(d[8]), "+f"(d[9]), "+f"(d[10]), "+f"(d[11]), "+f"(d[12]), "+f"(d[13]), "+f"(d[14]), "+f"(d[15]), "+f"(d[16]), "+f"(d[17]), "+f"(d[18]), "+f"(d[19]), "+f"(d[20]), "+f"(d[21]), "+f"(d[22]), "+f"(d[23]), "+f"(d[24]), "+f"(d[25]), "+f"(d[26]), "+f"(d[27]), "+f"(d[28]), "+f"(d[29]), "+f"(d[30]), "+f"(d[31]), "+f"(d[32]), "+f"(d[33]), "+f"(d[34]), "+f"(d[35]), "+f"(d[36]), "+f"(d[37]), "+f"(d[38]), "+f"(d[39]), "+f"(d[40]), "+f"(d[41]), "+f"(d[42]), "+f"(d[43]), "+f"(d[44]), "+f"(d[45]), "+f"(d[46]), "+f"(d[47])
        : "r"(a[AOFF + 0][0]), "r"(a[AOFF + 0][1]), "r"(a[AOFF + 0][2]), "r"(a[AOFF + 0][3]), "r"(a[AOFF + 1][0]), "r"(a[AOFF + 1][1]), "r"(a[AOFF + 1][2]), "r"(a[AOFF + 1][3]), "l"(descB), "n"(BOFF >> 4));
}
};
template <int V, int BOFF, int S0, int S1>
__device__ __forceinline__ void mma_rng(float (&d)[48], const uint32_t (&a)[12][4], uint64_t descB) {
    if constexpr (S0 < S1) Rng<V, S0, S1>::template run<BOFF, S0, 12>(d, a, descB);
}

template <int AOFF, int BOFF>
__device__ __forceinline__ void mma_qk0(float (&d)[28], uint64_t descA, uint64_t descB) {
    asm volatile(
        "{\n"
        ".reg .pred p0, p1;\n"
        ".reg .b64 ta, ta0, tb, tb0;\n"
        "setp.ne.b32 p0, 0, 0;\n"
        "setp.eq.b32 p1, 0, 0;\n"
        "add.s64 tb0, %30, %31;\n"
        "add.s64 ta0, %28, %29;\n"
        "add.s64 tb, tb0, 4;\n"
        "add.s64 ta, ta0, 0;\n"
        "wgmma.mma_async.sync.aligned.m64n56k16.f32.bf16.bf16 {%0, %1, %2, %3, %4, %5, %6, %7, %8, %9, %10, %11, %12, %13, %14, %15, %16, %17, %18, %19, %20, %21, %22, %23, %24, %25, %26, %27}, ta, tb, p0, 1, 1, 0, 0;\n"
        "add.s64 tb, tb0, 1572;\n"
        "add.s64 ta, ta0, 1568;\n"
        "wgmma.mma_async.sync.aligned.m64n56k16.f32.bf16.bf16 {%0, %1, %2, %3, %4, %5, %6, %7, %8, %9, %10, %11, %12, %13, %14, %15, %16, %17, %18, %19, %20, %21, %22, %23, %24, %25, %26, %27}, ta, tb, p1, 1, 1, 0, 0;\n"
        "add.s64 tb, tb0, 3140;\n"
        "add.s64 ta, ta0, 3136;\n"
        "wgmma.mma_async.sync.aligned.m64n56k16.f32.bf16.bf16 {%0, %1, %2, %3, %4, %5, %6, %7, %8, %9, %10, %11, %12, %13, %14, %15, %16, %17, %18, %19, %20, %21, %22, %23, %24, %25, %26, %27}, ta, tb, p1, 1, 1, 0, 0;\n"
        "}\n"
        : "=f"(d[0]), "=f"(d[1]), "=f"(d[2]), "=f"(d[3]), "=f"(d[4]), "=f"(d[5]), "=f"(d[6]), "=f"(d[7]), "=f"(d[8]), "=f"(d[9]), "=f"(d[10]), "=f"(d[11]), "=f"(d[12]), "=f"(d[13]), "=f"(d[14]), "=f"(d[15]), "=f"(d[16]), "=f"(d[17]), "=f"(d[18]), "=f"(d[19]), "=f"(d[20]), "=f"(d[21]), "=f"(d[22]), "=f"(d[23]), "=f"(d[24]), "=f"(d[25]), "=f"(d[26]), "=f"(d[27])
        : "l"(descA), "n"(AOFF >> 4), "l"(descB), "n"(BOFF >> 4));
}

template <int AOFF, int BOFF>
__device__ __forceinline__ void mma_qk1(float (&d)[28], uint64_t descA, uint64_t descB) {
    asm volatile(
        "{\n"
        ".reg .pred p0, p1;\n"
        ".reg .b64 ta, ta0, tb, tb0;\n"
        "setp.ne.b32 p0, 0, 0;\n"
        "setp.eq.b32 p1, 0, 0;\n"
        "add.s64 tb0, %30, %31;\n"
        "add.s64 ta0, %28, %29;\n"
        "add.s64 tb, tb0, 6;\n"
        "add.s64 ta, ta0, 2;\n"
        "wgmma.mma_async.sync.aligned.m64n56k16.f32.bf16.bf16 {%0, %1, %2, %3, %4, %5, %6, %7, %8, %9, %10, %11, %12, %13, %14, %15, %16, %17, %18, %19, %20, %21, %22, %23, %24, %25, %26, %27}, ta, tb, p0, 1, 1, 0, 0;\n"
        "add.s64 tb, tb0, 1574;\n"
        "add.s64 ta, ta0, 1570;\n"
        "wgmma.mma_async.sync.aligned.m64n56k16.f32.bf16.bf16 {%0, %1, %2, %3, %4, %5, %6, %7, %8, %9, %10, %11, %12, %13, %14, %15, %16, %17, %18, %19, %20, %21, %22, %23, %24, %25, %26, %27}, ta, tb, p1, 1, 1, 0, 0;\n"
        "add.s64 tb, tb0, 3142;\n"
        "add.s64 ta, ta0, 3138;\n"
        "wgmma.mma_async.sync.aligned.m64n56k16.f32.bf16.bf16 {%0, %1, %2, %3, %4, %5, %6, %7, %8, %9, %10, %11, %12, %13, %14, %15, %16, %17, %18, %19, %20, %21, %22, %23, %24, %25, %26, %27}, ta, tb, p1, 1, 1, 0, 0;\n"
        "}\n"
        : "=f"(d[0]), "=f"(d[1]), "=f"(d[2]), "=f"(d[3]), "=f"(d[4]), "=f"(d[5]), "=f"(d[6]), "=f"(d[7]), "=f"(d[8]), "=f"(d[9]), "=f"(d[10]), "=f"(d[11]), "=f"(d[12]), "=f"(d[13]), "=f"(d[14]), "=f"(d[15]), "=f"(d[16]), "=f"(d[17]), "=f"(d[18]), "=f"(d[19]), "=f"(d[20]), "=f"(d[21]), "=f"(d[22]), "=f"(d[23]), "=f"(d[24]), "=f"(d[25]), "=f"(d[26]), "=f"(d[27])
        : "l"(descA), "n"(AOFF >> 4), "l"(descB), "n"(BOFF >> 4));
}

template <int BOFF, int AOFF, int NA>
__device__ __forceinline__ void mma_pv(float (&d)[28], const uint32_t (&a)[NA][4], uint64_t descB) {
    asm volatile(
        "{\n"
        ".reg .pred p0, p1;\n"
        ".reg .b64 ta, ta0, tb, tb0;\n"
        "setp.ne.b32 p0, 0, 0;\n"
        "setp.eq.b32 p1, 0, 0;\n"
        "add.s64 tb0, %44, %45;\n"
        "add.s64 tb, tb0, 0;\n"
        "wgmma.mma_async.sync.aligned.m64n56k16.f32.bf16.bf16 {%0, %1, %2, %3, %4, %5, %6, %7, %8, %9, %10, %11, %12, %13, %14, %15, %16, %17, %18, %19, %20, %21, %22, %23, %24, %25, %26, %27}, {%28, %29, %30, %31}, tb, p0, 1, 1, 1;\n"
        "add.s64 tb, tb0, 16;\n"
        "wgmma.mma_async.sync.aligned.m64n56k16.f32.bf16.bf16 {%0, %1, %2, %3, %4, %5, %6, %7, %8, %9, %10, %11, %12, %13, %14, %15, %16, %17, %18, %19, %20, %21, %22, %23, %24, %25, %26, %27}, {%32, %33, %34, %35}, tb, p1, 1, 1, 1;\n"
        "add.s64 tb, tb0, 32;\n"
        "wgmma.mma_async.sync.aligned.m64n56k16.f32.bf16.bf16 {%0, %1, %2, %3, %4, %5, %6, %7, %8, %9, %10, %11, %12, %13, %14, %15, %16, %17, %18, %19, %20, %21, %22, %23, %24, %25, %26, %27}, {%36, %37, %38, %39}, tb, p1, 1, 1, 1;\n"
        "add.s64 tb, tb0, 48;\n"
        "wgmma.mma_async.sync.aligned.m64n56k16.f32.bf16.bf16 {%0, %1, %2, %3, %4, %5, %6, %7, %8, %9, %10, %11, %12, %13, %14, %15, %16, %17, %18, %19, %20, %21, %22, %23, %24, %25, %26, %27}, {%40, %41, %42, %43}, tb, p1, 1, 1, 1;\n"
        "}\n"
        : "=f"(d[0]), "=f"(d[1]), "=f"(d[2]), "=f"(d[3]), "=f"(d[4]), "=f"(d[5]), "=f"(d[6]), "=f"(d[7]), "=f"(d[8]), "=f"(d[9]), "=f"(d[10]), "=f"(d[11]), "=f"(d[12]), "=f"(d[13]), "=f"(d[14]), "=f"(d[15]), "=f"(d[16]), "=f"(d[17]), "=f"(d[18]), "=f"(d[19]), "=f"(d[20]), "=f"(d[21]), "=f"(d[22]), "=f"(d[23]), "=f"(d[24]), "=f"(d[25]), "=f"(d[26]), "=f"(d[27])
        : "r"(a[AOFF + 0][0]), "r"(a[AOFF + 0][1]), "r"(a[AOFF + 0][2]), "r"(a[AOFF + 0][3]), "r"(a[AOFF + 1][0]), "r"(a[AOFF + 1][1]), "r"(a[AOFF + 1][2]), "r"(a[AOFF + 1][3]), "r"(a[AOFF + 2][0]), "r"(a[AOFF + 2][1]), "r"(a[AOFF + 2][2]), "r"(a[AOFF + 2][3]), "r"(a[AOFF + 3][0]), "r"(a[AOFF + 3][1]), "r"(a[AOFF + 3][2]), "r"(a[AOFF + 3][3]), "l"(descB), "n"(BOFF >> 4));
}

template <int AOFF, int BOFF>
__device__ __forceinline__ void mma_proj(float (&d)[96], uint64_t descA, uint64_t descB) {
    asm volatile(
        "{\n"
        ".reg .pred p0, p1;\n"
        ".reg .b64 ta, ta0, tb, tb0;\n"
        "setp.ne.b32 p0, 0, 0;\n"
        "setp.eq.b32 p1, 0, 0;\n"
        "add.s64 tb0, %98, %99;\n"
        "add.s64 ta0, %96, %97;\n"
        "add.s64 tb, tb0, 0;\n"
        "add.s64 ta, ta0, 0;\n"
        "wgmma.mma_async.sync.aligned.m64n192k16.f32.bf16.bf16 {%0, %1, %2, %3, %4, %5, %6, %7, %8, %9, %10, %11, %12, %13, %14, %15, %16, %17, %18, %19, %20, %21, %22, %23, %24, %25, %26, %27, %28, %29, %30, %31, %32, %33, %34, %35, %36, %37, %38, %39, %40, %41, %42, %43, %44, %45, %46, %47, %48, %49, %50, %51, %52, %53, %54, %55, %56, %57, %58, %59, %60, %61, %62, %63, %64, %65, %66, %67, %68, %69, %70, %71, %72, %73, %74, %75, %76, %77, %78, %79, %80, %81, %82, %83, %84, %85, %86, %87, %88, %89, %90, %91, %92, %93, %94, %95}, ta, tb, p0, 1, 1, 0, 1;\n"
        "add.s64 tb, tb0, 64;\n"
        "add.s64 ta, ta0, 2;\n"
        "wgmma.mma_async.sync.aligned.m64n192k16.f32.bf16.bf16 {%0, %1, %2, %3, %4, %5, %6, %7, %8, %9, %10, %11, %12, %13, %14, %15, %16, %17, %18, %19, %20, %21, %22, %23, %24, %25, %26, %27, %28, %29, %30, %31, %32, %33, %34, %35, %36, %37, %38, %39, %40, %41, %42, %43, %44, %45, %46, %47, %48, %49, %50, %51, %52, %53, %54, %55, %56, %57, %58, %59, %60, %61, %62, %63, %64, %65, %66, %67, %68, %69, %70, %71, %72, %73, %74, %75, %76, %77, %78, %79, %80, %81, %82, %83, %84, %85, %86, %87, %88, %89, %90, %91, %92, %93, %94, %95}, ta, tb, p1, 1, 1, 0, 1;\n"
        "add.s64 tb, tb0, 128;\n"
        "add.s64 ta, ta0, 4;\n"
        "wgmma.mma_async.sync.aligned.m64n192k16.f32.bf16.bf16 {%0, %1, %2, %3, %4, %5, %6, %7, %8, %9, %10, %11, %12, %13, %14, %15, %16, %17, %18, %19, %20, %21, %22, %23, %24, %25, %26, %27, %28, %29, %30, %31, %32, %33, %34, %35, %36, %37, %38, %39, %40, %41, %42, %43, %44, %45, %46, %47, %48, %49, %50, %51, %52, %53, %54, %55, %56, %57, %58, %59, %60, %61, %62, %63, %64, %65, %66, %67, %68, %69, %70, %71, %72, %73, %74, %75, %76, %77, %78, %79, %80, %81, %82, %83, %84, %85, %86, %87, %88, %89, %90, %91, %92, %93, %94, %95}, ta, tb, p1, 1, 1, 0, 1;\n"
        "add.s64 tb, tb0, 192;\n"
        "add.s64 ta, ta0, 6;\n"
        "wgmma.mma_async.sync.aligned.m64n192k16.f32.bf16.bf16 {%0, %1, %2, %3, %4, %5, %6, %7, %8, %9, %10, %11, %12, %13, %14, %15, %16, %17, %18, %19, %20, %21, %22, %23, %24, %25, %26, %27, %28, %29, %30, %31, %32, %33, %34, %35, %36, %37, %38, %39, %40, %41, %42, %43, %44, %45, %46, %47, %48, %49, %50, %51, %52, %53, %54, %55, %56, %57, %58, %59, %60, %61, %62, %63, %64, %65, %66, %67, %68, %69, %70, %71, %72, %73, %74, %75, %76, %77, %78, %79, %80, %81, %82, %83, %84, %85, %86, %87, %88, %89, %90, %91, %92, %93, %94, %95}, ta, tb, p1, 1, 1, 0, 1;\n"
        "add.s64 tb, tb0, 256;\n"
        "add.s64 ta, ta0, 512;\n"
        "wgmma.mma_async.sync.aligned.m64n192k16.f32.bf16.bf16 {%0, %1, %2, %3, %4, %5, %6, %7, %8, %9, %10, %11, %12, %13, %14, %15, %16, %17, %18, %19, %20, %21, %22, %23, %24, %25, %26, %27, %28, %29, %30, %31, %32, %33, %34, %35, %36, %37, %38, %39, %40, %41, %42, %43, %44, %45, %46, %47, %48, %49, %50, %51, %52, %53, %54, %55, %56, %57, %58, %59, %60, %61, %62, %63, %64, %65, %66, %67, %68, %69, %70, %71, %72, %73, %74, %75, %76, %77, %78, %79, %80, %81, %82, %83, %84, %85, %86, %87, %88, %89, %90, %91, %92, %93, %94, %95}, ta, tb, p1, 1, 1, 0, 1;\n"
        "add.s64 tb, tb0, 320;\n"
        "add.s64 ta, ta0, 514;\n"
        "wgmma.mma_async.sync.aligned.m64n192k16.f32.bf16.bf16 {%0, %1, %2, %3, %4, %5, %6, %7, %8, %9, %10, %11, %12, %13, %14, %15, %16, %17, %18, %19, %20, %21, %22, %23, %24, %25, %26, %27, %28, %29, %30, %31, %32, %33, %34, %35, %36, %37, %38, %39, %40, %41, %42, %43, %44, %45, %46, %47, %48, %49, %50, %51, %52, %53, %54, %55, %56, %57, %58, %59, %60, %61, %62, %63, %64, %65, %66, %67, %68, %69, %70, %71, %72, %73, %74, %75, %76, %77, %78, %79, %80, %81, %82, %83, %84, %85, %86, %87, %88, %89, %90, %91, %92, %93, %94, %95}, ta, tb, p1, 1, 1, 0, 1;\n"
        "add.s64 tb, tb0, 384;\n"
        "add.s64 ta, ta0, 516;\n"
        "wgmma.mma_async.sync.aligned.m64n192k16.f32.bf16.bf16 {%0, %1, %2, %3, %4, %5, %6, %7, %8, %9, %10, %11, %12, %13, %14, %15, %16, %17, %18, %19, %20, %21, %22, %23, %24, %25, %26, %27, %28, %29, %30, %31, %32, %33, %34, %35, %36, %37, %38, %39, %40, %41, %42, %43, %44, %45, %46, %47, %48, %49, %50, %51, %52, %53, %54, %55, %56, %57, %58, %59, %60, %61, %62, %63, %64, %65, %66, %67, %68, %69, %70, %71, %72, %73, %74, %75, %76, %77, %78, %79, %80, %81, %82, %83, %84, %85, %86, %87, %88, %89, %90, %91, %92, %93, %94, %95}, ta, tb, p1, 1, 1, 0, 1;\n"
        "add.s64 tb, tb0, 448;\n"
        "add.s64 ta, ta0, 518;\n"
        "wgmma.mma_async.sync.aligned.m64n192k16.f32.bf16.bf16 {%0, %1, %2, %3, %4, %5, %6, %7, %8, %9, %10, %11, %12, %13, %14, %15, %16, %17, %18, %19, %20, %21, %22, %23, %24, %25, %26, %27, %28, %29, %30, %31, %32, %33, %34, %35, %36, %37, %38, %39, %40, %41, %42, %43, %44, %45, %46, %47, %48, %49, %50, %51, %52, %53, %54, %55, %56, %57, %58, %59, %60, %61, %62, %63, %64, %65, %66, %67, %68, %69, %70, %71, %72, %73, %74, %75, %76, %77, %78, %79, %80, %81, %82, %83, %84, %85, %86, %87, %88, %89, %90, %91, %92, %93, %94, %95}, ta, tb, p1, 1, 1, 0, 1;\n"
        "add.s64 tb, tb0, 512;\n"
        "add.s64 ta, ta0, 1024;\n"
        "wgmma.mma_async.sync.aligned.m64n192k16.f32.bf16.bf16 {%0, %1, %2, %3, %4, %5, %6, %7, %8, %9, %10, %11, %12, %13, %14, %15, %16, %17, %18, %19, %20, %21, %22, %23, %24, %25, %26, %27, %28, %29, %30, %31, %32, %33, %34, %35, %36, %37, %38, %39, %40, %41, %42, %43, %44, %45, %46, %47, %48, %49, %50, %51, %52, %53, %54, %55, %56, %57, %58, %59, %60, %61, %62, %63, %64, %65, %66, %67, %68, %69, %70, %71, %72, %73, %74, %75, %76, %77, %78, %79, %80, %81, %82, %83, %84, %85, %86, %87, %88, %89, %90, %91, %92, %93, %94, %95}, ta, tb, p1, 1, 1, 0, 1;\n"
        "add.s64 tb, tb0, 576;\n"
        "add.s64 ta, ta0, 1026;\n"
        "wgmma.mma_async.sync.aligned.m64n192k16.f32.bf16.bf16 {%0, %1, %2, %3, %4, %5, %6, %7, %8, %9, %10, %11, %12, %13, %14, %15, %16, %17, %18, %19, %20, %21, %22, %23, %24, %25, %26, %27, %28, %29, %30, %31, %32, %33, %34, %35, %36, %37, %38, %39, %40, %41, %42, %43, %44, %45, %46, %47, %48, %49, %50, %51, %52, %53, %54, %55, %56, %57, %58, %59, %60, %61, %62, %63, %64, %65, %66, %67, %68, %69, %70, %71, %72, %73, %74, %75, %76, %77, %78, %79, %80, %81, %82, %83, %84, %85, %86, %87, %88, %89, %90, %91, %92, %93, %94, %95}, ta, tb, p1, 1, 1, 0, 1;\n"
        "add.s64 tb, tb0, 640;\n"
        "add.s64 ta, ta0, 1028;\n"
        "wgmma.mma_async.sync.aligned.m64n192k16.f32.bf16.bf16 {%0, %1, %2, %3, %4, %5, %6, %7, %8, %9, %10, %11, %12, %13, %14, %15, %16, %17, %18, %19, %20, %21, %22, %23, %24, %25, %26, %27, %28, %29, %30, %31, %32, %33, %34, %35, %36, %37, %38, %39, %40, %41, %42, %43, %44, %45, %46, %47, %48, %49, %50, %51, %52, %53, %54, %55, %56, %57, %58, %59, %60, %61, %62, %63, %64, %65, %66, %67, %68, %69, %70, %71, %72, %73, %74, %75, %76, %77, %78, %79, %80, %81, %82, %83, %84, %85, %86, %87, %88, %89, %90, %91, %92, %93, %94, %95}, ta, tb, p1, 1, 1, 0, 1;\n"
        "add.s64 tb, tb0, 704;\n"
        "add.s64 ta, ta0, 1030;\n"
        "wgmma.mma_async.sync.aligned.m64n192k16.f32.bf16.bf16 {%0, %1, %2, %3, %4, %5, %6, %7, %8, %9, %10, %11, %12, %13, %14, %15, %16, %17, %18, %19, %20, %21, %22, %23, %24, %25, %26, %27, %28, %29, %30, %31, %32, %33, %34, %35, %36, %37, %38, %39, %40, %41, %42, %43, %44, %45, %46, %47, %48, %49, %50, %51, %52, %53, %54, %55, %56, %57, %58, %59, %60, %61, %62, %63, %64, %65, %66, %67, %68, %69, %70, %71, %72, %73, %74, %75, %76, %77, %78, %79, %80, %81, %82, %83, %84, %85, %86, %87, %88, %89, %90, %91, %92, %93, %94, %95}, ta, tb, p1, 1, 1, 0, 1;\n"
        "}\n"
        : "+f"(d[0]), "+f"(d[1]), "+f"(d[2]), "+f"(d[3]), "+f"(d[4]), "+f"(d[5]), "+f"(d[6]), "+f"(d[7]), "+f"(d[8]), "+f"(d[9]), "+f"(d[10]), "+f"(d[11]), "+f"(d[12]), "+f"(d[13]), "+f"(d[14]), "+f"(d[15]), "+f"(d[16]), "+f"(d[17]), "+f"(d[18]), "+f"(d[19]), "+f"(d[20]), "+f"(d[21]), "+f"(d[22]), "+f"(d[23]), "+f"(d[24]), "+f"(d[25]), "+f"(d[26]), "+f"(d[27]), "+f"(d[28]), "+f"(d[29]), "+f"(d[30]), "+f"(d[31]), "+f"(d[32]), "+f"(d[33]), "+f"(d[34]), "+f"(d[35]), "+f"(d[36]), "+f"(d[37]), "+f"(d[38]), "+f"(d[39]), "+f"(d[40]), "+f"(d[41]), "+f"(d[42]), "+f"(d[43]), "+f"(d[44]), "+f"(d[45]), "+f"(d[46]), "+f"(d[47]), "+f"(d[48]), "+f"(d[49]), "+f"(d[50]), "+f"(d[51]), "+f"(d[52]), "+f"(d[53]), "+f"(d[54]), "+f"(d[55]), "+f"(d[56]), "+f"(d[57]), "+f"(d[58]), "+f"(d[59]), "+f"(d[60]), "+f"(d[61]), "+f"(d[62]), "+f"(d[63]), "+f"(d[64]), "+f"(d[65]), "+f"(d[66]), "+f"(d[67]), "+f"(d[68]), "+f"(d[69]), "+f"(d[70]), "+f"(d[71]), "+f"(d[72]), "+f"(d[73]), "+f"(d[74]), "+f"(d[75]), "+f"(d[76]), "+f"(d[77]), "+f"(d[78]), "+f"(d[79]), "+f"(d[80]), "+f"(d[81]), "+f"(d[82]), "+f"(d[83]), "+f"(d[84]), "+f"(d[85]), "+f"(d[86]), "+f"(d[87]), "+f"(d[88]), "+f"(d[89]), "+f"(d[90]), "+f"(d[91]), "+f"(d[92]), "+f"(d[93]), "+f"(d[94]), "+f"(d[95])
        : "l"(descA), "n"(AOFF >> 4), "l"(descB), "n"(BOFF >> 4));
}

template <int AOFF, int BOFF>
__device__ __forceinline__ void mma_proj64(float (&d)[32], uint64_t descA, uint64_t descB) {
    asm volatile(
        "{\n"
        ".reg .pred p0, p1;\n"
        ".reg .b64 ta, ta0, tb, tb0;\n"
        "setp.ne.b32 p0, 0, 0;\n"
        "setp.eq.b32 p1, 0, 0;\n"
        "add.s64 tb0, %34, %35;\n"
        "add.s64 ta0, %32, %33;\n"
        "add.s64 tb, tb0, 0;\n"
        "add.s64 ta, ta0, 0;\n"
        "wgmma.mma_async.sync.aligned.m64n64k16.f32.bf16.bf16 {%0, %1, %2, %3, %4, %5, %6, %7, %8, %9, %10, %11, %12, %13, %14, %15, %16, %17, %18, %19, %20, %21, %22, %23, %24, %25, %26, %27, %28, %29, %30, %31}, ta, tb, p0, 1, 1, 0, 1;\n"
        "add.s64 tb, tb0, 64;\n"
        "add.s64 ta, ta0, 2;\n"
        "wgmma.mma_async.sync.aligned.m64n64k16.f32.bf16.bf16 {%0, %1, %2, %3, %4, %5, %6, %7, %8, %9, %10, %11, %12, %13, %14, %15, %16, %17, %18, %19, %20, %21, %22, %23, %24, %25, %26, %27, %28, %29, %30, %31}, ta, tb, p1, 1, 1, 0, 1;\n"
        "add.s64 tb, tb0, 128;\n"
        "add.s64 ta, ta0, 4;\n"
        "wgmma.mma_async.sync.aligned.m64n64k16.f32.bf16.bf16 {%0, %1, %2, %3, %4, %5, %6, %7, %8, %9, %10, %11, %12, %13, %14, %15, %16, %17, %18, %19, %20, %21, %22, %23, %24, %25, %26, %27, %28, %29, %30, %31}, ta, tb, p1, 1, 1, 0, 1;\n"
        "add.s64 tb, tb0, 192;\n"
        "add.s64 ta, ta0, 6;\n"
        "wgmma.mma_async.sync.aligned.m64n64k16.f32.bf16.bf16 {%0, %1, %2, %3, %4, %5, %6, %7, %8, %9, %10, %11, %12, %13, %14, %15, %16, %17, %18, %19, %20, %21, %22, %23, %24, %25, %26, %27, %28, %29, %30, %31}, ta, tb, p1, 1, 1, 0, 1;\n"
        "add.s64 tb, tb0, 256;\n"
        "add.s64 ta, ta0, 512;\n"
        "wgmma.mma_async.sync.aligned.m64n64k16.f32.bf16.bf16 {%0, %1, %2, %3, %4, %5, %6, %7, %8, %9, %10, %11, %12, %13, %14, %15, %16, %17, %18, %19, %20, %21, %22, %23, %24, %25, %26, %27, %28, %29, %30, %31}, ta, tb, p1, 1, 1, 0, 1;\n"
        "add.s64 tb, tb0, 320;\n"
        "add.s64 ta, ta0, 514;\n"
        "wgmma.mma_async.sync.aligned.m64n64k16.f32.bf16.bf16 {%0, %1, %2, %3, %4, %5, %6, %7, %8, %9, %10, %11, %12, %13, %14, %15, %16, %17, %18, %19, %20, %21, %22, %23, %24, %25, %26, %27, %28, %29, %30, %31}, ta, tb, p1, 1, 1, 0, 1;\n"
        "add.s64 tb, tb0, 384;\n"
        "add.s64 ta, ta0, 516;\n"
        "wgmma.mma_async.sync.aligned.m64n64k16.f32.bf16.bf16 {%0, %1, %2, %3, %4, %5, %6, %7, %8, %9, %10, %11, %12, %13, %14, %15, %16, %17, %18, %19, %20, %21, %22, %23, %24, %25, %26, %27, %28, %29, %30, %31}, ta, tb, p1, 1, 1, 0, 1;\n"
        "add.s64 tb, tb0, 448;\n"
        "add.s64 ta, ta0, 518;\n"
        "wgmma.mma_async.sync.aligned.m64n64k16.f32.bf16.bf16 {%0, %1, %2, %3, %4, %5, %6, %7, %8, %9, %10, %11, %12, %13, %14, %15, %16, %17, %18, %19, %20, %21, %22, %23, %24, %25, %26, %27, %28, %29, %30, %31}, ta, tb, p1, 1, 1, 0, 1;\n"
        "add.s64 tb, tb0, 512;\n"
        "add.s64 ta, ta0, 1024;\n"
        "wgmma.mma_async.sync.aligned.m64n64k16.f32.bf16.bf16 {%0, %1, %2, %3, %4, %5, %6, %7, %8, %9, %10, %11, %12, %13, %14, %15, %16, %17, %18, %19, %20, %21, %22, %23, %24, %25, %26, %27, %28, %29, %30, %31}, ta, tb, p1, 1, 1, 0, 1;\n"
        "add.s64 tb, tb0, 576;\n"
        "add.s64 ta, ta0, 1026;\n"
        "wgmma.mma_async.sync.aligned.m64n64k16.f32.bf16.bf16 {%0, %1, %2, %3, %4, %5, %6, %7, %8, %9, %10, %11, %12, %13, %14, %15, %16, %17, %18, %19, %20, %21, %22, %23, %24, %25, %26, %27, %28, %29, %30, %31}, ta, tb, p1, 1, 1, 0, 1;\n"
        "add.s64 tb, tb0, 640;\n"
        "add.s64 ta, ta0, 1028;\n"
        "wgmma.mma_async.sync.aligned.m64n64k16.f32.bf16.bf16 {%0, %1, %2, %3, %4, %5, %6, %7, %8, %9, %10, %11, %12, %13, %14, %15, %16, %17, %18, %19, %20, %21, %22, %23, %24, %25, %26, %27, %28, %29, %30, %31}, ta, tb, p1, 1, 1, 0, 1;\n"
        "add.s64 tb, tb0, 704;\n"
        "add.s64 ta, ta0, 1030;\n"
        "wgmma.mma_async.sync.aligned.m64n64k16.f32.bf16.bf16 {%0, %1, %2, %3, %4, %5, %6, %7, %8, %9, %10, %11, %12, %13, %14, %15, %16, %17, %18, %19, %20, %21, %22, %23, %24, %25, %26, %27, %28, %29, %30, %31}, ta, tb, p1, 1, 1, 0, 1;\n"
        "}\n"
        : "=f"(d[0]), "=f"(d[1]), "=f"(d[2]), "=f"(d[3]), "=f"(d[4]), "=f"(d[5]), "=f"(d[6]), "=f"(d[7]), "=f"(d[8]), "=f"(d[9]), "=f"(d[10]), "=f"(d[11]), "=f"(d[12]), "=f"(d[13]), "=f"(d[14]), "=f"(d[15]), "=f"(d[16]), "=f"(d[17]), "=f"(d[18]), "=f"(d[19]), "=f"(d[20]), "=f"(d[21]), "=f"(d[22]), "=f"(d[23]), "=f"(d[24]), "=f"(d[25]), "=f"(d[26]), "=f"(d[27]), "=f"(d[28]), "=f"(d[29]), "=f"(d[30]), "=f"(d[31])
        : "l"(descA), "n"(AOFF >> 4), "l"(descB), "n"(BOFF >> 4));
}

struct Params {
    const __nv_bfloat16* x;
    const __nv_bfloat16* wqkv;
    const __nv_bfloat16* wo;
    const __nv_bfloat16* logit_scale;
    const __nv_bfloat16* cpb_w1;
    const __nv_bfloat16* cpb_w2;
    const __nv_bfloat16* rel_coords;
    const int*           rel_idx;
    const __nv_bfloat16* mask;
    __nv_bfloat16*       out;
    unsigned long long   z1;
};

struct Q {
    static constexpr int npair = NPAIR, nh = NH, hw = NH ? HW : 0;
    static constexpr uint32_t need = ROW_DONE;
    static constexpr int nq = (NWINDOWS - hw) / NPAIR, nr = (NWINDOWS - hw) % NPAIR;
    static constexpr int nr2 = 2 * nr, nt0 = (nq * TOK + 63) / 64, nt1 = ((nq + 1) * TOK + 63) / 64;
    static constexpr int hq = NH ? HW / (NH ? NH : 1) : 0, hr = NPAIR + (NH ? HW % (NH ? NH : 1) : 0), hr2 = 2 * hr;
    static constexpr int ht0 = (hq * TOK + 63) / 64, ht1 = ((hq + 1) * TOK + 63) / 64;
    static constexpr int t1 = TILES - NTAIL;
};
#define PQ(f) Q::f
#define GRID 132

struct Maps {
    CUtensorMap x77, x47, x37, x44, x43, x34, x33;
    CUtensorMap w64, w32, w;
    CUtensorMap s47, s37, s43, s33;
    CUtensorMap o, ob;
};

__device__ __forceinline__ uint32_t row_token(uint32_t r) {
    return r < 28 ? r + 3 * (r >> 2) : r - 24 + 4 * (((r - 28) * 11) >> 5);
}
__device__ __forceinline__ int unrot(int r) { return r ? r - 1 : NWS - 1; }
__device__ __forceinline__ void finish(uint32_t total) {
    __threadfence();
    if (atomicAdd(&g_done, 1u) == total - 1) {
        for (int i = 0; i <= NWS; i++) g_cnt[i] = 0;
        g_done = 0;
    }
}

__global__ void __launch_bounds__(NTHREADS, 1)
swin_window_attn_kernel(const Params P, const __grid_constant__ Maps M) {
    const CUtensorMap &xmap = M.x77, &omap = M.o, &omapb = M.ob, &wmap = M.w;
    extern __shared__ __align__(1024) uint8_t smem[];
    constexpr uint32_t sbase = 1024;
    if (smem_u32(smem) != sbase) return;
    const int tid = threadIdx.x;
    const int wg = __shfl_sync(0xffffffffu, tid >> 7, 0);
    const int warp = __shfl_sync(0xffffffffu, (tid >> 5) & 3, 0);
    const int lane = tid & 31;
    const int g = lane >> 2, c = lane & 3;

    TR(26, wg);
    TP(wg);
    if (tid == 0) TC(0);
    const bool attn = (int)blockIdx.x < 2 * (PQ(npair) + PQ(nh));
    const int pair = blockIdx.x >> 1, half = blockIdx.x & 1;
    const int nwin = pair < PQ(npair) ? PQ(nq) + (pair < PQ(nr) ? 1 : 0) : PQ(hq) + (pair < PQ(hr) ? 1 : 0);
    const int w0 = pair < PQ(npair) ? PQ(hw) + pair : pair - PQ(npair), wstep = pair < PQ(npair) ? PQ(npair) : PQ(nh);
    const int wr0 = w0 >= NWS, wq0 = w0 - wr0 * NWS;
    const int ntiles = (nwin * TOK + 63) >> 6;
    const uint32_t bars = sbase + SM_BAR;
    auto load_x = [&](uint32_t dst, uint32_t bar, uint32_t bar2, int wh, int ww) {
        const int x0 = 7 * ww + 3, y0 = 7 * wh + 3, x1 = ww == NWS - 1 ? 0 : x0 + 4;
        if (wh < NWS - 1) {
#pragma unroll
            for (int ch = 0; ch < 3; ch++) tma_3d_x(dst + ch * QK_CHUNK, &M.x47, bar, ch * 64, x0, y0);
#pragma unroll
            for (int ch = 0; ch < 3; ch++) tma_3d_x(dst + ch * QK_CHUNK + 28 * 128, &M.x37, bar2, ch * 64, x1, y0);
        } else {
#pragma unroll
            for (int ch = 0; ch < 3; ch++) {
                tma_3d_x(dst + ch * QK_CHUNK, &M.x44, bar, ch * 64, x0, y0);
                tma_3d_x(dst + ch * QK_CHUNK + 16 * 128, &M.x43, bar, ch * 64, x0, 0);
            }
#pragma unroll
            for (int ch = 0; ch < 3; ch++) {
                tma_3d_x(dst + ch * QK_CHUNK + 28 * 128, &M.x34, bar2, ch * 64, x1, y0);
                tma_3d_x(dst + ch * QK_CHUNK + 40 * 128, &M.x33, bar2, ch * 64, x1, 0);
            }
        }
    };
    if (EPF >= 6 && tid == 128) {
        const char* p = reinterpret_cast<const char*>(P.x) + (blockIdx.x & 127) * 1024;
        if (EPF == 6) {
            asm volatile("cp.async.bulk.prefetch.L2.global [%0], 16;\n" :: "l"(p) : "memory");
            asm volatile("cp.async.bulk.prefetch.L2.global [%0], 16;\n" :: "l"(p + (size_t)(IMG - 4) * (IMG * 384)) : "memory");
            asm volatile("cp.async.bulk.prefetch.L2.global [%0], 16;\n" :: "l"(p + (size_t)9 * (IMG * 384)) : "memory");
        } else {
            prefetch_l2(p);
            prefetch_l2(p + (size_t)(IMG - 4) * (IMG * 384));
            prefetch_l2(p + (size_t)9 * (IMG * 384));
        }
    }
    if (EPF >= 4 && EPF < 6 && tid >= 128 && tid < (EPF == 5 ? 192 : 160) && attn && elect_one()) {
        const int q = w0 + (half + (tid >> 5 & 1) * 2) * wstep, r = q / NWS, ww = unrot(q - r * NWS);
        int y = 7 * unrot(r) + 3;
        const char* p = reinterpret_cast<const char*>(P.x) + (7 * ww + 3) * 384;
#pragma unroll 1
        for (int i = 0; i < 7; i++, y++) {
            if (y == IMG) y = 0;
            asm volatile("cp.async.bulk.prefetch.L2.global [%0], %1;\n" :: "l"(p + (size_t)y * (IMG * 384)), "r"(ww == NWS - 1 ? 1536 : 2688) : "memory");
        }
    }
    if (EPF && EPF < 4 && (wg == 1 || wg == 2)) {
        const int i = tid - 128, q = w0 + half * wstep, r = q >= NWS;
        const int px = (i * 171) >> 9, py = (px * 37) >> 8;
        int y = 7 * unrot(r) + 3 + py, x = 7 * unrot(q - r * NWS) + 3 + px - 7 * py;
        if (y >= IMG) y -= IMG;
        if (x >= IMG) x -= IMG;
        const char* p = reinterpret_cast<const char*>(P.x) + (size_t)(y * IMG + x) * 384 + (i - 3 * px) * 128;
        if (EPW && i >= 147) p = reinterpret_cast<const char*>(P.wqkv) + min((int)blockIdx.x * 14 + i - 147, 1727) * 128;
        if (i < 147 ? attn : EPW && i < 161) {
            if (EPF == 1) asm volatile("prefetch.global.L2 [%0];\n" :: "l"(p) : "memory");
            if (EPF == 2) { uint32_t d; asm volatile("ld.global.nc.L2::128B.b32 %0, [%1];\n" : "=r"(d) : "l"(p) : "memory"); }
            if (EPF == 3) for (int j = 0; j < 4; j++) asm volatile("prefetch.global.L2 [%0];\n" :: "l"(p + 32 * j) : "memory");
        }
    }
    uint32_t ls = 0;
    if (wg == 0) {
        TP(28);
        if (attn && warp < (WSEQ ? 1 : 3) && elect_one()) {
#pragma unroll
            for (int i = 0; i < (WSEQ ? 3 : 1); i++) mbar_init(bars + B_WRAW + 16 - 8 * (warp + i), 1);
            fence_async_smem();
            if (HDEL && pair >= PQ(npair)) {
                const uint32_t c0 = clock();
                while (clock() - c0 < HDEL) __nanosleep(100);
            }
            TP(29);
#pragma unroll 1
            for (int i0 = warp; i0 < warp + (WSEQ ? 3 : 1); i0++) {
                const int i = WROT == 1 ? (i0 + pair) % 3 : WROT == 2 ? (pair & 1 ? 2 - i0 : i0) : WROT == 3 ? 2 - i0 : i0;
                const uint32_t bar = bars + B_WRAW + 16 - 8 * i, dst = sbase + i * 24576;
                mbar_arrive_expect_tx(bar, 24576);
                tma_3d(dst, &M.w64, bar, half * 128, 64 * i, 0);
                tma_3d(dst + 16384, &M.w32, bar, 64 + half * 32, 64 * i, 0);
            }
            TP(30);
        }
        __syncwarp();
        if (WFIRST && warp == 0) asm volatile("bar.arrive 3, 96;\n" ::: "memory");
        if (PPAR && warp == 0) nb_arrive<416>(11);
        if (attn) asm volatile("ld.global.nc.u16 %0, [%1];\n" : "=r"(ls) : "l"(P.logit_scale + 2 * half + (GORD == 2 ? c >> 1 : c & 1)));
    } else if (wg == 3) {
        if (warp == 3) {
            if (elect_one()) {
#pragma unroll
                for (int i = 0; i < 6; i++)
                    asm volatile("prefetch.tensormap [%0];\n" :: "l"(reinterpret_cast<uint64_t>(&M.x44 + (i < 4 ? i : i - 6))) : "memory");
            }
            if (attn)
#pragma unroll
                for (int i = 0; i < 4; i++) sts128(sbase + SM_V + i * V_STRIDE + (lane < 16 ? lane * 16 : V_STRIDE - 64 + (lane & 3) * 16), 0, 0, 0, 0);
            sts32(sbase + SM_FLAG + lane * 4, 0);
            fence_async_smem();
            asm volatile("bar.arrive 0, 256;\nbar.arrive 11, %0;\n" :: "n"(PPAR ? 416 : 384) : "memory");
        } else if (warp != 1) {
            if (tid == 384) {
                for (int b = 0; b < 4; b++) mbar_init(bars + B_XFULL + b * 8, 2);
                asm volatile("mbarrier.expect_tx.relaxed.cta.shared::cta.b64 [%0], %1;\n" :: "r"(bars + B_XFULL + 8), "r"(3 * 21 * 128) : "memory");
                fence_async_smem();
            }
            __syncwarp();
            asm volatile("bar.arrive 0, 256;\nbar.arrive 11, %0;\n" :: "n"(PPAR ? 416 : 384) : "memory");
            nb_sync<WFIRST ? 96 : 64>(3);
            if (attn && elect_one()) {
                const int j = warp >> 1, q = w0 + j * wstep, r = q >= NWS;
                mbar_arrive_expect_tx(bars + B_XFULL, j ? 3 * 28 * 128 : 3 * XCH);
                load_x(sbase + SM_QK + j * XCH, bars + B_XFULL, bars + B_XFULL + j * 8, unrot(r), unrot(q - r * NWS));
                TP(26 + j);
            }
            __syncwarp();
        } else {
            if (lane == 0) {
                for (int b = 0; b < 4; b++) {
                    mbar_init(bars + B_QKRAW + b * 8, 4);
                    mbar_init(bars + B_VRAW + b * 8, 4);
                    mbar_init(bars + B_VFREE + b * 8, 2);
                    mbar_init(bars + B_QKFREE + b * 8, (NB & 1) ? 1 : 4);
                    mbar_init(bars + B_ODONE + b * 8, 4);
                }
                mbar_init(bars + B_WFULL, 1);
                mbar_init(bars + B_MFULL, 1);
                mbar_init(bars + B_MCONS, 4);
                sts32(bars + B_PROG, 0);
                if (SDEF == 4) sts32(bars + B_PROG + 8, 0);
                for (int b = 0; b < 4; b++) mbar_init(bars + B_STORED + b * 8, 1);
                for (int b = 0; b < 6; b++) {
                    mbar_init(sbase + SM_PBAR + b * 8, 1);
                    mbar_init(sbase + SM_PBAR + 48 + b * 8, PSTORE ? 1 : 4);
                    mbar_init(sbase + SM_PBAR + 104 + b * 8, 4);
                }
                mbar_init(sbase + SM_PBAR + 96, 13);
                fence_async_smem();
            }
            __syncwarp();
            TP(19);
            asm volatile("bar.arrive 0, 256;\nbar.arrive 11, %0;\n" :: "n"(PPAR ? 416 : 384) : "memory");
        }
        asm volatile("bar.sync 2, 128;\n" ::: "memory");
        if (warp == 3 && lane < 8)
            asm volatile("prefetch.tensormap [%0];\n" :: "l"(reinterpret_cast<uint64_t>(&M.x77 + (lane ? lane + 8 : 0))) : "memory");
        TP(13);
    }
    uint32_t ridx[26];
    uint32_t rc, w2[16];
    uint4 w1[4];
    if (attn && (wg == 1 || wg == 2)) {
        rc = reinterpret_cast<const uint32_t*>(P.rel_coords)[min(tid - 128, 168)];
#pragma unroll
        for (int i = 0; i < 4; i++) w1[i] = reinterpret_cast<const uint4*>(P.cpb_w1)[i];
#pragma unroll
        for (int u = 0; u < 16; u++) w2[u] = reinterpret_cast<const uint32_t*>(P.cpb_w2)[2 * u + half];
        ls = reinterpret_cast<const uint32_t*>(P.logit_scale)[half];
        asm volatile("" ::: "memory");
        uint32_t col[7];
#pragma unroll
        for (int j = 0; j < 7; j++) {
            const uint32_t n = j ? 8 * ((j + 5) >> 1) + ((j + 1) & 1) : 0;
            col[j] = prmt(0, row_token(n) | row_token(n + 2) << 8 | row_token(n + 4) << 16 | row_token(n + 6) << 24, 4 + c);
        }
#pragma unroll
        for (int rh = 0; rh < 2; rh++) {
            const uint32_t* ri = reinterpret_cast<const uint32_t*>(P.rel_idx) + row_token(min(warp * 16 + g + 8 * rh, TOK - 1)) * TOK;
            asm volatile("" : "+l"(ri));
#pragma unroll
            for (int j = 0; j < 12; j++) ridx[13 * rh + j] = j < 6 ? (ri + col[0])[14 * (j >> 1) + (j & 1)] : ri[col[j - 5]];
            ridx[13 * rh + 12] = ri[48];
        }
    }
    if (wg == 1) TP(31);
    if (wg == 0) asm volatile("bar.sync 0, 256;\n" ::: "memory");
    else if (wg < 3) nb_sync<PPAR ? 416 : 384>(11);
    TP(4 + wg);

    const uint32_t nfinish = GRID + 4 * (PQ(npair) + PQ(nh));
#define PROJ_SCHEDULE                                                                                   \
    int bid = blockIdx.x;                                                                               \
    asm volatile("" : "+r"(bid));                      \
    const bool at = bid < 2 * PQ(npair);                                                                  \
    const int tile0 = at ? PQ(t1) + 2 * PQ(npair) - 1 - bid : bid - 2 * PQ(npair);                                              \
    const int tstep = at ? 2 * PQ(npair) : GRID - 2 * PQ(npair);                                  \
    const int tend = at ? TILES : PQ(t1);                                                                \
    const int nl = (TILES - 1 - tile0) / (2 * PQ(npair));        \
    const int tend1 = COOP && at ? tile0 + (nl + 1 - COOP) * tstep : tend;
    if (wg == 3) {
        asm volatile("setmaxnreg.dec.sync.aligned.u32 %0;\n" :: "n"(REG_H));
        if (attn && warp == 1 && !(XP & 1)) {
            uint32_t fph = 0, cph = 0, mis = 0, busy = 0;
            auto load = [&](int k, uint32_t dst) {
                const int wi = w0 + k * wstep, wr = wi / NWS;
                const uint32_t off = (uint32_t)(unrot(wr) * NWS + unrot(wi - wr * NWS)) * 4802u;
                mis = mis << 4 | (off & 15);
                if (busy) {
                    mbar_wait(bars + B_MCONS, cph);
                    cph ^= 1;
                    fence_async_smem();
                    busy = 0;
                }
                if (elect_one()) {
                    uint32_t bytes = 4816;
                    if (wi == 0) {
                        bytes = 4800;
                        asm volatile("st.shared.u16 [%0], %1;\n" :: "r"(sbase + SM_MASK + 4800),
                                     "h"(reinterpret_cast<const uint16_t*>(P.mask)[NWINDOWS * TOK * TOK - 1]) : "memory");
                    }
                    asm volatile("mbarrier.expect_tx.relaxed.cta.shared::cta.b64 [%0], %1;\n" :: "r"(bars + B_MFULL), "r"(bytes) : "memory");
                    if (dst == sbase + SM_MASK) mbar_arrive(bars + B_MFULL);
                    asm volatile("cp.async.bulk.shared::cluster.global.mbarrier::complete_tx::bytes.L2::cache_hint [%0], [%1], %2, [%3], %4;\n"
                                 :: "r"(dst), "l"(reinterpret_cast<const char*>(P.mask) + (off & ~15u)),
                                    "r"(bytes), "r"(bars + B_MFULL), "l"(EVICT_FIRST) : "memory");
                }
            };
            auto landed = [&]() {
                mbar_wait_s<HS & 1>(bars + B_MFULL, fph);
                fph ^= 1;
            };
            auto flag = [&](int k, uint32_t f) {
                asm volatile("st.volatile.shared.u8 [%0], %1;\n" :: "r"(sbase + SM_FLAG + k), "r"(f) : "memory");
                TR(18, k);
                if (k < 2) TP(14 + k);
            };
            auto pace = [&](int need) {
                int done = 0;
#pragma unroll 1
                for (uint32_t n = 0; n < (1u << 22); n++) {
                    asm volatile("ld.volatile.shared.b32 %0, [%1];\n" : "=r"(done) : "r"(bars + B_PROG) : "memory");
                    if (done >= need) break;
                    __nanosleep(PSLEEP);
                }
                return done;
            };
            auto buffer = [&](int k) { return sbase + (k == 0 || k > 3 ? SM_MASK : SM_V + 2 * V_STRIDE + 256 + (k >> 1) * 4816); };
            if (MWAIT) mbar_wait(bars + (MWAIT == 1 ? B_XFULL : MWAIT == 2 ? B_WRAW : B_WRAW + 8), 0);
#pragma unroll 1
            for (int k = 2 + half; k >= 0; k = (k >> 1) - (k == 0)) load(k, buffer(k));
            uint32_t todo = 0;
            int sp = 0;
#pragma unroll 1
            for (int k = 0, kn; sp < nwin; k = kn) {
                int done = 0;
                if (k < nwin) {
                    done = pace(MD ? k - MLEAD - MD : k + 2 < nwin ? k - MLEAD : k - 3);
                    if (MD) done = __shfl_sync(0xffffffffu, done, 0);
                    const uint32_t buf = buffer(k);
                    if (buf == sbase + SM_MASK) landed();
                    TR(17, k);
                    uint32_t any;
                    asm volatile("ld.shared.u16 %0, [%1];\n" : "=r"(any)
                                 : "r"(buf + (mis & 15) + ((lane & 8) ? 4800 - 14 : 0) + (lane & 7) * 2) : "memory");
                    mis >>= 4;
#pragma unroll
                    for (int i = 0; i < 10; i++) {
                        uint32_t v[4];
                        asm volatile("ld.shared.v4.b32 {%0, %1, %2, %3}, [%4];\n" : "=r"(v[0]), "=r"(v[1]), "=r"(v[2]), "=r"(v[3])
                                     : "r"(buf + lane * 16 + (i < 9 ? 16 + i * 512 : 4800 - 512)) : "memory");
                        any |= (v[0] | v[1]) | (v[2] | v[3]);
                    }
                    const uint32_t masked = __any_sync(0xffffffffu, any & 0x7FFF7FFFu);
                    if (k >= 2) asm volatile("st.relaxed.gpu.global.u32 [%0], %1;\n" :: "l"(g_flag + pair * 128 + k), "r"(1 + masked) : "memory");
                    if (masked && k) todo |= 1u << (k - sp);
                    else {
                        if (k == 0) __threadfence_block();
                        flag(k, 1 + masked);
                        busy |= masked;
                    }
                }
                if ((k >> 1) == 1 && lane == 0) mbar_arrive(bars + B_VFREE + 8);
                const int lim = MD && k < nwin ? min(k, done + MLEAD) : k;
#pragma unroll
                for (int pass = MD ? 1 : 0; pass >= 0; pass--) {
                if (pass == 0 && k > 2 && k <= nwin) {
                    uint32_t f;
#pragma unroll 1
                    for (uint32_t n = 0; n < (1u << 22); n++) {
                        asm volatile("ld.relaxed.gpu.global.u32 %0, [%1];\n" : "=r"(f) : "l"(g_flag + pair * 128 + k - 1) : "memory");
                        if (__all_sync(0xffffffffu, f)) break;
                        __nanosleep(PSLEEP);
                    }
                    g_flag[pair * 128 + k - 1] = 0;
                    if (f != 1) todo |= 1u << (k - 1 - sp);
                    else flag(k - 1, 1);
                }
#pragma unroll 1
                for (; sp < lim && sp < k - pass; sp++, todo >>= 1)
                    if (todo & 1) {
                        load(sp, sbase + SM_MASK);
                        landed();
                        __threadfence_block();
                        flag(sp, 2);
                        busy = 1;
                    }
                }
                kn = k >= 2 ? k + 2 : k + 1 + (k & half);
                if (kn < nwin && kn > 3) load(kn, sbase + SM_MASK);
                if (MP2 && kn + 2 * MP2 < nwin && kn > 1) {
                    const int wi = w0 + (kn + 2 * MP2) * wstep, wr = wi / NWS;
                    const uint32_t off = (uint32_t)(unrot(wr) * NWS + unrot(wi - wr * NWS)) * 4802u;
                    if (elect_one())
                        asm volatile("cp.async.bulk.prefetch.L2.global [%0], 4816;\n" :: "l"(reinterpret_cast<const char*>(P.mask) + (off & ~15u)) : "memory");
                }
            }
            if (MD) pace(nwin - 4);
        }
        if (!elect_one()) return;
        if (warp == 0) {
          if (attn) {
            const int kmax = (64 * ntiles + 63) / TOK;
            int wr = wr0, wq = wq0, npf = 0;
            int pr2 = (w0 + PF_DIST * wstep) / NWS, pq2 = w0 + PF_DIST * wstep - pr2 * NWS;
#pragma unroll 1
            for (int k = -4; k + 4 <= kmax; k++) {
                const int row0 = (k + 4) * TOK;
                const uint32_t dst = sbase + SM_QK + (k & 3) * XCH, bar = bars + B_XFULL + ((row0 >> 6) & 3) * 8;
                const bool alone = (row0 & 63) >= 64 - TOK && (row0 & 63) < TOK;
                const int wh = unrot(wr), ww = unrot(wq), ph2 = unrot(pr2), pw2 = unrot(pq2);
                const bool done = k < -2;
                if (k == WVK) {
                    if (WVW) mbar_wait(bars + (WVW == 1 ? B_XFULL : WVW == 2 ? B_WRAW : B_WRAW + 8), 0);
                    TP(24);
                    mbar_arrive_expect_tx(bars + B_WFULL, 6 * W_ATOM);
                    tma_3d(sbase + SM_WV, &wmap, bars + B_WFULL, 0, 0, V64 ? 12 + half * 3 : 24 + half * 6);
                }
                const uint32_t bar2 = (row0 & 63) >= 64 - 28 ? bars + B_XFULL + (((row0 >> 6) + 1) & 3) * 8 : bar;
                if (alone && !done) mbar_arrive(bar);
                if (!done && !(k + 4 >= nwin && k >= 0)) {
                    if (bar2 != bar) asm volatile("mbarrier.expect_tx.relaxed.cta.shared::cta.b64 [%0], %1;\n" :: "r"(bar2), "r"(3 * 21 * 128) : "memory");
                    mbar_arrive_expect_tx(bar, bar2 != bar ? 3 * 28 * 128 : 3 * XCH);
                }
                if (SDEF == 4 && k >= 0 && k + 4 < nwin) {
                    const int t1 = (TOK * (k + 1) - 1) >> 6;
                    mbar_wait(bars + B_QKRAW + (t1 & 3) * 8, (t1 >> 2) & 1);
                    asm volatile("st.volatile.shared.v2.b32 [%0], {%1, %2};\n" :: "r"(bars + B_PROG + 8), "r"(k), "r"(clock32()) : "memory");
                }
                if (k >= 0 && k + 4 < nwin && wh < NWS - 1) {
                    const int x0 = 7 * ww + 3, y0 = 7 * wh + 3, x1 = ww == NWS - 1 ? 0 : x0 + 4;
                    asm volatile("bar.sync %0, 160;\n"
                                 "cp.async.bulk.tensor.3d.shared::cluster.global.mbarrier::complete_tx::bytes [%1], [%7, {%14, %11, %13}], [%9];\n"
                                 "cp.async.bulk.tensor.3d.shared::cluster.global.mbarrier::complete_tx::bytes [%2], [%7, {%15, %11, %13}], [%9];\n"
                                 "cp.async.bulk.tensor.3d.shared::cluster.global.mbarrier::complete_tx::bytes [%3], [%7, {%16, %11, %13}], [%9];\n"
                                 "cp.async.bulk.tensor.3d.shared::cluster.global.mbarrier::complete_tx::bytes [%4], [%8, {%14, %12, %13}], [%10];\n"
                                 "cp.async.bulk.tensor.3d.shared::cluster.global.mbarrier::complete_tx::bytes [%5], [%8, {%15, %12, %13}], [%10];\n"
                                 "cp.async.bulk.tensor.3d.shared::cluster.global.mbarrier::complete_tx::bytes [%6], [%8, {%16, %12, %13}], [%10];\n"
                                 :: "r"(NB_QKFREE + (k & 1) + (EXD ? __umulhi(__umulhi((x0 | y0 | x1) + dst, bar2), bar) : 0)), "r"(dst), "r"(dst + QK_CHUNK), "r"(dst + 2 * QK_CHUNK), "r"(dst + 28 * 128),
                                    "r"(dst + QK_CHUNK + 28 * 128), "r"(dst + 2 * QK_CHUNK + 28 * 128),
                                    "l"(reinterpret_cast<uint64_t>(&M.x47)), "l"(reinterpret_cast<uint64_t>(&M.x37)), "r"(bar), "r"(bar2),
                                    "r"(x0), "r"(x1), "r"(y0), "r"(0), "r"(64), "r"(128) : "memory");
                } else {
                if (NB & 1) {
                    if (k >= 0) nb_sync<160>(NB_QKFREE + (k & 1));
                } else mbar_wait(bars + B_QKFREE + (k & 3) * 8, (k >> 2) & 1);
                if (!EXH && alone && !done) mbar_arrive(bar);
                if (k + 4 >= nwin && k >= 0) {
                    mbar_arrive(bar);
                    continue;
                }
                TR(20, k + 4);
                if (k < 0) TP(44 + k);
                if (!done) load_x(dst, bar, bar2, wh, ww);
                }
                TR(25, k + 4);
                asm volatile("st.volatile.shared.b32 [%0], %1;\n" :: "r"(bars + B_PROG), "r"(max(k + 1, 0)) : "memory");
                if (NOPF || (PFM >= 7 && k > 0)) {
                } else if (PFM == 6) {
                    npf++;
                    const int t1 = (TOK * (k + 2) - 1) >> 6;
                    if (half == 0 && (k < 0 || npf > 2 || !mbar_test(bars + B_QKRAW + (t1 & 3) * 8, (t1 >> 2) & 1))) {
#pragma unroll 1
                        for (; npf > 0; npf--) {
                            if (pr2 < NWS)
                                asm volatile("cp.async.bulk.prefetch.tensor.3d.L2.global.tile [%0, {%1, %2, %3}];\n"
                                             :: "l"(reinterpret_cast<uint64_t>(&xmap)), "r"(0), "r"(7 * unrot(pq2) + 3), "r"(7 * unrot(pr2) + 3) : "memory");
                            pq2 += wstep; if (pq2 >= NWS) { pq2 -= NWS; pr2++; }
                        }
                    }
                } else if (PFM == 2) {
                    if (pr2 < NWS && half == 0) {
                        const char* xp = reinterpret_cast<const char*>(P.x) + (size_t)((7 * ph2 + 3) * IMG + 7 * pw2 + 3) * 384;
#pragma unroll 1
                        for (int r = 0; r < (ph2 == NWS - 1 ? 3 : 7); r++)
                            asm volatile("cp.async.bulk.prefetch.L2.global [%0], 2688;\n" :: "l"(xp + r * (IMG * 384)) : "memory");
                    }
                } else if (PFM == 1 ? ((k ^ half) & 1) : PFM == 4 ? half == 1 : PFM == 5 ? 1 : half == 0) {
                    if (pr2 < NWS) {
#pragma unroll
                        for (int ch = 0; ch < (PF1 ? 1 : 3); ch++)
                            if (CH & 8)
                            asm volatile("cp.async.bulk.prefetch.tensor.3d.L2.global.tile.L2::cache_hint [%0, {%1, %2, %3}], %4;\n"
                                         :: "l"(reinterpret_cast<uint64_t>(&xmap)), "r"(ch * 64), "r"(7 * pw2 + 3), "r"(7 * ph2 + 3), "l"(EVICT_FIRST)
                                         : "memory");
                            else
                            asm volatile("cp.async.bulk.prefetch.tensor.3d.L2.global.tile [%0, {%1, %2, %3}];\n"
                                         :: "l"(reinterpret_cast<uint64_t>(&xmap)), "r"(ch * 64), "r"(7 * pw2 + 3), "r"(7 * ph2 + 3)
                                         : "memory");
                        if (PFW && pw2 == NWS - 1)
                            asm volatile("cp.async.bulk.prefetch.tensor.3d.L2.global.tile [%0, {%1, %2, %3}];\n"
                                         :: "l"(reinterpret_cast<uint64_t>(&xmap)), "r"(0), "r"(-4), "r"(7 * ph2 + 3) : "memory");
                    }
                }
                wq += wstep; if (wq >= NWS) { wq -= NWS; wr++; }
                if (PFM != 6) { pq2 += wstep; if (pq2 >= NWS) { pq2 -= NWS; pr2++; } }
            }
            if (!VLATE) mbar_wait(bars + B_VRAW + ((ntiles - 1) & 3) * 8, ((ntiles - 1) >> 2) & 1);
          }
            PROJ_SCHEDULE
            int st = 0, ready = -1, pwa = 0, pwi = -1;
            auto look = [&](uint32_t bar, uint32_t par) {
#pragma unroll 1
                for (uint32_t n = 0; n < (1u << 22) && ready < NWS - LOOKE && !mbar_test(bar, par); n++) {
                    uint32_t a;
                    asm volatile("ld.acquire.gpu.global.u32 %0, [%1];\n" : "=r"(a) : "l"(g_cnt + ready + 1) : "memory");
                    if (a >= PQ(need)) {
                        ready++;
                        asm volatile("fence.proxy.async.global;\n" ::: "memory");
                    }
                }
            };
            uint32_t ph = 1;
#pragma unroll 1
            for (int t = tile0; t < tend; t += tstep) {
                const int p0 = (t < TILES_A) ? SEG_B + 64 * t : 64 * (t - TILES_A);
                const int w1 = (t < TILES_A) ? 0 : min((p0 + 63 + 4 * IMG) / (7 * IMG), NWS - 1);
                if (bid < 2 * (PQ(npair) + PQ(nh)) && t == tile0 + tstep) {
                    if (LOOKA && at) look(sbase + SM_PBAR + 96, 0);
                    mbar_wait(sbase + SM_PBAR + 96, 0);
                    fence_async_smem();
                }
                if (CHK && !at) {
#pragma unroll 1
                    for (uint32_t n = 0; ready < w1 && n < (1u << 24); n++) {
                        if (n) __nanosleep(32);
                        asm volatile("ld.acquire.cta.shared.b32 %0, [%1];\n" : "=r"(ready) : "r"(sbase + SM_FLAG + 124) : "memory");
                        ready--;
                    }
                } else if (ready < w1) {
                    ready = max(ready, w1 - 2);
#pragma unroll 1
                    while (ready < w1) {
                        ready++;
#pragma unroll 1
                        for (uint32_t n = 0; n < (1u << 22); n++) {
                            uint32_t a;
                            asm volatile("ld.acquire.gpu.global.u32 %0, [%1];\n" : "=r"(a) : "l"(g_cnt + ready) : "memory");
                            if (a >= PQ(need)) break;
                            if (PSL2 >= 0) __nanosleep(PSL2);
                            else if (!at) __nanosleep(64);
                        }
                    }
                    asm volatile("fence.proxy.async.global;\n" ::: "memory");
                }
                if (VLATE && attn && t == tile0) {
                    if (VLATE == 2 && at) look(bars + B_VRAW + ((ntiles - 1) & 3) * 8, ((ntiles - 1) >> 2) & 1);
                    mbar_wait(bars + B_VRAW + ((ntiles - 1) & 3) * 8, ((ntiles - 1) >> 2) & 1);
                }
                TRH(9, (t - tile0) / tstep);
                mbar_wait_s<(HS & 4) != 0>(sbase + SM_PBAR + 48 + st * 8, ph);
                TRH(5, (t - tile0) / tstep);
                if (PEXP & 2) mbar_arrive(sbase + SM_PBAR + st * 8); else {
                mbar_arrive_expect_tx(sbase + SM_PBAR + st * 8, STAGE_BYTES);
#pragma unroll
                for (int ch = 0; ch < 3; ch++)
                    tma_2d(sbase + SM_STAGE + st * STAGE_BYTES + ch * 8192, &omap, sbase + SM_PBAR + st * 8, ch * 64, (PEXP & 4) ? p0 & 8191 : p0);
                }
                if (++st == 6) { st = 0; ph ^= 1; }
            }
            finish(nfinish);
        } else if (!attn) {
        } else if (warp == 1) {
          {
            if (PQ(t1) < TILES) {
#pragma unroll 1
                for (uint32_t n = 0; n < (1u << 22); n++) {
                    uint32_t a;
                    asm volatile("ld.acquire.gpu.global.u32 %0, [%1];\n" : "=r"(a) : "l"(g_cnt + NWS) : "memory");
                    if (a) break;
                    __nanosleep(64);
                }
                asm volatile("fence.proxy.async.global;\n" ::: "memory");
                if (blockIdx.x % 6 == 0)
                    asm volatile("cp.async.bulk.prefetch.L2.global [%0], 4096;\n" :: "l"(g_wo + blockIdx.x / 6 % 18 * 4096) : "memory");
                if (NB & 4) mbar_wait(bars + B_QKRAW, 0);
                else mbar_wait(bars + B_QKRAW + ((ntiles - 1) & 3) * 8, ((ntiles - 1) >> 2) & 1);
                mbar_arrive_expect_tx(bars + B_WRAW, 73728);
#pragma unroll
                for (int i = 0; i < 4; i++) {
                    const uint32_t o = ((i + pair) & 3) * 18432;
                    asm volatile("cp.async.bulk.shared::cluster.global.mbarrier::complete_tx::bytes [%0], [%1], 18432, [%2];\n"
                                 :: "r"(sbase + SM_WO + o), "l"(g_wo + o), "r"(bars + B_WRAW) : "memory");
                }
            }
            finish(nfinish);
          }
        } else if (warp == 2) {
            int wh = wr0, ww = wq0, nb = wr0 + 1, k = 0;
#pragma unroll 1
            for (int j = 0; k < nwin; j++) {
                mbar_wait_s<HS & 1>(bars + B_STORED + (j & 1) * 8, (j >> 1) & 1);
                mbar_arrive(bars + B_PUBD + (j & 1) * 8);
                if (SELFP && (wh == NWS - 1 || pair >= PQ(npair))) break;
                if (WFEN == 2) asm volatile("fence.proxy.async.global;\n" ::: "memory");
                if (PUBM != 1) asm volatile("fence.release.gpu;\n" ::: "memory");
#pragma unroll 1
                for (; wh < nb && k < nwin; k++) {
                    asm volatile("red.relaxed.gpu.global.add.u32 [%0], 1;\n" :: "l"(g_cnt + wh) : "memory");
                    ww += wstep; if (ww >= NWS) { ww -= NWS; wh++; }
                }
                nb = wh >= PBE ? wh + 1 : (wh | 1) + 1;
            }
            if (!SELFP) TC(7);
            finish(nfinish);
        } else {
            for (int t = 0; t < 2; t++) mbar_arrive_n(bars + B_VFREE + t * 8, M01 == 2 ? 2 - t : 2);
            int wr = wr0, wq = wq0, nb = wr0 + 1, j = 0, npf = 0, tprev = 0, klast = 0, wlast = wr0, pend = 0;
            int pr2 = (w0 + (PF_DIST + 5) * wstep) / NWS, pq2 = w0 + (PF_DIST + 5) * wstep - pr2 * NWS;
#pragma unroll 1
            for (int k = 0; k < nwin; k++) {
                const uint32_t src = sbase + SM_V + (k & 3) * V_STRIDE;
                const int wh = unrot(wr), ww = unrot(wq);
                const int x0 = 7 * ww + 3, y0 = 7 * wh + 3;
                if (NB & 2) nb_sync<160>(NB_ODONE + (k & 3));
                else mbar_wait_s<(HS & 2) != 0>(bars + B_ODONE + (k & 3) * 8, (k >> 2) & 1);
                if (SDEF) {
                    const int t1 = (TOK * (k + 2) - 1) >> 6, t2 = (TOK * (k + 3) - 1) >> 6;
                    int need = 0;
                    if (SDEF == 4) {
                        int tag, tq;
                        asm volatile("ld.volatile.shared.v2.b32 {%0, %1}, [%2];\n" : "=r"(tag), "=r"(tq) : "r"(bars + B_PROG + 8) : "memory");
                        const int now = clock32();
                        if (tag == k + 1 && now - tq > STH && now - tprev > STH + STP) need = k + 2;
                        tprev = now;
                    } else
                    if (SDEF == 3 || mbar_test(bars + B_QKRAW + (t1 & 3) * 8, (t1 >> 2) & 1)) need = k + 2;
                    if (SDEF == 2 && mbar_test(bars + B_QKRAW + (t2 & 3) * 8, (t2 >> 2) & 1)) need = k + 3;
                    need = min(need, nwin - 4);
#pragma unroll 1
                    for (int n = 0; n < (SDV == 2 ? 0 : 4096); n++) {
                        int done;
                        asm volatile("ld.volatile.shared.b32 %0, [%1];\n" : "=r"(done) : "r"(bars + B_PROG) : "memory");
                        if (done >= need) break;
                        __nanosleep(SDN);
                    }
                    if (SDV && need == k + 2) mbar_wait(bars + B_VRAW + (t1 & 3) * 8, (t1 >> 2) & 1);
                }
                fence_async_smem();
                TR(22, k);
                const int x1 = ww == NWS - 1 ? 0 : x0 + 4;
                if (!(XP & 2)) tma_store_4d(&M.s47, src, 0, half, x0, y0);
                if (!(XP & 2)) tma_store_4d(&M.s37, src + 28 * O_PITCH, 0, half, x1, y0);
                if (wh == NWS - 1) {
                    tma_store_4d(&M.s43, src + 16 * O_PITCH, 0, half, x0, 0);
                    tma_store_4d(&M.s33, src + 40 * O_PITCH, 0, half, x1, 0);
                }
                asm volatile("cp.async.bulk.commit_group;\n" ::: "memory");
                if (PFM >= 7) {
                    npf++;
                    const int t2 = (TOK * (k + 3) - 1) >> 6;
                    if (half == 0 && (PFM == 8 || npf > 2 || !mbar_test(bars + B_QKRAW + (t2 & 3) * 8, (t2 >> 2) & 1))) {
#pragma unroll 1
                        for (; npf > 0; npf--) {
                            if (pr2 < NWS && k + PF_DIST + 6 - npf < nwin)
                                asm volatile("cp.async.bulk.prefetch.tensor.3d.L2.global.tile [%0, {%1, %2, %3}];\n"
                                             :: "l"(reinterpret_cast<uint64_t>(&xmap)), "r"(0), "r"(7 * unrot(pq2) + 3), "r"(7 * unrot(pr2) + 3) : "memory");
                            pq2 += wstep; if (pq2 >= NWS) { pq2 -= NWS; pr2++; }
                        }
                    }
                }
                asm volatile("cp.async.bulk.wait_group.read 0;\n" ::: "memory");
                {
                    const int row0 = (k + 4) * TOK;
                    mbar_arrive_n(bars + B_VFREE + ((row0 >> 6) & 3) * 8, ((row0 & 63) >= 64 - TOK && (row0 & 63) < TOK) ? 2 : 1);
                }
                TR(23, k);
                if (k == nwin - 1) mbar_arrive(sbase + SM_PBAR + 96);
                if (LAZY && pend) {
                    pend = 0;
                    asm volatile("cp.async.bulk.wait_group 1;\n" ::: "memory");
                    if (WFEN == 1) asm volatile("fence.proxy.async.global;\n" ::: "memory");
                    mbar_wait(bars + B_PUBD + (j & 1) * 8, ((j >> 1) + 1) & 1);
                    mbar_arrive(bars + B_STORED + (j & 1) * 8);
                    j++;
                }
                wq += wstep; if (wq >= NWS) { wq -= NWS; wr++; }
                if (wr >= nb || k == nwin - 1) {
                    nb = wr >= PBE ? wr + 1 : (wr | 1) + 1;
                    if (LAZY && wr > 2 && wr < LAZY) { pend = 1; continue; }
                    asm volatile("cp.async.bulk.wait_group 0;\n" ::: "memory");
                    if (WFEN == 1) asm volatile("fence.proxy.async.global;\n" ::: "memory");
                    if (SELFP && k == nwin - 1) {
                        asm volatile("red.release.gpu.global.add.u32 [%0], %1;\n" :: "l"(g_cnt + wlast), "r"(nwin - klast) : "memory");
                        TC(7);
                    }
                    klast = k + 1;
                    wlast = wr;
                    mbar_wait(bars + B_PUBD + (j & 1) * 8, ((j >> 1) + 1) & 1);
                    mbar_arrive(bars + B_STORED + (j & 1) * 8);
                    j++;
                }
            }
        }
        if (CHK && warp == 2) {
            PROJ_SCHEDULE
            const int tl = tile0 + (tend - 1 - tile0) / tstep * tstep, wl = min((64 * (tl - TILES_A) + 63 + 4 * IMG) / (7 * IMG), NWS - 1);
#pragma unroll 1
            for (int r = 0; !at && r <= wl; r++) {
#pragma unroll 1
                for (uint32_t n = 0; n < (1u << 22); n++) {
                    uint32_t a;
                    asm volatile("ld.acquire.gpu.global.u32 %0, [%1];\n" : "=r"(a) : "l"(g_cnt + r) : "memory");
                    if (a >= PQ(need)) break;
                    __nanosleep(CHKS);
                }
#pragma unroll 1
                for (int i = 0; i < CHKB && r < wl; i++, r++) {
                    uint32_t a;
                    asm volatile("ld.acquire.gpu.global.u32 %0, [%1];\n" : "=r"(a) : "l"(g_cnt + r + 1) : "memory");
                    if (a < PQ(need)) break;
                }
                asm volatile("fence.proxy.async.global;\n" ::: "memory");
                asm volatile("st.release.cta.shared.b32 [%0], %1;\n" :: "r"(sbase + SM_FLAG + 124), "r"(r + 1) : "memory");
            }
        }
        if (PSTORE && warp == 1) {
            PROJ_SCHEDULE
            int st = 0, prev = -1;
            uint32_t ph = 0;
#pragma unroll 1
            for (int t = tile0; t < tend1; t += tstep) {
                const int p0 = (t < TILES_A) ? SEG_B + 64 * t : 64 * (t - TILES_A);
                mbar_wait_s<(HS & 4) != 0>(sbase + SM_PBAR + 104 + st * 8, ph);
                fence_async_smem();
#pragma unroll
                for (int ch = 0; ch < ((PEXP & 1) ? 0 : 3); ch++)
                    if (CH & 1)
                    asm volatile("cp.async.bulk.tensor.2d.global.shared::cta.tile.bulk_group.L2::cache_hint [%0, {%2, %3}], [%1], %4;\n"
                                 :: "l"(reinterpret_cast<uint64_t>(t < TILES_A ? &omap : &omapb)),
                                    "r"(sbase + SM_STAGE + st * STAGE_BYTES + ch * 8192), "r"(ch * 64), "r"(p0), "l"(EVICT_FIRST) : "memory");
                    else
                    asm volatile("cp.async.bulk.tensor.2d.global.shared::cta.tile.bulk_group [%0, {%2, %3}], [%1];\n"
                                 :: "l"(reinterpret_cast<uint64_t>(t < TILES_A ? &omap : &omapb)),
                                    "r"(sbase + SM_STAGE + st * STAGE_BYTES + ch * 8192), "r"(ch * 64), "r"((PEXP & 8) ? (p0 & 8191) + 16384 : p0) : "memory");
                asm volatile("cp.async.bulk.commit_group;\n" ::: "memory");
                TRH(6, (t - tile0) / tstep);
                if (prev >= 0) {
                    asm volatile("cp.async.bulk.wait_group.read 1;\n" ::: "memory");
                    mbar_arrive(sbase + SM_PBAR + 48 + prev * 8);
                    TRH(21, (t - tile0) / tstep - 1);
                }
                prev = st;
                if (++st == 6) { st = 0; ph ^= 1; }
            }
            if (ENDR) asm volatile("cp.async.bulk.wait_group.read 0;\n" ::: "memory");
            else asm volatile("cp.async.bulk.wait_group 0;\n" ::: "memory");
            TR(30, 0);
            if (!(COOP && at)) TC(1);
        }
        return;
    }
    auto permute = [&](int i0, int i1) {
            uint32_t src[3][4], dst[3];
#pragma unroll
            for (int it = 0; it < 3; it++) {
                const int o = warp * 12 + it * 4 + (lane >> 3), r = (o / 6) * 8 + (lane & 7), u = o % 6;
#pragma unroll
                for (int h = 0; h < (GORD == 2 ? 0 : 2); h++) {
                    const int v = u + 6 * h + 4 * half;
                    const bool wide = v >> 3 == half;
                    src[it][h] = wide ? r * 128 + (((v ^ r) & 7) << 4) : 16384 + r * 64 + (((v ^ (r >> 1)) & 3) << 4);
                    src[it][2 + h] = src[it][h] + (wide ? 8192 : 4096);
                }
                dst[it] = sbase + u * 4096 + r * 32 + ((lane >> 2) & 1) * 16;
            }
            TP(16);
#pragma unroll 1
            for (int i = i0; i < i1; i++) {
                uint4 w[3][4];
                mbar_wait(bars + B_WRAW + 16 - 8 * i, 0);
                TP(20 + i);
#pragma unroll
                for (int it = 0; it < 3; it++)
#pragma unroll
                    for (int m = 0; m < 4; m++) w[it][m] = *reinterpret_cast<const uint4*>(smem + src[it][m] + i * 24576);
                wg_bar(PPAR ? 12 + wg : 7);
#pragma unroll
                for (int it = 0; it < 3; it++) {
                    const uint32_t d = dst[it] + i * 24576;
                    sts128(d, w[it][0].x, w[it][1].x, w[it][2].x, w[it][3].x);
                    sts128(d ^ 16, w[it][0].y, w[it][1].y, w[it][2].y, w[it][3].y);
                    sts128(d + 2048, w[it][0].z, w[it][1].z, w[it][2].z, w[it][3].z);
                    sts128((d ^ 16) + 2048, w[it][0].w, w[it][1].w, w[it][2].w, w[it][3].w);
                }
            }
        };
    if (PPAR && attn) {
        permute(wg, wg + 1);
        if (wg) nb_arrive<384>(15);
    }
    if (!attn) {
        asm volatile("setmaxnreg.inc.sync.aligned.u32 160;\n");
    } else if (wg == 0) {
        if (!PPAR) permute(0, 3);
        asm volatile("setmaxnreg.inc.sync.aligned.u32 %0;\n" :: "n"(REG_G));
        float qs = 1.f;
        if (GORD == 2 || c < 2) qs = round_bf16(expf(round_bf16(fminf(fmaxf(bf16lo(ls), -100.f), 4.6052f)))) * LOG2E;
        uint32_t xa[12][4];
        float accA[48], accB[48], accV[48];
        uint32_t rho = warp * 16 + (lane & 15), rq = warp * 16 + g;
        uint32_t hi = lane >> 4, lane0 = lane == 0, c2 = 2 * c;
        asm volatile("" : "+r"(hi), "+r"(lane0), "+r"(c2));
        auto row_addr = [&](uint32_t (&ax)[4], uint32_t r) {
            ax[0] = sbase + SM_QK + r * 128 + (((r & 7) ^ hi) << 4);
#pragma unroll
            for (int i = 1; i < 4; i++) ax[i] = ax[0] ^ (32 * i);
        };
#define XADDR(ax, s) ((ax)[((s) & 3) ^ (((s) >> 1) & 2)] + ((s) >> 2) * QK_CHUNK)
        uint64_t descW = make_desc(sbase, 2048, 256, 3);
        const uint32_t zero = (uint32_t)P.z1;
        const uint32_t vbase = sbase + SM_V + (lane >> 4) * GRP;
        const uint32_t ones = 0x3F803F80u, ones2 = ones;
        TP(10);
        {
            uint32_t ax[4];
            row_addr(ax, rho);
            mbar_wait(bars + B_XFULL, 0);
#pragma unroll
            for (int s = 0; s < 12; s++) ldsm_x4(xa[s], XADDR(ax, s));
        }
        TP(8);
        if (PPAR) nb_sync<384>(15); else wg_bar(7);
        fence_async_smem();
        TP(9);
        wgmma_fence();
        mma_qkv_a<SM_WA, 0>(accA, xa, descW);
        mma_qkv_b<SM_WA, KLO>(accA, xa, descW);
        wgmma_commit();
        mma_qkv_a<SM_WB, 0>(accB, xa, descW);
        wgmma_commit();
        TP(11);
        mbar_wait(bars + B_WFULL, 0);
        TP(12);
        if (tid == 0) TC(3);
        const int nt = (int)blockIdx.x < 2 * PQ(npair) ? ((int)blockIdx.x < PQ(nr2) ? PQ(nt1) : PQ(nt0)) : ((int)blockIdx.x < PQ(hr2) ? PQ(ht1) : PQ(ht0));
        for (int t = 0; t < nt; t++) {
            descW += P.z1;
            float ss[4];
            uint32_t pk[2][24];
            wgmma_wait<1>();
            reg_fence(accA);
            TR(0, t);
            TA(1, 0);
            if (t < 12 && (t < 4 || (t & 1))) TP(t < 4 ? 32 + t : 34 + (t >> 1));
#pragma unroll
            for (int i = 0; i < 4; i++) ss[i] = accA[i] * accA[i];
#pragma unroll
            for (int i = 4; i < 48; i++) ss[i & 3] = fmaf(accA[i], accA[i], ss[i & 3]);
            mma_qkv_b<SM_WB, KLO>(accB, xa, descW);
            wgmma_commit();
            TA(1, 1);
            sched_fence(zero, __float_as_uint(ss[0]), __float_as_uint(ss[1]), __float_as_uint(ss[2]), __float_as_uint(ss[3]));
#pragma unroll
            for (int j = 0; j < 12; j++) {
                pk[0][j] = pack_bf16(accA[4 * j], accA[4 * j + 1]);
                pk[1][j] = pack_bf16(accA[4 * j + 2], accA[4 * j + 3]);
                asm volatile("" : "+r"(pk[0][j]), "+r"(pk[1][j]));
            }
            wgmma_fence();
            if (V64) mma_w_a<0, 0>(accV, xa, descW + D_WV64); else mma_v_a<D_WV, 0>(accV, xa, descW);
            wgmma_commit();
            TA(1, 2);
            uint32_t av = vbase + rho * 16 + ((rho * 1338) >> 16) * (V_STRIDE - GRP);
            uint32_t aq[2];
            aq[0] = sbase + SM_QK + rq * 128 + (((rq & 7) ^ c2) << 4);
            aq[1] = aq[0] + 1024;
            if (rq >= 4 * TOK - 8) aq[1] = (aq[1] - QK_CHUNK) ^ 64;
            rho += 64;
            if (rho >= 4 * TOK) rho -= 4 * TOK;
            rq += 64;
            if (rq >= 4 * TOK) rq -= 4 * TOK;
            uint32_t an[4];
            row_addr(an, rho);
            const uint32_t bt = bars + (t & 3) * 8, pt = (t >> 2) & 1, bn = bars + ((t + 1) & 3) * 8, pn = ((t + 1) >> 2) & 1;
            uint32_t xok;
            wgmma_wait<1>();
            reg_fence(accB);
            TA(1, 3);
#pragma unroll
            for (int i = 0; i < 48; i++) ss[i & 3] = fmaf(accB[i], accB[i], ss[i & 3]);
            ss[0] += ss[1]; ss[2] += ss[3];
            if (V64) mma_w_b<0, KLO>(accV, xa, descW + D_WV64); else mma_v_b<D_WV, KLO>(accV, xa, descW);
            wgmma_commit();
            TA(1, 4);
            sched_fence(zero, __float_as_uint(ss[0]), __float_as_uint(ss[2]), av, aq[0], aq[1], an[0], an[1], an[2], an[3], rho, rq);
            const float f0 = rsqrt_ftz(ss[0] + 1e-12f) * qs, f1 = rsqrt_ftz(ss[2] + 1e-12f) * qs;
            const uint32_t f2[2] = {pack_bf16(f0, f0), pack_bf16(f1, f1)};
#pragma unroll
            for (int j = 0; j < 12; j++) {
                pk[0][12 + j] = (FM & 1) ? pack_bf16(accB[4 * j] * f0, accB[4 * j + 1] * f0) : pack_bf16(accB[4 * j], accB[4 * j + 1]);
                pk[1][12 + j] = (FM & 1) ? pack_bf16(accB[4 * j + 2] * f1, accB[4 * j + 3] * f1) : pack_bf16(accB[4 * j + 2], accB[4 * j + 3]);
            }
            auto qk_store = [&](int u0, int u1) {
#pragma unroll
                for (int u = u0; u < u1; u++)
#pragma unroll
                    for (int r = 0; r < 2; r++)
                        if ((FM & 1) && u >= 3)
                        sts128((aq[r] ^ ((u & 1) * 16 + (u & 2) * 32)) + (u >> 1) * QK_CHUNK, pk[r][4 * u], pk[r][4 * u + 1], pk[r][4 * u + 2], pk[r][4 * u + 3]);
                        else
                        sts128((aq[r] ^ ((u & 1) * 16 + (u & 2) * 32)) + (u >> 1) * QK_CHUNK,
                               hmul2_bf16(pk[r][4 * u], f2[r]), hmul2_bf16(pk[r][4 * u + 1], f2[r]),
                               hmul2_bf16(pk[r][4 * u + 2], f2[r]), hmul2_bf16(pk[r][4 * u + 3], f2[r]));
            };
            qk_store(0, XPOS - 1);
            xok = mbar_test(bn + B_XFULL, pn);
            qk_store(XPOS - 1, QSPLIT);
            if (EARLYQ) {
                __syncwarp();
                mbar_arrive_if(bt + B_QKRAW, lane0);
            }
            TR(1, t);
            TA(1, 5);
            mbar_wait_unless(xok, bn + B_XFULL, pn);
            TR(2, t);
            wgmma_wait<1>();
            TA(1, 6);
#pragma unroll
            for (int s = 0; s < (LDE == 2 ? 12 : KLO); s++) ldsm_x4(xa[s], XADDR(an, s));
            qk_store(QSPLIT, 6 - QPOST);
            if (QPOST) {
                wgmma_fence();
                mma_qkv_a<SM_WA, 0>(accA, xa, descW);
                wgmma_commit();
                qk_store(6 - QPOST, 6);
            }
            if (!EARLYQ) {
                __syncwarp();
                mbar_arrive_if(bt + B_QKRAW, lane0);
            }
            TR(3, t);
            TA(1, 7);
            if (!QPOST) {
                wgmma_fence();
                mma_qkv_a<SM_WA, 0>(accA, xa, descW);
                wgmma_commit();
            }
            TA(1, 8);
            wgmma_wait<1>();
            reg_fence(accV);
            TA(1, 9);
#pragma unroll
            for (int s = KLO; s < 12; s++) ldsm_x4(xa[s], XADDR(an, s));
            const uint32_t vok = mbar_test(bt + B_VFREE, pt);
            uint32_t vp[24];
#pragma unroll
            for (int j = 0; j < 24; j++) vp[j] = pack_bf16(accV[2 * j], accV[2 * j + 1]);
            reg_fence(vp);
            wgmma_fence();
            mma_qkv_b<SM_WA, KLO>(accA, xa, descW);
            wgmma_commit();
            TA(1, 10);
            mbar_wait_unless(vok, bt + B_VFREE, pt);
#pragma unroll
            for (int p = 0; p < 6; p++)
                stsm_x4(av + (p < 3 ? 2 * p : 2 * p + 1) * GRP, vp[4 * p], vp[4 * p + 1], vp[4 * p + 2], vp[4 * p + 3]);
            stsm_x2(av + 6 * GRP, ones, ones2);
            __syncwarp();
            mbar_arrive_if(bt + B_VRAW, lane0);
            TR(4, t);
            if (MERGEW != 1) wgmma_fence();
            mma_qkv_a<SM_WB, 0>(accB, xa, descW);
            wgmma_commit();
            TA(1, 11);
        }
        TAEND(1);
        wgmma_wait<0>();
        reg_fence(accA);
        reg_fence(accB);
        asm volatile("setmaxnreg.dec.sync.aligned.u32 160;\n");
    } else {
        if (REG_A > 128) asm volatile("setmaxnreg.inc.sync.aligned.u32 %0;\n" :: "n"(REG_A));
        {
            const float c0 = bf16lo(rc), c1 = bf16hi(rc);
            float a0 = 0.f, a1 = 0.f;
#pragma unroll
            for (int u = 0; u < 16; u += 2) {
                const uint32_t p = reinterpret_cast<const uint32_t*>(w1)[u >> 1], q = reinterpret_cast<const uint32_t*>(w1)[8 + (u >> 1)];
                uint32_t h;
                asm("cvt.rn.relu.bf16x2.f32 %0, %1, %2;\n" : "=r"(h) : "f"(c0 * bf16hi(p) + c1 * bf16hi(q)), "f"(c0 * bf16lo(p) + c1 * bf16lo(q)));
                a0 += bf16lo(h) * bf16lo(w2[u]);
                a1 += bf16lo(h) * bf16hi(w2[u]);
                a0 += bf16hi(h) * bf16lo(w2[u + 1]);
                a1 += bf16hi(h) * bf16hi(w2[u + 1]);
            }
            const float s0 = round_bf16(__fdividef(1.f, 1.f + expf(-round_bf16(a0))));
            const float s1 = round_bf16(__fdividef(1.f, 1.f + expf(-round_bf16(a1))));
            if (tid - 128 < 169) sts32(sbase + SM_TAB + (tid - 128) * 4, pack_bf16(exp2f(fmaf(s0, 16.f * LOG2E, -12.f)), exp2f(fmaf(s1, 16.f * LOG2E, -12.f))));
        }
        asm volatile("bar.sync 1, 256;\n" ::: "memory");
        uint32_t eb[26];
        {
            const uint32_t* tab = reinterpret_cast<const uint32_t*>(smem + SM_TAB);
#pragma unroll
            for (int i = 0; i < 13; i++) {
                const uint32_t lo = tab[min(ridx[i < 12 ? 13 * (i & 1) + (i & ~1) : 12], 168u)];
                const uint32_t hi = tab[min(ridx[i < 12 ? 13 * (i & 1) + (i | 1) : 25], 168u)];
                eb[i]      = prmt(lo, hi, 0x5410);
                eb[13 + i] = prmt(lo, hi, 0x7632);
            }
            if (c != 0) eb[12] = eb[25] = 0;
            if (EBZ) {
                const uint32_t k0 = warp * 16 + g < TOK ? ~0u : 0u, k1 = warp < 3 ? ~0u : 0u;
#pragma unroll
                for (int i = 0; i < 26; i++) eb[i] &= i % 13 == 12 ? (k0 & 0xFFFFu) | (k1 & 0xFFFF0000u) : ((i % 13) & 1) ? k1 : k0;
            }
        }
        uint32_t slow = (bf16lo(ls) <= LS_FAST ? 0 : 1) | (bf16hi(ls) <= LS_FAST ? 0 : 2);
        reg_fence(eb);
        if (SLOWH == 2) sts32(bars + B_PROG + 4, slow);
        wg_bar(3 + wg);
        if ((tid & 127) == 0) mbar_arrive(bars + B_VFREE + 16);
        const uint32_t ov0 = warp * 16 + g < TOK, ov1 = warp < 3;
        const uint64_t descK0 = make_desc(sbase + SM_QK, 16, 1024, 1);
        const uint64_t descV0 = make_desc(sbase + SM_V, 128, GRP, 0);
        slow = __shfl_sync(0xffffffffu, slow, 0);
        const uint32_t barw = bars + (wg - 1) * 8;
        const uint64_t descKw = descK0 + (uint64_t)((wg - 1) * (XCH >> 4)), descVw = descV0 + (uint64_t)((wg - 1) * (V_STRIDE >> 4));
        const uint32_t oa = sbase + SM_V + (wg - 1) * V_STRIDE + (warp * 16 + g) * O_PITCH + c * 48;
        uint32_t qok = 0;
        const uint32_t zero = (uint32_t)P.z1;
        auto window = [&](auto IT_, int k) {
            constexpr int IT = decltype(IT_)::value;
            const uint32_t bar = barw + 16 * IT;
            const int tl = (k * TOK + TOK - 1) >> 6, tn = ((k + 2) * TOK + TOK - 1) >> 6;
            const uint32_t bt = bars + (tl & 3) * 8, pt = (tl >> 2) & 1;
            TR(8, k);
            if (k < 2) TP(44 + k);
            float sc0[28], sc1[28];
            TR(10, k);
            TA(2, 0);
            if (NB & 4) nb_sync<256>(NB_QKRAW + 2 * IT - 1 + wg);
            else mbar_wait_unless(qok, bt + B_QKRAW, pt);
            fence_async_smem();
            TR(11, k);
            TA(2, 1);
            if (k == 0) TP(17);
            wgmma_fence();
            mma_qk0<2 * IT * XCH, 2 * IT * XCH>(sc0, descKw, descKw);
            mma_qk1<2 * IT * XCH, 2 * IT * XCH>(sc1, descKw, descKw);
            wgmma_commit();
            TA(2, 2);
            uint32_t vok = PVL || VT ? 0 : mbar_test(bt + B_VRAW, pt);
            uint32_t mflag = 1;
            if (!(XP & 1)) asm volatile("ld.volatile.shared.u8 %0, [%1];\n" : "=r"(mflag) : "r"(sbase + SM_FLAG + k) : "memory");
            wgmma_wait<0>();
            reg_fence(sc0);
            reg_fence(sc1);
            if (NB & 1) nb_arrive<160>(NB_QKFREE - 1 + wg);
            else if (lane == 0) mbar_arrive(bar + B_QKFREE);
            TR(12, k);
            TA(2, 3);
            if (k == 0) TP(18);
            if (mflag != 1) {
              asm volatile(
                "{\n.reg .pred p;\n.reg .u32 n;\nmov.u32 n, 0;\n"
                "WAIT_%=:\n"
                "ld.volatile.shared.u8 %0, [%1];\n"
                "setp.ne.u32 p, %0, 0;\n"
                "@p bra DONE_%=;\n"
                "add.u32 n, n, 1;\n"
                "setp.lt.u32 p, n, 16777216;\n"
                "@p bra WAIT_%=;\n"
                "trap;\n"
                "DONE_%=:\n}\n" : "=r"(mflag) : "r"(sbase + SM_FLAG + k) : "memory");
              if (mflag == 2) {
                uint32_t mk[13];
                __threadfence_block();
                uint32_t u = threadIdx.x, bid = blockIdx.x;
                asm volatile("" : "+r"(u), "+r"(bid));
                const uint32_t r0 = ((u >> 1) & 48) + ((u >> 2) & 7);
                const int pr = bid >> 1, wi = pr < PQ(npair) ? PQ(hw) + pr + k * PQ(npair) : pr - PQ(npair) + k * PQ(nh), wr = wi / NWS;
                const uint32_t mp = sbase + SM_MASK + (((unrot(wr) * NWS + unrot(wi - wr * NWS)) * 2) & 15);
                const uint32_t mr[2] = {mp + row_token(min(r0, TOK - 1u)) * (2 * TOK), mp + row_token(min(r0 + 8, TOK - 1u)) * (2 * TOK)};
                const uint32_t c0 = 2 * row_token(2 * (u & 3));
#pragma unroll
                for (int i = 0; i < 13; i++) {
                    const uint32_t a0 = i < 6 ? mr[i & 1] + c0 + 28 * (i >> 1) : i < 12 ? mr[i & 1] + 2 * row_token(2 * (u & 3) + 8 * (i >> 1)) : mr[0] + 2 * TOK - 2;
                    const uint32_t a1 = i < 6 ? a0 + 2 : i < 12 ? mr[i & 1] + 2 * row_token(2 * (u & 3) + 8 * (i >> 1) + 1) : mr[1] + 2 * TOK - 2;
                    uint32_t lo, hi;
                    asm volatile("ld.shared.u16 %0, [%1];\n" : "=r"(lo) : "r"(a0) : "memory");
                    asm volatile("ld.shared.u16 %0, [%1];\n" : "=r"(hi) : "r"(a1) : "memory");
                    mk[i] = prmt(lo, hi, 0x5410);
                }
                reg_fence(mk);
                __syncwarp();
                if (lane == 0) mbar_arrive(bars + B_MCONS);
                uint32_t m0 = mk[0], m1 = mk[1];
#pragma unroll
                for (int i = 2; i < 12; i += 2) { m0 = hmax2_bf16(m0, mk[i]); m1 = hmax2_bf16(m1, mk[i + 1]); }
                m0 = hmax2_bf16(hmax2_bf16(prmt(m0, m1, 0x5410), prmt(m0, m1, 0x7632)), mk[12]);
                m0 = hmax2_bf16(m0, __shfl_xor_sync(0xffffffffu, m0, 1));
                m0 = hmax2_bf16(m0, __shfl_xor_sync(0xffffffffu, m0, 2));
                const float m[2] = {bf16lo(m0), bf16hi(m0)};
#pragma unroll
                for (int i = 0; i < 13; i++) {
                    const float lo = bf16lo(mk[i]) - m[i & 1], hi = bf16hi(mk[i]) - m[i < 12 ? i & 1 : 1];
                    const int j = i < 12 ? 2 * i + 1 : 26;
                    sc0[2 * i] = fmaf(lo, LOG2E, sc0[2 * i]); sc0[j] = fmaf(hi, LOG2E, sc0[j]);
                    sc1[2 * i] = fmaf(lo, LOG2E, sc1[2 * i]); sc1[j] = fmaf(hi, LOG2E, sc1[j]);
                }
              }
            }
            if (slow) {
                auto shift = [&](float (&S)[28], int h) {
                    float m[2];
#pragma unroll
                    for (int i = 12; i >= 0; i--) {
                        uint32_t e = eb[13 * h + i];
                        asm volatile("" : "+r"(e));
                        const float a = S[2 * i] + lg2_ftz(bf16lo(e)), b = S[i < 12 ? 2 * i + 1 : 26] + lg2_ftz(bf16hi(e));
                        if (i == 12) { m[0] = a; m[1] = b; }
                        else m[i & 1] = fmaxf(m[i & 1], fmaxf(a, b));
                    }
#pragma unroll
                    for (int r = 0; r < 2; r++) {
                        m[r] = fmaxf(m[r], __shfl_xor_sync(0xffffffffu, m[r], 1));
                        m[r] = fmaxf(m[r], __shfl_xor_sync(0xffffffffu, m[r], 2));
                    }
#pragma unroll
                    for (int i = 0; i < 27; i++) S[i] -= m[(i >> 1) & 1];
                };
                uint32_t sl = slow;
                if (SLOWH == 2) asm volatile("ld.volatile.shared.u32 %0, [%1];\n" : "=r"(sl) : "r"(bars + B_PROG + 4) : "memory");
                if (!SLOWH || (sl & 1)) shift(sc0, 0);
                if (!SLOWH || (sl & 2)) shift(sc1, 1);
            }
            auto exps = [&](const float (&S)[28], uint32_t (&e)[13]) {
#pragma unroll
                for (int i = 0; i < 12; i++) e[i] = pack_bf16(ex2_ftz(S[2 * i]), ex2_ftz(S[2 * i + 1]));
                e[12] = hmin2_bf16(pack_bf16(ex2_ftz(S[24]), ex2_ftz(S[26])), 0x7F7F7F7Fu);
            };
            auto probs = [&](const uint32_t (&e)[13], int h, uint32_t (&pa)[4][4]) {
#pragma unroll
                for (int i = 0; i < 12; i++) pa[i >> 2][i & 3] = hmul2_bf16(e[i], eb[13 * h + i]);
                const uint32_t l = hmul2_bf16(e[12], eb[13 * h + 12]);
                pa[3][0] = l & 0xFFFFu;
                pa[3][1] = l >> 16;
                pa[3][2] = 0u; pa[3][3] = 0u;
                reg_fence(pa);
            };
            uint32_t pa0[4][4], pa1[4][4], e[13];
            float o0[28], o1[28];
            TR(13, k);
            TA(2, 10);
            if (k == 0) TP(23);
            if (VT == 3) vok = mbar_test(bt + B_VRAW, pt);
            exps(sc0, e);
            if (VT == 1) { reg_fence(e); vok = mbar_test(bt + B_VRAW, pt); }
            probs(e, 0, pa0);
            TA(2, 4);
            mbar_wait_unless(vok, bt + B_VRAW, pt);
            fence_async_smem();
            TR(14, k);
            TA(2, 5);
            wgmma_fence();
            mma_pv<2 * IT * V_STRIDE, 0>(o0, pa0, descVw);
            wgmma_commit();
            exps(sc1, e);
            reg_fence(e);
            TA(2, 6);
            wgmma_wait<0>();
            reg_fence(o0);
            TA(2, 7);
            sched_fence_rw(zero, e);
            if (!PVL || PVL == 3) {
                probs(e, 1, pa1);
                wgmma_fence();
            }
            mma_pv<2 * IT * V_STRIDE + 6 * GRP, 0>(o1, pa1, descVw);
            wgmma_commit();
            uint32_t w[24];
            {
                const float il0 = rcp_ftz(o0[24]), il1 = rcp_ftz(o0[26]);
                const uint32_t l0 = pack_bf16(il0, il0), l1 = pack_bf16(il1, il1);
#pragma unroll
                for (int j = 0; j < 12; j++) w[j] = (FM & 2) ? pack_bf16(o0[2 * j] * ((j & 1) ? il1 : il0), o0[2 * j + 1] * ((j & 1) ? il1 : il0)) : hmul2_bf16(pack_bf16(o0[2 * j], o0[2 * j + 1]), (j & 1) ? l1 : l0);
            }
            TA(2, 8);
            wgmma_wait<0>();
            reg_fence(o1);
            TA(2, 9);
            TR(15, k);
            if (k == 0) TP(25);
            wg_bar(3 + wg);
            if (!(NB & 4) && !QT) qok = mbar_test(bars + (tn & 3) * 8 + B_QKRAW, (tn >> 2) & 1);
            {
                const float il2 = rcp_ftz(o1[0]), il3 = rcp_ftz(o1[2]);
                const uint32_t l2 = pack_bf16(il2, il2), l3 = pack_bf16(il3, il3);
#pragma unroll
                for (int j = 0; j < 12; j++) w[12 + j] = (FM & 4) ? pack_bf16(o1[2 * j + 4] * ((j & 1) ? il3 : il2), o1[2 * j + 5] * ((j & 1) ? il3 : il2)) : hmul2_bf16(pack_bf16(o1[2 * j + 4], o1[2 * j + 5]), (j & 1) ? l3 : l2);
#pragma unroll
                for (int p = 0; p < 6; p++) {
                    const int j = 8 * (p >> 1) + (p & 1);
                    sts128_if((p & 1) ? ov1 : ov0, oa + 2 * IT * V_STRIDE + (p & 1) * 8 * O_PITCH + (p >> 1) * 16, w[j], w[j + 2], w[j + 4], w[j + 6]);
                }
            }
            if (NB & 2) nb_arrive<160>(NB_ODONE + 2 * IT - 1 + wg);
            else {
                __syncwarp();
                if (lane == 0) mbar_arrive(bar + B_ODONE);
            }
            TR(16, k);
            TA(2, 11);
            if (k < 2) TP(46 + k);
        };
        for (int k = wg - 1;; k += 4) {
            window(std::integral_constant<int, 0>(), k);
            if (k + 2 >= nwin) break;
            window(std::integral_constant<int, 1>(), k + 2);
            if (k + 4 >= nwin) break;
        }
        TAEND(2);
        (void)zero;
        asm volatile("setmaxnreg.inc.sync.aligned.u32 160;\n");
    }

    TR(27, wg);
    if ((tid & 127) == 0) TC(4 + wg);
    if (attn) {
        __syncwarp();
        if (lane == 0) mbar_arrive(sbase + SM_PBAR + 96);
    }
    if (!attn) {
#pragma unroll
        for (int row = tid >> 2; row < 192; row += 96) {
            uint4 w[6];
            const int pr = row % 96, srow = row - pr + (pr % 24) / 12 * 48 + (pr % 12) / 2 * 8 + pr / 24 * 2 + (pr & 1);
#pragma unroll
            for (int a = 0; a < 6; a++) w[a] = *reinterpret_cast<const uint4*>(P.wo + srow * 192 + 32 * a + 8 * c);
            float s = 0.f;
#pragma unroll
            for (int a = 0; a < 6; a++)
                s += ((bf16lo(w[a].x) + bf16hi(w[a].x)) + (bf16lo(w[a].y) + bf16hi(w[a].y))) +
                     ((bf16lo(w[a].z) + bf16hi(w[a].z)) + (bf16lo(w[a].w) + bf16hi(w[a].w)));
            s += __shfl_xor_sync(0xffffffffu, s, 1);
            s += __shfl_xor_sync(0xffffffffu, s, 2);
            s *= (1.f / 192.f);
            const uint32_t d = sbase + SM_WO + row * 64 + ((c ^ ((row >> 1) & 3)) << 4);
#pragma unroll
            for (int a = 0; a < 6; a++)
                sts128(d + a * 12288, pack_bf16(bf16lo(w[a].x) - s, bf16hi(w[a].x) - s), pack_bf16(bf16lo(w[a].y) - s, bf16hi(w[a].y) - s),
                       pack_bf16(bf16lo(w[a].z) - s, bf16hi(w[a].z) - s), pack_bf16(bf16lo(w[a].w) - s, bf16hi(w[a].w) - s));
        }
        fence_async_smem();
        asm volatile("bar.sync 6, 384;\n" ::: "memory");
        if (tid == 0 && (int)blockIdx.x == 2 * (PQ(npair) + PQ(nh))) {
            asm volatile("cp.async.bulk.global.shared::cta.bulk_group [%0], [%1], 73728;\n" :: "l"(g_wo), "r"(sbase + SM_WO) : "memory");
            asm volatile("cp.async.bulk.commit_group;\n" ::: "memory");
            asm volatile("cp.async.bulk.wait_group 0;\n" ::: "memory");
            asm volatile("fence.proxy.async.global;\n" ::: "memory");
            asm volatile("red.release.gpu.global.add.u32 [%0], 1;\n" :: "l"(g_cnt + NWS) : "memory");
        }
        __syncwarp();
    } else if (PQ(t1) < TILES) {
        mbar_wait(sbase + SM_BAR + B_WRAW, 1);
    }
    TR(27, 4 + wg);
    if (tid == 0) TC(2);
    {
        PROJ_SCHEDULE
        uint64_t descW = make_desc(sbase + SM_WO, 12288, 512, 2);
        const uint64_t descA = make_desc(sbase + SM_STAGE + wg * STAGE_BYTES, 16, 1024, 1);
        const uint32_t bar = sbase + SM_PBAR + wg * 8;
        const uint32_t yrel = sbase + SM_STAGE + wg * STAGE_BYTES + (warp * 16 + (lane & 15)) * 128 + (((lane & 7) ^ (lane >> 4)) << 4);
        float acc[96];
#pragma unroll
        for (int i = 0; i < 96; i++) acc[i] = 0.f;
        uint32_t it = 0;
        for (int tile = tile0 + wg * tstep; tile < tend1; tile += 3 * tstep, it++) {
            descW += P.z1;
            mbar_wait_s<(HS & 8) != 0>(bar + (it & 1) * 24, (it >> 1) & 1);
            TR(28, it * 3 + wg);
            if (it > 0 || wg > 0) asm volatile("bar.sync %0, 256;\n" :: "r"(8 + wg) : "memory");
            wgmma_fence();
            mma_proj<0, 0>(acc, descA + (uint64_t)((it & 1) * (3 * STAGE_BYTES >> 4)), descW);
            wgmma_commit();
            if (tile + tstep < tend1) asm volatile("bar.arrive %0, 256;\n" :: "r"(wg == 2 ? 8 : 9 + wg) : "memory");
            wgmma_wait<0>();
            reg_fence(acc);
            float a[4];
#pragma unroll
            for (int i = 0; i < 4; i++) a[i] = acc[i] * acc[i];
#pragma unroll
            for (int j = 1; j < 24; j++)
#pragma unroll
                for (int i = 0; i < 4; i++) a[i] = fmaf(acc[4 * j + i], acc[4 * j + i], a[i]);
            float s0 = a[0] + a[1], s1 = a[2] + a[3];
            s0 += __shfl_xor_sync(0xffffffffu, s0, 1);
            s1 += __shfl_xor_sync(0xffffffffu, s1, 1);
            s0 += __shfl_xor_sync(0xffffffffu, s0, 2);
            s1 += __shfl_xor_sync(0xffffffffu, s1, 2);
            const float rs0 = rsqrt_ftz(fmaf(s0, 1.f / 192.f, 1e-5f));
            const float rs1 = rsqrt_ftz(fmaf(s1, 1.f / 192.f, 1e-5f));
            const uint32_t ya = yrel + (it & 1) * 3 * STAGE_BYTES;
#pragma unroll
            for (int p = 0; p < 12; p++)
                stsm_x4((ya ^ (32 * (p & 3))) + (p >> 2) * 8192,
                        pack_bf16(acc[8 * p] * rs0, acc[8 * p + 1] * rs0), pack_bf16(acc[8 * p + 2] * rs1, acc[8 * p + 3] * rs1),
                        pack_bf16(acc[8 * p + 4] * rs0, acc[8 * p + 5] * rs0), pack_bf16(acc[8 * p + 6] * rs1, acc[8 * p + 7] * rs1));
            __syncwarp();
            if (lane == 0) mbar_arrive(bar + 104 + (it & 1) * 24);
            TR(29, it * 3 + wg);
        }
#pragma unroll 1
        for (int j = nl + 1 - COOP; COOP && at && j <= nl; j++) {
            float d[32];
            const uint32_t stage = sbase + SM_STAGE + j * STAGE_BYTES;
            mbar_wait(sbase + SM_PBAR + j * 8, 0);
            wgmma_fence();
            mma_proj64<0, 0>(d, make_desc(stage, 16, 1024, 1), descW + (uint64_t)(wg * (2 * 12288 >> 4)));
            wgmma_commit();
            wgmma_wait<0>();
            reg_fence(d);
            float a[4];
#pragma unroll
            for (int i = 0; i < 4; i++) a[i] = d[i] * d[i];
#pragma unroll
            for (int j = 1; j < 8; j++)
#pragma unroll
                for (int i = 0; i < 4; i++) a[i] = fmaf(d[4 * j + i], d[4 * j + i], a[i]);
            const uint32_t sa = sbase + SM_MASK - (j & 1) * 3072 + (warp * 16 + g) * 48;
            sts32(sa + wg * 16 + c * 4, __float_as_uint(a[0] + a[1]));
            sts32(sa + wg * 16 + c * 4 + 8 * 48, __float_as_uint(a[2] + a[3]));
            nb_sync<384>(15);
            float rs[2];
#pragma unroll
            for (int r = 0; r < 2; r++) {
                float v[12];
#pragma unroll
                for (int i = 0; i < 3; i++)
                    asm volatile("ld.shared.v4.f32 {%0, %1, %2, %3}, [%4];\n" : "=f"(v[4 * i]), "=f"(v[4 * i + 1]), "=f"(v[4 * i + 2]), "=f"(v[4 * i + 3])
                                 : "r"(sa + r * 8 * 48 + i * 16) : "memory");
                const float s = ((v[0] + v[1]) + (v[2] + v[3])) + ((v[4] + v[5]) + (v[6] + v[7])) + ((v[8] + v[9]) + (v[10] + v[11]));
                rs[r] = rsqrt_ftz(fmaf(s, 1.f / 192.f, 1e-5f));
            }
            const uint32_t ya = stage + wg * 8192 + (warp * 16 + (lane & 15)) * 128 + (((lane & 7) ^ (lane >> 4)) << 4);
#pragma unroll
            for (int p = 0; p < 4; p++)
                stsm_x4(ya ^ (32 * p),
                        pack_bf16(d[8 * p] * rs[0], d[8 * p + 1] * rs[0]), pack_bf16(d[8 * p + 2] * rs[1], d[8 * p + 3] * rs[1]),
                        pack_bf16(d[8 * p + 4] * rs[0], d[8 * p + 5] * rs[0]), pack_bf16(d[8 * p + 6] * rs[1], d[8 * p + 7] * rs[1]));
            fence_async_smem();
            wg_bar(12 + wg);
            if (warp == 0 && elect_one()) {
                asm volatile("cp.async.bulk.tensor.2d.global.shared::cta.tile.bulk_group.L2::cache_hint [%0, {%2, %3}], [%1], %4;\n"
                             :: "l"(reinterpret_cast<uint64_t>(&omapb)), "r"(stage + wg * 8192), "r"(wg * 64), "r"(64 * (tile0 + j * tstep - TILES_A)),
                                "l"(EVICT_FIRST) : "memory");
                asm volatile("cp.async.bulk.commit_group;\n" ::: "memory");
                if (j == nl) {
                    if (ENDR) asm volatile("cp.async.bulk.wait_group.read 0;\n" ::: "memory");
                    else asm volatile("cp.async.bulk.wait_group 0;\n" ::: "memory");
                }
                if (wg == 0) TC(1);
            }
        }
    }
}

}

typedef CUresult (*PFN_encodeTiled)(CUtensorMap*, CUtensorMapDataType, cuuint32_t, void*, const cuuint64_t*,
                                    const cuuint64_t*, const cuuint32_t*, const cuuint32_t*, CUtensorMapInterleave,
                                    CUtensorMapSwizzle, CUtensorMapL2promotion, CUtensorMapFloatOOBfill);

extern "C" void kernel_launch(void* const* d_in, const int* in_sizes, int n_in, void* d_out, int out_size) {
    swin::Params P;
    P.x           = (const __nv_bfloat16*)d_in[0];
    P.wqkv        = (const __nv_bfloat16*)d_in[1];
    P.wo          = (const __nv_bfloat16*)d_in[2];
    P.logit_scale = (const __nv_bfloat16*)d_in[3];
    P.cpb_w1      = (const __nv_bfloat16*)d_in[4];
    P.cpb_w2      = (const __nv_bfloat16*)d_in[5];
    P.rel_coords  = (const __nv_bfloat16*)d_in[6];
    P.rel_idx     = (const int*)d_in[7];
    P.mask        = (const __nv_bfloat16*)d_in[8];
    P.out         = (__nv_bfloat16*)d_out;
    P.z1 = 0;
    static PFN_encodeTiled encode = nullptr;
    if (!encode) {
        cudaFuncSetAttribute(swin::swin_window_attn_kernel, cudaFuncAttributeMaxDynamicSharedMemorySize, swin::SM_TOTAL);
        cudaDriverEntryPointQueryResult qr;
        cudaGetDriverEntryPoint("cuTensorMapEncodeTiled", (void**)&encode, cudaEnableDefault, &qr);
    }
    swin::Maps M;
    const cuuint32_t estr[4] = {1, 1, 1, 1};
    auto make = [&](CUtensorMap* m, const void* base, int rank, const cuuint64_t* gdim, const cuuint64_t* gstr,
                    const cuuint32_t* box, CUtensorMapSwizzle swz = CU_TENSOR_MAP_SWIZZLE_128B) {
        CUresult r = encode(m, CU_TENSOR_MAP_DATA_TYPE_BFLOAT16, rank, const_cast<void*>(base), gdim, gstr, box, estr,
               CU_TENSOR_MAP_INTERLEAVE_NONE, swz, CU_TENSOR_MAP_L2_PROMOTION_L2_128B,
               CU_TENSOR_MAP_FLOAT_OOB_FILL_NONE);
        (void)r;
    };
    {
        const cuuint64_t gdim[3] = {192, swin::IMG, swin::IMG}, gstr[2] = {384, swin::IMG * 384};
        const cuuint32_t box[7][3] = {{64, 7, 7}, {64, 4, 7}, {64, 3, 7}, {64, 4, 4}, {64, 4, 3}, {64, 3, 4}, {64, 3, 3}};
        for (int i = 0; i < 7; i++) make(&M.x77 + i, P.x, 3, gdim, gstr, box[i]);
        const cuuint32_t boxp[3] = {192, 7, 7};
        if (PF1) make(&M.x77, P.x, 3, gdim, gstr, boxp, CU_TENSOR_MAP_SWIZZLE_NONE);
    }
    {
        const cuuint64_t gdim[2] = {192, (cuuint64_t)swin::NPIX}, gstr[1] = {384};
        const cuuint32_t box64[2] = {64, 64};
        make(&M.o, d_out, 2, gdim, gstr, box64);
        const cuuint64_t gdimb[2] = {192, (cuuint64_t)swin::SEG_B};
        make(&M.ob, d_out, 2, gdimb, gstr, box64);
    }
    {
        const cuuint64_t gdim[3] = {V64 ? 32 : 16, 192, V64 ? 18 : 36}, gstr[2] = {1152, V64 ? 64 : 32};
        const cuuint32_t box[3] = {V64 ? 32 : 16, 192, V64 ? 3 : 6};
        make(&M.w, P.wqkv, 3, gdim, gstr, box, V64 ? CU_TENSOR_MAP_SWIZZLE_64B : CU_TENSOR_MAP_SWIZZLE_32B);
        const cuuint64_t gdim3[3] = {192, 192, 3}, gstr3[2] = {1152, 384};
        const cuuint32_t box64[3] = {64, 64, 2}, box32[3] = {32, 64, 2};
        make(&M.w64, P.wqkv, 3, gdim3, gstr3, box64);
        make(&M.w32, P.wqkv, 3, gdim3, gstr3, box32, CU_TENSOR_MAP_SWIZZLE_64B);
    }
    {
        const cuuint64_t gdim[4] = {96, 2, swin::IMG, swin::IMG}, gstr[3] = {192, 384, swin::IMG * 384};
        const cuuint32_t box[4][4] = {{96, 1, 4, 7}, {96, 1, 3, 7}, {96, 1, 4, 3}, {96, 1, 3, 3}};
        for (int i = 0; i < 4; i++) make(&M.s47 + i, d_out, 4, gdim, gstr, box[i], CU_TENSOR_MAP_SWIZZLE_NONE);
    }
    swin::swin_window_attn_kernel<<<132, swin::NTHREADS, swin::SM_TOTAL>>>(P, M);
}
```
